```python
import torch

def _softmax(x, axis=-1):
    return torch.softmax(x, dim=axis)

def _gelu(x):
    return torch.nn.functional.gelu(x, approximate='tanh')

def _silu(x):
    return torch.nn.functional.silu(x)

def _sigmoid(x):
    return torch.sigmoid(x)

def _layernorm(x, axis=-1, eps=1e-05):
    m = x.mean(dim=axis, keepdim=True)
    v = x.var(dim=axis, keepdim=True, unbiased=False)
    return (x - m) / torch.sqrt(v + eps)

def _scatter_add(tgt, idx, src, axis=0):
    return tgt.clone().index_add_(axis, idx, src)

def _segment_sum(src, seg, n):
    out = torch.zeros((n,) + src.shape[1:], dtype=src.dtype)
    return out.index_add_(0, seg, src)

def _pad(x, pw):
    flat = tuple((v for pair in reversed(pw) for v in pair))
    return torch.nn.functional.pad(x, flat)
kernel_name = 'adaLN_cond__ssm_conv_h3__mixer_s_mlp__prompt'

def setup_inputs():

    _w = lambda a: (lambda t: t.to(torch.bfloat16) if t.is_floating_point() else t)(torch.as_tensor(a))

    def _A_setup():
        B, S, D = (1, 2048, 640)
        ks = 4
        return {'q': _w((lambda *s: torch.randn(*s, dtype=torch.bfloat16) * 0.05)(B, S, D)), 'k': _w((lambda *s: torch.randn(*s, dtype=torch.bfloat16) * 0.8)(B, S, D)), 'v': _w((lambda *s: torch.randn(*s, dtype=torch.bfloat16) * 0.8)(B, S, D)), 'shift_k': _w((lambda *s: torch.randn(*s, dtype=torch.bfloat16) * 0.8)(D, ks) * 0.5), 'ssm_k': _w((lambda *s: torch.randn(*s, dtype=torch.bfloat16) * 0.8)(D, S) * (1.0 / S ** 0.5)), 'ssm_D': _w((lambda *s: torch.randn(*s, dtype=torch.bfloat16) * 0.8)(D))}
    _A_in = _A_setup()

    def _B_setup():
        B, S, D, F = (1, 2048, 640, 1728)
        return {'x': _w((lambda *s: torch.randn(*s, dtype=torch.bfloat16) * 0.05)(B, S, D)), 'w1': _w((lambda *s: torch.randn(*s, dtype=torch.bfloat16) * 3.2)(D, D) * D ** (-0.5)), 'w2': _w((lambda *s: torch.randn(*s, dtype=torch.bfloat16) * 3.2)(D, D) * D ** (-0.5)), 'w3': _w((lambda *s: torch.randn(*s, dtype=torch.bfloat16) * 3.2)(D, F) * D ** (-0.5)), 'w4': _w((lambda *s: torch.randn(*s, dtype=torch.bfloat16) * 3.2)(F, D) * F ** (-0.5))}
    _B_in = _B_setup()
    return {'A_q': _A_in['q'], 'A_k': _A_in['k'], 'A_v': _A_in['v'], 'A_shift_k': _A_in['shift_k'], 'A_ssm_k': _A_in['ssm_k'], 'A_ssm_D': _A_in['ssm_D'], 'B_x': _B_in['x'], 'B_w1': _B_in['w1'], 'B_w2': _B_in['w2'], 'B_w3': _B_in['w3'], 'B_w4': _B_in['w4'], 'c': _w((lambda *s: torch.randn(*s, dtype=torch.bfloat16) * 0.1)(1, 640) * 8.0), 'w_mod': _w((lambda *s: torch.randn(*s, dtype=torch.bfloat16) * 0.1)(640, 6 * 640) * 640 ** (-0.5) * 8.0)}

def reference(A_q, A_k, A_v, A_shift_k, A_ssm_k, A_ssm_D, B_x, B_w1, B_w2, B_w3, B_w4, c, w_mod):

    def _A_ref(q, k, v, shift_k, ssm_k, ssm_D):
        B, S, D = q.shape
        ks = shift_k.shape[-1]
        k_pad = _pad(k, ((0, 0), (ks - 1, 0), (0, 0)))
        k_shift = torch.zeros_like(k)
        for t in range(ks):
            k_shift = k_shift + k_pad[:, t:t + S, :] * shift_k[:, ks - 1 - t][None, None, :]
        kv = k_shift * v
        L = 2 * S
        kv_pad = _pad(kv, ((0, 0), (0, S), (0, 0)))
        kf_pad = _pad(ssm_k, ((0, 0), (0, S)))
        kv_f = (lambda x, axes=(-2, -1): torch.fft.rfft2(x.float(), dim=axes))(kv_pad[:, None, :, :], axes=(1, 2))
        kf_f = (lambda x, axes=(-2, -1): torch.fft.rfft2(x.float(), dim=axes))(kf_pad[:, None, :], axes=(1, 2))
        kf_f = (lambda x, *d: x.permute(*d))(kf_f, 1, 2, 0)
        y_f = kv_f * kf_f[None, :, :, :]
        y = (lambda x, s, axes=(-2, -1): torch.fft.irfft2(x, s=s, dim=axes).to(torch.bfloat16))(y_f, (1, L), axes=(1, 2))[:, 0, :S, :]
        y = y + kv * ssm_D[None, None, :]
        return q * y

    def _B_ref(x, w1, w2, w3, w4):
        B, S, D = x.shape
        h = _gelu(_layernorm(x, axis=-1) @ w1)
        c = D // 4
        g0 = _pad(h[:, :, 0 * c:1 * c], ((0, 0), (1, 0), (0, 0)))[:, :S, :]
        g1 = _pad(h[:, :, 1 * c:2 * c], ((0, 0), (0, 1), (0, 0)))[:, 1:, :]
        g2 = _pad(h[:, :, 2 * c:3 * c], ((0, 0), (2, 0), (0, 0)))[:, :S, :]
        g3 = _pad(h[:, :, 3 * c:], ((0, 0), (0, 2), (0, 0)))[:, 2:, :]
        hs = torch.concatenate([g0, g1, g2, g3], axis=-1) @ w2
        x1 = x + hs
        h2 = _gelu(_layernorm(x1, axis=-1) @ w3) @ w4
        return x1 + h2
    x = A_q
    mod = (_silu(c) @ w_mod).reshape(c.shape[0], 6, 1, -1)
    sa, ca, ga, sb, cb, gb = (mod[:, 0].clone(), mod[:, 1].clone(), mod[:, 2].clone(), mod[:, 3].clone(), mod[:, 4].clone(), mod[:, 5].clone())
    h = _layernorm(x, axis=-1) * (1 + ca) + sa
    x = x + ga * _A_ref(h, A_k, A_v, A_shift_k, A_ssm_k, A_ssm_D)
    h = _layernorm(x, axis=-1) * (1 + cb) + sb
    x = x + gb * _B_ref(h, B_w1, B_w2, B_w3, B_w4)
    return x
```

```cpp
#include <cuda_runtime.h>
#include <cuda_bf16.h>
#include <cuda.h>
#include <stdint.h>
#include <stdio.h>

typedef __nv_bfloat16 bf16;

constexpr int S_ = 2048, D_ = 640, F_ = 1728;
constexpr int NCTA = 132, NTHR = 512;

constexpr int TAB_BYTES = 9216, VEC_BYTES = 1440;
struct Counters {
    unsigned kv[8 * 32];
    unsigned q[4 * 32], x[2 * 4 * 32];
    unsigned wr[32], tab[32], uv[32], cs[32], done[32];
    unsigned g1[32 * 32];
    unsigned g2[32 * 32];
};
struct Scratch {
    Counters cnt;
    unsigned epoch;
    alignas(1024) bf16 qst[2 * S_];
    alignas(1024) uint4 wr[2 * 8 * 10 * 128];
    alignas(1024) uint2 mod[2 * 6 * D_];
    alignas(1024) uint4 tab[(TAB_BYTES + 8 * VEC_BYTES) / 16];
    alignas(1024) float uv[2 * 3 * D_];
    alignas(1024) float cs3[2 * 1920];
    alignas(1024) float2 stats[32 * 8 * 64];
    alignas(1024) bf16 kvT[D_ * S_];
    alignas(1024) bf16 qT[D_ * S_];
    alignas(1024) bf16 x1T[D_ * S_];
    alignas(1024) bf16 t[(S_ + 4) * D_];
    alignas(1024) uint4 x2f[32 * 40 * 128];
    alignas(1024) uint4 x1f[32 * 8 * 5 * 128];
    alignas(1024) uint4 part[32 * 8 * 10 * 4 * 128];
};
__device__ Scratch g_scratch;
#define g_kvT (pp.s->kvT)
#define g_qT (pp.s->qT)
#define g_x1T (pp.s->x1T)
#define g_qst (pp.s->qst)
#define g_t (pp.s->t)
#define g_x2f (pp.s->x2f)
#define g_x1f (pp.s->x1f)
#define g_part (pp.s->part)
#define g_wr (pp.s->wr)
#define g_mod (pp.s->mod)
#define g_tab (pp.s->tab)
#define g_uv (pp.s->uv)
#define g_cs3 (pp.s->cs3)
#define g_stats (pp.s->stats)
#define g_cnt (pp.s->cnt)
#define g_epoch (pp.s->epoch)

struct Maps {
    CUtensorMap k, v, q;
    CUtensorMap qT;
    CUtensorMap x1_ld, t_ld;
    CUtensorMap w1, w1h, w3h, wmod;
    CUtensorMap w2a, w2b;
    CUtensorMap w3a, w3b;
    CUtensorMap w4[2];
};

struct Ptrs {
    Scratch* s;
    uint64_t nil;
    const bf16 *q, *w_mod, *shift_k, *ssm_k, *ssm_D, *w1, *w2, *w4, *c;
};

constexpr int OFF_W = 0;
constexpr int OFF_XR = 131072;
constexpr int OFF_REM = 196608;
constexpr int OFF_TAB = OFF_REM + 5 * 4096;
constexpr int OFF_ROW = OFF_TAB + 4608;
constexpr int OFF_F1 = OFF_ROW + 4096;
constexpr int RECV_BYTES = 30720;
constexpr int OFF_M = OFF_REM + RECV_BYTES;
constexpr int OFF_OUT = OFF_XR + 32768;
static_assert(OFF_F1 + 1280 <= OFF_M, "G1 map");
constexpr int OFF_ST = 0;
constexpr int OFF_SSM = 20480;
constexpr int OFF_WM = 0;
constexpr int OFF_QIN = 49152;
constexpr int OFF_QT = 49152;
constexpr int OFF_Z = OFF_TAB;
constexpr int OFF_RING = 80896;
constexpr int OFF_KIN = OFF_RING, OFF_VIN = OFF_KIN + 2 * 10752;
constexpr int OFF_CH = OFF_RING + 3 * 16384, CH_BYTES = 13312, OFF_P = 5120;
static_assert(OFF_RING + 5 * 16384 <= OFF_CH + 3 * CH_BYTES && OFF_CH + 5 * CH_BYTES <= OFF_REM, "the last two rings replace channels 0..2");
constexpr int M_BAR = OFF_M;
constexpr int M_F1 = OFF_M + 720;
constexpr int M_GB = M_F1 + 1280, M_C = M_GB + 320, M_SB = M_C + 320, M_CI = M_SB + 320;
constexpr int M_KS = M_CI + 320;
constexpr int M_AB = M_KS + 160;
constexpr int M_EP = M_AB + 80;
constexpr int M_NUL = M_EP + 16;
constexpr int M_TS = M_NUL + 16;
constexpr int SMEM_BYTES = M_TS;
static_assert(SMEM_BYTES <= 232448, "smem");

enum { B_WFULL = 0, B_WEMPTY = 8, B_XEMPTY = 16, B_XFULL = 24  ,
       B_RAW = 40, B_IN = 41, B_QIN = 43, B_SSM = 44, B_VEC = 45, B_VEC3 = 46, B_WM = 47, B_TAB = 48,
       B_QRDY = 49, B_MODR = 50, B_PUB = 51, B_RETRY = 57, B_S30 = 60,
       B_SIG = 61, B_OWN = 63, B_COEF = 65, B_RES = 67, B_RING = 69  ,
       B_XS = 74, B_BK = 76,
       B_KVS = 77,
       B_XFREE = 78,
       B_SUMS = 79, B_RECV = 81  , B_NUM = 89 };
#define T_KVB 1800
#define T_SSM 4700
#define PF_T0 3500
#define PF_DT 420
#define PF_N 16
#define POLL_NS 0
#define HELP_T 1000
#define EPI_SPLIT 1
#define GATE3
#define GATE10
#define GATE16 16
#define ST3 1
#define LD3 23
#define XLEAD 3

#define SPIN_FAIL(code) __trap();
#define SPIN_LIMIT (1u << 22)
#define STALE(c)
#define TS(c, i)
#define TG(c, i)
#define TR(c, i)
#define TR2(c, i)
#define CKV
#define CK(i)
#define CKD(c, o)
__device__ __forceinline__ uint32_t s2u(const void* p) { return (uint32_t)__cvta_generic_to_shared(p); }
__device__ __forceinline__ bool elect() {
    uint32_t p;
    asm volatile("{.reg .pred P; elect.sync _|P, 0xffffffff; selp.u32 %0,1,0,P;}" : "=r"(p));
    return p != 0;
}
__device__ __forceinline__ void mbar_init(uint32_t b, uint32_t n) { asm volatile("mbarrier.init.shared.b64 [%0], %1;" ::"r"(b), "r"(n)); }
__device__ __forceinline__ void mbar_expect(uint32_t b, uint32_t bytes) {
    asm volatile("mbarrier.arrive.expect_tx.shared.b64 _, [%0], %1;" ::"r"(b), "r"(bytes) : "memory");
}
__device__ __forceinline__ void mbar_arrive(uint32_t b) { asm volatile("mbarrier.arrive.shared.b64 _, [%0];" ::"r"(b) : "memory"); }
__device__ __forceinline__ void mbar_arrive_after(uint32_t b, uint32_t v0, uint32_t v1, uint32_t nil) { mbar_arrive(b + ((v0 | v1) & nil)); }
__device__ __forceinline__ void warp_arrive(uint32_t b) { __syncwarp(); if (elect()) mbar_arrive(b); }
__device__ __forceinline__ uint32_t peer_addr(uint32_t a) {
    uint32_t r;
    asm("{\n.reg .b32 q;\nmov.u32 q, %%cluster_ctarank;\nxor.b32 q, q, 1;\nmapa.shared::cluster.u32 %0, %1, q;\n}" : "=r"(r) : "r"(a));
    return r;
}
__device__ __forceinline__ bool mbar_test(uint32_t b, uint32_t parity) {
    uint32_t ok;
    asm volatile("{.reg .pred P; mbarrier.test_wait.parity.shared.b64 P, [%1], %2; selp.u32 %0,1,0,P;}" : "=r"(ok) : "r"(b), "r"(parity) : "memory");
    return ok != 0;
}
__device__ __forceinline__ bool mbar_try(uint32_t b, uint32_t parity) {
    uint32_t ok;
    asm volatile("{.reg .pred P; mbarrier.try_wait.parity.shared.b64 P, [%1], %2; selp.u32 %0,1,0,P;}" : "=r"(ok) : "r"(b), "r"(parity) : "memory");
    return ok != 0;
}
__device__ __forceinline__ void mbar_wait(uint32_t b, uint32_t parity) {
    if (__all_sync(0xffffffffu, mbar_try(b, parity))) return;
    uint32_t it = 0;
    while (!__all_sync(0xffffffffu, mbar_try(b, parity))) { if (++it > SPIN_LIMIT) SPIN_FAIL((b >> 3) & 63) }
}
__device__ __forceinline__ void mbar_spin(uint32_t b, uint32_t parity) {
    asm volatile("{\n.reg .pred P;\nSPIN:\nmbarrier.try_wait.parity.shared.b64 P, [%0], %1;\n@!P bra.uni SPIN;\n}" ::"r"(b), "r"(parity) : "memory");
}
__device__ __forceinline__ void bar_sync(int id, int n) { asm volatile("bar.sync %0, %1;" ::"r"(id), "r"(n) : "memory"); }
__device__ __forceinline__ void fence_async_smem() { asm volatile("fence.proxy.async.shared::cta;" ::: "memory"); }
__device__ __forceinline__ void wait_cnt(const unsigned* p, unsigned target, int ns = 0) {
    unsigned v, it = 0;
    do {
        if (ns) __nanosleep(ns);
        asm volatile("ld.relaxed.gpu.global.u32 %0, [%1];" : "=r"(v) : "l"(p) : "memory");
        if (++it > SPIN_LIMIT) SPIN_FAIL(60 + (target & 3))
    } while (!__all_sync(0xffffffffu, v >= target));
    asm volatile("fence.acquire.gpu;" ::: "memory");
}
#define X_NOFENCE 0
__device__ __forceinline__ void signal_cnt(unsigned* p, int lane, int n, bool nofence = false) {
    if (nofence) { if (lane < n) asm volatile("red.relaxed.gpu.global.add.u32 [%0], 1;" ::"l"(p) : "memory"); }
    else if (lane < n) asm volatile("red.release.gpu.global.add.u32 [%0], 1;" ::"l"(p) : "memory");
    __syncwarp();
}
__device__ __forceinline__ void wait_clock(long long c0, int t) {
    while (clock64() - c0 < t) __nanosleep(20);
    __syncwarp();
}
__device__ __forceinline__ void tma_ld2(uint32_t dst, const CUtensorMap* m, int c0, int c1, uint32_t bar) {
    asm volatile("cp.async.bulk.tensor.2d.shared::cluster.global.mbarrier::complete_tx::bytes [%0], [%1, {%3, %4}], [%2];"
                 ::"r"(dst), "l"(m), "r"(bar), "r"(c0), "r"(c1) : "memory");
}
__device__ __forceinline__ void tma_ld3(uint32_t dst, const CUtensorMap* m, int c0, int c1, int c2, uint32_t bar) {
    asm volatile("cp.async.bulk.tensor.3d.shared::cluster.global.mbarrier::complete_tx::bytes [%0], [%1, {%3, %4, %5}], [%2];"
                 ::"r"(dst), "l"(m), "r"(bar), "r"(c0), "r"(c1), "r"(c2) : "memory");
}
__device__ __forceinline__ void tma_ld5(uint32_t dst, const CUtensorMap* m, int col, int blk, uint32_t bar) {
    asm volatile("cp.async.bulk.tensor.5d.shared::cluster.global.mbarrier::complete_tx::bytes [%0], [%1, {%3, %4, %4, %4, %5}], [%2];"
                 ::"r"(dst), "l"(m), "r"(bar), "r"(col), "r"(0), "r"(blk) : "memory");
}
__device__ __forceinline__ void bulk_ld(uint32_t dst, const void* src, uint32_t bytes, uint32_t bar) {
    asm volatile("cp.async.bulk.shared::cluster.global.mbarrier::complete_tx::bytes [%0], [%1], %2, [%3];" ::"r"(dst), "l"(src), "r"(bytes), "r"(bar) : "memory");
}
__device__ __forceinline__ void l2_prefetch(const void* p, uint32_t bytes) {
    asm volatile("cp.async.bulk.prefetch.L2.global [%0], %1;" ::"l"(p), "r"(bytes) : "memory");
}
__device__ __forceinline__ void wg_fence() { asm volatile("wgmma.fence.sync.aligned;" ::: "memory"); }
__device__ __forceinline__ void wg_commit() { asm volatile("wgmma.commit_group.sync.aligned;" ::: "memory"); }
template <int N> __device__ __forceinline__ void wg_wait() { asm volatile("wgmma.wait_group.sync.aligned %0;" ::"n"(N) : "memory"); }
template <int N> __device__ __forceinline__ void reg_fence(float (&d)[N]) {
#pragma unroll
    for (int i = 0; i < N; i++) asm volatile("" : "+f"(d[i])::"memory");
}
template <int N> __device__ __forceinline__ void zero(float (&d)[N]) {
#pragma unroll
    for (int i = 0; i < N; i++) asm volatile("mov.b32 %0, 0;" : "=f"(d[i]));
}
__device__ __forceinline__ uint32_t lds32(uint32_t a) { uint32_t v; asm volatile("ld.shared.b32 %0, [%1];" : "=r"(v) : "r"(a)); return v; }
__device__ __forceinline__ uint2 lds64(uint32_t a) { uint2 v; asm volatile("ld.shared.v2.b32 {%0,%1}, [%2];" : "=r"(v.x), "=r"(v.y) : "r"(a)); return v; }
__device__ __forceinline__ float2 lds64f(uint32_t a) { float2 v; asm volatile("ld.shared.v2.f32 {%0,%1}, [%2];" : "=f"(v.x), "=f"(v.y) : "r"(a)); return v; }
__device__ __forceinline__ void sts32(uint32_t a, uint32_t v) { asm volatile("st.shared.b32 [%0], %1;" ::"r"(a), "r"(v) : "memory"); }
__device__ __forceinline__ void sts64f(uint32_t a, float x, float y) { asm volatile("st.shared.v2.f32 [%0], {%1,%2};" ::"r"(a), "f"(x), "f"(y) : "memory"); }
__device__ __forceinline__ void sts128(uint32_t a, uint32_t x, uint32_t y, uint32_t z, uint32_t w) {
    asm volatile("st.shared.v4.b32 [%0], {%1,%2,%3,%4};" ::"r"(a), "r"(x), "r"(y), "r"(z), "r"(w) : "memory");
}
__device__ __forceinline__ void sts128f(uint32_t a, float x, float y, float z, float w) {
    asm volatile("st.shared.v4.f32 [%0], {%1,%2,%3,%4};" ::"r"(a), "f"(x), "f"(y), "f"(z), "f"(w) : "memory");
}
__device__ __forceinline__ uint4 lds128(uint32_t a) {
    uint4 v;
    asm volatile("ld.shared.v4.b32 {%0,%1,%2,%3}, [%4];" : "=r"(v.x), "=r"(v.y), "=r"(v.z), "=r"(v.w) : "r"(a) : "memory");
    return v;
}
__device__ __forceinline__ float4 lds128f(uint32_t a) {
    float4 v;
    asm volatile("ld.shared.v4.f32 {%0,%1,%2,%3}, [%4];" : "=f"(v.x), "=f"(v.y), "=f"(v.z), "=f"(v.w) : "r"(a) : "memory");
    return v;
}
__device__ __forceinline__ void stg128(void* p, uint32_t x, uint32_t y, uint32_t z, uint32_t w) {
    asm volatile("st.global.v4.b32 [%0], {%1,%2,%3,%4};" ::"l"(p), "r"(x), "r"(y), "r"(z), "r"(w) : "memory");
}
__device__ __forceinline__ void stg128(void* p, uint4 v) { stg128(p, v.x, v.y, v.z, v.w); }
__device__ __forceinline__ void stg128_if(void* p, uint4 v, int on) {
    asm volatile("{\n.reg .pred p;\nsetp.ne.s32 p, %5, 0;\n@p st.global.v4.b32 [%0], {%1,%2,%3,%4};\n}" ::"l"(p), "r"(v.x), "r"(v.y), "r"(v.z), "r"(v.w), "r"(on) : "memory");
}
__device__ __forceinline__ void stg64(void* p, uint32_t x, uint32_t y) { asm volatile("st.global.v2.b32 [%0], {%1,%2};" ::"l"(p), "r"(x), "r"(y) : "memory"); }
__device__ __forceinline__ void stsm4(uint32_t a, uint32_t r0, uint32_t r1, uint32_t r2, uint32_t r3) {
    asm volatile("stmatrix.sync.aligned.m8n8.x4.shared.b16 [%0], {%1,%2,%3,%4};" ::"r"(a), "r"(r0), "r"(r1), "r"(r2), "r"(r3) : "memory");
}
__device__ __forceinline__ void stsm4t(uint32_t a, uint32_t r0, uint32_t r1, uint32_t r2, uint32_t r3) {
    asm volatile("stmatrix.sync.aligned.m8n8.x4.trans.shared.b16 [%0], {%1,%2,%3,%4};" ::"r"(a), "r"(r0), "r"(r1), "r"(r2), "r"(r3) : "memory");
}
__device__ __forceinline__ void ldsm4t(uint32_t a, uint32_t& r0, uint32_t& r1, uint32_t& r2, uint32_t& r3) {
    asm volatile("ldmatrix.sync.aligned.m8n8.x4.trans.shared.b16 {%0,%1,%2,%3}, [%4];" : "=r"(r0), "=r"(r1), "=r"(r2), "=r"(r3) : "r"(a) : "memory");
}
__device__ __forceinline__ uint32_t pack2(float lo, float hi) {
    uint32_t r;
    asm("cvt.rn.bf16x2.f32 %0, %1, %2;" : "=r"(r) : "f"(hi), "f"(lo));
    return r;
}
__device__ __forceinline__ uint32_t mul2(uint32_t a, uint32_t b) { uint32_t r; asm("mul.rn.bf16x2 %0, %1, %2;" : "=r"(r) : "r"(a), "r"(b)); return r; }
__device__ __forceinline__ uint32_t fma2(uint32_t a, uint32_t b, uint32_t c) { uint32_t r; asm("fma.rn.bf16x2 %0, %1, %2, %3;" : "=r"(r) : "r"(a), "r"(b), "r"(c)); return r; }
__device__ __forceinline__ uint32_t add2(uint32_t a, uint32_t b) { uint32_t r; asm("add.rn.bf16x2 %0, %1, %2;" : "=r"(r) : "r"(a), "r"(b)); return r; }
__device__ __forceinline__ void hmma(float (&d)[4], uint32_t a0, uint32_t a1, uint32_t a2, uint32_t a3, uint32_t b0, uint32_t b1) {
    asm volatile("mma.sync.aligned.m16n8k16.row.col.f32.bf16.bf16.f32 {%0,%1,%2,%3}, {%4,%5,%6,%7}, {%8,%9}, {%0,%1,%2,%3};"
        : "+f"(d[0]), "+f"(d[1]), "+f"(d[2]), "+f"(d[3]) : "r"(a0), "r"(a1), "r"(a2), "r"(a3), "r"(b0), "r"(b1));
}
__device__ __forceinline__ float blo(uint32_t w) { return __uint_as_float(w << 16); }
__device__ __forceinline__ float bhi(uint32_t w) { return __uint_as_float(w & 0xffff0000u); }
__device__ __forceinline__ float rbf(float x) { return __bfloat162float(__float2bfloat16_rn(x)); }
__device__ __forceinline__ uint32_t ldg32(const void* p) { uint32_t v; asm volatile("ld.global.nc.b32 %0, [%1];" : "=r"(v) : "l"(p)); return v; }
__device__ __forceinline__ uint2 ldg64(const void* p) { uint2 v; asm volatile("ld.global.nc.v2.b32 {%0,%1}, [%2];" : "=r"(v.x), "=r"(v.y) : "l"(p)); return v; }
__device__ __forceinline__ uint4 ldg128(const void* p) {
    uint4 v;
    asm volatile("ld.global.nc.v4.b32 {%0,%1,%2,%3}, [%4];" : "=r"(v.x), "=r"(v.y), "=r"(v.z), "=r"(v.w) : "l"(p));
    return v;
}
__device__ __forceinline__ uint4 ldcg128(const void* p) {
    uint4 v;
    asm volatile("ld.global.cg.v4.u32 {%0,%1,%2,%3}, [%4];" : "=r"(v.x), "=r"(v.y), "=r"(v.z), "=r"(v.w) : "l"(p) : "memory");
    return v;
}
__device__ __forceinline__ float4 ldcg128f(const void* p) {
    float4 v;
    asm volatile("ld.global.cg.v4.f32 {%0,%1,%2,%3}, [%4];" : "=f"(v.x), "=f"(v.y), "=f"(v.z), "=f"(v.w) : "l"(p) : "memory");
    return v;
}
__device__ __forceinline__ float2 ldcg64f(const void* p) { float2 v; asm volatile("ld.global.cg.v2.f32 {%0,%1}, [%2];" : "=f"(v.x), "=f"(v.y) : "l"(p) : "memory"); return v; }
__device__ __forceinline__ float ldcg32f(const void* p) { float v; asm volatile("ld.global.cg.f32 %0, [%1];" : "=f"(v) : "l"(p) : "memory"); return v; }
__device__ __forceinline__ uint2 ld_mod(const uint2* p) {
    uint64_t v;
    asm volatile("ld.relaxed.gpu.global.b64 %0, [%1];" : "=l"(v) : "l"(p) : "memory");
    return make_uint2((uint32_t)v, (uint32_t)(v >> 32));
}
__device__ __forceinline__ float gelu2(float h) {
    float u = h * fmaf(h * h, 8.f * 0.0356774081f, 2.f * 0.7978845608f);
    float th;
    asm("tanh.approx.f32 %0, %1;" : "=f"(th) : "f"(u));
    return fmaf(h, th, h);
}

__device__ __forceinline__ void conv_channel(float (&d)[64], uint32_t pa, uint64_t db) {
    asm volatile("{\n.reg .b32 a0, a1, a2, a3, b0, b1, b2, b3, t0, t1;\n.reg .b64 d;\nld.shared.b32 a0, [%64];\nld.shared.b32 a1, [%64+128];\nld.shared.b32 a2, [%64+-128];\nmov.b32 a3, a0;\n"
        "ld.shared.b32 t0, [%64+256];\nld.shared.b32 t1, [%64+384];\nadd.s64 d, %65, 0;\nwgmma.fence.sync.aligned;\nwgmma.mma_async.sync.aligned.m64n128k16.f32.bf16.bf16 {%0, %1, %2, %3, %4, %5, %6, %7, %8, %9, %10, %11, %12, %13, %14, %15, %16, %17, %18, %19, %20, %21, %22, %23, %24, %25, %26, %27, %28, %29, %30, %31, %32, %33, %34, %35, %36, %37, %38, %39, %40, %41, %42, %43, %44, %45, %46, %47, %48, %49, %50, %51, %52, %53, %54, %55, %56, %57, %58, %59, %60, %61, %62, %63}, {a0, a1, a2, a3}, d, 0, 1, 1, 0;\nwgmma.commit_group.sync.aligned;\nwgmma.wait_group.sync.aligned 1;\nmov.b32 b2, a1;\nmov.b32 b0, t0;\nmov.b32 b3, t0;\nmov.b32 b1, t1;\n"
        "ld.shared.b32 t0, [%64+512];\nld.shared.b32 t1, [%64+640];\nadd.s64 d, %65, 8;\nwgmma.fence.sync.aligned;\nwgmma.mma_async.sync.aligned.m64n128k16.f32.bf16.bf16 {%0, %1, %2, %3, %4, %5, %6, %7, %8, %9, %10, %11, %12, %13, %14, %15, %16, %17, %18, %19, %20, %21, %22, %23, %24, %25, %26, %27, %28, %29, %30, %31, %32, %33, %34, %35, %36, %37, %38, %39, %40, %41, %42, %43, %44, %45, %46, %47, %48, %49, %50, %51, %52, %53, %54, %55, %56, %57, %58, %59, %60, %61, %62, %63}, {b0, b1, b2, b3}, d, 1, 1, 1, 0;\nwgmma.commit_group.sync.aligned;\nwgmma.wait_group.sync.aligned 1;\nmov.b32 a2, b1;\nmov.b32 a0, t0;\nmov.b32 a3, t0;\nmov.b32 a1, t1;\n"
        "ld.shared.b32 t0, [%64+768];\nld.shared.b32 t1, [%64+896];\nadd.s64 d, %65, 16;\nwgmma.fence.sync.aligned;\nwgmma.mma_async.sync.aligned.m64n128k16.f32.bf16.bf16 {%0, %1, %2, %3, %4, %5, %6, %7, %8, %9, %10, %11, %12, %13, %14, %15, %16, %17, %18, %19, %20, %21, %22, %23, %24, %25, %26, %27, %28, %29, %30, %31, %32, %33, %34, %35, %36, %37, %38, %39, %40, %41, %42, %43, %44, %45, %46, %47, %48, %49, %50, %51, %52, %53, %54, %55, %56, %57, %58, %59, %60, %61, %62, %63}, {a0, a1, a2, a3}, d, 1, 1, 1, 0;\nwgmma.commit_group.sync.aligned;\nwgmma.wait_group.sync.aligned 1;\nmov.b32 b2, a1;\nmov.b32 b0, t0;\nmov.b32 b3, t0;\nmov.b32 b1, t1;\n"
        "ld.shared.b32 t0, [%64+1024];\nld.shared.b32 t1, [%64+1152];\nadd.s64 d, %65, 24;\nwgmma.fence.sync.aligned;\nwgmma.mma_async.sync.aligned.m64n128k16.f32.bf16.bf16 {%0, %1, %2, %3, %4, %5, %6, %7, %8, %9, %10, %11, %12, %13, %14, %15, %16, %17, %18, %19, %20, %21, %22, %23, %24, %25, %26, %27, %28, %29, %30, %31, %32, %33, %34, %35, %36, %37, %38, %39, %40, %41, %42, %43, %44, %45, %46, %47, %48, %49, %50, %51, %52, %53, %54, %55, %56, %57, %58, %59, %60, %61, %62, %63}, {b0, b1, b2, b3}, d, 1, 1, 1, 0;\nwgmma.commit_group.sync.aligned;\nwgmma.wait_group.sync.aligned 1;\nmov.b32 a2, b1;\nmov.b32 a0, t0;\nmov.b32 a3, t0;\nmov.b32 a1, t1;\n"
        "ld.shared.b32 t0, [%64+1280];\nld.shared.b32 t1, [%64+1408];\nadd.s64 d, %65, 32;\nwgmma.fence.sync.aligned;\nwgmma.mma_async.sync.aligned.m64n128k16.f32.bf16.bf16 {%0, %1, %2, %3, %4, %5, %6, %7, %8, %9, %10, %11, %12, %13, %14, %15, %16, %17, %18, %19, %20, %21, %22, %23, %24, %25, %26, %27, %28, %29, %30, %31, %32, %33, %34, %35, %36, %37, %38, %39, %40, %41, %42, %43, %44, %45, %46, %47, %48, %49, %50, %51, %52, %53, %54, %55, %56, %57, %58, %59, %60, %61, %62, %63}, {a0, a1, a2, a3}, d, 1, 1, 1, 0;\nwgmma.commit_group.sync.aligned;\nwgmma.wait_group.sync.aligned 1;\nmov.b32 b2, a1;\nmov.b32 b0, t0;\nmov.b32 b3, t0;\nmov.b32 b1, t1;\n"
        "ld.shared.b32 t0, [%64+1536];\nld.shared.b32 t1, [%64+1664];\nadd.s64 d, %65, 40;\nwgmma.fence.sync.aligned;\nwgmma.mma_async.sync.aligned.m64n128k16.f32.bf16.bf16 {%0, %1, %2, %3, %4, %5, %6, %7, %8, %9, %10, %11, %12, %13, %14, %15, %16, %17, %18, %19, %20, %21, %22, %23, %24, %25, %26, %27, %28, %29, %30, %31, %32, %33, %34, %35, %36, %37, %38, %39, %40, %41, %42, %43, %44, %45, %46, %47, %48, %49, %50, %51, %52, %53, %54, %55, %56, %57, %58, %59, %60, %61, %62, %63}, {b0, b1, b2, b3}, d, 1, 1, 1, 0;\nwgmma.commit_group.sync.aligned;\nwgmma.wait_group.sync.aligned 1;\nmov.b32 a2, b1;\nmov.b32 a0, t0;\nmov.b32 a3, t0;\nmov.b32 a1, t1;\n"
        "ld.shared.b32 t0, [%64+1792];\nld.shared.b32 t1, [%64+1920];\nadd.s64 d, %65, 48;\nwgmma.fence.sync.aligned;\nwgmma.mma_async.sync.aligned.m64n128k16.f32.bf16.bf16 {%0, %1, %2, %3, %4, %5, %6, %7, %8, %9, %10, %11, %12, %13, %14, %15, %16, %17, %18, %19, %20, %21, %22, %23, %24, %25, %26, %27, %28, %29, %30, %31, %32, %33, %34, %35, %36, %37, %38, %39, %40, %41, %42, %43, %44, %45, %46, %47, %48, %49, %50, %51, %52, %53, %54, %55, %56, %57, %58, %59, %60, %61, %62, %63}, {a0, a1, a2, a3}, d, 1, 1, 1, 0;\nwgmma.commit_group.sync.aligned;\nwgmma.wait_group.sync.aligned 1;\nmov.b32 b2, a1;\nmov.b32 b0, t0;\nmov.b32 b3, t0;\nmov.b32 b1, t1;\n"
        "ld.shared.b32 t0, [%64+2048];\nld.shared.b32 t1, [%64+2176];\nadd.s64 d, %65, 56;\nwgmma.fence.sync.aligned;\nwgmma.mma_async.sync.aligned.m64n128k16.f32.bf16.bf16 {%0, %1, %2, %3, %4, %5, %6, %7, %8, %9, %10, %11, %12, %13, %14, %15, %16, %17, %18, %19, %20, %21, %22, %23, %24, %25, %26, %27, %28, %29, %30, %31, %32, %33, %34, %35, %36, %37, %38, %39, %40, %41, %42, %43, %44, %45, %46, %47, %48, %49, %50, %51, %52, %53, %54, %55, %56, %57, %58, %59, %60, %61, %62, %63}, {b0, b1, b2, b3}, d, 1, 1, 1, 0;\nwgmma.commit_group.sync.aligned;\nwgmma.wait_group.sync.aligned 1;\nmov.b32 a2, b1;\nmov.b32 a0, t0;\nmov.b32 a3, t0;\nmov.b32 a1, t1;\n"
        "ld.shared.b32 t0, [%64+2304];\nld.shared.b32 t1, [%64+2432];\nadd.s64 d, %65, 64;\nwgmma.fence.sync.aligned;\nwgmma.mma_async.sync.aligned.m64n96k16.f32.bf16.bf16 {%0, %1, %2, %3, %4, %5, %6, %7, %8, %9, %10, %11, %12, %13, %14, %15, %16, %17, %18, %19, %20, %21, %22, %23, %24, %25, %26, %27, %28, %29, %30, %31, %32, %33, %34, %35, %36, %37, %38, %39, %40, %41, %42, %43, %44, %45, %46, %47}, {a0, a1, a2, a3}, d, 1, 1, 1, 0;\nwgmma.commit_group.sync.aligned;\nwgmma.wait_group.sync.aligned 1;\nmov.b32 b2, a1;\nmov.b32 b0, t0;\nmov.b32 b3, t0;\nmov.b32 b1, t1;\n"
        "ld.shared.b32 t0, [%64+2560];\nld.shared.b32 t1, [%64+2688];\nadd.s64 d, %65, 72;\nwgmma.fence.sync.aligned;\nwgmma.mma_async.sync.aligned.m64n96k16.f32.bf16.bf16 {%0, %1, %2, %3, %4, %5, %6, %7, %8, %9, %10, %11, %12, %13, %14, %15, %16, %17, %18, %19, %20, %21, %22, %23, %24, %25, %26, %27, %28, %29, %30, %31, %32, %33, %34, %35, %36, %37, %38, %39, %40, %41, %42, %43, %44, %45, %46, %47}, {b0, b1, b2, b3}, d, 1, 1, 1, 0;\nwgmma.commit_group.sync.aligned;\nwgmma.wait_group.sync.aligned 1;\nmov.b32 a2, b1;\nmov.b32 a0, t0;\nmov.b32 a3, t0;\nmov.b32 a1, t1;\n"
        "ld.shared.b32 t0, [%64+2816];\nld.shared.b32 t1, [%64+2944];\nadd.s64 d, %65, 80;\nwgmma.fence.sync.aligned;\nwgmma.mma_async.sync.aligned.m64n88k16.f32.bf16.bf16 {%0, %1, %2, %3, %4, %5, %6, %7, %8, %9, %10, %11, %12, %13, %14, %15, %16, %17, %18, %19, %20, %21, %22, %23, %24, %25, %26, %27, %28, %29, %30, %31, %32, %33, %34, %35, %36, %37, %38, %39, %40, %41, %42, %43}, {a0, a1, a2, a3}, d, 1, 1, 1, 0;\nwgmma.commit_group.sync.aligned;\nwgmma.wait_group.sync.aligned 1;\nmov.b32 b2, a1;\nmov.b32 b0, t0;\nmov.b32 b3, t0;\nmov.b32 b1, t1;\n"
        "ld.shared.b32 t0, [%64+3072];\nld.shared.b32 t1, [%64+3200];\nadd.s64 d, %65, 88;\nwgmma.fence.sync.aligned;\nwgmma.mma_async.sync.aligned.m64n88k16.f32.bf16.bf16 {%0, %1, %2, %3, %4, %5, %6, %7, %8, %9, %10, %11, %12, %13, %14, %15, %16, %17, %18, %19, %20, %21, %22, %23, %24, %25, %26, %27, %28, %29, %30, %31, %32, %33, %34, %35, %36, %37, %38, %39, %40, %41, %42, %43}, {b0, b1, b2, b3}, d, 1, 1, 1, 0;\nwgmma.commit_group.sync.aligned;\nwgmma.wait_group.sync.aligned 1;\nmov.b32 a2, b1;\nmov.b32 a0, t0;\nmov.b32 a3, t0;\nmov.b32 a1, t1;\n"
        "ld.shared.b32 t0, [%64+3328];\nld.shared.b32 t1, [%64+3456];\nadd.s64 d, %65, 96;\nwgmma.fence.sync.aligned;\nwgmma.mma_async.sync.aligned.m64n80k16.f32.bf16.bf16 {%0, %1, %2, %3, %4, %5, %6, %7, %8, %9, %10, %11, %12, %13, %14, %15, %16, %17, %18, %19, %20, %21, %22, %23, %24, %25, %26, %27, %28, %29, %30, %31, %32, %33, %34, %35, %36, %37, %38, %39}, {a0, a1, a2, a3}, d, 1, 1, 1, 0;\nwgmma.commit_group.sync.aligned;\nwgmma.wait_group.sync.aligned 1;\nmov.b32 b2, a1;\nmov.b32 b0, t0;\nmov.b32 b3, t0;\nmov.b32 b1, t1;\n"
        "ld.shared.b32 t0, [%64+3584];\nld.shared.b32 t1, [%64+3712];\nadd.s64 d, %65, 104;\nwgmma.fence.sync.aligned;\nwgmma.mma_async.sync.aligned.m64n80k16.f32.bf16.bf16 {%0, %1, %2, %3, %4, %5, %6, %7, %8, %9, %10, %11, %12, %13, %14, %15, %16, %17, %18, %19, %20, %21, %22, %23, %24, %25, %26, %27, %28, %29, %30, %31, %32, %33, %34, %35, %36, %37, %38, %39}, {b0, b1, b2, b3}, d, 1, 1, 1, 0;\nwgmma.commit_group.sync.aligned;\nwgmma.wait_group.sync.aligned 1;\nmov.b32 a2, b1;\nmov.b32 a0, t0;\nmov.b32 a3, t0;\nmov.b32 a1, t1;\n"
        "ld.shared.b32 t0, [%64+3840];\nld.shared.b32 t1, [%64+3968];\nadd.s64 d, %65, 112;\nwgmma.fence.sync.aligned;\nwgmma.mma_async.sync.aligned.m64n72k16.f32.bf16.bf16 {%0, %1, %2, %3, %4, %5, %6, %7, %8, %9, %10, %11, %12, %13, %14, %15, %16, %17, %18, %19, %20, %21, %22, %23, %24, %25, %26, %27, %28, %29, %30, %31, %32, %33, %34, %35}, {a0, a1, a2, a3}, d, 1, 1, 1, 0;\nwgmma.commit_group.sync.aligned;\nwgmma.wait_group.sync.aligned 1;\nmov.b32 b2, a1;\nmov.b32 b0, t0;\nmov.b32 b3, t0;\nmov.b32 b1, t1;\n"
        "ld.shared.b32 t0, [%64+4096];\nld.shared.b32 t1, [%64+4224];\nadd.s64 d, %65, 120;\nwgmma.fence.sync.aligned;\nwgmma.mma_async.sync.aligned.m64n72k16.f32.bf16.bf16 {%0, %1, %2, %3, %4, %5, %6, %7, %8, %9, %10, %11, %12, %13, %14, %15, %16, %17, %18, %19, %20, %21, %22, %23, %24, %25, %26, %27, %28, %29, %30, %31, %32, %33, %34, %35}, {b0, b1, b2, b3}, d, 1, 1, 1, 0;\nwgmma.commit_group.sync.aligned;\nwgmma.wait_group.sync.aligned 1;\nmov.b32 a2, b1;\nmov.b32 a0, t0;\nmov.b32 a3, t0;\nmov.b32 a1, t1;\n"
        "ld.shared.b32 t0, [%64+4352];\nld.shared.b32 t1, [%64+4480];\nadd.s64 d, %65, 128;\nwgmma.fence.sync.aligned;\nwgmma.mma_async.sync.aligned.m64n64k16.f32.bf16.bf16 {%0, %1, %2, %3, %4, %5, %6, %7, %8, %9, %10, %11, %12, %13, %14, %15, %16, %17, %18, %19, %20, %21, %22, %23, %24, %25, %26, %27, %28, %29, %30, %31}, {a0, a1, a2, a3}, d, 1, 1, 1, 0;\nwgmma.commit_group.sync.aligned;\nwgmma.wait_group.sync.aligned 1;\nmov.b32 b2, a1;\nmov.b32 b0, t0;\nmov.b32 b3, t0;\nmov.b32 b1, t1;\n"
        "ld.shared.b32 t0, [%64+4608];\nld.shared.b32 t1, [%64+4736];\nadd.s64 d, %65, 136;\nwgmma.fence.sync.aligned;\nwgmma.mma_async.sync.aligned.m64n64k16.f32.bf16.bf16 {%0, %1, %2, %3, %4, %5, %6, %7, %8, %9, %10, %11, %12, %13, %14, %15, %16, %17, %18, %19, %20, %21, %22, %23, %24, %25, %26, %27, %28, %29, %30, %31}, {b0, b1, b2, b3}, d, 1, 1, 1, 0;\nwgmma.commit_group.sync.aligned;\nwgmma.wait_group.sync.aligned 1;\nmov.b32 a2, b1;\nmov.b32 a0, t0;\nmov.b32 a3, t0;\nmov.b32 a1, t1;\n"
        "ld.shared.b32 t0, [%64+4864];\nld.shared.b32 t1, [%64+4992];\nadd.s64 d, %65, 144;\nwgmma.fence.sync.aligned;\nwgmma.mma_async.sync.aligned.m64n56k16.f32.bf16.bf16 {%0, %1, %2, %3, %4, %5, %6, %7, %8, %9, %10, %11, %12, %13, %14, %15, %16, %17, %18, %19, %20, %21, %22, %23, %24, %25, %26, %27}, {a0, a1, a2, a3}, d, 1, 1, 1, 0;\nwgmma.commit_group.sync.aligned;\nwgmma.wait_group.sync.aligned 1;\nmov.b32 b2, a1;\nmov.b32 b0, t0;\nmov.b32 b3, t0;\nmov.b32 b1, t1;\n"
        "ld.shared.b32 t0, [%64+5120];\nld.shared.b32 t1, [%64+5248];\nadd.s64 d, %65, 152;\nwgmma.fence.sync.aligned;\nwgmma.mma_async.sync.aligned.m64n56k16.f32.bf16.bf16 {%0, %1, %2, %3, %4, %5, %6, %7, %8, %9, %10, %11, %12, %13, %14, %15, %16, %17, %18, %19, %20, %21, %22, %23, %24, %25, %26, %27}, {b0, b1, b2, b3}, d, 1, 1, 1, 0;\nwgmma.commit_group.sync.aligned;\nwgmma.wait_group.sync.aligned 1;\nmov.b32 a2, b1;\nmov.b32 a0, t0;\nmov.b32 a3, t0;\nmov.b32 a1, t1;\n"
        "ld.shared.b32 t0, [%64+5376];\nld.shared.b32 t1, [%64+5504];\nadd.s64 d, %65, 160;\nwgmma.fence.sync.aligned;\nwgmma.mma_async.sync.aligned.m64n48k16.f32.bf16.bf16 {%0, %1, %2, %3, %4, %5, %6, %7, %8, %9, %10, %11, %12, %13, %14, %15, %16, %17, %18, %19, %20, %21, %22, %23}, {a0, a1, a2, a3}, d, 1, 1, 1, 0;\nwgmma.commit_group.sync.aligned;\nwgmma.wait_group.sync.aligned 1;\nmov.b32 b2, a1;\nmov.b32 b0, t0;\nmov.b32 b3, t0;\nmov.b32 b1, t1;\n"
        "ld.shared.b32 t0, [%64+5632];\nld.shared.b32 t1, [%64+5760];\nadd.s64 d, %65, 168;\nwgmma.fence.sync.aligned;\nwgmma.mma_async.sync.aligned.m64n48k16.f32.bf16.bf16 {%0, %1, %2, %3, %4, %5, %6, %7, %8, %9, %10, %11, %12, %13, %14, %15, %16, %17, %18, %19, %20, %21, %22, %23}, {b0, b1, b2, b3}, d, 1, 1, 1, 0;\nwgmma.commit_group.sync.aligned;\nwgmma.wait_group.sync.aligned 1;\nmov.b32 a2, b1;\nmov.b32 a0, t0;\nmov.b32 a3, t0;\nmov.b32 a1, t1;\n"
        "ld.shared.b32 t0, [%64+5888];\nld.shared.b32 t1, [%64+6016];\nadd.s64 d, %65, 176;\nwgmma.fence.sync.aligned;\nwgmma.mma_async.sync.aligned.m64n40k16.f32.bf16.bf16 {%0, %1, %2, %3, %4, %5, %6, %7, %8, %9, %10, %11, %12, %13, %14, %15, %16, %17, %18, %19}, {a0, a1, a2, a3}, d, 1, 1, 1, 0;\nwgmma.commit_group.sync.aligned;\nwgmma.wait_group.sync.aligned 1;\nmov.b32 b2, a1;\nmov.b32 b0, t0;\nmov.b32 b3, t0;\nmov.b32 b1, t1;\n"
        "ld.shared.b32 t0, [%64+6144];\nld.shared.b32 t1, [%64+6272];\nadd.s64 d, %65, 184;\nwgmma.fence.sync.aligned;\nwgmma.mma_async.sync.aligned.m64n40k16.f32.bf16.bf16 {%0, %1, %2, %3, %4, %5, %6, %7, %8, %9, %10, %11, %12, %13, %14, %15, %16, %17, %18, %19}, {b0, b1, b2, b3}, d, 1, 1, 1, 0;\nwgmma.commit_group.sync.aligned;\nwgmma.wait_group.sync.aligned 1;\nmov.b32 a2, b1;\nmov.b32 a0, t0;\nmov.b32 a3, t0;\nmov.b32 a1, t1;\n"
        "ld.shared.b32 t0, [%64+6400];\nld.shared.b32 t1, [%64+6528];\nadd.s64 d, %65, 192;\nwgmma.fence.sync.aligned;\nwgmma.mma_async.sync.aligned.m64n32k16.f32.bf16.bf16 {%0, %1, %2, %3, %4, %5, %6, %7, %8, %9, %10, %11, %12, %13, %14, %15}, {a0, a1, a2, a3}, d, 1, 1, 1, 0;\nwgmma.commit_group.sync.aligned;\nwgmma.wait_group.sync.aligned 1;\nmov.b32 b2, a1;\nmov.b32 b0, t0;\nmov.b32 b3, t0;\nmov.b32 b1, t1;\n"
        "ld.shared.b32 t0, [%64+6656];\nld.shared.b32 t1, [%64+6784];\nadd.s64 d, %65, 200;\nwgmma.fence.sync.aligned;\nwgmma.mma_async.sync.aligned.m64n32k16.f32.bf16.bf16 {%0, %1, %2, %3, %4, %5, %6, %7, %8, %9, %10, %11, %12, %13, %14, %15}, {b0, b1, b2, b3}, d, 1, 1, 1, 0;\nwgmma.commit_group.sync.aligned;\nwgmma.wait_group.sync.aligned 1;\nmov.b32 a2, b1;\nmov.b32 a0, t0;\nmov.b32 a3, t0;\nmov.b32 a1, t1;\n"
        "ld.shared.b32 t0, [%64+6912];\nld.shared.b32 t1, [%64+7040];\nadd.s64 d, %65, 208;\nwgmma.fence.sync.aligned;\nwgmma.mma_async.sync.aligned.m64n24k16.f32.bf16.bf16 {%0, %1, %2, %3, %4, %5, %6, %7, %8, %9, %10, %11}, {a0, a1, a2, a3}, d, 1, 1, 1, 0;\nwgmma.commit_group.sync.aligned;\nwgmma.wait_group.sync.aligned 1;\nmov.b32 b2, a1;\nmov.b32 b0, t0;\nmov.b32 b3, t0;\nmov.b32 b1, t1;\n"
        "ld.shared.b32 t0, [%64+7168];\nld.shared.b32 t1, [%64+7296];\nadd.s64 d, %65, 216;\nwgmma.fence.sync.aligned;\nwgmma.mma_async.sync.aligned.m64n24k16.f32.bf16.bf16 {%0, %1, %2, %3, %4, %5, %6, %7, %8, %9, %10, %11}, {b0, b1, b2, b3}, d, 1, 1, 1, 0;\nwgmma.commit_group.sync.aligned;\nwgmma.wait_group.sync.aligned 1;\nmov.b32 a2, b1;\nmov.b32 a0, t0;\nmov.b32 a3, t0;\nmov.b32 a1, t1;\n"
        "ld.shared.b32 t0, [%64+7424];\nld.shared.b32 t1, [%64+7552];\nadd.s64 d, %65, 224;\nwgmma.fence.sync.aligned;\nwgmma.mma_async.sync.aligned.m64n16k16.f32.bf16.bf16 {%0, %1, %2, %3, %4, %5, %6, %7}, {a0, a1, a2, a3}, d, 1, 1, 1, 0;\nwgmma.commit_group.sync.aligned;\nwgmma.wait_group.sync.aligned 1;\nmov.b32 b2, a1;\nmov.b32 b0, t0;\nmov.b32 b3, t0;\nmov.b32 b1, t1;\n"
        "ld.shared.b32 t0, [%64+7680];\nld.shared.b32 t1, [%64+7808];\nadd.s64 d, %65, 232;\nwgmma.fence.sync.aligned;\nwgmma.mma_async.sync.aligned.m64n16k16.f32.bf16.bf16 {%0, %1, %2, %3, %4, %5, %6, %7}, {b0, b1, b2, b3}, d, 1, 1, 1, 0;\nwgmma.commit_group.sync.aligned;\nwgmma.wait_group.sync.aligned 1;\nmov.b32 a2, b1;\nmov.b32 a0, t0;\nmov.b32 a3, t0;\nmov.b32 a1, t1;\n"
        "ld.shared.b32 t0, [%64+7936];\nld.shared.b32 t1, [%64+8064];\nadd.s64 d, %65, 240;\nwgmma.fence.sync.aligned;\nwgmma.mma_async.sync.aligned.m64n8k16.f32.bf16.bf16 {%0, %1, %2, %3}, {a0, a1, a2, a3}, d, 1, 1, 1, 0;\nwgmma.commit_group.sync.aligned;\nwgmma.wait_group.sync.aligned 1;\nmov.b32 b2, a1;\nmov.b32 b0, t0;\nmov.b32 b3, t0;\nmov.b32 b1, t1;\n"
        "add.s64 d, %65, 248;\nwgmma.fence.sync.aligned;\nwgmma.mma_async.sync.aligned.m64n8k16.f32.bf16.bf16 {%0, %1, %2, %3}, {b0, b1, b2, b3}, d, 1, 1, 1, 0;\nwgmma.commit_group.sync.aligned;\nwgmma.wait_group.sync.aligned 0;\n"
        "}" : "+f"(d[0]), "+f"(d[1]), "+f"(d[2]), "+f"(d[3]), "+f"(d[4]), "+f"(d[5]), "+f"(d[6]), "+f"(d[7]), "+f"(d[8]), "+f"(d[9]), "+f"(d[10]), "+f"(d[11]), "+f"(d[12]), "+f"(d[13]), "+f"(d[14]), "+f"(d[15]), "+f"(d[16]), "+f"(d[17]), "+f"(d[18]), "+f"(d[19]), "+f"(d[20]), "+f"(d[21]), "+f"(d[22]), "+f"(d[23]), "+f"(d[24]), "+f"(d[25]), "+f"(d[26]), "+f"(d[27]), "+f"(d[28]), "+f"(d[29]), "+f"(d[30]), "+f"(d[31]), "+f"(d[32]), "+f"(d[33]), "+f"(d[34]), "+f"(d[35]), "+f"(d[36]), "+f"(d[37]), "+f"(d[38]), "+f"(d[39]), "+f"(d[40]), "+f"(d[41]), "+f"(d[42]), "+f"(d[43]), "+f"(d[44]), "+f"(d[45]), "+f"(d[46]), "+f"(d[47]), "+f"(d[48]), "+f"(d[49]), "+f"(d[50]), "+f"(d[51]), "+f"(d[52]), "+f"(d[53]), "+f"(d[54]), "+f"(d[55]), "+f"(d[56]), "+f"(d[57]), "+f"(d[58]), "+f"(d[59]), "+f"(d[60]), "+f"(d[61]), "+f"(d[62]), "+f"(d[63]) : "r"(pa), "l"(db) : "memory");
}
__device__ __forceinline__ void wgmma_ss80(float (&d)[40], uint64_t da, uint64_t db, int sc) {
    asm volatile("{\n.reg .pred p;\nsetp.ne.b32 p, %42, 0;\n"
        "wgmma.mma_async.sync.aligned.m64n80k16.f32.bf16.bf16 {%0, %1, %2, %3, %4, %5, %6, %7, %8, %9, %10, %11, %12, %13, %14, %15, %16, %17, %18, %19, %20, %21, %22, %23, %24, %25, %26, %27, %28, %29, %30, %31, %32, %33, %34, %35, %36, %37, %38, %39}, %40, %41, p, 1, 1, 0, 1;\n}\n"
        : "+f"(d[0]), "+f"(d[1]), "+f"(d[2]), "+f"(d[3]), "+f"(d[4]), "+f"(d[5]), "+f"(d[6]), "+f"(d[7]), "+f"(d[8]), "+f"(d[9]), "+f"(d[10]), "+f"(d[11]), "+f"(d[12]), "+f"(d[13]), "+f"(d[14]), "+f"(d[15]), "+f"(d[16]), "+f"(d[17]), "+f"(d[18]), "+f"(d[19]), "+f"(d[20]), "+f"(d[21]), "+f"(d[22]), "+f"(d[23]), "+f"(d[24]), "+f"(d[25]), "+f"(d[26]), "+f"(d[27]), "+f"(d[28]), "+f"(d[29]), "+f"(d[30]), "+f"(d[31]), "+f"(d[32]), "+f"(d[33]), "+f"(d[34]), "+f"(d[35]), "+f"(d[36]), "+f"(d[37]), "+f"(d[38]), "+f"(d[39]) : "l"(da), "l"(db), "r"(sc));
}
__device__ __forceinline__ void wgmma_ss8_ta(float (&d)[4], uint64_t da, uint64_t db, int sc) {
    asm volatile("{\n.reg .pred p;\nsetp.ne.b32 p, %6, 0;\n"
        "wgmma.mma_async.sync.aligned.m64n8k16.f32.bf16.bf16 {%0, %1, %2, %3}, %4, %5, p, 1, 1, 1, 0;\n}\n"
        : "+f"(d[0]), "+f"(d[1]), "+f"(d[2]), "+f"(d[3]) : "l"(da), "l"(db), "r"(sc));
}
__device__ __forceinline__ void wgmma_ss80t(float (&d)[40], uint64_t da, uint64_t db, int sc) {
    asm volatile("{\n.reg .pred p;\nsetp.ne.b32 p, %42, 0;\n"
        "wgmma.mma_async.sync.aligned.m64n80k16.f32.bf16.bf16 {%0, %1, %2, %3, %4, %5, %6, %7, %8, %9, %10, %11, %12, %13, %14, %15, %16, %17, %18, %19, %20, %21, %22, %23, %24, %25, %26, %27, %28, %29, %30, %31, %32, %33, %34, %35, %36, %37, %38, %39}, %40, %41, p, 1, 1, 1, 1;\n}\n"
        : "+f"(d[0]), "+f"(d[1]), "+f"(d[2]), "+f"(d[3]), "+f"(d[4]), "+f"(d[5]), "+f"(d[6]), "+f"(d[7]), "+f"(d[8]), "+f"(d[9]), "+f"(d[10]), "+f"(d[11]), "+f"(d[12]), "+f"(d[13]), "+f"(d[14]), "+f"(d[15]), "+f"(d[16]), "+f"(d[17]), "+f"(d[18]), "+f"(d[19]), "+f"(d[20]), "+f"(d[21]), "+f"(d[22]), "+f"(d[23]), "+f"(d[24]), "+f"(d[25]), "+f"(d[26]), "+f"(d[27]), "+f"(d[28]), "+f"(d[29]), "+f"(d[30]), "+f"(d[31]), "+f"(d[32]), "+f"(d[33]), "+f"(d[34]), "+f"(d[35]), "+f"(d[36]), "+f"(d[37]), "+f"(d[38]), "+f"(d[39]) : "l"(da), "l"(db), "r"(sc));
}
__device__ __forceinline__ void wgmma_rs8(float (&d)[4], uint32_t a0, uint32_t a1, uint32_t a2, uint32_t a3, uint64_t db, int sc) {
    asm volatile("{\n.reg .pred p;\nsetp.ne.b32 p, %9, 0;\n"
        "wgmma.mma_async.sync.aligned.m64n8k16.f32.bf16.bf16 {%0, %1, %2, %3}, {%4, %5, %6, %7}, %8, p, 1, 1, 0;\n}\n"
        : "+f"(d[0]), "+f"(d[1]), "+f"(d[2]), "+f"(d[3]) : "r"(a0), "r"(a1), "r"(a2), "r"(a3), "l"(db), "r"(sc));
}
__device__ __forceinline__ void wgmma_rs128(float (&d)[64], uint32_t a0, uint32_t a1, uint32_t a2, uint32_t a3, uint64_t db, int sc) {
    asm volatile("{\n.reg .pred p;\nsetp.ne.b32 p, %69, 0;\n"
        "wgmma.mma_async.sync.aligned.m64n128k16.f32.bf16.bf16 {%0, %1, %2, %3, %4, %5, %6, %7, %8, %9, %10, %11, %12, %13, %14, %15, %16, %17, %18, %19, %20, %21, %22, %23, %24, %25, %26, %27, %28, %29, %30, %31, %32, %33, %34, %35, %36, %37, %38, %39, %40, %41, %42, %43, %44, %45, %46, %47, %48, %49, %50, %51, %52, %53, %54, %55, %56, %57, %58, %59, %60, %61, %62, %63}, {%64, %65, %66, %67}, %68, p, 1, 1, 1;\n}\n"
        : "+f"(d[0]), "+f"(d[1]), "+f"(d[2]), "+f"(d[3]), "+f"(d[4]), "+f"(d[5]), "+f"(d[6]), "+f"(d[7]), "+f"(d[8]), "+f"(d[9]), "+f"(d[10]), "+f"(d[11]), "+f"(d[12]), "+f"(d[13]), "+f"(d[14]), "+f"(d[15]), "+f"(d[16]), "+f"(d[17]), "+f"(d[18]), "+f"(d[19]), "+f"(d[20]), "+f"(d[21]), "+f"(d[22]), "+f"(d[23]), "+f"(d[24]), "+f"(d[25]), "+f"(d[26]), "+f"(d[27]), "+f"(d[28]), "+f"(d[29]), "+f"(d[30]), "+f"(d[31]), "+f"(d[32]), "+f"(d[33]), "+f"(d[34]), "+f"(d[35]), "+f"(d[36]), "+f"(d[37]), "+f"(d[38]), "+f"(d[39]), "+f"(d[40]), "+f"(d[41]), "+f"(d[42]), "+f"(d[43]), "+f"(d[44]), "+f"(d[45]), "+f"(d[46]), "+f"(d[47]), "+f"(d[48]), "+f"(d[49]), "+f"(d[50]), "+f"(d[51]), "+f"(d[52]), "+f"(d[53]), "+f"(d[54]), "+f"(d[55]), "+f"(d[56]), "+f"(d[57]), "+f"(d[58]), "+f"(d[59]), "+f"(d[60]), "+f"(d[61]), "+f"(d[62]), "+f"(d[63]) : "r"(a0), "r"(a1), "r"(a2), "r"(a3), "l"(db), "r"(sc));
}
__device__ __forceinline__ void wgmma_rs88(float (&d)[44], uint32_t a0, uint32_t a1, uint32_t a2, uint32_t a3, uint64_t db, int sc) {
    asm volatile("{\n.reg .pred p;\nsetp.ne.b32 p, %49, 0;\n"
        "wgmma.mma_async.sync.aligned.m64n88k16.f32.bf16.bf16 {%0, %1, %2, %3, %4, %5, %6, %7, %8, %9, %10, %11, %12, %13, %14, %15, %16, %17, %18, %19, %20, %21, %22, %23, %24, %25, %26, %27, %28, %29, %30, %31, %32, %33, %34, %35, %36, %37, %38, %39, %40, %41, %42, %43}, {%44, %45, %46, %47}, %48, p, 1, 1, 1;\n}\n"
        : "+f"(d[0]), "+f"(d[1]), "+f"(d[2]), "+f"(d[3]), "+f"(d[4]), "+f"(d[5]), "+f"(d[6]), "+f"(d[7]), "+f"(d[8]), "+f"(d[9]), "+f"(d[10]), "+f"(d[11]), "+f"(d[12]), "+f"(d[13]), "+f"(d[14]), "+f"(d[15]), "+f"(d[16]), "+f"(d[17]), "+f"(d[18]), "+f"(d[19]), "+f"(d[20]), "+f"(d[21]), "+f"(d[22]), "+f"(d[23]), "+f"(d[24]), "+f"(d[25]), "+f"(d[26]), "+f"(d[27]), "+f"(d[28]), "+f"(d[29]), "+f"(d[30]), "+f"(d[31]), "+f"(d[32]), "+f"(d[33]), "+f"(d[34]), "+f"(d[35]), "+f"(d[36]), "+f"(d[37]), "+f"(d[38]), "+f"(d[39]), "+f"(d[40]), "+f"(d[41]), "+f"(d[42]), "+f"(d[43]) : "r"(a0), "r"(a1), "r"(a2), "r"(a3), "l"(db), "r"(sc));
}
__device__ __forceinline__ void wgmma_rs128k(float (&d)[64], uint32_t a0, uint32_t a1, uint32_t a2, uint32_t a3, uint64_t db, int sc) {
    asm volatile("{\n.reg .pred p;\nsetp.ne.b32 p, %69, 0;\n"
        "wgmma.mma_async.sync.aligned.m64n128k16.f32.bf16.bf16 {%0, %1, %2, %3, %4, %5, %6, %7, %8, %9, %10, %11, %12, %13, %14, %15, %16, %17, %18, %19, %20, %21, %22, %23, %24, %25, %26, %27, %28, %29, %30, %31, %32, %33, %34, %35, %36, %37, %38, %39, %40, %41, %42, %43, %44, %45, %46, %47, %48, %49, %50, %51, %52, %53, %54, %55, %56, %57, %58, %59, %60, %61, %62, %63}, {%64, %65, %66, %67}, %68, p, 1, 1, 0;\n}\n"
        : "+f"(d[0]), "+f"(d[1]), "+f"(d[2]), "+f"(d[3]), "+f"(d[4]), "+f"(d[5]), "+f"(d[6]), "+f"(d[7]), "+f"(d[8]), "+f"(d[9]), "+f"(d[10]), "+f"(d[11]), "+f"(d[12]), "+f"(d[13]), "+f"(d[14]), "+f"(d[15]), "+f"(d[16]), "+f"(d[17]), "+f"(d[18]), "+f"(d[19]), "+f"(d[20]), "+f"(d[21]), "+f"(d[22]), "+f"(d[23]), "+f"(d[24]), "+f"(d[25]), "+f"(d[26]), "+f"(d[27]), "+f"(d[28]), "+f"(d[29]), "+f"(d[30]), "+f"(d[31]), "+f"(d[32]), "+f"(d[33]), "+f"(d[34]), "+f"(d[35]), "+f"(d[36]), "+f"(d[37]), "+f"(d[38]), "+f"(d[39]), "+f"(d[40]), "+f"(d[41]), "+f"(d[42]), "+f"(d[43]), "+f"(d[44]), "+f"(d[45]), "+f"(d[46]), "+f"(d[47]), "+f"(d[48]), "+f"(d[49]), "+f"(d[50]), "+f"(d[51]), "+f"(d[52]), "+f"(d[53]), "+f"(d[54]), "+f"(d[55]), "+f"(d[56]), "+f"(d[57]), "+f"(d[58]), "+f"(d[59]), "+f"(d[60]), "+f"(d[61]), "+f"(d[62]), "+f"(d[63]) : "r"(a0), "r"(a1), "r"(a2), "r"(a3), "l"(db), "r"(sc));
}
__device__ __forceinline__ void wgmma_rs88k(float (&d)[44], uint32_t a0, uint32_t a1, uint32_t a2, uint32_t a3, uint64_t db, int sc) {
    asm volatile("{\n.reg .pred p;\nsetp.ne.b32 p, %49, 0;\n"
        "wgmma.mma_async.sync.aligned.m64n88k16.f32.bf16.bf16 {%0, %1, %2, %3, %4, %5, %6, %7, %8, %9, %10, %11, %12, %13, %14, %15, %16, %17, %18, %19, %20, %21, %22, %23, %24, %25, %26, %27, %28, %29, %30, %31, %32, %33, %34, %35, %36, %37, %38, %39, %40, %41, %42, %43}, {%44, %45, %46, %47}, %48, p, 1, 1, 0;\n}\n"
        : "+f"(d[0]), "+f"(d[1]), "+f"(d[2]), "+f"(d[3]), "+f"(d[4]), "+f"(d[5]), "+f"(d[6]), "+f"(d[7]), "+f"(d[8]), "+f"(d[9]), "+f"(d[10]), "+f"(d[11]), "+f"(d[12]), "+f"(d[13]), "+f"(d[14]), "+f"(d[15]), "+f"(d[16]), "+f"(d[17]), "+f"(d[18]), "+f"(d[19]), "+f"(d[20]), "+f"(d[21]), "+f"(d[22]), "+f"(d[23]), "+f"(d[24]), "+f"(d[25]), "+f"(d[26]), "+f"(d[27]), "+f"(d[28]), "+f"(d[29]), "+f"(d[30]), "+f"(d[31]), "+f"(d[32]), "+f"(d[33]), "+f"(d[34]), "+f"(d[35]), "+f"(d[36]), "+f"(d[37]), "+f"(d[38]), "+f"(d[39]), "+f"(d[40]), "+f"(d[41]), "+f"(d[42]), "+f"(d[43]) : "r"(a0), "r"(a1), "r"(a2), "r"(a3), "l"(db), "r"(sc));
}
__device__ __forceinline__ void wgmma_rs80k(float (&d)[40], uint32_t a0, uint32_t a1, uint32_t a2, uint32_t a3, uint64_t db, int sc) {
    asm volatile("{\n.reg .pred p;\nsetp.ne.b32 p, %45, 0;\n"
        "wgmma.mma_async.sync.aligned.m64n80k16.f32.bf16.bf16 {%0, %1, %2, %3, %4, %5, %6, %7, %8, %9, %10, %11, %12, %13, %14, %15, %16, %17, %18, %19, %20, %21, %22, %23, %24, %25, %26, %27, %28, %29, %30, %31, %32, %33, %34, %35, %36, %37, %38, %39}, {%40, %41, %42, %43}, %44, p, 1, 1, 0;\n}\n"
        : "+f"(d[0]), "+f"(d[1]), "+f"(d[2]), "+f"(d[3]), "+f"(d[4]), "+f"(d[5]), "+f"(d[6]), "+f"(d[7]), "+f"(d[8]), "+f"(d[9]), "+f"(d[10]), "+f"(d[11]), "+f"(d[12]), "+f"(d[13]), "+f"(d[14]), "+f"(d[15]), "+f"(d[16]), "+f"(d[17]), "+f"(d[18]), "+f"(d[19]), "+f"(d[20]), "+f"(d[21]), "+f"(d[22]), "+f"(d[23]), "+f"(d[24]), "+f"(d[25]), "+f"(d[26]), "+f"(d[27]), "+f"(d[28]), "+f"(d[29]), "+f"(d[30]), "+f"(d[31]), "+f"(d[32]), "+f"(d[33]), "+f"(d[34]), "+f"(d[35]), "+f"(d[36]), "+f"(d[37]), "+f"(d[38]), "+f"(d[39]) : "r"(a0), "r"(a1), "r"(a2), "r"(a3), "l"(db), "r"(sc));
}
__device__ __forceinline__ void wgmma_rs128x(float (&d)[32], float (&e)[32], uint32_t a0, uint32_t a1, uint32_t a2, uint32_t a3, uint64_t db, int sc) {
    asm volatile("{\n.reg .pred p;\nsetp.ne.b32 p, %69, 0;\n"
        "wgmma.mma_async.sync.aligned.m64n128k16.f32.bf16.bf16 {%0, %1, %2, %3, %4, %5, %6, %7, %8, %9, %10, %11, %12, %13, %14, %15, %16, %17, %18, %19, %20, %21, %22, %23, %24, %25, %26, %27, %28, %29, %30, %31, %32, %33, %34, %35, %36, %37, %38, %39, %40, %41, %42, %43, %44, %45, %46, %47, %48, %49, %50, %51, %52, %53, %54, %55, %56, %57, %58, %59, %60, %61, %62, %63}, {%64, %65, %66, %67}, %68, p, 1, 1, 1;\n}\n"
        : "+f"(d[0]), "+f"(d[1]), "+f"(d[2]), "+f"(d[3]), "+f"(d[4]), "+f"(d[5]), "+f"(d[6]), "+f"(d[7]), "+f"(d[8]), "+f"(d[9]), "+f"(d[10]), "+f"(d[11]), "+f"(d[12]), "+f"(d[13]), "+f"(d[14]), "+f"(d[15]), "+f"(d[16]), "+f"(d[17]), "+f"(d[18]), "+f"(d[19]), "+f"(d[20]), "+f"(d[21]), "+f"(d[22]), "+f"(d[23]), "+f"(d[24]), "+f"(d[25]), "+f"(d[26]), "+f"(d[27]), "+f"(d[28]), "+f"(d[29]), "+f"(d[30]), "+f"(d[31]), "+f"(e[0]), "+f"(e[1]), "+f"(e[2]), "+f"(e[3]), "+f"(e[4]), "+f"(e[5]), "+f"(e[6]), "+f"(e[7]), "+f"(e[8]), "+f"(e[9]), "+f"(e[10]), "+f"(e[11]), "+f"(e[12]), "+f"(e[13]), "+f"(e[14]), "+f"(e[15]), "+f"(e[16]), "+f"(e[17]), "+f"(e[18]), "+f"(e[19]), "+f"(e[20]), "+f"(e[21]), "+f"(e[22]), "+f"(e[23]), "+f"(e[24]), "+f"(e[25]), "+f"(e[26]), "+f"(e[27]), "+f"(e[28]), "+f"(e[29]), "+f"(e[30]), "+f"(e[31]) : "r"(a0), "r"(a1), "r"(a2), "r"(a3), "l"(db), "r"(sc));
}
__device__ __forceinline__ void wgmma_rs64(float (&d)[32], uint32_t a0, uint32_t a1, uint32_t a2, uint32_t a3, uint64_t db, int sc) {
    asm volatile("{\n.reg .pred p;\nsetp.ne.b32 p, %37, 0;\n"
        "wgmma.mma_async.sync.aligned.m64n64k16.f32.bf16.bf16 {%0, %1, %2, %3, %4, %5, %6, %7, %8, %9, %10, %11, %12, %13, %14, %15, %16, %17, %18, %19, %20, %21, %22, %23, %24, %25, %26, %27, %28, %29, %30, %31}, {%32, %33, %34, %35}, %36, p, 1, 1, 1;\n}\n"
        : "+f"(d[0]), "+f"(d[1]), "+f"(d[2]), "+f"(d[3]), "+f"(d[4]), "+f"(d[5]), "+f"(d[6]), "+f"(d[7]), "+f"(d[8]), "+f"(d[9]), "+f"(d[10]), "+f"(d[11]), "+f"(d[12]), "+f"(d[13]), "+f"(d[14]), "+f"(d[15]), "+f"(d[16]), "+f"(d[17]), "+f"(d[18]), "+f"(d[19]), "+f"(d[20]), "+f"(d[21]), "+f"(d[22]), "+f"(d[23]), "+f"(d[24]), "+f"(d[25]), "+f"(d[26]), "+f"(d[27]), "+f"(d[28]), "+f"(d[29]), "+f"(d[30]), "+f"(d[31]) : "r"(a0), "r"(a1), "r"(a2), "r"(a3), "l"(db), "r"(sc));
}
__device__ __forceinline__ void wgmma_ss64(float (&d)[32], uint64_t da, uint64_t db, int sc) {
    asm volatile("{\n.reg .pred p;\nsetp.ne.b32 p, %34, 0;\n"
        "wgmma.mma_async.sync.aligned.m64n64k16.f32.bf16.bf16 {%0, %1, %2, %3, %4, %5, %6, %7, %8, %9, %10, %11, %12, %13, %14, %15, %16, %17, %18, %19, %20, %21, %22, %23, %24, %25, %26, %27, %28, %29, %30, %31}, %32, %33, p, 1, 1, 0, 1;\n}\n"
        : "+f"(d[0]), "+f"(d[1]), "+f"(d[2]), "+f"(d[3]), "+f"(d[4]), "+f"(d[5]), "+f"(d[6]), "+f"(d[7]), "+f"(d[8]), "+f"(d[9]), "+f"(d[10]), "+f"(d[11]), "+f"(d[12]), "+f"(d[13]), "+f"(d[14]), "+f"(d[15]), "+f"(d[16]), "+f"(d[17]), "+f"(d[18]), "+f"(d[19]), "+f"(d[20]), "+f"(d[21]), "+f"(d[22]), "+f"(d[23]), "+f"(d[24]), "+f"(d[25]), "+f"(d[26]), "+f"(d[27]), "+f"(d[28]), "+f"(d[29]), "+f"(d[30]), "+f"(d[31]) : "l"(da), "l"(db), "r"(sc));
}
__device__ __forceinline__ void wgmma_ss128(float (&d)[64], uint64_t da, uint64_t db, int sc) {
    asm volatile("{\n.reg .pred p;\nsetp.ne.b32 p, %66, 0;\n"
        "wgmma.mma_async.sync.aligned.m64n128k16.f32.bf16.bf16 {%0, %1, %2, %3, %4, %5, %6, %7, %8, %9, %10, %11, %12, %13, %14, %15, %16, %17, %18, %19, %20, %21, %22, %23, %24, %25, %26, %27, %28, %29, %30, %31, %32, %33, %34, %35, %36, %37, %38, %39, %40, %41, %42, %43, %44, %45, %46, %47, %48, %49, %50, %51, %52, %53, %54, %55, %56, %57, %58, %59, %60, %61, %62, %63}, %64, %65, p, 1, 1, 0, 1;\n}\n"
        : "+f"(d[0]), "+f"(d[1]), "+f"(d[2]), "+f"(d[3]), "+f"(d[4]), "+f"(d[5]), "+f"(d[6]), "+f"(d[7]), "+f"(d[8]), "+f"(d[9]), "+f"(d[10]), "+f"(d[11]), "+f"(d[12]), "+f"(d[13]), "+f"(d[14]), "+f"(d[15]), "+f"(d[16]), "+f"(d[17]), "+f"(d[18]), "+f"(d[19]), "+f"(d[20]), "+f"(d[21]), "+f"(d[22]), "+f"(d[23]), "+f"(d[24]), "+f"(d[25]), "+f"(d[26]), "+f"(d[27]), "+f"(d[28]), "+f"(d[29]), "+f"(d[30]), "+f"(d[31]), "+f"(d[32]), "+f"(d[33]), "+f"(d[34]), "+f"(d[35]), "+f"(d[36]), "+f"(d[37]), "+f"(d[38]), "+f"(d[39]), "+f"(d[40]), "+f"(d[41]), "+f"(d[42]), "+f"(d[43]), "+f"(d[44]), "+f"(d[45]), "+f"(d[46]), "+f"(d[47]), "+f"(d[48]), "+f"(d[49]), "+f"(d[50]), "+f"(d[51]), "+f"(d[52]), "+f"(d[53]), "+f"(d[54]), "+f"(d[55]), "+f"(d[56]), "+f"(d[57]), "+f"(d[58]), "+f"(d[59]), "+f"(d[60]), "+f"(d[61]), "+f"(d[62]), "+f"(d[63]) : "l"(da), "l"(db), "r"(sc));
}

__device__ __forceinline__ uint64_t mkdesc(uint32_t lo) { return ((uint64_t)0x40000040u << 32) | lo; }
__device__ __forceinline__ uint32_t tag(uint32_t w, uint32_t ep) { asm("lop3.b32 %0, %0, 1, %1, 0xB8;" : "+r"(w) : "r"(ep)); return w; }
template <int N> __device__ __forceinline__ void pack_part(uint32_t (&p)[32], const float (&v)[N], uint32_t ep) {
#pragma unroll
    for (int i = 0; i < N / 2; i++) p[i] = (i & 3) ? pack2(v[2 * i], v[2 * i + 1]) : tag(pack2(v[2 * i], v[2 * i + 1]), ep);
#pragma unroll
    for (int i = 0; i < N / 2; i++) asm volatile("" : "+r"(p[i]));
}
__device__ __forceinline__ void st_part(uint4* p, const uint32_t* v) {
    asm volatile("{\n.reg .b64 l, h;\n.reg .b128 q;\nmov.b64 l, {%1, %2};\nmov.b64 h, {%3, %4};\nmov.b128 q, {l, h};\nst.relaxed.gpu.global.b128 [%0], q;\n}"
                 ::"l"(p), "r"(v[0]), "r"(v[1]), "r"(v[2]), "r"(v[3]) : "memory");
}
__device__ __forceinline__ void st_peer(uint32_t a, uint32_t x, uint32_t y, uint32_t z, uint32_t w, uint32_t bar) {
    asm volatile("st.async.shared::cluster.mbarrier::complete_tx::bytes.v4.b32 [%0], {%1, %2, %3, %4}, [%5];" ::"r"(a), "r"(x), "r"(y), "r"(z), "r"(w), "r"(bar) : "memory");
}
__device__ __forceinline__ int g4_block(int c, int j) { return c ? j ^ (8 - 2 * c) : 8 + (j & 1); }
__device__ __forceinline__ uint32_t recv_off(int w) { return w ? OFF_XR : OFF_REM; }
__device__ __forceinline__ uint4 ld_part(const void* p) {
    uint4 v;
    asm volatile("{\n.reg .b64 l, h;\n.reg .b128 q;\nld.relaxed.gpu.global.b128 q, [%4];\nmov.b128 {l, h}, q;\nmov.b64 {%0, %1}, l;\nmov.b64 {%2, %3}, h;\n}"
                 : "=r"(v.x), "=r"(v.y), "=r"(v.z), "=r"(v.w) : "l"(p) : "memory");
    return v;
}
__device__ __forceinline__ void ld_part4(uint4 (&u)[4], const uint4* p, int st) {
#pragma unroll
    for (int i = 0; i < 4; i++) u[i] = ld_part(p + i * st);
}
__device__ __forceinline__ uint32_t stale4(const uint4 (&u)[4], uint32_t ep) { return (u[0].x ^ ep) | (u[1].x ^ ep) | (u[2].x ^ ep) | (u[3].x ^ ep); }
__device__ __forceinline__ void fix4(uint4 (&u)[4], const uint4* p, uint32_t ep, int code) {
    unsigned it = 0;
    while (__any_sync(~0u, stale4(u, ep) & 1)) {
        ld_part4(u, p, 128);
        STALE(code)
        if (++it > SPIN_LIMIT) SPIN_FAIL(58)
    }
}
__device__ __forceinline__ void add8(float* v, uint4 u) {
    v[0] += blo(u.x); v[1] += bhi(u.x); v[2] += blo(u.y); v[3] += bhi(u.y);
    v[4] += blo(u.z); v[5] += bhi(u.z); v[6] += blo(u.w); v[7] += bhi(u.w);
}
__device__ __forceinline__ void unpack8(float* v, uint4 u) {
    v[0] = blo(u.x); v[1] = bhi(u.x); v[2] = blo(u.y); v[3] = bhi(u.y); v[4] = blo(u.z); v[5] = bhi(u.z); v[6] = blo(u.w); v[7] = bhi(u.w);
}
__device__ __forceinline__ uint4 add2(uint4 a, uint4 b) { return make_uint4(add2(a.x, b.x), add2(a.y, b.y), add2(a.z, b.z), add2(a.w, b.w)); }
__device__ __forceinline__ void base16(float* v, uint4 b, float2 c, float2 d) {
    v[0] = fmaf(c.x, v[0], blo(b.x)); v[1] = fmaf(c.y, v[1], bhi(b.x)); v[2] = fmaf(c.x, v[2], blo(b.y)); v[3] = fmaf(c.y, v[3], bhi(b.y));
    v[4] = fmaf(d.x, v[4], blo(b.z)); v[5] = fmaf(d.y, v[5], bhi(b.z)); v[6] = fmaf(d.x, v[6], blo(b.w)); v[7] = fmaf(d.y, v[7], bhi(b.w));
}
__device__ __forceinline__ uint32_t split2(float x) { const float h = rbf(x); return pack2(h, x - h); }
__device__ __forceinline__ uint32_t b80_desc(uint32_t dsb, uint32_t wn, uint32_t rn, uint32_t h) {
    const uint32_t wb = dsb + OFF_W + (wn & 7) * 16384 + h * 8192, rm = dsb + OFF_REM + rn * 4096 + h * 2048;
    return (wb >> 4) | ((rm - wb) << 12);
}
constexpr int64_t B80_STEP = 128 - (126 << 16), B80_HALF = 512 - (384 << 16);
__device__ __forceinline__ int g1_block(int n, int j) { return n < 5 ? 2 * n + (j & 1) : 2 * n - 9 - (j & 1); }

template <int OCT>
__device__ __forceinline__ void gemv_tile(float (&d)[4], uint32_t a, uint32_t b, int kb0) {
    uint32_t alo = ((a & 0x3FFFF) >> 4) | 0x10000u, blo_ = ((b & 0x3FFFF) >> 4) | (OCT << 16);
#pragma unroll 1
    for (int s = 0; s < 20; s += 4) {
        const int kb = kb0 + (s >> 2);
        const uint32_t bk = blo_ + (OCT == 7 ? (kb & 1) * 288 + (kb >> 1) * 56 : kb * 64);
        wg_fence();
#pragma unroll
        for (int q = 0; q < 4; q++) wgmma_ss8_ta(d, mkdesc(alo + (s + q) * 128), ((uint64_t)8 << 32) | (bk + q * 2 * OCT), s + q);
        wg_commit();
    }
    wg_wait<0>();
    reg_fence(d);
}

__device__ __forceinline__ void flush_tile(uint32_t st, bf16* dst, int u) {
#pragma unroll
    for (int i = 0; i < 2; i++) {
        const int idx = u + 320 * i, row = idx >> 3, c = idx & 7;
        stg128(dst + (size_t)row * S_ + 8 * c, lds128(st + row * 128 + ((c ^ ((row >> 1) & 7)) << 4)));
    }
}

__device__ __forceinline__ int tid_now() { int t; asm volatile("mov.u32 %0, %%tid.x;" : "=r"(t)); return t; }
__device__ __forceinline__ float zscale(float c) { return c == 0.f ? 0x1p-30f : c; }
__device__ __forceinline__ bool bar_any(int id, bool p) {
    uint32_t r;
    asm volatile("{\n.reg .pred a, b;\nsetp.ne.u32 a, %2, 0;\nbarrier.red.or.pred.aligned b, %1, 128, a;\nselp.u32 %0, 1, 0, b;\n}" : "=r"(r) : "r"(id), "r"((uint32_t)p) : "memory");
    return r != 0;
}

__device__ __forceinline__ void init_barriers(uint32_t bars, int warp) {
    if (elect()) {
#pragma unroll 1
        for (int i = warp; i < B_NUM; i += 15) {
            const int n = i < B_WEMPTY ? 1 : i < B_XFULL ? 8 : i < B_SIG ? 1 : i < B_XS ? 4 : i < B_KVS ? 12 : i == B_KVS ? 20 : i == B_XFREE ? 16 : 1;
            if (i != B_IN) mbar_init(bars + i * 8, n);
            if (i >= B_SUMS) mbar_expect(bars + i * 8, i < B_RECV ? 2048 : ((i - B_RECV) & 3) < 3 ? 8192 : 3072);
        }
        asm volatile("fence.mbarrier_init.release.cluster;" ::: "memory");
    }
}

__global__ void __launch_bounds__(NTHR, 1) fused_kernel(const __grid_constant__ Ptrs pp, bf16* __restrict__ out, const __grid_constant__ Maps mp) {
    extern __shared__ __align__(1024) uint8_t smem_raw[];
    const uint32_t sb = s2u(smem_raw), bars = sb + M_BAR, dsb = sb & 0x3FFFF;
    const int id = blockIdx.x, warp = __shfl_sync(0xffffffffu, (int)threadIdx.x >> 5, 0), wg = warp >> 2;
    const long long c0 = clock64();
#define TIDS const int tid = tid_now(), lane = tid & 31, wt = tid & 127, g = lane >> 2, t = lane & 3; (void)wt; (void)g; (void)t;
    TS(threadIdx.x == 0, 0) TG(threadIdx.x == 0, 62)

    if (id >= 128) {
        TIDS
        if (sb & 1023) __trap();
        const int hs = id - 128;
        constexpr int H_B = 204800;
        static_assert(H_B + TAB_BYTES + 8 * VEC_BYTES <= OFF_M, "helper map");
        if (warp < 10 && elect()) { mbar_init(bars + warp * 8, 1); mbar_init(bars + 80 + warp * 8, 1); asm volatile("fence.mbarrier_init.release.cluster;" ::: "memory"); }
        __syncthreads();
        wait_clock(c0, HELP_T);
        uint4 wr[10];
#pragma unroll
        for (int u = 0; u < 10; u++) wr[u] = ldg128(((hs >> 1) ? pp.w2 : pp.w1) + (size_t)(320 * (hs & 1) + (tid >> 4) + 32 * u) * D_ + 512 + 8 * (tid & 15));
        {
            const int r = tid >> 4, c = tid & 15;
            uint4* dst[2];
#pragma unroll
            for (int e = 0; e < 2; e++) {
                const int p = !(hs >> 1) ? r : e && (hs & 1) ? (r & ~14) | ((r & 6) << 1) | ((r & 8) >> 2) : (r & ~30) | ((r & 6) << 2) | ((r & 24) >> 2);
                dst[e] = &g_wr[(((hs >> 1) * 8 + (c >> 1)) * 10 + 5 * (hs & 1)) * 128 + (p & 15) * 8 + ((2 * (p >> 4) + (c & 1)) ^ (p & 7))];
            }
#pragma unroll
            for (int u = 0; u < 10; u++) stg128(reinterpret_cast<uint4*>(reinterpret_cast<uintptr_t>(dst[u >= 6]) ^ (64 * (u & 1))) + (u >> 1) * 128, wr[u]);
        }
        __syncthreads();
        if (warp == 0) signal_cnt(&g_cnt.wr[0], lane, 1);
        __syncthreads();
        if (warp < 5 && elect()) {
            const int un = 5 * hs + warp;
            mbar_expect(bars + warp * 8, 40960);
            tma_ld2(sb + warp * 40960, &mp.w1h, 64 * (un >> 1), 320 * (un & 1), bars + warp * 8);
            tma_ld2(sb + warp * 40960 + 20480, &mp.w1h, 64 * (un >> 1), 320 * (un & 1) + 160, bars + warp * 8);
        }
        if (tid < 320) {
            const uint4* gm = reinterpret_cast<const uint4*>(g_mod + 3 * D_) + tid;
            const unsigned epoch = *(volatile unsigned*)&g_epoch + 1;
            uint4 r[6];
            unsigned it = 0;
            for (;;) {
                uint32_t bad = 0;
#pragma unroll
                for (int i = 0; i < 6; i++) { r[i] = ld_part(gm + (i >> 1) * (D_ / 2) + (i & 1) * 3 * D_); bad |= (r[i].y ^ epoch) | (r[i].w ^ epoch); }
                if (__all_sync(~0u, !bad)) break;
                if (++it > SPIN_LIMIT) SPIN_FAIL(54)
            }
            uint32_t mv[3];
#pragma unroll
            for (int i = 0; i < 3; i++) mv[i] = pack2(__uint_as_float(r[2 * i].x) + __uint_as_float(r[2 * i + 1].x), __uint_as_float(r[2 * i].z) + __uint_as_float(r[2 * i + 1].z));
            const uint32_t sw2 = mv[0], cw = add2(mv[1], 0x3f803f80u), gw = mv[2];
            const float c0 = blo(cw), c1 = bhi(cw), s0 = blo(sw2), s1 = bhi(sw2);
            const float i0 = __frcp_rn(zscale(c0)), i1 = __frcp_rn(zscale(c1));
            const uint32_t ci = pack2(i0, i1), cq = pack2(i0 * i0, i1 * i1);
            const uint32_t a = sb + H_B + ((tid >> 5) & 1) * 4608 + (tid >> 6) * 896 + ((tid >> 2) & 7) * 112 + (tid & 3) * 4;
            sts32(a, ci); sts32(a + 16, pack2(i0 - blo(ci), i1 - bhi(ci)));
            sts32(a + 32, cq); sts32(a + 48, pack2(fmaf(i0, i0, -blo(cq)), fmaf(i1, i1, -bhi(cq))));
            sts32(a + 64, cw); sts32(a + 80, sw2); sts32(a + 96, 0x3f803f80u);
            if ((tid & ~35) == 284) sts32(a + 112, 0);
            const uint32_t v = sb + H_B + TAB_BYTES + (tid < 256 ? (tid >> 5) * VEC_BYTES + (tid & 31) * 8 : ((tid - 256) >> 3) * VEC_BYTES + 256 + (tid & 7) * 8);
            sts64f(v, blo(gw), bhi(gw)); sts64f(v + 320, c0, c1); sts64f(v + 640, s0, s1); sts64f(v + 960, i0, i1);
            float k[5] = {c0 + c1, s0 + s1, fmaf(c0, c0, c1 * c1), fmaf(c0, s0, c1 * s1), fmaf(s0, s0, s1 * s1)};
#pragma unroll 1
            for (int o = 16; o; o >>= 1) {
#pragma unroll
                for (int e = 0; e < 5; e++) k[e] += __shfl_xor_sync(~0u, k[e], o);
            }
            const uint32_t ks = sb + H_B + TAB_BYTES + (lane & 7) * VEC_BYTES + 1280 + (warp >> 1) * 32;
            if ((warp & 1) && lane < 8) { sts128f(ks, k[0], k[1], k[2], k[3]); sts128f(ks + 16, k[4], 0.f, 0.f, 0.f); }
            bar_sync(3, 320);
            if (!(warp & 1) && lane < 8) {
                const float4 o = lds128f(ks);
                sts128f(ks, k[0] + o.x, k[1] + o.y, k[2] + o.z, k[3] + o.w); sts32(ks + 16, __float_as_uint(k[4] + __uint_as_float(lds32(ks + 16))));
            }
            fence_async_smem();
        }
        __syncthreads();
        if (hs == 0 && warp == 15 && elect()) {
            asm volatile("cp.async.bulk.global.shared::cta.bulk_group [%0], [%1], %2;\ncp.async.bulk.commit_group;\ncp.async.bulk.wait_group 0;"
                         ::"l"(g_tab), "r"(sb + H_B), "n"(TAB_BYTES + 8 * VEC_BYTES) : "memory");
            asm volatile("red.release.gpu.global.add.u32 [%0], 1;" ::"l"(&g_cnt.tab[0]) : "memory");
        }
        __syncwarp();
#pragma unroll 1
        for (int i = wg; i < 20; i += 4) {
            const int r = i / 5, b = i - 5 * r, un = 5 * hs + b, u3 = 20 * r + un;
            auto refill = [&](int e, int u, uint32_t fb) {
                mbar_expect(fb, 40960);
                tma_ld2(sb + e * 40960, &mp.w3h, 64 * (u >> 1), 320 * (u & 1), fb);
                tma_ld2(sb + e * 40960 + 20480, &mp.w3h, 64 * (u >> 1), 320 * (u & 1) + 160, fb);
            };
            if (i > 4 && i < 9) {
                bar_sync(1, 512);
                if (warp == 0) {
                    signal_cnt(&g_cnt.uv[0], lane, 1);
                    if (elect()) {
#pragma unroll 1
                        for (int e = 0; e < 5; e++) refill(e, 5 * hs + e, bars + (5 + e) * 8);
                        l2_prefetch(pp.w2 + (size_t)160 * hs * D_, 160 * D_ * 2);
                    }
                    __syncwarp();
                }
            }
            mbar_wait(bars + i * 8, 0);
            float d[4];
            gemv_tile<7>(d, sb + b * 40960, sb + H_B, 5 * (un & 1));
            const int col = 16 * (warp & 3) + g;
            float* dst = r ? g_cs3 + (un & 1) * 1920 + 64 * ((u3 >> 1) - 10) + col : g_uv + (un & 1) * 3 * D_ + 2 * D_ + 64 * (un >> 1) + col;
            if (t == 3) { dst[0] = d[0]; dst[8] = d[2]; }
            if (r == 0 && t == 2) { dst[-2 * D_] = d[0]; dst[8 - 2 * D_] = d[2]; dst[-D_] = d[1]; dst[8 - D_] = d[3]; }
            if (r == 1 || r == 2) {
                bar_sync(4 + wg, 128);
                if (wt == 0) refill(b, u3, bars + (i + 5) * 8);
            }
        }
        __syncthreads();
        if (warp == 0) signal_cnt(&g_cnt.cs[0], lane, 1);
        if (tid == 511) l2_prefetch(pp.w4 + (size_t)432 * hs * D_, 432 * D_ * 2);
        return;
    }

    if (warp == 15) {
        if (elect()) {
            mbar_init(bars + B_IN * 8, 1);
            asm volatile("fence.mbarrier_init.release.cluster;" ::: "memory");
            mbar_expect(bars + B_IN * 8, 131 * 160);
            tma_ld2(sb + OFF_KIN, &mp.k, 80 * (id & 7), 64 * (id >> 3) - 3, bars + B_IN * 8);
            tma_ld2(sb + OFF_VIN, &mp.v, 80 * (id & 7), 64 * (id >> 3), bars + B_IN * 8);
        }
    } else {
        init_barriers(bars, warp);
    }
    const int pr = id >> 1;
    const int grp = pr < 4 ? 15 : pr < 36 ? (pr - 4) & 7 : 8 + (pr - 36) % 7;
    const int j = 2 * (pr < 4 ? pr : pr < 36 ? (pr - 4) >> 3 : (pr - 36) / 7) + (id & 1);

    if (wg == 3) {
        TIDS
        const int sw = warp - 12;
        const uint32_t ep = *(volatile unsigned*)&g_epoch + 1;
        __syncthreads();
        asm volatile("barrier.cluster.arrive.relaxed.aligned;" ::: "memory");
        if (sw == 0) {
            wait_clock(c0, T_KVB);
            if (elect()) {
                mbar_expect(bars + (B_IN + 1) * 8, 131 * 160);
                tma_ld2(sb + OFF_KIN + 10752, &mp.k, 80 * (id & 7), 64 * (id >> 3) + 1021, bars + (B_IN + 1) * 8);
                tma_ld2(sb + OFF_VIN + 10240, &mp.v, 80 * (id & 7), 64 * (id >> 3) + 1024, bars + (B_IN + 1) * 8);
            }
#pragma unroll 1
            for (int n = 0; n < PF_N; n++) {
                wait_clock(c0, PF_T0 + PF_DT * n);
                if (elect()) {
                    if (n < 8) l2_prefetch((const char*)(n < 4 ? pp.ssm_k : pp.q) + (size_t)id * 20480 + (n & 3) * 5120, 5120);
                    else l2_prefetch((const char*)pp.w_mod + (size_t)id * 38400 + (n - 8) * 4800, 4800);
                }
            }
        } else if (sw == 1) {
            wait_clock(c0, T_SSM);
            if (elect()) {
                mbar_expect(bars + B_SSM * 8, 20480);
                bulk_ld(sb + OFF_SSM, pp.ssm_k + (size_t)5 * id * S_, 20480, bars + B_SSM * 8);
            }
            mbar_wait(bars + B_KVS * 8, 0);
            signal_cnt(&g_cnt.kv[(id & 7) * 32], lane, 1, true);
            TS(lane == 0, 2)
            mbar_wait(bars + B_RAW * 8, 0);
            if (elect()) {
                mbar_expect(bars + B_QIN * 8, 20480);
                tma_ld3(sb + OFF_QIN, &mp.q, 0, 16 * id, 0, bars + B_QIN * 8);
                mbar_expect(bars + B_WM * 8, 40960);
            }
            mbar_wait(bars + B_BK * 8, 0);
            mbar_wait(bars + B_QIN * 8, 0);
            if (id < 120 && elect()) {
                tma_ld2(sb + OFF_WM, &mp.wmod, 64 * pr, 320 * (id & 1), bars + B_WM * 8);
                tma_ld2(sb + OFF_WM + 20480, &mp.wmod, 64 * pr, 320 * (id & 1) + 160, bars + B_WM * 8);
            }
            TS(lane == 0, 57)
        } else if (sw == 2) {
            if (elect()) {
#pragma unroll 1
                for (int i = 2; i < (int)(sizeof(Maps) / sizeof(CUtensorMap)); i++) asm volatile("prefetch.tensormap [%0];" ::"l"(&mp.k + i) : "memory");
            }
            wait_cnt(&g_cnt.kv[(id >> 4) * 32], 16, POLL_NS);
            TS(lane == 0, 4)
            if (elect()) {
                mbar_expect(bars + B_RAW * 8, 20480);
#pragma unroll
                for (int c = 0; c < 5; c++) bulk_ld(sb + OFF_CH + c * CH_BYTES, g_kvT + (size_t)(5 * id + c) * S_, 4096, bars + B_RAW * 8);
            }
        } else {
            if (lane == 0) sts32(sb + M_EP, ep);
#pragma unroll 1
            for (int m = lane; m < 40; m += 32) {
                const uint4 c = ldg128(pp.c + 320 * (id & 1) + 8 * m);
                uint32_t w[4] = {c.x, c.y, c.z, c.w};
#pragma unroll
                for (int i = 0; i < 4; i++) { const float a = blo(w[i]), b = bhi(w[i]); w[i] = pack2(__fdividef(a, 1.f + __expf(-a)), __fdividef(b, 1.f + __expf(-b))); }
                sts128(sb + OFF_Z + m * 128, w[0], w[1], w[2], w[3]);
#pragma unroll 1
                for (int r = 1; r < 8; r++) sts128(sb + OFF_Z + m * 128 + r * 16, 0, 0, 0, 0);
            }
            fence_async_smem();
        }
        {
            mbar_wait(bars + B_QIN * 8, 0);
            TS(wt == 0, 54)
            const int tk = 8 * ((lane >> 1) & 1) + 2 * (lane >> 3) + (lane & 1), ck = 4 * (sw & 1) + ((lane >> 1) & 2);
            const uint32_t src = sb + OFF_QIN + (sw >> 1) * 2048 + tk * 128;
            bf16* dst = g_qT + (size_t)id * 16 * D_ + (32 * sw + 8 * (t & 2) + g) * 16 + 8 * (t & 1);
#pragma unroll
            for (int i = 0; i < 5; i++) {
                uint32_t r[8];
                ldsm4t(src + i * 4096 + ((ck ^ (tk & 7)) << 4), r[0], r[1], r[2], r[3]);
                ldsm4t(src + i * 4096 + (((ck + 1) ^ (tk & 7)) << 4), r[4], r[5], r[6], r[7]);
                stg128(dst + i * 2048, tag(r[0], ep), r[1], r[2], r[3]);
                stg128(dst + i * 2048 + 128, tag(r[4], ep), r[5], r[6], r[7]);
            }
            float s1 = 0.f, s2 = 0.f;
#pragma unroll 2
            for (int i = 0; i < 10; i++) {
                const uint4 w4 = lds128(sb + OFF_QIN + i * 2048 + wt * 16);
                const uint32_t w[4] = {w4.x, w4.y, w4.z, w4.w};
#pragma unroll
                for (int e = 0; e < 4; e++) { const float a = blo(w[e]), b = bhi(w[e]); s1 += a + b; s2 = fmaf(a, a, fmaf(b, b, s2)); }
            }
#pragma unroll
            for (int o = 1; o < 8; o *= 2) { s1 += __shfl_xor_sync(~0u, s1, o); s2 += __shfl_xor_sync(~0u, s2, o); }
            s1 *= 1.f / D_;
            uint32_t rs = pack2(rsqrtf(fmaxf(s2 * (1.f / D_) - s1 * s1, 0.f) + 1e-5f), 0.f);
            if (lane < 8) rs = tag(rs, ep);
            rs = pack2(blo(rs), -s1 * blo(rs));
            const uint32_t sel = lane ? 0x7632 : 0x5410;
            const uint32_t a0 = __shfl_sync(~0u, rs, 0), a1 = __shfl_sync(~0u, rs, 8), a2 = __shfl_sync(~0u, rs, 16), a3 = __shfl_sync(~0u, rs, 24);
            if (lane < 2) stg64(g_qst + lane * S_ + 16 * id + 4 * sw, tag(__byte_perm(a0, a1, sel), ep), __byte_perm(a2, a3, sel));
            TS(wt == 0, 55)
        }
        bar_sync(6, 128);
        if (sw == 3) {
            signal_cnt(&g_cnt.q[(lane & 3) * 32], lane, 4, true);
            TS(lane == 0, 3)
        }
        if (id < 120) {
            mbar_wait(bars + B_WM * 8, 0);
            TS(wt == 0, 56)
            float d[4];
            gemv_tile<8>(d, sb + OFF_WM, sb + OFF_Z, 0);
            const float d2 = __shfl_up_sync(~0u, d[2], 1);
            TS(wt == 0, 7)
            if (t < 2) asm volatile("{\n.reg .b64 v;\nmov.b64 v, {%1, %2};\nst.relaxed.gpu.global.b64 [%0], v;\n}" ::"l"(g_mod + (id & 1) * 6 * D_ + 64 * pr + 16 * sw + g + 8 * t),
                                    "r"(__float_as_uint(t ? d2 : d[0])), "r"(ep) : "memory");
        }
        bar_sync(6, 128);
        asm volatile("setmaxnreg.dec.sync.aligned.u32 32;");
        asm volatile("barrier.cluster.wait.aligned;" ::: "memory");
        if (sw == 2) {
            wait_cnt(&g_cnt.tab[0], 1);
            if (elect()) {
                mbar_expect(bars + B_TAB * 8, TAB_BYTES / 2 + VEC_BYTES);
                bulk_ld(sb + OFF_TAB, g_tab + (j & 1) * (TAB_BYTES / 32), TAB_BYTES / 2, bars + B_TAB * 8);
                bulk_ld(sb + M_GB, g_tab + (TAB_BYTES + j * VEC_BYTES) / 16, VEC_BYTES, bars + B_TAB * 8);
            }
            TS(lane == 0, 5)
            int n = 0;
            auto xslot = [&](int w, int m) {
                mbar_spin(bars + (B_XEMPTY + (n & 7)) * 8, ((n >> 3) & 1) ^ 1);
                return bars + (B_XFULL + (m & 7) + 8 * w) * 8;
            };
#pragma unroll 1
            for (int e = 0; e < 4; e++) {
                const int w = e & 1, tile = grp + 16 * w;
                if (e < 2) wait_cnt(&g_cnt.x[(4 * w + (id & 3)) * 32], 128);
                else wait_cnt(&g_cnt.g1[min(max(tile + min(lane, 2) - 1, 0), 31) * 32], 8);
                TS(lane == 0, 26 + e)
                if (e == 0) mbar_wait(bars + (B_XS + 1) * 8, 0);
#pragma unroll 1
                for (int kb = 0; kb < 10; kb++, n++) {
                    const uint32_t fb = xslot(w, 5 * (e & 2) + kb);
                    TR2(lane == 0, 20 + 10 * e + kb)
                    if (elect()) {
                        mbar_expect(fb, 8192);
                        tma_ld2(sb + OFF_XR + (n & 7) * 8192, e < 2 ? &mp.x1_ld : &mp.t_ld, 64 * (e < 2 ? tile : kb), 64 * (e < 2 ? g1_block(kb, j) : tile), fb);
                    }
                }
            }
#pragma unroll 1
            for (int i = 0; i < 20; i++, n++) {
                const int w = i < XLEAD ? 0 : i >= 20 - XLEAD ? 1 : ((i - XLEAD) & 1) ^ 1;
                const int kb = i < XLEAD ? i : i >= 20 - XLEAD ? i - 10 : w ? (i - XLEAD) >> 1 : (i + XLEAD) >> 1;
                if (kb == 0) { wait_cnt(&g_cnt.g2[(grp + 16 * w) * 32], 8); TS(lane == 0, 30 + w) }
                const uint32_t fb = xslot(w, 20 + kb);
                if (elect()) {
                    mbar_expect(fb, 8192);
                    bulk_ld(sb + OFF_XR + (n & 7) * 8192, &g_x2f[((grp + 16 * w) * 10 + kb) * 512], 8192, fb);
                }
            }
            mbar_wait(bars + B_VEC3 * 8, 0);
            unsigned old = 0;
            if (lane == 0) old = atomicAdd(&g_cnt.done[0], 1u);
            if (__shfl_sync(~0u, old, 0) == 127) {
#pragma unroll 1
                for (int i = lane; i < (int)(sizeof(Counters) / 128); i += 32) reinterpret_cast<unsigned*>(&g_cnt)[i * 32] = 0;
                if (lane == 0) atomicAdd(&g_epoch, 1u);
            }
        } else if (sw == 0) {
            wait_cnt(&g_cnt.wr[0], 4);
            mbar_wait(bars + B_QRDY * 8, 0);
            const uint32_t wf = bars + B_WFULL * 8, we = bars + B_WEMPTY * 8;
#pragma unroll 1
            for (int n = 0; n < 10; n++) {
                if (n == 3) mbar_wait(bars + (B_XS + 1) * 8, 0);
                if (n == 3) mbar_wait(bars + (B_PUB + 1) * 8, 0);
                if (n >= 5) mbar_spin(we + (n - 5) * 8, 0);
                TR2(lane == 0, 70 + n)
                if (elect()) {
                    const uint32_t fb = wf + (n & 7) * 8, dst = sb + OFF_W + (n & 7) * 16384;
                    mbar_expect(fb, 20480);
                    if (n >= 5) {
                        tma_ld5(dst, n < 9 ? &mp.w2a : &mp.w2b, 64 * j, n < 9 ? 4 * (n - 5) : 0, fb);
                        bulk_ld(sb + OFF_REM + (n - 5) * 4096, &g_wr[((8 + j) * 10 + 2 * (n - 5)) * 128], 4096, fb);
                    } else {
#pragma unroll 1
                        for (int h = 0; h < 2; h++) {
                            const int kb = g1_block(2 * n + h, j);
                            tma_ld2(dst + h * 8192, &mp.w1, 64 * j, 64 * kb, fb);
                            bulk_ld(sb + OFF_REM + n * 4096 + h * 2048, &g_wr[(j * 10 + kb) * 128], 2048, fb);
                        }
                    }
                }
            }
#pragma unroll 1
            for (int n = 10; n < 30; n++) {
                if (n == 10) mbar_wait(bars + (B_PUB + 3) * 8, 0);
                if (n == GATE16) mbar_wait(bars + (B_PUB + 5) * 8, 0);
                mbar_spin(we + (n & 7) * 8, ((n >> 3) & 1) ^ 1);
                TR2(lane == 0, 70 + n)
                if (elect()) {
                    const uint32_t dst = sb + OFF_W + (n & 7) * 16384, fb = wf + (n & 7) * 8;
                    mbar_expect(fb, 13824);
                    tma_ld3(dst, &mp.w3a, 0, 32 * (n - 10), 3 * j, fb);
                    tma_ld2(dst + 12288, &mp.w3b, 1536 + 24 * j, 32 * (n - 10), fb);
                }
            }
            mbar_spin(we + 6 * 8, 0);
            if (elect()) mbar_arrive(bars + B_S30 * 8);
#pragma unroll 1
            for (int n = 31; n < 50; n++) {
                const int rem = 96 + 3 * (j >> 1);
                int m0, m1, r0, r1, c0_, c1_;
                if (n < 38) {
                    c0_ = g4_block(0, j); c1_ = g4_block(1, j);
                    m0 = m1 = n == 35;
                    r0 = r1 = n == 35 ? rem : 6 * (j ^ (n >= 34)) + ((0x2004204 >> (4 * (n - 31))) & 15);
                } else {
                    const int e = (n - 38) & 3;
                    c0_ = c1_ = g4_block(2 + ((n - 38) >> 2), j);
                    m0 = 0; m1 = e == 1 ? 1 : e == 3 ? -1 : 0;
                    r0 = 6 * (j ^ (e >> 1)) + 4 * (e & 1); r1 = e == 1 ? rem : r0 + 2;
                }
                mbar_spin(we + (n & 7) * 8, ((n >> 3) & 1) ^ 1);
                if (elect()) {
                    const uint32_t dst = sb + OFF_W + (n & 7) * 16384, fb = wf + (n & 7) * 8;
                    mbar_expect(fb, m1 < 0 ? 8192 : 16384 - 2048 * (m0 + m1));
                    tma_ld2(dst, &mp.w4[m0], 64 * c0_, r0 * (32 >> m0), fb);
                    if (m1 >= 0) tma_ld2(dst + 8192, &mp.w4[m1], 64 * c1_, r1 * (32 >> m1), fb);
                }
            }
#pragma unroll 1
            for (int w = 0; w < 2; w++) {
                const uint4* src = g_part + (size_t)(grp + 16 * w) * 40960;
                mbar_spin(bars + (B_RING + w) * 8, 1);
                if (elect()) {
                    const uint32_t fb = bars + (B_IN + w) * 8, rem = sb + OFF_OUT + w * 10240;
                    mbar_expect(fb, 10240);
                    bulk_ld(rem + 8192, &g_x1f[((grp + 16 * w) * 8 + j) * 640 + 512], 2048, fb);
#pragma unroll 1
                    for (int i = 0; i < 4; i++) bulk_ld(rem + i * 2048, src + ((j >> 2) + 2 * i) * 5120 + 4096 + j * 128, 2048, fb);
                }
            }
        } else {
            const int w = sw >> 1;
#pragma unroll 1
            for (int e = 0; e < 3; e++) {
                mbar_wait(bars + ((e ? B_SIG : B_XS) + w) * 8, e >> 1);
                signal_cnt(e == 0 ? &g_cnt.x[(4 * w + (lane & 3)) * 32] : e == 1 ? &g_cnt.g1[(grp + 16 * w) * 32] : &g_cnt.g2[(grp + 16 * w) * 32], lane, e ? 1 : 4, X_NOFENCE & (4 << e));
                if (elect()) mbar_arrive(bars + (B_PUB + 2 * e + w) * 8);
                TS(lane == 0, 20 + 2 * e + w)
                if (e == 0 && w) {
                    wait_cnt(&g_cnt.uv[0], 4);
#pragma unroll 1
                    for (int c = lane; c < 80; c += 32) {
                        const float* src = g_uv + (c < 64 ? 64 * j + c : 448 + 16 * j + c);
                        const uint32_t u = split2(ldcg32f(src) + ldcg32f(src + 3 * D_)), v = split2(ldcg32f(src + D_) + ldcg32f(src + 4 * D_));
                        const uint32_t s = split2(ldcg32f(src + 2 * D_) + ldcg32f(src + 5 * D_));
                        sts128(sb + OFF_F1 + c * 16, u, __byte_perm(u, v, 0x5410), __byte_perm(v, 0, 0x1032), s);
                        sts128(sb + M_F1 + c * 16, s & 0xffffu, 0, 0, 0);
                    }
                    fence_async_smem();
                    warp_arrive(bars + B_VEC * 8);
                    TS(lane == 0, 9)
                }
            }
        }
        return;
    }

    {
        uint32_t ep;
        {
            TIDS
            ep = *(volatile unsigned*)&g_epoch + 1;
            const int cp = (tid + 16) % 40, cp1 = tid % 40;
            const uint4 sh0 = ldg128(pp.shift_k + (80 * (id & 7) + 2 * cp1) * 4), sh1 = ldg128(pp.shift_k + (80 * (id & 7) + 2 * cp) * 4);
            const float dd = __bfloat162float(pp.ssm_D[5 * id + min(wg + 3 * lane, 4)]);
            __syncthreads();
            asm volatile("barrier.cluster.arrive.relaxed.aligned;" ::: "memory");
#pragma unroll 1
            for (int hw = 0; hw < 2; hw++) {
                if ((unsigned)(warp - 2 * hw) >= 10) continue;
                const int u = tid - 64 * hw;
                const int c = hw ? cp : cp1, oc = u / 40, line = 31 - 16 * hw - (id >> 3);
                const uint4 sh = hw ? sh1 : sh0;
                const uint32_t st = sb + OFF_ST + hw * 10240, sta = st + c * 256 + ((((6 - 2 * (oc & 3)) ^ (oc >> 2) ^ (line & 1)) ^ (c & 7)) << 4), in = oc * 1280 + c * 4;
                const uint32_t f0 = __byte_perm(sh.x, sh.z, 0x5410), f1 = __byte_perm(sh.x, sh.z, 0x7632), f2 = __byte_perm(sh.y, sh.w, 0x5410), f3 = __byte_perm(sh.y, sh.w, 0x7632);
                uint32_t kk[11], vv[8];
                mbar_spin(bars + (B_IN + hw) * 8, 0);
                TS(tid == 64, 18 + 42 * hw)
#pragma unroll
                for (int i = 0; i < 11; i++) kk[i] = lds32(sb + OFF_KIN + hw * 10752 + in + i * 160);
#pragma unroll
                for (int i = 0; i < 8; i++) vv[i] = lds32(sb + OFF_VIN + hw * 10240 + in + i * 160);
#pragma unroll
                for (int i = 0; i < 8; i++) vv[i] = mul2(fma2(kk[i + 3], f0, fma2(kk[i + 2], f1, fma2(kk[i + 1], f2, mul2(kk[i], f3)))), vv[i]);
                sts128(sta, tag(__byte_perm(vv[0], vv[1], 0x5410), ep), __byte_perm(vv[2], vv[3], 0x5410), __byte_perm(vv[4], vv[5], 0x5410), __byte_perm(vv[6], vv[7], 0x5410));
                sts128(sta + 128, tag(__byte_perm(vv[0], vv[1], 0x7632), ep), __byte_perm(vv[2], vv[3], 0x7632), __byte_perm(vv[4], vv[5], 0x7632), __byte_perm(vv[6], vv[7], 0x7632));
                bar_sync(7 + hw, 320);
                flush_tile(st, g_kvT + (size_t)(80 * (id & 7)) * S_ + 64 * line, u);
                warp_arrive(bars + B_KVS * 8);
                TS(tid == 64 && hw, 1)
            }
            if (tid < 320) sts128(sb + OFF_CH + (tid >> 6) * CH_BYTES + 4096 + (tid & 63) * 16, 0, 0, 0, 0);
            mbar_spin(bars + B_SSM * 8, 0);
            TS(tid == 0, 14)
            uint2 w[7];
            uint32_t pv[7];
#pragma unroll
            for (int i = 0; i < 7; i++) {
                const uint32_t a = sb + OFF_SSM + min(wg + 3 * i, 19) * 1024 + wt * 8;
                w[i] = lds64(a); pv[i] = lds32(a - 4);
            }
#pragma unroll
            for (int i = 0; i < 7; i++) {
                const int un = min(wg + 3 * i, 19);
                sts128(sb + OFF_CH + (un >> 2) * CH_BYTES + OFF_P + (un & 3) * 2048 + wt * 16, __byte_perm(w[i].x, pv[i], 0x7610), __byte_perm(w[i].x, 0, 0x1032), __byte_perm(w[i].y, w[i].x, 0x7610), __byte_perm(w[i].y, 0, 0x1032));
            }
            __syncwarp();
            if (wt < 2 - (wg >> 1)) {
                const uint32_t h = lds32(sb + OFF_SSM + (wg + 3 * wt) * 4096), h0 = pack2(blo(h) + dd, 0.f);
                sts64f(sb + OFF_CH + (wg + 3 * wt) * CH_BYTES + OFF_P, __uint_as_float(h0), __uint_as_float(__byte_perm(h, h0, 0x5432)));
            }
            fence_async_smem();
            warp_arrive(bars + B_BK * 8);
            asm volatile("barrier.cluster.wait.aligned;" ::: "memory");
            mbar_spin(bars + B_BK * 8, 0);
            TS(tid == 0, 15)
        }

        mbar_spin(bars + B_RAW * 8, 0);
#pragma unroll 1
        for (int c = wg; c < 5; c += 3) {
            const uint32_t kvb = sb + OFF_CH + c * CH_BYTES;
            for (uint32_t it = 0;; it++) {
                const int wt = tid_now() & 127;
                if (!bar_any(1 + wg, ((lds32(kvb + wt * 16) ^ ep) | (lds32(kvb + 2048 + wt * 16) ^ ep)) & 1)) break;
                if (wt == 0) { mbar_expect(bars + (B_RETRY + wg) * 8, 4096); bulk_ld(kvb, g_kvT + (size_t)(5 * id + c) * S_, 4096, bars + (B_RETRY + wg) * 8); }
                mbar_wait(bars + (B_RETRY + wg) * 8, ep >> 31);
                ep ^= 0x80000000u;
                STALE(0)
                if (it > 4096) SPIN_FAIL(57)
            }
            TS(threadIdx.x == 0, c ? 13 : 11)
            float acc[64];
            {
                const int l = tid_now() & 31;
                conv_channel(acc, kvb + OFF_P + (8 * (warp & 3) + (l >> 2) - 2 * (l & 3)) * 4, (((uint64_t)0xC0000010u << 32) | ((kvb & 0x3FFFF) >> 4) | 0x10000u) + pp.nil);
            }
            TS(threadIdx.x == 0, c ? 16 : 12)
            TS(threadIdx.x == 256, 53)
            if (c >= 3) {
#pragma unroll 1
                for (int e = 0; e < 3; e++) mbar_spin(bars + (B_RING + e) * 8, 0);
            }
            TIDS
            const int e = 127 - 8 * (lane >> 4) - (lane & 7), u0 = (warp & 3) + 8 * (e >> 2) + (e & 3) + 4 * ((lane >> 3) & 1);
            const uint32_t ring = sb + OFF_RING + c * 16384 + (warp & 3) * 4096, wa = ring + (u0 ^ ((u0 >> 1) & 4)) * 16;
            if (lane < (warp & 3)) sts128(ring + lane * 16, 0, 0, 0, 0);
#pragma unroll
            for (int i = 0; i < 8; i++)
                stsm4t(i == 0 && u0 >= 256 ? sb + M_NUL : wa - 512 * i, pack2(acc[8 * i], acc[8 * i + 1]), pack2(acc[8 * i + 2], acc[8 * i + 3]),
                       pack2(acc[8 * i + 4], acc[8 * i + 5]), pack2(acc[8 * i + 6], acc[8 * i + 7]));
            fence_async_smem();
            warp_arrive(bars + (B_RING + c) * 8);
        }
        TIDS
        if (warp == 8) {
            wait_cnt(&g_cnt.q[(id & 3) * 32], 128);
            if (elect()) {
                mbar_expect(bars + B_QRDY * 8, 28672);
                tma_ld2(sb + OFF_QT, &mp.qT, 80 * id, 0, bars + B_QRDY * 8);
                bulk_ld(sb + OFF_QT + 20480, g_qst, 8192, bars + B_QRDY * 8);
            }
            TS(lane == 0, 8)
        } else if (warp == 9) {
            const int v = min(lane / 5, 3);
            const uint2* gm = g_mod + (v + (v == 3)) * D_ + 5 * id + lane % 5;
            const unsigned epoch = lds32(sb + M_EP);
            uint2 r0, r1;
            unsigned it = 0;
            do {
                r0 = ld_mod(gm); r1 = ld_mod(gm + 6 * D_);
                if (++it > SPIN_LIMIT) SPIN_FAIL(55)
            } while (!__all_sync(~0u, r0.y == epoch && r1.y == epoch));
            const float m0 = __uint_as_float(r0.x), m1 = __uint_as_float(r1.x);
            const float m = rbf(m0 + m1), p = rbf(1.f + m);
            const float cz = zscale(__shfl_sync(~0u, p, 15 + lane % 5)), ga = __shfl_sync(~0u, m, 10 + lane % 5);
            if (lane < 15) sts32(sb + M_AB + lane % 5 * 16 + v * 4, lane < 10 ? __float_as_uint(cz * ga * (lane < 5 ? m : p)) : pack2(cz, cz));
            warp_arrive(bars + B_MODR * 8);
            TS(lane == 0, 6)
        }
        mbar_spin(bars + B_QRDY * 8, 0);
        mbar_spin(bars + B_MODR * 8, 0);
#pragma unroll 1
        for (int hf = 0; hf < 2; hf++) {
            const int u = wt + 128 * hf;
            uint4 rs = lds128(sb + OFF_QT + 20480 + u * 16), nm = lds128(sb + OFF_QT + 24576 + u * 16);
            uint32_t it = 0;
            while (__any_sync(~0u, ((rs.x ^ ep) | (rs.z ^ ep) | (nm.x ^ ep) | (nm.z ^ ep)) & 1)) {
                rs = ld_part(g_qst + 8 * u); nm = ld_part(g_qst + S_ + 8 * u);
                STALE(1)
                if (++it > SPIN_LIMIT) SPIN_FAIL(53)
            }
            const int c1 = wg == 2 ? 2 + !EPI_SPLIT : 5;
#pragma unroll 1
            for (int c = wg == 2 ? 0 : EPI_SPLIT && wg == hf ? 2 : 3 + wg; c < c1; c += wg == 2 ? 1 : c == 2 ? 1 + wg : 2) {
                uint4 q = lds128(sb + OFF_QT + (u >> 1) * 160 + c * 32 + (u & 1) * 16);
                const float4 ab = lds128f(sb + M_AB + c * 16);
                mbar_spin(bars + (B_RING + c) * 8, 0);
                const uint32_t ra = sb + OFF_RING + c * 16384 + (u ^ ((u >> 1) & 4)) * 16;
                const uint4 p0 = lds128(ra), p1 = lds128(ra + 4096), p2 = lds128(ra + 8192), p3 = lds128(ra + 12288);
                while (__any_sync(~0u, (q.x ^ ep) & 1)) {
                    q = ld_part(g_qT + ((u >> 1) * D_ + 5 * id + c) * 16 + 8 * (u & 1));
                    STALE(2)
                    if (++it > SPIN_LIMIT) SPIN_FAIL(52)
                }
                uint32_t gq[4] = {q.x, q.y, q.z, q.w}, gg[4] = {fma2(q.x, rs.x, nm.x), fma2(q.y, rs.y, nm.y), fma2(q.z, rs.z, nm.z), fma2(q.w, rs.w, nm.w)};
#pragma unroll
                for (int i = 0; i < 4; i++) {
                    gg[i] = pack2(fmaf(blo(gg[i]), ab.y, ab.x), fmaf(bhi(gg[i]), ab.y, ab.x));
                    gq[i] = mul2(gq[i], __float_as_uint(ab.z));
                }
                stg128(g_x1T + (size_t)(5 * id + c) * S_ + 8 * u,
                       fma2(gg[0], add2(add2(p0.x, p1.x), add2(p2.x, p3.x)), gq[0]), fma2(gg[1], add2(add2(p0.y, p1.y), add2(p2.y, p3.y)), gq[1]),
                       fma2(gg[2], add2(add2(p0.z, p1.z), add2(p2.z, p3.z)), gq[2]), fma2(gg[3], add2(add2(p0.w, p1.w), add2(p2.w, p3.w)), gq[3]));
            }
            warp_arrive(bars + (B_XS + hf) * 8);
            TS(tid == 0, hf ? 17 : 58)
            TS(tid == 256 && hf, 52)
        }
    }

    const uint32_t nil = pp.nil;
    const int wq = warp & 3;
    if (wg == 2) {
        TIDS
        const uint32_t lrow = sb + OFF_XR + ((lane & 7) + 8 * (lane >> 4)) * 128 + (((2 * wq + ((lane >> 3) & 1)) ^ (lane & 7)) << 4);
        const uint32_t nr = ((j ^ (j >> 2)) & 1) ? 9 : 4;
        mbar_wait(bars + B_TAB * 8, 0);
        float4 k = lds128f(sb + M_KS);
        float k4 = __uint_as_float(lds32(sb + M_KS + 16));
#pragma unroll
        for (int w = 1; w < 5; w++) {
            const float4 o = lds128f(sb + M_KS + w * 32);
            k.x += o.x; k.y += o.y; k.z += o.z; k.w += o.w; k4 += __uint_as_float(lds32(sb + M_KS + w * 32 + 16));
        }
#pragma unroll 1
        for (int uw = 0; uw < 2; uw++) {
            const int tile = grp + 16 * uw;
            float sl[4], sq[4];
            uint32_t z[16], zz[16];
            zero(sl); zero(sq);
#pragma unroll 1
            for (int i = 0; i < 5; i++) {
                const uint32_t xs = (2 * uw + i) & 7;
                const uint64_t tb = (((uint64_t)8 << 32) | ((dsb + OFF_TAB) >> 4) | (7u << 16)) + pp.nil + i * 56;
                mbar_spin(bars + (B_XFULL + 8 * uw + i) * 8, 0);
                wg_wait<0>();
#pragma unroll
                for (int q = 0; q < 4; q++) ldsm4t(lrow + xs * 8192 + q * 2048, z[4 * q], z[4 * q + 1], z[4 * q + 2], z[4 * q + 3]);
                if (lane == 0 && i != nr) mbar_arrive_after(bars + (B_XEMPTY + xs) * 8, z[0] | z[4], z[8] | z[12], nil);
#pragma unroll
                for (int e = 0; e < 16; e++) zz[e] = mul2(z[e], z[e]);
                wg_fence();
#pragma unroll
                for (int q = 0; q < 4; q++) wgmma_rs8(sl, z[4 * q], z[4 * q + 1], z[4 * q + 2], z[4 * q + 3], tb + q * 14, 1);
#pragma unroll
                for (int q = 0; q < 4; q++) wgmma_rs8(sq, zz[4 * q], zz[4 * q + 1], zz[4 * q + 2], zz[4 * q + 3], tb + q * 14, 1);
                wg_commit();
                if (i == (j >> 1)) {
#pragma unroll
                    for (int q = 0; q < 4; q++) stg128(&g_x1f[(tile * 8 + j) * 640 + q * 128 + wt], z[4 * q], z[4 * q + 1], z[4 * q + 2], z[4 * q + 3]);
                }
            }
            wg_wait<0>();
            reg_fence(sl); reg_fence(sq);
            TS(wt == 0 && !uw, 59)
            float v[4];
#pragma unroll
            for (int h = 0; h < 2; h++) {
                v[2 * h] = t == 0 ? sl[2 * h] + sl[2 * h + 1] : t == 1 ? sq[2 * h] + sq[2 * h + 1] : sl[2 * h];
                v[2 * h + 1] = t == 2 ? sl[2 * h + 1] : sq[2 * h];
            }
            const uint32_t rows = sb + OFF_ROW + uw * 2048;
            st_peer(peer_addr(rows + wt * 16), __float_as_uint(v[0]), __float_as_uint(v[1]), __float_as_uint(v[2]), __float_as_uint(v[3]), peer_addr(bars + (B_SUMS + uw) * 8));
            mbar_wait(bars + (B_SUMS + uw) * 8, 0);
            const float4 o = lds128f(rows + wt * 16);
            const int l0 = lane & ~3;
            const bool hi = t >= 2;
            float w[8];
#pragma unroll
            for (int e = 0; e < 4; e++) {
                const float a0 = __shfl_sync(~0u, v[0] + o.x, l0 + e), a1 = __shfl_sync(~0u, v[2] + o.z, l0 + e);
                w[e] = hi ? a1 : a0;
                if (e >= 2) { const float b0 = __shfl_sync(~0u, v[1] + o.y, l0 + e), b1 = __shfl_sync(~0u, v[3] + o.w, l0 + e); w[4 + e] = hi ? b1 : b0; }
            }
            const float s1 = w[0], s2 = w[1], scc = w[2], scs = w[6], sc = w[3], sqq = w[7];
            const float m1 = s1 * (1.f / D_), va = fmaxf(s2 * (1.f / D_) - m1 * m1, 0.f) + 1e-5f, r = rsqrtf(va);
            const float m2 = (r * (sc - m1 * k.x) + k.y) * (1.f / D_);
            const float e2 = (r * (r * (sqq + m1 * (m1 * k.z - 2.f * scc)) + 2.f * (scs - m1 * k.w)) + k4) * (1.f / D_);
            const float r2 = 0.5f * rsqrtf(fmaxf(e2 - m2 * m2, 0.f) + 1e-5f);
            const uint32_t fa = split2(-m1), fb = split2(va * r), fc = split2(-m2 * va * r);
            const uint32_t ca = rows + (16 * wq + g + 8 * hi) * 32;
            if (t & 1) sts128(ca + 16, fc >> 16, __float_as_uint(r * r2), __float_as_uint(r), __float_as_uint(-m1 * r));
            else sts128(ca, __byte_perm(fa, 0, 0x1010), __byte_perm(fa, fb, 0x5432), fb, __byte_perm(fc, 0, 0x1010));
            warp_arrive(bars + (B_COEF + uw) * 8);
            {
                uint32_t r0, r1, r2, r3;
                const uint32_t xs = (2 * uw + nr) & 7;
                mbar_spin(bars + (B_XFULL + 8 * uw + (nr & 7)) * 8, nr >> 3);
                ldsm4t(lrow + xs * 8192 + (j & 3) * 2048, r0, r1, r2, r3);
                stg128(&g_x1f[(tile * 8 + j) * 640 + 512 + wt], r0, r1, r2, r3);
                if (lane == 0) mbar_arrive_after(bars + (B_XEMPTY + xs) * 8, r0, 0, nil);
                warp_arrive(bars + (B_RES + uw) * 8);
            }
        }
        asm volatile("setmaxnreg.dec.sync.aligned.u32 32;");
        {
            wait_cnt(&g_cnt.cs[0], 4);
            uint32_t s[2];
#pragma unroll
            for (int i = 0; i < 2; i++) {
                const int c = min(wt + 128 * i, 215);
                const float* src = g_cs3 + (c < 192 ? 192 * j + c : 1344 + 24 * j + c);
                s[i] = split2(ldcg32f(src) + ldcg32f(src + 1920));
            }
            asm volatile("" : "+r"(s[0]), "+r"(s[1]));
            bar_sync(3, 128);
            if (wt == 0) mbar_arrive(bars + B_VEC3 * 8);
            TS(wt == 0, 19)
            mbar_wait(bars + B_S30 * 8, 0);
#pragma unroll
            for (int i = 0; i < 2; i++) sts128(sb + OFF_W + 6 * 16384 + min(wt + 128 * i, 215) * 16, s[i], s[i] & 0xffffu, 0, 0);
            fence_async_smem();
            bar_sync(3, 128);
            if (wt == 0) mbar_arrive(bars + (B_WFULL + 6) * 8);
        }
#pragma unroll 1
        for (int uw = 0; uw < 2; uw++) {
            const int tile = grp + 16 * uw;
            const uint32_t ep = lds32(sb + M_EP), in = sb + OFF_OUT + uw * 10240 + wt * 16, sr = in - lane * 16;
            mbar_wait(bars + (B_IN + uw) * 8, 1);
            float r[8];
#pragma unroll
            for (int h = 0; h < 2; h++) {
                uint4 a = lds128(in + h * 4096), b = lds128(in + h * 4096 + 2048);
                uint32_t it = 0;
                while (__any_sync(~0u, ((a.x ^ ep) | (b.x ^ ep)) & 1)) {
                    const uint4* p = g_part + (size_t)tile * 40960 + ((j >> 2) + 4 * h) * 5120 + 4096 + j * 128 + wt;
                    a = ld_part(p); b = ld_part(p + 10240);
                    STALE(3)
                    if (++it > SPIN_LIMIT) SPIN_FAIL(58)
                }
                if (h) add8(r, add2(a, b)); else unpack8(r, add2(a, b));
            }
            base16(r, lds128(in + 8192), lds64f(sb + M_GB + (64 + 2 * t) * 4), lds64f(sb + M_GB + (72 + 2 * t) * 4));
            __syncwarp();
            stsm4(sr + (lane & 15) * 32 + (((lane >> 4) ^ ((lane >> 2) & 1)) << 4), pack2(r[0], r[1]), pack2(r[2], r[3]), pack2(r[4], r[5]), pack2(r[6], r[7]));
            __syncwarp();
            stg128(out + (size_t)(64 * tile + 16 * wq + (lane >> 1)) * D_ + 512 + 16 * j + 8 * (lane & 1), lds128(sr + (lane >> 1) * 32 + (((lane & 1) ^ ((lane >> 3) & 1)) << 4)));
            __syncwarp();
        }
        if (wq == 0) {
#pragma unroll 1
            for (int w = 0; w < 2; w++) {
                uint32_t it = 0;
                while (!mbar_try(bars + (B_OWN + w) * 8, 0)) { if (++it > SPIN_LIMIT) SPIN_FAIL(56) }
            }
        }
        return;
    }

    TIDS
    const int uw = wg, tile = grp + 16 * uw, row0 = 64 * tile + 16 * wq;
    const bool leader = wt == 0; (void)leader;
    const uint32_t xfull = bars + (B_XFULL + 8 * uw) * 8, xempty = bars + B_XEMPTY * 8, wfull = bars + B_WFULL * 8, wempty = bars + B_WEMPTY * 8;
    const uint64_t dz = mkdesc(0) + pp.nil;
    auto xwait = [&](uint32_t n) { mbar_spin(xfull + (n & 7) * 8, (n >> 3) & 1); };
    {
        float acc[40];
        uint32_t res[20];
        const uint32_t two = (((j ^ (j >> 2)) & 1) ? 0x1E0u : 0x3E0u) << 1;
        {
            zero(acc);
            uint64_t bd = dz + b80_desc(dsb, 0, 0, 0);
            mbar_spin(wfull, 0);
            xwait(0);
            TS(leader, 32 + uw)
#pragma unroll 1
            for (int i = 0; i < 5; i++) {
                const uint32_t xs = (2 * uw + 2 * i) & 7;
                const uint64_t alo = dz + (((dsb + OFF_XR + xs * 8192) >> 4) | 0x10000u);
#pragma unroll
                for (int h = 0; h < 2; h++) {
                    const uint32_t nn = min(2 * i + h + 1, 9);
                    const bool ok = mbar_test(xfull + (nn & 7) * 8, nn >> 3), okw = !h || mbar_test(wfull + min(i + 1, 4) * 8, 0);
                    wg_fence();
#pragma unroll
                    for (int q = 0; q < 4; q++) wgmma_ss80t(acc, alo + h * 512 + q * 128, bd + q * B80_STEP, 1);
                    wg_commit();
                    bd = bd + (uint64_t)B80_HALF;
                    wg_wait<1>();
                    if (lane < ((two >> (2 * i + h)) & 1) + (h || i)) mbar_arrive(xempty + ((xs + h - 1) & 7) * 8);
                    if (!h && i && lane == 0) mbar_arrive(wempty + (i - 1) * 8);
                    if (!ok) xwait(nn);
                    if (!okw) mbar_spin(wfull + min(i + 1, 4) * 8, 0);
                    TR(leader, 100 + 10 * uw + 2 * i + h)
                }
            }
        }
        float al[2], r1[2], n1[2];
        {
            mbar_spin(bars + (B_COEF + uw) * 8, 0);
            TS(leader && !uw, 10)
            uint32_t fa[4];
#pragma unroll
            for (int h = 0; h < 2; h++) {
                const uint32_t ca = sb + OFF_ROW + uw * 2048 + (16 * wq + g + 8 * h) * 32;
                const float4 c4 = lds128f(ca + 16);
                fa[h] = lds32(ca + t * 4);
                fa[2 + h] = t ? 0 : __float_as_uint(c4.x);
                al[h] = c4.y; r1[h] = c4.z; n1[h] = c4.w;
            }
            mbar_spin(bars + B_VEC * 8, 0);
            wg_fence();
            wgmma_rs80k(acc, fa[0], fa[1], fa[2], fa[3], ((uint64_t)8 << 32) | ((dsb + OFF_F1) >> 4) | (((M_F1 - OFF_F1) >> 4) << 16), 1);
            wg_commit();
        }
        wg_wait<0>();
        reg_fence(acc);
        if (lane <= (two >> 10)) mbar_arrive(xempty + ((2 * uw + 9) & 7) * 8);
        if (lane == 0) mbar_arrive(wempty + 4 * 8);
        TS(leader, 34 + uw)
        {
            bf16* const trow = g_t + (size_t)(row0 + g + 2) * D_;
#pragma unroll
            for (int b = 0; b < 3; b++) {
                uint32_t p[8];
#pragma unroll
                for (int ii = 0; ii < 4; ii++) {
                    const int i = 4 * b + ii;
                    if (i >= 10) continue;
#pragma unroll
                    for (int h = 0; h < 2; h++) p[(i & 3) + 4 * h] = pack2(gelu2(acc[4 * i + 2 * h] * al[h]), gelu2(acc[4 * i + 2 * h + 1] * al[h]));
                }
                if (b < 2) {
                    const int gr = (2 * j + b) / 5, sh = (gr & 1) ? -1 - (gr >> 1) : 1 + (gr >> 1);
                    bf16* dst = trow + 64 * j + 32 * b + 8 * t;
                    stg128(dst + sh * D_, p[0], p[1], p[2], p[3]);
                    stg128(dst + (sh + 8) * D_, p[4], p[5], p[6], p[7]);
                    if (row0 + g < sh || row0 + g + 8 >= S_ + sh) stg128(dst + (sh > 0 ? 0 : 8) * D_, 0, 0, 0, 0);
                } else {
                    bf16* dst = trow + 512 + 16 * j + 4 * t;
                    stg64(dst - 2 * D_, p[0], p[1]);
                    stg64(dst + 6 * D_, p[4], p[5]);
                    if (row0 + g + 8 >= S_ - 2) stg64(dst + 8 * D_, 0, 0);
                }
            }
        }
        warp_arrive(bars + (B_SIG + uw) * 8);
        TS(leader, 36 + uw)
        mbar_spin(bars + (B_RES + uw) * 8, 0);
#pragma unroll
        for (int i = 0; i < 5; i++) {
            const uint4 v = ldcg128(&g_x1f[(tile * 8 + j) * 640 + i * 128 + wt]);
            res[4 * i] = v.x; res[4 * i + 1] = v.y; res[4 * i + 2] = v.z; res[4 * i + 3] = v.w;
        }
#pragma unroll
        for (int i = 0; i < 10; i++) {
            const float2 c = lds64f(sb + M_C + (8 * i + 2 * t) * 4), s = lds64f(sb + M_SB + (8 * i + 2 * t) * 4);
#pragma unroll
            for (int h = 0; h < 2; h++) {
                acc[4 * i + 2 * h] = fmaf(blo(res[2 * i + h]), r1[h], fmaf(n1[h], c.x, s.x));
                acc[4 * i + 2 * h + 1] = fmaf(bhi(res[2 * i + h]), r1[h], fmaf(n1[h], c.y, s.y));
            }
        }
        mbar_spin(wfull + 5 * 8, 0);
        xwait(10);
#pragma unroll 1
        for (int i = 0; i < 5; i++) {
            const uint32_t wn = 5 + i, xs = (4 + 2 * uw + 2 * i) & 7;
            const uint64_t alo = dz + (((dsb + OFF_XR + xs * 8192) >> 4) | 0x10000u), bd = dz + b80_desc(dsb, wn, i, 0);
#pragma unroll
            for (int h = 0; h < 2; h++) {
                const uint32_t nn = min(11 + 2 * i + h, 19), wx = min(wn + 1, 9u);
                const bool ok = mbar_test(xfull + (nn & 7) * 8, (nn >> 3) & 1), okw = !h || mbar_test(wfull + (wx & 7) * 8, wx >> 3);
                wg_fence();
#pragma unroll
                for (int q = 0; q < 4; q++) wgmma_ss80(acc, alo + h * 512 + q * 2, bd + h * B80_HALF + q * B80_STEP, 1);
                wg_commit();
                wg_wait<1>();
                if (lane < 2 && (h || i)) mbar_arrive(xempty + ((xs + h - 1) & 7) * 8);
                if (!h && i && lane == 0) mbar_arrive(wempty + ((wn - 1) & 7) * 8);
                if (!ok) xwait(nn);
                if (!okw) mbar_spin(wfull + (wx & 7) * 8, wx >> 3);
                TR(leader, (uw ? 86 : 20) + 2 * i + h)
            }
        }
        wg_wait<0>();
        reg_fence(acc);
        if (lane < 2) mbar_arrive(xempty + ((29 + 10 * uw) & 7) * 8);
        if (lane == 0) mbar_arrive(wempty + (9 & 7) * 8);
        TS(leader, 38 + uw)
        float a0 = 0.f, b0 = 0.f, a1 = 0.f, b1 = 0.f;
#pragma unroll
        for (int i = 0; i < 5; i++) {
            uint32_t p[4];
#pragma unroll
            for (int e = 0; e < 4; e++) p[e] = pack2(acc[8 * i + 2 * e], acc[8 * i + 2 * e + 1]);
            stg128(&g_x2f[(tile * 40 + (i < 4 ? 4 * j + i : 32 + j)) * 128 + wt], p[0], p[1], p[2], p[3]);
#pragma unroll
            for (int e = 0; e < 4; e += 2) {
                const float u0 = blo(p[e]), u1 = bhi(p[e]), v0 = blo(p[e + 1]), v1 = bhi(p[e + 1]);
                a0 += u0 + u1; b0 = fmaf(u0, u0, fmaf(u1, u1, b0));
                a1 += v0 + v1; b1 = fmaf(v0, v0, fmaf(v1, v1, b1));
            }
        }
#pragma unroll
        for (int o = 1; o < 4; o *= 2) {
            a0 += __shfl_xor_sync(~0u, a0, o); b0 += __shfl_xor_sync(~0u, b0, o);
            a1 += __shfl_xor_sync(~0u, a1, o); b1 += __shfl_xor_sync(~0u, b1, o);
        }
        if (t < 2) g_stats[(tile * 8 + j) * 64 + 16 * wq + g + 8 * t] = t ? make_float2(a1, b1) : make_float2(a0, b0);
        warp_arrive(bars + (B_SIG + uw) * 8);
        TS(leader, 40 + uw)
#pragma unroll
        for (int i = 0; i < 10; i++) {
            const float2 c = lds64f(sb + M_GB + (8 * i + 2 * t) * 4), e = lds64f(sb + M_CI + (8 * i + 2 * t) * 4);
#pragma unroll
            for (int h = 0; h < 2; h++)
                res[2 * i + h] = pack2(fmaf(c.x, rbf(acc[4 * i + 2 * h]), e.x * blo(res[2 * i + h])), fmaf(c.y, rbf(acc[4 * i + 2 * h + 1]), e.y * bhi(res[2 * i + h])));
        }
#pragma unroll
        for (int i = 0; i < 5; i++) stg128(&g_x1f[(tile * 8 + j) * 640 + i * 128 + wt], res[4 * i], res[4 * i + 1], res[4 * i + 2], res[4 * i + 3]);
        asm volatile("fence.proxy.async.global;" ::: "memory");
    }
    asm volatile("setmaxnreg.inc.sync.aligned.u32 224;");
    float acc0[64], acc1[44];
    float2 q[4];
    {
        uint4 f0, f1, f2, f3;
        auto xseq = [&](int kb) { return (uint32_t)(40 + (uw ? (kb < 10 - XLEAD ? XLEAD + 2 * kb : 10 + kb) : (kb < XLEAD ? kb : 2 * kb - XLEAD + 1))) & 7; };
        auto step = [&](const uint4& f, uint64_t bd) {
            wg_fence();
            wgmma_rs128(acc0, f.x, f.y, f.z, f.w, bd, 1);
            wgmma_rs88(acc1, f.x, f.y, f.z, f.w, bd + 512, 1);
            wg_commit();
        };
        const uint32_t xa = sb + OFF_XR + wt * 16;
        zero(acc0); zero(acc1);
        uint32_t xs = xseq(0);
        xwait(20);
        TS(leader, 42 + uw)
        f0 = lds128(xa + xs * 8192); f1 = lds128(xa + xs * 8192 + 2048);
#pragma unroll
        for (int i = 0; i < 4; i++) q[i] = ldcg64f(&g_stats[(tile * 8 + 2 * t + (i & 1)) * 64 + 16 * wq + g + 8 * (i >> 1)]);
        mbar_spin(wfull + (10 & 7) * 8, (10 >> 3) & 1);
#pragma unroll 1
        for (int kb = 0; kb < 10; kb++) {
            const uint32_t wn = 10 + 2 * kb;
            const uint64_t bd = dz + (((dsb + OFF_W + (wn & 7) * 16384) >> 4) | (256u << 16));
            step(f0, bd);
            wg_wait<1>();
            if (kb && lane == 0) mbar_arrive(wempty + ((wn - 1) & 7) * 8);
            f2 = lds128(xa + xs * 8192 + 4096); f3 = lds128(xa + xs * 8192 + 6144);
            const bool w1 = mbar_test(wfull + ((wn + 1) & 7) * 8, (wn >> 3) & 1), x1 = mbar_test(xfull + ((21 + kb) & 7) * 8, ((21 + kb) >> 3) & 1);
            step(f1, bd + 128);
            if (!w1) mbar_spin(wfull + ((wn + 1) & 7) * 8, (wn >> 3) & 1);
            step(f2, bd + 1024);
            if (lane < 2) mbar_arrive_after(xempty + xs * 8, f2.x, f3.x, nil);
            wg_wait<1>();
            if (lane == 0) mbar_arrive(wempty + (wn & 7) * 8);
            xs = xseq(kb + 1);
            if (x1) { f0 = lds128(xa + xs * 8192); f1 = lds128(xa + xs * 8192 + 2048); }
            const bool w2 = mbar_test(wfull + ((wn + 2) & 7) * 8, ((wn + 2) >> 3) & 1);
            step(f3, bd + 1152);
            if (kb < 9 && !x1) { xwait(21 + kb); f0 = lds128(xa + xs * 8192); f1 = lds128(xa + xs * 8192 + 2048); }
            if (!w2) mbar_spin(wfull + ((wn + 2) & 7) * 8, ((wn + 2) >> 3) & 1);
            if (kb == 4) {
                float a0 = q[0].x + q[1].x, b0 = q[0].y + q[1].y, a1 = q[2].x + q[3].x, b1 = q[2].y + q[3].y;
#pragma unroll
                for (int o = 1; o < 4; o *= 2) {
                    a0 += __shfl_xor_sync(~0u, a0, o); b0 += __shfl_xor_sync(~0u, b0, o);
                    a1 += __shfl_xor_sync(~0u, a1, o); b1 += __shfl_xor_sync(~0u, b1, o);
                }
                a0 *= 1.f / D_; a1 *= 1.f / D_;
                const float r0 = 0.5f * rsqrtf(fmaxf(b0 * (1.f / D_) - a0 * a0, 0.f) + 1e-5f), r1 = 0.5f * rsqrtf(fmaxf(b1 * (1.f / D_) - a1 * a1, 0.f) + 1e-5f);
                const uint32_t sel = t == 0 ? 0x1010 : t == 1 ? 0x4432 : 0x4444;
                q[0] = make_float2(r0, r1);
                q[1] = make_float2(__uint_as_float(__byte_perm(split2(-a0), 0, sel)), __uint_as_float(__byte_perm(split2(-a1), 0, sel)));
            }
            TR(leader, 10 * uw + kb)
        }
        const uint64_t fd = ((uint64_t)8 << 32) | ((dsb + OFF_W + 6 * 16384) >> 4);
        wg_fence();
        wgmma_rs128k(acc0, __float_as_uint(q[1].x), __float_as_uint(q[1].y), 0, 0, fd, 1);
        wgmma_rs88k(acc1, __float_as_uint(q[1].x), __float_as_uint(q[1].y), 0, 0, fd + 128, 1);
        wg_commit();
        if (lane == 0) {
            mbar_arrive(bars + B_XFREE * 8);
            asm volatile("mbarrier.arrive.shared::cluster.b64 _, [%0];" ::"r"(peer_addr(bars + B_XFREE * 8)) : "memory");
        }
    }
    const uint32_t recv = sb + recv_off(uw) + wt * 16;
    uint32_t ha[48] = {}, hb[48], hx[12];
    uint64_t wb = dz + (((dsb + OFF_W) >> 4) | (512u << 16));
    auto wdesc = [&](int n) { return wb + (n & 7) * 1024; };
    auto wwait = [&](int n) { mbar_spin(wfull + (n & 7) * 8, (n >> 3) & 1); };
    auto wfree = [&](int n) { if (lane == 0) mbar_arrive(wempty + (n & 7) * 8); };
    auto fresh = [&]() { wb += pp.nil; asm volatile("" : "+l"(wb)); };
    const uint32_t ep = lds32(sb + M_EP);
    uint32_t pk[32];
    {
        float P0[64];
        const float r0 = q[0].x, r1 = q[0].y;
        const uint32_t ra = peer_addr(recv), rb = peer_addr(bars + (B_RECV + 4 * uw) * 8);
        auto conv32 = [&](const float* v, int b) {
#pragma unroll
            for (int i = 0; i < 4; i++) {
                ha[8 * b + 2 * i] = pack2(gelu2(v[4 * i] * r0), gelu2(v[4 * i + 1] * r0));
                ha[8 * b + 2 * i + 1] = pack2(gelu2(v[4 * i + 2] * r1), gelu2(v[4 * i + 3] * r1));
            }
#pragma unroll
            for (int s = 2 * b; s < 2 * b + 2; s++) st_peer(ra + s * 2048, ha[4 * s], ha[4 * s + 1], ha[4 * s + 2], ha[4 * s + 3], rb + (b >> 1) * 8);
        };
        auto fetch = [&](int k) {
            mbar_spin(bars + (B_RECV + 4 * uw + k) * 8, 0);
#pragma unroll
            for (int s = 4 * k; s < 4 * k + 4; s++) { const uint4 x = lds128(recv + s * 2048); hb[4 * s] = x.x; hb[4 * s + 1] = x.y; hb[4 * s + 2] = x.z; hb[4 * s + 3] = x.w; }
        };
        auto stage = [&](int n, const uint32_t* a, int steps, int sc) {
            wwait(n);
            wg_fence();
#pragma unroll
            for (int s = 0; s < steps; s++) wgmma_rs128(P0, a[4 * s], a[4 * s + 1], a[4 * s + 2], a[4 * s + 3], wdesc(n) + s * 128, sc || s);
            wg_commit();
        };
        wg_wait<0>();
        reg_fence(acc0); reg_fence(acc1);
        wfree(29); wfree(30);
        TS(leader, 44 + uw)
        uint32_t hr[6];
#pragma unroll
        for (int i = 0; i < 6; i++) {
            const float r = (i & 1) ? r1 : r0;
            hr[i] = pack2(gelu2(acc1[32 + 2 * i] * r), gelu2(acc1[33 + 2 * i] * r));
        }
        if (uw) mbar_spin(bars + B_XFREE * 8, 0);
        st_peer(ra + 24576, hr[0], hr[1], hr[2], hr[3], rb + 24);
        asm volatile("st.async.shared::cluster.mbarrier::complete_tx::bytes.v2.b32 [%0], {%1, %2}, [%3];" ::"r"(ra + 26624 - wt * 8), "r"(hr[4]), "r"(hr[5]), "r"(rb + 24) : "memory");
        conv32(&acc1[0], 4);
        conv32(&acc1[16], 5);
        TS(leader, 46 + uw)
        stage(31, &ha[32], 4, 0);
#pragma unroll
        for (int b = 0; b < 4; b++) {
            conv32(&acc0[16 * b], b);
            if (b == 3) {
                fetch(2);
                mbar_spin(bars + (B_RECV + 4 * uw + 3) * 8, 0);
                const uint4 x = lds128(recv + 24576);
                const uint2 y = lds64(recv + 26624 - wt * 8);
                const uint32_t hp[6] = {x.x, x.y, x.z, x.w, y.x, y.y};
#pragma unroll
                for (int i = 0; i < 6; i++) { hx[i] = (j & 1) ? hp[i] : hr[i]; hx[6 + i] = (j & 1) ? hr[i] : hp[i]; }
            }
            if (!(b & 1)) wwait(32 + (b >> 1));
            wg_fence();
#pragma unroll
            for (int s = 0; s < 2; s++) wgmma_rs128(P0, ha[8 * b + 4 * s], ha[8 * b + 4 * s + 1], ha[8 * b + 4 * s + 2], ha[8 * b + 4 * s + 3], wdesc(32 + (b >> 1)) + (2 * (b & 1) + s) * 128, 1);
            wg_commit();
            if (!(b & 1)) { wg_wait<1>(); wfree(31 + (b >> 1)); }
        }
        TR(leader, 64 + 10 * uw)
        fresh();
        stage(34, &hb[32], 4, 1); wg_wait<1>(); wfree(33);
        fetch(0);
        stage(35, hx, 3, 1); wg_wait<1>(); wfree(34);
        fetch(1);
        stage(36, &hb[0], 4, 1); wg_wait<1>(); wfree(35);
        stage(37, &hb[16], 4, 1); wg_wait<1>(); wfree(36);
        wg_wait<0>();
        reg_fence(P0);
        pack_part<64>(pk, P0, ep);
        uint32_t all = 0;
#pragma unroll
        for (int i = 0; i < 32; i++) all |= pk[i];
        if (lane == 0) mbar_arrive_after(wempty + (37 & 7) * 8, all, 0, nil);
        TR(leader, 65 + 10 * uw)
    }
    {
        uint4* const dst = g_part + (size_t)(tile * 8 + j) * 5120 + wt;
        const uint4* const src = g_part + (size_t)tile * 40960 + j * 512 + wt;
        float F[2][32];
        float2 gb[8];
        uint4 base[4], u1[4], u2[4], u3[4];
#pragma unroll
        for (int c = 2; c < 5; c++) {
            float (&P)[32] = F[c & 1];
            fresh();
#pragma unroll
            for (int s = 0; s < 27; s++) {
                const int e = s < 8 ? 0 : s < 15 ? 1 : s < 23 ? 2 : 3, o = s - (e == 0 ? 0 : e == 1 ? 8 : e == 2 ? 15 : 23), n = 30 + 4 * c + e;
                const uint32_t* a = s < 12 ? &ha[4 * s] : s < 15 ? &hx[4 * (s - 12)] : &hb[4 * (s - 15)];
                if (o == 0) wwait(n);
                if (o == 0 || s == 1) wg_fence();
                wgmma_rs64(P, a[0], a[1], a[2], a[3], wdesc(n) + o * 128, s);
                if (o == 0) { wg_commit(); wg_wait<1>(); if (c > 2 || s) wfree(n - 1); }
                if (s == 0 && c > 2) { reg_fence(F[~c & 1]); pack_part<32>(pk, F[~c & 1], ep); }
                if (c == 2 && s % 3 == 0 && s < 24) st_part(dst + g4_block(s / 12, j) * 512 + (s / 3 & 3) * 128, &pk[4 * (s / 3)]);
                if (c == 3 && s % 4 == 1 && s < 16) st_part(dst + g4_block(2, j) * 512 + s / 4 * 128, &pk[4 * (s / 4)]);
                if (c == 4 && s % ST3 == 0 && s < 4 * ST3) st_part(dst + g4_block(3, j) * 512 + s / ST3 * 128, &pk[4 * (s / ST3)]);
                if (c == 4 && s >= 4 && s < 8) base[s - 4] = ldcg128(&g_x1f[(tile * 8 + j) * 640 + (s - 4) * 128 + wt]);
                if (c == 4 && s >= 19 && s < 23) { gb[2 * s - 38] = lds64f(sb + M_GB + (16 * (s - 19) + 2 * t) * 4); gb[2 * s - 37] = lds64f(sb + M_GB + (16 * (s - 19) + 8 + 2 * t) * 4); }
                if (c == 4 && s >= 8 && s < 12) u1[s - 8] = ld_part(src + (j ^ 6) * 5120 + (s - 8) * 128);
                if (c == 4 && s >= 15 && s < 19) u2[s - 15] = ld_part(src + (j ^ 4) * 5120 + (s - 15) * 128);
                if (c == 4 && s >= LD3 && s < LD3 + 4) u3[s - LD3] = ld_part(src + (j ^ 2) * 5120 + (s - LD3) * 128);
                if (s == 7 || s == 14 || s == 22 || s == 26) wg_commit();
                if (c == 4) { TR(leader && s == 7, 68 + 10 * uw) TR(leader && s == 14, 69 + 10 * uw) TR(leader && s == 22, 70 + 10 * uw) }
            }
            if (c == 2 && lane == 0) mbar_arrive(bars + (B_RING + uw) * 8);
            TR(leader, 64 + c + (c == 4 ? 3 : 0) + 10 * uw)
        }
        float (&O)[32] = F[0];
        float v[32];
        fix4(u1, src + (j ^ 6) * 5120, ep, 4);
        fix4(u2, src + (j ^ 4) * 5120, ep, 5);
        TR(leader, 72 + 10 * uw)
        fix4(u3, src + (j ^ 2) * 5120, ep, 6);
        TR(leader, 73 + 10 * uw)
#pragma unroll
        for (int i = 0; i < 4; i++) { unpack8(&v[8 * i], add2(add2(u1[i], u2[i]), u3[i])); base16(&v[8 * i], base[i], gb[2 * i], gb[2 * i + 1]); }
        reg_fence(v);
        TS(leader, 50 + uw)
        wg_wait<0>();
        reg_fence(O);
        TS(leader, 48 + uw)
        const uint32_t so = sb + recv_off(uw) + wq * 2048;
#pragma unroll
        for (int i = 0; i < 4; i++) {
            float* o = &O[8 * i];
#pragma unroll
            for (int e = 0; e < 8; e++) o[e] = fmaf((e & 1) ? gb[2 * i + (e >> 2)].y : gb[2 * i + (e >> 2)].x, o[e], v[8 * i + e]);
            stsm4(so + (lane & 15) * 128 + (((2 * i + (lane >> 4)) ^ (lane & 7)) << 4), pack2(o[0], o[1]), pack2(o[2], o[3]), pack2(o[4], o[5]), pack2(o[6], o[7]));
        }
        __syncwarp();
#pragma unroll
        for (int i = 0; i < 4; i++) {
            const int row = (lane >> 3) + 4 * i;
            stg128(out + (size_t)(row0 + row) * D_ + 64 * j + 8 * (lane & 7), lds128(so + row * 128 + (((lane & 7) ^ (row & 7)) << 4)));
        }
        warp_arrive(bars + (B_OWN + uw) * 8);
    }
}

typedef CUresult (*EncFn)(CUtensorMap*, CUtensorMapDataType, cuuint32_t, void*, const cuuint64_t*, const cuuint64_t*, const cuuint32_t*,
                          const cuuint32_t*, CUtensorMapInterleave, CUtensorMapSwizzle, CUtensorMapL2promotion, CUtensorMapFloatOOBfill);

static void enc(EncFn fn, CUtensorMap* m, void* p, int rank, const cuuint64_t* dims, const cuuint64_t* strides, const cuuint32_t* box) {
    const CUtensorMapSwizzle sw = box[0] > 64 ? CU_TENSOR_MAP_SWIZZLE_NONE : CU_TENSOR_MAP_SWIZZLE_128B;
    cuuint32_t es[5] = {1, 1, 1, 1, 1};
    CUresult r = fn(m, CU_TENSOR_MAP_DATA_TYPE_BFLOAT16, rank, p, dims, strides, box, es, CU_TENSOR_MAP_INTERLEAVE_NONE, sw,
                    CU_TENSOR_MAP_L2_PROMOTION_L2_128B, CU_TENSOR_MAP_FLOAT_OOB_FILL_NONE);
    (void)r;
}
static void enc2(EncFn fn, CUtensorMap* m, void* p, uint64_t cols, uint64_t rows, uint32_t bc, uint32_t br) {
    cuuint64_t dims[2] = {cols, rows}, st[1] = {cols * 2};
    cuuint32_t box[2] = {bc, br};
    enc(fn, m, p, 2, dims, st, box);
}

extern "C" void kernel_launch(void* const* d_in, const int* in_sizes, int n_in, void* d_out, int out_size) {
    static Maps mp;
    static Ptrs pp;
    static void* cached[13];
    bool same = true;
    for (int i = 0; i < 13; i++) same = same && (cached[i] == d_in[i]);
    if (!same) {
        void* fnp = nullptr;
        cudaDriverEntryPointQueryResult qr;
        cudaGetDriverEntryPoint("cuTensorMapEncodeTiled", &fnp, cudaEnableDefault, &qr);
        EncFn fn = (EncFn)fnp;
        cudaGetSymbolAddress((void**)&pp.s, g_scratch);
        void *x1T = g_x1T, *t = g_t;
        cuuint64_t dq[3] = {64, S_, 10}, sq[2] = {D_ * 2, 128};
        cuuint32_t bq[3] = {64, 16, 10};
        enc(fn, &mp.q, d_in[0], 3, dq, sq, bq);
        enc2(fn, &mp.k, d_in[1], D_, S_, 80, 67); enc2(fn, &mp.v, d_in[2], D_, S_, 80, 64);
        enc2(fn, &mp.qT, g_qT, 16 * D_, 128, 80, 128);
        enc2(fn, &mp.x1_ld, x1T, S_, D_, 64, 64); enc2(fn, &mp.t_ld, (bf16*)t + 2 * D_, D_, S_, 64, 64);
        enc2(fn, &mp.w1, d_in[7], D_, D_, 64, 64); enc2(fn, &mp.w1h, d_in[7], D_, D_, 64, 160); enc2(fn, &mp.w3h, d_in[9], F_, D_, 64, 160);
        enc2(fn, &mp.wmod, d_in[12], 6 * D_, D_, 64, 160);
        const cuuint64_t R = D_ * 2;
        cuuint64_t da[5] = {D_, 2, 4, 4, 16}, sa[4] = {R, 8 * R, 2 * R, 32 * R}, db[5] = {D_, 2, 2, 4, 8}, sb[4] = {R, 8 * R, 2 * R, 16 * R};
        cuuint32_t ba[5] = {64, 2, 4, 4, 4}, bb[5] = {64, 2, 2, 4, 8};
        enc(fn, &mp.w2a, d_in[8], 5, da, sa, ba); enc(fn, &mp.w2b, (bf16*)d_in[8] + 512 * D_, 5, db, sb, bb);
        cuuint64_t dw[3] = {64, D_, 27}, sw[2] = {F_ * 2, 128};
        cuuint32_t bw[3] = {64, 32, 3};
        enc(fn, &mp.w3a, d_in[9], 3, dw, sw, bw);
        enc2(fn, &mp.w3b, d_in[9], F_, D_, 24, 32);
        enc2(fn, &mp.w4[0], d_in[10], D_, F_, 64, 64); enc2(fn, &mp.w4[1], d_in[10], D_, F_, 64, 48);
        pp.q = (const bf16*)d_in[0]; pp.w_mod = (const bf16*)d_in[12]; pp.shift_k = (const bf16*)d_in[3];
        pp.ssm_k = (const bf16*)d_in[4]; pp.ssm_D = (const bf16*)d_in[5]; pp.w1 = (const bf16*)d_in[7]; pp.w2 = (const bf16*)d_in[8];
        pp.w4 = (const bf16*)d_in[10]; pp.c = (const bf16*)d_in[11];
        cudaFuncSetAttribute(fused_kernel, cudaFuncAttributeMaxDynamicSharedMemorySize, SMEM_BYTES);
        for (int i = 0; i < 13; i++) cached[i] = d_in[i];
    }
    cudaLaunchConfig_t cfg = {};
    cfg.gridDim = dim3(NCTA); cfg.blockDim = dim3(NTHR); cfg.dynamicSmemBytes = SMEM_BYTES; cfg.stream = cudaStreamPerThread;
    cudaLaunchAttribute at[1];
    at[0].id = cudaLaunchAttributeClusterDimension; at[0].val.clusterDim.x = 2; at[0].val.clusterDim.y = 1; at[0].val.clusterDim.z = 1;
    cfg.attrs = at; cfg.numAttrs = 1;
    cudaLaunchKernelEx(&cfg, fused_kernel, pp, (bf16*)d_out, mp);
}
```

```cpp
#include <cuda_runtime.h>
#include <cuda_bf16.h>
#include <cuda.h>
#include <stdint.h>
#include <stdio.h>

typedef __nv_bfloat16 bf16;

constexpr int S_ = 2048, D_ = 640, F_ = 1728;
constexpr int NCTA = 132, NTHR = 512;

constexpr int TAB_BYTES = 9216, VEC_BYTES = 1440;
struct Counters {
    unsigned kv[8 * 32];
    unsigned q[4 * 32], x[2 * 4 * 32];
    unsigned wr[32], tab[32], uv[32], cs[32], done[32];
    unsigned g1[32 * 32];
    unsigned g2[32 * 32];
};
struct Scratch {
    Counters cnt;
    unsigned epoch;
    alignas(1024) bf16 qst[2 * S_];
    alignas(1024) uint4 wr[2 * 8 * 10 * 128];
    alignas(1024) uint2 mod[2 * 6 * D_];
    alignas(1024) uint4 tab[(TAB_BYTES + 8 * VEC_BYTES) / 16];
    alignas(1024) float uv[2 * 3 * D_];
    alignas(1024) float cs3[2 * 1920];
    alignas(1024) float2 stats[32 * 8 * 64];
    alignas(1024) bf16 kvT[D_ * S_];
    alignas(1024) bf16 qT[D_ * S_];
    alignas(1024) bf16 x1T[D_ * S_];
    alignas(1024) bf16 t[(S_ + 4) * D_];
    alignas(1024) uint4 x2f[32 * 40 * 128];
    alignas(1024) uint4 x1f[32 * 8 * 5 * 128];
    alignas(1024) uint4 part[32 * 8 * 10 * 4 * 128];
};
__device__ Scratch g_scratch;
#define g_kvT (pp.s->kvT)
#define g_qT (pp.s->qT)
#define g_x1T (pp.s->x1T)
#define g_qst (pp.s->qst)
#define g_t (pp.s->t)
#define g_x2f (pp.s->x2f)
#define g_x1f (pp.s->x1f)
#define g_part (pp.s->part)
#define g_wr (pp.s->wr)
#define g_mod (pp.s->mod)
#define g_tab (pp.s->tab)
#define g_uv (pp.s->uv)
#define g_cs3 (pp.s->cs3)
#define g_stats (pp.s->stats)
#define g_cnt (pp.s->cnt)
#define g_epoch (pp.s->epoch)

struct Maps {
    CUtensorMap k, v, q;
    CUtensorMap qT;
    CUtensorMap x1_ld, t_ld;
    CUtensorMap w1, w1h, w3h, wmod;
    CUtensorMap w2a, w2b;
    CUtensorMap w3a, w3b;
    CUtensorMap w4[2];
};

struct Ptrs {
    Scratch* s;
    uint64_t nil;
    const bf16 *q, *w_mod, *shift_k, *ssm_k, *ssm_D, *w1, *w2, *w4, *c;
};

constexpr int OFF_W = 0;
constexpr int OFF_XR = 131072;
constexpr int OFF_REM = 196608;
constexpr int OFF_TAB = OFF_REM + 5 * 4096;
constexpr int OFF_ROW = OFF_TAB + 4608;
constexpr int OFF_F1 = OFF_ROW + 4096;
constexpr int RECV_BYTES = 30720;
constexpr int OFF_M = OFF_REM + RECV_BYTES;
constexpr int OFF_OUT = OFF_XR + 32768;
static_assert(OFF_F1 + 1280 <= OFF_M, "G1 map");
constexpr int OFF_ST = 0;
constexpr int OFF_SSM = 20480;
constexpr int OFF_WM = 0;
constexpr int OFF_QIN = 49152;
constexpr int OFF_QT = 49152;
constexpr int OFF_Z = OFF_TAB;
constexpr int OFF_RING = 80896;
constexpr int OFF_KIN = OFF_RING, OFF_VIN = OFF_KIN + 2 * 10752;
constexpr int OFF_CH = OFF_RING + 3 * 16384, CH_BYTES = 13312, OFF_P = 5120;
static_assert(OFF_RING + 5 * 16384 <= OFF_CH + 3 * CH_BYTES && OFF_CH + 5 * CH_BYTES <= OFF_REM, "the last two rings replace channels 0..2");
constexpr int M_BAR = OFF_M;
constexpr int M_F1 = OFF_M + 768;
constexpr int M_GB = M_F1 + 1280, M_C = M_GB + 320, M_SB = M_C + 320, M_CI = M_SB + 320;
constexpr int M_KS = M_CI + 320;
constexpr int M_AB = M_KS + 160;
constexpr int M_EP = M_AB + 80;
constexpr int M_NUL = M_EP + 16;
constexpr int M_TS = M_NUL + 16;
constexpr int SMEM_BYTES = M_TS;
static_assert(SMEM_BYTES <= 232448, "smem");

enum { B_WFULL = 0, B_WEMPTY = 8, B_XEMPTY = 16, B_XFULL = 24  ,
       B_RAW = 40, B_QIN = 41, B_SSM = 42, B_VEC = 43, B_VEC3 = 44, B_WM = 45, B_TAB = 46, B_QRDY = 47,
       B_MODR = 48, B_PUB = 49, B_RETRY = 55, B_S30 = 58, B_RAW2 = 59, B_SUMS = 62, B_RECV = 64  ,
       B_SIG = 72, B_OWN = 74, B_COEF = 76, B_RES = 78, B_RING = 80  ,
       B_XS = 88, B_BK = 90, B_KVS = 91,
       B_XFREE = 92,
       B_IN = 94 };
#define T_KVB 1800
#define T_SSM 3300
#define T_Q 0
#define PF_T0 4800
#define PF_DT 420
#define PF_N0 4
#define PF_N 16
#define CH2_DELAY 0
#define POLL_NS 0
#define HELP_T 1000
#define EPI_SPLIT 1
#define GATE3
#define GATE10
#define GATE16 16
#define ST3 1
#define LD3 23
#define XLEAD 3

#define SPIN_FAIL(code) __trap();
#define SPIN_LIMIT (1u << 22)
#define STALE(c)
#define TS(c, i)
#define TG(c, i)
#define TR(c, i)
#define TR2(c, i)
#define TR4(c, i)
#define CKV
#define CK(i)
#define CKD(c, o)
__device__ __forceinline__ uint32_t s2u(const void* p) { return (uint32_t)__cvta_generic_to_shared(p); }
__device__ __forceinline__ bool elect() {
    uint32_t p;
    asm volatile("{.reg .pred P; elect.sync _|P, 0xffffffff; selp.u32 %0,1,0,P;}" : "=r"(p));
    return p != 0;
}
__device__ __forceinline__ void mbar_init(uint32_t b, uint32_t n) { asm volatile("mbarrier.init.shared.b64 [%0], %1;" ::"r"(b), "r"(n)); }
__device__ __forceinline__ void mbar_expect(uint32_t b, uint32_t bytes) {
    asm volatile("mbarrier.arrive.expect_tx.shared.b64 _, [%0], %1;" ::"r"(b), "r"(bytes) : "memory");
}
__device__ __forceinline__ void mbar_arrive(uint32_t b) { asm volatile("mbarrier.arrive.shared.b64 _, [%0];" ::"r"(b) : "memory"); }
__device__ __forceinline__ void mbar_arrive_after(uint32_t b, uint32_t v0, uint32_t v1, uint32_t nil) { mbar_arrive(b + ((v0 | v1) & nil)); }
__device__ __forceinline__ void warp_arrive(uint32_t b) { __syncwarp(); if (elect()) mbar_arrive(b); }
__device__ __forceinline__ uint32_t peer_addr(uint32_t a) {
    uint32_t r;
    asm("{\n.reg .b32 q;\nmov.u32 q, %%cluster_ctarank;\nxor.b32 q, q, 1;\nmapa.shared::cluster.u32 %0, %1, q;\n}" : "=r"(r) : "r"(a));
    return r;
}
__device__ __forceinline__ bool mbar_test(uint32_t b, uint32_t parity) {
    uint32_t ok;
    asm volatile("{.reg .pred P; mbarrier.test_wait.parity.shared.b64 P, [%1], %2; selp.u32 %0,1,0,P;}" : "=r"(ok) : "r"(b), "r"(parity) : "memory");
    return ok != 0;
}
__device__ __forceinline__ bool mbar_try(uint32_t b, uint32_t parity) {
    uint32_t ok;
    asm volatile("{.reg .pred P; mbarrier.try_wait.parity.shared.b64 P, [%1], %2; selp.u32 %0,1,0,P;}" : "=r"(ok) : "r"(b), "r"(parity) : "memory");
    return ok != 0;
}
__device__ __forceinline__ void mbar_wait(uint32_t b, uint32_t parity) {
    if (__all_sync(0xffffffffu, mbar_try(b, parity))) return;
    uint32_t it = 0;
    while (!__all_sync(0xffffffffu, mbar_try(b, parity))) { if (++it > SPIN_LIMIT) SPIN_FAIL((b >> 3) & 63) }
}
__device__ __forceinline__ void mbar_spin(uint32_t b, uint32_t parity) {
    asm volatile("{\n.reg .pred P;\nSPIN:\nmbarrier.try_wait.parity.shared.b64 P, [%0], %1;\n@!P bra.uni SPIN;\n}" ::"r"(b), "r"(parity) : "memory");
}
__device__ __forceinline__ void bar_sync(int id, int n) { asm volatile("bar.sync %0, %1;" ::"r"(id), "r"(n) : "memory"); }
__device__ __forceinline__ void fence_async_smem() { asm volatile("fence.proxy.async.shared::cta;" ::: "memory"); }
__device__ __forceinline__ void wait_cnt(const unsigned* p, unsigned target, int ns = 0) {
    unsigned v, it = 0;
    do {
        if (ns) __nanosleep(ns);
        asm volatile("ld.relaxed.gpu.global.u32 %0, [%1];" : "=r"(v) : "l"(p) : "memory");
        if (++it > SPIN_LIMIT) SPIN_FAIL(60 + (target & 3))
    } while (!__all_sync(0xffffffffu, v >= target));
    asm volatile("fence.acquire.gpu;" ::: "memory");
}
#define X_NOFENCE 0
__device__ __forceinline__ void signal_cnt(unsigned* p, int lane, int n, bool nofence = false) {
    if (nofence) { if (lane < n) asm volatile("red.relaxed.gpu.global.add.u32 [%0], 1;" ::"l"(p) : "memory"); }
    else if (lane < n) asm volatile("red.release.gpu.global.add.u32 [%0], 1;" ::"l"(p) : "memory");
    __syncwarp();
}
__device__ __forceinline__ void wait_clock(long long c0, int t) {
    while (clock64() - c0 < t) __nanosleep(20);
    __syncwarp();
}
__device__ __forceinline__ void tma_ld2(uint32_t dst, const CUtensorMap* m, int c0, int c1, uint32_t bar) {
    asm volatile("cp.async.bulk.tensor.2d.shared::cluster.global.mbarrier::complete_tx::bytes [%0], [%1, {%3, %4}], [%2];"
                 ::"r"(dst), "l"(m), "r"(bar), "r"(c0), "r"(c1) : "memory");
}
__device__ __forceinline__ void tma_ld3(uint32_t dst, const CUtensorMap* m, int c0, int c1, int c2, uint32_t bar) {
    asm volatile("cp.async.bulk.tensor.3d.shared::cluster.global.mbarrier::complete_tx::bytes [%0], [%1, {%3, %4, %5}], [%2];"
                 ::"r"(dst), "l"(m), "r"(bar), "r"(c0), "r"(c1), "r"(c2) : "memory");
}
__device__ __forceinline__ void tma_ld5(uint32_t dst, const CUtensorMap* m, int col, int blk, uint32_t bar) {
    asm volatile("cp.async.bulk.tensor.5d.shared::cluster.global.mbarrier::complete_tx::bytes [%0], [%1, {%3, %4, %4, %4, %5}], [%2];"
                 ::"r"(dst), "l"(m), "r"(bar), "r"(col), "r"(0), "r"(blk) : "memory");
}
__device__ __forceinline__ void bulk_ld(uint32_t dst, const void* src, uint32_t bytes, uint32_t bar) {
    asm volatile("cp.async.bulk.shared::cluster.global.mbarrier::complete_tx::bytes [%0], [%1], %2, [%3];" ::"r"(dst), "l"(src), "r"(bytes), "r"(bar) : "memory");
}
__device__ __forceinline__ void l2_prefetch(const void* p, uint32_t bytes) {
    asm volatile("cp.async.bulk.prefetch.L2.global [%0], %1;" ::"l"(p), "r"(bytes) : "memory");
}
__device__ __forceinline__ void wg_fence() { asm volatile("wgmma.fence.sync.aligned;" ::: "memory"); }
__device__ __forceinline__ void wg_commit() { asm volatile("wgmma.commit_group.sync.aligned;" ::: "memory"); }
template <int N> __device__ __forceinline__ void wg_wait() { asm volatile("wgmma.wait_group.sync.aligned %0;" ::"n"(N) : "memory"); }
template <int N> __device__ __forceinline__ void reg_fence(float (&d)[N]) {
#pragma unroll
    for (int i = 0; i < N; i++) asm volatile("" : "+f"(d[i])::"memory");
}
template <int N> __device__ __forceinline__ void zero(float (&d)[N]) {
#pragma unroll
    for (int i = 0; i < N; i++) asm volatile("mov.b32 %0, 0;" : "=f"(d[i]));
}
__device__ __forceinline__ uint32_t lds32(uint32_t a) { uint32_t v; asm volatile("ld.shared.b32 %0, [%1];" : "=r"(v) : "r"(a)); return v; }
__device__ __forceinline__ uint2 lds64(uint32_t a) { uint2 v; asm volatile("ld.shared.v2.b32 {%0,%1}, [%2];" : "=r"(v.x), "=r"(v.y) : "r"(a)); return v; }
__device__ __forceinline__ float2 lds64f(uint32_t a) { float2 v; asm volatile("ld.shared.v2.f32 {%0,%1}, [%2];" : "=f"(v.x), "=f"(v.y) : "r"(a)); return v; }
__device__ __forceinline__ void sts32(uint32_t a, uint32_t v) { asm volatile("st.shared.b32 [%0], %1;" ::"r"(a), "r"(v) : "memory"); }
__device__ __forceinline__ void sts64f(uint32_t a, float x, float y) { asm volatile("st.shared.v2.f32 [%0], {%1,%2};" ::"r"(a), "f"(x), "f"(y) : "memory"); }
__device__ __forceinline__ void sts128(uint32_t a, uint32_t x, uint32_t y, uint32_t z, uint32_t w) {
    asm volatile("st.shared.v4.b32 [%0], {%1,%2,%3,%4};" ::"r"(a), "r"(x), "r"(y), "r"(z), "r"(w) : "memory");
}
__device__ __forceinline__ void sts128f(uint32_t a, float x, float y, float z, float w) {
    asm volatile("st.shared.v4.f32 [%0], {%1,%2,%3,%4};" ::"r"(a), "f"(x), "f"(y), "f"(z), "f"(w) : "memory");
}
__device__ __forceinline__ uint4 lds128(uint32_t a) {
    uint4 v;
    asm volatile("ld.shared.v4.b32 {%0,%1,%2,%3}, [%4];" : "=r"(v.x), "=r"(v.y), "=r"(v.z), "=r"(v.w) : "r"(a) : "memory");
    return v;
}
__device__ __forceinline__ float4 lds128f(uint32_t a) {
    float4 v;
    asm volatile("ld.shared.v4.f32 {%0,%1,%2,%3}, [%4];" : "=f"(v.x), "=f"(v.y), "=f"(v.z), "=f"(v.w) : "r"(a) : "memory");
    return v;
}
__device__ __forceinline__ void stg128(void* p, uint32_t x, uint32_t y, uint32_t z, uint32_t w) {
    asm volatile("st.global.v4.b32 [%0], {%1,%2,%3,%4};" ::"l"(p), "r"(x), "r"(y), "r"(z), "r"(w) : "memory");
}
__device__ __forceinline__ void stg128(void* p, uint4 v) { stg128(p, v.x, v.y, v.z, v.w); }
__device__ __forceinline__ void stg128_if(void* p, uint4 v, int on) {
    asm volatile("{\n.reg .pred p;\nsetp.ne.s32 p, %5, 0;\n@p st.global.v4.b32 [%0], {%1,%2,%3,%4};\n}" ::"l"(p), "r"(v.x), "r"(v.y), "r"(v.z), "r"(v.w), "r"(on) : "memory");
}
__device__ __forceinline__ void stg64(void* p, uint32_t x, uint32_t y) { asm volatile("st.global.v2.b32 [%0], {%1,%2};" ::"l"(p), "r"(x), "r"(y) : "memory"); }
__device__ __forceinline__ void stsm4(uint32_t a, uint32_t r0, uint32_t r1, uint32_t r2, uint32_t r3) {
    asm volatile("stmatrix.sync.aligned.m8n8.x4.shared.b16 [%0], {%1,%2,%3,%4};" ::"r"(a), "r"(r0), "r"(r1), "r"(r2), "r"(r3) : "memory");
}
__device__ __forceinline__ void stsm4t(uint32_t a, uint32_t r0, uint32_t r1, uint32_t r2, uint32_t r3) {
    asm volatile("stmatrix.sync.aligned.m8n8.x4.trans.shared.b16 [%0], {%1,%2,%3,%4};" ::"r"(a), "r"(r0), "r"(r1), "r"(r2), "r"(r3) : "memory");
}
__device__ __forceinline__ void ldsm4t(uint32_t a, uint32_t& r0, uint32_t& r1, uint32_t& r2, uint32_t& r3) {
    asm volatile("ldmatrix.sync.aligned.m8n8.x4.trans.shared.b16 {%0,%1,%2,%3}, [%4];" : "=r"(r0), "=r"(r1), "=r"(r2), "=r"(r3) : "r"(a) : "memory");
}
__device__ __forceinline__ uint32_t pack2(float lo, float hi) {
    uint32_t r;
    asm("cvt.rn.bf16x2.f32 %0, %1, %2;" : "=r"(r) : "f"(hi), "f"(lo));
    return r;
}
__device__ __forceinline__ uint32_t mul2(uint32_t a, uint32_t b) { uint32_t r; asm("mul.rn.bf16x2 %0, %1, %2;" : "=r"(r) : "r"(a), "r"(b)); return r; }
__device__ __forceinline__ uint32_t fma2(uint32_t a, uint32_t b, uint32_t c) { uint32_t r; asm("fma.rn.bf16x2 %0, %1, %2, %3;" : "=r"(r) : "r"(a), "r"(b), "r"(c)); return r; }
__device__ __forceinline__ uint32_t add2(uint32_t a, uint32_t b) { uint32_t r; asm("add.rn.bf16x2 %0, %1, %2;" : "=r"(r) : "r"(a), "r"(b)); return r; }
__device__ __forceinline__ void hmma(float (&d)[4], uint32_t a0, uint32_t a1, uint32_t a2, uint32_t a3, uint32_t b0, uint32_t b1) {
    asm volatile("mma.sync.aligned.m16n8k16.row.col.f32.bf16.bf16.f32 {%0,%1,%2,%3}, {%4,%5,%6,%7}, {%8,%9}, {%0,%1,%2,%3};"
        : "+f"(d[0]), "+f"(d[1]), "+f"(d[2]), "+f"(d[3]) : "r"(a0), "r"(a1), "r"(a2), "r"(a3), "r"(b0), "r"(b1));
}
__device__ __forceinline__ float blo(uint32_t w) { return __uint_as_float(w << 16); }
__device__ __forceinline__ float bhi(uint32_t w) { return __uint_as_float(w & 0xffff0000u); }
__device__ __forceinline__ float rbf(float x) { return __bfloat162float(__float2bfloat16_rn(x)); }
__device__ __forceinline__ uint32_t ldg32(const void* p) { uint32_t v; asm volatile("ld.global.nc.b32 %0, [%1];" : "=r"(v) : "l"(p)); return v; }
__device__ __forceinline__ uint2 ldg64(const void* p) { uint2 v; asm volatile("ld.global.nc.v2.b32 {%0,%1}, [%2];" : "=r"(v.x), "=r"(v.y) : "l"(p)); return v; }
__device__ __forceinline__ uint4 ldg128(const void* p) {
    uint4 v;
    asm volatile("ld.global.nc.v4.b32 {%0,%1,%2,%3}, [%4];" : "=r"(v.x), "=r"(v.y), "=r"(v.z), "=r"(v.w) : "l"(p));
    return v;
}
__device__ __forceinline__ uint4 ldcg128(const void* p) {
    uint4 v;
    asm volatile("ld.global.cg.v4.u32 {%0,%1,%2,%3}, [%4];" : "=r"(v.x), "=r"(v.y), "=r"(v.z), "=r"(v.w) : "l"(p) : "memory");
    return v;
}
__device__ __forceinline__ float4 ldcg128f(const void* p) {
    float4 v;
    asm volatile("ld.global.cg.v4.f32 {%0,%1,%2,%3}, [%4];" : "=f"(v.x), "=f"(v.y), "=f"(v.z), "=f"(v.w) : "l"(p) : "memory");
    return v;
}
__device__ __forceinline__ float2 ldcg64f(const void* p) { float2 v; asm volatile("ld.global.cg.v2.f32 {%0,%1}, [%2];" : "=f"(v.x), "=f"(v.y) : "l"(p) : "memory"); return v; }
__device__ __forceinline__ float ldcg32f(const void* p) { float v; asm volatile("ld.global.cg.f32 %0, [%1];" : "=f"(v) : "l"(p) : "memory"); return v; }
__device__ __forceinline__ uint32_t ld_cold(const unsigned* p) { uint32_t v; asm volatile("ld.relaxed.gpu.global.u32 %0, [%1];" : "=r"(v) : "l"(p) : "memory"); return v; }
__device__ __forceinline__ uint2 ld_mod(const uint2* p) {
    uint64_t v;
    asm volatile("ld.relaxed.gpu.global.b64 %0, [%1];" : "=l"(v) : "l"(p) : "memory");
    return make_uint2((uint32_t)v, (uint32_t)(v >> 32));
}
__device__ __forceinline__ float gelu2(float h) {
    float u = h * fmaf(h * h, 8.f * 0.0356774081f, 2.f * 0.7978845608f);
    float th;
    asm("tanh.approx.f32 %0, %1;" : "=f"(th) : "f"(u));
    return fmaf(h, th, h);
}

__device__ __forceinline__ void conv_channel(float (&d)[64], uint32_t pa, uint64_t db) {
    asm volatile("{\n.reg .b32 a0, a1, a2, a3, b0, b1, b2, b3, t0, t1;\n.reg .b64 d;\nld.shared.b32 a0, [%64];\nld.shared.b32 a1, [%64+128];\nld.shared.b32 a2, [%64+-128];\nmov.b32 a3, a0;\n"
        "ld.shared.b32 t0, [%64+256];\nld.shared.b32 t1, [%64+384];\nadd.s64 d, %65, 0;\nwgmma.fence.sync.aligned;\nwgmma.mma_async.sync.aligned.m64n128k16.f32.bf16.bf16 {%0, %1, %2, %3, %4, %5, %6, %7, %8, %9, %10, %11, %12, %13, %14, %15, %16, %17, %18, %19, %20, %21, %22, %23, %24, %25, %26, %27, %28, %29, %30, %31, %32, %33, %34, %35, %36, %37, %38, %39, %40, %41, %42, %43, %44, %45, %46, %47, %48, %49, %50, %51, %52, %53, %54, %55, %56, %57, %58, %59, %60, %61, %62, %63}, {a0, a1, a2, a3}, d, 0, 1, 1, 0;\nwgmma.commit_group.sync.aligned;\nwgmma.wait_group.sync.aligned 1;\nmov.b32 b2, a1;\nmov.b32 b0, t0;\nmov.b32 b3, t0;\nmov.b32 b1, t1;\n"
        "ld.shared.b32 t0, [%64+512];\nld.shared.b32 t1, [%64+640];\nadd.s64 d, %65, 8;\nwgmma.fence.sync.aligned;\nwgmma.mma_async.sync.aligned.m64n128k16.f32.bf16.bf16 {%0, %1, %2, %3, %4, %5, %6, %7, %8, %9, %10, %11, %12, %13, %14, %15, %16, %17, %18, %19, %20, %21, %22, %23, %24, %25, %26, %27, %28, %29, %30, %31, %32, %33, %34, %35, %36, %37, %38, %39, %40, %41, %42, %43, %44, %45, %46, %47, %48, %49, %50, %51, %52, %53, %54, %55, %56, %57, %58, %59, %60, %61, %62, %63}, {b0, b1, b2, b3}, d, 1, 1, 1, 0;\nwgmma.commit_group.sync.aligned;\nwgmma.wait_group.sync.aligned 1;\nmov.b32 a2, b1;\nmov.b32 a0, t0;\nmov.b32 a3, t0;\nmov.b32 a1, t1;\n"
        "ld.shared.b32 t0, [%64+768];\nld.shared.b32 t1, [%64+896];\nadd.s64 d, %65, 16;\nwgmma.fence.sync.aligned;\nwgmma.mma_async.sync.aligned.m64n128k16.f32.bf16.bf16 {%0, %1, %2, %3, %4, %5, %6, %7, %8, %9, %10, %11, %12, %13, %14, %15, %16, %17, %18, %19, %20, %21, %22, %23, %24, %25, %26, %27, %28, %29, %30, %31, %32, %33, %34, %35, %36, %37, %38, %39, %40, %41, %42, %43, %44, %45, %46, %47, %48, %49, %50, %51, %52, %53, %54, %55, %56, %57, %58, %59, %60, %61, %62, %63}, {a0, a1, a2, a3}, d, 1, 1, 1, 0;\nwgmma.commit_group.sync.aligned;\nwgmma.wait_group.sync.aligned 1;\nmov.b32 b2, a1;\nmov.b32 b0, t0;\nmov.b32 b3, t0;\nmov.b32 b1, t1;\n"
        "ld.shared.b32 t0, [%64+1024];\nld.shared.b32 t1, [%64+1152];\nadd.s64 d, %65, 24;\nwgmma.fence.sync.aligned;\nwgmma.mma_async.sync.aligned.m64n128k16.f32.bf16.bf16 {%0, %1, %2, %3, %4, %5, %6, %7, %8, %9, %10, %11, %12, %13, %14, %15, %16, %17, %18, %19, %20, %21, %22, %23, %24, %25, %26, %27, %28, %29, %30, %31, %32, %33, %34, %35, %36, %37, %38, %39, %40, %41, %42, %43, %44, %45, %46, %47, %48, %49, %50, %51, %52, %53, %54, %55, %56, %57, %58, %59, %60, %61, %62, %63}, {b0, b1, b2, b3}, d, 1, 1, 1, 0;\nwgmma.commit_group.sync.aligned;\nwgmma.wait_group.sync.aligned 1;\nmov.b32 a2, b1;\nmov.b32 a0, t0;\nmov.b32 a3, t0;\nmov.b32 a1, t1;\n"
        "ld.shared.b32 t0, [%64+1280];\nld.shared.b32 t1, [%64+1408];\nadd.s64 d, %65, 32;\nwgmma.fence.sync.aligned;\nwgmma.mma_async.sync.aligned.m64n128k16.f32.bf16.bf16 {%0, %1, %2, %3, %4, %5, %6, %7, %8, %9, %10, %11, %12, %13, %14, %15, %16, %17, %18, %19, %20, %21, %22, %23, %24, %25, %26, %27, %28, %29, %30, %31, %32, %33, %34, %35, %36, %37, %38, %39, %40, %41, %42, %43, %44, %45, %46, %47, %48, %49, %50, %51, %52, %53, %54, %55, %56, %57, %58, %59, %60, %61, %62, %63}, {a0, a1, a2, a3}, d, 1, 1, 1, 0;\nwgmma.commit_group.sync.aligned;\nwgmma.wait_group.sync.aligned 1;\nmov.b32 b2, a1;\nmov.b32 b0, t0;\nmov.b32 b3, t0;\nmov.b32 b1, t1;\n"
        "ld.shared.b32 t0, [%64+1536];\nld.shared.b32 t1, [%64+1664];\nadd.s64 d, %65, 40;\nwgmma.fence.sync.aligned;\nwgmma.mma_async.sync.aligned.m64n128k16.f32.bf16.bf16 {%0, %1, %2, %3, %4, %5, %6, %7, %8, %9, %10, %11, %12, %13, %14, %15, %16, %17, %18, %19, %20, %21, %22, %23, %24, %25, %26, %27, %28, %29, %30, %31, %32, %33, %34, %35, %36, %37, %38, %39, %40, %41, %42, %43, %44, %45, %46, %47, %48, %49, %50, %51, %52, %53, %54, %55, %56, %57, %58, %59, %60, %61, %62, %63}, {b0, b1, b2, b3}, d, 1, 1, 1, 0;\nwgmma.commit_group.sync.aligned;\nwgmma.wait_group.sync.aligned 1;\nmov.b32 a2, b1;\nmov.b32 a0, t0;\nmov.b32 a3, t0;\nmov.b32 a1, t1;\n"
        "ld.shared.b32 t0, [%64+1792];\nld.shared.b32 t1, [%64+1920];\nadd.s64 d, %65, 48;\nwgmma.fence.sync.aligned;\nwgmma.mma_async.sync.aligned.m64n128k16.f32.bf16.bf16 {%0, %1, %2, %3, %4, %5, %6, %7, %8, %9, %10, %11, %12, %13, %14, %15, %16, %17, %18, %19, %20, %21, %22, %23, %24, %25, %26, %27, %28, %29, %30, %31, %32, %33, %34, %35, %36, %37, %38, %39, %40, %41, %42, %43, %44, %45, %46, %47, %48, %49, %50, %51, %52, %53, %54, %55, %56, %57, %58, %59, %60, %61, %62, %63}, {a0, a1, a2, a3}, d, 1, 1, 1, 0;\nwgmma.commit_group.sync.aligned;\nwgmma.wait_group.sync.aligned 1;\nmov.b32 b2, a1;\nmov.b32 b0, t0;\nmov.b32 b3, t0;\nmov.b32 b1, t1;\n"
        "ld.shared.b32 t0, [%64+2048];\nld.shared.b32 t1, [%64+2176];\nadd.s64 d, %65, 56;\nwgmma.fence.sync.aligned;\nwgmma.mma_async.sync.aligned.m64n128k16.f32.bf16.bf16 {%0, %1, %2, %3, %4, %5, %6, %7, %8, %9, %10, %11, %12, %13, %14, %15, %16, %17, %18, %19, %20, %21, %22, %23, %24, %25, %26, %27, %28, %29, %30, %31, %32, %33, %34, %35, %36, %37, %38, %39, %40, %41, %42, %43, %44, %45, %46, %47, %48, %49, %50, %51, %52, %53, %54, %55, %56, %57, %58, %59, %60, %61, %62, %63}, {b0, b1, b2, b3}, d, 1, 1, 1, 0;\nwgmma.commit_group.sync.aligned;\nwgmma.wait_group.sync.aligned 1;\nmov.b32 a2, b1;\nmov.b32 a0, t0;\nmov.b32 a3, t0;\nmov.b32 a1, t1;\n"
        "ld.shared.b32 t0, [%64+2304];\nld.shared.b32 t1, [%64+2432];\nadd.s64 d, %65, 64;\nwgmma.fence.sync.aligned;\nwgmma.mma_async.sync.aligned.m64n96k16.f32.bf16.bf16 {%0, %1, %2, %3, %4, %5, %6, %7, %8, %9, %10, %11, %12, %13, %14, %15, %16, %17, %18, %19, %20, %21, %22, %23, %24, %25, %26, %27, %28, %29, %30, %31, %32, %33, %34, %35, %36, %37, %38, %39, %40, %41, %42, %43, %44, %45, %46, %47}, {a0, a1, a2, a3}, d, 1, 1, 1, 0;\nwgmma.commit_group.sync.aligned;\nwgmma.wait_group.sync.aligned 1;\nmov.b32 b2, a1;\nmov.b32 b0, t0;\nmov.b32 b3, t0;\nmov.b32 b1, t1;\n"
        "ld.shared.b32 t0, [%64+2560];\nld.shared.b32 t1, [%64+2688];\nadd.s64 d, %65, 72;\nwgmma.fence.sync.aligned;\nwgmma.mma_async.sync.aligned.m64n96k16.f32.bf16.bf16 {%0, %1, %2, %3, %4, %5, %6, %7, %8, %9, %10, %11, %12, %13, %14, %15, %16, %17, %18, %19, %20, %21, %22, %23, %24, %25, %26, %27, %28, %29, %30, %31, %32, %33, %34, %35, %36, %37, %38, %39, %40, %41, %42, %43, %44, %45, %46, %47}, {b0, b1, b2, b3}, d, 1, 1, 1, 0;\nwgmma.commit_group.sync.aligned;\nwgmma.wait_group.sync.aligned 1;\nmov.b32 a2, b1;\nmov.b32 a0, t0;\nmov.b32 a3, t0;\nmov.b32 a1, t1;\n"
        "ld.shared.b32 t0, [%64+2816];\nld.shared.b32 t1, [%64+2944];\nadd.s64 d, %65, 80;\nwgmma.fence.sync.aligned;\nwgmma.mma_async.sync.aligned.m64n88k16.f32.bf16.bf16 {%0, %1, %2, %3, %4, %5, %6, %7, %8, %9, %10, %11, %12, %13, %14, %15, %16, %17, %18, %19, %20, %21, %22, %23, %24, %25, %26, %27, %28, %29, %30, %31, %32, %33, %34, %35, %36, %37, %38, %39, %40, %41, %42, %43}, {a0, a1, a2, a3}, d, 1, 1, 1, 0;\nwgmma.commit_group.sync.aligned;\nwgmma.wait_group.sync.aligned 1;\nmov.b32 b2, a1;\nmov.b32 b0, t0;\nmov.b32 b3, t0;\nmov.b32 b1, t1;\n"
        "ld.shared.b32 t0, [%64+3072];\nld.shared.b32 t1, [%64+3200];\nadd.s64 d, %65, 88;\nwgmma.fence.sync.aligned;\nwgmma.mma_async.sync.aligned.m64n88k16.f32.bf16.bf16 {%0, %1, %2, %3, %4, %5, %6, %7, %8, %9, %10, %11, %12, %13, %14, %15, %16, %17, %18, %19, %20, %21, %22, %23, %24, %25, %26, %27, %28, %29, %30, %31, %32, %33, %34, %35, %36, %37, %38, %39, %40, %41, %42, %43}, {b0, b1, b2, b3}, d, 1, 1, 1, 0;\nwgmma.commit_group.sync.aligned;\nwgmma.wait_group.sync.aligned 1;\nmov.b32 a2, b1;\nmov.b32 a0, t0;\nmov.b32 a3, t0;\nmov.b32 a1, t1;\n"
        "ld.shared.b32 t0, [%64+3328];\nld.shared.b32 t1, [%64+3456];\nadd.s64 d, %65, 96;\nwgmma.fence.sync.aligned;\nwgmma.mma_async.sync.aligned.m64n80k16.f32.bf16.bf16 {%0, %1, %2, %3, %4, %5, %6, %7, %8, %9, %10, %11, %12, %13, %14, %15, %16, %17, %18, %19, %20, %21, %22, %23, %24, %25, %26, %27, %28, %29, %30, %31, %32, %33, %34, %35, %36, %37, %38, %39}, {a0, a1, a2, a3}, d, 1, 1, 1, 0;\nwgmma.commit_group.sync.aligned;\nwgmma.wait_group.sync.aligned 1;\nmov.b32 b2, a1;\nmov.b32 b0, t0;\nmov.b32 b3, t0;\nmov.b32 b1, t1;\n"
        "ld.shared.b32 t0, [%64+3584];\nld.shared.b32 t1, [%64+3712];\nadd.s64 d, %65, 104;\nwgmma.fence.sync.aligned;\nwgmma.mma_async.sync.aligned.m64n80k16.f32.bf16.bf16 {%0, %1, %2, %3, %4, %5, %6, %7, %8, %9, %10, %11, %12, %13, %14, %15, %16, %17, %18, %19, %20, %21, %22, %23, %24, %25, %26, %27, %28, %29, %30, %31, %32, %33, %34, %35, %36, %37, %38, %39}, {b0, b1, b2, b3}, d, 1, 1, 1, 0;\nwgmma.commit_group.sync.aligned;\nwgmma.wait_group.sync.aligned 1;\nmov.b32 a2, b1;\nmov.b32 a0, t0;\nmov.b32 a3, t0;\nmov.b32 a1, t1;\n"
        "ld.shared.b32 t0, [%64+3840];\nld.shared.b32 t1, [%64+3968];\nadd.s64 d, %65, 112;\nwgmma.fence.sync.aligned;\nwgmma.mma_async.sync.aligned.m64n72k16.f32.bf16.bf16 {%0, %1, %2, %3, %4, %5, %6, %7, %8, %9, %10, %11, %12, %13, %14, %15, %16, %17, %18, %19, %20, %21, %22, %23, %24, %25, %26, %27, %28, %29, %30, %31, %32, %33, %34, %35}, {a0, a1, a2, a3}, d, 1, 1, 1, 0;\nwgmma.commit_group.sync.aligned;\nwgmma.wait_group.sync.aligned 1;\nmov.b32 b2, a1;\nmov.b32 b0, t0;\nmov.b32 b3, t0;\nmov.b32 b1, t1;\n"
        "ld.shared.b32 t0, [%64+4096];\nld.shared.b32 t1, [%64+4224];\nadd.s64 d, %65, 120;\nwgmma.fence.sync.aligned;\nwgmma.mma_async.sync.aligned.m64n72k16.f32.bf16.bf16 {%0, %1, %2, %3, %4, %5, %6, %7, %8, %9, %10, %11, %12, %13, %14, %15, %16, %17, %18, %19, %20, %21, %22, %23, %24, %25, %26, %27, %28, %29, %30, %31, %32, %33, %34, %35}, {b0, b1, b2, b3}, d, 1, 1, 1, 0;\nwgmma.commit_group.sync.aligned;\nwgmma.wait_group.sync.aligned 1;\nmov.b32 a2, b1;\nmov.b32 a0, t0;\nmov.b32 a3, t0;\nmov.b32 a1, t1;\n"
        "ld.shared.b32 t0, [%64+4352];\nld.shared.b32 t1, [%64+4480];\nadd.s64 d, %65, 128;\nwgmma.fence.sync.aligned;\nwgmma.mma_async.sync.aligned.m64n64k16.f32.bf16.bf16 {%0, %1, %2, %3, %4, %5, %6, %7, %8, %9, %10, %11, %12, %13, %14, %15, %16, %17, %18, %19, %20, %21, %22, %23, %24, %25, %26, %27, %28, %29, %30, %31}, {a0, a1, a2, a3}, d, 1, 1, 1, 0;\nwgmma.commit_group.sync.aligned;\nwgmma.wait_group.sync.aligned 1;\nmov.b32 b2, a1;\nmov.b32 b0, t0;\nmov.b32 b3, t0;\nmov.b32 b1, t1;\n"
        "ld.shared.b32 t0, [%64+4608];\nld.shared.b32 t1, [%64+4736];\nadd.s64 d, %65, 136;\nwgmma.fence.sync.aligned;\nwgmma.mma_async.sync.aligned.m64n64k16.f32.bf16.bf16 {%0, %1, %2, %3, %4, %5, %6, %7, %8, %9, %10, %11, %12, %13, %14, %15, %16, %17, %18, %19, %20, %21, %22, %23, %24, %25, %26, %27, %28, %29, %30, %31}, {b0, b1, b2, b3}, d, 1, 1, 1, 0;\nwgmma.commit_group.sync.aligned;\nwgmma.wait_group.sync.aligned 1;\nmov.b32 a2, b1;\nmov.b32 a0, t0;\nmov.b32 a3, t0;\nmov.b32 a1, t1;\n"
        "ld.shared.b32 t0, [%64+4864];\nld.shared.b32 t1, [%64+4992];\nadd.s64 d, %65, 144;\nwgmma.fence.sync.aligned;\nwgmma.mma_async.sync.aligned.m64n56k16.f32.bf16.bf16 {%0, %1, %2, %3, %4, %5, %6, %7, %8, %9, %10, %11, %12, %13, %14, %15, %16, %17, %18, %19, %20, %21, %22, %23, %24, %25, %26, %27}, {a0, a1, a2, a3}, d, 1, 1, 1, 0;\nwgmma.commit_group.sync.aligned;\nwgmma.wait_group.sync.aligned 1;\nmov.b32 b2, a1;\nmov.b32 b0, t0;\nmov.b32 b3, t0;\nmov.b32 b1, t1;\n"
        "ld.shared.b32 t0, [%64+5120];\nld.shared.b32 t1, [%64+5248];\nadd.s64 d, %65, 152;\nwgmma.fence.sync.aligned;\nwgmma.mma_async.sync.aligned.m64n56k16.f32.bf16.bf16 {%0, %1, %2, %3, %4, %5, %6, %7, %8, %9, %10, %11, %12, %13, %14, %15, %16, %17, %18, %19, %20, %21, %22, %23, %24, %25, %26, %27}, {b0, b1, b2, b3}, d, 1, 1, 1, 0;\nwgmma.commit_group.sync.aligned;\nwgmma.wait_group.sync.aligned 1;\nmov.b32 a2, b1;\nmov.b32 a0, t0;\nmov.b32 a3, t0;\nmov.b32 a1, t1;\n"
        "ld.shared.b32 t0, [%64+5376];\nld.shared.b32 t1, [%64+5504];\nadd.s64 d, %65, 160;\nwgmma.fence.sync.aligned;\nwgmma.mma_async.sync.aligned.m64n48k16.f32.bf16.bf16 {%0, %1, %2, %3, %4, %5, %6, %7, %8, %9, %10, %11, %12, %13, %14, %15, %16, %17, %18, %19, %20, %21, %22, %23}, {a0, a1, a2, a3}, d, 1, 1, 1, 0;\nwgmma.commit_group.sync.aligned;\nwgmma.wait_group.sync.aligned 1;\nmov.b32 b2, a1;\nmov.b32 b0, t0;\nmov.b32 b3, t0;\nmov.b32 b1, t1;\n"
        "ld.shared.b32 t0, [%64+5632];\nld.shared.b32 t1, [%64+5760];\nadd.s64 d, %65, 168;\nwgmma.fence.sync.aligned;\nwgmma.mma_async.sync.aligned.m64n48k16.f32.bf16.bf16 {%0, %1, %2, %3, %4, %5, %6, %7, %8, %9, %10, %11, %12, %13, %14, %15, %16, %17, %18, %19, %20, %21, %22, %23}, {b0, b1, b2, b3}, d, 1, 1, 1, 0;\nwgmma.commit_group.sync.aligned;\nwgmma.wait_group.sync.aligned 1;\nmov.b32 a2, b1;\nmov.b32 a0, t0;\nmov.b32 a3, t0;\nmov.b32 a1, t1;\n"
        "ld.shared.b32 t0, [%64+5888];\nld.shared.b32 t1, [%64+6016];\nadd.s64 d, %65, 176;\nwgmma.fence.sync.aligned;\nwgmma.mma_async.sync.aligned.m64n40k16.f32.bf16.bf16 {%0, %1, %2, %3, %4, %5, %6, %7, %8, %9, %10, %11, %12, %13, %14, %15, %16, %17, %18, %19}, {a0, a1, a2, a3}, d, 1, 1, 1, 0;\nwgmma.commit_group.sync.aligned;\nwgmma.wait_group.sync.aligned 1;\nmov.b32 b2, a1;\nmov.b32 b0, t0;\nmov.b32 b3, t0;\nmov.b32 b1, t1;\n"
        "ld.shared.b32 t0, [%64+6144];\nld.shared.b32 t1, [%64+6272];\nadd.s64 d, %65, 184;\nwgmma.fence.sync.aligned;\nwgmma.mma_async.sync.aligned.m64n40k16.f32.bf16.bf16 {%0, %1, %2, %3, %4, %5, %6, %7, %8, %9, %10, %11, %12, %13, %14, %15, %16, %17, %18, %19}, {b0, b1, b2, b3}, d, 1, 1, 1, 0;\nwgmma.commit_group.sync.aligned;\nwgmma.wait_group.sync.aligned 1;\nmov.b32 a2, b1;\nmov.b32 a0, t0;\nmov.b32 a3, t0;\nmov.b32 a1, t1;\n"
        "ld.shared.b32 t0, [%64+6400];\nld.shared.b32 t1, [%64+6528];\nadd.s64 d, %65, 192;\nwgmma.fence.sync.aligned;\nwgmma.mma_async.sync.aligned.m64n32k16.f32.bf16.bf16 {%0, %1, %2, %3, %4, %5, %6, %7, %8, %9, %10, %11, %12, %13, %14, %15}, {a0, a1, a2, a3}, d, 1, 1, 1, 0;\nwgmma.commit_group.sync.aligned;\nwgmma.wait_group.sync.aligned 1;\nmov.b32 b2, a1;\nmov.b32 b0, t0;\nmov.b32 b3, t0;\nmov.b32 b1, t1;\n"
        "ld.shared.b32 t0, [%64+6656];\nld.shared.b32 t1, [%64+6784];\nadd.s64 d, %65, 200;\nwgmma.fence.sync.aligned;\nwgmma.mma_async.sync.aligned.m64n32k16.f32.bf16.bf16 {%0, %1, %2, %3, %4, %5, %6, %7, %8, %9, %10, %11, %12, %13, %14, %15}, {b0, b1, b2, b3}, d, 1, 1, 1, 0;\nwgmma.commit_group.sync.aligned;\nwgmma.wait_group.sync.aligned 1;\nmov.b32 a2, b1;\nmov.b32 a0, t0;\nmov.b32 a3, t0;\nmov.b32 a1, t1;\n"
        "ld.shared.b32 t0, [%64+6912];\nld.shared.b32 t1, [%64+7040];\nadd.s64 d, %65, 208;\nwgmma.fence.sync.aligned;\nwgmma.mma_async.sync.aligned.m64n24k16.f32.bf16.bf16 {%0, %1, %2, %3, %4, %5, %6, %7, %8, %9, %10, %11}, {a0, a1, a2, a3}, d, 1, 1, 1, 0;\nwgmma.commit_group.sync.aligned;\nwgmma.wait_group.sync.aligned 1;\nmov.b32 b2, a1;\nmov.b32 b0, t0;\nmov.b32 b3, t0;\nmov.b32 b1, t1;\n"
        "ld.shared.b32 t0, [%64+7168];\nld.shared.b32 t1, [%64+7296];\nadd.s64 d, %65, 216;\nwgmma.fence.sync.aligned;\nwgmma.mma_async.sync.aligned.m64n24k16.f32.bf16.bf16 {%0, %1, %2, %3, %4, %5, %6, %7, %8, %9, %10, %11}, {b0, b1, b2, b3}, d, 1, 1, 1, 0;\nwgmma.commit_group.sync.aligned;\nwgmma.wait_group.sync.aligned 1;\nmov.b32 a2, b1;\nmov.b32 a0, t0;\nmov.b32 a3, t0;\nmov.b32 a1, t1;\n"
        "ld.shared.b32 t0, [%64+7424];\nld.shared.b32 t1, [%64+7552];\nadd.s64 d, %65, 224;\nwgmma.fence.sync.aligned;\nwgmma.mma_async.sync.aligned.m64n16k16.f32.bf16.bf16 {%0, %1, %2, %3, %4, %5, %6, %7}, {a0, a1, a2, a3}, d, 1, 1, 1, 0;\nwgmma.commit_group.sync.aligned;\nwgmma.wait_group.sync.aligned 1;\nmov.b32 b2, a1;\nmov.b32 b0, t0;\nmov.b32 b3, t0;\nmov.b32 b1, t1;\n"
        "ld.shared.b32 t0, [%64+7680];\nld.shared.b32 t1, [%64+7808];\nadd.s64 d, %65, 232;\nwgmma.fence.sync.aligned;\nwgmma.mma_async.sync.aligned.m64n16k16.f32.bf16.bf16 {%0, %1, %2, %3, %4, %5, %6, %7}, {b0, b1, b2, b3}, d, 1, 1, 1, 0;\nwgmma.commit_group.sync.aligned;\nwgmma.wait_group.sync.aligned 1;\nmov.b32 a2, b1;\nmov.b32 a0, t0;\nmov.b32 a3, t0;\nmov.b32 a1, t1;\n"
        "ld.shared.b32 t0, [%64+7936];\nld.shared.b32 t1, [%64+8064];\nadd.s64 d, %65, 240;\nwgmma.fence.sync.aligned;\nwgmma.mma_async.sync.aligned.m64n8k16.f32.bf16.bf16 {%0, %1, %2, %3}, {a0, a1, a2, a3}, d, 1, 1, 1, 0;\nwgmma.commit_group.sync.aligned;\nwgmma.wait_group.sync.aligned 1;\nmov.b32 b2, a1;\nmov.b32 b0, t0;\nmov.b32 b3, t0;\nmov.b32 b1, t1;\n"
        "add.s64 d, %65, 248;\nwgmma.fence.sync.aligned;\nwgmma.mma_async.sync.aligned.m64n8k16.f32.bf16.bf16 {%0, %1, %2, %3}, {b0, b1, b2, b3}, d, 1, 1, 1, 0;\nwgmma.commit_group.sync.aligned;\nwgmma.wait_group.sync.aligned 0;\n"
        "}" : "+f"(d[0]), "+f"(d[1]), "+f"(d[2]), "+f"(d[3]), "+f"(d[4]), "+f"(d[5]), "+f"(d[6]), "+f"(d[7]), "+f"(d[8]), "+f"(d[9]), "+f"(d[10]), "+f"(d[11]), "+f"(d[12]), "+f"(d[13]), "+f"(d[14]), "+f"(d[15]), "+f"(d[16]), "+f"(d[17]), "+f"(d[18]), "+f"(d[19]), "+f"(d[20]), "+f"(d[21]), "+f"(d[22]), "+f"(d[23]), "+f"(d[24]), "+f"(d[25]), "+f"(d[26]), "+f"(d[27]), "+f"(d[28]), "+f"(d[29]), "+f"(d[30]), "+f"(d[31]), "+f"(d[32]), "+f"(d[33]), "+f"(d[34]), "+f"(d[35]), "+f"(d[36]), "+f"(d[37]), "+f"(d[38]), "+f"(d[39]), "+f"(d[40]), "+f"(d[41]), "+f"(d[42]), "+f"(d[43]), "+f"(d[44]), "+f"(d[45]), "+f"(d[46]), "+f"(d[47]), "+f"(d[48]), "+f"(d[49]), "+f"(d[50]), "+f"(d[51]), "+f"(d[52]), "+f"(d[53]), "+f"(d[54]), "+f"(d[55]), "+f"(d[56]), "+f"(d[57]), "+f"(d[58]), "+f"(d[59]), "+f"(d[60]), "+f"(d[61]), "+f"(d[62]), "+f"(d[63]) : "r"(pa), "l"(db) : "memory");
}
__device__ __forceinline__ void wgmma_ss80(float (&d)[40], uint64_t da, uint64_t db, int sc) {
    asm volatile("{\n.reg .pred p;\nsetp.ne.b32 p, %42, 0;\n"
        "wgmma.mma_async.sync.aligned.m64n80k16.f32.bf16.bf16 {%0, %1, %2, %3, %4, %5, %6, %7, %8, %9, %10, %11, %12, %13, %14, %15, %16, %17, %18, %19, %20, %21, %22, %23, %24, %25, %26, %27, %28, %29, %30, %31, %32, %33, %34, %35, %36, %37, %38, %39}, %40, %41, p, 1, 1, 0, 1;\n}\n"
        : "+f"(d[0]), "+f"(d[1]), "+f"(d[2]), "+f"(d[3]), "+f"(d[4]), "+f"(d[5]), "+f"(d[6]), "+f"(d[7]), "+f"(d[8]), "+f"(d[9]), "+f"(d[10]), "+f"(d[11]), "+f"(d[12]), "+f"(d[13]), "+f"(d[14]), "+f"(d[15]), "+f"(d[16]), "+f"(d[17]), "+f"(d[18]), "+f"(d[19]), "+f"(d[20]), "+f"(d[21]), "+f"(d[22]), "+f"(d[23]), "+f"(d[24]), "+f"(d[25]), "+f"(d[26]), "+f"(d[27]), "+f"(d[28]), "+f"(d[29]), "+f"(d[30]), "+f"(d[31]), "+f"(d[32]), "+f"(d[33]), "+f"(d[34]), "+f"(d[35]), "+f"(d[36]), "+f"(d[37]), "+f"(d[38]), "+f"(d[39]) : "l"(da), "l"(db), "r"(sc));
}
__device__ __forceinline__ void wgmma_ss8_ta(float (&d)[4], uint64_t da, uint64_t db, int sc) {
    asm volatile("{\n.reg .pred p;\nsetp.ne.b32 p, %6, 0;\n"
        "wgmma.mma_async.sync.aligned.m64n8k16.f32.bf16.bf16 {%0, %1, %2, %3}, %4, %5, p, 1, 1, 1, 0;\n}\n"
        : "+f"(d[0]), "+f"(d[1]), "+f"(d[2]), "+f"(d[3]) : "l"(da), "l"(db), "r"(sc));
}
__device__ __forceinline__ void wgmma_ss80t(float (&d)[40], uint64_t da, uint64_t db, int sc) {
    asm volatile("{\n.reg .pred p;\nsetp.ne.b32 p, %42, 0;\n"
        "wgmma.mma_async.sync.aligned.m64n80k16.f32.bf16.bf16 {%0, %1, %2, %3, %4, %5, %6, %7, %8, %9, %10, %11, %12, %13, %14, %15, %16, %17, %18, %19, %20, %21, %22, %23, %24, %25, %26, %27, %28, %29, %30, %31, %32, %33, %34, %35, %36, %37, %38, %39}, %40, %41, p, 1, 1, 1, 1;\n}\n"
        : "+f"(d[0]), "+f"(d[1]), "+f"(d[2]), "+f"(d[3]), "+f"(d[4]), "+f"(d[5]), "+f"(d[6]), "+f"(d[7]), "+f"(d[8]), "+f"(d[9]), "+f"(d[10]), "+f"(d[11]), "+f"(d[12]), "+f"(d[13]), "+f"(d[14]), "+f"(d[15]), "+f"(d[16]), "+f"(d[17]), "+f"(d[18]), "+f"(d[19]), "+f"(d[20]), "+f"(d[21]), "+f"(d[22]), "+f"(d[23]), "+f"(d[24]), "+f"(d[25]), "+f"(d[26]), "+f"(d[27]), "+f"(d[28]), "+f"(d[29]), "+f"(d[30]), "+f"(d[31]), "+f"(d[32]), "+f"(d[33]), "+f"(d[34]), "+f"(d[35]), "+f"(d[36]), "+f"(d[37]), "+f"(d[38]), "+f"(d[39]) : "l"(da), "l"(db), "r"(sc));
}
__device__ __forceinline__ void wgmma_rs8(float (&d)[4], uint32_t a0, uint32_t a1, uint32_t a2, uint32_t a3, uint64_t db, int sc) {
    asm volatile("{\n.reg .pred p;\nsetp.ne.b32 p, %9, 0;\n"
        "wgmma.mma_async.sync.aligned.m64n8k16.f32.bf16.bf16 {%0, %1, %2, %3}, {%4, %5, %6, %7}, %8, p, 1, 1, 0;\n}\n"
        : "+f"(d[0]), "+f"(d[1]), "+f"(d[2]), "+f"(d[3]) : "r"(a0), "r"(a1), "r"(a2), "r"(a3), "l"(db), "r"(sc));
}
__device__ __forceinline__ void wgmma_rs128(float (&d)[64], uint32_t a0, uint32_t a1, uint32_t a2, uint32_t a3, uint64_t db, int sc) {
    asm volatile("{\n.reg .pred p;\nsetp.ne.b32 p, %69, 0;\n"
        "wgmma.mma_async.sync.aligned.m64n128k16.f32.bf16.bf16 {%0, %1, %2, %3, %4, %5, %6, %7, %8, %9, %10, %11, %12, %13, %14, %15, %16, %17, %18, %19, %20, %21, %22, %23, %24, %25, %26, %27, %28, %29, %30, %31, %32, %33, %34, %35, %36, %37, %38, %39, %40, %41, %42, %43, %44, %45, %46, %47, %48, %49, %50, %51, %52, %53, %54, %55, %56, %57, %58, %59, %60, %61, %62, %63}, {%64, %65, %66, %67}, %68, p, 1, 1, 1;\n}\n"
        : "+f"(d[0]), "+f"(d[1]), "+f"(d[2]), "+f"(d[3]), "+f"(d[4]), "+f"(d[5]), "+f"(d[6]), "+f"(d[7]), "+f"(d[8]), "+f"(d[9]), "+f"(d[10]), "+f"(d[11]), "+f"(d[12]), "+f"(d[13]), "+f"(d[14]), "+f"(d[15]), "+f"(d[16]), "+f"(d[17]), "+f"(d[18]), "+f"(d[19]), "+f"(d[20]), "+f"(d[21]), "+f"(d[22]), "+f"(d[23]), "+f"(d[24]), "+f"(d[25]), "+f"(d[26]), "+f"(d[27]), "+f"(d[28]), "+f"(d[29]), "+f"(d[30]), "+f"(d[31]), "+f"(d[32]), "+f"(d[33]), "+f"(d[34]), "+f"(d[35]), "+f"(d[36]), "+f"(d[37]), "+f"(d[38]), "+f"(d[39]), "+f"(d[40]), "+f"(d[41]), "+f"(d[42]), "+f"(d[43]), "+f"(d[44]), "+f"(d[45]), "+f"(d[46]), "+f"(d[47]), "+f"(d[48]), "+f"(d[49]), "+f"(d[50]), "+f"(d[51]), "+f"(d[52]), "+f"(d[53]), "+f"(d[54]), "+f"(d[55]), "+f"(d[56]), "+f"(d[57]), "+f"(d[58]), "+f"(d[59]), "+f"(d[60]), "+f"(d[61]), "+f"(d[62]), "+f"(d[63]) : "r"(a0), "r"(a1), "r"(a2), "r"(a3), "l"(db), "r"(sc));
}
__device__ __forceinline__ void wgmma_rs88(float (&d)[44], uint32_t a0, uint32_t a1, uint32_t a2, uint32_t a3, uint64_t db, int sc) {
    asm volatile("{\n.reg .pred p;\nsetp.ne.b32 p, %49, 0;\n"
        "wgmma.mma_async.sync.aligned.m64n88k16.f32.bf16.bf16 {%0, %1, %2, %3, %4, %5, %6, %7, %8, %9, %10, %11, %12, %13, %14, %15, %16, %17, %18, %19, %20, %21, %22, %23, %24, %25, %26, %27, %28, %29, %30, %31, %32, %33, %34, %35, %36, %37, %38, %39, %40, %41, %42, %43}, {%44, %45, %46, %47}, %48, p, 1, 1, 1;\n}\n"
        : "+f"(d[0]), "+f"(d[1]), "+f"(d[2]), "+f"(d[3]), "+f"(d[4]), "+f"(d[5]), "+f"(d[6]), "+f"(d[7]), "+f"(d[8]), "+f"(d[9]), "+f"(d[10]), "+f"(d[11]), "+f"(d[12]), "+f"(d[13]), "+f"(d[14]), "+f"(d[15]), "+f"(d[16]), "+f"(d[17]), "+f"(d[18]), "+f"(d[19]), "+f"(d[20]), "+f"(d[21]), "+f"(d[22]), "+f"(d[23]), "+f"(d[24]), "+f"(d[25]), "+f"(d[26]), "+f"(d[27]), "+f"(d[28]), "+f"(d[29]), "+f"(d[30]), "+f"(d[31]), "+f"(d[32]), "+f"(d[33]), "+f"(d[34]), "+f"(d[35]), "+f"(d[36]), "+f"(d[37]), "+f"(d[38]), "+f"(d[39]), "+f"(d[40]), "+f"(d[41]), "+f"(d[42]), "+f"(d[43]) : "r"(a0), "r"(a1), "r"(a2), "r"(a3), "l"(db), "r"(sc));
}
__device__ __forceinline__ void wgmma_rs128k(float (&d)[64], uint32_t a0, uint32_t a1, uint32_t a2, uint32_t a3, uint64_t db, int sc) {
    asm volatile("{\n.reg .pred p;\nsetp.ne.b32 p, %69, 0;\n"
        "wgmma.mma_async.sync.aligned.m64n128k16.f32.bf16.bf16 {%0, %1, %2, %3, %4, %5, %6, %7, %8, %9, %10, %11, %12, %13, %14, %15, %16, %17, %18, %19, %20, %21, %22, %23, %24, %25, %26, %27, %28, %29, %30, %31, %32, %33, %34, %35, %36, %37, %38, %39, %40, %41, %42, %43, %44, %45, %46, %47, %48, %49, %50, %51, %52, %53, %54, %55, %56, %57, %58, %59, %60, %61, %62, %63}, {%64, %65, %66, %67}, %68, p, 1, 1, 0;\n}\n"
        : "+f"(d[0]), "+f"(d[1]), "+f"(d[2]), "+f"(d[3]), "+f"(d[4]), "+f"(d[5]), "+f"(d[6]), "+f"(d[7]), "+f"(d[8]), "+f"(d[9]), "+f"(d[10]), "+f"(d[11]), "+f"(d[12]), "+f"(d[13]), "+f"(d[14]), "+f"(d[15]), "+f"(d[16]), "+f"(d[17]), "+f"(d[18]), "+f"(d[19]), "+f"(d[20]), "+f"(d[21]), "+f"(d[22]), "+f"(d[23]), "+f"(d[24]), "+f"(d[25]), "+f"(d[26]), "+f"(d[27]), "+f"(d[28]), "+f"(d[29]), "+f"(d[30]), "+f"(d[31]), "+f"(d[32]), "+f"(d[33]), "+f"(d[34]), "+f"(d[35]), "+f"(d[36]), "+f"(d[37]), "+f"(d[38]), "+f"(d[39]), "+f"(d[40]), "+f"(d[41]), "+f"(d[42]), "+f"(d[43]), "+f"(d[44]), "+f"(d[45]), "+f"(d[46]), "+f"(d[47]), "+f"(d[48]), "+f"(d[49]), "+f"(d[50]), "+f"(d[51]), "+f"(d[52]), "+f"(d[53]), "+f"(d[54]), "+f"(d[55]), "+f"(d[56]), "+f"(d[57]), "+f"(d[58]), "+f"(d[59]), "+f"(d[60]), "+f"(d[61]), "+f"(d[62]), "+f"(d[63]) : "r"(a0), "r"(a1), "r"(a2), "r"(a3), "l"(db), "r"(sc));
}
__device__ __forceinline__ void wgmma_rs88k(float (&d)[44], uint32_t a0, uint32_t a1, uint32_t a2, uint32_t a3, uint64_t db, int sc) {
    asm volatile("{\n.reg .pred p;\nsetp.ne.b32 p, %49, 0;\n"
        "wgmma.mma_async.sync.aligned.m64n88k16.f32.bf16.bf16 {%0, %1, %2, %3, %4, %5, %6, %7, %8, %9, %10, %11, %12, %13, %14, %15, %16, %17, %18, %19, %20, %21, %22, %23, %24, %25, %26, %27, %28, %29, %30, %31, %32, %33, %34, %35, %36, %37, %38, %39, %40, %41, %42, %43}, {%44, %45, %46, %47}, %48, p, 1, 1, 0;\n}\n"
        : "+f"(d[0]), "+f"(d[1]), "+f"(d[2]), "+f"(d[3]), "+f"(d[4]), "+f"(d[5]), "+f"(d[6]), "+f"(d[7]), "+f"(d[8]), "+f"(d[9]), "+f"(d[10]), "+f"(d[11]), "+f"(d[12]), "+f"(d[13]), "+f"(d[14]), "+f"(d[15]), "+f"(d[16]), "+f"(d[17]), "+f"(d[18]), "+f"(d[19]), "+f"(d[20]), "+f"(d[21]), "+f"(d[22]), "+f"(d[23]), "+f"(d[24]), "+f"(d[25]), "+f"(d[26]), "+f"(d[27]), "+f"(d[28]), "+f"(d[29]), "+f"(d[30]), "+f"(d[31]), "+f"(d[32]), "+f"(d[33]), "+f"(d[34]), "+f"(d[35]), "+f"(d[36]), "+f"(d[37]), "+f"(d[38]), "+f"(d[39]), "+f"(d[40]), "+f"(d[41]), "+f"(d[42]), "+f"(d[43]) : "r"(a0), "r"(a1), "r"(a2), "r"(a3), "l"(db), "r"(sc));
}
__device__ __forceinline__ void wgmma_rs80k(float (&d)[40], uint32_t a0, uint32_t a1, uint32_t a2, uint32_t a3, uint64_t db, int sc) {
    asm volatile("{\n.reg .pred p;\nsetp.ne.b32 p, %45, 0;\n"
        "wgmma.mma_async.sync.aligned.m64n80k16.f32.bf16.bf16 {%0, %1, %2, %3, %4, %5, %6, %7, %8, %9, %10, %11, %12, %13, %14, %15, %16, %17, %18, %19, %20, %21, %22, %23, %24, %25, %26, %27, %28, %29, %30, %31, %32, %33, %34, %35, %36, %37, %38, %39}, {%40, %41, %42, %43}, %44, p, 1, 1, 0;\n}\n"
        : "+f"(d[0]), "+f"(d[1]), "+f"(d[2]), "+f"(d[3]), "+f"(d[4]), "+f"(d[5]), "+f"(d[6]), "+f"(d[7]), "+f"(d[8]), "+f"(d[9]), "+f"(d[10]), "+f"(d[11]), "+f"(d[12]), "+f"(d[13]), "+f"(d[14]), "+f"(d[15]), "+f"(d[16]), "+f"(d[17]), "+f"(d[18]), "+f"(d[19]), "+f"(d[20]), "+f"(d[21]), "+f"(d[22]), "+f"(d[23]), "+f"(d[24]), "+f"(d[25]), "+f"(d[26]), "+f"(d[27]), "+f"(d[28]), "+f"(d[29]), "+f"(d[30]), "+f"(d[31]), "+f"(d[32]), "+f"(d[33]), "+f"(d[34]), "+f"(d[35]), "+f"(d[36]), "+f"(d[37]), "+f"(d[38]), "+f"(d[39]) : "r"(a0), "r"(a1), "r"(a2), "r"(a3), "l"(db), "r"(sc));
}
__device__ __forceinline__ void wgmma_rs128x(float (&d)[32], float (&e)[32], uint32_t a0, uint32_t a1, uint32_t a2, uint32_t a3, uint64_t db, int sc) {
    asm volatile("{\n.reg .pred p;\nsetp.ne.b32 p, %69, 0;\n"
        "wgmma.mma_async.sync.aligned.m64n128k16.f32.bf16.bf16 {%0, %1, %2, %3, %4, %5, %6, %7, %8, %9, %10, %11, %12, %13, %14, %15, %16, %17, %18, %19, %20, %21, %22, %23, %24, %25, %26, %27, %28, %29, %30, %31, %32, %33, %34, %35, %36, %37, %38, %39, %40, %41, %42, %43, %44, %45, %46, %47, %48, %49, %50, %51, %52, %53, %54, %55, %56, %57, %58, %59, %60, %61, %62, %63}, {%64, %65, %66, %67}, %68, p, 1, 1, 1;\n}\n"
        : "+f"(d[0]), "+f"(d[1]), "+f"(d[2]), "+f"(d[3]), "+f"(d[4]), "+f"(d[5]), "+f"(d[6]), "+f"(d[7]), "+f"(d[8]), "+f"(d[9]), "+f"(d[10]), "+f"(d[11]), "+f"(d[12]), "+f"(d[13]), "+f"(d[14]), "+f"(d[15]), "+f"(d[16]), "+f"(d[17]), "+f"(d[18]), "+f"(d[19]), "+f"(d[20]), "+f"(d[21]), "+f"(d[22]), "+f"(d[23]), "+f"(d[24]), "+f"(d[25]), "+f"(d[26]), "+f"(d[27]), "+f"(d[28]), "+f"(d[29]), "+f"(d[30]), "+f"(d[31]), "+f"(e[0]), "+f"(e[1]), "+f"(e[2]), "+f"(e[3]), "+f"(e[4]), "+f"(e[5]), "+f"(e[6]), "+f"(e[7]), "+f"(e[8]), "+f"(e[9]), "+f"(e[10]), "+f"(e[11]), "+f"(e[12]), "+f"(e[13]), "+f"(e[14]), "+f"(e[15]), "+f"(e[16]), "+f"(e[17]), "+f"(e[18]), "+f"(e[19]), "+f"(e[20]), "+f"(e[21]), "+f"(e[22]), "+f"(e[23]), "+f"(e[24]), "+f"(e[25]), "+f"(e[26]), "+f"(e[27]), "+f"(e[28]), "+f"(e[29]), "+f"(e[30]), "+f"(e[31]) : "r"(a0), "r"(a1), "r"(a2), "r"(a3), "l"(db), "r"(sc));
}
__device__ __forceinline__ void wgmma_rs64(float (&d)[32], uint32_t a0, uint32_t a1, uint32_t a2, uint32_t a3, uint64_t db, int sc) {
    asm volatile("{\n.reg .pred p;\nsetp.ne.b32 p, %37, 0;\n"
        "wgmma.mma_async.sync.aligned.m64n64k16.f32.bf16.bf16 {%0, %1, %2, %3, %4, %5, %6, %7, %8, %9, %10, %11, %12, %13, %14, %15, %16, %17, %18, %19, %20, %21, %22, %23, %24, %25, %26, %27, %28, %29, %30, %31}, {%32, %33, %34, %35}, %36, p, 1, 1, 1;\n}\n"
        : "+f"(d[0]), "+f"(d[1]), "+f"(d[2]), "+f"(d[3]), "+f"(d[4]), "+f"(d[5]), "+f"(d[6]), "+f"(d[7]), "+f"(d[8]), "+f"(d[9]), "+f"(d[10]), "+f"(d[11]), "+f"(d[12]), "+f"(d[13]), "+f"(d[14]), "+f"(d[15]), "+f"(d[16]), "+f"(d[17]), "+f"(d[18]), "+f"(d[19]), "+f"(d[20]), "+f"(d[21]), "+f"(d[22]), "+f"(d[23]), "+f"(d[24]), "+f"(d[25]), "+f"(d[26]), "+f"(d[27]), "+f"(d[28]), "+f"(d[29]), "+f"(d[30]), "+f"(d[31]) : "r"(a0), "r"(a1), "r"(a2), "r"(a3), "l"(db), "r"(sc));
}
__device__ __forceinline__ void wgmma_ss64(float (&d)[32], uint64_t da, uint64_t db, int sc) {
    asm volatile("{\n.reg .pred p;\nsetp.ne.b32 p, %34, 0;\n"
        "wgmma.mma_async.sync.aligned.m64n64k16.f32.bf16.bf16 {%0, %1, %2, %3, %4, %5, %6, %7, %8, %9, %10, %11, %12, %13, %14, %15, %16, %17, %18, %19, %20, %21, %22, %23, %24, %25, %26, %27, %28, %29, %30, %31}, %32, %33, p, 1, 1, 0, 1;\n}\n"
        : "+f"(d[0]), "+f"(d[1]), "+f"(d[2]), "+f"(d[3]), "+f"(d[4]), "+f"(d[5]), "+f"(d[6]), "+f"(d[7]), "+f"(d[8]), "+f"(d[9]), "+f"(d[10]), "+f"(d[11]), "+f"(d[12]), "+f"(d[13]), "+f"(d[14]), "+f"(d[15]), "+f"(d[16]), "+f"(d[17]), "+f"(d[18]), "+f"(d[19]), "+f"(d[20]), "+f"(d[21]), "+f"(d[22]), "+f"(d[23]), "+f"(d[24]), "+f"(d[25]), "+f"(d[26]), "+f"(d[27]), "+f"(d[28]), "+f"(d[29]), "+f"(d[30]), "+f"(d[31]) : "l"(da), "l"(db), "r"(sc));
}
__device__ __forceinline__ void wgmma_ss128(float (&d)[64], uint64_t da, uint64_t db, int sc) {
    asm volatile("{\n.reg .pred p;\nsetp.ne.b32 p, %66, 0;\n"
        "wgmma.mma_async.sync.aligned.m64n128k16.f32.bf16.bf16 {%0, %1, %2, %3, %4, %5, %6, %7, %8, %9, %10, %11, %12, %13, %14, %15, %16, %17, %18, %19, %20, %21, %22, %23, %24, %25, %26, %27, %28, %29, %30, %31, %32, %33, %34, %35, %36, %37, %38, %39, %40, %41, %42, %43, %44, %45, %46, %47, %48, %49, %50, %51, %52, %53, %54, %55, %56, %57, %58, %59, %60, %61, %62, %63}, %64, %65, p, 1, 1, 0, 1;\n}\n"
        : "+f"(d[0]), "+f"(d[1]), "+f"(d[2]), "+f"(d[3]), "+f"(d[4]), "+f"(d[5]), "+f"(d[6]), "+f"(d[7]), "+f"(d[8]), "+f"(d[9]), "+f"(d[10]), "+f"(d[11]), "+f"(d[12]), "+f"(d[13]), "+f"(d[14]), "+f"(d[15]), "+f"(d[16]), "+f"(d[17]), "+f"(d[18]), "+f"(d[19]), "+f"(d[20]), "+f"(d[21]), "+f"(d[22]), "+f"(d[23]), "+f"(d[24]), "+f"(d[25]), "+f"(d[26]), "+f"(d[27]), "+f"(d[28]), "+f"(d[29]), "+f"(d[30]), "+f"(d[31]), "+f"(d[32]), "+f"(d[33]), "+f"(d[34]), "+f"(d[35]), "+f"(d[36]), "+f"(d[37]), "+f"(d[38]), "+f"(d[39]), "+f"(d[40]), "+f"(d[41]), "+f"(d[42]), "+f"(d[43]), "+f"(d[44]), "+f"(d[45]), "+f"(d[46]), "+f"(d[47]), "+f"(d[48]), "+f"(d[49]), "+f"(d[50]), "+f"(d[51]), "+f"(d[52]), "+f"(d[53]), "+f"(d[54]), "+f"(d[55]), "+f"(d[56]), "+f"(d[57]), "+f"(d[58]), "+f"(d[59]), "+f"(d[60]), "+f"(d[61]), "+f"(d[62]), "+f"(d[63]) : "l"(da), "l"(db), "r"(sc));
}

__device__ __forceinline__ uint64_t mkdesc(uint32_t lo) { return ((uint64_t)0x40000040u << 32) | lo; }
__device__ __forceinline__ uint32_t tag(uint32_t w, uint32_t ep) { asm("lop3.b32 %0, %0, 1, %1, 0xB8;" : "+r"(w) : "r"(ep)); return w; }
template <int N> __device__ __forceinline__ void pack_part(uint32_t (&p)[32], const float (&v)[N], uint32_t ep) {
#pragma unroll
    for (int i = 0; i < N / 2; i++) p[i] = (i & 3) ? pack2(v[2 * i], v[2 * i + 1]) : tag(pack2(v[2 * i], v[2 * i + 1]), ep);
#pragma unroll
    for (int i = 0; i < N / 2; i++) asm volatile("" : "+r"(p[i]));
}
__device__ __forceinline__ void st_part(uint4* p, const uint32_t* v) {
    asm volatile("{\n.reg .b64 l, h;\n.reg .b128 q;\nmov.b64 l, {%1, %2};\nmov.b64 h, {%3, %4};\nmov.b128 q, {l, h};\nst.relaxed.gpu.global.b128 [%0], q;\n}"
                 ::"l"(p), "r"(v[0]), "r"(v[1]), "r"(v[2]), "r"(v[3]) : "memory");
}
__device__ __forceinline__ void st_peer(uint32_t a, uint32_t x, uint32_t y, uint32_t z, uint32_t w, uint32_t bar) {
    asm volatile("st.async.shared::cluster.mbarrier::complete_tx::bytes.v4.b32 [%0], {%1, %2, %3, %4}, [%5];" ::"r"(a), "r"(x), "r"(y), "r"(z), "r"(w), "r"(bar) : "memory");
}
__device__ __forceinline__ int g4_block(int c, int j) { return c ? j ^ (8 - 2 * c) : 8 + (j & 1); }
__device__ __forceinline__ uint32_t recv_off(int w) { return w ? OFF_XR : OFF_REM; }
__device__ __forceinline__ uint4 ld_part(const void* p) {
    uint4 v;
    asm volatile("{\n.reg .b64 l, h;\n.reg .b128 q;\nld.relaxed.gpu.global.b128 q, [%4];\nmov.b128 {l, h}, q;\nmov.b64 {%0, %1}, l;\nmov.b64 {%2, %3}, h;\n}"
                 : "=r"(v.x), "=r"(v.y), "=r"(v.z), "=r"(v.w) : "l"(p) : "memory");
    return v;
}
__device__ __forceinline__ void ld_part4(uint4 (&u)[4], const uint4* p, int st) {
#pragma unroll
    for (int i = 0; i < 4; i++) u[i] = ld_part(p + i * st);
}
__device__ __forceinline__ uint32_t stale4(const uint4 (&u)[4], uint32_t ep) { return (u[0].x ^ ep) | (u[1].x ^ ep) | (u[2].x ^ ep) | (u[3].x ^ ep); }
__device__ __forceinline__ void fix4(uint4 (&u)[4], const uint4* p, uint32_t ep, int code) {
    unsigned it = 0;
    while (__any_sync(~0u, stale4(u, ep) & 1)) {
        ld_part4(u, p, 128);
        STALE(code)
        if (++it > SPIN_LIMIT) SPIN_FAIL(58)
    }
}
__device__ __forceinline__ void add8(float* v, uint4 u) {
    v[0] += blo(u.x); v[1] += bhi(u.x); v[2] += blo(u.y); v[3] += bhi(u.y);
    v[4] += blo(u.z); v[5] += bhi(u.z); v[6] += blo(u.w); v[7] += bhi(u.w);
}
__device__ __forceinline__ void unpack8(float* v, uint4 u) {
    v[0] = blo(u.x); v[1] = bhi(u.x); v[2] = blo(u.y); v[3] = bhi(u.y); v[4] = blo(u.z); v[5] = bhi(u.z); v[6] = blo(u.w); v[7] = bhi(u.w);
}
__device__ __forceinline__ uint4 add2(uint4 a, uint4 b) { return make_uint4(add2(a.x, b.x), add2(a.y, b.y), add2(a.z, b.z), add2(a.w, b.w)); }
__device__ __forceinline__ void base16(float* v, uint4 b, float2 c, float2 d) {
    v[0] = fmaf(c.x, v[0], blo(b.x)); v[1] = fmaf(c.y, v[1], bhi(b.x)); v[2] = fmaf(c.x, v[2], blo(b.y)); v[3] = fmaf(c.y, v[3], bhi(b.y));
    v[4] = fmaf(d.x, v[4], blo(b.z)); v[5] = fmaf(d.y, v[5], bhi(b.z)); v[6] = fmaf(d.x, v[6], blo(b.w)); v[7] = fmaf(d.y, v[7], bhi(b.w));
}
__device__ __forceinline__ uint32_t split2(float x) { const float h = rbf(x); return pack2(h, x - h); }
__device__ __forceinline__ uint32_t b80_desc(uint32_t dsb, uint32_t wn, uint32_t rn, uint32_t h) {
    const uint32_t wb = dsb + OFF_W + (wn & 7) * 16384 + h * 8192, rm = dsb + OFF_REM + rn * 4096 + h * 2048;
    return (wb >> 4) | ((rm - wb) << 12);
}
constexpr int64_t B80_STEP = 128 - (126 << 16), B80_HALF = 512 - (384 << 16);
__device__ __forceinline__ int g1_block(int n, int j) { return n < 5 ? 2 * n + (j & 1) : 2 * n - 9 - (j & 1); }

template <int OCT>
__device__ __forceinline__ void gemv_tile(float (&d)[4], uint32_t a, uint32_t b, int kb0) {
    uint32_t alo = ((a & 0x3FFFF) >> 4) | 0x10000u, blo_ = ((b & 0x3FFFF) >> 4) | (OCT << 16);
#pragma unroll 1
    for (int s = 0; s < 20; s += 4) {
        const int kb = kb0 + (s >> 2);
        const uint32_t bk = blo_ + (OCT == 7 ? (kb & 1) * 288 + (kb >> 1) * 56 : kb * 64);
        wg_fence();
#pragma unroll
        for (int q = 0; q < 4; q++) wgmma_ss8_ta(d, mkdesc(alo + (s + q) * 128), ((uint64_t)8 << 32) | (bk + q * 2 * OCT), s + q);
        wg_commit();
    }
    wg_wait<0>();
    reg_fence(d);
}

__device__ __forceinline__ void flush_tile(uint32_t st, bf16* dst, int u) {
#pragma unroll
    for (int i = 0; i < 2; i++) {
        const int idx = u + 320 * i, row = idx >> 3, c = idx & 7;
        stg128(dst + (size_t)row * S_ + 8 * c, lds128(st + row * 128 + ((c ^ ((row >> 1) & 7)) << 4)));
    }
}

__device__ __forceinline__ int tid_now() { int t; asm volatile("mov.u32 %0, %%tid.x;" : "=r"(t)); return t; }
__device__ __forceinline__ float zscale(float c) { return c == 0.f ? 0x1p-30f : c; }
__device__ __forceinline__ bool bar_any(int id, bool p) {
    uint32_t r;
    asm volatile("{\n.reg .pred a, b;\nsetp.ne.u32 a, %2, 0;\nbarrier.red.or.pred.aligned b, %1, 128, a;\nselp.u32 %0, 1, 0, b;\n}" : "=r"(r) : "r"(id), "r"((uint32_t)p) : "memory");
    return r != 0;
}

__global__ void __launch_bounds__(NTHR, 1) fused_kernel(const __grid_constant__ Ptrs pp, bf16* __restrict__ out, const __grid_constant__ Maps mp) {
    extern __shared__ __align__(1024) uint8_t smem_raw[];
    const uint32_t sb = s2u(smem_raw), bars = sb + M_BAR, dsb = sb & 0x3FFFF;
    const int id = blockIdx.x, warp = __shfl_sync(0xffffffffu, (int)threadIdx.x >> 5, 0), wg = warp >> 2;
    const long long c0 = clock64();
#define TIDS const int tid = tid_now(), lane = tid & 31, wt = tid & 127, g = lane >> 2, t = lane & 3; (void)wt; (void)g; (void)t;
    TS(threadIdx.x == 0, 0) TG(threadIdx.x == 0, 62)

    if (id >= 128) {
        TIDS
        if (sb & 1023) __trap();
        const int hs = id - 128;
        constexpr int H_B = 204800;
        static_assert(H_B + TAB_BYTES + 8 * VEC_BYTES <= OFF_M, "helper map");
        if (warp < 10 && elect()) { mbar_init(bars + warp * 8, 1); mbar_init(bars + 80 + warp * 8, 1); asm volatile("fence.mbarrier_init.release.cluster;" ::: "memory"); }
        __syncthreads();
        wait_clock(c0, HELP_T);
        uint4 wr[10];
#pragma unroll
        for (int u = 0; u < 10; u++) wr[u] = ldg128(((hs >> 1) ? pp.w2 : pp.w1) + (size_t)(320 * (hs & 1) + (tid >> 4) + 32 * u) * D_ + 512 + 8 * (tid & 15));
        {
            const int r = tid >> 4, c = tid & 15;
            uint4* dst[2];
#pragma unroll
            for (int e = 0; e < 2; e++) {
                const int p = !(hs >> 1) ? r : e && (hs & 1) ? (r & ~14) | ((r & 6) << 1) | ((r & 8) >> 2) : (r & ~30) | ((r & 6) << 2) | ((r & 24) >> 2);
                dst[e] = &g_wr[(((hs >> 1) * 8 + (c >> 1)) * 10 + 5 * (hs & 1)) * 128 + (p & 15) * 8 + ((2 * (p >> 4) + (c & 1)) ^ (p & 7))];
            }
#pragma unroll
            for (int u = 0; u < 10; u++) stg128(reinterpret_cast<uint4*>(reinterpret_cast<uintptr_t>(dst[u >= 6]) ^ (64 * (u & 1))) + (u >> 1) * 128, wr[u]);
        }
        __syncthreads();
        if (warp == 0) signal_cnt(&g_cnt.wr[0], lane, 1);
        __syncthreads();
        if (warp < 5 && elect()) {
            const int un = 5 * hs + warp;
            mbar_expect(bars + warp * 8, 40960);
            tma_ld2(sb + warp * 40960, &mp.w1h, 64 * (un >> 1), 320 * (un & 1), bars + warp * 8);
            tma_ld2(sb + warp * 40960 + 20480, &mp.w1h, 64 * (un >> 1), 320 * (un & 1) + 160, bars + warp * 8);
        }
        if (tid < 320) {
            const uint4* gm = reinterpret_cast<const uint4*>(g_mod + 3 * D_) + tid;
            const unsigned epoch = *(volatile unsigned*)&g_epoch + 1;
            uint4 r[6];
            unsigned it = 0;
            for (;;) {
                uint32_t bad = 0;
#pragma unroll
                for (int i = 0; i < 6; i++) { r[i] = ld_part(gm + (i >> 1) * (D_ / 2) + (i & 1) * 3 * D_); bad |= (r[i].y ^ epoch) | (r[i].w ^ epoch); }
                if (__all_sync(~0u, !bad)) break;
                if (++it > SPIN_LIMIT) SPIN_FAIL(54)
            }
            uint32_t mv[3];
#pragma unroll
            for (int i = 0; i < 3; i++) mv[i] = pack2(__uint_as_float(r[2 * i].x) + __uint_as_float(r[2 * i + 1].x), __uint_as_float(r[2 * i].z) + __uint_as_float(r[2 * i + 1].z));
            const uint32_t sw2 = mv[0], cw = add2(mv[1], 0x3f803f80u), gw = mv[2];
            const float c0 = blo(cw), c1 = bhi(cw), s0 = blo(sw2), s1 = bhi(sw2);
            const float i0 = __frcp_rn(zscale(c0)), i1 = __frcp_rn(zscale(c1));
            const uint32_t ci = pack2(i0, i1), cq = pack2(i0 * i0, i1 * i1);
            const uint32_t a = sb + H_B + ((tid >> 5) & 1) * 4608 + (tid >> 6) * 896 + ((tid >> 2) & 7) * 112 + (tid & 3) * 4;
            sts32(a, ci); sts32(a + 16, pack2(i0 - blo(ci), i1 - bhi(ci)));
            sts32(a + 32, cq); sts32(a + 48, pack2(fmaf(i0, i0, -blo(cq)), fmaf(i1, i1, -bhi(cq))));
            sts32(a + 64, cw); sts32(a + 80, sw2); sts32(a + 96, 0x3f803f80u);
            if ((tid & ~35) == 284) sts32(a + 112, 0);
            const uint32_t v = sb + H_B + TAB_BYTES + (tid < 256 ? (tid >> 5) * VEC_BYTES + (tid & 31) * 8 : ((tid - 256) >> 3) * VEC_BYTES + 256 + (tid & 7) * 8);
            sts64f(v, blo(gw), bhi(gw)); sts64f(v + 320, c0, c1); sts64f(v + 640, s0, s1); sts64f(v + 960, i0, i1);
            float k[5] = {c0 + c1, s0 + s1, fmaf(c0, c0, c1 * c1), fmaf(c0, s0, c1 * s1), fmaf(s0, s0, s1 * s1)};
#pragma unroll 1
            for (int o = 16; o; o >>= 1) {
#pragma unroll
                for (int e = 0; e < 5; e++) k[e] += __shfl_xor_sync(~0u, k[e], o);
            }
            const uint32_t ks = sb + H_B + TAB_BYTES + (lane & 7) * VEC_BYTES + 1280 + (warp >> 1) * 32;
            if ((warp & 1) && lane < 8) { sts128f(ks, k[0], k[1], k[2], k[3]); sts128f(ks + 16, k[4], 0.f, 0.f, 0.f); }
            bar_sync(3, 320);
            if (!(warp & 1) && lane < 8) {
                const float4 o = lds128f(ks);
                sts128f(ks, k[0] + o.x, k[1] + o.y, k[2] + o.z, k[3] + o.w); sts32(ks + 16, __float_as_uint(k[4] + __uint_as_float(lds32(ks + 16))));
            }
            fence_async_smem();
        }
        __syncthreads();
        if (hs == 0 && warp == 15 && elect()) {
            asm volatile("cp.async.bulk.global.shared::cta.bulk_group [%0], [%1], %2;\ncp.async.bulk.commit_group;\ncp.async.bulk.wait_group 0;"
                         ::"l"(g_tab), "r"(sb + H_B), "n"(TAB_BYTES + 8 * VEC_BYTES) : "memory");
            asm volatile("red.release.gpu.global.add.u32 [%0], 1;" ::"l"(&g_cnt.tab[0]) : "memory");
        }
        __syncwarp();
#pragma unroll 1
        for (int i = wg; i < 20; i += 4) {
            const int r = i / 5, b = i - 5 * r, un = 5 * hs + b, u3 = 20 * r + un;
            auto refill = [&](int e, int u, uint32_t fb) {
                mbar_expect(fb, 40960);
                tma_ld2(sb + e * 40960, &mp.w3h, 64 * (u >> 1), 320 * (u & 1), fb);
                tma_ld2(sb + e * 40960 + 20480, &mp.w3h, 64 * (u >> 1), 320 * (u & 1) + 160, fb);
            };
            if (i > 4 && i < 9) {
                bar_sync(1, 512);
                if (warp == 0) {
                    signal_cnt(&g_cnt.uv[0], lane, 1);
                    if (elect()) {
#pragma unroll 1
                        for (int e = 0; e < 5; e++) refill(e, 5 * hs + e, bars + (5 + e) * 8);
                        l2_prefetch(pp.w2 + (size_t)160 * hs * D_, 160 * D_ * 2);
                    }
                    __syncwarp();
                }
            }
            mbar_wait(bars + i * 8, 0);
            float d[4];
            gemv_tile<7>(d, sb + b * 40960, sb + H_B, 5 * (un & 1));
            const int col = 16 * (warp & 3) + g;
            float* dst = r ? g_cs3 + (un & 1) * 1920 + 64 * ((u3 >> 1) - 10) + col : g_uv + (un & 1) * 3 * D_ + 2 * D_ + 64 * (un >> 1) + col;
            if (t == 3) { dst[0] = d[0]; dst[8] = d[2]; }
            if (r == 0 && t == 2) { dst[-2 * D_] = d[0]; dst[8 - 2 * D_] = d[2]; dst[-D_] = d[1]; dst[8 - D_] = d[3]; }
            if (r == 1 || r == 2) {
                bar_sync(4 + wg, 128);
                if (wt == 0) refill(b, u3, bars + (i + 5) * 8);
            }
        }
        __syncthreads();
        if (warp == 0) signal_cnt(&g_cnt.cs[0], lane, 1);
        if (tid == 511) l2_prefetch(pp.w4 + (size_t)432 * hs * D_, 432 * D_ * 2);
        return;
    }

    if (elect()) {
        if (warp == 15) {
            mbar_init(bars + B_IN * 8, 1); mbar_init(bars + B_IN * 8 + 8, 1);
            asm volatile("fence.mbarrier_init.release.cluster;" ::: "memory");
            mbar_expect(bars + B_IN * 8, 131 * 160);
            tma_ld2(sb + OFF_KIN, &mp.k, 80 * (id & 7), 64 * (id >> 3) - 3, bars + B_IN * 8);
            tma_ld2(sb + OFF_VIN, &mp.v, 80 * (id & 7), 64 * (id >> 3), bars + B_IN * 8);
        } else if (warp < 12) {
            const uint32_t n = (0xC44111111881ull >> (4 * warp)) & 15;
#pragma unroll
            for (int i = 0; i < 4; i++) mbar_init(bars + warp * 64 + i * 8, n);
            if (warp == 11) mbar_init(bars + B_XFREE * 8, 16);
            else {
#pragma unroll
                for (int i = 4; i < 8; i++) mbar_init(bars + warp * 64 + i * 8, n);
            }
            asm volatile("fence.mbarrier_init.release.cluster;" ::: "memory");
        }
    }
    asm volatile("" ::"l"(pp.s), "l"(pp.c), "l"(out));
    TR4((threadIdx.x & 31) == 0, warp)
    const int pr = id >> 1;
    const int grp = pr < 4 ? 15 : pr < 36 ? (pr - 4) & 7 : 8 + (pr - 36) % 7;
    const int j = 2 * (pr < 4 ? pr : pr < 36 ? (pr - 4) >> 3 : (pr - 36) / 7) + (id & 1);

    if (wg == 3) {
        TIDS
        const int sw = warp - 12;
        uint32_t ep = ld_cold(&g_epoch);
        TR4(lane == 0, 20 + sw)
        __syncthreads();
        TR4(lane == 0, 30 + sw)
        asm volatile("barrier.cluster.arrive.relaxed.aligned;" ::: "memory");
        if (sw == 0) {
#pragma unroll 1
            for (int n = PF_N0; n < PF_N; n++) {
                wait_clock(c0, PF_T0 + PF_DT * (n - PF_N0));
                if (elect()) {
                    if (n < 8) l2_prefetch((const char*)(n < 4 ? pp.ssm_k : pp.q) + (size_t)id * 20480 + (n & 3) * 5120, 5120);
                    else l2_prefetch((const char*)pp.w_mod + (size_t)id * 38400 + (n - 8) * 4800, 4800);
                }
            }
        } else if (sw == 1) {
            wait_clock(c0, T_SSM);
            if (elect()) {
                mbar_expect(bars + B_SSM * 8, 20480);
                bulk_ld(sb + OFF_SSM, pp.ssm_k + (size_t)5 * id * S_, 20480, bars + B_SSM * 8);
            }
            mbar_wait(bars + B_KVS * 8, 0);
            signal_cnt(&g_cnt.kv[(id & 7) * 32], lane, 1, true);
            TS(lane == 0, 2)
            if (T_Q) wait_clock(c0, T_Q); else mbar_wait(bars + B_RAW * 8, 0);
            if (elect()) {
                mbar_expect(bars + B_QIN * 8, 20480);
                tma_ld3(sb + OFF_QIN, &mp.q, 0, 16 * id, 0, bars + B_QIN * 8);
            }
        } else if (sw == 2) {
            if (elect()) {
#pragma unroll 1
                for (int i = 2; i < (int)(sizeof(Maps) / sizeof(CUtensorMap)); i++) asm volatile("prefetch.tensormap [%0];" ::"l"(&mp.k + i) : "memory");
#pragma unroll 1
                for (int i = B_SUMS; i < B_SIG; i++) mbar_expect(bars + i * 8, i < B_RECV ? 2048 : (i & 3) < 3 ? 8192 : 3072);
            }
            wait_cnt(&g_cnt.kv[(id >> 4) * 32], 16, POLL_NS);
            TS(lane == 0, 4)
            if (elect()) {
                mbar_expect(bars + B_RAW * 8, 12288);
                mbar_expect(bars + B_RAW2 * 8, 8192);
#pragma unroll
                for (int c = 0; c < 5; c++) bulk_ld(sb + OFF_CH + c * CH_BYTES, g_kvT + (size_t)(5 * id + c) * S_, 4096, bars + (c < 3 ? B_RAW : B_RAW2) * 8);
            }
            mbar_wait(bars + B_BK * 8, 0);
            mbar_wait(bars + B_RAW2 * 8, 0);
            if (!T_Q) mbar_wait(bars + B_QIN * 8, 0);
            if (id < 120 && elect()) {
                mbar_expect(bars + B_WM * 8, 40960);
                tma_ld2(sb + OFF_WM, &mp.wmod, 64 * pr, 320 * (id & 1), bars + B_WM * 8);
                tma_ld2(sb + OFF_WM + 20480, &mp.wmod, 64 * pr, 320 * (id & 1) + 160, bars + B_WM * 8);
            }
            TS(lane == 0, 57)
        } else {
            wait_clock(c0, T_KVB);
            if (elect()) {
                mbar_expect(bars + (B_IN + 1) * 8, 131 * 160);
                tma_ld2(sb + OFF_KIN + 10752, &mp.k, 80 * (id & 7), 64 * (id >> 3) + 1021, bars + (B_IN + 1) * 8);
                tma_ld2(sb + OFF_VIN + 10240, &mp.v, 80 * (id & 7), 64 * (id >> 3) + 1024, bars + (B_IN + 1) * 8);
            }
            TS(lane == 0, 53)
            if (lane == 0) sts32(sb + M_EP, ep + 1);
#pragma unroll 1
            for (int m = lane; m < 40; m += 32) {
                const uint4 c = ldg128(pp.c + 320 * (id & 1) + 8 * m);
                uint32_t w[4] = {c.x, c.y, c.z, c.w};
#pragma unroll
                for (int i = 0; i < 4; i++) { const float a = blo(w[i]), b = bhi(w[i]); w[i] = pack2(__fdividef(a, 1.f + __expf(-a)), __fdividef(b, 1.f + __expf(-b))); }
                sts128(sb + OFF_Z + m * 128, w[0], w[1], w[2], w[3]);
#pragma unroll 1
                for (int r = 1; r < 8; r++) sts128(sb + OFF_Z + m * 128 + r * 16, 0, 0, 0, 0);
            }
            fence_async_smem();
        }
        {
            mbar_wait(bars + B_QIN * 8, 0);
            asm volatile("add.u32 %0, %0, 1;" : "+r"(ep));
            TS(wt == 0, 54)
            const int tk = 8 * ((lane >> 1) & 1) + 2 * (lane >> 3) + (lane & 1), ck = 4 * (sw & 1) + ((lane >> 1) & 2);
            const uint32_t src = sb + OFF_QIN + (sw >> 1) * 2048 + tk * 128;
            bf16* dst = g_qT + (size_t)id * 16 * D_ + (32 * sw + 8 * (t & 2) + g) * 16 + 8 * (t & 1);
#pragma unroll
            for (int i = 0; i < 5; i++) {
                uint32_t r[8];
                ldsm4t(src + i * 4096 + ((ck ^ (tk & 7)) << 4), r[0], r[1], r[2], r[3]);
                ldsm4t(src + i * 4096 + (((ck + 1) ^ (tk & 7)) << 4), r[4], r[5], r[6], r[7]);
                stg128(dst + i * 2048, tag(r[0], ep), r[1], r[2], r[3]);
                stg128(dst + i * 2048 + 128, tag(r[4], ep), r[5], r[6], r[7]);
            }
            float s1 = 0.f, s2 = 0.f;
#pragma unroll 2
            for (int i = 0; i < 10; i++) {
                const uint4 w4 = lds128(sb + OFF_QIN + i * 2048 + wt * 16);
                const uint32_t w[4] = {w4.x, w4.y, w4.z, w4.w};
#pragma unroll
                for (int e = 0; e < 4; e++) { const float a = blo(w[e]), b = bhi(w[e]); s1 += a + b; s2 = fmaf(a, a, fmaf(b, b, s2)); }
            }
#pragma unroll
            for (int o = 1; o < 8; o *= 2) { s1 += __shfl_xor_sync(~0u, s1, o); s2 += __shfl_xor_sync(~0u, s2, o); }
            s1 *= 1.f / D_;
            uint32_t rs = pack2(rsqrtf(fmaxf(s2 * (1.f / D_) - s1 * s1, 0.f) + 1e-5f), 0.f);
            if (lane < 8) rs = tag(rs, ep);
            rs = pack2(blo(rs), -s1 * blo(rs));
            const uint32_t sel = lane ? 0x7632 : 0x5410;
            const uint32_t a0 = __shfl_sync(~0u, rs, 0), a1 = __shfl_sync(~0u, rs, 8), a2 = __shfl_sync(~0u, rs, 16), a3 = __shfl_sync(~0u, rs, 24);
            if (lane < 2) stg64(g_qst + lane * S_ + 16 * id + 4 * sw, tag(__byte_perm(a0, a1, sel), ep), __byte_perm(a2, a3, sel));
            TS(wt == 0, 55)
        }
        bar_sync(6, 128);
        if (sw == 3) {
            signal_cnt(&g_cnt.q[(lane & 3) * 32], lane, 4, true);
            TS(lane == 0, 3)
        }
        if (id < 120) {
            mbar_wait(bars + B_WM * 8, 0);
            TS(wt == 0, 56)
            float d[4];
            gemv_tile<8>(d, sb + OFF_WM, sb + OFF_Z, 0);
            const float d2 = __shfl_up_sync(~0u, d[2], 1);
            TS(wt == 0, 7)
            if (t < 2) asm volatile("{\n.reg .b64 v;\nmov.b64 v, {%1, %2};\nst.relaxed.gpu.global.b64 [%0], v;\n}" ::"l"(g_mod + (id & 1) * 6 * D_ + 64 * pr + 16 * sw + g + 8 * t),
                                    "r"(__float_as_uint(t ? d2 : d[0])), "r"(ep) : "memory");
        }
        bar_sync(6, 128);
        asm volatile("setmaxnreg.dec.sync.aligned.u32 32;");
        asm volatile("barrier.cluster.wait.aligned;" ::: "memory");
        if (sw == 2) {
            wait_cnt(&g_cnt.tab[0], 1);
            if (elect()) {
                mbar_expect(bars + B_TAB * 8, TAB_BYTES / 2 + VEC_BYTES);
                bulk_ld(sb + OFF_TAB, g_tab + (j & 1) * (TAB_BYTES / 32), TAB_BYTES / 2, bars + B_TAB * 8);
                bulk_ld(sb + M_GB, g_tab + (TAB_BYTES + j * VEC_BYTES) / 16, VEC_BYTES, bars + B_TAB * 8);
            }
            TS(lane == 0, 5)
            int n = 0;
            auto xslot = [&](int w, int m) {
                mbar_spin(bars + (B_XEMPTY + (n & 7)) * 8, ((n >> 3) & 1) ^ 1);
                return bars + (B_XFULL + (m & 7) + 8 * w) * 8;
            };
#pragma unroll 1
            for (int e = 0; e < 4; e++) {
                const int w = e & 1, tile = grp + 16 * w;
                if (e < 2) wait_cnt(&g_cnt.x[(4 * w + (id & 3)) * 32], 128);
                else wait_cnt(&g_cnt.g1[min(max(tile + min(lane, 2) - 1, 0), 31) * 32], 8);
                TS(lane == 0, 26 + e)
                if (e == 0) mbar_wait(bars + (B_XS + 1) * 8, 0);
#pragma unroll 1
                for (int kb = 0; kb < 10; kb++, n++) {
                    const uint32_t fb = xslot(w, 5 * (e & 2) + kb);
                    TR2(lane == 0, 20 + 10 * e + kb)
                    if (elect()) {
                        mbar_expect(fb, 8192);
                        tma_ld2(sb + OFF_XR + (n & 7) * 8192, e < 2 ? &mp.x1_ld : &mp.t_ld, 64 * (e < 2 ? tile : kb), 64 * (e < 2 ? g1_block(kb, j) : tile), fb);
                    }
                }
            }
#pragma unroll 1
            for (int i = 0; i < 20; i++, n++) {
                const int w = i < XLEAD ? 0 : i >= 20 - XLEAD ? 1 : ((i - XLEAD) & 1) ^ 1;
                const int kb = i < XLEAD ? i : i >= 20 - XLEAD ? i - 10 : w ? (i - XLEAD) >> 1 : (i + XLEAD) >> 1;
                if (kb == 0) { wait_cnt(&g_cnt.g2[(grp + 16 * w) * 32], 8); TS(lane == 0, 30 + w) }
                const uint32_t fb = xslot(w, 20 + kb);
                if (elect()) {
                    mbar_expect(fb, 8192);
                    bulk_ld(sb + OFF_XR + (n & 7) * 8192, &g_x2f[((grp + 16 * w) * 10 + kb) * 512], 8192, fb);
                }
            }
            mbar_wait(bars + B_VEC3 * 8, 0);
            unsigned old = 0;
            if (lane == 0) old = atomicAdd(&g_cnt.done[0], 1u);
            if (__shfl_sync(~0u, old, 0) == 127) {
#pragma unroll 1
                for (int i = lane; i < (int)(sizeof(Counters) / 128); i += 32) reinterpret_cast<unsigned*>(&g_cnt)[i * 32] = 0;
                if (lane == 0) atomicAdd(&g_epoch, 1u);
            }
        } else if (sw == 0) {
            wait_cnt(&g_cnt.wr[0], 4);
            mbar_wait(bars + B_QRDY * 8, 0);
            const uint32_t wf = bars + B_WFULL * 8, we = bars + B_WEMPTY * 8;
#pragma unroll 1
            for (int n = 0; n < 10; n++) {
                if (n == 3) mbar_wait(bars + (B_XS + 1) * 8, 0);
                if (n == 3) mbar_wait(bars + (B_PUB + 1) * 8, 0);
                if (n >= 5) mbar_spin(we + (n - 5) * 8, 0);
                TR2(lane == 0, 70 + n)
                if (elect()) {
                    const uint32_t fb = wf + (n & 7) * 8, dst = sb + OFF_W + (n & 7) * 16384;
                    mbar_expect(fb, 20480);
                    if (n >= 5) {
                        tma_ld5(dst, n < 9 ? &mp.w2a : &mp.w2b, 64 * j, n < 9 ? 4 * (n - 5) : 0, fb);
                        bulk_ld(sb + OFF_REM + (n - 5) * 4096, &g_wr[((8 + j) * 10 + 2 * (n - 5)) * 128], 4096, fb);
                    } else {
#pragma unroll 1
                        for (int h = 0; h < 2; h++) {
                            const int kb = g1_block(2 * n + h, j);
                            tma_ld2(dst + h * 8192, &mp.w1, 64 * j, 64 * kb, fb);
                            bulk_ld(sb + OFF_REM + n * 4096 + h * 2048, &g_wr[(j * 10 + kb) * 128], 2048, fb);
                        }
                    }
                }
            }
#pragma unroll 1
            for (int n = 10; n < 30; n++) {
                if (n == 10) mbar_wait(bars + (B_PUB + 3) * 8, 0);
                if (n == GATE16) mbar_wait(bars + (B_PUB + 5) * 8, 0);
                mbar_spin(we + (n & 7) * 8, ((n >> 3) & 1) ^ 1);
                TR2(lane == 0, 70 + n)
                if (elect()) {
                    const uint32_t dst = sb + OFF_W + (n & 7) * 16384, fb = wf + (n & 7) * 8;
                    mbar_expect(fb, 13824);
                    tma_ld3(dst, &mp.w3a, 0, 32 * (n - 10), 3 * j, fb);
                    tma_ld2(dst + 12288, &mp.w3b, 1536 + 24 * j, 32 * (n - 10), fb);
                }
            }
            mbar_spin(we + 6 * 8, 0);
            if (elect()) mbar_arrive(bars + B_S30 * 8);
#pragma unroll 1
            for (int n = 31; n < 50; n++) {
                const int rem = 96 + 3 * (j >> 1);
                int m0, m1, r0, r1, c0_, c1_;
                if (n < 38) {
                    c0_ = g4_block(0, j); c1_ = g4_block(1, j);
                    m0 = m1 = n == 35;
                    r0 = r1 = n == 35 ? rem : 6 * (j ^ (n >= 34)) + ((0x2004204 >> (4 * (n - 31))) & 15);
                } else {
                    const int e = (n - 38) & 3;
                    c0_ = c1_ = g4_block(2 + ((n - 38) >> 2), j);
                    m0 = 0; m1 = e == 1 ? 1 : e == 3 ? -1 : 0;
                    r0 = 6 * (j ^ (e >> 1)) + 4 * (e & 1); r1 = e == 1 ? rem : r0 + 2;
                }
                mbar_spin(we + (n & 7) * 8, ((n >> 3) & 1) ^ 1);
                if (elect()) {
                    const uint32_t dst = sb + OFF_W + (n & 7) * 16384, fb = wf + (n & 7) * 8;
                    mbar_expect(fb, m1 < 0 ? 8192 : 16384 - 2048 * (m0 + m1));
                    tma_ld2(dst, &mp.w4[m0], 64 * c0_, r0 * (32 >> m0), fb);
                    if (m1 >= 0) tma_ld2(dst + 8192, &mp.w4[m1], 64 * c1_, r1 * (32 >> m1), fb);
                }
            }
#pragma unroll 1
            for (int w = 0; w < 2; w++) {
                const uint4* src = g_part + (size_t)(grp + 16 * w) * 40960;
                mbar_spin(bars + (B_RING + w) * 8, 1);
                if (elect()) {
                    const uint32_t fb = bars + (B_IN + w) * 8, rem = sb + OFF_OUT + w * 10240;
                    mbar_expect(fb, 10240);
                    bulk_ld(rem + 8192, &g_x1f[((grp + 16 * w) * 8 + j) * 640 + 512], 2048, fb);
#pragma unroll 1
                    for (int i = 0; i < 4; i++) bulk_ld(rem + i * 2048, src + ((j >> 2) + 2 * i) * 5120 + 4096 + j * 128, 2048, fb);
                }
            }
        } else {
            const int w = sw >> 1;
#pragma unroll 1
            for (int e = 0; e < 3; e++) {
                mbar_wait(bars + ((e ? B_SIG : B_XS) + w) * 8, e >> 1);
                signal_cnt(e == 0 ? &g_cnt.x[(4 * w + (lane & 3)) * 32] : e == 1 ? &g_cnt.g1[(grp + 16 * w) * 32] : &g_cnt.g2[(grp + 16 * w) * 32], lane, e ? 1 : 4, X_NOFENCE & (4 << e));
                if (elect()) mbar_arrive(bars + (B_PUB + 2 * e + w) * 8);
                TS(lane == 0, 20 + 2 * e + w)
                if (e == 0 && w) {
                    wait_cnt(&g_cnt.uv[0], 4);
#pragma unroll 1
                    for (int c = lane; c < 80; c += 32) {
                        const float* src = g_uv + (c < 64 ? 64 * j + c : 448 + 16 * j + c);
                        const uint32_t u = split2(ldcg32f(src) + ldcg32f(src + 3 * D_)), v = split2(ldcg32f(src + D_) + ldcg32f(src + 4 * D_));
                        const uint32_t s = split2(ldcg32f(src + 2 * D_) + ldcg32f(src + 5 * D_));
                        sts128(sb + OFF_F1 + c * 16, u, __byte_perm(u, v, 0x5410), __byte_perm(v, 0, 0x1032), s);
                        sts128(sb + M_F1 + c * 16, s & 0xffffu, 0, 0, 0);
                    }
                    fence_async_smem();
                    warp_arrive(bars + B_VEC * 8);
                    TS(lane == 0, 9)
                }
            }
        }
        return;
    }

    {
        uint32_t ep;
        {
            TIDS
            ep = ld_cold(&g_epoch);
            const int cp = (tid + 16) % 40, cp1 = tid % 40;
            const uint4 sh0 = ldg128(pp.shift_k + (80 * (id & 7) + 2 * cp1) * 4), sh1 = ldg128(pp.shift_k + (80 * (id & 7) + 2 * cp) * 4);
            uint32_t dd;
            asm volatile("ld.global.nc.u16 %0, [%1];" : "=r"(dd) : "l"(pp.ssm_D + 5 * id + min(wg + 3 * lane, 4)));
            TR4(lane == 0, 40 + warp)
            __syncthreads();
            asm volatile("barrier.cluster.arrive.relaxed.aligned;" ::: "memory");
            asm volatile("add.u32 %0, %0, 1;" : "+r"(ep));
#pragma unroll 1
            for (int hw = 0; hw < 2; hw++) {
                if ((unsigned)(warp - 2 * hw) >= 10) continue;
                const int u = tid - 64 * hw;
                const int c = hw ? cp : cp1, oc = u / 40, line = 31 - 16 * hw - (id >> 3);
                const uint4 sh = hw ? sh1 : sh0;
                const uint32_t st = sb + OFF_ST + hw * 10240, sta = st + c * 256 + ((((6 - 2 * (oc & 3)) ^ (oc >> 2) ^ (line & 1)) ^ (c & 7)) << 4), in = oc * 1280 + c * 4;
                const uint32_t f0 = __byte_perm(sh.x, sh.z, 0x5410), f1 = __byte_perm(sh.x, sh.z, 0x7632), f2 = __byte_perm(sh.y, sh.w, 0x5410), f3 = __byte_perm(sh.y, sh.w, 0x7632);
                uint32_t kk[11], vv[8];
                mbar_spin(bars + (B_IN + hw) * 8, 0);
                TS(tid == 64, 18 + 42 * hw)
#pragma unroll
                for (int i = 0; i < 11; i++) kk[i] = lds32(sb + OFF_KIN + hw * 10752 + in + i * 160);
#pragma unroll
                for (int i = 0; i < 8; i++) vv[i] = lds32(sb + OFF_VIN + hw * 10240 + in + i * 160);
#pragma unroll
                for (int i = 0; i < 8; i++) vv[i] = mul2(fma2(kk[i + 3], f0, fma2(kk[i + 2], f1, fma2(kk[i + 1], f2, mul2(kk[i], f3)))), vv[i]);
                sts128(sta, tag(__byte_perm(vv[0], vv[1], 0x5410), ep), __byte_perm(vv[2], vv[3], 0x5410), __byte_perm(vv[4], vv[5], 0x5410), __byte_perm(vv[6], vv[7], 0x5410));
                sts128(sta + 128, tag(__byte_perm(vv[0], vv[1], 0x7632), ep), __byte_perm(vv[2], vv[3], 0x7632), __byte_perm(vv[4], vv[5], 0x7632), __byte_perm(vv[6], vv[7], 0x7632));
                bar_sync(7 + hw, 320);
                flush_tile(st, g_kvT + (size_t)(80 * (id & 7)) * S_ + 64 * line, u);
                TS(tid == 64 && hw, 1)
            }
            warp_arrive(bars + B_KVS * 8);
            if (tid < 320) sts128(sb + OFF_CH + (tid >> 6) * CH_BYTES + 4096 + (tid & 63) * 16, 0, 0, 0, 0);
            mbar_spin(bars + B_SSM * 8, 0);
            TS(tid == 0, 14)
            uint2 w[7];
            uint32_t pv[7];
#pragma unroll
            for (int i = 0; i < 7; i++) {
                const uint32_t a = sb + OFF_SSM + min(wg + 3 * i, 19) * 1024 + wt * 8;
                w[i] = lds64(a); pv[i] = lds32(a - 4);
            }
#pragma unroll
            for (int i = 0; i < 7; i++) {
                const int un = min(wg + 3 * i, 19);
                sts128(sb + OFF_CH + (un >> 2) * CH_BYTES + OFF_P + (un & 3) * 2048 + wt * 16, __byte_perm(w[i].x, pv[i], 0x7610), __byte_perm(w[i].x, 0, 0x1032), __byte_perm(w[i].y, w[i].x, 0x7610), __byte_perm(w[i].y, 0, 0x1032));
            }
            __syncwarp();
            if (wt < 2 - (wg >> 1)) {
                const uint32_t h = lds32(sb + OFF_SSM + (wg + 3 * wt) * 4096), h0 = pack2(blo(h) + blo(dd), 0.f);
                sts64f(sb + OFF_CH + (wg + 3 * wt) * CH_BYTES + OFF_P, __uint_as_float(h0), __uint_as_float(__byte_perm(h, h0, 0x5432)));
            }
            fence_async_smem();
            warp_arrive(bars + B_BK * 8);
            asm volatile("barrier.cluster.wait.aligned;" ::: "memory");
            mbar_spin(bars + B_BK * 8, 0);
            TS(tid == 0, 15)
        }

#pragma unroll 1
        for (int c = wg; c < 5; c += 3) {
            const uint32_t kvb = sb + OFF_CH + c * CH_BYTES;
            mbar_spin(bars + (c < 3 ? B_RAW : B_RAW2) * 8, 0);
            if (CH2_DELAY && wg == 2) wait_clock(clock64(), CH2_DELAY);
            for (uint32_t it = 0;; it++) {
                const int wt = tid_now() & 127;
                if (!bar_any(1 + wg, ((lds32(kvb + wt * 16) ^ ep) | (lds32(kvb + 2048 + wt * 16) ^ ep)) & 1)) break;
                if (wt == 0) { mbar_expect(bars + (B_RETRY + wg) * 8, 4096); bulk_ld(kvb, g_kvT + (size_t)(5 * id + c) * S_, 4096, bars + (B_RETRY + wg) * 8); }
                mbar_wait(bars + (B_RETRY + wg) * 8, ep >> 31);
                ep ^= 0x80000000u;
                STALE(0)
                if (it > 4096) SPIN_FAIL(57)
            }
            TS(threadIdx.x == 0, c ? 13 : 11)
            float acc[64];
            {
                const int l = tid_now() & 31;
                conv_channel(acc, kvb + OFF_P + (8 * (warp & 3) + (l >> 2) - 2 * (l & 3)) * 4, (((uint64_t)0xC0000010u << 32) | ((kvb & 0x3FFFF) >> 4) | 0x10000u) + pp.nil);
            }
            TS(threadIdx.x == 0, c ? 16 : 12)
            if (c >= 3) {
#pragma unroll 1
                for (int e = 0; e < 3; e++) mbar_spin(bars + (B_RING + e) * 8, 0);
            }
            TIDS
            const int e = 127 - 8 * (lane >> 4) - (lane & 7), u0 = (warp & 3) + 8 * (e >> 2) + (e & 3) + 4 * ((lane >> 3) & 1);
            const uint32_t ring = sb + OFF_RING + c * 16384 + (warp & 3) * 4096, wa = ring + (u0 ^ ((u0 >> 1) & 4)) * 16;
            if (lane < (warp & 3)) sts128(ring + lane * 16, 0, 0, 0, 0);
#pragma unroll
            for (int i = 0; i < 8; i++)
                stsm4t(i == 0 && u0 >= 256 ? sb + M_NUL : wa - 512 * i, pack2(acc[8 * i], acc[8 * i + 1]), pack2(acc[8 * i + 2], acc[8 * i + 3]),
                       pack2(acc[8 * i + 4], acc[8 * i + 5]), pack2(acc[8 * i + 6], acc[8 * i + 7]));
            warp_arrive(bars + (B_RING + c) * 8);
        }
        fence_async_smem();
        TIDS
        if (warp == 8) {
            wait_cnt(&g_cnt.q[(id & 3) * 32], 128);
            if (elect()) {
                mbar_expect(bars + B_QRDY * 8, 28672);
                tma_ld2(sb + OFF_QT, &mp.qT, 80 * id, 0, bars + B_QRDY * 8);
                bulk_ld(sb + OFF_QT + 20480, g_qst, 8192, bars + B_QRDY * 8);
            }
            TS(lane == 0, 8)
        } else if (warp == 9) {
            const int v = min(lane / 5, 3);
            const uint2* gm = g_mod + (v + (v == 3)) * D_ + 5 * id + lane % 5;
            const unsigned epoch = lds32(sb + M_EP);
            uint2 r0, r1;
            unsigned it = 0;
            do {
                r0 = ld_mod(gm); r1 = ld_mod(gm + 6 * D_);
                if (++it > SPIN_LIMIT) SPIN_FAIL(55)
            } while (!__all_sync(~0u, r0.y == epoch && r1.y == epoch));
            const float m0 = __uint_as_float(r0.x), m1 = __uint_as_float(r1.x);
            const float m = rbf(m0 + m1), p = rbf(1.f + m);
            const float cz = zscale(__shfl_sync(~0u, p, 15 + lane % 5)), ga = __shfl_sync(~0u, m, 10 + lane % 5);
            if (lane < 15) sts32(sb + M_AB + lane % 5 * 16 + v * 4, lane < 10 ? __float_as_uint(cz * ga * (lane < 5 ? m : p)) : pack2(cz, cz));
            warp_arrive(bars + B_MODR * 8);
            TS(lane == 0, 6)
        }
        mbar_spin(bars + B_QRDY * 8, 0);
        mbar_spin(bars + B_MODR * 8, 0);
#pragma unroll 1
        for (int hf = 0; hf < 2; hf++) {
            const int u = wt + 128 * hf;
            uint4 rs = lds128(sb + OFF_QT + 20480 + u * 16), nm = lds128(sb + OFF_QT + 24576 + u * 16);
            uint32_t it = 0;
            while (__any_sync(~0u, ((rs.x ^ ep) | (rs.z ^ ep) | (nm.x ^ ep) | (nm.z ^ ep)) & 1)) {
                rs = ld_part(g_qst + 8 * u); nm = ld_part(g_qst + S_ + 8 * u);
                STALE(1)
                if (++it > SPIN_LIMIT) SPIN_FAIL(53)
            }
            const int c1 = wg == 2 ? 2 + !EPI_SPLIT : 5;
#pragma unroll 1
            for (int c = wg == 2 ? 0 : EPI_SPLIT && wg == hf ? 2 : 3 + wg; c < c1; c += wg == 2 ? 1 : c == 2 ? 1 + wg : 2) {
                uint4 q = lds128(sb + OFF_QT + (u >> 1) * 160 + c * 32 + (u & 1) * 16);
                const float4 ab = lds128f(sb + M_AB + c * 16);
                mbar_spin(bars + (B_RING + c) * 8, 0);
                const uint32_t ra = sb + OFF_RING + c * 16384 + (u ^ ((u >> 1) & 4)) * 16;
                const uint4 p0 = lds128(ra), p1 = lds128(ra + 4096), p2 = lds128(ra + 8192), p3 = lds128(ra + 12288);
                while (__any_sync(~0u, (q.x ^ ep) & 1)) {
                    q = ld_part(g_qT + ((u >> 1) * D_ + 5 * id + c) * 16 + 8 * (u & 1));
                    STALE(2)
                    if (++it > SPIN_LIMIT) SPIN_FAIL(52)
                }
                uint32_t gq[4] = {q.x, q.y, q.z, q.w}, gg[4] = {fma2(q.x, rs.x, nm.x), fma2(q.y, rs.y, nm.y), fma2(q.z, rs.z, nm.z), fma2(q.w, rs.w, nm.w)};
#pragma unroll
                for (int i = 0; i < 4; i++) {
                    gg[i] = pack2(fmaf(blo(gg[i]), ab.y, ab.x), fmaf(bhi(gg[i]), ab.y, ab.x));
                    gq[i] = mul2(gq[i], __float_as_uint(ab.z));
                }
                stg128(g_x1T + (size_t)(5 * id + c) * S_ + 8 * u,
                       fma2(gg[0], add2(add2(p0.x, p1.x), add2(p2.x, p3.x)), gq[0]), fma2(gg[1], add2(add2(p0.y, p1.y), add2(p2.y, p3.y)), gq[1]),
                       fma2(gg[2], add2(add2(p0.z, p1.z), add2(p2.z, p3.z)), gq[2]), fma2(gg[3], add2(add2(p0.w, p1.w), add2(p2.w, p3.w)), gq[3]));
            }
            warp_arrive(bars + (B_XS + hf) * 8);
            TS(tid == 0, hf ? 17 : 58)
            TS(tid == 256 && hf, 52)
        }
    }

    const uint32_t nil = pp.nil;
    const int wq = warp & 3;
    if (wg == 2) {
        TIDS
        const uint32_t lrow = sb + OFF_XR + ((lane & 7) + 8 * (lane >> 4)) * 128 + (((2 * wq + ((lane >> 3) & 1)) ^ (lane & 7)) << 4);
        const uint32_t nr = ((j ^ (j >> 2)) & 1) ? 9 : 4;
        mbar_wait(bars + B_TAB * 8, 0);
        float4 k = lds128f(sb + M_KS);
        float k4 = __uint_as_float(lds32(sb + M_KS + 16));
#pragma unroll
        for (int w = 1; w < 5; w++) {
            const float4 o = lds128f(sb + M_KS + w * 32);
            k.x += o.x; k.y += o.y; k.z += o.z; k.w += o.w; k4 += __uint_as_float(lds32(sb + M_KS + w * 32 + 16));
        }
#pragma unroll 1
        for (int uw = 0; uw < 2; uw++) {
            const int tile = grp + 16 * uw;
            float sl[4], sq[4];
            uint32_t z[16], zz[16];
            zero(sl); zero(sq);
#pragma unroll 1
            for (int i = 0; i < 5; i++) {
                const uint32_t xs = (2 * uw + i) & 7;
                const uint64_t tb = (((uint64_t)8 << 32) | ((dsb + OFF_TAB) >> 4) | (7u << 16)) + pp.nil + i * 56;
                mbar_spin(bars + (B_XFULL + 8 * uw + i) * 8, 0);
                wg_wait<0>();
#pragma unroll
                for (int q = 0; q < 4; q++) ldsm4t(lrow + xs * 8192 + q * 2048, z[4 * q], z[4 * q + 1], z[4 * q + 2], z[4 * q + 3]);
                if (lane == 0 && i != nr) mbar_arrive_after(bars + (B_XEMPTY + xs) * 8, z[0] | z[4], z[8] | z[12], nil);
#pragma unroll
                for (int e = 0; e < 16; e++) zz[e] = mul2(z[e], z[e]);
                wg_fence();
#pragma unroll
                for (int q = 0; q < 4; q++) wgmma_rs8(sl, z[4 * q], z[4 * q + 1], z[4 * q + 2], z[4 * q + 3], tb + q * 14, 1);
#pragma unroll
                for (int q = 0; q < 4; q++) wgmma_rs8(sq, zz[4 * q], zz[4 * q + 1], zz[4 * q + 2], zz[4 * q + 3], tb + q * 14, 1);
                wg_commit();
                if (i == (j >> 1)) {
#pragma unroll
                    for (int q = 0; q < 4; q++) stg128(&g_x1f[(tile * 8 + j) * 640 + q * 128 + wt], z[4 * q], z[4 * q + 1], z[4 * q + 2], z[4 * q + 3]);
                }
            }
            wg_wait<0>();
            reg_fence(sl); reg_fence(sq);
            TS(wt == 0 && !uw, 59)
            float v[4];
#pragma unroll
            for (int h = 0; h < 2; h++) {
                v[2 * h] = t == 0 ? sl[2 * h] + sl[2 * h + 1] : t == 1 ? sq[2 * h] + sq[2 * h + 1] : sl[2 * h];
                v[2 * h + 1] = t == 2 ? sl[2 * h + 1] : sq[2 * h];
            }
            const uint32_t rows = sb + OFF_ROW + uw * 2048;
            st_peer(peer_addr(rows + wt * 16), __float_as_uint(v[0]), __float_as_uint(v[1]), __float_as_uint(v[2]), __float_as_uint(v[3]), peer_addr(bars + (B_SUMS + uw) * 8));
            mbar_wait(bars + (B_SUMS + uw) * 8, 0);
            const float4 o = lds128f(rows + wt * 16);
            const int l0 = lane & ~3;
            const bool hi = t >= 2;
            float w[8];
#pragma unroll
            for (int e = 0; e < 4; e++) {
                const float a0 = __shfl_sync(~0u, v[0] + o.x, l0 + e), a1 = __shfl_sync(~0u, v[2] + o.z, l0 + e);
                w[e] = hi ? a1 : a0;
                if (e >= 2) { const float b0 = __shfl_sync(~0u, v[1] + o.y, l0 + e), b1 = __shfl_sync(~0u, v[3] + o.w, l0 + e); w[4 + e] = hi ? b1 : b0; }
            }
            const float s1 = w[0], s2 = w[1], scc = w[2], scs = w[6], sc = w[3], sqq = w[7];
            const float m1 = s1 * (1.f / D_), va = fmaxf(s2 * (1.f / D_) - m1 * m1, 0.f) + 1e-5f, r = rsqrtf(va);
            const float m2 = (r * (sc - m1 * k.x) + k.y) * (1.f / D_);
            const float e2 = (r * (r * (sqq + m1 * (m1 * k.z - 2.f * scc)) + 2.f * (scs - m1 * k.w)) + k4) * (1.f / D_);
            const float r2 = 0.5f * rsqrtf(fmaxf(e2 - m2 * m2, 0.f) + 1e-5f);
            const uint32_t fa = split2(-m1), fb = split2(va * r), fc = split2(-m2 * va * r);
            const uint32_t ca = rows + (16 * wq + g + 8 * hi) * 32;
            if (t & 1) sts128(ca + 16, fc >> 16, __float_as_uint(r * r2), __float_as_uint(r), __float_as_uint(-m1 * r));
            else sts128(ca, __byte_perm(fa, 0, 0x1010), __byte_perm(fa, fb, 0x5432), fb, __byte_perm(fc, 0, 0x1010));
            warp_arrive(bars + (B_COEF + uw) * 8);
            {
                uint32_t r0, r1, r2, r3;
                const uint32_t xs = (2 * uw + nr) & 7;
                mbar_spin(bars + (B_XFULL + 8 * uw + (nr & 7)) * 8, nr >> 3);
                ldsm4t(lrow + xs * 8192 + (j & 3) * 2048, r0, r1, r2, r3);
                stg128(&g_x1f[(tile * 8 + j) * 640 + 512 + wt], r0, r1, r2, r3);
                if (lane == 0) mbar_arrive_after(bars + (B_XEMPTY + xs) * 8, r0, 0, nil);
                warp_arrive(bars + (B_RES + uw) * 8);
            }
        }
        asm volatile("setmaxnreg.dec.sync.aligned.u32 32;");
        {
            wait_cnt(&g_cnt.cs[0], 4);
            uint32_t s[2];
#pragma unroll
            for (int i = 0; i < 2; i++) {
                const int c = min(wt + 128 * i, 215);
                const float* src = g_cs3 + (c < 192 ? 192 * j + c : 1344 + 24 * j + c);
                s[i] = split2(ldcg32f(src) + ldcg32f(src + 1920));
            }
            asm volatile("" : "+r"(s[0]), "+r"(s[1]));
            bar_sync(3, 128);
            if (wt == 0) mbar_arrive(bars + B_VEC3 * 8);
            TS(wt == 0, 19)
            mbar_wait(bars + B_S30 * 8, 0);
#pragma unroll
            for (int i = 0; i < 2; i++) sts128(sb + OFF_W + 6 * 16384 + min(wt + 128 * i, 215) * 16, s[i], s[i] & 0xffffu, 0, 0);
            fence_async_smem();
            bar_sync(3, 128);
            if (wt == 0) mbar_arrive(bars + (B_WFULL + 6) * 8);
        }
#pragma unroll 1
        for (int uw = 0; uw < 2; uw++) {
            const int tile = grp + 16 * uw;
            const uint32_t ep = lds32(sb + M_EP), in = sb + OFF_OUT + uw * 10240 + wt * 16, sr = in - lane * 16;
            mbar_wait(bars + (B_IN + uw) * 8, 1);
            float r[8];
#pragma unroll
            for (int h = 0; h < 2; h++) {
                uint4 a = lds128(in + h * 4096), b = lds128(in + h * 4096 + 2048);
                uint32_t it = 0;
                while (__any_sync(~0u, ((a.x ^ ep) | (b.x ^ ep)) & 1)) {
                    const uint4* p = g_part + (size_t)tile * 40960 + ((j >> 2) + 4 * h) * 5120 + 4096 + j * 128 + wt;
                    a = ld_part(p); b = ld_part(p + 10240);
                    STALE(3)
                    if (++it > SPIN_LIMIT) SPIN_FAIL(58)
                }
                if (h) add8(r, add2(a, b)); else unpack8(r, add2(a, b));
            }
            base16(r, lds128(in + 8192), lds64f(sb + M_GB + (64 + 2 * t) * 4), lds64f(sb + M_GB + (72 + 2 * t) * 4));
            __syncwarp();
            stsm4(sr + (lane & 15) * 32 + (((lane >> 4) ^ ((lane >> 2) & 1)) << 4), pack2(r[0], r[1]), pack2(r[2], r[3]), pack2(r[4], r[5]), pack2(r[6], r[7]));
            __syncwarp();
            stg128(out + (size_t)(64 * tile + 16 * wq + (lane >> 1)) * D_ + 512 + 16 * j + 8 * (lane & 1), lds128(sr + (lane >> 1) * 32 + (((lane & 1) ^ ((lane >> 3) & 1)) << 4)));
            __syncwarp();
        }
        if (wq == 0) {
#pragma unroll 1
            for (int w = 0; w < 2; w++) {
                uint32_t it = 0;
                while (!mbar_try(bars + (B_OWN + w) * 8, 0)) { if (++it > SPIN_LIMIT) SPIN_FAIL(56) }
            }
        }
        return;
    }

    TIDS
    const int uw = wg, tile = grp + 16 * uw, row0 = 64 * tile + 16 * wq;
    const bool leader = wt == 0; (void)leader;
    const uint32_t xfull = bars + (B_XFULL + 8 * uw) * 8, xempty = bars + B_XEMPTY * 8, wfull = bars + B_WFULL * 8, wempty = bars + B_WEMPTY * 8;
    const uint64_t dz = mkdesc(0) + pp.nil;
    auto xwait = [&](uint32_t n) { mbar_spin(xfull + (n & 7) * 8, (n >> 3) & 1); };
    {
        float acc[40];
        uint32_t res[20];
        const uint32_t two = (((j ^ (j >> 2)) & 1) ? 0x1E0u : 0x3E0u) << 1;
        {
            zero(acc);
            uint64_t bd = dz + b80_desc(dsb, 0, 0, 0);
            mbar_spin(wfull, 0);
            xwait(0);
            TS(leader, 32 + uw)
#pragma unroll 1
            for (int i = 0; i < 5; i++) {
                const uint32_t xs = (2 * uw + 2 * i) & 7;
                const uint64_t alo = dz + (((dsb + OFF_XR + xs * 8192) >> 4) | 0x10000u);
#pragma unroll
                for (int h = 0; h < 2; h++) {
                    const uint32_t nn = min(2 * i + h + 1, 9);
                    const bool ok = mbar_test(xfull + (nn & 7) * 8, nn >> 3), okw = !h || mbar_test(wfull + min(i + 1, 4) * 8, 0);
                    wg_fence();
#pragma unroll
                    for (int q = 0; q < 4; q++) wgmma_ss80t(acc, alo + h * 512 + q * 128, bd + q * B80_STEP, 1);
                    wg_commit();
                    bd = bd + (uint64_t)B80_HALF;
                    wg_wait<1>();
                    if (lane < ((two >> (2 * i + h)) & 1) + (h || i)) mbar_arrive(xempty + ((xs + h - 1) & 7) * 8);
                    if (!h && i && lane == 0) mbar_arrive(wempty + (i - 1) * 8);
                    if (!ok) xwait(nn);
                    if (!okw) mbar_spin(wfull + min(i + 1, 4) * 8, 0);
                    TR(leader, 100 + 10 * uw + 2 * i + h)
                }
            }
        }
        float al[2], r1[2], n1[2];
        {
            mbar_spin(bars + (B_COEF + uw) * 8, 0);
            TS(leader && !uw, 10)
            uint32_t fa[4];
#pragma unroll
            for (int h = 0; h < 2; h++) {
                const uint32_t ca = sb + OFF_ROW + uw * 2048 + (16 * wq + g + 8 * h) * 32;
                const float4 c4 = lds128f(ca + 16);
                fa[h] = lds32(ca + t * 4);
                fa[2 + h] = t ? 0 : __float_as_uint(c4.x);
                al[h] = c4.y; r1[h] = c4.z; n1[h] = c4.w;
            }
            mbar_spin(bars + B_VEC * 8, 0);
            wg_fence();
            wgmma_rs80k(acc, fa[0], fa[1], fa[2], fa[3], ((uint64_t)8 << 32) | ((dsb + OFF_F1) >> 4) | (((M_F1 - OFF_F1) >> 4) << 16), 1);
            wg_commit();
        }
        wg_wait<0>();
        reg_fence(acc);
        if (lane <= (two >> 10)) mbar_arrive(xempty + ((2 * uw + 9) & 7) * 8);
        if (lane == 0) mbar_arrive(wempty + 4 * 8);
        TS(leader, 34 + uw)
        {
            bf16* const trow = g_t + (size_t)(row0 + g + 2) * D_;
#pragma unroll
            for (int b = 0; b < 3; b++) {
                uint32_t p[8];
#pragma unroll
                for (int ii = 0; ii < 4; ii++) {
                    const int i = 4 * b + ii;
                    if (i >= 10) continue;
#pragma unroll
                    for (int h = 0; h < 2; h++) p[(i & 3) + 4 * h] = pack2(gelu2(acc[4 * i + 2 * h] * al[h]), gelu2(acc[4 * i + 2 * h + 1] * al[h]));
                }
                if (b < 2) {
                    const int gr = (2 * j + b) / 5, sh = (gr & 1) ? -1 - (gr >> 1) : 1 + (gr >> 1);
                    bf16* dst = trow + 64 * j + 32 * b + 8 * t;
                    stg128(dst + sh * D_, p[0], p[1], p[2], p[3]);
                    stg128(dst + (sh + 8) * D_, p[4], p[5], p[6], p[7]);
                    if (row0 + g < sh || row0 + g + 8 >= S_ + sh) stg128(dst + (sh > 0 ? 0 : 8) * D_, 0, 0, 0, 0);
                } else {
                    bf16* dst = trow + 512 + 16 * j + 4 * t;
                    stg64(dst - 2 * D_, p[0], p[1]);
                    stg64(dst + 6 * D_, p[4], p[5]);
                    if (row0 + g + 8 >= S_ - 2) stg64(dst + 8 * D_, 0, 0);
                }
            }
        }
        warp_arrive(bars + (B_SIG + uw) * 8);
        TS(leader, 36 + uw)
        mbar_spin(bars + (B_RES + uw) * 8, 0);
#pragma unroll
        for (int i = 0; i < 5; i++) {
            const uint4 v = ldcg128(&g_x1f[(tile * 8 + j) * 640 + i * 128 + wt]);
            res[4 * i] = v.x; res[4 * i + 1] = v.y; res[4 * i + 2] = v.z; res[4 * i + 3] = v.w;
        }
#pragma unroll
        for (int i = 0; i < 10; i++) {
            const float2 c = lds64f(sb + M_C + (8 * i + 2 * t) * 4), s = lds64f(sb + M_SB + (8 * i + 2 * t) * 4);
#pragma unroll
            for (int h = 0; h < 2; h++) {
                acc[4 * i + 2 * h] = fmaf(blo(res[2 * i + h]), r1[h], fmaf(n1[h], c.x, s.x));
                acc[4 * i + 2 * h + 1] = fmaf(bhi(res[2 * i + h]), r1[h], fmaf(n1[h], c.y, s.y));
            }
        }
        mbar_spin(wfull + 5 * 8, 0);
        xwait(10);
#pragma unroll 1
        for (int i = 0; i < 5; i++) {
            const uint32_t wn = 5 + i, xs = (4 + 2 * uw + 2 * i) & 7;
            const uint64_t alo = dz + (((dsb + OFF_XR + xs * 8192) >> 4) | 0x10000u), bd = dz + b80_desc(dsb, wn, i, 0);
#pragma unroll
            for (int h = 0; h < 2; h++) {
                const uint32_t nn = min(11 + 2 * i + h, 19), wx = min(wn + 1, 9u);
                const bool ok = mbar_test(xfull + (nn & 7) * 8, (nn >> 3) & 1), okw = !h || mbar_test(wfull + (wx & 7) * 8, wx >> 3);
                wg_fence();
#pragma unroll
                for (int q = 0; q < 4; q++) wgmma_ss80(acc, alo + h * 512 + q * 2, bd + h * B80_HALF + q * B80_STEP, 1);
                wg_commit();
                wg_wait<1>();
                if (lane < 2 && (h || i)) mbar_arrive(xempty + ((xs + h - 1) & 7) * 8);
                if (!h && i && lane == 0) mbar_arrive(wempty + ((wn - 1) & 7) * 8);
                if (!ok) xwait(nn);
                if (!okw) mbar_spin(wfull + (wx & 7) * 8, wx >> 3);
                TR(leader, (uw ? 86 : 20) + 2 * i + h)
            }
        }
        wg_wait<0>();
        reg_fence(acc);
        if (lane < 2) mbar_arrive(xempty + ((29 + 10 * uw) & 7) * 8);
        if (lane == 0) mbar_arrive(wempty + (9 & 7) * 8);
        TS(leader, 38 + uw)
        float a0 = 0.f, b0 = 0.f, a1 = 0.f, b1 = 0.f;
#pragma unroll
        for (int i = 0; i < 5; i++) {
            uint32_t p[4];
#pragma unroll
            for (int e = 0; e < 4; e++) p[e] = pack2(acc[8 * i + 2 * e], acc[8 * i + 2 * e + 1]);
            stg128(&g_x2f[(tile * 40 + (i < 4 ? 4 * j + i : 32 + j)) * 128 + wt], p[0], p[1], p[2], p[3]);
#pragma unroll
            for (int e = 0; e < 4; e += 2) {
                const float u0 = blo(p[e]), u1 = bhi(p[e]), v0 = blo(p[e + 1]), v1 = bhi(p[e + 1]);
                a0 += u0 + u1; b0 = fmaf(u0, u0, fmaf(u1, u1, b0));
                a1 += v0 + v1; b1 = fmaf(v0, v0, fmaf(v1, v1, b1));
            }
        }
#pragma unroll
        for (int o = 1; o < 4; o *= 2) {
            a0 += __shfl_xor_sync(~0u, a0, o); b0 += __shfl_xor_sync(~0u, b0, o);
            a1 += __shfl_xor_sync(~0u, a1, o); b1 += __shfl_xor_sync(~0u, b1, o);
        }
        if (t < 2) g_stats[(tile * 8 + j) * 64 + 16 * wq + g + 8 * t] = t ? make_float2(a1, b1) : make_float2(a0, b0);
        warp_arrive(bars + (B_SIG + uw) * 8);
        TS(leader, 40 + uw)
#pragma unroll
        for (int i = 0; i < 10; i++) {
            const float2 c = lds64f(sb + M_GB + (8 * i + 2 * t) * 4), e = lds64f(sb + M_CI + (8 * i + 2 * t) * 4);
#pragma unroll
            for (int h = 0; h < 2; h++)
                res[2 * i + h] = pack2(fmaf(c.x, rbf(acc[4 * i + 2 * h]), e.x * blo(res[2 * i + h])), fmaf(c.y, rbf(acc[4 * i + 2 * h + 1]), e.y * bhi(res[2 * i + h])));
        }
#pragma unroll
        for (int i = 0; i < 5; i++) stg128(&g_x1f[(tile * 8 + j) * 640 + i * 128 + wt], res[4 * i], res[4 * i + 1], res[4 * i + 2], res[4 * i + 3]);
        asm volatile("fence.proxy.async.global;" ::: "memory");
    }
    asm volatile("setmaxnreg.inc.sync.aligned.u32 224;");
    float acc0[64], acc1[44];
    float2 q[4];
    {
        uint4 f0, f1, f2, f3;
        auto xseq = [&](int kb) { return (uint32_t)(40 + (uw ? (kb < 10 - XLEAD ? XLEAD + 2 * kb : 10 + kb) : (kb < XLEAD ? kb : 2 * kb - XLEAD + 1))) & 7; };
        auto step = [&](const uint4& f, uint64_t bd) {
            wg_fence();
            wgmma_rs128(acc0, f.x, f.y, f.z, f.w, bd, 1);
            wgmma_rs88(acc1, f.x, f.y, f.z, f.w, bd + 512, 1);
            wg_commit();
        };
        const uint32_t xa = sb + OFF_XR + wt * 16;
        zero(acc0); zero(acc1);
        uint32_t xs = xseq(0);
        xwait(20);
        TS(leader, 42 + uw)
        f0 = lds128(xa + xs * 8192); f1 = lds128(xa + xs * 8192 + 2048);
#pragma unroll
        for (int i = 0; i < 4; i++) q[i] = ldcg64f(&g_stats[(tile * 8 + 2 * t + (i & 1)) * 64 + 16 * wq + g + 8 * (i >> 1)]);
        mbar_spin(wfull + (10 & 7) * 8, (10 >> 3) & 1);
#pragma unroll 1
        for (int kb = 0; kb < 10; kb++) {
            const uint32_t wn = 10 + 2 * kb;
            const uint64_t bd = dz + (((dsb + OFF_W + (wn & 7) * 16384) >> 4) | (256u << 16));
            step(f0, bd);
            wg_wait<1>();
            if (kb && lane == 0) mbar_arrive(wempty + ((wn - 1) & 7) * 8);
            f2 = lds128(xa + xs * 8192 + 4096); f3 = lds128(xa + xs * 8192 + 6144);
            const bool w1 = mbar_test(wfull + ((wn + 1) & 7) * 8, (wn >> 3) & 1), x1 = mbar_test(xfull + ((21 + kb) & 7) * 8, ((21 + kb) >> 3) & 1);
            step(f1, bd + 128);
            if (!w1) mbar_spin(wfull + ((wn + 1) & 7) * 8, (wn >> 3) & 1);
            step(f2, bd + 1024);
            if (lane < 2) mbar_arrive_after(xempty + xs * 8, f2.x, f3.x, nil);
            wg_wait<1>();
            if (lane == 0) mbar_arrive(wempty + (wn & 7) * 8);
            xs = xseq(kb + 1);
            if (x1) { f0 = lds128(xa + xs * 8192); f1 = lds128(xa + xs * 8192 + 2048); }
            const bool w2 = mbar_test(wfull + ((wn + 2) & 7) * 8, ((wn + 2) >> 3) & 1);
            step(f3, bd + 1152);
            if (kb < 9 && !x1) { xwait(21 + kb); f0 = lds128(xa + xs * 8192); f1 = lds128(xa + xs * 8192 + 2048); }
            if (!w2) mbar_spin(wfull + ((wn + 2) & 7) * 8, ((wn + 2) >> 3) & 1);
            if (kb == 4) {
                float a0 = q[0].x + q[1].x, b0 = q[0].y + q[1].y, a1 = q[2].x + q[3].x, b1 = q[2].y + q[3].y;
#pragma unroll
                for (int o = 1; o < 4; o *= 2) {
                    a0 += __shfl_xor_sync(~0u, a0, o); b0 += __shfl_xor_sync(~0u, b0, o);
                    a1 += __shfl_xor_sync(~0u, a1, o); b1 += __shfl_xor_sync(~0u, b1, o);
                }
                a0 *= 1.f / D_; a1 *= 1.f / D_;
                const float r0 = 0.5f * rsqrtf(fmaxf(b0 * (1.f / D_) - a0 * a0, 0.f) + 1e-5f), r1 = 0.5f * rsqrtf(fmaxf(b1 * (1.f / D_) - a1 * a1, 0.f) + 1e-5f);
                const uint32_t sel = t == 0 ? 0x1010 : t == 1 ? 0x4432 : 0x4444;
                q[0] = make_float2(r0, r1);
                q[1] = make_float2(__uint_as_float(__byte_perm(split2(-a0), 0, sel)), __uint_as_float(__byte_perm(split2(-a1), 0, sel)));
            }
            TR(leader, 10 * uw + kb)
        }
        const uint64_t fd = ((uint64_t)8 << 32) | ((dsb + OFF_W + 6 * 16384) >> 4);
        wg_fence();
        wgmma_rs128k(acc0, __float_as_uint(q[1].x), __float_as_uint(q[1].y), 0, 0, fd, 1);
        wgmma_rs88k(acc1, __float_as_uint(q[1].x), __float_as_uint(q[1].y), 0, 0, fd + 128, 1);
        wg_commit();
        if (lane == 0) {
            mbar_arrive(bars + B_XFREE * 8);
            asm volatile("mbarrier.arrive.shared::cluster.b64 _, [%0];" ::"r"(peer_addr(bars + B_XFREE * 8)) : "memory");
        }
    }
    const uint32_t recv = sb + recv_off(uw) + wt * 16;
    uint32_t ha[48] = {}, hb[48], hx[12];
    uint64_t wb = dz + (((dsb + OFF_W) >> 4) | (512u << 16));
    auto wdesc = [&](int n) { return wb + (n & 7) * 1024; };
    auto wwait = [&](int n) { mbar_spin(wfull + (n & 7) * 8, (n >> 3) & 1); };
    auto wfree = [&](int n) { if (lane == 0) mbar_arrive(wempty + (n & 7) * 8); };
    auto fresh = [&]() { wb += pp.nil; asm volatile("" : "+l"(wb)); };
    const uint32_t ep = lds32(sb + M_EP);
    uint32_t pk[32];
    {
        float P0[64];
        const float r0 = q[0].x, r1 = q[0].y;
        const uint32_t ra = peer_addr(recv), rb = peer_addr(bars + (B_RECV + 4 * uw) * 8);
        auto conv32 = [&](const float* v, int b) {
#pragma unroll
            for (int i = 0; i < 4; i++) {
                ha[8 * b + 2 * i] = pack2(gelu2(v[4 * i] * r0), gelu2(v[4 * i + 1] * r0));
                ha[8 * b + 2 * i + 1] = pack2(gelu2(v[4 * i + 2] * r1), gelu2(v[4 * i + 3] * r1));
            }
#pragma unroll
            for (int s = 2 * b; s < 2 * b + 2; s++) st_peer(ra + s * 2048, ha[4 * s], ha[4 * s + 1], ha[4 * s + 2], ha[4 * s + 3], rb + (b >> 1) * 8);
        };
        auto fetch = [&](int k) {
            mbar_spin(bars + (B_RECV + 4 * uw + k) * 8, 0);
#pragma unroll
            for (int s = 4 * k; s < 4 * k + 4; s++) { const uint4 x = lds128(recv + s * 2048); hb[4 * s] = x.x; hb[4 * s + 1] = x.y; hb[4 * s + 2] = x.z; hb[4 * s + 3] = x.w; }
        };
        auto stage = [&](int n, const uint32_t* a, int steps, int sc) {
            wwait(n);
            wg_fence();
#pragma unroll
            for (int s = 0; s < steps; s++) wgmma_rs128(P0, a[4 * s], a[4 * s + 1], a[4 * s + 2], a[4 * s + 3], wdesc(n) + s * 128, sc || s);
            wg_commit();
        };
        wg_wait<0>();
        reg_fence(acc0); reg_fence(acc1);
        wfree(29); wfree(30);
        TS(leader, 44 + uw)
        uint32_t hr[6];
#pragma unroll
        for (int i = 0; i < 6; i++) {
            const float r = (i & 1) ? r1 : r0;
            hr[i] = pack2(gelu2(acc1[32 + 2 * i] * r), gelu2(acc1[33 + 2 * i] * r));
        }
        if (uw) mbar_spin(bars + B_XFREE * 8, 0);
        st_peer(ra + 24576, hr[0], hr[1], hr[2], hr[3], rb + 24);
        asm volatile("st.async.shared::cluster.mbarrier::complete_tx::bytes.v2.b32 [%0], {%1, %2}, [%3];" ::"r"(ra + 26624 - wt * 8), "r"(hr[4]), "r"(hr[5]), "r"(rb + 24) : "memory");
        conv32(&acc1[0], 4);
        conv32(&acc1[16], 5);
        TS(leader, 46 + uw)
        stage(31, &ha[32], 4, 0);
#pragma unroll
        for (int b = 0; b < 4; b++) {
            conv32(&acc0[16 * b], b);
            if (b == 3) {
                fetch(2);
                mbar_spin(bars + (B_RECV + 4 * uw + 3) * 8, 0);
                const uint4 x = lds128(recv + 24576);
                const uint2 y = lds64(recv + 26624 - wt * 8);
                const uint32_t hp[6] = {x.x, x.y, x.z, x.w, y.x, y.y};
#pragma unroll
                for (int i = 0; i < 6; i++) { hx[i] = (j & 1) ? hp[i] : hr[i]; hx[6 + i] = (j & 1) ? hr[i] : hp[i]; }
            }
            if (!(b & 1)) wwait(32 + (b >> 1));
            wg_fence();
#pragma unroll
            for (int s = 0; s < 2; s++) wgmma_rs128(P0, ha[8 * b + 4 * s], ha[8 * b + 4 * s + 1], ha[8 * b + 4 * s + 2], ha[8 * b + 4 * s + 3], wdesc(32 + (b >> 1)) + (2 * (b & 1) + s) * 128, 1);
            wg_commit();
            if (!(b & 1)) { wg_wait<1>(); wfree(31 + (b >> 1)); }
        }
        TR(leader, 64 + 10 * uw)
        fresh();
        stage(34, &hb[32], 4, 1); wg_wait<1>(); wfree(33);
        fetch(0);
        stage(35, hx, 3, 1); wg_wait<1>(); wfree(34);
        fetch(1);
        stage(36, &hb[0], 4, 1); wg_wait<1>(); wfree(35);
        stage(37, &hb[16], 4, 1); wg_wait<1>(); wfree(36);
        wg_wait<0>();
        reg_fence(P0);
        pack_part<64>(pk, P0, ep);
        uint32_t all = 0;
#pragma unroll
        for (int i = 0; i < 32; i++) all |= pk[i];
        if (lane == 0) mbar_arrive_after(wempty + (37 & 7) * 8, all, 0, nil);
        TR(leader, 65 + 10 * uw)
    }
    {
        uint4* const dst = g_part + (size_t)(tile * 8 + j) * 5120 + wt;
        const uint4* const src = g_part + (size_t)tile * 40960 + j * 512 + wt;
        float F[2][32];
        float2 gb[8];
        uint4 base[4], u1[4], u2[4], u3[4];
#pragma unroll
        for (int c = 2; c < 5; c++) {
            float (&P)[32] = F[c & 1];
            fresh();
#pragma unroll
            for (int s = 0; s < 27; s++) {
                const int e = s < 8 ? 0 : s < 15 ? 1 : s < 23 ? 2 : 3, o = s - (e == 0 ? 0 : e == 1 ? 8 : e == 2 ? 15 : 23), n = 30 + 4 * c + e;
                const uint32_t* a = s < 12 ? &ha[4 * s] : s < 15 ? &hx[4 * (s - 12)] : &hb[4 * (s - 15)];
                if (o == 0) wwait(n);
                if (o == 0 || s == 1) wg_fence();
                wgmma_rs64(P, a[0], a[1], a[2], a[3], wdesc(n) + o * 128, s);
                if (o == 0) { wg_commit(); wg_wait<1>(); if (c > 2 || s) wfree(n - 1); }
                if (s == 0 && c > 2) { reg_fence(F[~c & 1]); pack_part<32>(pk, F[~c & 1], ep); }
                if (c == 2 && s % 3 == 0 && s < 24) st_part(dst + g4_block(s / 12, j) * 512 + (s / 3 & 3) * 128, &pk[4 * (s / 3)]);
                if (c == 3 && s % 4 == 1 && s < 16) st_part(dst + g4_block(2, j) * 512 + s / 4 * 128, &pk[4 * (s / 4)]);
                if (c == 4 && s % ST3 == 0 && s < 4 * ST3) st_part(dst + g4_block(3, j) * 512 + s / ST3 * 128, &pk[4 * (s / ST3)]);
                if (c == 4 && s >= 4 && s < 8) base[s - 4] = ldcg128(&g_x1f[(tile * 8 + j) * 640 + (s - 4) * 128 + wt]);
                if (c == 4 && s >= 19 && s < 23) { gb[2 * s - 38] = lds64f(sb + M_GB + (16 * (s - 19) + 2 * t) * 4); gb[2 * s - 37] = lds64f(sb + M_GB + (16 * (s - 19) + 8 + 2 * t) * 4); }
                if (c == 4 && s >= 8 && s < 12) u1[s - 8] = ld_part(src + (j ^ 6) * 5120 + (s - 8) * 128);
                if (c == 4 && s >= 15 && s < 19) u2[s - 15] = ld_part(src + (j ^ 4) * 5120 + (s - 15) * 128);
                if (c == 4 && s >= LD3 && s < LD3 + 4) u3[s - LD3] = ld_part(src + (j ^ 2) * 5120 + (s - LD3) * 128);
                if (s == 7 || s == 14 || s == 22 || s == 26) wg_commit();
                if (c == 4) { TR(leader && s == 7, 68 + 10 * uw) TR(leader && s == 14, 69 + 10 * uw) TR(leader && s == 22, 70 + 10 * uw) }
            }
            if (c == 2 && lane == 0) mbar_arrive(bars + (B_RING + uw) * 8);
            TR(leader, 64 + c + (c == 4 ? 3 : 0) + 10 * uw)
        }
        float (&O)[32] = F[0];
        float v[32];
        fix4(u1, src + (j ^ 6) * 5120, ep, 4);
        fix4(u2, src + (j ^ 4) * 5120, ep, 5);
        TR(leader, 72 + 10 * uw)
        fix4(u3, src + (j ^ 2) * 5120, ep, 6);
        TR(leader, 73 + 10 * uw)
#pragma unroll
        for (int i = 0; i < 4; i++) { unpack8(&v[8 * i], add2(add2(u1[i], u2[i]), u3[i])); base16(&v[8 * i], base[i], gb[2 * i], gb[2 * i + 1]); }
        reg_fence(v);
        TS(leader, 50 + uw)
        wg_wait<0>();
        reg_fence(O);
        TS(leader, 48 + uw)
        const uint32_t so = sb + recv_off(uw) + wq * 2048;
#pragma unroll
        for (int i = 0; i < 4; i++) {
            float* o = &O[8 * i];
#pragma unroll
            for (int e = 0; e < 8; e++) o[e] = fmaf((e & 1) ? gb[2 * i + (e >> 2)].y : gb[2 * i + (e >> 2)].x, o[e], v[8 * i + e]);
            stsm4(so + (lane & 15) * 128 + (((2 * i + (lane >> 4)) ^ (lane & 7)) << 4), pack2(o[0], o[1]), pack2(o[2], o[3]), pack2(o[4], o[5]), pack2(o[6], o[7]));
        }
        __syncwarp();
#pragma unroll
        for (int i = 0; i < 4; i++) {
            const int row = (lane >> 3) + 4 * i;
            stg128(out + (size_t)(row0 + row) * D_ + 64 * j + 8 * (lane & 7), lds128(so + row * 128 + (((lane & 7) ^ (row & 7)) << 4)));
        }
        warp_arrive(bars + (B_OWN + uw) * 8);
    }
}

typedef CUresult (*EncFn)(CUtensorMap*, CUtensorMapDataType, cuuint32_t, void*, const cuuint64_t*, const cuuint64_t*, const cuuint32_t*,
                          const cuuint32_t*, CUtensorMapInterleave, CUtensorMapSwizzle, CUtensorMapL2promotion, CUtensorMapFloatOOBfill);

static void enc(EncFn fn, CUtensorMap* m, void* p, int rank, const cuuint64_t* dims, const cuuint64_t* strides, const cuuint32_t* box) {
    const CUtensorMapSwizzle sw = box[0] > 64 ? CU_TENSOR_MAP_SWIZZLE_NONE : CU_TENSOR_MAP_SWIZZLE_128B;
    cuuint32_t es[5] = {1, 1, 1, 1, 1};
    CUresult r = fn(m, CU_TENSOR_MAP_DATA_TYPE_BFLOAT16, rank, p, dims, strides, box, es, CU_TENSOR_MAP_INTERLEAVE_NONE, sw,
                    CU_TENSOR_MAP_L2_PROMOTION_L2_128B, CU_TENSOR_MAP_FLOAT_OOB_FILL_NONE);
    (void)r;
}
static void enc2(EncFn fn, CUtensorMap* m, void* p, uint64_t cols, uint64_t rows, uint32_t bc, uint32_t br) {
    cuuint64_t dims[2] = {cols, rows}, st[1] = {cols * 2};
    cuuint32_t box[2] = {bc, br};
    enc(fn, m, p, 2, dims, st, box);
}

extern "C" void kernel_launch(void* const* d_in, const int* in_sizes, int n_in, void* d_out, int out_size) {
    static Maps mp;
    static Ptrs pp;
    static void* cached[13];
    bool same = true;
    for (int i = 0; i < 13; i++) same = same && (cached[i] == d_in[i]);
    if (!same) {
        void* fnp = nullptr;
        cudaDriverEntryPointQueryResult qr;
        cudaGetDriverEntryPoint("cuTensorMapEncodeTiled", &fnp, cudaEnableDefault, &qr);
        EncFn fn = (EncFn)fnp;
        cudaGetSymbolAddress((void**)&pp.s, g_scratch);
        void *x1T = g_x1T, *t = g_t;
        cuuint64_t dq[3] = {64, S_, 10}, sq[2] = {D_ * 2, 128};
        cuuint32_t bq[3] = {64, 16, 10};
        enc(fn, &mp.q, d_in[0], 3, dq, sq, bq);
        enc2(fn, &mp.k, d_in[1], D_, S_, 80, 67); enc2(fn, &mp.v, d_in[2], D_, S_, 80, 64);
        enc2(fn, &mp.qT, g_qT, 16 * D_, 128, 80, 128);
        enc2(fn, &mp.x1_ld, x1T, S_, D_, 64, 64); enc2(fn, &mp.t_ld, (bf16*)t + 2 * D_, D_, S_, 64, 64);
        enc2(fn, &mp.w1, d_in[7], D_, D_, 64, 64); enc2(fn, &mp.w1h, d_in[7], D_, D_, 64, 160); enc2(fn, &mp.w3h, d_in[9], F_, D_, 64, 160);
        enc2(fn, &mp.wmod, d_in[12], 6 * D_, D_, 64, 160);
        const cuuint64_t R = D_ * 2;
        cuuint64_t da[5] = {D_, 2, 4, 4, 16}, sa[4] = {R, 8 * R, 2 * R, 32 * R}, db[5] = {D_, 2, 2, 4, 8}, sb[4] = {R, 8 * R, 2 * R, 16 * R};
        cuuint32_t ba[5] = {64, 2, 4, 4, 4}, bb[5] = {64, 2, 2, 4, 8};
        enc(fn, &mp.w2a, d_in[8], 5, da, sa, ba); enc(fn, &mp.w2b, (bf16*)d_in[8] + 512 * D_, 5, db, sb, bb);
        cuuint64_t dw[3] = {64, D_, 27}, sw[2] = {F_ * 2, 128};
        cuuint32_t bw[3] = {64, 32, 3};
        enc(fn, &mp.w3a, d_in[9], 3, dw, sw, bw);
        enc2(fn, &mp.w3b, d_in[9], F_, D_, 24, 32);
        enc2(fn, &mp.w4[0], d_in[10], D_, F_, 64, 64); enc2(fn, &mp.w4[1], d_in[10], D_, F_, 64, 48);
        pp.q = (const bf16*)d_in[0]; pp.w_mod = (const bf16*)d_in[12]; pp.shift_k = (const bf16*)d_in[3];
        pp.ssm_k = (const bf16*)d_in[4]; pp.ssm_D = (const bf16*)d_in[5]; pp.w1 = (const bf16*)d_in[7]; pp.w2 = (const bf16*)d_in[8];
        pp.w4 = (const bf16*)d_in[10]; pp.c = (const bf16*)d_in[11];
        cudaFuncSetAttribute(fused_kernel, cudaFuncAttributeMaxDynamicSharedMemorySize, SMEM_BYTES);
        for (int i = 0; i < 13; i++) cached[i] = d_in[i];
    }
    cudaLaunchConfig_t cfg = {};
    cfg.gridDim = dim3(NCTA); cfg.blockDim = dim3(NTHR); cfg.dynamicSmemBytes = SMEM_BYTES; cfg.stream = cudaStreamPerThread;
    cudaLaunchAttribute at[1];
    at[0].id = cudaLaunchAttributeClusterDimension; at[0].val.clusterDim.x = 2; at[0].val.clusterDim.y = 1; at[0].val.clusterDim.z = 1;
    cfg.attrs = at; cfg.numAttrs = 1;
    cudaLaunchKernelEx(&cfg, fused_kernel, pp, (bf16*)d_out, mp);
}
```

```cpp
#include <cuda_runtime.h>
#include <cuda_bf16.h>
#include <cuda.h>
#include <stdint.h>
#include <stdio.h>

typedef __nv_bfloat16 bf16;

constexpr int S_ = 2048, D_ = 640, F_ = 1728;
constexpr int NCTA = 132, NTHR = 512;

constexpr int TAB_BYTES = 9216, VEC_BYTES = 1440;
struct Counters {
    unsigned kv[8 * 32];
    unsigned q[4 * 32], x[2 * 4 * 32];
    unsigned wr[32], tab[32], uv[32], cs[32], done[32];
    unsigned g1[32 * 32];
    unsigned g2[32 * 32];
};
struct Scratch {
    Counters cnt;
    unsigned epoch;
    alignas(1024) bf16 qst[2 * S_];
    alignas(1024) uint4 wr[2 * 8 * 10 * 128];
    alignas(1024) uint2 mod[2 * 6 * D_];
    alignas(1024) uint4 tab[(TAB_BYTES + 8 * VEC_BYTES) / 16];
    alignas(1024) float uv[2 * 3 * D_];
    alignas(1024) float cs3[2 * 1920];
    alignas(1024) float2 stats[32 * 8 * 64];
    alignas(1024) bf16 kvT[D_ * S_];
    alignas(1024) bf16 qT[D_ * S_];
    alignas(1024) bf16 x1T[D_ * S_];
    alignas(1024) bf16 t[(S_ + 4) * D_];
    alignas(1024) uint4 x2f[32 * 40 * 128];
    alignas(1024) uint4 x1f[32 * 8 * 5 * 128];
    alignas(1024) uint4 part[32 * 8 * 10 * 4 * 128];
};
__device__ Scratch g_scratch;
#define g_kvT (pp.s->kvT)
#define g_qT (pp.s->qT)
#define g_x1T (pp.s->x1T)
#define g_qst (pp.s->qst)
#define g_t (pp.s->t)
#define g_x2f (pp.s->x2f)
#define g_x1f (pp.s->x1f)
#define g_part (pp.s->part)
#define g_wr (pp.s->wr)
#define g_mod (pp.s->mod)
#define g_tab (pp.s->tab)
#define g_uv (pp.s->uv)
#define g_cs3 (pp.s->cs3)
#define g_stats (pp.s->stats)
#define g_cnt (pp.s->cnt)
#define g_epoch (pp.s->epoch)

struct Maps {
    CUtensorMap k, v, q;
    CUtensorMap qT;
    CUtensorMap x1_ld, t_ld;
    CUtensorMap w1, w1h, w3h, wmod;
    CUtensorMap w2a, w2b;
    CUtensorMap w3a, w3b;
    CUtensorMap w4[2];
};

struct Ptrs {
    Scratch* s;
    uint64_t nil;
    const bf16 *q, *w_mod, *shift_k, *ssm_k, *ssm_D, *w1, *w2, *w4, *c;
};

constexpr int OFF_W = 0;
constexpr int OFF_XR = 131072;
constexpr int OFF_REM = 196608;
constexpr int OFF_TAB = OFF_REM + 5 * 4096;
constexpr int OFF_ROW = OFF_TAB + 4608;
constexpr int OFF_F1 = OFF_ROW + 4096;
constexpr int RECV_BYTES = 30720;
constexpr int OFF_M = OFF_REM + RECV_BYTES;
constexpr int OFF_OUT = OFF_XR + 32768;
static_assert(OFF_F1 + 1280 <= OFF_M, "G1 map");
constexpr int OFF_ST = 0;
constexpr int OFF_SSM = 20480;
constexpr int OFF_WM = 0;
constexpr int OFF_QIN = 49152;
constexpr int OFF_QT = 49152;
constexpr int OFF_Z = OFF_TAB;
constexpr int OFF_RING = 80896;
constexpr int OFF_KIN = OFF_RING, OFF_VIN = OFF_KIN + 2 * 10752;
constexpr int OFF_CH = OFF_RING + 3 * 16384, CH_BYTES = 13312, OFF_P = 5120;
static_assert(OFF_RING + 5 * 16384 <= OFF_CH + 3 * CH_BYTES && OFF_CH + 5 * CH_BYTES <= OFF_REM, "the last two rings replace channels 0..2");
constexpr int M_BAR = OFF_M;
constexpr int M_F1 = OFF_M + 768;
constexpr int M_GB = M_F1 + 1280, M_C = M_GB + 320, M_SB = M_C + 320, M_CI = M_SB + 320;
constexpr int M_KS = M_CI + 320;
constexpr int M_AB = M_KS + 160;
constexpr int M_EP = M_AB + 80;
constexpr int M_SINK = M_EP + 16;
constexpr int M_NUL = M_SINK + 16;
constexpr int M_TS = M_NUL + 128;
constexpr int SMEM_BYTES = M_TS;
static_assert(SMEM_BYTES <= 232448, "smem");

enum { B_WFULL = 0, B_WEMPTY = 8, B_XEMPTY = 16, B_XFULL = 24  ,
       B_RAW = 40, B_QIN = 41, B_SSM = 42, B_VEC = 43, B_VEC3 = 44, B_WM = 45, B_TAB = 46, B_QRDY = 47,
       B_MODR = 48, B_PUB = 49, B_RETRY = 55, B_S30 = 58, B_RAW2 = 59, B_SUMS = 62, B_RECV = 64  ,
       B_SIG = 72, B_OWN = 74, B_COEF = 76, B_RES = 78, B_RING = 80  ,
       B_XS = 88, B_BK = 90, B_KVS = 91,
       B_XFREE = 92,
       B_IN = 94 };
#define T_KVB 1800
#define T_SSM 3300
#define T_Q 0
#define PF_T0 4800
#define PF_DT 420
#define PF_N0 4
#define PF_N 16
#define CH2_DELAY 0
#define POLL_NS 0
#define HELP_T 1000
#define EPI_SPLIT 1
#define ST3 1
#define LD3 23
#define XLEAD 3

#define SPIN_FAIL(code) __trap();
#define SPIN_LIMIT (1u << 22)
#define STALE(c)
#define STALE1(c)
#define TS(c, i)
#define TG(c, i)
#define TR(c, i)
#define TR2(c, i)
#define TR4(c, i)
#define TR5(c, i)
#define SPIN_CHECK(code) asm volatile("" ::"r"(it));
__device__ __forceinline__ uint32_t s2u(const void* p) { return (uint32_t)__cvta_generic_to_shared(p); }
__device__ __forceinline__ bool elect() {
    uint32_t p;
    asm volatile("{.reg .pred P; elect.sync _|P, 0xffffffff; selp.u32 %0,1,0,P;}" : "=r"(p));
    return p != 0;
}
__device__ __forceinline__ void mbar_init(uint32_t b, uint32_t n) { asm volatile("mbarrier.init.shared.b64 [%0], %1;" ::"r"(b), "r"(n)); }
__device__ __forceinline__ void mbar_expect(uint32_t b, uint32_t bytes) {
    asm volatile("mbarrier.arrive.expect_tx.shared.b64 _, [%0], %1;" ::"r"(b), "r"(bytes) : "memory");
}
__device__ __forceinline__ void mbar_arrive(uint32_t b) { asm volatile("mbarrier.arrive.shared.b64 _, [%0];" ::"r"(b) : "memory"); }
__device__ __forceinline__ void mbar_arrive_after(uint32_t b, uint32_t v0, uint32_t v1, uint32_t nil) { mbar_arrive(b + ((v0 | v1) & nil)); }
__device__ __forceinline__ void warp_arrive(uint32_t b) { __syncwarp(); if (elect()) mbar_arrive(b); }
__device__ __forceinline__ uint32_t peer_addr(uint32_t a) {
    uint32_t r;
    asm("{\n.reg .b32 q;\nmov.u32 q, %%cluster_ctarank;\nxor.b32 q, q, 1;\nmapa.shared::cluster.u32 %0, %1, q;\n}" : "=r"(r) : "r"(a));
    return r;
}
__device__ __forceinline__ bool mbar_test(uint32_t b, uint32_t parity) {
    uint32_t ok;
    asm volatile("{.reg .pred P; mbarrier.test_wait.parity.shared.b64 P, [%1], %2; selp.u32 %0,1,0,P;}" : "=r"(ok) : "r"(b), "r"(parity) : "memory");
    return ok != 0;
}
__device__ __forceinline__ bool mbar_try(uint32_t b, uint32_t parity) {
    uint32_t ok;
    asm volatile("{.reg .pred P; mbarrier.try_wait.parity.shared.b64 P, [%1], %2; selp.u32 %0,1,0,P;}" : "=r"(ok) : "r"(b), "r"(parity) : "memory");
    return ok != 0;
}
__device__ __forceinline__ void mbar_wait(uint32_t b, uint32_t parity) {
    if (__all_sync(0xffffffffu, mbar_try(b, parity))) return;
    uint32_t it = 0;
    while (!__all_sync(0xffffffffu, mbar_try(b, parity))) { if (++it > SPIN_LIMIT) SPIN_FAIL((b >> 3) & 63) }
}
__device__ __forceinline__ void mbar_spin(uint32_t b, uint32_t parity) {
    asm volatile("{\n.reg .pred P;\nSPIN:\nmbarrier.try_wait.parity.shared.b64 P, [%0], %1;\n@!P bra.uni SPIN;\n}" ::"r"(b), "r"(parity) : "memory");
}
__device__ __forceinline__ void bar_sync(int id, int n) { asm volatile("bar.sync %0, %1;" ::"r"(id), "r"(n) : "memory"); }
__device__ __forceinline__ void fence_async_smem() { asm volatile("fence.proxy.async.shared::cta;" ::: "memory"); }
__device__ __forceinline__ void wait_cnt(const unsigned* p, unsigned target, int ns = 0) {
    unsigned v, it = 0;
    do {
        if (ns) __nanosleep(ns);
        asm volatile("ld.relaxed.gpu.global.u32 %0, [%1];" : "=r"(v) : "l"(p) : "memory");
        SPIN_CHECK(60 + (target & 3))
    } while (!__all_sync(0xffffffffu, v >= target));
    asm volatile("fence.acquire.gpu;" ::: "memory");
}
#define X_FENCE 0
__device__ __forceinline__ void signal_cnt(unsigned* p, int lane, int n, bool nofence = false) {
    if (nofence) { if (lane < n) asm volatile("red.relaxed.gpu.global.add.u32 [%0], 1;" ::"l"(p) : "memory"); }
    else if (lane < n) asm volatile("red.release.gpu.global.add.u32 [%0], 1;" ::"l"(p) : "memory");
    __syncwarp();
}
__device__ __forceinline__ void wait_clock(long long c0, int t) {
    while (clock64() - c0 < t) __nanosleep(20);
    __syncwarp();
}
__device__ __forceinline__ void tma_ld2(uint32_t dst, const CUtensorMap* m, int c0, int c1, uint32_t bar) {
    asm volatile("cp.async.bulk.tensor.2d.shared::cluster.global.mbarrier::complete_tx::bytes [%0], [%1, {%3, %4}], [%2];"
                 ::"r"(dst), "l"(m), "r"(bar), "r"(c0), "r"(c1) : "memory");
}
__device__ __forceinline__ void tma_ld3(uint32_t dst, const CUtensorMap* m, int c0, int c1, int c2, uint32_t bar) {
    asm volatile("cp.async.bulk.tensor.3d.shared::cluster.global.mbarrier::complete_tx::bytes [%0], [%1, {%3, %4, %5}], [%2];"
                 ::"r"(dst), "l"(m), "r"(bar), "r"(c0), "r"(c1), "r"(c2) : "memory");
}
__device__ __forceinline__ void tma_ld5(uint32_t dst, const CUtensorMap* m, int col, int blk, uint32_t bar) {
    asm volatile("cp.async.bulk.tensor.5d.shared::cluster.global.mbarrier::complete_tx::bytes [%0], [%1, {%3, %4, %4, %4, %5}], [%2];"
                 ::"r"(dst), "l"(m), "r"(bar), "r"(col), "r"(0), "r"(blk) : "memory");
}
__device__ __forceinline__ void bulk_ld(uint32_t dst, const void* src, uint32_t bytes, uint32_t bar) {
    asm volatile("cp.async.bulk.shared::cluster.global.mbarrier::complete_tx::bytes [%0], [%1], %2, [%3];" ::"r"(dst), "l"(src), "r"(bytes), "r"(bar) : "memory");
}
__device__ __forceinline__ void l2_prefetch(const void* p, uint32_t bytes) {
    asm volatile("cp.async.bulk.prefetch.L2.global [%0], %1;" ::"l"(p), "r"(bytes) : "memory");
}
__device__ __forceinline__ void wg_fence() { asm volatile("wgmma.fence.sync.aligned;" ::: "memory"); }
__device__ __forceinline__ void wg_commit() { asm volatile("wgmma.commit_group.sync.aligned;" ::: "memory"); }
template <int N> __device__ __forceinline__ void wg_wait() { asm volatile("wgmma.wait_group.sync.aligned %0;" ::"n"(N) : "memory"); }
template <int N> __device__ __forceinline__ void reg_fence(float (&d)[N]) {
#pragma unroll
    for (int i = 0; i < N; i++) asm volatile("" : "+f"(d[i])::"memory");
}
template <int N> __device__ __forceinline__ void zero(float (&d)[N]) {
#pragma unroll
    for (int i = 0; i < N; i++) asm volatile("mov.b32 %0, 0;" : "=f"(d[i]));
}
__device__ __forceinline__ uint32_t lds32(uint32_t a) { uint32_t v; asm volatile("ld.shared.b32 %0, [%1];" : "=r"(v) : "r"(a)); return v; }
__device__ __forceinline__ uint2 lds64(uint32_t a) { uint2 v; asm volatile("ld.shared.v2.b32 {%0,%1}, [%2];" : "=r"(v.x), "=r"(v.y) : "r"(a)); return v; }
__device__ __forceinline__ float2 lds64f(uint32_t a) { float2 v; asm volatile("ld.shared.v2.f32 {%0,%1}, [%2];" : "=f"(v.x), "=f"(v.y) : "r"(a)); return v; }
__device__ __forceinline__ void sts32(uint32_t a, uint32_t v) { asm volatile("st.shared.b32 [%0], %1;" ::"r"(a), "r"(v) : "memory"); }
__device__ __forceinline__ void sts64f(uint32_t a, float x, float y) { asm volatile("st.shared.v2.f32 [%0], {%1,%2};" ::"r"(a), "f"(x), "f"(y) : "memory"); }
__device__ __forceinline__ void sts128(uint32_t a, uint32_t x, uint32_t y, uint32_t z, uint32_t w) {
    asm volatile("st.shared.v4.b32 [%0], {%1,%2,%3,%4};" ::"r"(a), "r"(x), "r"(y), "r"(z), "r"(w) : "memory");
}
__device__ __forceinline__ void sts128f(uint32_t a, float x, float y, float z, float w) {
    asm volatile("st.shared.v4.f32 [%0], {%1,%2,%3,%4};" ::"r"(a), "f"(x), "f"(y), "f"(z), "f"(w) : "memory");
}
__device__ __forceinline__ uint4 lds128(uint32_t a) {
    uint4 v;
    asm volatile("ld.shared.v4.b32 {%0,%1,%2,%3}, [%4];" : "=r"(v.x), "=r"(v.y), "=r"(v.z), "=r"(v.w) : "r"(a) : "memory");
    return v;
}
__device__ __forceinline__ float4 lds128f(uint32_t a) {
    float4 v;
    asm volatile("ld.shared.v4.f32 {%0,%1,%2,%3}, [%4];" : "=f"(v.x), "=f"(v.y), "=f"(v.z), "=f"(v.w) : "r"(a) : "memory");
    return v;
}
__device__ __forceinline__ void stg128(void* p, uint32_t x, uint32_t y, uint32_t z, uint32_t w) {
    asm volatile("st.global.v4.b32 [%0], {%1,%2,%3,%4};" ::"l"(p), "r"(x), "r"(y), "r"(z), "r"(w) : "memory");
}
__device__ __forceinline__ void stg128(void* p, uint4 v) { stg128(p, v.x, v.y, v.z, v.w); }
__device__ __forceinline__ void stg128_if(void* p, uint4 v, int on) {
    asm volatile("{\n.reg .pred p;\nsetp.ne.s32 p, %5, 0;\n@p st.global.v4.b32 [%0], {%1,%2,%3,%4};\n}" ::"l"(p), "r"(v.x), "r"(v.y), "r"(v.z), "r"(v.w), "r"(on) : "memory");
}
__device__ __forceinline__ void stg64(void* p, uint32_t x, uint32_t y) { asm volatile("st.global.v2.b32 [%0], {%1,%2};" ::"l"(p), "r"(x), "r"(y) : "memory"); }
__device__ __forceinline__ void stsm4(uint32_t a, uint32_t r0, uint32_t r1, uint32_t r2, uint32_t r3) {
    asm volatile("stmatrix.sync.aligned.m8n8.x4.shared.b16 [%0], {%1,%2,%3,%4};" ::"r"(a), "r"(r0), "r"(r1), "r"(r2), "r"(r3) : "memory");
}
__device__ __forceinline__ void stsm4t(uint32_t a, uint32_t r0, uint32_t r1, uint32_t r2, uint32_t r3) {
    asm volatile("stmatrix.sync.aligned.m8n8.x4.trans.shared.b16 [%0], {%1,%2,%3,%4};" ::"r"(a), "r"(r0), "r"(r1), "r"(r2), "r"(r3) : "memory");
}
__device__ __forceinline__ void ldsm4t(uint32_t a, uint32_t& r0, uint32_t& r1, uint32_t& r2, uint32_t& r3) {
    asm volatile("ldmatrix.sync.aligned.m8n8.x4.trans.shared.b16 {%0,%1,%2,%3}, [%4];" : "=r"(r0), "=r"(r1), "=r"(r2), "=r"(r3) : "r"(a) : "memory");
}
__device__ __forceinline__ uint32_t pack2(float lo, float hi) {
    uint32_t r;
    asm("cvt.rn.bf16x2.f32 %0, %1, %2;" : "=r"(r) : "f"(hi), "f"(lo));
    return r;
}
__device__ __forceinline__ uint32_t mul2(uint32_t a, uint32_t b) { uint32_t r; asm("mul.rn.bf16x2 %0, %1, %2;" : "=r"(r) : "r"(a), "r"(b)); return r; }
__device__ __forceinline__ uint32_t fma2(uint32_t a, uint32_t b, uint32_t c) { uint32_t r; asm("fma.rn.bf16x2 %0, %1, %2, %3;" : "=r"(r) : "r"(a), "r"(b), "r"(c)); return r; }
__device__ __forceinline__ uint32_t add2(uint32_t a, uint32_t b) { uint32_t r; asm("add.rn.bf16x2 %0, %1, %2;" : "=r"(r) : "r"(a), "r"(b)); return r; }
__device__ __forceinline__ void hmma(float (&d)[4], uint32_t a0, uint32_t a1, uint32_t a2, uint32_t a3, uint32_t b0, uint32_t b1) {
    asm volatile("mma.sync.aligned.m16n8k16.row.col.f32.bf16.bf16.f32 {%0,%1,%2,%3}, {%4,%5,%6,%7}, {%8,%9}, {%0,%1,%2,%3};"
        : "+f"(d[0]), "+f"(d[1]), "+f"(d[2]), "+f"(d[3]) : "r"(a0), "r"(a1), "r"(a2), "r"(a3), "r"(b0), "r"(b1));
}
__device__ __forceinline__ float blo(uint32_t w) { return __uint_as_float(w << 16); }
__device__ __forceinline__ float bhi(uint32_t w) { return __uint_as_float(w & 0xffff0000u); }
__device__ __forceinline__ float rbf(float x) { return __bfloat162float(__float2bfloat16_rn(x)); }
__device__ __forceinline__ uint32_t ldg32(const void* p) { uint32_t v; asm volatile("ld.global.nc.b32 %0, [%1];" : "=r"(v) : "l"(p)); return v; }
__device__ __forceinline__ uint2 ldg64(const void* p) { uint2 v; asm volatile("ld.global.nc.v2.b32 {%0,%1}, [%2];" : "=r"(v.x), "=r"(v.y) : "l"(p)); return v; }
__device__ __forceinline__ uint4 ldg128(const void* p) {
    uint4 v;
    asm volatile("ld.global.nc.v4.b32 {%0,%1,%2,%3}, [%4];" : "=r"(v.x), "=r"(v.y), "=r"(v.z), "=r"(v.w) : "l"(p));
    return v;
}
__device__ __forceinline__ uint4 ldcg128(const void* p) {
    uint4 v;
    asm volatile("ld.global.cg.v4.u32 {%0,%1,%2,%3}, [%4];" : "=r"(v.x), "=r"(v.y), "=r"(v.z), "=r"(v.w) : "l"(p) : "memory");
    return v;
}
__device__ __forceinline__ float4 ldcg128f(const void* p) {
    float4 v;
    asm volatile("ld.global.cg.v4.f32 {%0,%1,%2,%3}, [%4];" : "=f"(v.x), "=f"(v.y), "=f"(v.z), "=f"(v.w) : "l"(p) : "memory");
    return v;
}
__device__ __forceinline__ float2 ldcg64f(const void* p) { float2 v; asm volatile("ld.global.cg.v2.f32 {%0,%1}, [%2];" : "=f"(v.x), "=f"(v.y) : "l"(p) : "memory"); return v; }
__device__ __forceinline__ float ldcg32f(const void* p) { float v; asm volatile("ld.global.cg.f32 %0, [%1];" : "=f"(v) : "l"(p) : "memory"); return v; }
__device__ __forceinline__ float2 ld_stat(const float2* p) {
    float2 v;
    asm volatile("{\n.reg .b64 q;\nld.relaxed.gpu.global.b64 q, [%2];\nmov.b64 {%0, %1}, q;\n}" : "=f"(v.x), "=f"(v.y) : "l"(p) : "memory");
    return v;
}
__device__ __forceinline__ uint32_t ld_cold(const unsigned* p) { uint32_t v; asm volatile("ld.relaxed.gpu.global.u32 %0, [%1];" : "=r"(v) : "l"(p) : "memory"); return v; }
__device__ __forceinline__ uint2 ld_mod(const uint2* p) {
    uint64_t v;
    asm volatile("ld.relaxed.gpu.global.b64 %0, [%1];" : "=l"(v) : "l"(p) : "memory");
    return make_uint2((uint32_t)v, (uint32_t)(v >> 32));
}
__device__ __forceinline__ float gelu2(float h) {
    float u = h * fmaf(h * h, 8.f * 0.0356774081f, 2.f * 0.7978845608f);
    float th;
    asm("tanh.approx.f32 %0, %1;" : "=f"(th) : "f"(u));
    return fmaf(h, th, h);
}

__device__ __forceinline__ void conv_channel(float (&d)[64], uint32_t pa, uint64_t db) {
    asm volatile("{\n.reg .b32 a0, a1, a2, a3, b0, b1, b2, b3, t0, t1;\n.reg .b64 d;\nld.shared.b32 a0, [%64];\nld.shared.b32 a1, [%64+128];\nld.shared.b32 a2, [%64+-128];\nmov.b32 a3, a0;\n"
        "ld.shared.b32 t0, [%64+256];\nld.shared.b32 t1, [%64+384];\nadd.s64 d, %65, 0;\nwgmma.fence.sync.aligned;\nwgmma.mma_async.sync.aligned.m64n128k16.f32.bf16.bf16 {%0, %1, %2, %3, %4, %5, %6, %7, %8, %9, %10, %11, %12, %13, %14, %15, %16, %17, %18, %19, %20, %21, %22, %23, %24, %25, %26, %27, %28, %29, %30, %31, %32, %33, %34, %35, %36, %37, %38, %39, %40, %41, %42, %43, %44, %45, %46, %47, %48, %49, %50, %51, %52, %53, %54, %55, %56, %57, %58, %59, %60, %61, %62, %63}, {a0, a1, a2, a3}, d, 0, 1, 1, 0;\nwgmma.commit_group.sync.aligned;\nwgmma.wait_group.sync.aligned 1;\nmov.b32 b2, a1;\nmov.b32 b0, t0;\nmov.b32 b3, t0;\nmov.b32 b1, t1;\n"
        "ld.shared.b32 t0, [%64+512];\nld.shared.b32 t1, [%64+640];\nadd.s64 d, %65, 8;\nwgmma.fence.sync.aligned;\nwgmma.mma_async.sync.aligned.m64n128k16.f32.bf16.bf16 {%0, %1, %2, %3, %4, %5, %6, %7, %8, %9, %10, %11, %12, %13, %14, %15, %16, %17, %18, %19, %20, %21, %22, %23, %24, %25, %26, %27, %28, %29, %30, %31, %32, %33, %34, %35, %36, %37, %38, %39, %40, %41, %42, %43, %44, %45, %46, %47, %48, %49, %50, %51, %52, %53, %54, %55, %56, %57, %58, %59, %60, %61, %62, %63}, {b0, b1, b2, b3}, d, 1, 1, 1, 0;\nwgmma.commit_group.sync.aligned;\nwgmma.wait_group.sync.aligned 1;\nmov.b32 a2, b1;\nmov.b32 a0, t0;\nmov.b32 a3, t0;\nmov.b32 a1, t1;\n"
        "ld.shared.b32 t0, [%64+768];\nld.shared.b32 t1, [%64+896];\nadd.s64 d, %65, 16;\nwgmma.fence.sync.aligned;\nwgmma.mma_async.sync.aligned.m64n128k16.f32.bf16.bf16 {%0, %1, %2, %3, %4, %5, %6, %7, %8, %9, %10, %11, %12, %13, %14, %15, %16, %17, %18, %19, %20, %21, %22, %23, %24, %25, %26, %27, %28, %29, %30, %31, %32, %33, %34, %35, %36, %37, %38, %39, %40, %41, %42, %43, %44, %45, %46, %47, %48, %49, %50, %51, %52, %53, %54, %55, %56, %57, %58, %59, %60, %61, %62, %63}, {a0, a1, a2, a3}, d, 1, 1, 1, 0;\nwgmma.commit_group.sync.aligned;\nwgmma.wait_group.sync.aligned 1;\nmov.b32 b2, a1;\nmov.b32 b0, t0;\nmov.b32 b3, t0;\nmov.b32 b1, t1;\n"
        "ld.shared.b32 t0, [%64+1024];\nld.shared.b32 t1, [%64+1152];\nadd.s64 d, %65, 24;\nwgmma.fence.sync.aligned;\nwgmma.mma_async.sync.aligned.m64n128k16.f32.bf16.bf16 {%0, %1, %2, %3, %4, %5, %6, %7, %8, %9, %10, %11, %12, %13, %14, %15, %16, %17, %18, %19, %20, %21, %22, %23, %24, %25, %26, %27, %28, %29, %30, %31, %32, %33, %34, %35, %36, %37, %38, %39, %40, %41, %42, %43, %44, %45, %46, %47, %48, %49, %50, %51, %52, %53, %54, %55, %56, %57, %58, %59, %60, %61, %62, %63}, {b0, b1, b2, b3}, d, 1, 1, 1, 0;\nwgmma.commit_group.sync.aligned;\nwgmma.wait_group.sync.aligned 1;\nmov.b32 a2, b1;\nmov.b32 a0, t0;\nmov.b32 a3, t0;\nmov.b32 a1, t1;\n"
        "ld.shared.b32 t0, [%64+1280];\nld.shared.b32 t1, [%64+1408];\nadd.s64 d, %65, 32;\nwgmma.fence.sync.aligned;\nwgmma.mma_async.sync.aligned.m64n128k16.f32.bf16.bf16 {%0, %1, %2, %3, %4, %5, %6, %7, %8, %9, %10, %11, %12, %13, %14, %15, %16, %17, %18, %19, %20, %21, %22, %23, %24, %25, %26, %27, %28, %29, %30, %31, %32, %33, %34, %35, %36, %37, %38, %39, %40, %41, %42, %43, %44, %45, %46, %47, %48, %49, %50, %51, %52, %53, %54, %55, %56, %57, %58, %59, %60, %61, %62, %63}, {a0, a1, a2, a3}, d, 1, 1, 1, 0;\nwgmma.commit_group.sync.aligned;\nwgmma.wait_group.sync.aligned 1;\nmov.b32 b2, a1;\nmov.b32 b0, t0;\nmov.b32 b3, t0;\nmov.b32 b1, t1;\n"
        "ld.shared.b32 t0, [%64+1536];\nld.shared.b32 t1, [%64+1664];\nadd.s64 d, %65, 40;\nwgmma.fence.sync.aligned;\nwgmma.mma_async.sync.aligned.m64n128k16.f32.bf16.bf16 {%0, %1, %2, %3, %4, %5, %6, %7, %8, %9, %10, %11, %12, %13, %14, %15, %16, %17, %18, %19, %20, %21, %22, %23, %24, %25, %26, %27, %28, %29, %30, %31, %32, %33, %34, %35, %36, %37, %38, %39, %40, %41, %42, %43, %44, %45, %46, %47, %48, %49, %50, %51, %52, %53, %54, %55, %56, %57, %58, %59, %60, %61, %62, %63}, {b0, b1, b2, b3}, d, 1, 1, 1, 0;\nwgmma.commit_group.sync.aligned;\nwgmma.wait_group.sync.aligned 1;\nmov.b32 a2, b1;\nmov.b32 a0, t0;\nmov.b32 a3, t0;\nmov.b32 a1, t1;\n"
        "ld.shared.b32 t0, [%64+1792];\nld.shared.b32 t1, [%64+1920];\nadd.s64 d, %65, 48;\nwgmma.fence.sync.aligned;\nwgmma.mma_async.sync.aligned.m64n128k16.f32.bf16.bf16 {%0, %1, %2, %3, %4, %5, %6, %7, %8, %9, %10, %11, %12, %13, %14, %15, %16, %17, %18, %19, %20, %21, %22, %23, %24, %25, %26, %27, %28, %29, %30, %31, %32, %33, %34, %35, %36, %37, %38, %39, %40, %41, %42, %43, %44, %45, %46, %47, %48, %49, %50, %51, %52, %53, %54, %55, %56, %57, %58, %59, %60, %61, %62, %63}, {a0, a1, a2, a3}, d, 1, 1, 1, 0;\nwgmma.commit_group.sync.aligned;\nwgmma.wait_group.sync.aligned 1;\nmov.b32 b2, a1;\nmov.b32 b0, t0;\nmov.b32 b3, t0;\nmov.b32 b1, t1;\n"
        "ld.shared.b32 t0, [%64+2048];\nld.shared.b32 t1, [%64+2176];\nadd.s64 d, %65, 56;\nwgmma.fence.sync.aligned;\nwgmma.mma_async.sync.aligned.m64n128k16.f32.bf16.bf16 {%0, %1, %2, %3, %4, %5, %6, %7, %8, %9, %10, %11, %12, %13, %14, %15, %16, %17, %18, %19, %20, %21, %22, %23, %24, %25, %26, %27, %28, %29, %30, %31, %32, %33, %34, %35, %36, %37, %38, %39, %40, %41, %42, %43, %44, %45, %46, %47, %48, %49, %50, %51, %52, %53, %54, %55, %56, %57, %58, %59, %60, %61, %62, %63}, {b0, b1, b2, b3}, d, 1, 1, 1, 0;\nwgmma.commit_group.sync.aligned;\nwgmma.wait_group.sync.aligned 1;\nmov.b32 a2, b1;\nmov.b32 a0, t0;\nmov.b32 a3, t0;\nmov.b32 a1, t1;\n"
        "ld.shared.b32 t0, [%64+2304];\nld.shared.b32 t1, [%64+2432];\nadd.s64 d, %65, 64;\nwgmma.fence.sync.aligned;\nwgmma.mma_async.sync.aligned.m64n96k16.f32.bf16.bf16 {%0, %1, %2, %3, %4, %5, %6, %7, %8, %9, %10, %11, %12, %13, %14, %15, %16, %17, %18, %19, %20, %21, %22, %23, %24, %25, %26, %27, %28, %29, %30, %31, %32, %33, %34, %35, %36, %37, %38, %39, %40, %41, %42, %43, %44, %45, %46, %47}, {a0, a1, a2, a3}, d, 1, 1, 1, 0;\nwgmma.commit_group.sync.aligned;\nwgmma.wait_group.sync.aligned 1;\nmov.b32 b2, a1;\nmov.b32 b0, t0;\nmov.b32 b3, t0;\nmov.b32 b1, t1;\n"
        "ld.shared.b32 t0, [%64+2560];\nld.shared.b32 t1, [%64+2688];\nadd.s64 d, %65, 72;\nwgmma.fence.sync.aligned;\nwgmma.mma_async.sync.aligned.m64n96k16.f32.bf16.bf16 {%0, %1, %2, %3, %4, %5, %6, %7, %8, %9, %10, %11, %12, %13, %14, %15, %16, %17, %18, %19, %20, %21, %22, %23, %24, %25, %26, %27, %28, %29, %30, %31, %32, %33, %34, %35, %36, %37, %38, %39, %40, %41, %42, %43, %44, %45, %46, %47}, {b0, b1, b2, b3}, d, 1, 1, 1, 0;\nwgmma.commit_group.sync.aligned;\nwgmma.wait_group.sync.aligned 1;\nmov.b32 a2, b1;\nmov.b32 a0, t0;\nmov.b32 a3, t0;\nmov.b32 a1, t1;\n"
        "ld.shared.b32 t0, [%64+2816];\nld.shared.b32 t1, [%64+2944];\nadd.s64 d, %65, 80;\nwgmma.fence.sync.aligned;\nwgmma.mma_async.sync.aligned.m64n88k16.f32.bf16.bf16 {%0, %1, %2, %3, %4, %5, %6, %7, %8, %9, %10, %11, %12, %13, %14, %15, %16, %17, %18, %19, %20, %21, %22, %23, %24, %25, %26, %27, %28, %29, %30, %31, %32, %33, %34, %35, %36, %37, %38, %39, %40, %41, %42, %43}, {a0, a1, a2, a3}, d, 1, 1, 1, 0;\nwgmma.commit_group.sync.aligned;\nwgmma.wait_group.sync.aligned 1;\nmov.b32 b2, a1;\nmov.b32 b0, t0;\nmov.b32 b3, t0;\nmov.b32 b1, t1;\n"
        "ld.shared.b32 t0, [%64+3072];\nld.shared.b32 t1, [%64+3200];\nadd.s64 d, %65, 88;\nwgmma.fence.sync.aligned;\nwgmma.mma_async.sync.aligned.m64n88k16.f32.bf16.bf16 {%0, %1, %2, %3, %4, %5, %6, %7, %8, %9, %10, %11, %12, %13, %14, %15, %16, %17, %18, %19, %20, %21, %22, %23, %24, %25, %26, %27, %28, %29, %30, %31, %32, %33, %34, %35, %36, %37, %38, %39, %40, %41, %42, %43}, {b0, b1, b2, b3}, d, 1, 1, 1, 0;\nwgmma.commit_group.sync.aligned;\nwgmma.wait_group.sync.aligned 1;\nmov.b32 a2, b1;\nmov.b32 a0, t0;\nmov.b32 a3, t0;\nmov.b32 a1, t1;\n"
        "ld.shared.b32 t0, [%64+3328];\nld.shared.b32 t1, [%64+3456];\nadd.s64 d, %65, 96;\nwgmma.fence.sync.aligned;\nwgmma.mma_async.sync.aligned.m64n80k16.f32.bf16.bf16 {%0, %1, %2, %3, %4, %5, %6, %7, %8, %9, %10, %11, %12, %13, %14, %15, %16, %17, %18, %19, %20, %21, %22, %23, %24, %25, %26, %27, %28, %29, %30, %31, %32, %33, %34, %35, %36, %37, %38, %39}, {a0, a1, a2, a3}, d, 1, 1, 1, 0;\nwgmma.commit_group.sync.aligned;\nwgmma.wait_group.sync.aligned 1;\nmov.b32 b2, a1;\nmov.b32 b0, t0;\nmov.b32 b3, t0;\nmov.b32 b1, t1;\n"
        "ld.shared.b32 t0, [%64+3584];\nld.shared.b32 t1, [%64+3712];\nadd.s64 d, %65, 104;\nwgmma.fence.sync.aligned;\nwgmma.mma_async.sync.aligned.m64n80k16.f32.bf16.bf16 {%0, %1, %2, %3, %4, %5, %6, %7, %8, %9, %10, %11, %12, %13, %14, %15, %16, %17, %18, %19, %20, %21, %22, %23, %24, %25, %26, %27, %28, %29, %30, %31, %32, %33, %34, %35, %36, %37, %38, %39}, {b0, b1, b2, b3}, d, 1, 1, 1, 0;\nwgmma.commit_group.sync.aligned;\nwgmma.wait_group.sync.aligned 1;\nmov.b32 a2, b1;\nmov.b32 a0, t0;\nmov.b32 a3, t0;\nmov.b32 a1, t1;\n"
        "ld.shared.b32 t0, [%64+3840];\nld.shared.b32 t1, [%64+3968];\nadd.s64 d, %65, 112;\nwgmma.fence.sync.aligned;\nwgmma.mma_async.sync.aligned.m64n72k16.f32.bf16.bf16 {%0, %1, %2, %3, %4, %5, %6, %7, %8, %9, %10, %11, %12, %13, %14, %15, %16, %17, %18, %19, %20, %21, %22, %23, %24, %25, %26, %27, %28, %29, %30, %31, %32, %33, %34, %35}, {a0, a1, a2, a3}, d, 1, 1, 1, 0;\nwgmma.commit_group.sync.aligned;\nwgmma.wait_group.sync.aligned 1;\nmov.b32 b2, a1;\nmov.b32 b0, t0;\nmov.b32 b3, t0;\nmov.b32 b1, t1;\n"
        "ld.shared.b32 t0, [%64+4096];\nld.shared.b32 t1, [%64+4224];\nadd.s64 d, %65, 120;\nwgmma.fence.sync.aligned;\nwgmma.mma_async.sync.aligned.m64n72k16.f32.bf16.bf16 {%0, %1, %2, %3, %4, %5, %6, %7, %8, %9, %10, %11, %12, %13, %14, %15, %16, %17, %18, %19, %20, %21, %22, %23, %24, %25, %26, %27, %28, %29, %30, %31, %32, %33, %34, %35}, {b0, b1, b2, b3}, d, 1, 1, 1, 0;\nwgmma.commit_group.sync.aligned;\nwgmma.wait_group.sync.aligned 1;\nmov.b32 a2, b1;\nmov.b32 a0, t0;\nmov.b32 a3, t0;\nmov.b32 a1, t1;\n"
        "ld.shared.b32 t0, [%64+4352];\nld.shared.b32 t1, [%64+4480];\nadd.s64 d, %65, 128;\nwgmma.fence.sync.aligned;\nwgmma.mma_async.sync.aligned.m64n64k16.f32.bf16.bf16 {%0, %1, %2, %3, %4, %5, %6, %7, %8, %9, %10, %11, %12, %13, %14, %15, %16, %17, %18, %19, %20, %21, %22, %23, %24, %25, %26, %27, %28, %29, %30, %31}, {a0, a1, a2, a3}, d, 1, 1, 1, 0;\nwgmma.commit_group.sync.aligned;\nwgmma.wait_group.sync.aligned 1;\nmov.b32 b2, a1;\nmov.b32 b0, t0;\nmov.b32 b3, t0;\nmov.b32 b1, t1;\n"
        "ld.shared.b32 t0, [%64+4608];\nld.shared.b32 t1, [%64+4736];\nadd.s64 d, %65, 136;\nwgmma.fence.sync.aligned;\nwgmma.mma_async.sync.aligned.m64n64k16.f32.bf16.bf16 {%0, %1, %2, %3, %4, %5, %6, %7, %8, %9, %10, %11, %12, %13, %14, %15, %16, %17, %18, %19, %20, %21, %22, %23, %24, %25, %26, %27, %28, %29, %30, %31}, {b0, b1, b2, b3}, d, 1, 1, 1, 0;\nwgmma.commit_group.sync.aligned;\nwgmma.wait_group.sync.aligned 1;\nmov.b32 a2, b1;\nmov.b32 a0, t0;\nmov.b32 a3, t0;\nmov.b32 a1, t1;\n"
        "ld.shared.b32 t0, [%64+4864];\nld.shared.b32 t1, [%64+4992];\nadd.s64 d, %65, 144;\nwgmma.fence.sync.aligned;\nwgmma.mma_async.sync.aligned.m64n56k16.f32.bf16.bf16 {%0, %1, %2, %3, %4, %5, %6, %7, %8, %9, %10, %11, %12, %13, %14, %15, %16, %17, %18, %19, %20, %21, %22, %23, %24, %25, %26, %27}, {a0, a1, a2, a3}, d, 1, 1, 1, 0;\nwgmma.commit_group.sync.aligned;\nwgmma.wait_group.sync.aligned 1;\nmov.b32 b2, a1;\nmov.b32 b0, t0;\nmov.b32 b3, t0;\nmov.b32 b1, t1;\n"
        "ld.shared.b32 t0, [%64+5120];\nld.shared.b32 t1, [%64+5248];\nadd.s64 d, %65, 152;\nwgmma.fence.sync.aligned;\nwgmma.mma_async.sync.aligned.m64n56k16.f32.bf16.bf16 {%0, %1, %2, %3, %4, %5, %6, %7, %8, %9, %10, %11, %12, %13, %14, %15, %16, %17, %18, %19, %20, %21, %22, %23, %24, %25, %26, %27}, {b0, b1, b2, b3}, d, 1, 1, 1, 0;\nwgmma.commit_group.sync.aligned;\nwgmma.wait_group.sync.aligned 1;\nmov.b32 a2, b1;\nmov.b32 a0, t0;\nmov.b32 a3, t0;\nmov.b32 a1, t1;\n"
        "ld.shared.b32 t0, [%64+5376];\nld.shared.b32 t1, [%64+5504];\nadd.s64 d, %65, 160;\nwgmma.fence.sync.aligned;\nwgmma.mma_async.sync.aligned.m64n48k16.f32.bf16.bf16 {%0, %1, %2, %3, %4, %5, %6, %7, %8, %9, %10, %11, %12, %13, %14, %15, %16, %17, %18, %19, %20, %21, %22, %23}, {a0, a1, a2, a3}, d, 1, 1, 1, 0;\nwgmma.commit_group.sync.aligned;\nwgmma.wait_group.sync.aligned 1;\nmov.b32 b2, a1;\nmov.b32 b0, t0;\nmov.b32 b3, t0;\nmov.b32 b1, t1;\n"
        "ld.shared.b32 t0, [%64+5632];\nld.shared.b32 t1, [%64+5760];\nadd.s64 d, %65, 168;\nwgmma.fence.sync.aligned;\nwgmma.mma_async.sync.aligned.m64n48k16.f32.bf16.bf16 {%0, %1, %2, %3, %4, %5, %6, %7, %8, %9, %10, %11, %12, %13, %14, %15, %16, %17, %18, %19, %20, %21, %22, %23}, {b0, b1, b2, b3}, d, 1, 1, 1, 0;\nwgmma.commit_group.sync.aligned;\nwgmma.wait_group.sync.aligned 1;\nmov.b32 a2, b1;\nmov.b32 a0, t0;\nmov.b32 a3, t0;\nmov.b32 a1, t1;\n"
        "ld.shared.b32 t0, [%64+5888];\nld.shared.b32 t1, [%64+6016];\nadd.s64 d, %65, 176;\nwgmma.fence.sync.aligned;\nwgmma.mma_async.sync.aligned.m64n40k16.f32.bf16.bf16 {%0, %1, %2, %3, %4, %5, %6, %7, %8, %9, %10, %11, %12, %13, %14, %15, %16, %17, %18, %19}, {a0, a1, a2, a3}, d, 1, 1, 1, 0;\nwgmma.commit_group.sync.aligned;\nwgmma.wait_group.sync.aligned 1;\nmov.b32 b2, a1;\nmov.b32 b0, t0;\nmov.b32 b3, t0;\nmov.b32 b1, t1;\n"
        "ld.shared.b32 t0, [%64+6144];\nld.shared.b32 t1, [%64+6272];\nadd.s64 d, %65, 184;\nwgmma.fence.sync.aligned;\nwgmma.mma_async.sync.aligned.m64n40k16.f32.bf16.bf16 {%0, %1, %2, %3, %4, %5, %6, %7, %8, %9, %10, %11, %12, %13, %14, %15, %16, %17, %18, %19}, {b0, b1, b2, b3}, d, 1, 1, 1, 0;\nwgmma.commit_group.sync.aligned;\nwgmma.wait_group.sync.aligned 1;\nmov.b32 a2, b1;\nmov.b32 a0, t0;\nmov.b32 a3, t0;\nmov.b32 a1, t1;\n"
        "ld.shared.b32 t0, [%64+6400];\nld.shared.b32 t1, [%64+6528];\nadd.s64 d, %65, 192;\nwgmma.fence.sync.aligned;\nwgmma.mma_async.sync.aligned.m64n32k16.f32.bf16.bf16 {%0, %1, %2, %3, %4, %5, %6, %7, %8, %9, %10, %11, %12, %13, %14, %15}, {a0, a1, a2, a3}, d, 1, 1, 1, 0;\nwgmma.commit_group.sync.aligned;\nwgmma.wait_group.sync.aligned 1;\nmov.b32 b2, a1;\nmov.b32 b0, t0;\nmov.b32 b3, t0;\nmov.b32 b1, t1;\n"
        "ld.shared.b32 t0, [%64+6656];\nld.shared.b32 t1, [%64+6784];\nadd.s64 d, %65, 200;\nwgmma.fence.sync.aligned;\nwgmma.mma_async.sync.aligned.m64n32k16.f32.bf16.bf16 {%0, %1, %2, %3, %4, %5, %6, %7, %8, %9, %10, %11, %12, %13, %14, %15}, {b0, b1, b2, b3}, d, 1, 1, 1, 0;\nwgmma.commit_group.sync.aligned;\nwgmma.wait_group.sync.aligned 1;\nmov.b32 a2, b1;\nmov.b32 a0, t0;\nmov.b32 a3, t0;\nmov.b32 a1, t1;\n"
        "ld.shared.b32 t0, [%64+6912];\nld.shared.b32 t1, [%64+7040];\nadd.s64 d, %65, 208;\nwgmma.fence.sync.aligned;\nwgmma.mma_async.sync.aligned.m64n24k16.f32.bf16.bf16 {%0, %1, %2, %3, %4, %5, %6, %7, %8, %9, %10, %11}, {a0, a1, a2, a3}, d, 1, 1, 1, 0;\nwgmma.commit_group.sync.aligned;\nwgmma.wait_group.sync.aligned 1;\nmov.b32 b2, a1;\nmov.b32 b0, t0;\nmov.b32 b3, t0;\nmov.b32 b1, t1;\n"
        "ld.shared.b32 t0, [%64+7168];\nld.shared.b32 t1, [%64+7296];\nadd.s64 d, %65, 216;\nwgmma.fence.sync.aligned;\nwgmma.mma_async.sync.aligned.m64n24k16.f32.bf16.bf16 {%0, %1, %2, %3, %4, %5, %6, %7, %8, %9, %10, %11}, {b0, b1, b2, b3}, d, 1, 1, 1, 0;\nwgmma.commit_group.sync.aligned;\nwgmma.wait_group.sync.aligned 1;\nmov.b32 a2, b1;\nmov.b32 a0, t0;\nmov.b32 a3, t0;\nmov.b32 a1, t1;\n"
        "ld.shared.b32 t0, [%64+7424];\nld.shared.b32 t1, [%64+7552];\nadd.s64 d, %65, 224;\nwgmma.fence.sync.aligned;\nwgmma.mma_async.sync.aligned.m64n16k16.f32.bf16.bf16 {%0, %1, %2, %3, %4, %5, %6, %7}, {a0, a1, a2, a3}, d, 1, 1, 1, 0;\nwgmma.commit_group.sync.aligned;\nwgmma.wait_group.sync.aligned 1;\nmov.b32 b2, a1;\nmov.b32 b0, t0;\nmov.b32 b3, t0;\nmov.b32 b1, t1;\n"
        "ld.shared.b32 t0, [%64+7680];\nld.shared.b32 t1, [%64+7808];\nadd.s64 d, %65, 232;\nwgmma.fence.sync.aligned;\nwgmma.mma_async.sync.aligned.m64n16k16.f32.bf16.bf16 {%0, %1, %2, %3, %4, %5, %6, %7}, {b0, b1, b2, b3}, d, 1, 1, 1, 0;\nwgmma.commit_group.sync.aligned;\nwgmma.wait_group.sync.aligned 1;\nmov.b32 a2, b1;\nmov.b32 a0, t0;\nmov.b32 a3, t0;\nmov.b32 a1, t1;\n"
        "ld.shared.b32 t0, [%64+7936];\nld.shared.b32 t1, [%64+8064];\nadd.s64 d, %65, 240;\nwgmma.fence.sync.aligned;\nwgmma.mma_async.sync.aligned.m64n8k16.f32.bf16.bf16 {%0, %1, %2, %3}, {a0, a1, a2, a3}, d, 1, 1, 1, 0;\nwgmma.commit_group.sync.aligned;\nwgmma.wait_group.sync.aligned 1;\nmov.b32 b2, a1;\nmov.b32 b0, t0;\nmov.b32 b3, t0;\nmov.b32 b1, t1;\n"
        "add.s64 d, %65, 248;\nwgmma.fence.sync.aligned;\nwgmma.mma_async.sync.aligned.m64n8k16.f32.bf16.bf16 {%0, %1, %2, %3}, {b0, b1, b2, b3}, d, 1, 1, 1, 0;\nwgmma.commit_group.sync.aligned;\nwgmma.wait_group.sync.aligned 0;\n"
        "}" : "+f"(d[0]), "+f"(d[1]), "+f"(d[2]), "+f"(d[3]), "+f"(d[4]), "+f"(d[5]), "+f"(d[6]), "+f"(d[7]), "+f"(d[8]), "+f"(d[9]), "+f"(d[10]), "+f"(d[11]), "+f"(d[12]), "+f"(d[13]), "+f"(d[14]), "+f"(d[15]), "+f"(d[16]), "+f"(d[17]), "+f"(d[18]), "+f"(d[19]), "+f"(d[20]), "+f"(d[21]), "+f"(d[22]), "+f"(d[23]), "+f"(d[24]), "+f"(d[25]), "+f"(d[26]), "+f"(d[27]), "+f"(d[28]), "+f"(d[29]), "+f"(d[30]), "+f"(d[31]), "+f"(d[32]), "+f"(d[33]), "+f"(d[34]), "+f"(d[35]), "+f"(d[36]), "+f"(d[37]), "+f"(d[38]), "+f"(d[39]), "+f"(d[40]), "+f"(d[41]), "+f"(d[42]), "+f"(d[43]), "+f"(d[44]), "+f"(d[45]), "+f"(d[46]), "+f"(d[47]), "+f"(d[48]), "+f"(d[49]), "+f"(d[50]), "+f"(d[51]), "+f"(d[52]), "+f"(d[53]), "+f"(d[54]), "+f"(d[55]), "+f"(d[56]), "+f"(d[57]), "+f"(d[58]), "+f"(d[59]), "+f"(d[60]), "+f"(d[61]), "+f"(d[62]), "+f"(d[63]) : "r"(pa), "l"(db) : "memory");
}
__device__ __forceinline__ void wgmma_rs80(float (&d)[40], uint32_t a0, uint32_t a1, uint32_t a2, uint32_t a3, uint64_t db, int sc) {
    asm volatile("{\n.reg .pred p;\nsetp.ne.b32 p, %45, 0;\n"
        "wgmma.mma_async.sync.aligned.m64n80k16.f32.bf16.bf16 {%0, %1, %2, %3, %4, %5, %6, %7, %8, %9, %10, %11, %12, %13, %14, %15, %16, %17, %18, %19, %20, %21, %22, %23, %24, %25, %26, %27, %28, %29, %30, %31, %32, %33, %34, %35, %36, %37, %38, %39}, {%40, %41, %42, %43}, %44, p, 1, 1, 1;\n}\n"
        : "+f"(d[0]), "+f"(d[1]), "+f"(d[2]), "+f"(d[3]), "+f"(d[4]), "+f"(d[5]), "+f"(d[6]), "+f"(d[7]), "+f"(d[8]), "+f"(d[9]), "+f"(d[10]), "+f"(d[11]), "+f"(d[12]), "+f"(d[13]), "+f"(d[14]), "+f"(d[15]), "+f"(d[16]), "+f"(d[17]), "+f"(d[18]), "+f"(d[19]), "+f"(d[20]), "+f"(d[21]), "+f"(d[22]), "+f"(d[23]), "+f"(d[24]), "+f"(d[25]), "+f"(d[26]), "+f"(d[27]), "+f"(d[28]), "+f"(d[29]), "+f"(d[30]), "+f"(d[31]), "+f"(d[32]), "+f"(d[33]), "+f"(d[34]), "+f"(d[35]), "+f"(d[36]), "+f"(d[37]), "+f"(d[38]), "+f"(d[39]) : "r"(a0), "r"(a1), "r"(a2), "r"(a3), "l"(db), "r"(sc));
}
__device__ __forceinline__ void wgmma_ss80(float (&d)[40], uint64_t da, uint64_t db, int sc) {
    asm volatile("{\n.reg .pred p;\nsetp.ne.b32 p, %42, 0;\n"
        "wgmma.mma_async.sync.aligned.m64n80k16.f32.bf16.bf16 {%0, %1, %2, %3, %4, %5, %6, %7, %8, %9, %10, %11, %12, %13, %14, %15, %16, %17, %18, %19, %20, %21, %22, %23, %24, %25, %26, %27, %28, %29, %30, %31, %32, %33, %34, %35, %36, %37, %38, %39}, %40, %41, p, 1, 1, 0, 1;\n}\n"
        : "+f"(d[0]), "+f"(d[1]), "+f"(d[2]), "+f"(d[3]), "+f"(d[4]), "+f"(d[5]), "+f"(d[6]), "+f"(d[7]), "+f"(d[8]), "+f"(d[9]), "+f"(d[10]), "+f"(d[11]), "+f"(d[12]), "+f"(d[13]), "+f"(d[14]), "+f"(d[15]), "+f"(d[16]), "+f"(d[17]), "+f"(d[18]), "+f"(d[19]), "+f"(d[20]), "+f"(d[21]), "+f"(d[22]), "+f"(d[23]), "+f"(d[24]), "+f"(d[25]), "+f"(d[26]), "+f"(d[27]), "+f"(d[28]), "+f"(d[29]), "+f"(d[30]), "+f"(d[31]), "+f"(d[32]), "+f"(d[33]), "+f"(d[34]), "+f"(d[35]), "+f"(d[36]), "+f"(d[37]), "+f"(d[38]), "+f"(d[39]) : "l"(da), "l"(db), "r"(sc));
}
__device__ __forceinline__ void wgmma_ss80t(float (&d)[40], uint64_t da, uint64_t db, int sc) {
    asm volatile("{\n.reg .pred p;\nsetp.ne.b32 p, %42, 0;\n"
        "wgmma.mma_async.sync.aligned.m64n80k16.f32.bf16.bf16 {%0, %1, %2, %3, %4, %5, %6, %7, %8, %9, %10, %11, %12, %13, %14, %15, %16, %17, %18, %19, %20, %21, %22, %23, %24, %25, %26, %27, %28, %29, %30, %31, %32, %33, %34, %35, %36, %37, %38, %39}, %40, %41, p, 1, 1, 1, 1;\n}\n"
        : "+f"(d[0]), "+f"(d[1]), "+f"(d[2]), "+f"(d[3]), "+f"(d[4]), "+f"(d[5]), "+f"(d[6]), "+f"(d[7]), "+f"(d[8]), "+f"(d[9]), "+f"(d[10]), "+f"(d[11]), "+f"(d[12]), "+f"(d[13]), "+f"(d[14]), "+f"(d[15]), "+f"(d[16]), "+f"(d[17]), "+f"(d[18]), "+f"(d[19]), "+f"(d[20]), "+f"(d[21]), "+f"(d[22]), "+f"(d[23]), "+f"(d[24]), "+f"(d[25]), "+f"(d[26]), "+f"(d[27]), "+f"(d[28]), "+f"(d[29]), "+f"(d[30]), "+f"(d[31]), "+f"(d[32]), "+f"(d[33]), "+f"(d[34]), "+f"(d[35]), "+f"(d[36]), "+f"(d[37]), "+f"(d[38]), "+f"(d[39]) : "l"(da), "l"(db), "r"(sc));
}
__device__ __forceinline__ void wgmma_ss8_ta(float (&d)[4], uint64_t da, uint64_t db, int sc) {
    asm volatile("{\n.reg .pred p;\nsetp.ne.b32 p, %6, 0;\n"
        "wgmma.mma_async.sync.aligned.m64n8k16.f32.bf16.bf16 {%0, %1, %2, %3}, %4, %5, p, 1, 1, 1, 0;\n}\n"
        : "+f"(d[0]), "+f"(d[1]), "+f"(d[2]), "+f"(d[3]) : "l"(da), "l"(db), "r"(sc));
}
__device__ __forceinline__ void wgmma_rs8(float (&d)[4], uint32_t a0, uint32_t a1, uint32_t a2, uint32_t a3, uint64_t db, int sc) {
    asm volatile("{\n.reg .pred p;\nsetp.ne.b32 p, %9, 0;\n"
        "wgmma.mma_async.sync.aligned.m64n8k16.f32.bf16.bf16 {%0, %1, %2, %3}, {%4, %5, %6, %7}, %8, p, 1, 1, 0;\n}\n"
        : "+f"(d[0]), "+f"(d[1]), "+f"(d[2]), "+f"(d[3]) : "r"(a0), "r"(a1), "r"(a2), "r"(a3), "l"(db), "r"(sc));
}
__device__ __forceinline__ void wgmma_rs128(float (&d)[64], uint32_t a0, uint32_t a1, uint32_t a2, uint32_t a3, uint64_t db, int sc) {
    asm volatile("{\n.reg .pred p;\nsetp.ne.b32 p, %69, 0;\n"
        "wgmma.mma_async.sync.aligned.m64n128k16.f32.bf16.bf16 {%0, %1, %2, %3, %4, %5, %6, %7, %8, %9, %10, %11, %12, %13, %14, %15, %16, %17, %18, %19, %20, %21, %22, %23, %24, %25, %26, %27, %28, %29, %30, %31, %32, %33, %34, %35, %36, %37, %38, %39, %40, %41, %42, %43, %44, %45, %46, %47, %48, %49, %50, %51, %52, %53, %54, %55, %56, %57, %58, %59, %60, %61, %62, %63}, {%64, %65, %66, %67}, %68, p, 1, 1, 1;\n}\n"
        : "+f"(d[0]), "+f"(d[1]), "+f"(d[2]), "+f"(d[3]), "+f"(d[4]), "+f"(d[5]), "+f"(d[6]), "+f"(d[7]), "+f"(d[8]), "+f"(d[9]), "+f"(d[10]), "+f"(d[11]), "+f"(d[12]), "+f"(d[13]), "+f"(d[14]), "+f"(d[15]), "+f"(d[16]), "+f"(d[17]), "+f"(d[18]), "+f"(d[19]), "+f"(d[20]), "+f"(d[21]), "+f"(d[22]), "+f"(d[23]), "+f"(d[24]), "+f"(d[25]), "+f"(d[26]), "+f"(d[27]), "+f"(d[28]), "+f"(d[29]), "+f"(d[30]), "+f"(d[31]), "+f"(d[32]), "+f"(d[33]), "+f"(d[34]), "+f"(d[35]), "+f"(d[36]), "+f"(d[37]), "+f"(d[38]), "+f"(d[39]), "+f"(d[40]), "+f"(d[41]), "+f"(d[42]), "+f"(d[43]), "+f"(d[44]), "+f"(d[45]), "+f"(d[46]), "+f"(d[47]), "+f"(d[48]), "+f"(d[49]), "+f"(d[50]), "+f"(d[51]), "+f"(d[52]), "+f"(d[53]), "+f"(d[54]), "+f"(d[55]), "+f"(d[56]), "+f"(d[57]), "+f"(d[58]), "+f"(d[59]), "+f"(d[60]), "+f"(d[61]), "+f"(d[62]), "+f"(d[63]) : "r"(a0), "r"(a1), "r"(a2), "r"(a3), "l"(db), "r"(sc));
}
__device__ __forceinline__ void wgmma_rs88(float (&d)[44], uint32_t a0, uint32_t a1, uint32_t a2, uint32_t a3, uint64_t db, int sc) {
    asm volatile("{\n.reg .pred p;\nsetp.ne.b32 p, %49, 0;\n"
        "wgmma.mma_async.sync.aligned.m64n88k16.f32.bf16.bf16 {%0, %1, %2, %3, %4, %5, %6, %7, %8, %9, %10, %11, %12, %13, %14, %15, %16, %17, %18, %19, %20, %21, %22, %23, %24, %25, %26, %27, %28, %29, %30, %31, %32, %33, %34, %35, %36, %37, %38, %39, %40, %41, %42, %43}, {%44, %45, %46, %47}, %48, p, 1, 1, 1;\n}\n"
        : "+f"(d[0]), "+f"(d[1]), "+f"(d[2]), "+f"(d[3]), "+f"(d[4]), "+f"(d[5]), "+f"(d[6]), "+f"(d[7]), "+f"(d[8]), "+f"(d[9]), "+f"(d[10]), "+f"(d[11]), "+f"(d[12]), "+f"(d[13]), "+f"(d[14]), "+f"(d[15]), "+f"(d[16]), "+f"(d[17]), "+f"(d[18]), "+f"(d[19]), "+f"(d[20]), "+f"(d[21]), "+f"(d[22]), "+f"(d[23]), "+f"(d[24]), "+f"(d[25]), "+f"(d[26]), "+f"(d[27]), "+f"(d[28]), "+f"(d[29]), "+f"(d[30]), "+f"(d[31]), "+f"(d[32]), "+f"(d[33]), "+f"(d[34]), "+f"(d[35]), "+f"(d[36]), "+f"(d[37]), "+f"(d[38]), "+f"(d[39]), "+f"(d[40]), "+f"(d[41]), "+f"(d[42]), "+f"(d[43]) : "r"(a0), "r"(a1), "r"(a2), "r"(a3), "l"(db), "r"(sc));
}
__device__ __forceinline__ void wgmma_rs128k(float (&d)[64], uint32_t a0, uint32_t a1, uint32_t a2, uint32_t a3, uint64_t db, int sc) {
    asm volatile("{\n.reg .pred p;\nsetp.ne.b32 p, %69, 0;\n"
        "wgmma.mma_async.sync.aligned.m64n128k16.f32.bf16.bf16 {%0, %1, %2, %3, %4, %5, %6, %7, %8, %9, %10, %11, %12, %13, %14, %15, %16, %17, %18, %19, %20, %21, %22, %23, %24, %25, %26, %27, %28, %29, %30, %31, %32, %33, %34, %35, %36, %37, %38, %39, %40, %41, %42, %43, %44, %45, %46, %47, %48, %49, %50, %51, %52, %53, %54, %55, %56, %57, %58, %59, %60, %61, %62, %63}, {%64, %65, %66, %67}, %68, p, 1, 1, 0;\n}\n"
        : "+f"(d[0]), "+f"(d[1]), "+f"(d[2]), "+f"(d[3]), "+f"(d[4]), "+f"(d[5]), "+f"(d[6]), "+f"(d[7]), "+f"(d[8]), "+f"(d[9]), "+f"(d[10]), "+f"(d[11]), "+f"(d[12]), "+f"(d[13]), "+f"(d[14]), "+f"(d[15]), "+f"(d[16]), "+f"(d[17]), "+f"(d[18]), "+f"(d[19]), "+f"(d[20]), "+f"(d[21]), "+f"(d[22]), "+f"(d[23]), "+f"(d[24]), "+f"(d[25]), "+f"(d[26]), "+f"(d[27]), "+f"(d[28]), "+f"(d[29]), "+f"(d[30]), "+f"(d[31]), "+f"(d[32]), "+f"(d[33]), "+f"(d[34]), "+f"(d[35]), "+f"(d[36]), "+f"(d[37]), "+f"(d[38]), "+f"(d[39]), "+f"(d[40]), "+f"(d[41]), "+f"(d[42]), "+f"(d[43]), "+f"(d[44]), "+f"(d[45]), "+f"(d[46]), "+f"(d[47]), "+f"(d[48]), "+f"(d[49]), "+f"(d[50]), "+f"(d[51]), "+f"(d[52]), "+f"(d[53]), "+f"(d[54]), "+f"(d[55]), "+f"(d[56]), "+f"(d[57]), "+f"(d[58]), "+f"(d[59]), "+f"(d[60]), "+f"(d[61]), "+f"(d[62]), "+f"(d[63]) : "r"(a0), "r"(a1), "r"(a2), "r"(a3), "l"(db), "r"(sc));
}
__device__ __forceinline__ void wgmma_rs88k(float (&d)[44], uint32_t a0, uint32_t a1, uint32_t a2, uint32_t a3, uint64_t db, int sc) {
    asm volatile("{\n.reg .pred p;\nsetp.ne.b32 p, %49, 0;\n"
        "wgmma.mma_async.sync.aligned.m64n88k16.f32.bf16.bf16 {%0, %1, %2, %3, %4, %5, %6, %7, %8, %9, %10, %11, %12, %13, %14, %15, %16, %17, %18, %19, %20, %21, %22, %23, %24, %25, %26, %27, %28, %29, %30, %31, %32, %33, %34, %35, %36, %37, %38, %39, %40, %41, %42, %43}, {%44, %45, %46, %47}, %48, p, 1, 1, 0;\n}\n"
        : "+f"(d[0]), "+f"(d[1]), "+f"(d[2]), "+f"(d[3]), "+f"(d[4]), "+f"(d[5]), "+f"(d[6]), "+f"(d[7]), "+f"(d[8]), "+f"(d[9]), "+f"(d[10]), "+f"(d[11]), "+f"(d[12]), "+f"(d[13]), "+f"(d[14]), "+f"(d[15]), "+f"(d[16]), "+f"(d[17]), "+f"(d[18]), "+f"(d[19]), "+f"(d[20]), "+f"(d[21]), "+f"(d[22]), "+f"(d[23]), "+f"(d[24]), "+f"(d[25]), "+f"(d[26]), "+f"(d[27]), "+f"(d[28]), "+f"(d[29]), "+f"(d[30]), "+f"(d[31]), "+f"(d[32]), "+f"(d[33]), "+f"(d[34]), "+f"(d[35]), "+f"(d[36]), "+f"(d[37]), "+f"(d[38]), "+f"(d[39]), "+f"(d[40]), "+f"(d[41]), "+f"(d[42]), "+f"(d[43]) : "r"(a0), "r"(a1), "r"(a2), "r"(a3), "l"(db), "r"(sc));
}
__device__ __forceinline__ void wgmma_rs80k(float (&d)[40], uint32_t a0, uint32_t a1, uint32_t a2, uint32_t a3, uint64_t db, int sc) {
    asm volatile("{\n.reg .pred p;\nsetp.ne.b32 p, %45, 0;\n"
        "wgmma.mma_async.sync.aligned.m64n80k16.f32.bf16.bf16 {%0, %1, %2, %3, %4, %5, %6, %7, %8, %9, %10, %11, %12, %13, %14, %15, %16, %17, %18, %19, %20, %21, %22, %23, %24, %25, %26, %27, %28, %29, %30, %31, %32, %33, %34, %35, %36, %37, %38, %39}, {%40, %41, %42, %43}, %44, p, 1, 1, 0;\n}\n"
        : "+f"(d[0]), "+f"(d[1]), "+f"(d[2]), "+f"(d[3]), "+f"(d[4]), "+f"(d[5]), "+f"(d[6]), "+f"(d[7]), "+f"(d[8]), "+f"(d[9]), "+f"(d[10]), "+f"(d[11]), "+f"(d[12]), "+f"(d[13]), "+f"(d[14]), "+f"(d[15]), "+f"(d[16]), "+f"(d[17]), "+f"(d[18]), "+f"(d[19]), "+f"(d[20]), "+f"(d[21]), "+f"(d[22]), "+f"(d[23]), "+f"(d[24]), "+f"(d[25]), "+f"(d[26]), "+f"(d[27]), "+f"(d[28]), "+f"(d[29]), "+f"(d[30]), "+f"(d[31]), "+f"(d[32]), "+f"(d[33]), "+f"(d[34]), "+f"(d[35]), "+f"(d[36]), "+f"(d[37]), "+f"(d[38]), "+f"(d[39]) : "r"(a0), "r"(a1), "r"(a2), "r"(a3), "l"(db), "r"(sc));
}
__device__ __forceinline__ void wgmma_rs64(float (&d)[32], uint32_t a0, uint32_t a1, uint32_t a2, uint32_t a3, uint64_t db, int sc) {
    asm volatile("{\n.reg .pred p;\nsetp.ne.b32 p, %37, 0;\n"
        "wgmma.mma_async.sync.aligned.m64n64k16.f32.bf16.bf16 {%0, %1, %2, %3, %4, %5, %6, %7, %8, %9, %10, %11, %12, %13, %14, %15, %16, %17, %18, %19, %20, %21, %22, %23, %24, %25, %26, %27, %28, %29, %30, %31}, {%32, %33, %34, %35}, %36, p, 1, 1, 1;\n}\n"
        : "+f"(d[0]), "+f"(d[1]), "+f"(d[2]), "+f"(d[3]), "+f"(d[4]), "+f"(d[5]), "+f"(d[6]), "+f"(d[7]), "+f"(d[8]), "+f"(d[9]), "+f"(d[10]), "+f"(d[11]), "+f"(d[12]), "+f"(d[13]), "+f"(d[14]), "+f"(d[15]), "+f"(d[16]), "+f"(d[17]), "+f"(d[18]), "+f"(d[19]), "+f"(d[20]), "+f"(d[21]), "+f"(d[22]), "+f"(d[23]), "+f"(d[24]), "+f"(d[25]), "+f"(d[26]), "+f"(d[27]), "+f"(d[28]), "+f"(d[29]), "+f"(d[30]), "+f"(d[31]) : "r"(a0), "r"(a1), "r"(a2), "r"(a3), "l"(db), "r"(sc));
}

__device__ __forceinline__ uint64_t mkdesc(uint32_t lo) { return ((uint64_t)0x40000040u << 32) | lo; }
template <int F> __device__ __forceinline__ uint32_t lop3(uint32_t a, uint32_t b, uint32_t c) { uint32_t r; asm("lop3.b32 %0, %1, %2, %3, %4;" : "=r"(r) : "r"(a), "r"(b), "r"(c), "n"(F)); return r; }
__device__ __forceinline__ uint32_t tag(uint32_t w, uint32_t ep) { asm("lop3.b32 %0, %0, 1, %1, 0xB8;" : "+r"(w) : "r"(ep)); return w; }
template <int N> __device__ __forceinline__ void pack_part(uint32_t (&p)[32], const float (&v)[N], uint32_t ep) {
#pragma unroll
    for (int i = 0; i < N / 2; i++) p[i] = (i & 3) ? pack2(v[2 * i], v[2 * i + 1]) : tag(pack2(v[2 * i], v[2 * i + 1]), ep);
#pragma unroll
    for (int i = 0; i < N / 2; i++) asm volatile("" : "+r"(p[i]));
}
__device__ __forceinline__ void st_part(uint4* p, const uint32_t* v) {
    asm volatile("{\n.reg .b64 l, h;\n.reg .b128 q;\nmov.b64 l, {%1, %2};\nmov.b64 h, {%3, %4};\nmov.b128 q, {l, h};\nst.relaxed.gpu.global.b128 [%0], q;\n}"
                 ::"l"(p), "r"(v[0]), "r"(v[1]), "r"(v[2]), "r"(v[3]) : "memory");
}
__device__ __forceinline__ void st_peer(uint32_t a, uint32_t x, uint32_t y, uint32_t z, uint32_t w, uint32_t bar) {
    asm volatile("st.async.shared::cluster.mbarrier::complete_tx::bytes.v4.b32 [%0], {%1, %2, %3, %4}, [%5];" ::"r"(a), "r"(x), "r"(y), "r"(z), "r"(w), "r"(bar) : "memory");
}
__device__ __forceinline__ int g4_block(int c, int j) { return c ? j ^ (8 - 2 * c) : 8 + (j & 1); }
__device__ __forceinline__ uint32_t recv_off(int w) { return w ? OFF_XR : OFF_REM; }
__device__ __forceinline__ uint4 ld_part(const void* p) {
    uint4 v;
    asm volatile("{\n.reg .b64 l, h;\n.reg .b128 q;\nld.relaxed.gpu.global.b128 q, [%4];\nmov.b128 {l, h}, q;\nmov.b64 {%0, %1}, l;\nmov.b64 {%2, %3}, h;\n}"
                 : "=r"(v.x), "=r"(v.y), "=r"(v.z), "=r"(v.w) : "l"(p) : "memory");
    return v;
}
__device__ __forceinline__ void ld_part4(uint4 (&u)[4], const uint4* p, int st) {
#pragma unroll
    for (int i = 0; i < 4; i++) u[i] = ld_part(p + i * st);
}
__device__ __forceinline__ uint32_t stale4(const uint4 (&u)[4], uint32_t ep) { return (u[0].x ^ ep) | (u[1].x ^ ep) | (u[2].x ^ ep) | (u[3].x ^ ep); }
__device__ __forceinline__ void fix4(uint4 (&u)[4], const uint4* p, uint32_t ep, int code) {
    unsigned it = 0;
    while (__any_sync(~0u, stale4(u, ep) & 1)) {
        ld_part4(u, p, 128);
        STALE(code)
        SPIN_CHECK(58)
    }
}
__device__ __forceinline__ void add8(float* v, uint4 u) {
    v[0] += blo(u.x); v[1] += bhi(u.x); v[2] += blo(u.y); v[3] += bhi(u.y);
    v[4] += blo(u.z); v[5] += bhi(u.z); v[6] += blo(u.w); v[7] += bhi(u.w);
}
__device__ __forceinline__ void unpack8(float* v, uint4 u) {
    v[0] = blo(u.x); v[1] = bhi(u.x); v[2] = blo(u.y); v[3] = bhi(u.y); v[4] = blo(u.z); v[5] = bhi(u.z); v[6] = blo(u.w); v[7] = bhi(u.w);
}
__device__ __forceinline__ uint4 add2(uint4 a, uint4 b) { return make_uint4(add2(a.x, b.x), add2(a.y, b.y), add2(a.z, b.z), add2(a.w, b.w)); }
__device__ __forceinline__ void base16(float* v, uint4 b, float2 c, float2 d) {
    v[0] = fmaf(c.x, v[0], blo(b.x)); v[1] = fmaf(c.y, v[1], bhi(b.x)); v[2] = fmaf(c.x, v[2], blo(b.y)); v[3] = fmaf(c.y, v[3], bhi(b.y));
    v[4] = fmaf(d.x, v[4], blo(b.z)); v[5] = fmaf(d.y, v[5], bhi(b.z)); v[6] = fmaf(d.x, v[6], blo(b.w)); v[7] = fmaf(d.y, v[7], bhi(b.w));
}
__device__ __forceinline__ uint32_t split2(float x) { const float h = rbf(x); return pack2(h, x - h); }
__device__ __forceinline__ uint32_t b80_desc(uint32_t dsb, uint32_t wn, uint32_t rn, uint32_t h) {
    const uint32_t wb = dsb + OFF_W + (wn & 7) * 16384 + h * 8192, rm = dsb + OFF_REM + rn * 4096 + h * 2048;
    return (wb >> 4) | ((rm - wb) << 12);
}
constexpr int64_t B80_STEP = 128 - (126 << 16), B80_HALF = 512 - (384 << 16);
__device__ __forceinline__ int g1_block(int n, int j) { return n < 5 ? 2 * n + (j & 1) : 2 * n - 9 - (j & 1); }

template <int OCT>
__device__ __forceinline__ void gemv_tile(float (&d)[4], uint32_t a, uint32_t b, int kb0) {
    uint32_t alo = ((a & 0x3FFFF) >> 4) | 0x10000u, blo_ = ((b & 0x3FFFF) >> 4) | (OCT << 16);
#pragma unroll 1
    for (int s = 0; s < 20; s += 4) {
        const int kb = kb0 + (s >> 2);
        const uint32_t bk = blo_ + (OCT == 7 ? (kb & 1) * 288 + (kb >> 1) * 56 : kb * 64);
        wg_fence();
#pragma unroll
        for (int q = 0; q < 4; q++) wgmma_ss8_ta(d, mkdesc(alo + (s + q) * 128), ((uint64_t)8 << 32) | (bk + q * 2 * OCT), s + q);
        wg_commit();
    }
    wg_wait<0>();
    reg_fence(d);
}

__device__ __forceinline__ void flush_tile(uint32_t st, bf16* dst, int u) {
#pragma unroll
    for (int i = 0; i < 2; i++) {
        const int idx = u + 320 * i, row = idx >> 3, c = idx & 7;
        stg128(dst + (size_t)row * S_ + 8 * c, lds128(st + row * 128 + ((c ^ ((row >> 1) & 7)) << 4)));
    }
}

__device__ __forceinline__ int tid_now() { int t; asm volatile("mov.u32 %0, %%tid.x;" : "=r"(t)); return t; }
__device__ __forceinline__ float zscale(float c) { return c == 0.f ? 0x1p-30f : c; }
__device__ __forceinline__ bool bar_any(int id, bool p) {
    uint32_t r;
    asm volatile("{\n.reg .pred a, b;\nsetp.ne.u32 a, %2, 0;\nbarrier.red.or.pred.aligned b, %1, 128, a;\nselp.u32 %0, 1, 0, b;\n}" : "=r"(r) : "r"(id), "r"((uint32_t)p) : "memory");
    return r != 0;
}

__global__ void __launch_bounds__(NTHR, 1) fused_kernel(const __grid_constant__ Ptrs pp, bf16* __restrict__ out, const __grid_constant__ Maps mp) {
    extern __shared__ __align__(1024) uint8_t smem_raw[];
    const uint32_t sb = s2u(smem_raw), bars = sb + M_BAR, dsb = sb & 0x3FFFF;
    const int id = blockIdx.x, warp = __shfl_sync(0xffffffffu, (int)threadIdx.x >> 5, 0), wg = warp >> 2;
    const long long c0 = clock64();
#define TIDS const int tid = tid_now(), lane = tid & 31, wt = tid & 127, g = lane >> 2, t = lane & 3; (void)wt; (void)g; (void)t;
    TS(threadIdx.x == 0, 0) TG(threadIdx.x == 0, 62)

    if (id >= 128) {
        TIDS
        if (sb & 1023) __trap();
        const int hs = id - 128;
        constexpr int H_B = 204800;
        static_assert(H_B + TAB_BYTES + 8 * VEC_BYTES <= OFF_M, "helper map");
        if (warp < 10 && elect()) { mbar_init(bars + warp * 8, 1); mbar_init(bars + 80 + warp * 8, 1); asm volatile("fence.mbarrier_init.release.cluster;" ::: "memory"); }
        __syncthreads();
        const uint32_t e0 = ld_cold(&g_epoch);
        wait_clock(c0, HELP_T);
        uint4 wr[10];
#pragma unroll
        for (int u = 0; u < 10; u++) wr[u] = ldg128(((hs >> 1) ? pp.w2 : pp.w1) + (size_t)(320 * (hs & 1) + (tid >> 4) + 32 * u) * D_ + 512 + 8 * (tid & 15));
        {
            const int r = tid >> 4, c = tid & 15;
            uint4* dst[2];
#pragma unroll
            for (int e = 0; e < 2; e++) {
                const int p = !(hs >> 1) ? r : e && (hs & 1) ? (r & ~14) | ((r & 6) << 1) | ((r & 8) >> 2) : (r & ~30) | ((r & 6) << 2) | ((r & 24) >> 2);
                dst[e] = &g_wr[(((hs >> 1) * 8 + (c >> 1)) * 10 + 5 * (hs & 1)) * 128 + (p & 15) * 8 + ((2 * (p >> 4) + (c & 1)) ^ (p & 7))];
            }
#pragma unroll
            for (int u = 0; u < 10; u++) stg128(reinterpret_cast<uint4*>(reinterpret_cast<uintptr_t>(dst[u >= 6]) ^ (64 * (u & 1))) + (u >> 1) * 128, wr[u]);
        }
        __syncthreads();
        if (warp == 0) signal_cnt(&g_cnt.wr[0], lane, 1);
        __syncthreads();
        if (warp < 5 && elect()) {
            const int un = 5 * hs + warp;
            mbar_expect(bars + warp * 8, 40960);
            tma_ld2(sb + warp * 40960, &mp.w1h, 64 * (un >> 1), 320 * (un & 1), bars + warp * 8);
            tma_ld2(sb + warp * 40960 + 20480, &mp.w1h, 64 * (un >> 1), 320 * (un & 1) + 160, bars + warp * 8);
        }
        if (tid < 320) {
            const uint4* gm = reinterpret_cast<const uint4*>(g_mod + 3 * D_) + tid;
            const unsigned epoch = e0 + 1;
            uint4 r[6];
            unsigned it = 0;
            for (;;) {
                uint32_t bad = 0;
#pragma unroll
                for (int i = 0; i < 6; i++) { r[i] = ld_part(gm + (i >> 1) * (D_ / 2) + (i & 1) * 3 * D_); bad |= (r[i].y ^ epoch) | (r[i].w ^ epoch); }
                if (__all_sync(~0u, !bad)) break;
                if (++it > SPIN_LIMIT) SPIN_FAIL(54)
            }
            uint32_t mv[3];
#pragma unroll
            for (int i = 0; i < 3; i++) mv[i] = pack2(__uint_as_float(r[2 * i].x) + __uint_as_float(r[2 * i + 1].x), __uint_as_float(r[2 * i].z) + __uint_as_float(r[2 * i + 1].z));
            const uint32_t sw2 = mv[0], cw = add2(mv[1], 0x3f803f80u), gw = mv[2];
            const float c0 = blo(cw), c1 = bhi(cw), s0 = blo(sw2), s1 = bhi(sw2);
            const float i0 = __frcp_rn(zscale(c0)), i1 = __frcp_rn(zscale(c1));
            const uint32_t ci = pack2(i0, i1), cq = pack2(i0 * i0, i1 * i1);
            const uint32_t a = sb + H_B + ((tid >> 5) & 1) * 4608 + (tid >> 6) * 896 + ((tid >> 2) & 7) * 112 + (tid & 3) * 4;
            sts32(a, ci); sts32(a + 16, pack2(i0 - blo(ci), i1 - bhi(ci)));
            sts32(a + 32, cq); sts32(a + 48, pack2(fmaf(i0, i0, -blo(cq)), fmaf(i1, i1, -bhi(cq))));
            sts32(a + 64, cw); sts32(a + 80, sw2); sts32(a + 96, 0x3f803f80u);
            if ((tid & ~35) == 284) sts32(a + 112, 0);
            const uint32_t v = sb + H_B + TAB_BYTES + (tid < 256 ? (tid >> 5) * VEC_BYTES + (tid & 31) * 8 : ((tid - 256) >> 3) * VEC_BYTES + 256 + (tid & 7) * 8);
            sts64f(v, blo(gw), bhi(gw)); sts64f(v + 320, c0, c1); sts64f(v + 640, s0, s1); sts64f(v + 960, i0, i1);
            float k[5] = {c0 + c1, s0 + s1, fmaf(c0, c0, c1 * c1), fmaf(c0, s0, c1 * s1), fmaf(s0, s0, s1 * s1)};
#pragma unroll 1
            for (int o = 16; o; o >>= 1) {
#pragma unroll
                for (int e = 0; e < 5; e++) k[e] += __shfl_xor_sync(~0u, k[e], o);
            }
            const uint32_t ks = sb + H_B + TAB_BYTES + (lane & 7) * VEC_BYTES + 1280 + (warp >> 1) * 32;
            if ((warp & 1) && lane < 8) { sts128f(ks, k[0], k[1], k[2], k[3]); sts128f(ks + 16, k[4], 0.f, 0.f, 0.f); }
            bar_sync(3, 320);
            if (!(warp & 1) && lane < 8) {
                const float4 o = lds128f(ks);
                sts128f(ks, k[0] + o.x, k[1] + o.y, k[2] + o.z, k[3] + o.w); sts32(ks + 16, __float_as_uint(k[4] + __uint_as_float(lds32(ks + 16))));
            }
            fence_async_smem();
        }
        __syncthreads();
        if (hs == 0 && warp == 15 && elect()) {
            asm volatile("cp.async.bulk.global.shared::cta.bulk_group [%0], [%1], %2;\ncp.async.bulk.commit_group;\ncp.async.bulk.wait_group 0;"
                         ::"l"(g_tab), "r"(sb + H_B), "n"(TAB_BYTES + 8 * VEC_BYTES) : "memory");
            asm volatile("red.release.gpu.global.add.u32 [%0], 1;" ::"l"(&g_cnt.tab[0]) : "memory");
        }
        __syncwarp();
#pragma unroll 1
        for (int i = wg; i < 20; i += 4) {
            const int r = i / 5, b = i - 5 * r, un = 5 * hs + b, u3 = 20 * r + un;
            auto refill = [&](int e, int u, uint32_t fb) {
                mbar_expect(fb, 40960);
                tma_ld2(sb + e * 40960, &mp.w3h, 64 * (u >> 1), 320 * (u & 1), fb);
                tma_ld2(sb + e * 40960 + 20480, &mp.w3h, 64 * (u >> 1), 320 * (u & 1) + 160, fb);
            };
            if (i > 4 && i < 9) {
                bar_sync(1, 512);
                if (warp == 0) {
                    signal_cnt(&g_cnt.uv[0], lane, 1);
                    if (elect()) {
#pragma unroll 1
                        for (int e = 0; e < 5; e++) refill(e, 5 * hs + e, bars + (5 + e) * 8);
                        l2_prefetch(pp.w2 + (size_t)160 * hs * D_, 160 * D_ * 2);
                    }
                    __syncwarp();
                }
            }
            mbar_wait(bars + i * 8, 0);
            float d[4];
            gemv_tile<7>(d, sb + b * 40960, sb + H_B, 5 * (un & 1));
            const int col = 16 * (warp & 3) + g;
            float* dst = r ? g_cs3 + (un & 1) * 1920 + 64 * ((u3 >> 1) - 10) + col : g_uv + (un & 1) * 3 * D_ + 2 * D_ + 64 * (un >> 1) + col;
            if (t == 3) { dst[0] = d[0]; dst[8] = d[2]; }
            if (r == 0 && t == 2) { dst[-2 * D_] = d[0]; dst[8 - 2 * D_] = d[2]; dst[-D_] = d[1]; dst[8 - D_] = d[3]; }
            if (r == 1 || r == 2) {
                bar_sync(4 + wg, 128);
                if (wt == 0) refill(b, u3, bars + (i + 5) * 8);
            }
        }
        __syncthreads();
        if (warp == 0) signal_cnt(&g_cnt.cs[0], lane, 1);
        if (tid == 511) l2_prefetch(pp.w4 + (size_t)432 * hs * D_, 432 * D_ * 2);
        if (tid == 0 && hs == 3) {
            uint32_t it = 0;
            while (ld_cold(&g_epoch) == e0) { __nanosleep(256); if (++it > (1u << 20)) SPIN_FAIL(48) }
        }
        return;
    }

    if (elect()) {
        if (warp == 15) {
            mbar_init(bars + B_IN * 8, 1); mbar_init(bars + B_IN * 8 + 8, 1);
            asm volatile("fence.mbarrier_init.release.cluster;" ::: "memory");
            mbar_expect(bars + B_IN * 8, 131 * 160);
            tma_ld2(sb + OFF_KIN, &mp.k, 80 * (id & 7), 64 * (id >> 3) - 3, bars + B_IN * 8);
            tma_ld2(sb + OFF_VIN, &mp.v, 80 * (id & 7), 64 * (id >> 3), bars + B_IN * 8);
        } else if (warp < 12) {
            const uint32_t n = (0xC44111111881ull >> (4 * warp)) & 15;
#pragma unroll
            for (int i = 0; i < 4; i++) mbar_init(bars + warp * 64 + i * 8, n);
            if (warp == 11) mbar_init(bars + B_XFREE * 8, 16);
            else {
#pragma unroll
                for (int i = 4; i < 8; i++) mbar_init(bars + warp * 64 + i * 8, n);
            }
            asm volatile("fence.mbarrier_init.release.cluster;" ::: "memory");
        }
    }
    asm volatile("" ::"l"(pp.s), "l"(pp.c), "l"(out));
    TR4((threadIdx.x & 31) == 0, warp)
    const int pr = id >> 1;
    const int grp = pr < 4 ? 15 : pr < 36 ? (pr - 4) & 7 : 8 + (pr - 36) % 7;
    const int j = 2 * (pr < 4 ? pr : pr < 36 ? (pr - 4) >> 3 : (pr - 36) / 7) + (id & 1);

    if (wg == 3) {
        TIDS
        const int sw = warp - 12;
        uint32_t ep = ld_cold(&g_epoch);
        TR4(lane == 0, 20 + sw)
        __syncthreads();
        TR4(lane == 0, 30 + sw)
        asm volatile("barrier.cluster.arrive.relaxed.aligned;" ::: "memory");
        if (sw == 0) {
#pragma unroll 1
            for (int n = PF_N0; n < PF_N; n++) {
                wait_clock(c0, PF_T0 + PF_DT * (n - PF_N0));
                if (elect()) {
                    if (n < 8) l2_prefetch((const char*)(n < 4 ? pp.ssm_k : pp.q) + (size_t)id * 20480 + (n & 3) * 5120, 5120);
                    else l2_prefetch((const char*)pp.w_mod + (size_t)id * 38400 + (n - 8) * 4800, 4800);
                }
            }
        } else if (sw == 1) {
            wait_clock(c0, T_SSM);
            if (elect()) {
                mbar_expect(bars + B_SSM * 8, 20480);
                bulk_ld(sb + OFF_SSM, pp.ssm_k + (size_t)5 * id * S_, 20480, bars + B_SSM * 8);
            }
            mbar_spin(bars + B_KVS * 8, 0);
            signal_cnt(&g_cnt.kv[(id & 7) * 32], lane, 1, true);
            TS(lane == 0, 2)
            if (T_Q) wait_clock(c0, T_Q); else mbar_spin(bars + B_RAW * 8, 0);
            if (elect()) {
                mbar_expect(bars + B_QIN * 8, 20480);
                tma_ld3(sb + OFF_QIN, &mp.q, 0, 16 * id, 0, bars + B_QIN * 8);
            }
        } else if (sw == 2) {
            if (elect()) {
#pragma unroll 1
                for (int i = 2; i < (int)(sizeof(Maps) / sizeof(CUtensorMap)); i++) asm volatile("prefetch.tensormap [%0];" ::"l"(&mp.k + i) : "memory");
#pragma unroll 1
                for (int i = B_SUMS; i < B_SIG; i++) mbar_expect(bars + i * 8, i < B_RECV ? 2048 : (i & 3) < 3 ? 8192 : 3072);
            }
            wait_cnt(&g_cnt.kv[(id >> 4) * 32], 16, POLL_NS);
            TS(lane == 0, 4)
            if (elect()) {
                mbar_expect(bars + B_RAW * 8, 12288);
                mbar_expect(bars + B_RAW2 * 8, 8192);
#pragma unroll
                for (int c = 0; c < 5; c++) bulk_ld(sb + OFF_CH + c * CH_BYTES, g_kvT + (size_t)(5 * id + c) * S_, 4096, bars + (c < 3 ? B_RAW : B_RAW2) * 8);
            }
            mbar_spin(bars + B_BK * 8, 0);
            mbar_spin(bars + B_RAW2 * 8, 0);
            if (!T_Q) mbar_spin(bars + B_QIN * 8, 0);
            if (id < 120 && elect()) {
                mbar_expect(bars + B_WM * 8, 40960);
                tma_ld2(sb + OFF_WM, &mp.wmod, 64 * pr, 320 * (id & 1), bars + B_WM * 8);
                tma_ld2(sb + OFF_WM + 20480, &mp.wmod, 64 * pr, 320 * (id & 1) + 160, bars + B_WM * 8);
            }
            TS(lane == 0, 57)
        } else {
            wait_clock(c0, T_KVB);
            if (elect()) {
                mbar_expect(bars + (B_IN + 1) * 8, 131 * 160);
                tma_ld2(sb + OFF_KIN + 10752, &mp.k, 80 * (id & 7), 64 * (id >> 3) + 1021, bars + (B_IN + 1) * 8);
                tma_ld2(sb + OFF_VIN + 10240, &mp.v, 80 * (id & 7), 64 * (id >> 3) + 1024, bars + (B_IN + 1) * 8);
            }
            TS(lane == 0, 53)
            if (lane == 0) sts32(sb + M_EP, ep + 1);
            sts32(sb + M_NUL + lane * 4, 0);
#pragma unroll 1
            for (int m = lane; m < 40; m += 32) {
                const uint4 c = ldg128(pp.c + 320 * (id & 1) + 8 * m);
                uint32_t w[4] = {c.x, c.y, c.z, c.w};
#pragma unroll
                for (int i = 0; i < 4; i++) { const float a = blo(w[i]), b = bhi(w[i]); w[i] = pack2(__fdividef(a, 1.f + __expf(-a)), __fdividef(b, 1.f + __expf(-b))); }
                sts128(sb + OFF_Z + m * 128, w[0], w[1], w[2], w[3]);
#pragma unroll 1
                for (int r = 1; r < 8; r++) sts128(sb + OFF_Z + m * 128 + r * 16, 0, 0, 0, 0);
            }
            fence_async_smem();
        }
        {
            mbar_spin(bars + B_QIN * 8, 0);
            asm volatile("add.u32 %0, %0, 1;" : "+r"(ep));
            TS(wt == 0, 54)
            const int tk = 8 * ((lane >> 1) & 1) + 2 * (lane >> 3) + (lane & 1), ck = 4 * (sw & 1) + ((lane >> 1) & 2);
            const uint32_t src = sb + OFF_QIN + (sw >> 1) * 2048 + tk * 128;
            bf16* dst = g_qT + (size_t)id * 16 * D_ + (32 * sw + 8 * (t & 2) + g) * 16 + 8 * (t & 1);
#pragma unroll
            for (int i = 0; i < 5; i++) {
                uint32_t r[8];
                ldsm4t(src + i * 4096 + ((ck ^ (tk & 7)) << 4), r[0], r[1], r[2], r[3]);
                ldsm4t(src + i * 4096 + (((ck + 1) ^ (tk & 7)) << 4), r[4], r[5], r[6], r[7]);
                stg128(dst + i * 2048, tag(r[0], ep), r[1], r[2], r[3]);
                stg128(dst + i * 2048 + 128, tag(r[4], ep), r[5], r[6], r[7]);
            }
            float s1 = 0.f, s2 = 0.f;
#pragma unroll 2
            for (int i = 0; i < 10; i++) {
                const uint4 w4 = lds128(sb + OFF_QIN + i * 2048 + wt * 16);
                const uint32_t w[4] = {w4.x, w4.y, w4.z, w4.w};
#pragma unroll
                for (int e = 0; e < 4; e++) { const float a = blo(w[e]), b = bhi(w[e]); s1 += a + b; s2 = fmaf(a, a, fmaf(b, b, s2)); }
            }
#pragma unroll
            for (int o = 1; o < 8; o *= 2) { s1 += __shfl_xor_sync(~0u, s1, o); s2 += __shfl_xor_sync(~0u, s2, o); }
            s1 *= 1.f / D_;
            uint32_t rs = pack2(rsqrtf(fmaxf(s2 * (1.f / D_) - s1 * s1, 0.f) + 1e-5f), 0.f);
            if (lane < 8) rs = tag(rs, ep);
            rs = pack2(blo(rs), -s1 * blo(rs));
            const uint32_t sel = lane ? 0x7632 : 0x5410;
            const uint32_t a0 = __shfl_sync(~0u, rs, 0), a1 = __shfl_sync(~0u, rs, 8), a2 = __shfl_sync(~0u, rs, 16), a3 = __shfl_sync(~0u, rs, 24);
            if (lane < 2) stg64(g_qst + lane * S_ + 16 * id + 4 * sw, tag(__byte_perm(a0, a1, sel), ep), __byte_perm(a2, a3, sel));
            TS(wt == 0, 55)
        }
        bar_sync(6, 128);
        if (sw == 3) {
            signal_cnt(&g_cnt.q[(lane & 3) * 32], lane, 4, true);
            TS(lane == 0, 3)
        }
        if (id < 120) {
            mbar_spin(bars + B_WM * 8, 0);
            TS(wt == 0, 56)
            float d[4];
            gemv_tile<8>(d, sb + OFF_WM, sb + OFF_Z, 0);
            const float d2 = __shfl_up_sync(~0u, d[2], 1);
            TS(wt == 0, 7)
            if (t < 2) asm volatile("{\n.reg .b64 v;\nmov.b64 v, {%1, %2};\nst.relaxed.gpu.global.b64 [%0], v;\n}" ::"l"(g_mod + (id & 1) * 6 * D_ + 64 * pr + 16 * sw + g + 8 * t),
                                    "r"(__float_as_uint(t ? d2 : d[0])), "r"(ep) : "memory");
        }
        bar_sync(6, 128);
        asm volatile("setmaxnreg.dec.sync.aligned.u32 32;");
        asm volatile("barrier.cluster.wait.aligned;" ::: "memory");
        if (sw == 2) {
            wait_cnt(&g_cnt.tab[0], 1);
            if (elect()) {
                mbar_expect(bars + B_TAB * 8, TAB_BYTES / 2 + VEC_BYTES);
                bulk_ld(sb + OFF_TAB, g_tab + (j & 1) * (TAB_BYTES / 32), TAB_BYTES / 2, bars + B_TAB * 8);
                bulk_ld(sb + M_GB, g_tab + (TAB_BYTES + j * VEC_BYTES) / 16, VEC_BYTES, bars + B_TAB * 8);
            }
            TS(lane == 0, 5)
            int n = 0;
            auto xslot = [&](int w, int m) {
                mbar_spin(bars + (B_XEMPTY + (n & 7)) * 8, ((n >> 3) & 1) ^ 1);
                return bars + (B_XFULL + (m & 7) + 8 * w) * 8;
            };
#pragma unroll 1
            for (int e = 0; e < 4; e++) {
                const int w = e & 1, tile = grp + 16 * w;
                if (e < 2) wait_cnt(&g_cnt.x[(4 * w + (id & 3)) * 32], 128);
                else wait_cnt(&g_cnt.g1[min(max(tile + min(lane, 2) - 1, 0), 31) * 32], 8);
                TS(lane == 0, 26 + e)
                if (e == 0) mbar_spin(bars + (B_XS + 1) * 8, 0);
#pragma unroll 1
                for (int kb = 0; kb < 10; kb++, n++) {
                    const uint32_t fb = xslot(w, 5 * (e & 2) + kb);
                    TR2(lane == 0, 20 + 10 * e + kb)
                    if (elect()) {
                        mbar_expect(fb, 8192);
                        tma_ld2(sb + OFF_XR + (n & 7) * 8192, e < 2 ? &mp.x1_ld : &mp.t_ld, 64 * (e < 2 ? tile : kb), 64 * (e < 2 ? g1_block(kb, j) : tile), fb);
                    }
                }
            }
#pragma unroll 1
            for (int i = 0; i < 20; i++, n++) {
                const int w = i < XLEAD ? 0 : i >= 20 - XLEAD ? 1 : ((i - XLEAD) & 1) ^ 1;
                const int kb = i < XLEAD ? i : i >= 20 - XLEAD ? i - 10 : w ? (i - XLEAD) >> 1 : (i + XLEAD) >> 1;
                if (kb == 0) { wait_cnt(&g_cnt.g2[(grp + 16 * w) * 32], 8); TS(lane == 0, 30 + w) }
                const uint32_t fb = xslot(w, 20 + kb);
                if (elect()) {
                    mbar_expect(fb, 8192);
                    bulk_ld(sb + OFF_XR + (n & 7) * 8192, &g_x2f[((grp + 16 * w) * 10 + kb) * 512], 8192, fb);
                }
            }
            mbar_spin(bars + B_VEC3 * 8, 0);
            unsigned old = 0;
            if (lane == 0) old = atomicAdd(&g_cnt.done[0], 1u);
            if (__shfl_sync(~0u, old, 0) == 127) {
#pragma unroll 1
                for (int i = lane; i < (int)(sizeof(Counters) / 128); i += 32) reinterpret_cast<unsigned*>(&g_cnt)[i * 32] = 0;
                if (lane == 0) atomicAdd(&g_epoch, 1u);
            }
        } else if (sw == 0) {
            wait_cnt(&g_cnt.wr[0], 4);
            mbar_spin(bars + B_QRDY * 8, 0);
            const uint32_t wf = bars + B_WFULL * 8, we = bars + B_WEMPTY * 8;
#pragma unroll 1
            for (int n = 0; n < 10; n++) {
                if (n == 3) mbar_spin(bars + (B_XS + 1) * 8, 0);
                if (n >= 5) mbar_spin(we + (n - 5) * 8, 0);
                TR2(lane == 0, 70 + n)
                if (elect()) {
                    const uint32_t fb = wf + (n & 7) * 8, dst = sb + OFF_W + (n & 7) * 16384;
                    mbar_expect(fb, 20480);
                    if (n >= 5) {
                        tma_ld5(dst, n < 9 ? &mp.w2a : &mp.w2b, 64 * j, n < 9 ? 4 * (n - 5) : 0, fb);
                        bulk_ld(sb + OFF_REM + (n - 5) * 4096, &g_wr[((8 + j) * 10 + 2 * (n - 5)) * 128], 4096, fb);
                    } else {
#pragma unroll 1
                        for (int h = 0; h < 2; h++) {
                            const int kb = g1_block(2 * n + h, j);
                            tma_ld2(dst + h * 8192, &mp.w1, 64 * j, 64 * kb, fb);
                            bulk_ld(sb + OFF_REM + n * 4096 + h * 2048, &g_wr[(j * 10 + kb) * 128], 2048, fb);
                        }
                    }
                }
            }
#pragma unroll 1
            for (int n = 10; n < 30; n++) {
                mbar_spin(we + (n & 7) * 8, ((n >> 3) & 1) ^ 1);
                TR2(lane == 0, 70 + n)
                if (elect()) {
                    const uint32_t dst = sb + OFF_W + (n & 7) * 16384, fb = wf + (n & 7) * 8;
                    mbar_expect(fb, 13824);
                    tma_ld3(dst, &mp.w3a, 0, 32 * (n - 10), 3 * j, fb);
                    tma_ld2(dst + 12288, &mp.w3b, 1536 + 24 * j, 32 * (n - 10), fb);
                }
            }
            mbar_spin(we + 6 * 8, 0);
            if (elect()) mbar_arrive(bars + B_S30 * 8);
#pragma unroll 1
            for (int n = 31; n < 50; n++) {
                const int rem = 96 + 3 * (j >> 1);
                int m0, m1, r0, r1, c0_, c1_;
                if (n < 38) {
                    c0_ = g4_block(0, j); c1_ = g4_block(1, j);
                    m0 = m1 = n == 35;
                    r0 = r1 = n == 35 ? rem : 6 * (j ^ (n >= 34)) + ((0x2004204 >> (4 * (n - 31))) & 15);
                } else {
                    const int e = (n - 38) & 3;
                    c0_ = c1_ = g4_block(2 + ((n - 38) >> 2), j);
                    m0 = 0; m1 = e == 1 ? 1 : e == 3 ? -1 : 0;
                    r0 = 6 * (j ^ (e >> 1)) + 4 * (e & 1); r1 = e == 1 ? rem : r0 + 2;
                }
                mbar_spin(we + (n & 7) * 8, ((n >> 3) & 1) ^ 1);
                if (elect()) {
                    const uint32_t dst = sb + OFF_W + (n & 7) * 16384, fb = wf + (n & 7) * 8;
                    mbar_expect(fb, m1 < 0 ? 8192 : 16384 - 2048 * (m0 + m1));
                    tma_ld2(dst, &mp.w4[m0], 64 * c0_, r0 * (32 >> m0), fb);
                    if (m1 >= 0) tma_ld2(dst + 8192, &mp.w4[m1], 64 * c1_, r1 * (32 >> m1), fb);
                }
            }
#pragma unroll 1
            for (int w = 0; w < 2; w++) {
                const uint4* src = g_part + (size_t)(grp + 16 * w) * 40960;
                mbar_spin(bars + (B_RING + w) * 8, 1);
                if (elect()) {
                    const uint32_t fb = bars + (B_IN + w) * 8, rem = sb + OFF_OUT + w * 10240;
                    mbar_expect(fb, 10240);
                    bulk_ld(rem + 8192, &g_x1f[((grp + 16 * w) * 8 + j) * 640 + 512], 2048, fb);
#pragma unroll 1
                    for (int i = 0; i < 4; i++) bulk_ld(rem + i * 2048, src + ((j >> 2) + 2 * i) * 5120 + 4096 + j * 128, 2048, fb);
                }
            }
        } else {
            const int w = sw >> 1;
#pragma unroll 1
            for (int e = 0; e < 3; e++) {
                mbar_spin(bars + ((e ? B_SIG : B_XS) + w) * 8, e >> 1);
                signal_cnt(e == 0 ? &g_cnt.x[(4 * w + (lane & 3)) * 32] : e == 1 ? &g_cnt.g1[(grp + 16 * w) * 32] : &g_cnt.g2[(grp + 16 * w) * 32], lane, e ? 1 : 4, !(X_FENCE & (1 << e)));
                if (elect()) mbar_arrive(bars + (B_PUB + 2 * e + w) * 8);
                TS(lane == 0, 20 + 2 * e + w)
                if (e == 0 && w) {
                    wait_cnt(&g_cnt.uv[0], 4);
#pragma unroll 1
                    for (int c = lane; c < 80; c += 32) {
                        const float* src = g_uv + (c < 64 ? 64 * j + c : 448 + 16 * j + c);
                        const uint32_t u = split2(ldcg32f(src) + ldcg32f(src + 3 * D_)), v = split2(ldcg32f(src + D_) + ldcg32f(src + 4 * D_));
                        const uint32_t s = split2(ldcg32f(src + 2 * D_) + ldcg32f(src + 5 * D_));
                        sts128(sb + OFF_F1 + c * 16, u, __byte_perm(u, v, 0x5410), __byte_perm(v, 0, 0x1032), s);
                        sts128(sb + M_F1 + c * 16, s & 0xffffu, 0, 0, 0);
                    }
                    fence_async_smem();
                    warp_arrive(bars + B_VEC * 8);
                    TS(lane == 0, 9)
                }
            }
        }
        return;
    }

    {
        uint32_t ep;
        {
            TIDS
            ep = ld_cold(&g_epoch);
            const int cp = (tid + 16) % 40, cp1 = tid % 40;
            const uint4 sh0 = ldg128(pp.shift_k + (80 * (id & 7) + 2 * cp1) * 4), sh1 = ldg128(pp.shift_k + (80 * (id & 7) + 2 * cp) * 4);
            uint32_t dd;
            asm volatile("ld.global.nc.u16 %0, [%1];" : "=r"(dd) : "l"(pp.ssm_D + 5 * id + min(wg + 3 * lane, 4)));
            TR4(lane == 0, 40 + warp)
            __syncthreads();
            asm volatile("barrier.cluster.arrive.relaxed.aligned;" ::: "memory");
            asm volatile("add.u32 %0, %0, 1;" : "+r"(ep));
#pragma unroll 1
            for (int hw = 0; hw < 2; hw++) {
                if ((unsigned)(warp - 2 * hw) >= 10) continue;
                const int u = tid - 64 * hw;
                const int c = hw ? cp : cp1, oc = u / 40, line = 31 - 16 * hw - (id >> 3);
                const uint4 sh = hw ? sh1 : sh0;
                const uint32_t st = sb + OFF_ST + hw * 10240, sta = st + c * 256 + ((((6 - 2 * (oc & 3)) ^ (oc >> 2) ^ (line & 1)) ^ (c & 7)) << 4), in = oc * 1280 + c * 4;
                const uint32_t f0 = __byte_perm(sh.x, sh.z, 0x5410), f1 = __byte_perm(sh.x, sh.z, 0x7632), f2 = __byte_perm(sh.y, sh.w, 0x5410), f3 = __byte_perm(sh.y, sh.w, 0x7632);
                uint32_t kk[11], vv[8];
                mbar_spin(bars + (B_IN + hw) * 8, 0);
                TS(tid == 64, 18 + 42 * hw)
#pragma unroll
                for (int i = 0; i < 11; i++) kk[i] = lds32(sb + OFF_KIN + hw * 10752 + in + i * 160);
#pragma unroll
                for (int i = 0; i < 8; i++) vv[i] = lds32(sb + OFF_VIN + hw * 10240 + in + i * 160);
#pragma unroll
                for (int i = 0; i < 8; i++) vv[i] = mul2(fma2(kk[i + 3], f0, fma2(kk[i + 2], f1, fma2(kk[i + 1], f2, mul2(kk[i], f3)))), vv[i]);
                sts128(sta, tag(__byte_perm(vv[0], vv[1], 0x5410), ep), __byte_perm(vv[2], vv[3], 0x5410), __byte_perm(vv[4], vv[5], 0x5410), __byte_perm(vv[6], vv[7], 0x5410));
                sts128(sta + 128, tag(__byte_perm(vv[0], vv[1], 0x7632), ep), __byte_perm(vv[2], vv[3], 0x7632), __byte_perm(vv[4], vv[5], 0x7632), __byte_perm(vv[6], vv[7], 0x7632));
                bar_sync(7 + hw, 320);
                flush_tile(st, g_kvT + (size_t)(80 * (id & 7)) * S_ + 64 * line, u);
                TS(tid == 64 && hw, 1)
            }
            warp_arrive(bars + B_KVS * 8);
            if (tid < 320) sts128(sb + OFF_CH + (tid >> 6) * CH_BYTES + 4096 + (tid & 63) * 16, 0, 0, 0, 0);
            mbar_spin(bars + B_SSM * 8, 0);
            TS(tid == 0, 14)
            uint2 w[7];
            uint32_t pv[7];
#pragma unroll
            for (int i = 0; i < 7; i++) {
                const uint32_t a = sb + OFF_SSM + min(wg + 3 * i, 19) * 1024 + wt * 8;
                w[i] = lds64(a); pv[i] = lds32(a - 4);
            }
#pragma unroll
            for (int i = 0; i < 7; i++) {
                const int un = min(wg + 3 * i, 19);
                sts128(sb + OFF_CH + (un >> 2) * CH_BYTES + OFF_P + (un & 3) * 2048 + wt * 16, __byte_perm(w[i].x, pv[i], 0x7610), __byte_perm(w[i].x, 0, 0x1032), __byte_perm(w[i].y, w[i].x, 0x7610), __byte_perm(w[i].y, 0, 0x1032));
            }
            __syncwarp();
            if (wt < 2 - (wg >> 1)) {
                const uint32_t h = lds32(sb + OFF_SSM + (wg + 3 * wt) * 4096), h0 = pack2(blo(h) + blo(dd), 0.f);
                sts64f(sb + OFF_CH + (wg + 3 * wt) * CH_BYTES + OFF_P, __uint_as_float(h0), __uint_as_float(__byte_perm(h, h0, 0x5432)));
            }
            fence_async_smem();
            warp_arrive(bars + B_BK * 8);
            asm volatile("barrier.cluster.wait.aligned;" ::: "memory");
            mbar_spin(bars + B_BK * 8, 0);
            TS(tid == 0, 15)
        }

#pragma unroll 1
        for (int c = wg; c < 5; c += 3) {
            const uint32_t kvb = sb + OFF_CH + c * CH_BYTES;
            mbar_spin(bars + (c < 3 ? B_RAW : B_RAW2) * 8, 0);
            if (CH2_DELAY && wg == 2) wait_clock(clock64(), CH2_DELAY);
            for (uint32_t it = 0;;) {
                const int wt = tid_now() & 127;
                if (!bar_any(1 + wg, ((lds32(kvb + wt * 16) ^ ep) | (lds32(kvb + 2048 + wt * 16) ^ ep)) & 1)) break;
                if (wt == 0) { mbar_expect(bars + (B_RETRY + wg) * 8, 4096); bulk_ld(kvb, g_kvT + (size_t)(5 * id + c) * S_, 4096, bars + (B_RETRY + wg) * 8); }
                mbar_spin(bars + (B_RETRY + wg) * 8, ep >> 31);
                ep ^= 0x80000000u;
                STALE(0)
                SPIN_CHECK(57)
            }
            TS(threadIdx.x == 0, c ? 13 : 11)
            float acc[64];
            {
                const int l = tid_now() & 31;
                conv_channel(acc, kvb + OFF_P + (8 * (warp & 3) + (l >> 2) - 2 * (l & 3)) * 4, (((uint64_t)0xC0000010u << 32) | ((kvb & 0x3FFFF) >> 4) | 0x10000u) + pp.nil);
            }
            TS(threadIdx.x == 0, c ? 16 : 12)
            if (c >= 3) {
#pragma unroll 1
                for (int e = 0; e < 3; e++) mbar_spin(bars + (B_RING + e) * 8, 0);
            }
            TIDS
            const int e = 127 - 8 * (lane >> 4) - (lane & 7), u0 = (warp & 3) + 8 * (e >> 2) + (e & 3) + 4 * ((lane >> 3) & 1);
            const uint32_t ring = sb + OFF_RING + c * 16384 + (warp & 3) * 4096, wa = ring + (u0 ^ ((u0 >> 1) & 4)) * 16;
            if (lane < (warp & 3)) sts128(ring + lane * 16, 0, 0, 0, 0);
#pragma unroll
            for (int i = 0; i < 8; i++)
                stsm4t(i == 0 && u0 >= 256 ? sb + M_SINK : wa - 512 * i, pack2(acc[8 * i], acc[8 * i + 1]), pack2(acc[8 * i + 2], acc[8 * i + 3]),
                       pack2(acc[8 * i + 4], acc[8 * i + 5]), pack2(acc[8 * i + 6], acc[8 * i + 7]));
            warp_arrive(bars + (B_RING + c) * 8);
        }
        fence_async_smem();
        TIDS
        if (warp == 8) {
            wait_cnt(&g_cnt.q[(id & 3) * 32], 128);
            if (elect()) {
                mbar_expect(bars + B_QRDY * 8, 28672);
                tma_ld2(sb + OFF_QT, &mp.qT, 80 * id, 0, bars + B_QRDY * 8);
                bulk_ld(sb + OFF_QT + 20480, g_qst, 8192, bars + B_QRDY * 8);
            }
            TS(lane == 0, 8)
        } else if (warp == 9) {
            const int v = min(lane / 5, 3);
            const uint2* gm = g_mod + (v + (v == 3)) * D_ + 5 * id + lane % 5;
            const unsigned epoch = lds32(sb + M_EP);
            uint2 r0, r1;
            unsigned it = 0;
            do {
                r0 = ld_mod(gm); r1 = ld_mod(gm + 6 * D_);
                SPIN_CHECK(55)
            } while (!__all_sync(~0u, r0.y == epoch && r1.y == epoch));
            const float m0 = __uint_as_float(r0.x), m1 = __uint_as_float(r1.x);
            const float m = rbf(m0 + m1), p = rbf(1.f + m);
            const float cz = zscale(__shfl_sync(~0u, p, 15 + lane % 5)), ga = __shfl_sync(~0u, m, 10 + lane % 5);
            if (lane < 15) sts32(sb + M_AB + lane % 5 * 16 + v * 4, lane < 10 ? __float_as_uint(cz * ga * (lane < 5 ? m : p)) : pack2(cz, cz));
            warp_arrive(bars + B_MODR * 8);
            TS(lane == 0, 6)
        }
        mbar_spin(bars + B_QRDY * 8, 0);
        mbar_spin(bars + B_MODR * 8, 0);
#pragma unroll 1
        for (int hf = 0; hf < 2; hf++) {
            const int u = wt + 128 * hf;
            uint4 rs = lds128(sb + OFF_QT + 20480 + u * 16), nm = lds128(sb + OFF_QT + 24576 + u * 16);
            uint32_t it = 0;
            while (__any_sync(~0u, ((rs.x ^ ep) | (rs.z ^ ep) | (nm.x ^ ep) | (nm.z ^ ep)) & 1)) {
                rs = ld_part(g_qst + 8 * u); nm = ld_part(g_qst + S_ + 8 * u);
                STALE(1)
                SPIN_CHECK(53)
            }
            const int c1 = wg == 2 ? 2 + !EPI_SPLIT : 5;
#pragma unroll 1
            for (int c = wg == 2 ? 0 : EPI_SPLIT && wg == hf ? 2 : 3 + wg; c < c1; c += wg == 2 ? 1 : c == 2 ? 1 + wg : 2) {
                uint4 q = lds128(sb + OFF_QT + (u >> 1) * 160 + c * 32 + (u & 1) * 16);
                const float4 ab = lds128f(sb + M_AB + c * 16);
                mbar_spin(bars + (B_RING + c) * 8, 0);
                const uint32_t ra = sb + OFF_RING + c * 16384 + (u ^ ((u >> 1) & 4)) * 16;
                const uint4 p0 = lds128(ra), p1 = lds128(ra + 4096), p2 = lds128(ra + 8192), p3 = lds128(ra + 12288);
                while (__any_sync(~0u, (q.x ^ ep) & 1)) {
                    q = ld_part(g_qT + ((u >> 1) * D_ + 5 * id + c) * 16 + 8 * (u & 1));
                    STALE(2)
                    SPIN_CHECK(52)
                }
                uint32_t gq[4] = {q.x, q.y, q.z, q.w}, gg[4] = {fma2(q.x, rs.x, nm.x), fma2(q.y, rs.y, nm.y), fma2(q.z, rs.z, nm.z), fma2(q.w, rs.w, nm.w)};
#pragma unroll
                for (int i = 0; i < 4; i++) {
                    gg[i] = pack2(fmaf(blo(gg[i]), ab.y, ab.x), fmaf(bhi(gg[i]), ab.y, ab.x));
                    gq[i] = mul2(gq[i], __float_as_uint(ab.z));
                }
                stg128(g_x1T + (size_t)(5 * id + c) * S_ + 8 * u,
                       tag(fma2(gg[0], add2(add2(p0.x, p1.x), add2(p2.x, p3.x)), gq[0]), ep), fma2(gg[1], add2(add2(p0.y, p1.y), add2(p2.y, p3.y)), gq[1]),
                       fma2(gg[2], add2(add2(p0.z, p1.z), add2(p2.z, p3.z)), gq[2]), fma2(gg[3], add2(add2(p0.w, p1.w), add2(p2.w, p3.w)), gq[3]));
            }
            warp_arrive(bars + (B_XS + hf) * 8);
            TS(tid == 0, hf ? 17 : 58)
            TS(tid == 256 && hf, 52)
        }
    }

    const uint32_t nil = pp.nil;
    const int wq = warp & 3;
    if (wg == 2) {
        TIDS
        asm volatile("setmaxnreg.dec.sync.aligned.u32 32;");
        {
            wait_cnt(&g_cnt.cs[0], 4);
            uint32_t s[2];
#pragma unroll
            for (int i = 0; i < 2; i++) {
                const int c = min(wt + 128 * i, 215);
                const float* src = g_cs3 + (c < 192 ? 192 * j + c : 1344 + 24 * j + c);
                s[i] = split2(ldcg32f(src) + ldcg32f(src + 1920));
            }
            asm volatile("" : "+r"(s[0]), "+r"(s[1]));
            bar_sync(3, 128);
            if (wt == 0) mbar_arrive(bars + B_VEC3 * 8);
            TS(wt == 0, 19)
            mbar_wait(bars + B_S30 * 8, 0);
#pragma unroll
            for (int i = 0; i < 2; i++) sts128(sb + OFF_W + 6 * 16384 + min(wt + 128 * i, 215) * 16, s[i], s[i] & 0xffffu, 0, 0);
            fence_async_smem();
            bar_sync(3, 128);
            if (wt == 0) mbar_arrive(bars + (B_WFULL + 6) * 8);
        }
#pragma unroll 1
        for (int uw = 0; uw < 2; uw++) {
            const int tile = grp + 16 * uw;
            const uint32_t ep = lds32(sb + M_EP), in = sb + OFF_OUT + uw * 10240 + wt * 16, sr = in - lane * 16;
            mbar_wait(bars + (B_IN + uw) * 8, 1);
            float r[8];
#pragma unroll
            for (int h = 0; h < 2; h++) {
                uint4 a = lds128(in + h * 4096), b = lds128(in + h * 4096 + 2048);
                uint32_t it = 0;
                while (__any_sync(~0u, ((a.x ^ ep) | (b.x ^ ep)) & 1)) {
                    const uint4* p = g_part + (size_t)tile * 40960 + ((j >> 2) + 4 * h) * 5120 + 4096 + j * 128 + wt;
                    a = ld_part(p); b = ld_part(p + 10240);
                    STALE(3)
                    if (++it > SPIN_LIMIT) SPIN_FAIL(58)
                }
                if (h) add8(r, add2(a, b)); else unpack8(r, add2(a, b));
            }
            base16(r, lds128(in + 8192), lds64f(sb + M_GB + (64 + 2 * t) * 4), lds64f(sb + M_GB + (72 + 2 * t) * 4));
            __syncwarp();
            stsm4(sr + (lane & 15) * 32 + (((lane >> 4) ^ ((lane >> 2) & 1)) << 4), pack2(r[0], r[1]), pack2(r[2], r[3]), pack2(r[4], r[5]), pack2(r[6], r[7]));
            __syncwarp();
            stg128(out + (size_t)(64 * tile + 16 * wq + (lane >> 1)) * D_ + 512 + 16 * j + 8 * (lane & 1), lds128(sr + (lane >> 1) * 32 + (((lane & 1) ^ ((lane >> 3) & 1)) << 4)));
            __syncwarp();
        }
        if (wq == 0) {
#pragma unroll 1
            for (int w = 0; w < 2; w++) {
                uint32_t it = 0;
                while (!mbar_try(bars + (B_OWN + w) * 8, 0)) { if (++it > SPIN_LIMIT) SPIN_FAIL(56) }
            }
        }
        return;
    }

    TIDS
    const int uw = wg, tile = grp + 16 * uw, row0 = 64 * tile + 16 * wq;
    const bool leader = wt == 0; (void)leader;
    const uint32_t xfull = bars + (B_XFULL + 8 * uw) * 8, xempty = bars + B_XEMPTY * 8, wfull = bars + B_WFULL * 8, wempty = bars + B_WEMPTY * 8;
    const uint64_t dz = mkdesc(0) + pp.nil;
    auto xwait = [&](uint32_t n) { mbar_spin(xfull + (n & 7) * 8, (n >> 3) & 1); };
    asm volatile("setmaxnreg.inc.sync.aligned.u32 224;");
    const uint32_t ep = lds32(sb + M_EP);
    {
        float acc[40];
        uint4* const own = &g_x1f[(tile * 8 + j) * 640 + wt];
        uint32_t la = ((lane & 7) + 8 * (lane >> 4)) * 128 + (((2 * wq + ((lane >> 3) & 1)) ^ (lane & 7)) << 4);
        uint32_t ta = lane * 128 + (((2 * wq) ^ (lane & 7)) << 4);
        const bf16* ga = g_x1T + (size_t)((lane & 7) + 8 * (lane >> 4)) * S_ + row0 + (lane & 8);
        auto slot = [&](uint32_t m) { return sb + OFF_XR + (m & 7) * 8192; };
        uint32_t tg[2][2];
        auto tags = [&](int h, uint32_t m, bool g1) { tg[h][0] = lds32(slot(m) + ta); tg[h][1] = lds32(slot(m) + (g1 ? ta + 4096 : ta ^ 64)); };
        auto stale = [&](int h) { return __any_sync(~0u, lop3<0x7E>(tg[h][0], ep, tg[h][1]) & 1); };
        auto mend = [&](uint32_t m, int kb, bool g1) {
            const bf16* p = ga + kb * (g1 ? 64 * S_ : 64);
#pragma unroll 1
            for (uint32_t q = 0, it = 0; q < 4;) {
                const uint4 v = ld_part(p);
                SPIN_CHECK(51)
                if (__any_sync(~0u, ((v.x ^ ep) | (!g1 && kb >= 8 ? v.z ^ ep : 0)) & 1)) continue;
                sts128(slot(m) + (g1 ? la + q * 2048 : la ^ (q << 5)), v.x, v.y, v.z, v.w);
                q++; p += g1 ? 16 * S_ : 16;
            }
            fence_async_smem();
            __syncwarp();
            STALE1(g1 ? 1 : 2)
        };
        auto grab = [&](uint32_t m) {
            uint32_t r0, r1, r2, r3;
            ldsm4t(slot(m) + la + (j & 3) * 2048, r0, r1, r2, r3);
            stg128(own + 512, r0, r1, r2, r3);
        };
        float al[2], r1[2], n1[2];
        {
            float sl[4], sq[4], v[4];
            uint32_t z0[16], z1[16], zz[16];
            uint64_t bd = dz + b80_desc(dsb, 0, 0, 0), tb = (((uint64_t)8 << 32) | ((dsb + OFF_TAB) >> 4) | (7u << 16)) + pp.nil;
            auto ldfrag = [&](uint32_t (&z)[16], int n) {
#pragma unroll
                for (int q = 0; q < 4; q++) ldsm4t(slot(2 * uw + n) + la + q * 2048, z[4 * q], z[4 * q + 1], z[4 * q + 2], z[4 * q + 3]);
            };
            auto tile1 = [&](const uint32_t (&zc)[16], uint32_t (&zn)[16], int n, int h) {
                const bool last = h && n == 5, ok = mbar_test(xfull + (n + 2) * 8, 0), okw = !h || mbar_test(wfull + ((n + 1) >> 1) * 8, 0);
                const int kb = g1_block(n, j);
                wg_fence();
#pragma unroll
                for (int q = 0; q < 2; q++) wgmma_rs80(acc, zc[4 * q], zc[4 * q + 1], zc[4 * q + 2], zc[4 * q + 3], bd + q * B80_STEP, 1);
                wg_commit();
                if (!last && stale(h ^ 1)) mend(2 * uw + n + 1, g1_block(n + 1, j), true);
                wg_wait<1>();
                if (!last) ldfrag(zn, n + 1);
#pragma unroll
                for (int e = 0; e < 16; e++) zz[e] = mul2(zc[e], zc[e]);
                const uint64_t t0 = last ? ((uint64_t)8 << 32) | ((dsb + M_NUL) >> 4) : tb;
                const uint32_t ts = last ? 0 : 14;
                wg_fence();
#pragma unroll
                for (int q = 0; q < 4; q++) wgmma_rs8(sl, zc[4 * q], zc[4 * q + 1], zc[4 * q + 2], zc[4 * q + 3], t0 + q * ts, 1);
#pragma unroll
                for (int q = 0; q < 4; q++) wgmma_rs8(sq, zz[4 * q], zz[4 * q + 1], zz[4 * q + 2], zz[4 * q + 3], t0 + q * ts, 1);
#pragma unroll
                for (int q = 2; q < 4; q++) wgmma_rs80(acc, zc[4 * q], zc[4 * q + 1], zc[4 * q + 2], zc[4 * q + 3], bd + q * B80_STEP, 1);
                wg_commit();
                if (!ok) xwait(n + 2);
                tags(h, 2 * uw + n + 2, true);
                if (kb == j) {
#pragma unroll
                    for (int q = 0; q < 4; q++) stg128(own + q * 128, zc[4 * q], zc[4 * q + 1], zc[4 * q + 2], zc[4 * q + 3]);
                }
                if (!h && kb == 8 + (j >> 2)) grab(2 * uw + n);
                if (lane < 2) mbar_arrive(xempty + ((2 * uw + n) & 7) * 8);
                if (!h && n && lane == 0) mbar_arrive(wempty + ((n >> 1) - 1) * 8);
                tb += 56;
                bd = bd + (uint64_t)B80_HALF;
                if (!okw) mbar_spin(wfull + ((n + 1) >> 1) * 8, 0);
                TR(leader, 100 + 10 * uw + n)
            };
            zero(acc); zero(sl); zero(sq);
            mbar_spin(bars + B_TAB * 8, 0);
            mbar_spin(wfull, 0);
            xwait(0);
            TS(leader, 32 + uw)
            tags(0, 2 * uw, true);
            ldfrag(z0, 0);
            if (stale(0)) { mend(2 * uw, j & 1, true); ldfrag(z0, 0); }
            xwait(1);
            tags(1, 2 * uw + 1, true);
#pragma unroll 1
            for (int n = 0; n < 6; n += 2) { tile1(z0, z1, n, 0); tile1(z1, z0, n + 1, 1); }
#pragma unroll
            for (int n = 6; n < 10; n++) {
                const uint64_t ad = dz + (((dsb + OFF_XR + ((2 * uw + n) & 7) * 8192) >> 4) | 0x10000u);
                const bool ok = n >= 8 || mbar_test(xfull + (n - 6) * 8, 1), okw = n != 7 || mbar_test(wfull + 4 * 8, 0);
                if (stale(n & 1)) mend(2 * uw + n, g1_block(n, j), true);
                wg_fence();
#pragma unroll
                for (int q = 0; q < 4; q++) wgmma_ss80t(acc, ad + q * 128, bd + q * B80_STEP, 1);
                wg_commit();
                bd = bd + (uint64_t)B80_HALF;
                if (n < 8) { if (!ok) xwait(n + 2); tags(n & 1, 2 * uw + n + 2, true); }
                if (n == 9 && 9 - (j & 1) == 8 + (j >> 2)) grab(2 * uw + 9);
                wg_wait<1>();
                if (n > 6 && lane < 2) mbar_arrive(xempty + ((2 * uw + n - 1) & 7) * 8);
                if (!(n & 1) && lane == 0) mbar_arrive(wempty + ((n >> 1) - 1) * 8);
                if (n == 6) {
                    reg_fence(sl); reg_fence(sq);
#pragma unroll
                    for (int e = 0; e < 2; e++) {
                        v[2 * e] = t == 0 ? sl[2 * e] + sl[2 * e + 1] : t == 1 ? sq[2 * e] + sq[2 * e + 1] : sl[2 * e];
                        v[2 * e + 1] = t == 2 ? sl[2 * e + 1] : sq[2 * e];
                    }
                    st_peer(peer_addr(sb + OFF_ROW + uw * 2048 + wt * 16), __float_as_uint(v[0]), __float_as_uint(v[1]), __float_as_uint(v[2]), __float_as_uint(v[3]), peer_addr(bars + (B_SUMS + uw) * 8));
                    TS(leader && !uw, 59)
                }
                if (!okw) mbar_spin(wfull + 4 * 8, 0);
                TR(leader, 100 + 10 * uw + n)
            }
            float4 k = lds128f(sb + M_KS);
            float k4 = __uint_as_float(lds32(sb + M_KS + 16));
#pragma unroll
            for (int w = 1; w < 5; w++) {
                const float4 o = lds128f(sb + M_KS + w * 32);
                k.x += o.x; k.y += o.y; k.z += o.z; k.w += o.w; k4 += __uint_as_float(lds32(sb + M_KS + w * 32 + 16));
            }
            mbar_spin(bars + (B_SUMS + uw) * 8, 0);
            TS(leader && !uw, 10)
            const float4 o = lds128f(sb + OFF_ROW + uw * 2048 + wt * 16);
            v[0] += o.x; v[1] += o.y; v[2] += o.z; v[3] += o.w;
            uint32_t fa[4];
#pragma unroll
            for (int h = 0; h < 2; h++) {
                const int l0 = lane & ~3;
                const float s1 = __shfl_sync(~0u, v[2 * h], l0), s2 = __shfl_sync(~0u, v[2 * h], l0 + 1), scc = __shfl_sync(~0u, v[2 * h], l0 + 2);
                const float scs = __shfl_sync(~0u, v[2 * h + 1], l0 + 2), sc = __shfl_sync(~0u, v[2 * h], l0 + 3), sqq = __shfl_sync(~0u, v[2 * h + 1], l0 + 3);
                const float m1 = s1 * (1.f / D_), va = fmaxf(s2 * (1.f / D_) - m1 * m1, 0.f) + 1e-5f, r = rsqrtf(va);
                const float m2 = (r * (sc - m1 * k.x) + k.y) * (1.f / D_);
                const float e2 = (r * (r * (sqq + m1 * (m1 * k.z - 2.f * scc)) + 2.f * (scs - m1 * k.w)) + k4) * (1.f / D_);
                al[h] = r * 0.5f * rsqrtf(fmaxf(e2 - m2 * m2, 0.f) + 1e-5f); r1[h] = r; n1[h] = -m1 * r;
                const uint32_t fb = split2(va * r), fx = split2(t == 3 ? -m2 * va * r : -m1), fc = __shfl_sync(~0u, fx, lane | 3);
                fa[h] = __byte_perm(fx, fb, t == 1 ? 0x5432 : t == 2 ? 0x7654 : 0x1010);
                fa[2 + h] = t ? 0 : fc >> 16;
            }
            mbar_spin(bars + B_VEC * 8, 0);
            wg_fence();
            wgmma_rs80k(acc, fa[0], fa[1], fa[2], fa[3], ((uint64_t)8 << 32) | ((dsb + OFF_F1) >> 4) | (((M_F1 - OFF_F1) >> 4) << 16), 1);
            wg_commit();
        }
        wg_wait<0>();
        reg_fence(acc);
        if (lane < 2) mbar_arrive(xempty + ((2 * uw + 9) & 7) * 8);
        if (lane == 0) mbar_arrive(wempty + 4 * 8);
        TS(leader, 34 + uw)
        {
            bf16* const trow = g_t + (size_t)(row0 + g + 2) * D_;
#pragma unroll
            for (int b = 0; b < 3; b++) {
                uint32_t p[8];
#pragma unroll
                for (int ii = 0; ii < 4; ii++) {
                    const int i = 4 * b + ii;
                    if (i >= 10) continue;
#pragma unroll
                    for (int h = 0; h < 2; h++) p[(i & 3) + 4 * h] = pack2(gelu2(acc[4 * i + 2 * h] * al[h]), gelu2(acc[4 * i + 2 * h + 1] * al[h]));
                }
                if (b < 2) {
                    const int gr = (2 * j + b) / 5, sh = (gr & 1) ? -1 - (gr >> 1) : 1 + (gr >> 1);
                    bf16* dst = trow + 64 * j + 32 * b + 8 * t;
                    stg128(dst + sh * D_, tag(p[0], ep), p[1], p[2], p[3]);
                    stg128(dst + (sh + 8) * D_, tag(p[4], ep), p[5], p[6], p[7]);
                    if (row0 + g < sh || row0 + g + 8 >= S_ + sh) stg128(dst + (sh > 0 ? 0 : 8) * D_, ep & 1, 0, 0, 0);
                } else {
                    bf16* dst = trow + 512 + 16 * j + 4 * t;
                    stg64(dst - 2 * D_, tag(p[0], ep), p[1]);
                    stg64(dst + 6 * D_, tag(p[4], ep), p[5]);
                    if (row0 + g + 8 >= S_ - 2) stg64(dst + 8 * D_, ep & 1, 0);
                }
            }
        }
        warp_arrive(bars + (B_SIG + uw) * 8);
        TS(leader, 36 + uw)
        uint32_t res[20];
        auto ld_own = [&]() {
#pragma unroll
            for (int i = 0; i < 5; i++) { const uint4 v = ldcg128(own + i * 128); res[4 * i] = v.x; res[4 * i + 1] = v.y; res[4 * i + 2] = v.z; res[4 * i + 3] = v.w; }
        };
        ld_own();
#pragma unroll
        for (int i = 0; i < 10; i++) {
            const float2 c = lds64f(sb + M_C + (8 * i + 2 * t) * 4), s = lds64f(sb + M_SB + (8 * i + 2 * t) * 4);
#pragma unroll
            for (int h = 0; h < 2; h++) {
                acc[4 * i + 2 * h] = fmaf(blo(res[2 * i + h]), r1[h], fmaf(n1[h], c.x, s.x));
                acc[4 * i + 2 * h + 1] = fmaf(bhi(res[2 * i + h]), r1[h], fmaf(n1[h], c.y, s.y));
            }
        }
        la = (16 * wq + (lane & 15)) * 128 + (((lane >> 4) ^ (lane & 7)) << 4);
        ta = (16 * wq + (lane & 15)) * 128 + (((lane >> 4 << 1) ^ (lane & 7)) << 4);
        ga = g_t + (size_t)(row0 + 2 + (lane & 15)) * D_ + 8 * (lane >> 4);
        mbar_spin(wfull + 5 * 8, 0);
        xwait(10);
        tags(0, 4 + 2 * uw, false);
        xwait(11);
        tags(1, 5 + 2 * uw, false);
#pragma unroll 1
        for (int i = 0; i < 5; i++) {
            const uint32_t wn = 5 + i, xs = (4 + 2 * uw + 2 * i) & 7;
            const uint64_t alo = dz + (((dsb + OFF_XR + xs * 8192) >> 4) | 0x10000u), bd = dz + b80_desc(dsb, wn, i, 0);
#pragma unroll
            for (int h = 0; h < 2; h++) {
                const uint32_t nn = 12 + 2 * i + h, wx = min(wn + 1, 9u);
                const bool ok = mbar_test(xfull + (nn & 7) * 8, (nn >> 3) & 1), okw = !h || mbar_test(wfull + (wx & 7) * 8, wx >> 3);
                if (stale(h)) mend(xs + h, 2 * i + h, false);
                wg_fence();
#pragma unroll
                for (int q = 0; q < 4; q++) wgmma_ss80(acc, alo + h * 512 + q * 2, bd + h * B80_HALF + q * B80_STEP, 1);
                wg_commit();
                if (i < 4) { if (!ok) xwait(nn); tags(h, xs + h + 2, false); }
                wg_wait<1>();
                if (lane < 2 && (h || i)) mbar_arrive(xempty + ((xs + h - 1) & 7) * 8);
                if (!h && i && lane == 0) mbar_arrive(wempty + ((wn - 1) & 7) * 8);
                if (!okw) mbar_spin(wfull + (wx & 7) * 8, wx >> 3);
                TR(leader, (uw ? 86 : 20) + 2 * i + h)
            }
        }
        wg_wait<0>();
        reg_fence(acc);
        if (lane < 2) mbar_arrive(xempty + ((29 + 10 * uw) & 7) * 8);
        if (lane == 0) mbar_arrive(wempty + (9 & 7) * 8);
        TS(leader, 38 + uw)
        float a0 = 0.f, b0 = 0.f, a1 = 0.f, b1 = 0.f;
        uint32_t x2[20];
#pragma unroll
        for (int i = 0; i < 5; i++) {
            uint32_t* p = &x2[4 * i];
#pragma unroll
            for (int e = 0; e < 4; e++) p[e] = pack2(acc[8 * i + 2 * e], acc[8 * i + 2 * e + 1]);
            p[0] = tag(p[0], ep);
            stg128(&g_x2f[(tile * 40 + (i < 4 ? 4 * j + i : 32 + j)) * 128 + wt], p[0], p[1], p[2], p[3]);
#pragma unroll
            for (int e = 0; e < 4; e += 2) {
                const float u0 = blo(p[e]), u1 = bhi(p[e]), v0 = blo(p[e + 1]), v1 = bhi(p[e + 1]);
                a0 += u0 + u1; b0 = fmaf(u0, u0, fmaf(u1, u1, b0));
                a1 += v0 + v1; b1 = fmaf(v0, v0, fmaf(v1, v1, b1));
            }
        }
#pragma unroll
        for (int o = 1; o < 4; o *= 2) {
            a0 += __shfl_xor_sync(~0u, a0, o); b0 += __shfl_xor_sync(~0u, b0, o);
            a1 += __shfl_xor_sync(~0u, a1, o); b1 += __shfl_xor_sync(~0u, b1, o);
        }
        if (t < 2) stg64(&g_stats[(tile * 8 + j) * 64 + 16 * wq + g + 8 * t], tag(__float_as_uint(t ? a1 : a0), ep), __float_as_uint(t ? b1 : b0));
        warp_arrive(bars + (B_SIG + uw) * 8);
        TS(leader, 40 + uw)
        ld_own();
#pragma unroll
        for (int i = 0; i < 10; i++) {
            const float2 c = lds64f(sb + M_GB + (8 * i + 2 * t) * 4), e = lds64f(sb + M_CI + (8 * i + 2 * t) * 4);
#pragma unroll
            for (int h = 0; h < 2; h++)
                res[2 * i + h] = fma2(pack2(c.x, c.y), x2[2 * i + h], pack2(e.x * blo(res[2 * i + h]), e.y * bhi(res[2 * i + h])));
        }
#pragma unroll
        for (int i = 0; i < 5; i++) stg128(own + i * 128, res[4 * i], res[4 * i + 1], res[4 * i + 2], res[4 * i + 3]);
        asm volatile("fence.proxy.async.global;" ::: "memory");
    }
    float acc0[64], acc1[44];
    float2 q[4];
    {
        uint4 f0, f1, f2, f3;
        auto xseq = [&](int kb) { return (uint32_t)(40 + (uw ? (kb < 10 - XLEAD ? XLEAD + 2 * kb : 10 + kb) : (kb < XLEAD ? kb : 2 * kb - XLEAD + 1))) & 7; };
        auto step = [&](const uint4& f, uint64_t bd) {
            wg_fence();
            wgmma_rs128(acc0, f.x, f.y, f.z, f.w, bd, 1);
            wgmma_rs88(acc1, f.x, f.y, f.z, f.w, bd + 512, 1);
            wg_commit();
        };
        const uint32_t xa = sb + OFF_XR + wt * 16;
        auto fix2 = [&](uint4& a, uint4& b, int s) {
            uint32_t it = 0;
            while (__any_sync(~0u, ((a.x ^ ep) | (b.x ^ ep)) & 1)) {
                a = ld_part(&g_x2f[(tile * 40 + s) * 128 + wt]); b = ld_part(&g_x2f[(tile * 40 + s + 1) * 128 + wt]);
                STALE(7)
                SPIN_CHECK(50)
            }
        };
        const float2* const gs = &g_stats[(tile * 8 + 2 * t) * 64 + 16 * wq + g];
        zero(acc0); zero(acc1);
        uint32_t xs = xseq(0);
        xwait(20);
        TS(leader, 42 + uw)
        f0 = lds128(xa + xs * 8192); f1 = lds128(xa + xs * 8192 + 2048);
#pragma unroll
        for (int i = 0; i < 4; i++) q[i] = ld_stat(gs + (i & 1) * 64 + 8 * (i >> 1));
        mbar_spin(wfull + (10 & 7) * 8, (10 >> 3) & 1);
#pragma unroll 1
        for (int kb = 0; kb < 10; kb++) {
            const uint32_t wn = 10 + 2 * kb;
            const uint64_t bd = dz + (((dsb + OFF_W + (wn & 7) * 16384) >> 4) | (256u << 16));
            fix2(f0, f1, 4 * kb);
            step(f0, bd);
            wg_wait<1>();
            if (kb && lane == 0) mbar_arrive(wempty + ((wn - 1) & 7) * 8);
            f2 = lds128(xa + xs * 8192 + 4096); f3 = lds128(xa + xs * 8192 + 6144);
            const bool w1 = mbar_test(wfull + ((wn + 1) & 7) * 8, (wn >> 3) & 1), x1 = mbar_test(xfull + ((21 + kb) & 7) * 8, ((21 + kb) >> 3) & 1);
            step(f1, bd + 128);
            if (!w1) mbar_spin(wfull + ((wn + 1) & 7) * 8, (wn >> 3) & 1);
            fix2(f2, f3, 4 * kb + 2);
            step(f2, bd + 1024);
            if (lane < 2) mbar_arrive_after(xempty + xs * 8, f2.x, f3.x, nil);
            wg_wait<1>();
            if (lane == 0) mbar_arrive(wempty + (wn & 7) * 8);
            xs = xseq(kb + 1);
            if (x1) { f0 = lds128(xa + xs * 8192); f1 = lds128(xa + xs * 8192 + 2048); }
            const bool w2 = mbar_test(wfull + ((wn + 2) & 7) * 8, ((wn + 2) >> 3) & 1);
            step(f3, bd + 1152);
            if (kb < 9 && !x1) { xwait(21 + kb); f0 = lds128(xa + xs * 8192); f1 = lds128(xa + xs * 8192 + 2048); }
            if (!w2) mbar_spin(wfull + ((wn + 2) & 7) * 8, ((wn + 2) >> 3) & 1);
            if (kb == 4) {
                uint32_t it = 0;
                while (__any_sync(~0u, ((__float_as_uint(q[0].x) ^ ep) | (__float_as_uint(q[1].x) ^ ep) | (__float_as_uint(q[2].x) ^ ep) | (__float_as_uint(q[3].x) ^ ep)) & 1)) {
#pragma unroll
                    for (int i = 0; i < 4; i++) q[i] = ld_stat(gs + (i & 1) * 64 + 8 * (i >> 1));
                    SPIN_CHECK(49)
                }
                float a0 = q[0].x + q[1].x, b0 = q[0].y + q[1].y, a1 = q[2].x + q[3].x, b1 = q[2].y + q[3].y;
#pragma unroll
                for (int o = 1; o < 4; o *= 2) {
                    a0 += __shfl_xor_sync(~0u, a0, o); b0 += __shfl_xor_sync(~0u, b0, o);
                    a1 += __shfl_xor_sync(~0u, a1, o); b1 += __shfl_xor_sync(~0u, b1, o);
                }
                a0 *= 1.f / D_; a1 *= 1.f / D_;
                const float r0 = 0.5f * rsqrtf(fmaxf(b0 * (1.f / D_) - a0 * a0, 0.f) + 1e-5f), r1 = 0.5f * rsqrtf(fmaxf(b1 * (1.f / D_) - a1 * a1, 0.f) + 1e-5f);
                const uint32_t sel = t == 0 ? 0x1010 : t == 1 ? 0x4432 : 0x4444;
                q[0] = make_float2(r0, r1);
                q[1] = make_float2(__uint_as_float(__byte_perm(split2(-a0), 0, sel)), __uint_as_float(__byte_perm(split2(-a1), 0, sel)));
            }
            TR(leader, 10 * uw + kb)
        }
        const uint64_t fd = ((uint64_t)8 << 32) | ((dsb + OFF_W + 6 * 16384) >> 4);
        wg_fence();
        wgmma_rs128k(acc0, __float_as_uint(q[1].x), __float_as_uint(q[1].y), 0, 0, fd, 1);
        wgmma_rs88k(acc1, __float_as_uint(q[1].x), __float_as_uint(q[1].y), 0, 0, fd + 128, 1);
        wg_commit();
        if (lane == 0) {
            mbar_arrive(bars + B_XFREE * 8);
            asm volatile("mbarrier.arrive.shared::cluster.b64 _, [%0];" ::"r"(peer_addr(bars + B_XFREE * 8)) : "memory");
        }
    }
    const uint32_t recv = sb + recv_off(uw) + wt * 16;
    uint32_t ha[48] = {}, hb[48], hx[12];
    uint64_t wb = dz + (((dsb + OFF_W) >> 4) | (512u << 16));
    auto wdesc = [&](int n) { return wb + (n & 7) * 1024; };
    auto wwait = [&](int n) { mbar_spin(wfull + (n & 7) * 8, (n >> 3) & 1); };
    auto wfree = [&](int n) { if (lane == 0) mbar_arrive(wempty + (n & 7) * 8); };
    auto fresh = [&]() { wb += pp.nil; asm volatile("" : "+l"(wb)); };
    uint32_t pk[32];
    {
        float P0[64];
        const float r0 = q[0].x, r1 = q[0].y;
        const uint32_t ra = peer_addr(recv), rb = peer_addr(bars + (B_RECV + 4 * uw) * 8);
        auto conv32 = [&](const float* v, int b) {
#pragma unroll
            for (int i = 0; i < 4; i++) {
                ha[8 * b + 2 * i] = pack2(gelu2(v[4 * i] * r0), gelu2(v[4 * i + 1] * r0));
                ha[8 * b + 2 * i + 1] = pack2(gelu2(v[4 * i + 2] * r1), gelu2(v[4 * i + 3] * r1));
            }
#pragma unroll
            for (int s = 2 * b; s < 2 * b + 2; s++) st_peer(ra + s * 2048, ha[4 * s], ha[4 * s + 1], ha[4 * s + 2], ha[4 * s + 3], rb + (b >> 1) * 8);
        };
        auto fetch = [&](int k) {
            mbar_spin(bars + (B_RECV + 4 * uw + k) * 8, 0);
#pragma unroll
            for (int s = 4 * k; s < 4 * k + 4; s++) { const uint4 x = lds128(recv + s * 2048); hb[4 * s] = x.x; hb[4 * s + 1] = x.y; hb[4 * s + 2] = x.z; hb[4 * s + 3] = x.w; }
        };
        auto stage = [&](int n, const uint32_t* a, int steps, int sc) {
            wwait(n);
            wg_fence();
#pragma unroll
            for (int s = 0; s < steps; s++) wgmma_rs128(P0, a[4 * s], a[4 * s + 1], a[4 * s + 2], a[4 * s + 3], wdesc(n) + s * 128, sc || s);
            wg_commit();
        };
        wg_wait<0>();
        reg_fence(acc0); reg_fence(acc1);
        wfree(29); wfree(30);
        TS(leader, 44 + uw)
        uint32_t hr[6];
#pragma unroll
        for (int i = 0; i < 6; i++) {
            const float r = (i & 1) ? r1 : r0;
            hr[i] = pack2(gelu2(acc1[32 + 2 * i] * r), gelu2(acc1[33 + 2 * i] * r));
        }
        if (uw) mbar_spin(bars + B_XFREE * 8, 0);
        st_peer(ra + 24576, hr[0], hr[1], hr[2], hr[3], rb + 24);
        asm volatile("st.async.shared::cluster.mbarrier::complete_tx::bytes.v2.b32 [%0], {%1, %2}, [%3];" ::"r"(ra + 26624 - wt * 8), "r"(hr[4]), "r"(hr[5]), "r"(rb + 24) : "memory");
        conv32(&acc1[0], 4);
        conv32(&acc1[16], 5);
        TS(leader, 46 + uw)
        stage(31, &ha[32], 4, 0);
#pragma unroll
        for (int b = 0; b < 4; b++) {
            conv32(&acc0[16 * b], b);
            if (b == 3) {
                fetch(2);
                mbar_spin(bars + (B_RECV + 4 * uw + 3) * 8, 0);
                const uint4 x = lds128(recv + 24576);
                const uint2 y = lds64(recv + 26624 - wt * 8);
                const uint32_t hp[6] = {x.x, x.y, x.z, x.w, y.x, y.y};
#pragma unroll
                for (int i = 0; i < 6; i++) { hx[i] = (j & 1) ? hp[i] : hr[i]; hx[6 + i] = (j & 1) ? hr[i] : hp[i]; }
            }
            if (!(b & 1)) wwait(32 + (b >> 1));
            wg_fence();
#pragma unroll
            for (int s = 0; s < 2; s++) wgmma_rs128(P0, ha[8 * b + 4 * s], ha[8 * b + 4 * s + 1], ha[8 * b + 4 * s + 2], ha[8 * b + 4 * s + 3], wdesc(32 + (b >> 1)) + (2 * (b & 1) + s) * 128, 1);
            wg_commit();
            if (!(b & 1)) { wg_wait<1>(); wfree(31 + (b >> 1)); }
        }
        TR(leader, 64 + 10 * uw)
        fresh();
        stage(34, &hb[32], 4, 1); wg_wait<1>(); wfree(33);
        fetch(0);
        stage(35, hx, 3, 1); wg_wait<1>(); wfree(34);
        fetch(1);
        stage(36, &hb[0], 4, 1); wg_wait<1>(); wfree(35);
        stage(37, &hb[16], 4, 1); wg_wait<1>(); wfree(36);
        wg_wait<0>();
        reg_fence(P0);
        pack_part<64>(pk, P0, ep);
        uint32_t all = 0;
#pragma unroll
        for (int i = 0; i < 32; i++) all |= pk[i];
        if (lane == 0) mbar_arrive_after(wempty + (37 & 7) * 8, all, 0, nil);
        TR(leader, 65 + 10 * uw)
    }
    {
        uint4* const dst = g_part + (size_t)(tile * 8 + j) * 5120 + wt;
        const uint4* const src = g_part + (size_t)tile * 40960 + j * 512 + wt;
        float F[2][32];
        float2 gb[8];
        uint4 base[4], u1[4], u2[4], u3[4];
#pragma unroll
        for (int c = 2; c < 5; c++) {
            float (&P)[32] = F[c & 1];
            fresh();
#pragma unroll
            for (int s = 0; s < 27; s++) {
                const int e = s < 8 ? 0 : s < 15 ? 1 : s < 23 ? 2 : 3, o = s - (e == 0 ? 0 : e == 1 ? 8 : e == 2 ? 15 : 23), n = 30 + 4 * c + e;
                const uint32_t* a = s < 12 ? &ha[4 * s] : s < 15 ? &hx[4 * (s - 12)] : &hb[4 * (s - 15)];
                if (o == 0) wwait(n);
                if (o == 0 || s == 1) wg_fence();
                wgmma_rs64(P, a[0], a[1], a[2], a[3], wdesc(n) + o * 128, s);
                if (o == 0) { wg_commit(); wg_wait<1>(); if (c > 2 || s) wfree(n - 1); }
                if (s == 0 && c > 2) { reg_fence(F[~c & 1]); pack_part<32>(pk, F[~c & 1], ep); }
                if (c == 2 && s % 3 == 0 && s < 24) st_part(dst + g4_block(s / 12, j) * 512 + (s / 3 & 3) * 128, &pk[4 * (s / 3)]);
                if (c == 3 && s % 4 == 1 && s < 16) st_part(dst + g4_block(2, j) * 512 + s / 4 * 128, &pk[4 * (s / 4)]);
                if (c == 4 && s % ST3 == 0 && s < 4 * ST3) st_part(dst + g4_block(3, j) * 512 + s / ST3 * 128, &pk[4 * (s / ST3)]);
                if (c == 4 && s >= 4 && s < 8) base[s - 4] = ldcg128(&g_x1f[(tile * 8 + j) * 640 + (s - 4) * 128 + wt]);
                if (c == 4 && s >= 19 && s < 23) { gb[2 * s - 38] = lds64f(sb + M_GB + (16 * (s - 19) + 2 * t) * 4); gb[2 * s - 37] = lds64f(sb + M_GB + (16 * (s - 19) + 8 + 2 * t) * 4); }
                if (c == 4 && s >= 8 && s < 12) u1[s - 8] = ld_part(src + (j ^ 6) * 5120 + (s - 8) * 128);
                if (c == 4 && s >= 15 && s < 19) u2[s - 15] = ld_part(src + (j ^ 4) * 5120 + (s - 15) * 128);
                if (c == 4 && s >= LD3 && s < LD3 + 4) u3[s - LD3] = ld_part(src + (j ^ 2) * 5120 + (s - LD3) * 128);
                if (s == 7 || s == 14 || s == 22 || s == 26) wg_commit();
                if (c == 4) { TR(leader && s == 7, 68 + 10 * uw) TR(leader && s == 14, 69 + 10 * uw) TR(leader && s == 22, 70 + 10 * uw) }
            }
            if (c == 2 && lane == 0) mbar_arrive(bars + (B_RING + uw) * 8);
            TR(leader, 64 + c + (c == 4 ? 3 : 0) + 10 * uw)
        }
        float (&O)[32] = F[0];
        float v[32];
        fix4(u1, src + (j ^ 6) * 5120, ep, 4);
        fix4(u2, src + (j ^ 4) * 5120, ep, 5);
        TR(leader, 72 + 10 * uw)
        fix4(u3, src + (j ^ 2) * 5120, ep, 6);
        TR(leader, 73 + 10 * uw)
#pragma unroll
        for (int i = 0; i < 4; i++) { unpack8(&v[8 * i], add2(add2(u1[i], u2[i]), u3[i])); base16(&v[8 * i], base[i], gb[2 * i], gb[2 * i + 1]); }
        reg_fence(v);
        TS(leader, 50 + uw)
        wg_wait<0>();
        reg_fence(O);
        TS(leader, 48 + uw)
        const uint32_t so = sb + recv_off(uw) + wq * 2048;
#pragma unroll
        for (int i = 0; i < 4; i++) {
            float* o = &O[8 * i];
#pragma unroll
            for (int e = 0; e < 8; e++) o[e] = fmaf((e & 1) ? gb[2 * i + (e >> 2)].y : gb[2 * i + (e >> 2)].x, o[e], v[8 * i + e]);
            stsm4(so + (lane & 15) * 128 + (((2 * i + (lane >> 4)) ^ (lane & 7)) << 4), pack2(o[0], o[1]), pack2(o[2], o[3]), pack2(o[4], o[5]), pack2(o[6], o[7]));
        }
        __syncwarp();
#pragma unroll
        for (int i = 0; i < 4; i++) {
            const int row = (lane >> 3) + 4 * i;
            stg128(out + (size_t)(row0 + row) * D_ + 64 * j + 8 * (lane & 7), lds128(so + row * 128 + (((lane & 7) ^ (row & 7)) << 4)));
        }
        warp_arrive(bars + (B_OWN + uw) * 8);
    }
}

typedef CUresult (*EncFn)(CUtensorMap*, CUtensorMapDataType, cuuint32_t, void*, const cuuint64_t*, const cuuint64_t*, const cuuint32_t*,
                          const cuuint32_t*, CUtensorMapInterleave, CUtensorMapSwizzle, CUtensorMapL2promotion, CUtensorMapFloatOOBfill);

static void enc(EncFn fn, CUtensorMap* m, void* p, int rank, const cuuint64_t* dims, const cuuint64_t* strides, const cuuint32_t* box) {
    const CUtensorMapSwizzle sw = box[0] > 64 ? CU_TENSOR_MAP_SWIZZLE_NONE : CU_TENSOR_MAP_SWIZZLE_128B;
    cuuint32_t es[5] = {1, 1, 1, 1, 1};
    CUresult r = fn(m, CU_TENSOR_MAP_DATA_TYPE_BFLOAT16, rank, p, dims, strides, box, es, CU_TENSOR_MAP_INTERLEAVE_NONE, sw,
                    CU_TENSOR_MAP_L2_PROMOTION_L2_128B, CU_TENSOR_MAP_FLOAT_OOB_FILL_NONE);
    (void)r;
}
static void enc2(EncFn fn, CUtensorMap* m, void* p, uint64_t cols, uint64_t rows, uint32_t bc, uint32_t br) {
    cuuint64_t dims[2] = {cols, rows}, st[1] = {cols * 2};
    cuuint32_t box[2] = {bc, br};
    enc(fn, m, p, 2, dims, st, box);
}

extern "C" void kernel_launch(void* const* d_in, const int* in_sizes, int n_in, void* d_out, int out_size) {
    static Maps mp;
    static Ptrs pp;
    static void* cached[13];
    bool same = true;
    for (int i = 0; i < 13; i++) same = same && (cached[i] == d_in[i]);
    if (!same) {
        void* fnp = nullptr;
        cudaDriverEntryPointQueryResult qr;
        cudaGetDriverEntryPoint("cuTensorMapEncodeTiled", &fnp, cudaEnableDefault, &qr);
        EncFn fn = (EncFn)fnp;
        cudaGetSymbolAddress((void**)&pp.s, g_scratch);
        void *x1T = g_x1T, *t = g_t;
        cuuint64_t dq[3] = {64, S_, 10}, sq[2] = {D_ * 2, 128};
        cuuint32_t bq[3] = {64, 16, 10};
        enc(fn, &mp.q, d_in[0], 3, dq, sq, bq);
        enc2(fn, &mp.k, d_in[1], D_, S_, 80, 67); enc2(fn, &mp.v, d_in[2], D_, S_, 80, 64);
        enc2(fn, &mp.qT, g_qT, 16 * D_, 128, 80, 128);
        enc2(fn, &mp.x1_ld, x1T, S_, D_, 64, 64); enc2(fn, &mp.t_ld, (bf16*)t + 2 * D_, D_, S_, 64, 64);
        enc2(fn, &mp.w1, d_in[7], D_, D_, 64, 64); enc2(fn, &mp.w1h, d_in[7], D_, D_, 64, 160); enc2(fn, &mp.w3h, d_in[9], F_, D_, 64, 160);
        enc2(fn, &mp.wmod, d_in[12], 6 * D_, D_, 64, 160);
        const cuuint64_t R = D_ * 2;
        cuuint64_t da[5] = {D_, 2, 4, 4, 16}, sa[4] = {R, 8 * R, 2 * R, 32 * R}, db[5] = {D_, 2, 2, 4, 8}, sb[4] = {R, 8 * R, 2 * R, 16 * R};
        cuuint32_t ba[5] = {64, 2, 4, 4, 4}, bb[5] = {64, 2, 2, 4, 8};
        enc(fn, &mp.w2a, d_in[8], 5, da, sa, ba); enc(fn, &mp.w2b, (bf16*)d_in[8] + 512 * D_, 5, db, sb, bb);
        cuuint64_t dw[3] = {64, D_, 27}, sw[2] = {F_ * 2, 128};
        cuuint32_t bw[3] = {64, 32, 3};
        enc(fn, &mp.w3a, d_in[9], 3, dw, sw, bw);
        enc2(fn, &mp.w3b, d_in[9], F_, D_, 24, 32);
        enc2(fn, &mp.w4[0], d_in[10], D_, F_, 64, 64); enc2(fn, &mp.w4[1], d_in[10], D_, F_, 64, 48);
        pp.q = (const bf16*)d_in[0]; pp.w_mod = (const bf16*)d_in[12]; pp.shift_k = (const bf16*)d_in[3];
        pp.ssm_k = (const bf16*)d_in[4]; pp.ssm_D = (const bf16*)d_in[5]; pp.w1 = (const bf16*)d_in[7]; pp.w2 = (const bf16*)d_in[8];
        pp.w4 = (const bf16*)d_in[10]; pp.c = (const bf16*)d_in[11];
        cudaFuncSetAttribute(fused_kernel, cudaFuncAttributeMaxDynamicSharedMemorySize, SMEM_BYTES);
        for (int i = 0; i < 13; i++) cached[i] = d_in[i];
    }
    cudaLaunchConfig_t cfg = {};
    cfg.gridDim = dim3(NCTA); cfg.blockDim = dim3(NTHR); cfg.dynamicSmemBytes = SMEM_BYTES; cfg.stream = cudaStreamPerThread;
    cudaLaunchAttribute at[1];
    at[0].id = cudaLaunchAttributeClusterDimension; at[0].val.clusterDim.x = 2; at[0].val.clusterDim.y = 1; at[0].val.clusterDim.z = 1;
    cfg.attrs = at; cfg.numAttrs = 1;
    cudaLaunchKernelEx(&cfg, fused_kernel, pp, (bf16*)d_out, mp);
}
```

```cpp
#include <cuda_runtime.h>
#include <cuda_bf16.h>
#include <cuda.h>
#include <stdint.h>
#include <stdio.h>

typedef __nv_bfloat16 bf16;

constexpr int S_ = 2048, D_ = 640, F_ = 1728;
constexpr int NCTA = 132, NTHR = 512;

constexpr int TAB_BYTES = 9216, VEC_BYTES = 1440;
struct Counters {
    unsigned kv[8 * 32];
    unsigned q[4 * 32], x[2 * 4 * 32];
    unsigned wr[32], tab[32], uv[32], cs[32], done[32];
    unsigned g1[32 * 32];
    unsigned g2[32 * 32];
};
struct Scratch {
    Counters cnt;
    unsigned epoch;
    alignas(1024) bf16 qst[2 * S_];
    alignas(1024) uint4 wr[2 * 8 * 10 * 128];
    alignas(1024) uint2 mod[2 * 6 * D_];
    alignas(1024) uint4 tab[(TAB_BYTES + 8 * VEC_BYTES) / 16];
    alignas(1024) float uv[2 * 3 * D_];
    alignas(1024) float cs3[2 * 1920];
    alignas(1024) float2 stats[32 * 8 * 64];
    alignas(1024) bf16 kvT[D_ * S_];
    alignas(1024) bf16 qT[D_ * S_];
    alignas(1024) bf16 x1T[D_ * S_];
    alignas(1024) bf16 t[(S_ + 4) * D_];
    alignas(1024) uint4 x2f[32 * 40 * 128];
    alignas(1024) uint4 x1f[32 * 8 * 5 * 128];
    alignas(1024) uint4 part[32 * 8 * 10 * 4 * 128];
};
__device__ Scratch g_scratch;
#define g_kvT (pp.s->kvT)
#define g_qT (pp.s->qT)
#define g_x1T (pp.s->x1T)
#define g_qst (pp.s->qst)
#define g_t (pp.s->t)
#define g_x2f (pp.s->x2f)
#define g_x1f (pp.s->x1f)
#define g_part (pp.s->part)
#define g_wr (pp.s->wr)
#define g_mod (pp.s->mod)
#define g_tab (pp.s->tab)
#define g_uv (pp.s->uv)
#define g_cs3 (pp.s->cs3)
#define g_stats (pp.s->stats)
#define g_cnt (pp.s->cnt)
#define g_epoch (pp.s->epoch)

struct Maps {
    CUtensorMap k, v, q;
    CUtensorMap qT;
    CUtensorMap x1_ld, t_ld;
    CUtensorMap w1, w1h, w3h, wmod;
    CUtensorMap w2a, w2b;
    CUtensorMap w3a, w3b;
    CUtensorMap w4[2];
};

struct Ptrs {
    Scratch* s;
    uint64_t nil;
    const bf16 *q, *w_mod, *shift_k, *ssm_k, *ssm_D, *w1, *w2, *w4, *c;
};

constexpr int OFF_W = 0;
constexpr int OFF_XR = 131072;
constexpr int OFF_REM = 196608;
constexpr int OFF_TAB = OFF_REM + 5 * 4096;
constexpr int OFF_ROW = OFF_TAB + 4608;
constexpr int OFF_F1 = OFF_ROW + 4096;
constexpr int RECV_BYTES = 30720;
constexpr int OFF_M = OFF_REM + RECV_BYTES;
constexpr int OFF_OUT = OFF_XR + 32768;
static_assert(OFF_F1 + 1280 <= OFF_M, "G1 map");
constexpr int OFF_ST = 0;
constexpr int OFF_SSM = 20480;
constexpr int OFF_WM = 0;
constexpr int OFF_QIN = 49152;
constexpr int OFF_QT = 49152;
constexpr int OFF_Z = OFF_TAB;
constexpr int OFF_RING = 80896;
constexpr int OFF_KIN = OFF_RING, OFF_VIN = OFF_KIN + 2 * 10752;
constexpr int OFF_CH = OFF_RING + 3 * 16384, CH_BYTES = 13312, OFF_P = 5120;
static_assert(OFF_RING + 5 * 16384 <= OFF_CH + 3 * CH_BYTES && OFF_CH + 5 * CH_BYTES <= OFF_REM, "the last two rings replace channels 0..2");
constexpr int M_BAR = OFF_M;
constexpr int M_F1 = OFF_M + 800;
constexpr int M_GB = M_F1 + 1280, M_C = M_GB + 320, M_SB = M_C + 320, M_CI = M_SB + 320;
constexpr int M_KS = M_CI + 320;
constexpr int M_AB = M_KS + 160;
constexpr int M_EP = M_AB + 80;
constexpr int M_SINK = M_EP + 16;
constexpr int M_NUL = M_SINK + 16;
constexpr int M_TS = M_NUL + 128;
constexpr int SMEM_BYTES = M_TS;
static_assert(SMEM_BYTES <= 232448, "smem");

enum { B_WFULL = 0, B_WEMPTY = 8, B_XEMPTY = 16, B_XFULL = 24  ,
       B_RAW = 40, B_QIN = 41, B_SSM = 42, B_VEC = 43, B_VEC3 = 44, B_WM = 45, B_TAB = 46, B_QRDY = 47,
       B_MODR = 48, B_GATE = 49, B_RETRY = 55, B_S30 = 58, B_RAW2 = 59, B_SUMS = 62, B_RECV = 64  ,
       B_SIG = 72, B_RING = 74  ,
       B_LAND = 80,
       B_XS = 88, B_BK = 90, B_KVS = 91,
       B_XFREE = 92, B_OWN = 93,
       B_IN = 94, B_AGAIN = 96 };
#define T_KVB 1800
#define T_SSM 3300
#define T_Q 0
#define PF_T0 4800
#define PF_DT 420
#define PF_N0 4
#define PF_N 16
#define CH2_DELAY 0
#define POLL_NS 0
#define HELP_T 1000
#define EPI_SPLIT 1
#define ST3 1
#define LD3 23
#define GATE_W2 7
#define GATE_W3 27
#define GATE_W3B 37
#define W3_N2 13
#define XLEAD 3

#define SPIN_FAIL(code) __trap();
#define SPIN_LIMIT (1u << 22)
#define STALE(c)
#define STALE1(c)
#define TS(c, i)
#define TG(c, i)
#define TR(c, i)
#define TR2(c, i)
#define TR4(c, i)
#define TR5(c, i)
#define SPIN_CHECK(code) asm volatile("" ::"r"(it));
__device__ __forceinline__ uint32_t s2u(const void* p) { return (uint32_t)__cvta_generic_to_shared(p); }
__device__ __forceinline__ bool elect() {
    uint32_t p;
    asm volatile("{.reg .pred P; elect.sync _|P, 0xffffffff; selp.u32 %0,1,0,P;}" : "=r"(p));
    return p != 0;
}
__device__ __forceinline__ void mbar_init(uint32_t b, uint32_t n) { asm volatile("mbarrier.init.shared.b64 [%0], %1;" ::"r"(b), "r"(n)); }
__device__ __forceinline__ void mbar_expect(uint32_t b, uint32_t bytes) {
    asm volatile("mbarrier.arrive.expect_tx.shared.b64 _, [%0], %1;" ::"r"(b), "r"(bytes) : "memory");
}
__device__ __forceinline__ void mbar_arrive(uint32_t b) { asm volatile("mbarrier.arrive.shared.b64 _, [%0];" ::"r"(b) : "memory"); }
__device__ __forceinline__ void mbar_arrive_after(uint32_t b, uint32_t v0, uint32_t v1, uint32_t nil) { mbar_arrive(b + ((v0 | v1) & nil)); }
__device__ __forceinline__ void warp_arrive(uint32_t b) { __syncwarp(); if (elect()) mbar_arrive(b); }
__device__ __forceinline__ uint32_t peer_addr(uint32_t a) {
    uint32_t r;
    asm("{\n.reg .b32 q;\nmov.u32 q, %%cluster_ctarank;\nxor.b32 q, q, 1;\nmapa.shared::cluster.u32 %0, %1, q;\n}" : "=r"(r) : "r"(a));
    return r;
}
__device__ __forceinline__ bool mbar_test(uint32_t b, uint32_t parity) {
    uint32_t ok;
    asm volatile("{.reg .pred P; mbarrier.test_wait.parity.shared.b64 P, [%1], %2; selp.u32 %0,1,0,P;}" : "=r"(ok) : "r"(b), "r"(parity) : "memory");
    return ok != 0;
}
__device__ __forceinline__ bool mbar_try(uint32_t b, uint32_t parity) {
    uint32_t ok;
    asm volatile("{.reg .pred P; mbarrier.try_wait.parity.shared.b64 P, [%1], %2; selp.u32 %0,1,0,P;}" : "=r"(ok) : "r"(b), "r"(parity) : "memory");
    return ok != 0;
}
__device__ __forceinline__ void mbar_wait(uint32_t b, uint32_t parity) {
    if (__all_sync(0xffffffffu, mbar_try(b, parity))) return;
    uint32_t it = 0;
    while (!__all_sync(0xffffffffu, mbar_try(b, parity))) { if (++it > SPIN_LIMIT) SPIN_FAIL((b >> 3) & 63) }
}
__device__ __forceinline__ void mbar_spin(uint32_t b, uint32_t parity) {
    asm volatile("{\n.reg .pred P;\nSPIN:\nmbarrier.try_wait.parity.shared.b64 P, [%0], %1;\n@!P bra.uni SPIN;\n}" ::"r"(b), "r"(parity) : "memory");
}
__device__ __forceinline__ void bar_sync(int id, int n) { asm volatile("bar.sync %0, %1;" ::"r"(id), "r"(n) : "memory"); }
__device__ __forceinline__ void fence_async_smem() { asm volatile("fence.proxy.async.shared::cta;" ::: "memory"); }
__device__ __forceinline__ void wait_cnt(const unsigned* p, unsigned target, int ns = 0) {
    unsigned v, it = 0;
    do {
        if (ns) __nanosleep(ns);
        asm volatile("ld.relaxed.gpu.global.u32 %0, [%1];" : "=r"(v) : "l"(p) : "memory");
        SPIN_CHECK(60 + (target & 3))
    } while (!__all_sync(0xffffffffu, v >= target));
    asm volatile("fence.acquire.gpu;" ::: "memory");
}
#define X_FENCE 0
__device__ __forceinline__ void signal_cnt(unsigned* p, int lane, int n, bool nofence = false) {
    if (nofence) { if (lane < n) asm volatile("red.relaxed.gpu.global.add.u32 [%0], 1;" ::"l"(p) : "memory"); }
    else if (lane < n) asm volatile("red.release.gpu.global.add.u32 [%0], 1;" ::"l"(p) : "memory");
    __syncwarp();
}
__device__ __forceinline__ void wait_clock(long long c0, int t) {
    while (clock64() - c0 < t) __nanosleep(20);
    __syncwarp();
}
__device__ __forceinline__ void tma_ld2(uint32_t dst, const CUtensorMap* m, int c0, int c1, uint32_t bar) {
    asm volatile("cp.async.bulk.tensor.2d.shared::cluster.global.mbarrier::complete_tx::bytes [%0], [%1, {%3, %4}], [%2];"
                 ::"r"(dst), "l"(m), "r"(bar), "r"(c0), "r"(c1) : "memory");
}
__device__ __forceinline__ void tma_ld3(uint32_t dst, const CUtensorMap* m, int c0, int c1, int c2, uint32_t bar) {
    asm volatile("cp.async.bulk.tensor.3d.shared::cluster.global.mbarrier::complete_tx::bytes [%0], [%1, {%3, %4, %5}], [%2];"
                 ::"r"(dst), "l"(m), "r"(bar), "r"(c0), "r"(c1), "r"(c2) : "memory");
}
__device__ __forceinline__ void tma_ld5(uint32_t dst, const CUtensorMap* m, int col, int blk, uint32_t bar) {
    asm volatile("cp.async.bulk.tensor.5d.shared::cluster.global.mbarrier::complete_tx::bytes [%0], [%1, {%3, %4, %4, %4, %5}], [%2];"
                 ::"r"(dst), "l"(m), "r"(bar), "r"(col), "r"(0), "r"(blk) : "memory");
}
__device__ __forceinline__ void bulk_ld(uint32_t dst, const void* src, uint32_t bytes, uint32_t bar) {
    asm volatile("cp.async.bulk.shared::cluster.global.mbarrier::complete_tx::bytes [%0], [%1], %2, [%3];" ::"r"(dst), "l"(src), "r"(bytes), "r"(bar) : "memory");
}
__device__ __forceinline__ void l2_prefetch(const void* p, uint32_t bytes) {
    asm volatile("cp.async.bulk.prefetch.L2.global [%0], %1;" ::"l"(p), "r"(bytes) : "memory");
}
__device__ __forceinline__ void wg_fence() { asm volatile("wgmma.fence.sync.aligned;" ::: "memory"); }
__device__ __forceinline__ void wg_commit() { asm volatile("wgmma.commit_group.sync.aligned;" ::: "memory"); }
template <int N> __device__ __forceinline__ void wg_wait() { asm volatile("wgmma.wait_group.sync.aligned %0;" ::"n"(N) : "memory"); }
template <int N> __device__ __forceinline__ void reg_fence(float (&d)[N]) {
#pragma unroll
    for (int i = 0; i < N; i++) asm volatile("" : "+f"(d[i])::"memory");
}
template <int N> __device__ __forceinline__ void zero(float (&d)[N]) {
#pragma unroll
    for (int i = 0; i < N; i++) asm volatile("mov.b32 %0, 0;" : "=f"(d[i]));
}
__device__ __forceinline__ uint32_t lds32(uint32_t a) { uint32_t v; asm volatile("ld.shared.b32 %0, [%1];" : "=r"(v) : "r"(a)); return v; }
__device__ __forceinline__ uint2 lds64(uint32_t a) { uint2 v; asm volatile("ld.shared.v2.b32 {%0,%1}, [%2];" : "=r"(v.x), "=r"(v.y) : "r"(a)); return v; }
__device__ __forceinline__ float2 lds64f(uint32_t a) { float2 v; asm volatile("ld.shared.v2.f32 {%0,%1}, [%2];" : "=f"(v.x), "=f"(v.y) : "r"(a)); return v; }
__device__ __forceinline__ void sts32(uint32_t a, uint32_t v) { asm volatile("st.shared.b32 [%0], %1;" ::"r"(a), "r"(v) : "memory"); }
__device__ __forceinline__ void sts64f(uint32_t a, float x, float y) { asm volatile("st.shared.v2.f32 [%0], {%1,%2};" ::"r"(a), "f"(x), "f"(y) : "memory"); }
__device__ __forceinline__ void sts128(uint32_t a, uint32_t x, uint32_t y, uint32_t z, uint32_t w) {
    asm volatile("st.shared.v4.b32 [%0], {%1,%2,%3,%4};" ::"r"(a), "r"(x), "r"(y), "r"(z), "r"(w) : "memory");
}
__device__ __forceinline__ void sts128f(uint32_t a, float x, float y, float z, float w) {
    asm volatile("st.shared.v4.f32 [%0], {%1,%2,%3,%4};" ::"r"(a), "f"(x), "f"(y), "f"(z), "f"(w) : "memory");
}
__device__ __forceinline__ uint4 lds128(uint32_t a) {
    uint4 v;
    asm volatile("ld.shared.v4.b32 {%0,%1,%2,%3}, [%4];" : "=r"(v.x), "=r"(v.y), "=r"(v.z), "=r"(v.w) : "r"(a) : "memory");
    return v;
}
__device__ __forceinline__ float4 lds128f(uint32_t a) {
    float4 v;
    asm volatile("ld.shared.v4.f32 {%0,%1,%2,%3}, [%4];" : "=f"(v.x), "=f"(v.y), "=f"(v.z), "=f"(v.w) : "r"(a) : "memory");
    return v;
}
__device__ __forceinline__ void stg128(void* p, uint32_t x, uint32_t y, uint32_t z, uint32_t w) {
    asm volatile("st.global.v4.b32 [%0], {%1,%2,%3,%4};" ::"l"(p), "r"(x), "r"(y), "r"(z), "r"(w) : "memory");
}
__device__ __forceinline__ void stg128(void* p, uint4 v) { stg128(p, v.x, v.y, v.z, v.w); }
__device__ __forceinline__ void stg128_if(void* p, uint4 v, int on) {
    asm volatile("{\n.reg .pred p;\nsetp.ne.s32 p, %5, 0;\n@p st.global.v4.b32 [%0], {%1,%2,%3,%4};\n}" ::"l"(p), "r"(v.x), "r"(v.y), "r"(v.z), "r"(v.w), "r"(on) : "memory");
}
__device__ __forceinline__ void stg64(void* p, uint32_t x, uint32_t y) { asm volatile("st.global.v2.b32 [%0], {%1,%2};" ::"l"(p), "r"(x), "r"(y) : "memory"); }
__device__ __forceinline__ void stsm4(uint32_t a, uint32_t r0, uint32_t r1, uint32_t r2, uint32_t r3) {
    asm volatile("stmatrix.sync.aligned.m8n8.x4.shared.b16 [%0], {%1,%2,%3,%4};" ::"r"(a), "r"(r0), "r"(r1), "r"(r2), "r"(r3) : "memory");
}
__device__ __forceinline__ void stsm4t(uint32_t a, uint32_t r0, uint32_t r1, uint32_t r2, uint32_t r3) {
    asm volatile("stmatrix.sync.aligned.m8n8.x4.trans.shared.b16 [%0], {%1,%2,%3,%4};" ::"r"(a), "r"(r0), "r"(r1), "r"(r2), "r"(r3) : "memory");
}
__device__ __forceinline__ void ldsm4t(uint32_t a, uint32_t& r0, uint32_t& r1, uint32_t& r2, uint32_t& r3) {
    asm volatile("ldmatrix.sync.aligned.m8n8.x4.trans.shared.b16 {%0,%1,%2,%3}, [%4];" : "=r"(r0), "=r"(r1), "=r"(r2), "=r"(r3) : "r"(a) : "memory");
}
__device__ __forceinline__ uint32_t pack2(float lo, float hi) {
    uint32_t r;
    asm("cvt.rn.bf16x2.f32 %0, %1, %2;" : "=r"(r) : "f"(hi), "f"(lo));
    return r;
}
__device__ __forceinline__ uint32_t mul2(uint32_t a, uint32_t b) { uint32_t r; asm("mul.rn.bf16x2 %0, %1, %2;" : "=r"(r) : "r"(a), "r"(b)); return r; }
__device__ __forceinline__ uint32_t fma2(uint32_t a, uint32_t b, uint32_t c) { uint32_t r; asm("fma.rn.bf16x2 %0, %1, %2, %3;" : "=r"(r) : "r"(a), "r"(b), "r"(c)); return r; }
__device__ __forceinline__ uint32_t add2(uint32_t a, uint32_t b) { uint32_t r; asm("add.rn.bf16x2 %0, %1, %2;" : "=r"(r) : "r"(a), "r"(b)); return r; }
__device__ __forceinline__ void hmma(float (&d)[4], uint32_t a0, uint32_t a1, uint32_t a2, uint32_t a3, uint32_t b0, uint32_t b1) {
    asm volatile("mma.sync.aligned.m16n8k16.row.col.f32.bf16.bf16.f32 {%0,%1,%2,%3}, {%4,%5,%6,%7}, {%8,%9}, {%0,%1,%2,%3};"
        : "+f"(d[0]), "+f"(d[1]), "+f"(d[2]), "+f"(d[3]) : "r"(a0), "r"(a1), "r"(a2), "r"(a3), "r"(b0), "r"(b1));
}
__device__ __forceinline__ float blo(uint32_t w) { return __uint_as_float(w << 16); }
__device__ __forceinline__ float bhi(uint32_t w) { return __uint_as_float(w & 0xffff0000u); }
__device__ __forceinline__ float rbf(float x) { return __bfloat162float(__float2bfloat16_rn(x)); }
__device__ __forceinline__ uint32_t ldg32(const void* p) { uint32_t v; asm volatile("ld.global.nc.b32 %0, [%1];" : "=r"(v) : "l"(p)); return v; }
__device__ __forceinline__ uint2 ldg64(const void* p) { uint2 v; asm volatile("ld.global.nc.v2.b32 {%0,%1}, [%2];" : "=r"(v.x), "=r"(v.y) : "l"(p)); return v; }
__device__ __forceinline__ uint4 ldg128(const void* p) {
    uint4 v;
    asm volatile("ld.global.nc.v4.b32 {%0,%1,%2,%3}, [%4];" : "=r"(v.x), "=r"(v.y), "=r"(v.z), "=r"(v.w) : "l"(p));
    return v;
}
__device__ __forceinline__ uint4 ldcg128(const void* p) {
    uint4 v;
    asm volatile("ld.global.cg.v4.u32 {%0,%1,%2,%3}, [%4];" : "=r"(v.x), "=r"(v.y), "=r"(v.z), "=r"(v.w) : "l"(p) : "memory");
    return v;
}
__device__ __forceinline__ float4 ldcg128f(const void* p) {
    float4 v;
    asm volatile("ld.global.cg.v4.f32 {%0,%1,%2,%3}, [%4];" : "=f"(v.x), "=f"(v.y), "=f"(v.z), "=f"(v.w) : "l"(p) : "memory");
    return v;
}
__device__ __forceinline__ float2 ldcg64f(const void* p) { float2 v; asm volatile("ld.global.cg.v2.f32 {%0,%1}, [%2];" : "=f"(v.x), "=f"(v.y) : "l"(p) : "memory"); return v; }
__device__ __forceinline__ float ldcg32f(const void* p) { float v; asm volatile("ld.global.cg.f32 %0, [%1];" : "=f"(v) : "l"(p) : "memory"); return v; }
__device__ __forceinline__ float2 ld_stat(const float2* p) {
    float2 v;
    asm volatile("{\n.reg .b64 q;\nld.relaxed.gpu.global.b64 q, [%2];\nmov.b64 {%0, %1}, q;\n}" : "=f"(v.x), "=f"(v.y) : "l"(p) : "memory");
    return v;
}
__device__ __forceinline__ uint32_t ld_cold(const unsigned* p) { uint32_t v; asm volatile("ld.relaxed.gpu.global.u32 %0, [%1];" : "=r"(v) : "l"(p) : "memory"); return v; }
__device__ __forceinline__ uint2 ld_mod(const uint2* p) {
    uint64_t v;
    asm volatile("ld.relaxed.gpu.global.b64 %0, [%1];" : "=l"(v) : "l"(p) : "memory");
    return make_uint2((uint32_t)v, (uint32_t)(v >> 32));
}
__device__ __forceinline__ float gelu2(float h) {
    float u = h * fmaf(h * h, 8.f * 0.0356774081f, 2.f * 0.7978845608f);
    float th;
    asm("tanh.approx.f32 %0, %1;" : "=f"(th) : "f"(u));
    return fmaf(h, th, h);
}

__device__ __forceinline__ void conv_channel(float (&d)[64], uint32_t pa, uint64_t db) {
    asm volatile("{\n.reg .b32 a0, a1, a2, a3, b0, b1, b2, b3, t0, t1;\n.reg .b64 d;\nld.shared.b32 a0, [%64];\nld.shared.b32 a1, [%64+128];\nld.shared.b32 a2, [%64+-128];\nmov.b32 a3, a0;\n"
        "ld.shared.b32 t0, [%64+256];\nld.shared.b32 t1, [%64+384];\nadd.s64 d, %65, 0;\nwgmma.fence.sync.aligned;\nwgmma.mma_async.sync.aligned.m64n128k16.f32.bf16.bf16 {%0, %1, %2, %3, %4, %5, %6, %7, %8, %9, %10, %11, %12, %13, %14, %15, %16, %17, %18, %19, %20, %21, %22, %23, %24, %25, %26, %27, %28, %29, %30, %31, %32, %33, %34, %35, %36, %37, %38, %39, %40, %41, %42, %43, %44, %45, %46, %47, %48, %49, %50, %51, %52, %53, %54, %55, %56, %57, %58, %59, %60, %61, %62, %63}, {a0, a1, a2, a3}, d, 0, 1, 1, 0;\nwgmma.commit_group.sync.aligned;\nwgmma.wait_group.sync.aligned 1;\nmov.b32 b2, a1;\nmov.b32 b0, t0;\nmov.b32 b3, t0;\nmov.b32 b1, t1;\n"
        "ld.shared.b32 t0, [%64+512];\nld.shared.b32 t1, [%64+640];\nadd.s64 d, %65, 8;\nwgmma.fence.sync.aligned;\nwgmma.mma_async.sync.aligned.m64n128k16.f32.bf16.bf16 {%0, %1, %2, %3, %4, %5, %6, %7, %8, %9, %10, %11, %12, %13, %14, %15, %16, %17, %18, %19, %20, %21, %22, %23, %24, %25, %26, %27, %28, %29, %30, %31, %32, %33, %34, %35, %36, %37, %38, %39, %40, %41, %42, %43, %44, %45, %46, %47, %48, %49, %50, %51, %52, %53, %54, %55, %56, %57, %58, %59, %60, %61, %62, %63}, {b0, b1, b2, b3}, d, 1, 1, 1, 0;\nwgmma.commit_group.sync.aligned;\nwgmma.wait_group.sync.aligned 1;\nmov.b32 a2, b1;\nmov.b32 a0, t0;\nmov.b32 a3, t0;\nmov.b32 a1, t1;\n"
        "ld.shared.b32 t0, [%64+768];\nld.shared.b32 t1, [%64+896];\nadd.s64 d, %65, 16;\nwgmma.fence.sync.aligned;\nwgmma.mma_async.sync.aligned.m64n128k16.f32.bf16.bf16 {%0, %1, %2, %3, %4, %5, %6, %7, %8, %9, %10, %11, %12, %13, %14, %15, %16, %17, %18, %19, %20, %21, %22, %23, %24, %25, %26, %27, %28, %29, %30, %31, %32, %33, %34, %35, %36, %37, %38, %39, %40, %41, %42, %43, %44, %45, %46, %47, %48, %49, %50, %51, %52, %53, %54, %55, %56, %57, %58, %59, %60, %61, %62, %63}, {a0, a1, a2, a3}, d, 1, 1, 1, 0;\nwgmma.commit_group.sync.aligned;\nwgmma.wait_group.sync.aligned 1;\nmov.b32 b2, a1;\nmov.b32 b0, t0;\nmov.b32 b3, t0;\nmov.b32 b1, t1;\n"
        "ld.shared.b32 t0, [%64+1024];\nld.shared.b32 t1, [%64+1152];\nadd.s64 d, %65, 24;\nwgmma.fence.sync.aligned;\nwgmma.mma_async.sync.aligned.m64n128k16.f32.bf16.bf16 {%0, %1, %2, %3, %4, %5, %6, %7, %8, %9, %10, %11, %12, %13, %14, %15, %16, %17, %18, %19, %20, %21, %22, %23, %24, %25, %26, %27, %28, %29, %30, %31, %32, %33, %34, %35, %36, %37, %38, %39, %40, %41, %42, %43, %44, %45, %46, %47, %48, %49, %50, %51, %52, %53, %54, %55, %56, %57, %58, %59, %60, %61, %62, %63}, {b0, b1, b2, b3}, d, 1, 1, 1, 0;\nwgmma.commit_group.sync.aligned;\nwgmma.wait_group.sync.aligned 1;\nmov.b32 a2, b1;\nmov.b32 a0, t0;\nmov.b32 a3, t0;\nmov.b32 a1, t1;\n"
        "ld.shared.b32 t0, [%64+1280];\nld.shared.b32 t1, [%64+1408];\nadd.s64 d, %65, 32;\nwgmma.fence.sync.aligned;\nwgmma.mma_async.sync.aligned.m64n128k16.f32.bf16.bf16 {%0, %1, %2, %3, %4, %5, %6, %7, %8, %9, %10, %11, %12, %13, %14, %15, %16, %17, %18, %19, %20, %21, %22, %23, %24, %25, %26, %27, %28, %29, %30, %31, %32, %33, %34, %35, %36, %37, %38, %39, %40, %41, %42, %43, %44, %45, %46, %47, %48, %49, %50, %51, %52, %53, %54, %55, %56, %57, %58, %59, %60, %61, %62, %63}, {a0, a1, a2, a3}, d, 1, 1, 1, 0;\nwgmma.commit_group.sync.aligned;\nwgmma.wait_group.sync.aligned 1;\nmov.b32 b2, a1;\nmov.b32 b0, t0;\nmov.b32 b3, t0;\nmov.b32 b1, t1;\n"
        "ld.shared.b32 t0, [%64+1536];\nld.shared.b32 t1, [%64+1664];\nadd.s64 d, %65, 40;\nwgmma.fence.sync.aligned;\nwgmma.mma_async.sync.aligned.m64n128k16.f32.bf16.bf16 {%0, %1, %2, %3, %4, %5, %6, %7, %8, %9, %10, %11, %12, %13, %14, %15, %16, %17, %18, %19, %20, %21, %22, %23, %24, %25, %26, %27, %28, %29, %30, %31, %32, %33, %34, %35, %36, %37, %38, %39, %40, %41, %42, %43, %44, %45, %46, %47, %48, %49, %50, %51, %52, %53, %54, %55, %56, %57, %58, %59, %60, %61, %62, %63}, {b0, b1, b2, b3}, d, 1, 1, 1, 0;\nwgmma.commit_group.sync.aligned;\nwgmma.wait_group.sync.aligned 1;\nmov.b32 a2, b1;\nmov.b32 a0, t0;\nmov.b32 a3, t0;\nmov.b32 a1, t1;\n"
        "ld.shared.b32 t0, [%64+1792];\nld.shared.b32 t1, [%64+1920];\nadd.s64 d, %65, 48;\nwgmma.fence.sync.aligned;\nwgmma.mma_async.sync.aligned.m64n128k16.f32.bf16.bf16 {%0, %1, %2, %3, %4, %5, %6, %7, %8, %9, %10, %11, %12, %13, %14, %15, %16, %17, %18, %19, %20, %21, %22, %23, %24, %25, %26, %27, %28, %29, %30, %31, %32, %33, %34, %35, %36, %37, %38, %39, %40, %41, %42, %43, %44, %45, %46, %47, %48, %49, %50, %51, %52, %53, %54, %55, %56, %57, %58, %59, %60, %61, %62, %63}, {a0, a1, a2, a3}, d, 1, 1, 1, 0;\nwgmma.commit_group.sync.aligned;\nwgmma.wait_group.sync.aligned 1;\nmov.b32 b2, a1;\nmov.b32 b0, t0;\nmov.b32 b3, t0;\nmov.b32 b1, t1;\n"
        "ld.shared.b32 t0, [%64+2048];\nld.shared.b32 t1, [%64+2176];\nadd.s64 d, %65, 56;\nwgmma.fence.sync.aligned;\nwgmma.mma_async.sync.aligned.m64n128k16.f32.bf16.bf16 {%0, %1, %2, %3, %4, %5, %6, %7, %8, %9, %10, %11, %12, %13, %14, %15, %16, %17, %18, %19, %20, %21, %22, %23, %24, %25, %26, %27, %28, %29, %30, %31, %32, %33, %34, %35, %36, %37, %38, %39, %40, %41, %42, %43, %44, %45, %46, %47, %48, %49, %50, %51, %52, %53, %54, %55, %56, %57, %58, %59, %60, %61, %62, %63}, {b0, b1, b2, b3}, d, 1, 1, 1, 0;\nwgmma.commit_group.sync.aligned;\nwgmma.wait_group.sync.aligned 1;\nmov.b32 a2, b1;\nmov.b32 a0, t0;\nmov.b32 a3, t0;\nmov.b32 a1, t1;\n"
        "ld.shared.b32 t0, [%64+2304];\nld.shared.b32 t1, [%64+2432];\nadd.s64 d, %65, 64;\nwgmma.fence.sync.aligned;\nwgmma.mma_async.sync.aligned.m64n96k16.f32.bf16.bf16 {%0, %1, %2, %3, %4, %5, %6, %7, %8, %9, %10, %11, %12, %13, %14, %15, %16, %17, %18, %19, %20, %21, %22, %23, %24, %25, %26, %27, %28, %29, %30, %31, %32, %33, %34, %35, %36, %37, %38, %39, %40, %41, %42, %43, %44, %45, %46, %47}, {a0, a1, a2, a3}, d, 1, 1, 1, 0;\nwgmma.commit_group.sync.aligned;\nwgmma.wait_group.sync.aligned 1;\nmov.b32 b2, a1;\nmov.b32 b0, t0;\nmov.b32 b3, t0;\nmov.b32 b1, t1;\n"
        "ld.shared.b32 t0, [%64+2560];\nld.shared.b32 t1, [%64+2688];\nadd.s64 d, %65, 72;\nwgmma.fence.sync.aligned;\nwgmma.mma_async.sync.aligned.m64n96k16.f32.bf16.bf16 {%0, %1, %2, %3, %4, %5, %6, %7, %8, %9, %10, %11, %12, %13, %14, %15, %16, %17, %18, %19, %20, %21, %22, %23, %24, %25, %26, %27, %28, %29, %30, %31, %32, %33, %34, %35, %36, %37, %38, %39, %40, %41, %42, %43, %44, %45, %46, %47}, {b0, b1, b2, b3}, d, 1, 1, 1, 0;\nwgmma.commit_group.sync.aligned;\nwgmma.wait_group.sync.aligned 1;\nmov.b32 a2, b1;\nmov.b32 a0, t0;\nmov.b32 a3, t0;\nmov.b32 a1, t1;\n"
        "ld.shared.b32 t0, [%64+2816];\nld.shared.b32 t1, [%64+2944];\nadd.s64 d, %65, 80;\nwgmma.fence.sync.aligned;\nwgmma.mma_async.sync.aligned.m64n88k16.f32.bf16.bf16 {%0, %1, %2, %3, %4, %5, %6, %7, %8, %9, %10, %11, %12, %13, %14, %15, %16, %17, %18, %19, %20, %21, %22, %23, %24, %25, %26, %27, %28, %29, %30, %31, %32, %33, %34, %35, %36, %37, %38, %39, %40, %41, %42, %43}, {a0, a1, a2, a3}, d, 1, 1, 1, 0;\nwgmma.commit_group.sync.aligned;\nwgmma.wait_group.sync.aligned 1;\nmov.b32 b2, a1;\nmov.b32 b0, t0;\nmov.b32 b3, t0;\nmov.b32 b1, t1;\n"
        "ld.shared.b32 t0, [%64+3072];\nld.shared.b32 t1, [%64+3200];\nadd.s64 d, %65, 88;\nwgmma.fence.sync.aligned;\nwgmma.mma_async.sync.aligned.m64n88k16.f32.bf16.bf16 {%0, %1, %2, %3, %4, %5, %6, %7, %8, %9, %10, %11, %12, %13, %14, %15, %16, %17, %18, %19, %20, %21, %22, %23, %24, %25, %26, %27, %28, %29, %30, %31, %32, %33, %34, %35, %36, %37, %38, %39, %40, %41, %42, %43}, {b0, b1, b2, b3}, d, 1, 1, 1, 0;\nwgmma.commit_group.sync.aligned;\nwgmma.wait_group.sync.aligned 1;\nmov.b32 a2, b1;\nmov.b32 a0, t0;\nmov.b32 a3, t0;\nmov.b32 a1, t1;\n"
        "ld.shared.b32 t0, [%64+3328];\nld.shared.b32 t1, [%64+3456];\nadd.s64 d, %65, 96;\nwgmma.fence.sync.aligned;\nwgmma.mma_async.sync.aligned.m64n80k16.f32.bf16.bf16 {%0, %1, %2, %3, %4, %5, %6, %7, %8, %9, %10, %11, %12, %13, %14, %15, %16, %17, %18, %19, %20, %21, %22, %23, %24, %25, %26, %27, %28, %29, %30, %31, %32, %33, %34, %35, %36, %37, %38, %39}, {a0, a1, a2, a3}, d, 1, 1, 1, 0;\nwgmma.commit_group.sync.aligned;\nwgmma.wait_group.sync.aligned 1;\nmov.b32 b2, a1;\nmov.b32 b0, t0;\nmov.b32 b3, t0;\nmov.b32 b1, t1;\n"
        "ld.shared.b32 t0, [%64+3584];\nld.shared.b32 t1, [%64+3712];\nadd.s64 d, %65, 104;\nwgmma.fence.sync.aligned;\nwgmma.mma_async.sync.aligned.m64n80k16.f32.bf16.bf16 {%0, %1, %2, %3, %4, %5, %6, %7, %8, %9, %10, %11, %12, %13, %14, %15, %16, %17, %18, %19, %20, %21, %22, %23, %24, %25, %26, %27, %28, %29, %30, %31, %32, %33, %34, %35, %36, %37, %38, %39}, {b0, b1, b2, b3}, d, 1, 1, 1, 0;\nwgmma.commit_group.sync.aligned;\nwgmma.wait_group.sync.aligned 1;\nmov.b32 a2, b1;\nmov.b32 a0, t0;\nmov.b32 a3, t0;\nmov.b32 a1, t1;\n"
        "ld.shared.b32 t0, [%64+3840];\nld.shared.b32 t1, [%64+3968];\nadd.s64 d, %65, 112;\nwgmma.fence.sync.aligned;\nwgmma.mma_async.sync.aligned.m64n72k16.f32.bf16.bf16 {%0, %1, %2, %3, %4, %5, %6, %7, %8, %9, %10, %11, %12, %13, %14, %15, %16, %17, %18, %19, %20, %21, %22, %23, %24, %25, %26, %27, %28, %29, %30, %31, %32, %33, %34, %35}, {a0, a1, a2, a3}, d, 1, 1, 1, 0;\nwgmma.commit_group.sync.aligned;\nwgmma.wait_group.sync.aligned 1;\nmov.b32 b2, a1;\nmov.b32 b0, t0;\nmov.b32 b3, t0;\nmov.b32 b1, t1;\n"
        "ld.shared.b32 t0, [%64+4096];\nld.shared.b32 t1, [%64+4224];\nadd.s64 d, %65, 120;\nwgmma.fence.sync.aligned;\nwgmma.mma_async.sync.aligned.m64n72k16.f32.bf16.bf16 {%0, %1, %2, %3, %4, %5, %6, %7, %8, %9, %10, %11, %12, %13, %14, %15, %16, %17, %18, %19, %20, %21, %22, %23, %24, %25, %26, %27, %28, %29, %30, %31, %32, %33, %34, %35}, {b0, b1, b2, b3}, d, 1, 1, 1, 0;\nwgmma.commit_group.sync.aligned;\nwgmma.wait_group.sync.aligned 1;\nmov.b32 a2, b1;\nmov.b32 a0, t0;\nmov.b32 a3, t0;\nmov.b32 a1, t1;\n"
        "ld.shared.b32 t0, [%64+4352];\nld.shared.b32 t1, [%64+4480];\nadd.s64 d, %65, 128;\nwgmma.fence.sync.aligned;\nwgmma.mma_async.sync.aligned.m64n64k16.f32.bf16.bf16 {%0, %1, %2, %3, %4, %5, %6, %7, %8, %9, %10, %11, %12, %13, %14, %15, %16, %17, %18, %19, %20, %21, %22, %23, %24, %25, %26, %27, %28, %29, %30, %31}, {a0, a1, a2, a3}, d, 1, 1, 1, 0;\nwgmma.commit_group.sync.aligned;\nwgmma.wait_group.sync.aligned 1;\nmov.b32 b2, a1;\nmov.b32 b0, t0;\nmov.b32 b3, t0;\nmov.b32 b1, t1;\n"
        "ld.shared.b32 t0, [%64+4608];\nld.shared.b32 t1, [%64+4736];\nadd.s64 d, %65, 136;\nwgmma.fence.sync.aligned;\nwgmma.mma_async.sync.aligned.m64n64k16.f32.bf16.bf16 {%0, %1, %2, %3, %4, %5, %6, %7, %8, %9, %10, %11, %12, %13, %14, %15, %16, %17, %18, %19, %20, %21, %22, %23, %24, %25, %26, %27, %28, %29, %30, %31}, {b0, b1, b2, b3}, d, 1, 1, 1, 0;\nwgmma.commit_group.sync.aligned;\nwgmma.wait_group.sync.aligned 1;\nmov.b32 a2, b1;\nmov.b32 a0, t0;\nmov.b32 a3, t0;\nmov.b32 a1, t1;\n"
        "ld.shared.b32 t0, [%64+4864];\nld.shared.b32 t1, [%64+4992];\nadd.s64 d, %65, 144;\nwgmma.fence.sync.aligned;\nwgmma.mma_async.sync.aligned.m64n56k16.f32.bf16.bf16 {%0, %1, %2, %3, %4, %5, %6, %7, %8, %9, %10, %11, %12, %13, %14, %15, %16, %17, %18, %19, %20, %21, %22, %23, %24, %25, %26, %27}, {a0, a1, a2, a3}, d, 1, 1, 1, 0;\nwgmma.commit_group.sync.aligned;\nwgmma.wait_group.sync.aligned 1;\nmov.b32 b2, a1;\nmov.b32 b0, t0;\nmov.b32 b3, t0;\nmov.b32 b1, t1;\n"
        "ld.shared.b32 t0, [%64+5120];\nld.shared.b32 t1, [%64+5248];\nadd.s64 d, %65, 152;\nwgmma.fence.sync.aligned;\nwgmma.mma_async.sync.aligned.m64n56k16.f32.bf16.bf16 {%0, %1, %2, %3, %4, %5, %6, %7, %8, %9, %10, %11, %12, %13, %14, %15, %16, %17, %18, %19, %20, %21, %22, %23, %24, %25, %26, %27}, {b0, b1, b2, b3}, d, 1, 1, 1, 0;\nwgmma.commit_group.sync.aligned;\nwgmma.wait_group.sync.aligned 1;\nmov.b32 a2, b1;\nmov.b32 a0, t0;\nmov.b32 a3, t0;\nmov.b32 a1, t1;\n"
        "ld.shared.b32 t0, [%64+5376];\nld.shared.b32 t1, [%64+5504];\nadd.s64 d, %65, 160;\nwgmma.fence.sync.aligned;\nwgmma.mma_async.sync.aligned.m64n48k16.f32.bf16.bf16 {%0, %1, %2, %3, %4, %5, %6, %7, %8, %9, %10, %11, %12, %13, %14, %15, %16, %17, %18, %19, %20, %21, %22, %23}, {a0, a1, a2, a3}, d, 1, 1, 1, 0;\nwgmma.commit_group.sync.aligned;\nwgmma.wait_group.sync.aligned 1;\nmov.b32 b2, a1;\nmov.b32 b0, t0;\nmov.b32 b3, t0;\nmov.b32 b1, t1;\n"
        "ld.shared.b32 t0, [%64+5632];\nld.shared.b32 t1, [%64+5760];\nadd.s64 d, %65, 168;\nwgmma.fence.sync.aligned;\nwgmma.mma_async.sync.aligned.m64n48k16.f32.bf16.bf16 {%0, %1, %2, %3, %4, %5, %6, %7, %8, %9, %10, %11, %12, %13, %14, %15, %16, %17, %18, %19, %20, %21, %22, %23}, {b0, b1, b2, b3}, d, 1, 1, 1, 0;\nwgmma.commit_group.sync.aligned;\nwgmma.wait_group.sync.aligned 1;\nmov.b32 a2, b1;\nmov.b32 a0, t0;\nmov.b32 a3, t0;\nmov.b32 a1, t1;\n"
        "ld.shared.b32 t0, [%64+5888];\nld.shared.b32 t1, [%64+6016];\nadd.s64 d, %65, 176;\nwgmma.fence.sync.aligned;\nwgmma.mma_async.sync.aligned.m64n40k16.f32.bf16.bf16 {%0, %1, %2, %3, %4, %5, %6, %7, %8, %9, %10, %11, %12, %13, %14, %15, %16, %17, %18, %19}, {a0, a1, a2, a3}, d, 1, 1, 1, 0;\nwgmma.commit_group.sync.aligned;\nwgmma.wait_group.sync.aligned 1;\nmov.b32 b2, a1;\nmov.b32 b0, t0;\nmov.b32 b3, t0;\nmov.b32 b1, t1;\n"
        "ld.shared.b32 t0, [%64+6144];\nld.shared.b32 t1, [%64+6272];\nadd.s64 d, %65, 184;\nwgmma.fence.sync.aligned;\nwgmma.mma_async.sync.aligned.m64n40k16.f32.bf16.bf16 {%0, %1, %2, %3, %4, %5, %6, %7, %8, %9, %10, %11, %12, %13, %14, %15, %16, %17, %18, %19}, {b0, b1, b2, b3}, d, 1, 1, 1, 0;\nwgmma.commit_group.sync.aligned;\nwgmma.wait_group.sync.aligned 1;\nmov.b32 a2, b1;\nmov.b32 a0, t0;\nmov.b32 a3, t0;\nmov.b32 a1, t1;\n"
        "ld.shared.b32 t0, [%64+6400];\nld.shared.b32 t1, [%64+6528];\nadd.s64 d, %65, 192;\nwgmma.fence.sync.aligned;\nwgmma.mma_async.sync.aligned.m64n32k16.f32.bf16.bf16 {%0, %1, %2, %3, %4, %5, %6, %7, %8, %9, %10, %11, %12, %13, %14, %15}, {a0, a1, a2, a3}, d, 1, 1, 1, 0;\nwgmma.commit_group.sync.aligned;\nwgmma.wait_group.sync.aligned 1;\nmov.b32 b2, a1;\nmov.b32 b0, t0;\nmov.b32 b3, t0;\nmov.b32 b1, t1;\n"
        "ld.shared.b32 t0, [%64+6656];\nld.shared.b32 t1, [%64+6784];\nadd.s64 d, %65, 200;\nwgmma.fence.sync.aligned;\nwgmma.mma_async.sync.aligned.m64n32k16.f32.bf16.bf16 {%0, %1, %2, %3, %4, %5, %6, %7, %8, %9, %10, %11, %12, %13, %14, %15}, {b0, b1, b2, b3}, d, 1, 1, 1, 0;\nwgmma.commit_group.sync.aligned;\nwgmma.wait_group.sync.aligned 1;\nmov.b32 a2, b1;\nmov.b32 a0, t0;\nmov.b32 a3, t0;\nmov.b32 a1, t1;\n"
        "ld.shared.b32 t0, [%64+6912];\nld.shared.b32 t1, [%64+7040];\nadd.s64 d, %65, 208;\nwgmma.fence.sync.aligned;\nwgmma.mma_async.sync.aligned.m64n24k16.f32.bf16.bf16 {%0, %1, %2, %3, %4, %5, %6, %7, %8, %9, %10, %11}, {a0, a1, a2, a3}, d, 1, 1, 1, 0;\nwgmma.commit_group.sync.aligned;\nwgmma.wait_group.sync.aligned 1;\nmov.b32 b2, a1;\nmov.b32 b0, t0;\nmov.b32 b3, t0;\nmov.b32 b1, t1;\n"
        "ld.shared.b32 t0, [%64+7168];\nld.shared.b32 t1, [%64+7296];\nadd.s64 d, %65, 216;\nwgmma.fence.sync.aligned;\nwgmma.mma_async.sync.aligned.m64n24k16.f32.bf16.bf16 {%0, %1, %2, %3, %4, %5, %6, %7, %8, %9, %10, %11}, {b0, b1, b2, b3}, d, 1, 1, 1, 0;\nwgmma.commit_group.sync.aligned;\nwgmma.wait_group.sync.aligned 1;\nmov.b32 a2, b1;\nmov.b32 a0, t0;\nmov.b32 a3, t0;\nmov.b32 a1, t1;\n"
        "ld.shared.b32 t0, [%64+7424];\nld.shared.b32 t1, [%64+7552];\nadd.s64 d, %65, 224;\nwgmma.fence.sync.aligned;\nwgmma.mma_async.sync.aligned.m64n16k16.f32.bf16.bf16 {%0, %1, %2, %3, %4, %5, %6, %7}, {a0, a1, a2, a3}, d, 1, 1, 1, 0;\nwgmma.commit_group.sync.aligned;\nwgmma.wait_group.sync.aligned 1;\nmov.b32 b2, a1;\nmov.b32 b0, t0;\nmov.b32 b3, t0;\nmov.b32 b1, t1;\n"
        "ld.shared.b32 t0, [%64+7680];\nld.shared.b32 t1, [%64+7808];\nadd.s64 d, %65, 232;\nwgmma.fence.sync.aligned;\nwgmma.mma_async.sync.aligned.m64n16k16.f32.bf16.bf16 {%0, %1, %2, %3, %4, %5, %6, %7}, {b0, b1, b2, b3}, d, 1, 1, 1, 0;\nwgmma.commit_group.sync.aligned;\nwgmma.wait_group.sync.aligned 1;\nmov.b32 a2, b1;\nmov.b32 a0, t0;\nmov.b32 a3, t0;\nmov.b32 a1, t1;\n"
        "ld.shared.b32 t0, [%64+7936];\nld.shared.b32 t1, [%64+8064];\nadd.s64 d, %65, 240;\nwgmma.fence.sync.aligned;\nwgmma.mma_async.sync.aligned.m64n8k16.f32.bf16.bf16 {%0, %1, %2, %3}, {a0, a1, a2, a3}, d, 1, 1, 1, 0;\nwgmma.commit_group.sync.aligned;\nwgmma.wait_group.sync.aligned 1;\nmov.b32 b2, a1;\nmov.b32 b0, t0;\nmov.b32 b3, t0;\nmov.b32 b1, t1;\n"
        "add.s64 d, %65, 248;\nwgmma.fence.sync.aligned;\nwgmma.mma_async.sync.aligned.m64n8k16.f32.bf16.bf16 {%0, %1, %2, %3}, {b0, b1, b2, b3}, d, 1, 1, 1, 0;\nwgmma.commit_group.sync.aligned;\nwgmma.wait_group.sync.aligned 0;\n"
        "}" : "+f"(d[0]), "+f"(d[1]), "+f"(d[2]), "+f"(d[3]), "+f"(d[4]), "+f"(d[5]), "+f"(d[6]), "+f"(d[7]), "+f"(d[8]), "+f"(d[9]), "+f"(d[10]), "+f"(d[11]), "+f"(d[12]), "+f"(d[13]), "+f"(d[14]), "+f"(d[15]), "+f"(d[16]), "+f"(d[17]), "+f"(d[18]), "+f"(d[19]), "+f"(d[20]), "+f"(d[21]), "+f"(d[22]), "+f"(d[23]), "+f"(d[24]), "+f"(d[25]), "+f"(d[26]), "+f"(d[27]), "+f"(d[28]), "+f"(d[29]), "+f"(d[30]), "+f"(d[31]), "+f"(d[32]), "+f"(d[33]), "+f"(d[34]), "+f"(d[35]), "+f"(d[36]), "+f"(d[37]), "+f"(d[38]), "+f"(d[39]), "+f"(d[40]), "+f"(d[41]), "+f"(d[42]), "+f"(d[43]), "+f"(d[44]), "+f"(d[45]), "+f"(d[46]), "+f"(d[47]), "+f"(d[48]), "+f"(d[49]), "+f"(d[50]), "+f"(d[51]), "+f"(d[52]), "+f"(d[53]), "+f"(d[54]), "+f"(d[55]), "+f"(d[56]), "+f"(d[57]), "+f"(d[58]), "+f"(d[59]), "+f"(d[60]), "+f"(d[61]), "+f"(d[62]), "+f"(d[63]) : "r"(pa), "l"(db) : "memory");
}
__device__ __forceinline__ void wgmma_rs80(float (&d)[40], uint32_t a0, uint32_t a1, uint32_t a2, uint32_t a3, uint64_t db, int sc) {
    asm volatile("{\n.reg .pred p;\nsetp.ne.b32 p, %45, 0;\n"
        "wgmma.mma_async.sync.aligned.m64n80k16.f32.bf16.bf16 {%0, %1, %2, %3, %4, %5, %6, %7, %8, %9, %10, %11, %12, %13, %14, %15, %16, %17, %18, %19, %20, %21, %22, %23, %24, %25, %26, %27, %28, %29, %30, %31, %32, %33, %34, %35, %36, %37, %38, %39}, {%40, %41, %42, %43}, %44, p, 1, 1, 1;\n}\n"
        : "+f"(d[0]), "+f"(d[1]), "+f"(d[2]), "+f"(d[3]), "+f"(d[4]), "+f"(d[5]), "+f"(d[6]), "+f"(d[7]), "+f"(d[8]), "+f"(d[9]), "+f"(d[10]), "+f"(d[11]), "+f"(d[12]), "+f"(d[13]), "+f"(d[14]), "+f"(d[15]), "+f"(d[16]), "+f"(d[17]), "+f"(d[18]), "+f"(d[19]), "+f"(d[20]), "+f"(d[21]), "+f"(d[22]), "+f"(d[23]), "+f"(d[24]), "+f"(d[25]), "+f"(d[26]), "+f"(d[27]), "+f"(d[28]), "+f"(d[29]), "+f"(d[30]), "+f"(d[31]), "+f"(d[32]), "+f"(d[33]), "+f"(d[34]), "+f"(d[35]), "+f"(d[36]), "+f"(d[37]), "+f"(d[38]), "+f"(d[39]) : "r"(a0), "r"(a1), "r"(a2), "r"(a3), "l"(db), "r"(sc));
}
__device__ __forceinline__ void wgmma_ss80(float (&d)[40], uint64_t da, uint64_t db, int sc) {
    asm volatile("{\n.reg .pred p;\nsetp.ne.b32 p, %42, 0;\n"
        "wgmma.mma_async.sync.aligned.m64n80k16.f32.bf16.bf16 {%0, %1, %2, %3, %4, %5, %6, %7, %8, %9, %10, %11, %12, %13, %14, %15, %16, %17, %18, %19, %20, %21, %22, %23, %24, %25, %26, %27, %28, %29, %30, %31, %32, %33, %34, %35, %36, %37, %38, %39}, %40, %41, p, 1, 1, 0, 1;\n}\n"
        : "+f"(d[0]), "+f"(d[1]), "+f"(d[2]), "+f"(d[3]), "+f"(d[4]), "+f"(d[5]), "+f"(d[6]), "+f"(d[7]), "+f"(d[8]), "+f"(d[9]), "+f"(d[10]), "+f"(d[11]), "+f"(d[12]), "+f"(d[13]), "+f"(d[14]), "+f"(d[15]), "+f"(d[16]), "+f"(d[17]), "+f"(d[18]), "+f"(d[19]), "+f"(d[20]), "+f"(d[21]), "+f"(d[22]), "+f"(d[23]), "+f"(d[24]), "+f"(d[25]), "+f"(d[26]), "+f"(d[27]), "+f"(d[28]), "+f"(d[29]), "+f"(d[30]), "+f"(d[31]), "+f"(d[32]), "+f"(d[33]), "+f"(d[34]), "+f"(d[35]), "+f"(d[36]), "+f"(d[37]), "+f"(d[38]), "+f"(d[39]) : "l"(da), "l"(db), "r"(sc));
}
__device__ __forceinline__ void wgmma_ss80t(float (&d)[40], uint64_t da, uint64_t db, int sc) {
    asm volatile("{\n.reg .pred p;\nsetp.ne.b32 p, %42, 0;\n"
        "wgmma.mma_async.sync.aligned.m64n80k16.f32.bf16.bf16 {%0, %1, %2, %3, %4, %5, %6, %7, %8, %9, %10, %11, %12, %13, %14, %15, %16, %17, %18, %19, %20, %21, %22, %23, %24, %25, %26, %27, %28, %29, %30, %31, %32, %33, %34, %35, %36, %37, %38, %39}, %40, %41, p, 1, 1, 1, 1;\n}\n"
        : "+f"(d[0]), "+f"(d[1]), "+f"(d[2]), "+f"(d[3]), "+f"(d[4]), "+f"(d[5]), "+f"(d[6]), "+f"(d[7]), "+f"(d[8]), "+f"(d[9]), "+f"(d[10]), "+f"(d[11]), "+f"(d[12]), "+f"(d[13]), "+f"(d[14]), "+f"(d[15]), "+f"(d[16]), "+f"(d[17]), "+f"(d[18]), "+f"(d[19]), "+f"(d[20]), "+f"(d[21]), "+f"(d[22]), "+f"(d[23]), "+f"(d[24]), "+f"(d[25]), "+f"(d[26]), "+f"(d[27]), "+f"(d[28]), "+f"(d[29]), "+f"(d[30]), "+f"(d[31]), "+f"(d[32]), "+f"(d[33]), "+f"(d[34]), "+f"(d[35]), "+f"(d[36]), "+f"(d[37]), "+f"(d[38]), "+f"(d[39]) : "l"(da), "l"(db), "r"(sc));
}
__device__ __forceinline__ void wgmma_ss8_ta(float (&d)[4], uint64_t da, uint64_t db, int sc) {
    asm volatile("{\n.reg .pred p;\nsetp.ne.b32 p, %6, 0;\n"
        "wgmma.mma_async.sync.aligned.m64n8k16.f32.bf16.bf16 {%0, %1, %2, %3}, %4, %5, p, 1, 1, 1, 0;\n}\n"
        : "+f"(d[0]), "+f"(d[1]), "+f"(d[2]), "+f"(d[3]) : "l"(da), "l"(db), "r"(sc));
}
__device__ __forceinline__ void wgmma_rs8(float (&d)[4], uint32_t a0, uint32_t a1, uint32_t a2, uint32_t a3, uint64_t db, int sc) {
    asm volatile("{\n.reg .pred p;\nsetp.ne.b32 p, %9, 0;\n"
        "wgmma.mma_async.sync.aligned.m64n8k16.f32.bf16.bf16 {%0, %1, %2, %3}, {%4, %5, %6, %7}, %8, p, 1, 1, 0;\n}\n"
        : "+f"(d[0]), "+f"(d[1]), "+f"(d[2]), "+f"(d[3]) : "r"(a0), "r"(a1), "r"(a2), "r"(a3), "l"(db), "r"(sc));
}
__device__ __forceinline__ void wgmma_rs128(float (&d)[64], uint32_t a0, uint32_t a1, uint32_t a2, uint32_t a3, uint64_t db, int sc) {
    asm volatile("{\n.reg .pred p;\nsetp.ne.b32 p, %69, 0;\n"
        "wgmma.mma_async.sync.aligned.m64n128k16.f32.bf16.bf16 {%0, %1, %2, %3, %4, %5, %6, %7, %8, %9, %10, %11, %12, %13, %14, %15, %16, %17, %18, %19, %20, %21, %22, %23, %24, %25, %26, %27, %28, %29, %30, %31, %32, %33, %34, %35, %36, %37, %38, %39, %40, %41, %42, %43, %44, %45, %46, %47, %48, %49, %50, %51, %52, %53, %54, %55, %56, %57, %58, %59, %60, %61, %62, %63}, {%64, %65, %66, %67}, %68, p, 1, 1, 1;\n}\n"
        : "+f"(d[0]), "+f"(d[1]), "+f"(d[2]), "+f"(d[3]), "+f"(d[4]), "+f"(d[5]), "+f"(d[6]), "+f"(d[7]), "+f"(d[8]), "+f"(d[9]), "+f"(d[10]), "+f"(d[11]), "+f"(d[12]), "+f"(d[13]), "+f"(d[14]), "+f"(d[15]), "+f"(d[16]), "+f"(d[17]), "+f"(d[18]), "+f"(d[19]), "+f"(d[20]), "+f"(d[21]), "+f"(d[22]), "+f"(d[23]), "+f"(d[24]), "+f"(d[25]), "+f"(d[26]), "+f"(d[27]), "+f"(d[28]), "+f"(d[29]), "+f"(d[30]), "+f"(d[31]), "+f"(d[32]), "+f"(d[33]), "+f"(d[34]), "+f"(d[35]), "+f"(d[36]), "+f"(d[37]), "+f"(d[38]), "+f"(d[39]), "+f"(d[40]), "+f"(d[41]), "+f"(d[42]), "+f"(d[43]), "+f"(d[44]), "+f"(d[45]), "+f"(d[46]), "+f"(d[47]), "+f"(d[48]), "+f"(d[49]), "+f"(d[50]), "+f"(d[51]), "+f"(d[52]), "+f"(d[53]), "+f"(d[54]), "+f"(d[55]), "+f"(d[56]), "+f"(d[57]), "+f"(d[58]), "+f"(d[59]), "+f"(d[60]), "+f"(d[61]), "+f"(d[62]), "+f"(d[63]) : "r"(a0), "r"(a1), "r"(a2), "r"(a3), "l"(db), "r"(sc));
}
__device__ __forceinline__ void wgmma_rs88(float (&d)[44], uint32_t a0, uint32_t a1, uint32_t a2, uint32_t a3, uint64_t db, int sc) {
    asm volatile("{\n.reg .pred p;\nsetp.ne.b32 p, %49, 0;\n"
        "wgmma.mma_async.sync.aligned.m64n88k16.f32.bf16.bf16 {%0, %1, %2, %3, %4, %5, %6, %7, %8, %9, %10, %11, %12, %13, %14, %15, %16, %17, %18, %19, %20, %21, %22, %23, %24, %25, %26, %27, %28, %29, %30, %31, %32, %33, %34, %35, %36, %37, %38, %39, %40, %41, %42, %43}, {%44, %45, %46, %47}, %48, p, 1, 1, 1;\n}\n"
        : "+f"(d[0]), "+f"(d[1]), "+f"(d[2]), "+f"(d[3]), "+f"(d[4]), "+f"(d[5]), "+f"(d[6]), "+f"(d[7]), "+f"(d[8]), "+f"(d[9]), "+f"(d[10]), "+f"(d[11]), "+f"(d[12]), "+f"(d[13]), "+f"(d[14]), "+f"(d[15]), "+f"(d[16]), "+f"(d[17]), "+f"(d[18]), "+f"(d[19]), "+f"(d[20]), "+f"(d[21]), "+f"(d[22]), "+f"(d[23]), "+f"(d[24]), "+f"(d[25]), "+f"(d[26]), "+f"(d[27]), "+f"(d[28]), "+f"(d[29]), "+f"(d[30]), "+f"(d[31]), "+f"(d[32]), "+f"(d[33]), "+f"(d[34]), "+f"(d[35]), "+f"(d[36]), "+f"(d[37]), "+f"(d[38]), "+f"(d[39]), "+f"(d[40]), "+f"(d[41]), "+f"(d[42]), "+f"(d[43]) : "r"(a0), "r"(a1), "r"(a2), "r"(a3), "l"(db), "r"(sc));
}
__device__ __forceinline__ void wgmma_rs128k(float (&d)[64], uint32_t a0, uint32_t a1, uint32_t a2, uint32_t a3, uint64_t db, int sc) {
    asm volatile("{\n.reg .pred p;\nsetp.ne.b32 p, %69, 0;\n"
        "wgmma.mma_async.sync.aligned.m64n128k16.f32.bf16.bf16 {%0, %1, %2, %3, %4, %5, %6, %7, %8, %9, %10, %11, %12, %13, %14, %15, %16, %17, %18, %19, %20, %21, %22, %23, %24, %25, %26, %27, %28, %29, %30, %31, %32, %33, %34, %35, %36, %37, %38, %39, %40, %41, %42, %43, %44, %45, %46, %47, %48, %49, %50, %51, %52, %53, %54, %55, %56, %57, %58, %59, %60, %61, %62, %63}, {%64, %65, %66, %67}, %68, p, 1, 1, 0;\n}\n"
        : "+f"(d[0]), "+f"(d[1]), "+f"(d[2]), "+f"(d[3]), "+f"(d[4]), "+f"(d[5]), "+f"(d[6]), "+f"(d[7]), "+f"(d[8]), "+f"(d[9]), "+f"(d[10]), "+f"(d[11]), "+f"(d[12]), "+f"(d[13]), "+f"(d[14]), "+f"(d[15]), "+f"(d[16]), "+f"(d[17]), "+f"(d[18]), "+f"(d[19]), "+f"(d[20]), "+f"(d[21]), "+f"(d[22]), "+f"(d[23]), "+f"(d[24]), "+f"(d[25]), "+f"(d[26]), "+f"(d[27]), "+f"(d[28]), "+f"(d[29]), "+f"(d[30]), "+f"(d[31]), "+f"(d[32]), "+f"(d[33]), "+f"(d[34]), "+f"(d[35]), "+f"(d[36]), "+f"(d[37]), "+f"(d[38]), "+f"(d[39]), "+f"(d[40]), "+f"(d[41]), "+f"(d[42]), "+f"(d[43]), "+f"(d[44]), "+f"(d[45]), "+f"(d[46]), "+f"(d[47]), "+f"(d[48]), "+f"(d[49]), "+f"(d[50]), "+f"(d[51]), "+f"(d[52]), "+f"(d[53]), "+f"(d[54]), "+f"(d[55]), "+f"(d[56]), "+f"(d[57]), "+f"(d[58]), "+f"(d[59]), "+f"(d[60]), "+f"(d[61]), "+f"(d[62]), "+f"(d[63]) : "r"(a0), "r"(a1), "r"(a2), "r"(a3), "l"(db), "r"(sc));
}
__device__ __forceinline__ void wgmma_rs88k(float (&d)[44], uint32_t a0, uint32_t a1, uint32_t a2, uint32_t a3, uint64_t db, int sc) {
    asm volatile("{\n.reg .pred p;\nsetp.ne.b32 p, %49, 0;\n"
        "wgmma.mma_async.sync.aligned.m64n88k16.f32.bf16.bf16 {%0, %1, %2, %3, %4, %5, %6, %7, %8, %9, %10, %11, %12, %13, %14, %15, %16, %17, %18, %19, %20, %21, %22, %23, %24, %25, %26, %27, %28, %29, %30, %31, %32, %33, %34, %35, %36, %37, %38, %39, %40, %41, %42, %43}, {%44, %45, %46, %47}, %48, p, 1, 1, 0;\n}\n"
        : "+f"(d[0]), "+f"(d[1]), "+f"(d[2]), "+f"(d[3]), "+f"(d[4]), "+f"(d[5]), "+f"(d[6]), "+f"(d[7]), "+f"(d[8]), "+f"(d[9]), "+f"(d[10]), "+f"(d[11]), "+f"(d[12]), "+f"(d[13]), "+f"(d[14]), "+f"(d[15]), "+f"(d[16]), "+f"(d[17]), "+f"(d[18]), "+f"(d[19]), "+f"(d[20]), "+f"(d[21]), "+f"(d[22]), "+f"(d[23]), "+f"(d[24]), "+f"(d[25]), "+f"(d[26]), "+f"(d[27]), "+f"(d[28]), "+f"(d[29]), "+f"(d[30]), "+f"(d[31]), "+f"(d[32]), "+f"(d[33]), "+f"(d[34]), "+f"(d[35]), "+f"(d[36]), "+f"(d[37]), "+f"(d[38]), "+f"(d[39]), "+f"(d[40]), "+f"(d[41]), "+f"(d[42]), "+f"(d[43]) : "r"(a0), "r"(a1), "r"(a2), "r"(a3), "l"(db), "r"(sc));
}
__device__ __forceinline__ void wgmma_rs80k(float (&d)[40], uint32_t a0, uint32_t a1, uint32_t a2, uint32_t a3, uint64_t db, int sc) {
    asm volatile("{\n.reg .pred p;\nsetp.ne.b32 p, %45, 0;\n"
        "wgmma.mma_async.sync.aligned.m64n80k16.f32.bf16.bf16 {%0, %1, %2, %3, %4, %5, %6, %7, %8, %9, %10, %11, %12, %13, %14, %15, %16, %17, %18, %19, %20, %21, %22, %23, %24, %25, %26, %27, %28, %29, %30, %31, %32, %33, %34, %35, %36, %37, %38, %39}, {%40, %41, %42, %43}, %44, p, 1, 1, 0;\n}\n"
        : "+f"(d[0]), "+f"(d[1]), "+f"(d[2]), "+f"(d[3]), "+f"(d[4]), "+f"(d[5]), "+f"(d[6]), "+f"(d[7]), "+f"(d[8]), "+f"(d[9]), "+f"(d[10]), "+f"(d[11]), "+f"(d[12]), "+f"(d[13]), "+f"(d[14]), "+f"(d[15]), "+f"(d[16]), "+f"(d[17]), "+f"(d[18]), "+f"(d[19]), "+f"(d[20]), "+f"(d[21]), "+f"(d[22]), "+f"(d[23]), "+f"(d[24]), "+f"(d[25]), "+f"(d[26]), "+f"(d[27]), "+f"(d[28]), "+f"(d[29]), "+f"(d[30]), "+f"(d[31]), "+f"(d[32]), "+f"(d[33]), "+f"(d[34]), "+f"(d[35]), "+f"(d[36]), "+f"(d[37]), "+f"(d[38]), "+f"(d[39]) : "r"(a0), "r"(a1), "r"(a2), "r"(a3), "l"(db), "r"(sc));
}
__device__ __forceinline__ void wgmma_rs64(float (&d)[32], uint32_t a0, uint32_t a1, uint32_t a2, uint32_t a3, uint64_t db, int sc) {
    asm volatile("{\n.reg .pred p;\nsetp.ne.b32 p, %37, 0;\n"
        "wgmma.mma_async.sync.aligned.m64n64k16.f32.bf16.bf16 {%0, %1, %2, %3, %4, %5, %6, %7, %8, %9, %10, %11, %12, %13, %14, %15, %16, %17, %18, %19, %20, %21, %22, %23, %24, %25, %26, %27, %28, %29, %30, %31}, {%32, %33, %34, %35}, %36, p, 1, 1, 1;\n}\n"
        : "+f"(d[0]), "+f"(d[1]), "+f"(d[2]), "+f"(d[3]), "+f"(d[4]), "+f"(d[5]), "+f"(d[6]), "+f"(d[7]), "+f"(d[8]), "+f"(d[9]), "+f"(d[10]), "+f"(d[11]), "+f"(d[12]), "+f"(d[13]), "+f"(d[14]), "+f"(d[15]), "+f"(d[16]), "+f"(d[17]), "+f"(d[18]), "+f"(d[19]), "+f"(d[20]), "+f"(d[21]), "+f"(d[22]), "+f"(d[23]), "+f"(d[24]), "+f"(d[25]), "+f"(d[26]), "+f"(d[27]), "+f"(d[28]), "+f"(d[29]), "+f"(d[30]), "+f"(d[31]) : "r"(a0), "r"(a1), "r"(a2), "r"(a3), "l"(db), "r"(sc));
}

__device__ __forceinline__ uint64_t mkdesc(uint32_t lo) { return ((uint64_t)0x40000040u << 32) | lo; }
template <int F> __device__ __forceinline__ uint32_t lop3(uint32_t a, uint32_t b, uint32_t c) { uint32_t r; asm("lop3.b32 %0, %1, %2, %3, %4;" : "=r"(r) : "r"(a), "r"(b), "r"(c), "n"(F)); return r; }
__device__ __forceinline__ void stg128_tag(void* p, uint32_t x, uint32_t y, uint32_t z, uint32_t u, uint32_t ep, int w) {
    stg128(p, lop3<0xB8>(x, w == 0, ep), lop3<0xB8>(y, w == 1, ep), lop3<0xB8>(z, w == 2, ep), lop3<0xB8>(u, w == 3, ep));
}
__device__ __forceinline__ uint32_t tag(uint32_t w, uint32_t ep) { asm("lop3.b32 %0, %0, 1, %1, 0xB8;" : "+r"(w) : "r"(ep)); return w; }
template <int N> __device__ __forceinline__ void pack_part(uint32_t (&p)[32], const float (&v)[N], uint32_t ep) {
#pragma unroll
    for (int i = 0; i < N / 2; i++) p[i] = (i & 3) ? pack2(v[2 * i], v[2 * i + 1]) : tag(pack2(v[2 * i], v[2 * i + 1]), ep);
#pragma unroll
    for (int i = 0; i < N / 2; i++) asm volatile("" : "+r"(p[i]));
}
__device__ __forceinline__ void st_part(uint4* p, const uint32_t* v) {
    asm volatile("{\n.reg .b64 l, h;\n.reg .b128 q;\nmov.b64 l, {%1, %2};\nmov.b64 h, {%3, %4};\nmov.b128 q, {l, h};\nst.relaxed.gpu.global.b128 [%0], q;\n}"
                 ::"l"(p), "r"(v[0]), "r"(v[1]), "r"(v[2]), "r"(v[3]) : "memory");
}
__device__ __forceinline__ void st_peer(uint32_t a, uint32_t x, uint32_t y, uint32_t z, uint32_t w, uint32_t bar) {
    asm volatile("st.async.shared::cluster.mbarrier::complete_tx::bytes.v4.b32 [%0], {%1, %2, %3, %4}, [%5];" ::"r"(a), "r"(x), "r"(y), "r"(z), "r"(w), "r"(bar) : "memory");
}
__device__ __forceinline__ int g4_block(int c, int j) { return c ? j ^ (8 - 2 * c) : 8 + (j & 1); }
__device__ __forceinline__ uint32_t recv_off(int w) { return w ? OFF_XR : OFF_REM; }
__device__ __forceinline__ uint4 ld_part(const void* p) {
    uint4 v;
    asm volatile("{\n.reg .b64 l, h;\n.reg .b128 q;\nld.relaxed.gpu.global.b128 q, [%4];\nmov.b128 {l, h}, q;\nmov.b64 {%0, %1}, l;\nmov.b64 {%2, %3}, h;\n}"
                 : "=r"(v.x), "=r"(v.y), "=r"(v.z), "=r"(v.w) : "l"(p) : "memory");
    return v;
}
__device__ __forceinline__ void ld_part4(uint4 (&u)[4], const uint4* p, int st) {
#pragma unroll
    for (int i = 0; i < 4; i++) u[i] = ld_part(p + i * st);
}
__device__ __forceinline__ uint32_t stale4(const uint4 (&u)[4], uint32_t ep) { return (u[0].x ^ ep) | (u[1].x ^ ep) | (u[2].x ^ ep) | (u[3].x ^ ep); }
__device__ __forceinline__ void fix4(uint4 (&u)[4], const uint4* p, uint32_t ep, int code) {
    unsigned it = 0;
    while (__any_sync(~0u, stale4(u, ep) & 1)) {
        ld_part4(u, p, 128);
        STALE(code)
        SPIN_CHECK(58)
    }
}
__device__ __forceinline__ void add8(float* v, uint4 u) {
    v[0] += blo(u.x); v[1] += bhi(u.x); v[2] += blo(u.y); v[3] += bhi(u.y);
    v[4] += blo(u.z); v[5] += bhi(u.z); v[6] += blo(u.w); v[7] += bhi(u.w);
}
__device__ __forceinline__ void unpack8(float* v, uint4 u) {
    v[0] = blo(u.x); v[1] = bhi(u.x); v[2] = blo(u.y); v[3] = bhi(u.y); v[4] = blo(u.z); v[5] = bhi(u.z); v[6] = blo(u.w); v[7] = bhi(u.w);
}
__device__ __forceinline__ uint4 add2(uint4 a, uint4 b) { return make_uint4(add2(a.x, b.x), add2(a.y, b.y), add2(a.z, b.z), add2(a.w, b.w)); }
__device__ __forceinline__ void base16(float* v, uint4 b, float2 c, float2 d) {
    v[0] = fmaf(c.x, v[0], blo(b.x)); v[1] = fmaf(c.y, v[1], bhi(b.x)); v[2] = fmaf(c.x, v[2], blo(b.y)); v[3] = fmaf(c.y, v[3], bhi(b.y));
    v[4] = fmaf(d.x, v[4], blo(b.z)); v[5] = fmaf(d.y, v[5], bhi(b.z)); v[6] = fmaf(d.x, v[6], blo(b.w)); v[7] = fmaf(d.y, v[7], bhi(b.w));
}
__device__ __forceinline__ uint32_t split2(float x) { const float h = rbf(x); return pack2(h, x - h); }
__device__ __forceinline__ uint32_t b80_desc(uint32_t dsb, uint32_t wn, uint32_t rn, uint32_t h) {
    const uint32_t wb = dsb + OFF_W + (wn & 7) * 16384 + h * 8192, rm = dsb + OFF_REM + rn * 4096 + h * 2048;
    return (wb >> 4) | ((rm - wb) << 12);
}
constexpr int64_t B80_STEP = 128 - (126 << 16), B80_HALF = 512 - (384 << 16);
__device__ __forceinline__ int g1_block(int n, int j) { return n < 5 ? 2 * n + (j & 1) : 2 * n - 9 - (j & 1); }

template <int OCT>
__device__ __forceinline__ void gemv_tile(float (&d)[4], uint32_t a, uint32_t b, int kb0) {
    uint32_t alo = ((a & 0x3FFFF) >> 4) | 0x10000u, blo_ = ((b & 0x3FFFF) >> 4) | (OCT << 16);
#pragma unroll 1
    for (int s = 0; s < 20; s += 4) {
        const int kb = kb0 + (s >> 2);
        const uint32_t bk = blo_ + (OCT == 7 ? (kb & 1) * 288 + (kb >> 1) * 56 : kb * 64);
        wg_fence();
#pragma unroll
        for (int q = 0; q < 4; q++) wgmma_ss8_ta(d, mkdesc(alo + (s + q) * 128), ((uint64_t)8 << 32) | (bk + q * 2 * OCT), s + q);
        wg_commit();
    }
    wg_wait<0>();
    reg_fence(d);
}

__device__ __forceinline__ void flush_tile(uint32_t st, bf16* dst, int u) {
#pragma unroll
    for (int i = 0; i < 2; i++) {
        const int idx = u + 320 * i, row = idx >> 3, c = idx & 7;
        stg128(dst + (size_t)row * S_ + 8 * c, lds128(st + row * 128 + ((c ^ ((row >> 1) & 7)) << 4)));
    }
}

__device__ __forceinline__ int tid_now() { int t; asm volatile("mov.u32 %0, %%tid.x;" : "=r"(t)); return t; }
__device__ __forceinline__ float zscale(float c) { return c == 0.f ? 0x1p-30f : c; }
__device__ __forceinline__ bool bar_any(int id, bool p) {
    uint32_t r;
    asm volatile("{\n.reg .pred a, b;\nsetp.ne.u32 a, %2, 0;\nbarrier.red.or.pred.aligned b, %1, 128, a;\nselp.u32 %0, 1, 0, b;\n}" : "=r"(r) : "r"(id), "r"((uint32_t)p) : "memory");
    return r != 0;
}

__global__ void __launch_bounds__(NTHR, 1) fused_kernel(const __grid_constant__ Ptrs pp, bf16* __restrict__ out, const __grid_constant__ Maps mp) {
    extern __shared__ __align__(1024) uint8_t smem_raw[];
    const uint32_t sb = s2u(smem_raw), bars = sb + M_BAR, dsb = sb & 0x3FFFF;
    const int id = blockIdx.x, warp = __shfl_sync(0xffffffffu, (int)threadIdx.x >> 5, 0), wg = warp >> 2;
    const long long c0 = clock64();
#define TIDS const int tid = tid_now(), lane = tid & 31, wt = tid & 127, g = lane >> 2, t = lane & 3; (void)wt; (void)g; (void)t;
    TS(threadIdx.x == 0, 0) TG(threadIdx.x == 0, 62)

    if (id >= 128) {
        TIDS
        if (sb & 1023) __trap();
        const int hs = id - 128;
        constexpr int H_B = 204800;
        static_assert(H_B + TAB_BYTES + 8 * VEC_BYTES <= OFF_M, "helper map");
        if (warp < 10 && elect()) { mbar_init(bars + warp * 8, 1); mbar_init(bars + 80 + warp * 8, 1); asm volatile("fence.mbarrier_init.release.cluster;" ::: "memory"); }
        __syncthreads();
        const uint32_t e0 = ld_cold(&g_epoch);
        wait_clock(c0, HELP_T);
        uint4 wr[10];
#pragma unroll
        for (int u = 0; u < 10; u++) wr[u] = ldg128(((hs >> 1) ? pp.w2 : pp.w1) + (size_t)(320 * (hs & 1) + (tid >> 4) + 32 * u) * D_ + 512 + 8 * (tid & 15));
        {
            const int r = tid >> 4, c = tid & 15;
            uint4* dst[2];
#pragma unroll
            for (int e = 0; e < 2; e++) {
                const int p = !(hs >> 1) ? r : e && (hs & 1) ? (r & ~14) | ((r & 6) << 1) | ((r & 8) >> 2) : (r & ~30) | ((r & 6) << 2) | ((r & 24) >> 2);
                dst[e] = &g_wr[(((hs >> 1) * 8 + (c >> 1)) * 10 + 5 * (hs & 1)) * 128 + (p & 15) * 8 + ((2 * (p >> 4) + (c & 1)) ^ (p & 7))];
            }
#pragma unroll
            for (int u = 0; u < 10; u++) stg128(reinterpret_cast<uint4*>(reinterpret_cast<uintptr_t>(dst[u >= 6]) ^ (64 * (u & 1))) + (u >> 1) * 128, wr[u]);
        }
        __syncthreads();
        if (warp == 0) signal_cnt(&g_cnt.wr[0], lane, 1);
        __syncthreads();
        if (warp < 5 && elect()) {
            const int un = 5 * hs + warp;
            mbar_expect(bars + warp * 8, 40960);
            tma_ld2(sb + warp * 40960, &mp.w1h, 64 * (un >> 1), 320 * (un & 1), bars + warp * 8);
            tma_ld2(sb + warp * 40960 + 20480, &mp.w1h, 64 * (un >> 1), 320 * (un & 1) + 160, bars + warp * 8);
        }
        if (tid < 320) {
            const uint4* gm = reinterpret_cast<const uint4*>(g_mod + 3 * D_) + tid;
            const unsigned epoch = e0 + 1;
            uint4 r[6];
            unsigned it = 0;
            for (;;) {
                uint32_t bad = 0;
#pragma unroll
                for (int i = 0; i < 6; i++) { r[i] = ld_part(gm + (i >> 1) * (D_ / 2) + (i & 1) * 3 * D_); bad |= (r[i].y ^ epoch) | (r[i].w ^ epoch); }
                if (__all_sync(~0u, !bad)) break;
                if (++it > SPIN_LIMIT) SPIN_FAIL(54)
            }
            uint32_t mv[3];
#pragma unroll
            for (int i = 0; i < 3; i++) mv[i] = pack2(__uint_as_float(r[2 * i].x) + __uint_as_float(r[2 * i + 1].x), __uint_as_float(r[2 * i].z) + __uint_as_float(r[2 * i + 1].z));
            const uint32_t sw2 = mv[0], cw = add2(mv[1], 0x3f803f80u), gw = mv[2];
            const float c0 = blo(cw), c1 = bhi(cw), s0 = blo(sw2), s1 = bhi(sw2);
            const float i0 = __frcp_rn(zscale(c0)), i1 = __frcp_rn(zscale(c1));
            const uint32_t ci = pack2(i0, i1), cq = pack2(i0 * i0, i1 * i1);
            const uint32_t a = sb + H_B + ((tid >> 5) & 1) * 4608 + (tid >> 6) * 896 + ((tid >> 2) & 7) * 112 + (tid & 3) * 4;
            sts32(a, ci); sts32(a + 16, pack2(i0 - blo(ci), i1 - bhi(ci)));
            sts32(a + 32, cq); sts32(a + 48, pack2(fmaf(i0, i0, -blo(cq)), fmaf(i1, i1, -bhi(cq))));
            sts32(a + 64, cw); sts32(a + 80, sw2); sts32(a + 96, 0x3f803f80u);
            if ((tid & ~35) == 284) sts32(a + 112, 0);
            const uint32_t v = sb + H_B + TAB_BYTES + (tid < 256 ? (tid >> 5) * VEC_BYTES + (tid & 31) * 8 : ((tid - 256) >> 3) * VEC_BYTES + 256 + (tid & 7) * 8);
            sts64f(v, blo(gw), bhi(gw)); sts64f(v + 320, c0, c1); sts64f(v + 640, s0, s1); sts64f(v + 960, i0, i1);
            float k[5] = {c0 + c1, s0 + s1, fmaf(c0, c0, c1 * c1), fmaf(c0, s0, c1 * s1), fmaf(s0, s0, s1 * s1)};
#pragma unroll 1
            for (int o = 16; o; o >>= 1) {
#pragma unroll
                for (int e = 0; e < 5; e++) k[e] += __shfl_xor_sync(~0u, k[e], o);
            }
            const uint32_t ks = sb + H_B + TAB_BYTES + (lane & 7) * VEC_BYTES + 1280 + (warp >> 1) * 32;
            if ((warp & 1) && lane < 8) { sts128f(ks, k[0], k[1], k[2], k[3]); sts128f(ks + 16, k[4], 0.f, 0.f, 0.f); }
            bar_sync(3, 320);
            if (!(warp & 1) && lane < 8) {
                const float4 o = lds128f(ks);
                sts128f(ks, k[0] + o.x, k[1] + o.y, k[2] + o.z, k[3] + o.w); sts32(ks + 16, __float_as_uint(k[4] + __uint_as_float(lds32(ks + 16))));
            }
            fence_async_smem();
        }
        __syncthreads();
        if (hs == 0 && warp == 15 && elect()) {
            asm volatile("cp.async.bulk.global.shared::cta.bulk_group [%0], [%1], %2;\ncp.async.bulk.commit_group;\ncp.async.bulk.wait_group 0;"
                         ::"l"(g_tab), "r"(sb + H_B), "n"(TAB_BYTES + 8 * VEC_BYTES) : "memory");
            asm volatile("red.release.gpu.global.add.u32 [%0], 1;" ::"l"(&g_cnt.tab[0]) : "memory");
        }
        __syncwarp();
#pragma unroll 1
        for (int i = wg; i < 20; i += 4) {
            const int r = i / 5, b = i - 5 * r, un = 5 * hs + b, u3 = 20 * r + un;
            auto refill = [&](int e, int u, uint32_t fb) {
                mbar_expect(fb, 40960);
                tma_ld2(sb + e * 40960, &mp.w3h, 64 * (u >> 1), 320 * (u & 1), fb);
                tma_ld2(sb + e * 40960 + 20480, &mp.w3h, 64 * (u >> 1), 320 * (u & 1) + 160, fb);
            };
            if (i > 4 && i < 9) {
                bar_sync(1, 512);
                if (warp == 0) {
                    signal_cnt(&g_cnt.uv[0], lane, 1);
                    if (elect()) {
#pragma unroll 1
                        for (int e = 0; e < 5; e++) refill(e, 5 * hs + e, bars + (5 + e) * 8);
                        l2_prefetch(pp.w2 + (size_t)160 * hs * D_, 160 * D_ * 2);
                    }
                    __syncwarp();
                }
            }
            mbar_wait(bars + i * 8, 0);
            float d[4];
            gemv_tile<7>(d, sb + b * 40960, sb + H_B, 5 * (un & 1));
            const int col = 16 * (warp & 3) + g;
            float* dst = r ? g_cs3 + (un & 1) * 1920 + 64 * ((u3 >> 1) - 10) + col : g_uv + (un & 1) * 3 * D_ + 2 * D_ + 64 * (un >> 1) + col;
            if (t == 3) { dst[0] = d[0]; dst[8] = d[2]; }
            if (r == 0 && t == 2) { dst[-2 * D_] = d[0]; dst[8 - 2 * D_] = d[2]; dst[-D_] = d[1]; dst[8 - D_] = d[3]; }
            if (r == 1 || r == 2) {
                bar_sync(4 + wg, 128);
                if (wt == 0) refill(b, u3, bars + (i + 5) * 8);
            }
        }
        __syncthreads();
        if (warp == 0) signal_cnt(&g_cnt.cs[0], lane, 1);
        if (tid == 511) l2_prefetch(pp.w4 + (size_t)432 * hs * D_, 432 * D_ * 2);
        if (tid == 0 && hs == 3) {
            uint32_t it = 0;
            while (ld_cold(&g_epoch) == e0) { __nanosleep(256); if (++it > (1u << 20)) SPIN_FAIL(48) }
        }
        return;
    }

    if (elect()) {
        if (warp == 15) {
            mbar_init(bars + B_IN * 8, 1); mbar_init(bars + B_IN * 8 + 8, 1);
            asm volatile("fence.mbarrier_init.release.cluster;" ::: "memory");
            mbar_expect(bars + B_IN * 8, 131 * 160);
            tma_ld2(sb + OFF_KIN, &mp.k, 80 * (id & 7), 64 * (id >> 3) - 3, bars + B_IN * 8);
            tma_ld2(sb + OFF_VIN, &mp.v, 80 * (id & 7), 64 * (id >> 3), bars + B_IN * 8);
        } else if (warp < 13) {
            const uint32_t n = (0x1C14111111881ull >> (4 * warp)) & 15;
#pragma unroll
            for (int i = 0; i < 4; i++) mbar_init(bars + warp * 64 + i * 8, n);
            if (warp == 11) { mbar_init(bars + B_XFREE * 8, 16); mbar_init(bars + B_OWN * 8, 8); }
            else if (warp < 11) {
#pragma unroll
                for (int i = 4; i < 8; i++) mbar_init(bars + warp * 64 + i * 8, n);
            }
            asm volatile("fence.mbarrier_init.release.cluster;" ::: "memory");
        }
    }
    asm volatile("" ::"l"(pp.s), "l"(pp.c), "l"(out));
    TR4((threadIdx.x & 31) == 0, warp)
    const int pr = id >> 1;
    const int grp = pr < 4 ? 15 : pr < 36 ? (pr - 4) & 7 : 8 + (pr - 36) % 7;
    const int j = 2 * (pr < 4 ? pr : pr < 36 ? (pr - 4) >> 3 : (pr - 36) / 7) + (id & 1);

    if (wg == 3) {
        TIDS
        const int sw = warp - 12;
        uint32_t ep = ld_cold(&g_epoch);
        TR4(lane == 0, 20 + sw)
        __syncthreads();
        TR4(lane == 0, 30 + sw)
        asm volatile("barrier.cluster.arrive.relaxed.aligned;" ::: "memory");
        if (sw == 0) {
#pragma unroll 1
            for (int n = PF_N0; n < PF_N; n++) {
                wait_clock(c0, PF_T0 + PF_DT * (n - PF_N0));
                if (elect()) {
                    if (n < 8) l2_prefetch((const char*)(n < 4 ? pp.ssm_k : pp.q) + (size_t)id * 20480 + (n & 3) * 5120, 5120);
                    else l2_prefetch((const char*)pp.w_mod + (size_t)id * 38400 + (n - 8) * 4800, 4800);
                }
            }
        } else if (sw == 1) {
            wait_clock(c0, T_SSM);
            if (elect()) {
                mbar_expect(bars + B_SSM * 8, 20480);
                bulk_ld(sb + OFF_SSM, pp.ssm_k + (size_t)5 * id * S_, 20480, bars + B_SSM * 8);
            }
            mbar_spin(bars + B_KVS * 8, 0);
            signal_cnt(&g_cnt.kv[(id & 7) * 32], lane, 1, true);
            TS(lane == 0, 2)
            if (T_Q) wait_clock(c0, T_Q); else mbar_spin(bars + B_RAW * 8, 0);
            if (elect()) {
                mbar_expect(bars + B_QIN * 8, 20480);
                tma_ld3(sb + OFF_QIN, &mp.q, 0, 16 * id, 0, bars + B_QIN * 8);
            }
        } else if (sw == 2) {
            if (elect()) {
#pragma unroll 1
                for (int i = 2; i < (int)(sizeof(Maps) / sizeof(CUtensorMap)); i++) asm volatile("prefetch.tensormap [%0];" ::"l"(&mp.k + i) : "memory");
#pragma unroll 1
                for (int i = B_SUMS; i < B_SIG; i++) mbar_expect(bars + i * 8, i < B_RECV ? 2048 : (i & 3) < 3 ? 8192 : 3072);
            }
            wait_cnt(&g_cnt.kv[(id >> 4) * 32], 16, POLL_NS);
            TS(lane == 0, 4)
            if (elect()) {
                mbar_expect(bars + B_RAW * 8, 12288);
                mbar_expect(bars + B_RAW2 * 8, 8192);
#pragma unroll
                for (int c = 0; c < 5; c++) bulk_ld(sb + OFF_CH + c * CH_BYTES, g_kvT + (size_t)(5 * id + c) * S_, 4096, bars + (c < 3 ? B_RAW : B_RAW2) * 8);
            }
            mbar_spin(bars + B_BK * 8, 0);
            mbar_spin(bars + B_RAW2 * 8, 0);
            if (!T_Q) mbar_spin(bars + B_QIN * 8, 0);
            if (id < 120 && elect()) {
                mbar_expect(bars + B_WM * 8, 40960);
                tma_ld2(sb + OFF_WM, &mp.wmod, 64 * pr, 320 * (id & 1), bars + B_WM * 8);
                tma_ld2(sb + OFF_WM + 20480, &mp.wmod, 64 * pr, 320 * (id & 1) + 160, bars + B_WM * 8);
            }
            TS(lane == 0, 57)
        } else {
            wait_clock(c0, T_KVB);
            if (elect()) {
                mbar_expect(bars + (B_IN + 1) * 8, 131 * 160);
                tma_ld2(sb + OFF_KIN + 10752, &mp.k, 80 * (id & 7), 64 * (id >> 3) + 1021, bars + (B_IN + 1) * 8);
                tma_ld2(sb + OFF_VIN + 10240, &mp.v, 80 * (id & 7), 64 * (id >> 3) + 1024, bars + (B_IN + 1) * 8);
            }
            TS(lane == 0, 53)
            if (lane == 0) sts32(sb + M_EP, ep + 1);
            sts32(sb + M_NUL + lane * 4, 0);
#pragma unroll 1
            for (int m = lane; m < 40; m += 32) {
                const uint4 c = ldg128(pp.c + 320 * (id & 1) + 8 * m);
                uint32_t w[4] = {c.x, c.y, c.z, c.w};
#pragma unroll
                for (int i = 0; i < 4; i++) { const float a = blo(w[i]), b = bhi(w[i]); w[i] = pack2(__fdividef(a, 1.f + __expf(-a)), __fdividef(b, 1.f + __expf(-b))); }
                sts128(sb + OFF_Z + m * 128, w[0], w[1], w[2], w[3]);
#pragma unroll 1
                for (int r = 1; r < 8; r++) sts128(sb + OFF_Z + m * 128 + r * 16, 0, 0, 0, 0);
            }
            fence_async_smem();
        }
        {
            mbar_spin(bars + B_QIN * 8, 0);
            asm volatile("add.u32 %0, %0, 1;" : "+r"(ep));
            TS(wt == 0, 54)
            const int tk = 8 * ((lane >> 1) & 1) + 2 * (lane >> 3) + (lane & 1), ck = 4 * (sw & 1) + ((lane >> 1) & 2);
            const uint32_t src = sb + OFF_QIN + (sw >> 1) * 2048 + tk * 128;
            bf16* dst = g_qT + (size_t)id * 16 * D_ + (32 * sw + 8 * (t & 2) + g) * 16 + 8 * (t & 1);
#pragma unroll
            for (int i = 0; i < 5; i++) {
                uint32_t r[8];
                ldsm4t(src + i * 4096 + ((ck ^ (tk & 7)) << 4), r[0], r[1], r[2], r[3]);
                ldsm4t(src + i * 4096 + (((ck + 1) ^ (tk & 7)) << 4), r[4], r[5], r[6], r[7]);
                stg128(dst + i * 2048, tag(r[0], ep), r[1], r[2], r[3]);
                stg128(dst + i * 2048 + 128, tag(r[4], ep), r[5], r[6], r[7]);
            }
            float s1 = 0.f, s2 = 0.f;
#pragma unroll 2
            for (int i = 0; i < 10; i++) {
                const uint4 w4 = lds128(sb + OFF_QIN + i * 2048 + wt * 16);
                const uint32_t w[4] = {w4.x, w4.y, w4.z, w4.w};
#pragma unroll
                for (int e = 0; e < 4; e++) { const float a = blo(w[e]), b = bhi(w[e]); s1 += a + b; s2 = fmaf(a, a, fmaf(b, b, s2)); }
            }
#pragma unroll
            for (int o = 1; o < 8; o *= 2) { s1 += __shfl_xor_sync(~0u, s1, o); s2 += __shfl_xor_sync(~0u, s2, o); }
            s1 *= 1.f / D_;
            uint32_t rs = pack2(rsqrtf(fmaxf(s2 * (1.f / D_) - s1 * s1, 0.f) + 1e-5f), 0.f);
            if (lane < 8) rs = tag(rs, ep);
            rs = pack2(blo(rs), -s1 * blo(rs));
            const uint32_t sel = lane ? 0x7632 : 0x5410;
            const uint32_t a0 = __shfl_sync(~0u, rs, 0), a1 = __shfl_sync(~0u, rs, 8), a2 = __shfl_sync(~0u, rs, 16), a3 = __shfl_sync(~0u, rs, 24);
            if (lane < 2) stg64(g_qst + lane * S_ + 16 * id + 4 * sw, tag(__byte_perm(a0, a1, sel), ep), __byte_perm(a2, a3, sel));
            TS(wt == 0, 55)
        }
        bar_sync(6, 128);
        if (sw == 3) {
            signal_cnt(&g_cnt.q[(lane & 3) * 32], lane, 4, true);
            TS(lane == 0, 3)
        }
        if (id < 120) {
            mbar_spin(bars + B_WM * 8, 0);
            TS(wt == 0, 56)
            float d[4];
            gemv_tile<8>(d, sb + OFF_WM, sb + OFF_Z, 0);
            const float d2 = __shfl_up_sync(~0u, d[2], 1);
            TS(wt == 0, 7)
            if (t < 2) asm volatile("{\n.reg .b64 v;\nmov.b64 v, {%1, %2};\nst.relaxed.gpu.global.b64 [%0], v;\n}" ::"l"(g_mod + (id & 1) * 6 * D_ + 64 * pr + 16 * sw + g + 8 * t),
                                    "r"(__float_as_uint(t ? d2 : d[0])), "r"(ep) : "memory");
        }
        bar_sync(6, 128);
        asm volatile("setmaxnreg.dec.sync.aligned.u32 32;");
        asm volatile("barrier.cluster.wait.aligned;" ::: "memory");
        if (sw == 2) {
            wait_cnt(&g_cnt.tab[0], 1);
            if (elect()) {
                mbar_expect(bars + B_TAB * 8, TAB_BYTES / 2 + VEC_BYTES);
                bulk_ld(sb + OFF_TAB, g_tab + (j & 1) * (TAB_BYTES / 32), TAB_BYTES / 2, bars + B_TAB * 8);
                bulk_ld(sb + M_GB, g_tab + (TAB_BYTES + j * VEC_BYTES) / 16, VEC_BYTES, bars + B_TAB * 8);
            }
            TS(lane == 0, 5)
            int n = 0;
            auto xslot = [&]() {
                mbar_spin(bars + (B_XEMPTY + (n & 7)) * 8, ((n >> 3) & 1) ^ 1);
                return bars + (B_LAND + (n & 7)) * 8;
            };
#pragma unroll 1
            for (int e = 0; e < 4; e++) {
                const int w = e & 1, tile = grp + 16 * w;
                if (e < 2) wait_cnt(&g_cnt.x[(4 * w + (id & 3)) * 32], 128);
                else wait_cnt(&g_cnt.g1[min(max(tile + min(lane, 2) - 1, 0), 31) * 32], 8);
                TS(lane == 0, 26 + e)
                if (e == 0) mbar_spin(bars + (B_XS + 1) * 8, 0);
#pragma unroll 1
                for (int kb = 0; kb < 10; kb++, n++) {
                    const uint32_t fb = xslot();
                    TR2(lane == 0, 20 + 10 * e + kb)
                    if (elect()) {
                        mbar_expect(fb, 8192);
                        tma_ld2(sb + OFF_XR + (n & 7) * 8192, e < 2 ? &mp.x1_ld : &mp.t_ld, 64 * (e < 2 ? tile : kb), 64 * (e < 2 ? g1_block(kb, j) : tile), fb);
                    }
                }
            }
#pragma unroll 1
            for (int i = 0; i < 20; i++, n++) {
                const int w = i < XLEAD ? 0 : i >= 20 - XLEAD ? 1 : ((i - XLEAD) & 1) ^ 1;
                const int kb = i < XLEAD ? i : i >= 20 - XLEAD ? i - 10 : w ? (i - XLEAD) >> 1 : (i + XLEAD) >> 1;
                if (kb == 0) { wait_cnt(&g_cnt.g2[(grp + 16 * w) * 32], 8); TS(lane == 0, 30 + w) }
                xslot();
                if (elect()) {
                    const uint32_t fb = bars + (B_XFULL + 8 * w + ((20 + kb) & 7)) * 8;
                    mbar_expect(fb, 8192);
                    bulk_ld(sb + OFF_XR + (n & 7) * 8192, &g_x2f[((grp + 16 * w) * 10 + kb) * 512], 8192, fb);
                }
            }
            mbar_spin(bars + B_VEC3 * 8, 0);
            unsigned old = 0;
            if (lane == 0) old = atomicAdd(&g_cnt.done[0], 1u);
            if (__shfl_sync(~0u, old, 0) == 127) {
#pragma unroll 1
                for (int i = lane; i < (int)(sizeof(Counters) / 128); i += 32) reinterpret_cast<unsigned*>(&g_cnt)[i * 32] = 0;
                if (lane == 0) atomicAdd(&g_epoch, 1u);
            }
        } else if (sw == 0) {
            wait_cnt(&g_cnt.wr[0], 4);
            mbar_spin(bars + B_QRDY * 8, 0);
            const uint32_t wf = bars + B_WFULL * 8, we = bars + B_WEMPTY * 8;
#pragma unroll 1
            for (int n = 0; n < 5; n++) {
                if (n == 3) mbar_spin(bars + (B_XS + 1) * 8, 0);
                TR2(lane == 0, 70 + n)
                if (elect()) {
                    const uint32_t fb = wf + n * 8, dst = sb + OFF_W + n * 16384;
                    mbar_expect(fb, 20480);
#pragma unroll 1
                    for (int h = 0; h < 2; h++) {
                        const int kb = g1_block(2 * n + h, j);
                        tma_ld2(dst + h * 8192, &mp.w1, 64 * j, 64 * kb, fb);
                        bulk_ld(sb + OFF_REM + n * 4096 + h * 2048, &g_wr[(j * 10 + kb) * 128], 2048, fb);
                    }
                }
            }
            mbar_spin(bars + B_GATE * 8, 0);
#pragma unroll 1
            for (int i = -3; i < 5; i++) {
                const int n = i < 0 ? 8 + i : 5 + i;
                const uint32_t fb = wf + (n & 7) * 8;
                if (i >= 0) mbar_spin(we + i * 8, 0);
                TR2(lane == 0 && i >= 0, 70 + n)
                if (elect()) {
                    if (i < 0 || i >= 3) { mbar_expect(fb, 20480); tma_ld5(sb + OFF_W + (n & 7) * 16384, n < 9 ? &mp.w2a : &mp.w2b, 64 * j, n < 9 ? 4 * (n - 5) : 0, fb); }
                    if (i >= 0) bulk_ld(sb + OFF_REM + i * 4096, &g_wr[((8 + j) * 10 + 2 * i) * 128], 4096, fb);
                }
            }
            mbar_spin(bars + (B_GATE + 1) * 8, 0);
#pragma unroll 1
            for (int n = 10; n < 30; n++) {
                if (n == W3_N2) mbar_spin(bars + (B_GATE + 2) * 8, 0);
                mbar_spin(we + (n & 7) * 8, ((n >> 3) & 1) ^ 1);
                TR2(lane == 0, 70 + n)
                if (elect()) {
                    const uint32_t dst = sb + OFF_W + (n & 7) * 16384, fb = wf + (n & 7) * 8;
                    mbar_expect(fb, 13824);
                    tma_ld3(dst, &mp.w3a, 0, 32 * (n - 10), 3 * j, fb);
                    tma_ld2(dst + 12288, &mp.w3b, 1536 + 24 * j, 32 * (n - 10), fb);
                }
            }
            mbar_spin(we + 6 * 8, 0);
            if (elect()) mbar_arrive(bars + B_S30 * 8);
#pragma unroll 1
            for (int n = 31; n < 50; n++) {
                const int rem = 96 + 3 * (j >> 1);
                int m0, m1, r0, r1, c0_, c1_;
                if (n < 38) {
                    c0_ = g4_block(0, j); c1_ = g4_block(1, j);
                    m0 = m1 = n == 35;
                    r0 = r1 = n == 35 ? rem : 6 * (j ^ (n >= 34)) + ((0x2004204 >> (4 * (n - 31))) & 15);
                } else {
                    const int e = (n - 38) & 3;
                    c0_ = c1_ = g4_block(2 + ((n - 38) >> 2), j);
                    m0 = 0; m1 = e == 1 ? 1 : e == 3 ? -1 : 0;
                    r0 = 6 * (j ^ (e >> 1)) + 4 * (e & 1); r1 = e == 1 ? rem : r0 + 2;
                }
                mbar_spin(we + (n & 7) * 8, ((n >> 3) & 1) ^ 1);
                if (elect()) {
                    const uint32_t dst = sb + OFF_W + (n & 7) * 16384, fb = wf + (n & 7) * 8;
                    mbar_expect(fb, m1 < 0 ? 8192 : 16384 - 2048 * (m0 + m1));
                    tma_ld2(dst, &mp.w4[m0], 64 * c0_, r0 * (32 >> m0), fb);
                    if (m1 >= 0) tma_ld2(dst + 8192, &mp.w4[m1], 64 * c1_, r1 * (32 >> m1), fb);
                }
            }
#pragma unroll 1
            for (int w = 0; w < 2; w++) {
                const uint4* src = g_part + (size_t)(grp + 16 * w) * 40960;
                mbar_spin(bars + (B_RING + w) * 8, 1);
                if (elect()) {
                    const uint32_t fb = bars + (B_IN + w) * 8, rem = sb + OFF_OUT + w * 10240;
                    mbar_expect(fb, 10240);
                    bulk_ld(rem + 8192, &g_x1f[((grp + 16 * w) * 8 + j) * 640 + 512], 2048, fb);
#pragma unroll 1
                    for (int i = 0; i < 4; i++) bulk_ld(rem + i * 2048, src + ((j >> 2) + 2 * i) * 5120 + 4096 + j * 128, 2048, fb);
                }
            }
        } else {
            const int w = sw >> 1;
#pragma unroll 1
            for (int e = 0; e < 3; e++) {
                mbar_spin(bars + ((e ? B_SIG : B_XS) + w) * 8, e >> 1);
                signal_cnt(e == 0 ? &g_cnt.x[(4 * w + (lane & 3)) * 32] : e == 1 ? &g_cnt.g1[(grp + 16 * w) * 32] : &g_cnt.g2[(grp + 16 * w) * 32], lane, e ? 1 : 4, !(X_FENCE & (1 << e)));
                TS(lane == 0, 20 + 2 * e + w)
                if (e == 0 && w) {
                    wait_cnt(&g_cnt.uv[0], 4);
#pragma unroll 1
                    for (int c = lane; c < 80; c += 32) {
                        const float* src = g_uv + (c < 64 ? 64 * j + c : 448 + 16 * j + c);
                        const uint32_t u = split2(ldcg32f(src) + ldcg32f(src + 3 * D_)), v = split2(ldcg32f(src + D_) + ldcg32f(src + 4 * D_));
                        const uint32_t s = split2(ldcg32f(src + 2 * D_) + ldcg32f(src + 5 * D_));
                        sts128(sb + OFF_F1 + c * 16, u, __byte_perm(u, v, 0x5410), __byte_perm(v, 0, 0x1032), s);
                        sts128(sb + M_F1 + c * 16, s & 0xffffu, 0, 0, 0);
                    }
                    fence_async_smem();
                    warp_arrive(bars + B_VEC * 8);
                    TS(lane == 0, 9)
                }
            }
        }
        return;
    }

    {
        uint32_t ep;
        {
            TIDS
            ep = ld_cold(&g_epoch);
            const int cp = (tid + 16) % 40, cp1 = tid % 40;
            const uint4 sh0 = ldg128(pp.shift_k + (80 * (id & 7) + 2 * cp1) * 4), sh1 = ldg128(pp.shift_k + (80 * (id & 7) + 2 * cp) * 4);
            uint32_t dd;
            asm volatile("ld.global.nc.u16 %0, [%1];" : "=r"(dd) : "l"(pp.ssm_D + 5 * id + min(wg + 3 * lane, 4)));
            TR4(lane == 0, 40 + warp)
            __syncthreads();
            asm volatile("barrier.cluster.arrive.relaxed.aligned;" ::: "memory");
            asm volatile("add.u32 %0, %0, 1;" : "+r"(ep));
#pragma unroll 1
            for (int hw = 0; hw < 2; hw++) {
                if ((unsigned)(warp - 2 * hw) >= 10) continue;
                const int u = tid - 64 * hw;
                const int c = hw ? cp : cp1, oc = u / 40, line = 31 - 16 * hw - (id >> 3);
                const uint4 sh = hw ? sh1 : sh0;
                const uint32_t st = sb + OFF_ST + hw * 10240, sta = st + c * 256 + ((((6 - 2 * (oc & 3)) ^ (oc >> 2) ^ (line & 1)) ^ (c & 7)) << 4), in = oc * 1280 + c * 4;
                const uint32_t f0 = __byte_perm(sh.x, sh.z, 0x5410), f1 = __byte_perm(sh.x, sh.z, 0x7632), f2 = __byte_perm(sh.y, sh.w, 0x5410), f3 = __byte_perm(sh.y, sh.w, 0x7632);
                uint32_t kk[11], vv[8];
                mbar_spin(bars + (B_IN + hw) * 8, 0);
                TS(tid == 64, 18 + 42 * hw)
#pragma unroll
                for (int i = 0; i < 11; i++) kk[i] = lds32(sb + OFF_KIN + hw * 10752 + in + i * 160);
#pragma unroll
                for (int i = 0; i < 8; i++) vv[i] = lds32(sb + OFF_VIN + hw * 10240 + in + i * 160);
#pragma unroll
                for (int i = 0; i < 8; i++) vv[i] = mul2(fma2(kk[i + 3], f0, fma2(kk[i + 2], f1, fma2(kk[i + 1], f2, mul2(kk[i], f3)))), vv[i]);
                sts128(sta, tag(__byte_perm(vv[0], vv[1], 0x5410), ep), __byte_perm(vv[2], vv[3], 0x5410), __byte_perm(vv[4], vv[5], 0x5410), __byte_perm(vv[6], vv[7], 0x5410));
                sts128(sta + 128, tag(__byte_perm(vv[0], vv[1], 0x7632), ep), __byte_perm(vv[2], vv[3], 0x7632), __byte_perm(vv[4], vv[5], 0x7632), __byte_perm(vv[6], vv[7], 0x7632));
                bar_sync(7 + hw, 320);
                flush_tile(st, g_kvT + (size_t)(80 * (id & 7)) * S_ + 64 * line, u);
                TS(tid == 64 && hw, 1)
            }
            warp_arrive(bars + B_KVS * 8);
            if (tid < 320) sts128(sb + OFF_CH + (tid >> 6) * CH_BYTES + 4096 + (tid & 63) * 16, 0, 0, 0, 0);
            mbar_spin(bars + B_SSM * 8, 0);
            TS(tid == 0, 14)
            uint2 w[7];
            uint32_t pv[7];
#pragma unroll
            for (int i = 0; i < 7; i++) {
                const uint32_t a = sb + OFF_SSM + min(wg + 3 * i, 19) * 1024 + wt * 8;
                w[i] = lds64(a); pv[i] = lds32(a - 4);
            }
#pragma unroll
            for (int i = 0; i < 7; i++) {
                const int un = min(wg + 3 * i, 19);
                sts128(sb + OFF_CH + (un >> 2) * CH_BYTES + OFF_P + (un & 3) * 2048 + wt * 16, __byte_perm(w[i].x, pv[i], 0x7610), __byte_perm(w[i].x, 0, 0x1032), __byte_perm(w[i].y, w[i].x, 0x7610), __byte_perm(w[i].y, 0, 0x1032));
            }
            __syncwarp();
            if (wt < 2 - (wg >> 1)) {
                const uint32_t h = lds32(sb + OFF_SSM + (wg + 3 * wt) * 4096), h0 = pack2(blo(h) + blo(dd), 0.f);
                sts64f(sb + OFF_CH + (wg + 3 * wt) * CH_BYTES + OFF_P, __uint_as_float(h0), __uint_as_float(__byte_perm(h, h0, 0x5432)));
            }
            fence_async_smem();
            warp_arrive(bars + B_BK * 8);
            asm volatile("barrier.cluster.wait.aligned;" ::: "memory");
            mbar_spin(bars + B_BK * 8, 0);
            TS(tid == 0, 15)
        }

#pragma unroll 1
        for (int c = wg; c < 5; c += 3) {
            const uint32_t kvb = sb + OFF_CH + c * CH_BYTES;
            mbar_spin(bars + (c < 3 ? B_RAW : B_RAW2) * 8, 0);
            if (CH2_DELAY && wg == 2) wait_clock(clock64(), CH2_DELAY);
            for (uint32_t it = 0;;) {
                const int wt = tid_now() & 127;
                if (!bar_any(1 + wg, ((lds32(kvb + wt * 16) ^ ep) | (lds32(kvb + 2048 + wt * 16) ^ ep)) & 1)) break;
                if (wt == 0) { mbar_expect(bars + (B_RETRY + wg) * 8, 4096); bulk_ld(kvb, g_kvT + (size_t)(5 * id + c) * S_, 4096, bars + (B_RETRY + wg) * 8); }
                mbar_spin(bars + (B_RETRY + wg) * 8, ep >> 31);
                ep ^= 0x80000000u;
                STALE(0)
                SPIN_CHECK(57)
            }
            TS(threadIdx.x == 0, c ? 13 : 11)
            float acc[64];
            {
                const int l = tid_now() & 31;
                conv_channel(acc, kvb + OFF_P + (8 * (warp & 3) + (l >> 2) - 2 * (l & 3)) * 4, (((uint64_t)0xC0000010u << 32) | ((kvb & 0x3FFFF) >> 4) | 0x10000u) + pp.nil);
            }
            TS(threadIdx.x == 0, c ? 16 : 12)
            if (c >= 3) {
#pragma unroll 1
                for (int e = 0; e < 3; e++) mbar_spin(bars + (B_RING + e) * 8, 0);
            }
            TIDS
            const int e = 127 - 8 * (lane >> 4) - (lane & 7), u0 = (warp & 3) + 8 * (e >> 2) + (e & 3) + 4 * ((lane >> 3) & 1);
            const uint32_t ring = sb + OFF_RING + c * 16384 + (warp & 3) * 4096, wa = ring + (u0 ^ ((u0 >> 1) & 4)) * 16;
            if (lane < (warp & 3)) sts128(ring + lane * 16, 0, 0, 0, 0);
#pragma unroll
            for (int i = 0; i < 8; i++)
                stsm4t(i == 0 && u0 >= 256 ? sb + M_SINK : wa - 512 * i, pack2(acc[8 * i], acc[8 * i + 1]), pack2(acc[8 * i + 2], acc[8 * i + 3]),
                       pack2(acc[8 * i + 4], acc[8 * i + 5]), pack2(acc[8 * i + 6], acc[8 * i + 7]));
            warp_arrive(bars + (B_RING + c) * 8);
        }
        fence_async_smem();
        TIDS
        if (warp == 8) {
            wait_cnt(&g_cnt.q[(id & 3) * 32], 128);
            if (elect()) {
                mbar_expect(bars + B_QRDY * 8, 28672);
                tma_ld2(sb + OFF_QT, &mp.qT, 80 * id, 0, bars + B_QRDY * 8);
                bulk_ld(sb + OFF_QT + 20480, g_qst, 8192, bars + B_QRDY * 8);
            }
            TS(lane == 0, 8)
        } else if (warp == 9) {
            const int v = min(lane / 5, 3);
            const uint2* gm = g_mod + (v + (v == 3)) * D_ + 5 * id + lane % 5;
            const unsigned epoch = lds32(sb + M_EP);
            uint2 r0, r1;
            unsigned it = 0;
            do {
                r0 = ld_mod(gm); r1 = ld_mod(gm + 6 * D_);
                SPIN_CHECK(55)
            } while (!__all_sync(~0u, r0.y == epoch && r1.y == epoch));
            const float m0 = __uint_as_float(r0.x), m1 = __uint_as_float(r1.x);
            const float m = rbf(m0 + m1), p = rbf(1.f + m);
            const float cz = zscale(__shfl_sync(~0u, p, 15 + lane % 5)), ga = __shfl_sync(~0u, m, 10 + lane % 5);
            if (lane < 15) sts32(sb + M_AB + lane % 5 * 16 + v * 4, lane < 10 ? __float_as_uint(cz * ga * (lane < 5 ? m : p)) : pack2(cz, cz));
            warp_arrive(bars + B_MODR * 8);
            TS(lane == 0, 6)
        }
        mbar_spin(bars + B_QRDY * 8, 0);
        mbar_spin(bars + B_MODR * 8, 0);
#pragma unroll 1
        for (int hf = 0; hf < 2; hf++) {
            const int u = wt + 128 * hf;
            uint4 rs = lds128(sb + OFF_QT + 20480 + u * 16), nm = lds128(sb + OFF_QT + 24576 + u * 16);
            uint32_t it = 0;
            while (__any_sync(~0u, ((rs.x ^ ep) | (rs.z ^ ep) | (nm.x ^ ep) | (nm.z ^ ep)) & 1)) {
                rs = ld_part(g_qst + 8 * u); nm = ld_part(g_qst + S_ + 8 * u);
                STALE(1)
                SPIN_CHECK(53)
            }
            const int c1 = wg == 2 ? 2 + !EPI_SPLIT : 5;
#pragma unroll 1
            for (int c = wg == 2 ? 0 : EPI_SPLIT && wg == hf ? 2 : 3 + wg; c < c1; c += wg == 2 ? 1 : c == 2 ? 1 + wg : 2) {
                uint4 q = lds128(sb + OFF_QT + (u >> 1) * 160 + c * 32 + (u & 1) * 16);
                const float4 ab = lds128f(sb + M_AB + c * 16);
                mbar_spin(bars + (B_RING + c) * 8, 0);
                const uint32_t ra = sb + OFF_RING + c * 16384 + (u ^ ((u >> 1) & 4)) * 16;
                const uint4 p0 = lds128(ra), p1 = lds128(ra + 4096), p2 = lds128(ra + 8192), p3 = lds128(ra + 12288);
                while (__any_sync(~0u, (q.x ^ ep) & 1)) {
                    q = ld_part(g_qT + ((u >> 1) * D_ + 5 * id + c) * 16 + 8 * (u & 1));
                    STALE(2)
                    SPIN_CHECK(52)
                }
                uint32_t gq[4] = {q.x, q.y, q.z, q.w}, gg[4] = {fma2(q.x, rs.x, nm.x), fma2(q.y, rs.y, nm.y), fma2(q.z, rs.z, nm.z), fma2(q.w, rs.w, nm.w)};
#pragma unroll
                for (int i = 0; i < 4; i++) {
                    gg[i] = pack2(fmaf(blo(gg[i]), ab.y, ab.x), fmaf(bhi(gg[i]), ab.y, ab.x));
                    gq[i] = mul2(gq[i], __float_as_uint(ab.z));
                }
                stg128_tag(g_x1T + (size_t)(5 * id + c) * S_ + 8 * u,
                           fma2(gg[0], add2(add2(p0.x, p1.x), add2(p2.x, p3.x)), gq[0]), fma2(gg[1], add2(add2(p0.y, p1.y), add2(p2.y, p3.y)), gq[1]),
                           fma2(gg[2], add2(add2(p0.z, p1.z), add2(p2.z, p3.z)), gq[2]), fma2(gg[3], add2(add2(p0.w, p1.w), add2(p2.w, p3.w)), gq[3]), ep, ((5 * id + c) >> 3) & 3);
            }
            warp_arrive(bars + (B_XS + hf) * 8);
            TS(tid == 0, hf ? 17 : 58)
            TS(tid == 256 && hf, 52)
        }
    }

    const uint32_t nil = pp.nil;
    const int wq = warp & 3;
    if (wg == 2) {
        TIDS
        asm volatile("setmaxnreg.dec.sync.aligned.u32 32;");
        {
            const uint32_t ep = lds32(sb + M_EP);
            uint32_t ph = 0;
#pragma unroll 1
            for (int n = wq; n < 40; n += 4) {
                const int e = n / 10, kb = n - 10 * e, tile = grp + 16 * (e & 1);
                const uint32_t a = sb + OFF_XR + (n & 7) * 8192;
                const uint32_t ta = a + (e < 2 ? lane * 128 + ((lane & 7) << 4) + (lane >> 3) * 4
                                               : (lane & 15) * 128 + (((lane >> 4 << 1) ^ (lane & 7)) << 4) + (lane & 8) + (lane >> 4) * 4);
                const uint32_t tb = e < 2 ? ta ^ 32 : ta + 2048;
                mbar_spin(bars + (B_LAND + (n & 7)) * 8, (n >> 3) & 1);
                while (true) {
                    uint32_t w[8];
#pragma unroll
                    for (int i = 0; i < 8; i++) w[i] = lds32((((i & 1) ? tb : ta) ^ ((i & 2) * 32)) + (i >> 2) * 4096);
                    if (!__any_sync(~0u, (lop3<0x7E>(w[0], ep, w[1]) | lop3<0x7E>(w[2], ep, w[3]) | lop3<0x7E>(w[4], ep, w[5]) | lop3<0x7E>(w[6], ep, w[7])) & 1)) break;
                    if (elect()) {
                        mbar_expect(bars + (B_AGAIN + wq) * 8, 8192);
                        tma_ld2(a, e < 2 ? &mp.x1_ld : &mp.t_ld, 64 * (e < 2 ? tile : kb), 64 * (e < 2 ? g1_block(kb, j) : tile), bars + (B_AGAIN + wq) * 8);
                    }
                    mbar_spin(bars + (B_AGAIN + wq) * 8, ph);
                    ph ^= 1;
                    STALE1(1 + (e >> 1))
                }
                if (elect()) {
                    mbar_arrive(bars + (B_XFULL + 8 * (e & 1) + ((5 * (e & 2) + kb) & 7)) * 8);
                    if (n == GATE_W2 || n == GATE_W3 || n == GATE_W3B) mbar_arrive(bars + (B_GATE + (n >= GATE_W3) + (n >= GATE_W3B)) * 8);
                }
            }
        }
        {
            wait_cnt(&g_cnt.cs[0], 4);
            uint32_t s[2];
#pragma unroll
            for (int i = 0; i < 2; i++) {
                const int c = min(wt + 128 * i, 215);
                const float* src = g_cs3 + (c < 192 ? 192 * j + c : 1344 + 24 * j + c);
                s[i] = split2(ldcg32f(src) + ldcg32f(src + 1920));
            }
            asm volatile("" : "+r"(s[0]), "+r"(s[1]));
            bar_sync(3, 128);
            if (wt == 0) mbar_arrive(bars + B_VEC3 * 8);
            TS(wt == 0, 19)
            mbar_wait(bars + B_S30 * 8, 0);
#pragma unroll
            for (int i = 0; i < 2; i++) sts128(sb + OFF_W + 6 * 16384 + min(wt + 128 * i, 215) * 16, s[i], s[i] & 0xffffu, 0, 0);
            fence_async_smem();
            bar_sync(3, 128);
            if (wt == 0) mbar_arrive(bars + (B_WFULL + 6) * 8);
        }
#pragma unroll 1
        for (int uw = 0; uw < 2; uw++) {
            const int tile = grp + 16 * uw;
            const uint32_t ep = lds32(sb + M_EP), in = sb + OFF_OUT + uw * 10240 + wt * 16, sr = in - lane * 16;
            mbar_wait(bars + (B_IN + uw) * 8, 1);
            float r[8];
#pragma unroll
            for (int h = 0; h < 2; h++) {
                uint4 a = lds128(in + h * 4096), b = lds128(in + h * 4096 + 2048);
                uint32_t it = 0;
                while (__any_sync(~0u, ((a.x ^ ep) | (b.x ^ ep)) & 1)) {
                    const uint4* p = g_part + (size_t)tile * 40960 + ((j >> 2) + 4 * h) * 5120 + 4096 + j * 128 + wt;
                    a = ld_part(p); b = ld_part(p + 10240);
                    STALE(3)
                    if (++it > SPIN_LIMIT) SPIN_FAIL(58)
                }
                if (h) add8(r, add2(a, b)); else unpack8(r, add2(a, b));
            }
            base16(r, lds128(in + 8192), lds64f(sb + M_GB + (64 + 2 * t) * 4), lds64f(sb + M_GB + (72 + 2 * t) * 4));
            __syncwarp();
            stsm4(sr + (lane & 15) * 32 + (((lane >> 4) ^ ((lane >> 2) & 1)) << 4), pack2(r[0], r[1]), pack2(r[2], r[3]), pack2(r[4], r[5]), pack2(r[6], r[7]));
            __syncwarp();
            stg128(out + (size_t)(64 * tile + 16 * wq + (lane >> 1)) * D_ + 512 + 16 * j + 8 * (lane & 1), lds128(sr + (lane >> 1) * 32 + (((lane & 1) ^ ((lane >> 3) & 1)) << 4)));
            __syncwarp();
        }
        if (wq == 0) {
            uint32_t it = 0;
            while (!mbar_try(bars + B_OWN * 8, 0)) { if (++it > SPIN_LIMIT) SPIN_FAIL(56) }
        }
        return;
    }

    TIDS
    const int uw = wg, tile = grp + 16 * uw, row0 = 64 * tile + 16 * wq;
    const bool leader = wt == 0; (void)leader;
    const uint32_t xfull = bars + (B_XFULL + 8 * uw) * 8, xempty = bars + B_XEMPTY * 8, wfull = bars + B_WFULL * 8, wempty = bars + B_WEMPTY * 8;
    const uint64_t dz = mkdesc(0) + pp.nil;
    auto xwait = [&](uint32_t n) { mbar_spin(xfull + (n & 7) * 8, (n >> 3) & 1); };
    asm volatile("setmaxnreg.inc.sync.aligned.u32 224;");
    const uint32_t ep = lds32(sb + M_EP);
    {
        float acc[40];
        uint4* const own = &g_x1f[(tile * 8 + j) * 640 + wt];
        const uint32_t la = ((lane & 7) + 8 * (lane >> 4)) * 128 + (((2 * wq + ((lane >> 3) & 1)) ^ (lane & 7)) << 4);
        auto slot = [&](uint32_t m) { return sb + OFF_XR + (m & 7) * 8192; };
        auto grab = [&](uint32_t m) {
            uint32_t r0, r1, r2, r3;
            ldsm4t(slot(m) + la + (j & 3) * 2048, r0, r1, r2, r3);
            stg128(own + 512, r0, r1, r2, r3);
        };
        float al[2], r1[2], n1[2];
        {
            float sl[4], sq[4], v[4];
            uint32_t z0[16], z1[16], zz[16];
            uint64_t bd = dz + b80_desc(dsb, 0, 0, 0), tb = (((uint64_t)8 << 32) | ((dsb + OFF_TAB) >> 4) | (7u << 16)) + pp.nil;
            auto ldfrag = [&](uint32_t (&z)[16], int n) {
#pragma unroll
                for (int q = 0; q < 4; q++) ldsm4t(slot(2 * uw + n) + la + q * 2048, z[4 * q], z[4 * q + 1], z[4 * q + 2], z[4 * q + 3]);
            };
            auto tile1 = [&](const uint32_t (&zc)[16], uint32_t (&zn)[16], int n, int h) {
                const bool last = h && n == 5, ok = mbar_test(xfull + (n + 1) * 8, 0), okw = !h || mbar_test(wfull + ((n + 1) >> 1) * 8, 0);
                const int kb = g1_block(n, j);
                wg_fence();
#pragma unroll
                for (int q = 0; q < 2; q++) wgmma_rs80(acc, zc[4 * q], zc[4 * q + 1], zc[4 * q + 2], zc[4 * q + 3], bd + q * B80_STEP, 1);
                wg_commit();
                wg_wait<1>();
                if (!ok) xwait(n + 1);
                if (!last) ldfrag(zn, n + 1);
#pragma unroll
                for (int e = 0; e < 16; e++) zz[e] = mul2(zc[e], zc[e]);
                const uint64_t t0 = last ? ((uint64_t)8 << 32) | ((dsb + M_NUL) >> 4) : tb;
                const uint32_t ts = last ? 0 : 14;
                wg_fence();
#pragma unroll
                for (int q = 0; q < 4; q++) wgmma_rs8(sl, zc[4 * q], zc[4 * q + 1], zc[4 * q + 2], zc[4 * q + 3], t0 + q * ts, 1);
#pragma unroll
                for (int q = 0; q < 4; q++) wgmma_rs8(sq, zz[4 * q], zz[4 * q + 1], zz[4 * q + 2], zz[4 * q + 3], t0 + q * ts, 1);
#pragma unroll
                for (int q = 2; q < 4; q++) wgmma_rs80(acc, zc[4 * q], zc[4 * q + 1], zc[4 * q + 2], zc[4 * q + 3], bd + q * B80_STEP, 1);
                wg_commit();
                if (kb == j) {
#pragma unroll
                    for (int q = 0; q < 4; q++) stg128(own + q * 128, zc[4 * q], zc[4 * q + 1], zc[4 * q + 2], zc[4 * q + 3]);
                }
                if (!h && kb == 8 + (j >> 2)) grab(2 * uw + n);
                if (lane < 2) mbar_arrive(xempty + ((2 * uw + n) & 7) * 8);
                if (!h && n && lane == 0) mbar_arrive(wempty + ((n >> 1) - 1) * 8);
                tb += 56;
                bd = bd + (uint64_t)B80_HALF;
                if (!okw) mbar_spin(wfull + ((n + 1) >> 1) * 8, 0);
                TR(leader, 100 + 10 * uw + n)
            };
            zero(acc); zero(sl); zero(sq);
            mbar_spin(bars + B_TAB * 8, 0);
            mbar_spin(wfull, 0);
            xwait(0);
            TS(leader, 32 + uw)
            ldfrag(z0, 0);
#pragma unroll 1
            for (int n = 0; n < 6; n += 2) { tile1(z0, z1, n, 0); tile1(z1, z0, n + 1, 1); }
#pragma unroll
            for (int n = 6; n < 10; n++) {
                const uint64_t ad = dz + (((dsb + OFF_XR + ((2 * uw + n) & 7) * 8192) >> 4) | 0x10000u);
                const bool ok = n == 9 || mbar_test(xfull + ((n + 1) & 7) * 8, (n + 1) >> 3), okw = n != 7 || mbar_test(wfull + 4 * 8, 0);
                wg_fence();
#pragma unroll
                for (int q = 0; q < 4; q++) wgmma_ss80t(acc, ad + q * 128, bd + q * B80_STEP, 1);
                wg_commit();
                bd = bd + (uint64_t)B80_HALF;
                if (n == 9 && 9 - (j & 1) == 8 + (j >> 2)) grab(2 * uw + 9);
                wg_wait<1>();
                if (n > 6 && lane < 2) mbar_arrive(xempty + ((2 * uw + n - 1) & 7) * 8);
                if (!(n & 1) && lane == 0) mbar_arrive(wempty + ((n >> 1) - 1) * 8);
                if (n == 6) {
                    reg_fence(sl); reg_fence(sq);
#pragma unroll
                    for (int e = 0; e < 2; e++) {
                        v[2 * e] = t == 0 ? sl[2 * e] + sl[2 * e + 1] : t == 1 ? sq[2 * e] + sq[2 * e + 1] : sl[2 * e];
                        v[2 * e + 1] = t == 2 ? sl[2 * e + 1] : sq[2 * e];
                    }
                    st_peer(peer_addr(sb + OFF_ROW + uw * 2048 + wt * 16), __float_as_uint(v[0]), __float_as_uint(v[1]), __float_as_uint(v[2]), __float_as_uint(v[3]), peer_addr(bars + (B_SUMS + uw) * 8));
                    TS(leader && !uw, 59)
                }
                if (!ok) xwait(n + 1);
                if (!okw) mbar_spin(wfull + 4 * 8, 0);
                TR(leader, 100 + 10 * uw + n)
            }
            float4 k = lds128f(sb + M_KS);
            float k4 = __uint_as_float(lds32(sb + M_KS + 16));
#pragma unroll
            for (int w = 1; w < 5; w++) {
                const float4 o = lds128f(sb + M_KS + w * 32);
                k.x += o.x; k.y += o.y; k.z += o.z; k.w += o.w; k4 += __uint_as_float(lds32(sb + M_KS + w * 32 + 16));
            }
            mbar_spin(bars + (B_SUMS + uw) * 8, 0);
            TS(leader && !uw, 10)
            const float4 o = lds128f(sb + OFF_ROW + uw * 2048 + wt * 16);
            v[0] += o.x; v[1] += o.y; v[2] += o.z; v[3] += o.w;
            uint32_t fa[4];
#pragma unroll
            for (int h = 0; h < 2; h++) {
                const int l0 = lane & ~3;
                const float s1 = __shfl_sync(~0u, v[2 * h], l0), s2 = __shfl_sync(~0u, v[2 * h], l0 + 1), scc = __shfl_sync(~0u, v[2 * h], l0 + 2);
                const float scs = __shfl_sync(~0u, v[2 * h + 1], l0 + 2), sc = __shfl_sync(~0u, v[2 * h], l0 + 3), sqq = __shfl_sync(~0u, v[2 * h + 1], l0 + 3);
                const float m1 = s1 * (1.f / D_), va = fmaxf(s2 * (1.f / D_) - m1 * m1, 0.f) + 1e-5f, r = rsqrtf(va);
                const float m2 = (r * (sc - m1 * k.x) + k.y) * (1.f / D_);
                const float e2 = (r * (r * (sqq + m1 * (m1 * k.z - 2.f * scc)) + 2.f * (scs - m1 * k.w)) + k4) * (1.f / D_);
                al[h] = r * 0.5f * rsqrtf(fmaxf(e2 - m2 * m2, 0.f) + 1e-5f); r1[h] = r; n1[h] = -m1 * r;
                const uint32_t fb = split2(va * r), fx = split2(t == 3 ? -m2 * va * r : -m1), fc = __shfl_sync(~0u, fx, lane | 3);
                fa[h] = __byte_perm(fx, fb, t == 1 ? 0x5432 : t == 2 ? 0x7654 : 0x1010);
                fa[2 + h] = t ? 0 : fc >> 16;
            }
            mbar_spin(bars + B_VEC * 8, 0);
            wg_fence();
            wgmma_rs80k(acc, fa[0], fa[1], fa[2], fa[3], ((uint64_t)8 << 32) | ((dsb + OFF_F1) >> 4) | (((M_F1 - OFF_F1) >> 4) << 16), 1);
            wg_commit();
        }
        wg_wait<0>();
        reg_fence(acc);
        if (lane < 2) mbar_arrive(xempty + ((2 * uw + 9) & 7) * 8);
        if (lane == 0) mbar_arrive(wempty + 4 * 8);
        TS(leader, 34 + uw)
        {
            bf16* const trow = g_t + (size_t)(row0 + g + 2) * D_;
#pragma unroll
            for (int b = 0; b < 3; b++) {
                uint32_t p[8];
#pragma unroll
                for (int ii = 0; ii < 4; ii++) {
                    const int i = 4 * b + ii;
                    if (i >= 10) continue;
#pragma unroll
                    for (int h = 0; h < 2; h++) p[(i & 3) + 4 * h] = pack2(gelu2(acc[4 * i + 2 * h] * al[h]), gelu2(acc[4 * i + 2 * h + 1] * al[h]));
                }
                if (b < 2) {
                    const int gr = (2 * j + b) / 5, sh = (gr & 1) ? -1 - (gr >> 1) : 1 + (gr >> 1);
                    bf16* dst = trow + 64 * j + 32 * b + 8 * t;
                    const int w = (((g + sh) >> 2) & 2) + (t >> 1);
                    stg128_tag(dst + sh * D_, p[0], p[1], p[2], p[3], ep, w);
                    stg128_tag(dst + (sh + 8) * D_, p[4], p[5], p[6], p[7], ep, w ^ 2);
                    if (row0 + g < sh || row0 + g + 8 >= S_ + sh) stg128_tag(dst + (sh > 0 ? 0 : 8) * D_, 0, 0, 0, 0, ep, (sh > 0 ? 0 : 2) + (t >> 1));
                } else {
                    bf16* dst = trow + 512 + 16 * j + 4 * t;
                    const uint32_t lo = t == (g < 2), hi = t == (g >= 2), o = j & 1;
                    stg64(dst - 2 * D_, lop3<0xB8>(p[0], lo & ~o, ep), lop3<0xB8>(p[1], lo & o, ep));
                    stg64(dst + 6 * D_, lop3<0xB8>(p[4], hi & ~o, ep), lop3<0xB8>(p[5], hi & o, ep));
                    if (row0 + g + 8 >= S_ - 2) stg64(dst + 8 * D_, ep & (t == 1) & ~o, ep & (t == 1) & o);
                }
            }
        }
        warp_arrive(bars + (B_SIG + uw) * 8);
        TS(leader, 36 + uw)
        uint32_t res[20];
        auto ld_own = [&]() {
#pragma unroll
            for (int i = 0; i < 5; i++) { const uint4 v = ldcg128(own + i * 128); res[4 * i] = v.x; res[4 * i + 1] = v.y; res[4 * i + 2] = v.z; res[4 * i + 3] = v.w; }
        };
        ld_own();
#pragma unroll
        for (int i = 0; i < 10; i++) {
            const float2 c = lds64f(sb + M_C + (8 * i + 2 * t) * 4), s = lds64f(sb + M_SB + (8 * i + 2 * t) * 4);
#pragma unroll
            for (int h = 0; h < 2; h++) {
                acc[4 * i + 2 * h] = fmaf(blo(res[2 * i + h]), r1[h], fmaf(n1[h], c.x, s.x));
                acc[4 * i + 2 * h + 1] = fmaf(bhi(res[2 * i + h]), r1[h], fmaf(n1[h], c.y, s.y));
            }
        }
        mbar_spin(wfull + 5 * 8, 0);
        xwait(10);
#pragma unroll 1
        for (int i = 0; i < 5; i++) {
            const uint32_t wn = 5 + i, xs = (4 + 2 * uw + 2 * i) & 7;
            const uint64_t alo = dz + (((dsb + OFF_XR + xs * 8192) >> 4) | 0x10000u), bd = dz + b80_desc(dsb, wn, i, 0);
#pragma unroll
            for (int h = 0; h < 2; h++) {
                const uint32_t nn = min(11 + 2 * i + h, 19), wx = min(wn + 1, 9u);
                const bool ok = mbar_test(xfull + (nn & 7) * 8, (nn >> 3) & 1), okw = !h || mbar_test(wfull + (wx & 7) * 8, wx >> 3);
                wg_fence();
#pragma unroll
                for (int q = 0; q < 4; q++) wgmma_ss80(acc, alo + h * 512 + q * 2, bd + h * B80_HALF + q * B80_STEP, 1);
                wg_commit();
                wg_wait<1>();
                if (lane < 2 && (h || i)) mbar_arrive(xempty + ((xs + h - 1) & 7) * 8);
                if (!h && i && lane == 0) mbar_arrive(wempty + ((wn - 1) & 7) * 8);
                if (!ok) xwait(nn);
                if (!okw) mbar_spin(wfull + (wx & 7) * 8, wx >> 3);
                TR(leader, (uw ? 86 : 20) + 2 * i + h)
            }
        }
        wg_wait<0>();
        reg_fence(acc);
        if (lane < 2) mbar_arrive(xempty + ((29 + 10 * uw) & 7) * 8);
        if (lane == 0) mbar_arrive(wempty + (9 & 7) * 8);
        TS(leader, 38 + uw)
        float a0 = 0.f, b0 = 0.f, a1 = 0.f, b1 = 0.f;
        uint32_t x2[20];
#pragma unroll
        for (int i = 0; i < 5; i++) {
            uint32_t* p = &x2[4 * i];
#pragma unroll
            for (int e = 0; e < 4; e++) p[e] = pack2(acc[8 * i + 2 * e], acc[8 * i + 2 * e + 1]);
            p[0] = tag(p[0], ep);
            stg128(&g_x2f[(tile * 40 + (i < 4 ? 4 * j + i : 32 + j)) * 128 + wt], p[0], p[1], p[2], p[3]);
#pragma unroll
            for (int e = 0; e < 4; e += 2) {
                const float u0 = blo(p[e]), u1 = bhi(p[e]), v0 = blo(p[e + 1]), v1 = bhi(p[e + 1]);
                a0 += u0 + u1; b0 = fmaf(u0, u0, fmaf(u1, u1, b0));
                a1 += v0 + v1; b1 = fmaf(v0, v0, fmaf(v1, v1, b1));
            }
        }
#pragma unroll
        for (int o = 1; o < 4; o *= 2) {
            a0 += __shfl_xor_sync(~0u, a0, o); b0 += __shfl_xor_sync(~0u, b0, o);
            a1 += __shfl_xor_sync(~0u, a1, o); b1 += __shfl_xor_sync(~0u, b1, o);
        }
        if (t < 2) stg64(&g_stats[(tile * 8 + j) * 64 + 16 * wq + g + 8 * t], tag(__float_as_uint(t ? a1 : a0), ep), __float_as_uint(t ? b1 : b0));
        warp_arrive(bars + (B_SIG + uw) * 8);
        TS(leader, 40 + uw)
        ld_own();
#pragma unroll
        for (int i = 0; i < 10; i++) {
            const float2 c = lds64f(sb + M_GB + (8 * i + 2 * t) * 4), e = lds64f(sb + M_CI + (8 * i + 2 * t) * 4);
#pragma unroll
            for (int h = 0; h < 2; h++)
                res[2 * i + h] = fma2(pack2(c.x, c.y), x2[2 * i + h], pack2(e.x * blo(res[2 * i + h]), e.y * bhi(res[2 * i + h])));
        }
#pragma unroll
        for (int i = 0; i < 5; i++) stg128(own + i * 128, res[4 * i], res[4 * i + 1], res[4 * i + 2], res[4 * i + 3]);
        asm volatile("fence.proxy.async.global;" ::: "memory");
    }
    float acc0[64], acc1[44];
    float2 q[4];
    {
        uint4 f0, f1, f2, f3;
        auto xseq = [&](int kb) { return (uint32_t)(40 + (uw ? (kb < 10 - XLEAD ? XLEAD + 2 * kb : 10 + kb) : (kb < XLEAD ? kb : 2 * kb - XLEAD + 1))) & 7; };
        auto step = [&](const uint4& f, uint64_t bd) {
            wg_fence();
            wgmma_rs128(acc0, f.x, f.y, f.z, f.w, bd, 1);
            wgmma_rs88(acc1, f.x, f.y, f.z, f.w, bd + 512, 1);
            wg_commit();
        };
        const uint32_t xa = sb + OFF_XR + wt * 16;
        auto fix2 = [&](uint4& a, uint4& b, int s) {
            uint32_t it = 0;
            while (__any_sync(~0u, ((a.x ^ ep) | (b.x ^ ep)) & 1)) {
                a = ld_part(&g_x2f[(tile * 40 + s) * 128 + wt]); b = ld_part(&g_x2f[(tile * 40 + s + 1) * 128 + wt]);
                STALE(7)
                SPIN_CHECK(50)
            }
        };
        const float2* const gs = &g_stats[(tile * 8 + 2 * t) * 64 + 16 * wq + g];
        zero(acc0); zero(acc1);
        uint32_t xs = xseq(0);
        xwait(20);
        TS(leader, 42 + uw)
        f0 = lds128(xa + xs * 8192); f1 = lds128(xa + xs * 8192 + 2048);
#pragma unroll
        for (int i = 0; i < 4; i++) q[i] = ld_stat(gs + (i & 1) * 64 + 8 * (i >> 1));
        mbar_spin(wfull + (10 & 7) * 8, (10 >> 3) & 1);
#pragma unroll 1
        for (int kb = 0; kb < 10; kb++) {
            const uint32_t wn = 10 + 2 * kb;
            const uint64_t bd = dz + (((dsb + OFF_W + (wn & 7) * 16384) >> 4) | (256u << 16));
            fix2(f0, f1, 4 * kb);
            step(f0, bd);
            wg_wait<1>();
            if (kb && lane == 0) mbar_arrive(wempty + ((wn - 1) & 7) * 8);
            f2 = lds128(xa + xs * 8192 + 4096); f3 = lds128(xa + xs * 8192 + 6144);
            const bool w1 = mbar_test(wfull + ((wn + 1) & 7) * 8, (wn >> 3) & 1), x1 = mbar_test(xfull + ((21 + kb) & 7) * 8, ((21 + kb) >> 3) & 1);
            step(f1, bd + 128);
            if (!w1) mbar_spin(wfull + ((wn + 1) & 7) * 8, (wn >> 3) & 1);
            fix2(f2, f3, 4 * kb + 2);
            step(f2, bd + 1024);
            if (lane < 2) mbar_arrive_after(xempty + xs * 8, f2.x, f3.x, nil);
            wg_wait<1>();
            if (lane == 0) mbar_arrive(wempty + (wn & 7) * 8);
            xs = xseq(kb + 1);
            if (x1) { f0 = lds128(xa + xs * 8192); f1 = lds128(xa + xs * 8192 + 2048); }
            const bool w2 = mbar_test(wfull + ((wn + 2) & 7) * 8, ((wn + 2) >> 3) & 1);
            step(f3, bd + 1152);
            if (kb < 9 && !x1) { xwait(21 + kb); f0 = lds128(xa + xs * 8192); f1 = lds128(xa + xs * 8192 + 2048); }
            if (!w2) mbar_spin(wfull + ((wn + 2) & 7) * 8, ((wn + 2) >> 3) & 1);
            if (kb == 4) {
                uint32_t it = 0;
                while (__any_sync(~0u, ((__float_as_uint(q[0].x) ^ ep) | (__float_as_uint(q[1].x) ^ ep) | (__float_as_uint(q[2].x) ^ ep) | (__float_as_uint(q[3].x) ^ ep)) & 1)) {
#pragma unroll
                    for (int i = 0; i < 4; i++) q[i] = ld_stat(gs + (i & 1) * 64 + 8 * (i >> 1));
                    SPIN_CHECK(49)
                }
                float a0 = q[0].x + q[1].x, b0 = q[0].y + q[1].y, a1 = q[2].x + q[3].x, b1 = q[2].y + q[3].y;
#pragma unroll
                for (int o = 1; o < 4; o *= 2) {
                    a0 += __shfl_xor_sync(~0u, a0, o); b0 += __shfl_xor_sync(~0u, b0, o);
                    a1 += __shfl_xor_sync(~0u, a1, o); b1 += __shfl_xor_sync(~0u, b1, o);
                }
                a0 *= 1.f / D_; a1 *= 1.f / D_;
                const float r0 = 0.5f * rsqrtf(fmaxf(b0 * (1.f / D_) - a0 * a0, 0.f) + 1e-5f), r1 = 0.5f * rsqrtf(fmaxf(b1 * (1.f / D_) - a1 * a1, 0.f) + 1e-5f);
                const uint32_t sel = t == 0 ? 0x1010 : t == 1 ? 0x4432 : 0x4444;
                q[0] = make_float2(r0, r1);
                q[1] = make_float2(__uint_as_float(__byte_perm(split2(-a0), 0, sel)), __uint_as_float(__byte_perm(split2(-a1), 0, sel)));
            }
            TR(leader, 10 * uw + kb)
        }
        const uint64_t fd = ((uint64_t)8 << 32) | ((dsb + OFF_W + 6 * 16384) >> 4);
        wg_fence();
        wgmma_rs128k(acc0, __float_as_uint(q[1].x), __float_as_uint(q[1].y), 0, 0, fd, 1);
        wgmma_rs88k(acc1, __float_as_uint(q[1].x), __float_as_uint(q[1].y), 0, 0, fd + 128, 1);
        wg_commit();
        if (lane == 0) {
            mbar_arrive(bars + B_XFREE * 8);
            asm volatile("mbarrier.arrive.shared::cluster.b64 _, [%0];" ::"r"(peer_addr(bars + B_XFREE * 8)) : "memory");
        }
    }
    const uint32_t recv = sb + recv_off(uw) + wt * 16;
    uint32_t ha[48] = {}, hb[48], hx[12];
    uint64_t wb = dz + (((dsb + OFF_W) >> 4) | (512u << 16));
    auto wdesc = [&](int n) { return wb + (n & 7) * 1024; };
    auto wwait = [&](int n) { mbar_spin(wfull + (n & 7) * 8, (n >> 3) & 1); };
    auto wfree = [&](int n) { if (lane == 0) mbar_arrive(wempty + (n & 7) * 8); };
    auto fresh = [&]() { wb += pp.nil; asm volatile("" : "+l"(wb)); };
    uint32_t pk[32];
    {
        float P0[64];
        const float r0 = q[0].x, r1 = q[0].y;
        const uint32_t ra = peer_addr(recv), rb = peer_addr(bars + (B_RECV + 4 * uw) * 8);
        auto conv32 = [&](const float* v, int b) {
#pragma unroll
            for (int i = 0; i < 4; i++) {
                ha[8 * b + 2 * i] = pack2(gelu2(v[4 * i] * r0), gelu2(v[4 * i + 1] * r0));
                ha[8 * b + 2 * i + 1] = pack2(gelu2(v[4 * i + 2] * r1), gelu2(v[4 * i + 3] * r1));
            }
#pragma unroll
            for (int s = 2 * b; s < 2 * b + 2; s++) st_peer(ra + s * 2048, ha[4 * s], ha[4 * s + 1], ha[4 * s + 2], ha[4 * s + 3], rb + (b >> 1) * 8);
        };
        auto fetch = [&](int k) {
            mbar_spin(bars + (B_RECV + 4 * uw + k) * 8, 0);
#pragma unroll
            for (int s = 4 * k; s < 4 * k + 4; s++) { const uint4 x = lds128(recv + s * 2048); hb[4 * s] = x.x; hb[4 * s + 1] = x.y; hb[4 * s + 2] = x.z; hb[4 * s + 3] = x.w; }
        };
        auto stage = [&](int n, const uint32_t* a, int steps, int sc) {
            wwait(n);
            wg_fence();
#pragma unroll
            for (int s = 0; s < steps; s++) wgmma_rs128(P0, a[4 * s], a[4 * s + 1], a[4 * s + 2], a[4 * s + 3], wdesc(n) + s * 128, sc || s);
            wg_commit();
        };
        wg_wait<0>();
        reg_fence(acc0); reg_fence(acc1);
        wfree(29); wfree(30);
        TS(leader, 44 + uw)
        uint32_t hr[6];
#pragma unroll
        for (int i = 0; i < 6; i++) {
            const float r = (i & 1) ? r1 : r0;
            hr[i] = pack2(gelu2(acc1[32 + 2 * i] * r), gelu2(acc1[33 + 2 * i] * r));
        }
        if (uw) mbar_spin(bars + B_XFREE * 8, 0);
        st_peer(ra + 24576, hr[0], hr[1], hr[2], hr[3], rb + 24);
        asm volatile("st.async.shared::cluster.mbarrier::complete_tx::bytes.v2.b32 [%0], {%1, %2}, [%3];" ::"r"(ra + 26624 - wt * 8), "r"(hr[4]), "r"(hr[5]), "r"(rb + 24) : "memory");
        conv32(&acc1[0], 4);
        conv32(&acc1[16], 5);
        TS(leader, 46 + uw)
        stage(31, &ha[32], 4, 0);
#pragma unroll
        for (int b = 0; b < 4; b++) {
            conv32(&acc0[16 * b], b);
            if (b == 3) {
                fetch(2);
                mbar_spin(bars + (B_RECV + 4 * uw + 3) * 8, 0);
                const uint4 x = lds128(recv + 24576);
                const uint2 y = lds64(recv + 26624 - wt * 8);
                const uint32_t hp[6] = {x.x, x.y, x.z, x.w, y.x, y.y};
#pragma unroll
                for (int i = 0; i < 6; i++) { hx[i] = (j & 1) ? hp[i] : hr[i]; hx[6 + i] = (j & 1) ? hr[i] : hp[i]; }
            }
            if (!(b & 1)) wwait(32 + (b >> 1));
            wg_fence();
#pragma unroll
            for (int s = 0; s < 2; s++) wgmma_rs128(P0, ha[8 * b + 4 * s], ha[8 * b + 4 * s + 1], ha[8 * b + 4 * s + 2], ha[8 * b + 4 * s + 3], wdesc(32 + (b >> 1)) + (2 * (b & 1) + s) * 128, 1);
            wg_commit();
            if (!(b & 1)) { wg_wait<1>(); wfree(31 + (b >> 1)); }
        }
        TR(leader, 64 + 10 * uw)
        fresh();
        stage(34, &hb[32], 4, 1); wg_wait<1>(); wfree(33);
        fetch(0);
        stage(35, hx, 3, 1); wg_wait<1>(); wfree(34);
        fetch(1);
        stage(36, &hb[0], 4, 1); wg_wait<1>(); wfree(35);
        stage(37, &hb[16], 4, 1); wg_wait<1>(); wfree(36);
        wg_wait<0>();
        reg_fence(P0);
        pack_part<64>(pk, P0, ep);
        uint32_t all = 0;
#pragma unroll
        for (int i = 0; i < 32; i++) all |= pk[i];
        if (lane == 0) mbar_arrive_after(wempty + (37 & 7) * 8, all, 0, nil);
        TR(leader, 65 + 10 * uw)
    }
    {
        uint4* const dst = g_part + (size_t)(tile * 8 + j) * 5120 + wt;
        const uint4* const src = g_part + (size_t)tile * 40960 + j * 512 + wt;
        float F[2][32];
        float2 gb[8];
        uint4 base[4], u1[4], u2[4], u3[4];
#pragma unroll
        for (int c = 2; c < 5; c++) {
            float (&P)[32] = F[c & 1];
            fresh();
#pragma unroll
            for (int s = 0; s < 27; s++) {
                const int e = s < 8 ? 0 : s < 15 ? 1 : s < 23 ? 2 : 3, o = s - (e == 0 ? 0 : e == 1 ? 8 : e == 2 ? 15 : 23), n = 30 + 4 * c + e;
                const uint32_t* a = s < 12 ? &ha[4 * s] : s < 15 ? &hx[4 * (s - 12)] : &hb[4 * (s - 15)];
                if (o == 0) wwait(n);
                if (o == 0 || s == 1) wg_fence();
                wgmma_rs64(P, a[0], a[1], a[2], a[3], wdesc(n) + o * 128, s);
                if (o == 0) { wg_commit(); wg_wait<1>(); if (c > 2 || s) wfree(n - 1); }
                if (s == 0 && c > 2) { reg_fence(F[~c & 1]); pack_part<32>(pk, F[~c & 1], ep); }
                if (c == 2 && s % 3 == 0 && s < 24) st_part(dst + g4_block(s / 12, j) * 512 + (s / 3 & 3) * 128, &pk[4 * (s / 3)]);
                if (c == 3 && s % 4 == 1 && s < 16) st_part(dst + g4_block(2, j) * 512 + s / 4 * 128, &pk[4 * (s / 4)]);
                if (c == 4 && s % ST3 == 0 && s < 4 * ST3) st_part(dst + g4_block(3, j) * 512 + s / ST3 * 128, &pk[4 * (s / ST3)]);
                if (c == 4 && s >= 4 && s < 8) base[s - 4] = ldcg128(&g_x1f[(tile * 8 + j) * 640 + (s - 4) * 128 + wt]);
                if (c == 4 && s >= 19 && s < 23) { gb[2 * s - 38] = lds64f(sb + M_GB + (16 * (s - 19) + 2 * t) * 4); gb[2 * s - 37] = lds64f(sb + M_GB + (16 * (s - 19) + 8 + 2 * t) * 4); }
                if (c == 4 && s >= 8 && s < 12) u1[s - 8] = ld_part(src + (j ^ 6) * 5120 + (s - 8) * 128);
                if (c == 4 && s >= 15 && s < 19) u2[s - 15] = ld_part(src + (j ^ 4) * 5120 + (s - 15) * 128);
                if (c == 4 && s >= LD3 && s < LD3 + 4) u3[s - LD3] = ld_part(src + (j ^ 2) * 5120 + (s - LD3) * 128);
                if (s == 7 || s == 14 || s == 22 || s == 26) wg_commit();
                if (c == 4) { TR(leader && s == 7, 68 + 10 * uw) TR(leader && s == 14, 69 + 10 * uw) TR(leader && s == 22, 70 + 10 * uw) }
            }
            if (c == 2 && lane == 0) mbar_arrive(bars + (B_RING + uw) * 8);
            TR(leader, 64 + c + (c == 4 ? 3 : 0) + 10 * uw)
        }
        float (&O)[32] = F[0];
        float v[32];
        fix4(u1, src + (j ^ 6) * 5120, ep, 4);
        fix4(u2, src + (j ^ 4) * 5120, ep, 5);
        TR(leader, 72 + 10 * uw)
        fix4(u3, src + (j ^ 2) * 5120, ep, 6);
        TR(leader, 73 + 10 * uw)
#pragma unroll
        for (int i = 0; i < 4; i++) { unpack8(&v[8 * i], add2(add2(u1[i], u2[i]), u3[i])); base16(&v[8 * i], base[i], gb[2 * i], gb[2 * i + 1]); }
        reg_fence(v);
        TS(leader, 50 + uw)
        wg_wait<0>();
        reg_fence(O);
        TS(leader, 48 + uw)
        const uint32_t so = sb + recv_off(uw) + wq * 2048;
#pragma unroll
        for (int i = 0; i < 4; i++) {
            float* o = &O[8 * i];
#pragma unroll
            for (int e = 0; e < 8; e++) o[e] = fmaf((e & 1) ? gb[2 * i + (e >> 2)].y : gb[2 * i + (e >> 2)].x, o[e], v[8 * i + e]);
            stsm4(so + (lane & 15) * 128 + (((2 * i + (lane >> 4)) ^ (lane & 7)) << 4), pack2(o[0], o[1]), pack2(o[2], o[3]), pack2(o[4], o[5]), pack2(o[6], o[7]));
        }
        __syncwarp();
#pragma unroll
        for (int i = 0; i < 4; i++) {
            const int row = (lane >> 3) + 4 * i;
            stg128(out + (size_t)(row0 + row) * D_ + 64 * j + 8 * (lane & 7), lds128(so + row * 128 + (((lane & 7) ^ (row & 7)) << 4)));
        }
        warp_arrive(bars + B_OWN * 8);
    }
}

typedef CUresult (*EncFn)(CUtensorMap*, CUtensorMapDataType, cuuint32_t, void*, const cuuint64_t*, const cuuint64_t*, const cuuint32_t*,
                          const cuuint32_t*, CUtensorMapInterleave, CUtensorMapSwizzle, CUtensorMapL2promotion, CUtensorMapFloatOOBfill);

static void enc(EncFn fn, CUtensorMap* m, void* p, int rank, const cuuint64_t* dims, const cuuint64_t* strides, const cuuint32_t* box) {
    const CUtensorMapSwizzle sw = box[0] > 64 ? CU_TENSOR_MAP_SWIZZLE_NONE : CU_TENSOR_MAP_SWIZZLE_128B;
    cuuint32_t es[5] = {1, 1, 1, 1, 1};
    CUresult r = fn(m, CU_TENSOR_MAP_DATA_TYPE_BFLOAT16, rank, p, dims, strides, box, es, CU_TENSOR_MAP_INTERLEAVE_NONE, sw,
                    CU_TENSOR_MAP_L2_PROMOTION_L2_128B, CU_TENSOR_MAP_FLOAT_OOB_FILL_NONE);
    (void)r;
}
static void enc2(EncFn fn, CUtensorMap* m, void* p, uint64_t cols, uint64_t rows, uint32_t bc, uint32_t br) {
    cuuint64_t dims[2] = {cols, rows}, st[1] = {cols * 2};
    cuuint32_t box[2] = {bc, br};
    enc(fn, m, p, 2, dims, st, box);
}

extern "C" void kernel_launch(void* const* d_in, const int* in_sizes, int n_in, void* d_out, int out_size) {
    static Maps mp;
    static Ptrs pp;
    static void* cached[13];
    bool same = true;
    for (int i = 0; i < 13; i++) same = same && (cached[i] == d_in[i]);
    if (!same) {
        void* fnp = nullptr;
        cudaDriverEntryPointQueryResult qr;
        cudaGetDriverEntryPoint("cuTensorMapEncodeTiled", &fnp, cudaEnableDefault, &qr);
        EncFn fn = (EncFn)fnp;
        cudaGetSymbolAddress((void**)&pp.s, g_scratch);
        void *x1T = g_x1T, *t = g_t;
        cuuint64_t dq[3] = {64, S_, 10}, sq[2] = {D_ * 2, 128};
        cuuint32_t bq[3] = {64, 16, 10};
        enc(fn, &mp.q, d_in[0], 3, dq, sq, bq);
        enc2(fn, &mp.k, d_in[1], D_, S_, 80, 67); enc2(fn, &mp.v, d_in[2], D_, S_, 80, 64);
        enc2(fn, &mp.qT, g_qT, 16 * D_, 128, 80, 128);
        enc2(fn, &mp.x1_ld, x1T, S_, D_, 64, 64); enc2(fn, &mp.t_ld, (bf16*)t + 2 * D_, D_, S_, 64, 64);
        enc2(fn, &mp.w1, d_in[7], D_, D_, 64, 64); enc2(fn, &mp.w1h, d_in[7], D_, D_, 64, 160); enc2(fn, &mp.w3h, d_in[9], F_, D_, 64, 160);
        enc2(fn, &mp.wmod, d_in[12], 6 * D_, D_, 64, 160);
        const cuuint64_t R = D_ * 2;
        cuuint64_t da[5] = {D_, 2, 4, 4, 16}, sa[4] = {R, 8 * R, 2 * R, 32 * R}, db[5] = {D_, 2, 2, 4, 8}, sb[4] = {R, 8 * R, 2 * R, 16 * R};
        cuuint32_t ba[5] = {64, 2, 4, 4, 4}, bb[5] = {64, 2, 2, 4, 8};
        enc(fn, &mp.w2a, d_in[8], 5, da, sa, ba); enc(fn, &mp.w2b, (bf16*)d_in[8] + 512 * D_, 5, db, sb, bb);
        cuuint64_t dw[3] = {64, D_, 27}, sw[2] = {F_ * 2, 128};
        cuuint32_t bw[3] = {64, 32, 3};
        enc(fn, &mp.w3a, d_in[9], 3, dw, sw, bw);
        enc2(fn, &mp.w3b, d_in[9], F_, D_, 24, 32);
        enc2(fn, &mp.w4[0], d_in[10], D_, F_, 64, 64); enc2(fn, &mp.w4[1], d_in[10], D_, F_, 64, 48);
        pp.q = (const bf16*)d_in[0]; pp.w_mod = (const bf16*)d_in[12]; pp.shift_k = (const bf16*)d_in[3];
        pp.ssm_k = (const bf16*)d_in[4]; pp.ssm_D = (const bf16*)d_in[5]; pp.w1 = (const bf16*)d_in[7]; pp.w2 = (const bf16*)d_in[8];
        pp.w4 = (const bf16*)d_in[10]; pp.c = (const bf16*)d_in[11];
        cudaFuncSetAttribute(fused_kernel, cudaFuncAttributeMaxDynamicSharedMemorySize, SMEM_BYTES);
        for (int i = 0; i < 13; i++) cached[i] = d_in[i];
    }
    cudaLaunchConfig_t cfg = {};
    cfg.gridDim = dim3(NCTA); cfg.blockDim = dim3(NTHR); cfg.dynamicSmemBytes = SMEM_BYTES; cfg.stream = cudaStreamPerThread;
    cudaLaunchAttribute at[1];
    at[0].id = cudaLaunchAttributeClusterDimension; at[0].val.clusterDim.x = 2; at[0].val.clusterDim.y = 1; at[0].val.clusterDim.z = 1;
    cfg.attrs = at; cfg.numAttrs = 1;
    cudaLaunchKernelEx(&cfg, fused_kernel, pp, (bf16*)d_out, mp);
}
```

```cpp
#include <cuda_runtime.h>
#include <cuda_bf16.h>
#include <cuda.h>
#include <stdint.h>
#include <stdio.h>

typedef __nv_bfloat16 bf16;

constexpr int S_ = 2048, D_ = 640, F_ = 1728;
constexpr int NCTA = 132, NTHR = 512;

constexpr int TAB_BYTES = 9216, VEC_BYTES = 1440;
struct Counters {
    unsigned kv[8 * 32];
    unsigned q[4 * 32], x[2 * 4 * 32];
    unsigned wr[32], tab[32], uv[32], cs[32], done[32];
    unsigned g1[32 * 32];
    unsigned g2[32 * 32];
};
struct Scratch {
    Counters cnt;
    unsigned epoch;
    alignas(1024) bf16 qst[2 * S_];
    alignas(1024) uint4 wr[2 * 8 * 10 * 128];
    alignas(1024) uint2 mod[2 * 6 * D_];
    alignas(1024) uint4 tab[(TAB_BYTES + 8 * VEC_BYTES) / 16];
    alignas(1024) float uv[2 * 3 * D_];
    alignas(1024) float cs3[2 * 1920];
    alignas(1024) float2 stats[32 * 8 * 64];
    alignas(1024) bf16 kvT[D_ * S_];
    alignas(1024) bf16 qT[D_ * S_];
    alignas(1024) bf16 x1T[D_ * S_];
    alignas(1024) bf16 t[(S_ + 4) * D_];
    alignas(1024) uint4 x2f[32 * 40 * 128];
    alignas(1024) uint4 x1f[32 * 8 * 5 * 128];
    alignas(1024) uint4 part[32 * 8 * 10 * 4 * 128];
};
__device__ Scratch g_scratch;
#define g_kvT (pp.s->kvT)
#define g_qT (pp.s->qT)
#define g_x1T (pp.s->x1T)
#define g_qst (pp.s->qst)
#define g_t (pp.s->t)
#define g_x2f (pp.s->x2f)
#define g_x1f (pp.s->x1f)
#define g_part (pp.s->part)
#define g_wr (pp.s->wr)
#define g_mod (pp.s->mod)
#define g_tab (pp.s->tab)
#define g_uv (pp.s->uv)
#define g_cs3 (pp.s->cs3)
#define g_stats (pp.s->stats)
#define g_cnt (pp.s->cnt)
#define g_epoch (pp.s->epoch)

struct Maps {
    CUtensorMap k, v, q;
    CUtensorMap qT;
    CUtensorMap x1_ld, t_ld;
    CUtensorMap w1, w1h, w3h, wmod;
    CUtensorMap w2a, w2b;
    CUtensorMap w3a, w3b;
    CUtensorMap w4[2];
};

struct Ptrs {
    Scratch* s;
    uint64_t nil;
    const bf16 *q, *w_mod, *shift_k, *ssm_k, *ssm_D, *w1, *w2, *w4, *c;
};

constexpr int OFF_W = 0;
constexpr int OFF_XR = 131072;
constexpr int OFF_REM = 196608;
constexpr int OFF_TAB = OFF_REM + 5 * 4096;
constexpr int OFF_ROW = OFF_TAB + 4608;
constexpr int OFF_F1 = OFF_ROW + 4096;
constexpr int RECV_BYTES = 30720;
constexpr int OFF_M = OFF_REM + RECV_BYTES;
constexpr int OFF_OUT = OFF_XR + 32768;
static_assert(OFF_F1 + 1280 <= OFF_M, "G1 map");
constexpr int OFF_ST = 0;
constexpr int OFF_SSM = 20480;
constexpr int OFF_WM = 0;
constexpr int OFF_QIN = 49152;
constexpr int OFF_QT = 49152;
constexpr int OFF_Z = OFF_TAB;
constexpr int OFF_RING = 80896;
constexpr int OFF_KIN = OFF_RING, OFF_VIN = OFF_KIN + 2 * 10752;
constexpr int OFF_CH = OFF_RING + 3 * 16384, CH_BYTES = 13312, OFF_P = 5120;
static_assert(OFF_RING + 5 * 16384 <= OFF_CH + 3 * CH_BYTES && OFF_CH + 5 * CH_BYTES <= OFF_REM, "the last two rings replace channels 0..2");
constexpr int M_BAR = OFF_M;
constexpr int M_F1 = OFF_M + 800;
constexpr int M_GB = M_F1 + 1280, M_C = M_GB + 320, M_SB = M_C + 320, M_CI = M_SB + 320;
constexpr int M_KS = M_CI + 320;
constexpr int M_AB = M_KS + 160;
constexpr int M_EP = M_AB + 80;
constexpr int M_SINK = M_EP + 16;
constexpr int M_NUL = M_SINK + 16;
constexpr int M_TS = M_NUL + 128;
constexpr int SMEM_BYTES = M_TS;
static_assert(SMEM_BYTES <= 232448, "smem");

enum { B_WFULL = 0, B_WEMPTY = 8, B_XEMPTY = 16, B_XFULL = 24  ,
       B_RAW = 40, B_QIN = 41, B_SSM = 42, B_VEC = 43, B_VEC3 = 44, B_WM = 45, B_TAB = 46, B_QRDY = 47,
       B_MODR = 48, B_GATE = 49, B_RETRY = 55, B_S30 = 58, B_RAW2 = 59, B_SUMS = 62, B_RECV = 64  ,
       B_SIG = 72, B_RING = 74  ,
       B_LAND = 80,
       B_XS = 88, B_BK = 90, B_KVS = 91,
       B_XFREE = 92, B_OWN = 93,
       B_IN = 94, B_AGAIN = 96 };
#define T_KVB 1800
#define T_SSM 3300
#define T_Q 0
#define PF_T0 4800
#define PF_DT 420
#define PF_N0 4
#define PF_N 16
#define CH2_DELAY 0
#define POLL_NS 0
#define HELP_T 1000
#define EPI_SPLIT 1
#define ST3 1
#define LD3 23
#define GATE_W2 7
#define GATE_W3 27
#define GATE_W3B 37
#define W3_N2 13
#define XLEAD 3

#define SPIN_FAIL(code) __trap();
#define SPIN_LIMIT (1u << 22)
#define STALE(c)
#define STALE1(c)
#define TS(c, i)
#define TG(c, i)
#define TR(c, i)
#define TR2(c, i)
#define TR4(c, i)
#define TR5(c, i)
#define SPIN_CHECK(code) asm volatile("" ::"r"(it));
__device__ __forceinline__ uint32_t s2u(const void* p) { return (uint32_t)__cvta_generic_to_shared(p); }
__device__ __forceinline__ bool elect() {
    uint32_t p;
    asm volatile("{.reg .pred P; elect.sync _|P, 0xffffffff; selp.u32 %0,1,0,P;}" : "=r"(p));
    return p != 0;
}
__device__ __forceinline__ void mbar_init(uint32_t b, uint32_t n) { asm volatile("mbarrier.init.shared.b64 [%0], %1;" ::"r"(b), "r"(n)); }
__device__ __forceinline__ void mbar_expect(uint32_t b, uint32_t bytes) {
    asm volatile("mbarrier.arrive.expect_tx.shared.b64 _, [%0], %1;" ::"r"(b), "r"(bytes) : "memory");
}
__device__ __forceinline__ void mbar_arrive(uint32_t b) { asm volatile("mbarrier.arrive.shared.b64 _, [%0];" ::"r"(b) : "memory"); }
__device__ __forceinline__ void mbar_arrive_after(uint32_t b, uint32_t v0, uint32_t v1, uint32_t nil) { mbar_arrive(b + ((v0 | v1) & nil)); }
__device__ __forceinline__ void warp_arrive(uint32_t b) { __syncwarp(); if (elect()) mbar_arrive(b); }
__device__ __forceinline__ uint32_t peer_addr(uint32_t a) {
    uint32_t r;
    asm("{\n.reg .b32 q;\nmov.u32 q, %%cluster_ctarank;\nxor.b32 q, q, 1;\nmapa.shared::cluster.u32 %0, %1, q;\n}" : "=r"(r) : "r"(a));
    return r;
}
__device__ __forceinline__ bool mbar_test(uint32_t b, uint32_t parity) {
    uint32_t ok;
    asm volatile("{.reg .pred P; mbarrier.test_wait.parity.shared.b64 P, [%1], %2; selp.u32 %0,1,0,P;}" : "=r"(ok) : "r"(b), "r"(parity) : "memory");
    return ok != 0;
}
__device__ __forceinline__ bool mbar_try(uint32_t b, uint32_t parity) {
    uint32_t ok;
    asm volatile("{.reg .pred P; mbarrier.try_wait.parity.shared.b64 P, [%1], %2; selp.u32 %0,1,0,P;}" : "=r"(ok) : "r"(b), "r"(parity) : "memory");
    return ok != 0;
}
__device__ __forceinline__ void mbar_wait(uint32_t b, uint32_t parity) {
    if (__all_sync(0xffffffffu, mbar_try(b, parity))) return;
    uint32_t it = 0;
    while (!__all_sync(0xffffffffu, mbar_try(b, parity))) { if (++it > SPIN_LIMIT) SPIN_FAIL((b >> 3) & 63) }
}
__device__ __forceinline__ void mbar_spin(uint32_t b, uint32_t parity) {
    asm volatile("{\n.reg .pred P;\nSPIN:\nmbarrier.try_wait.parity.shared.b64 P, [%0], %1;\n@!P bra.uni SPIN;\n}" ::"r"(b), "r"(parity) : "memory");
}
__device__ __forceinline__ void bar_sync(int id, int n) { asm volatile("bar.sync %0, %1;" ::"r"(id), "r"(n) : "memory"); }
__device__ __forceinline__ void fence_async_smem() { asm volatile("fence.proxy.async.shared::cta;" ::: "memory"); }
__device__ __forceinline__ void wait_cnt(const unsigned* p, unsigned target, int ns = 0) {
    unsigned v, it = 0;
    do {
        if (ns) __nanosleep(ns);
        asm volatile("ld.relaxed.gpu.global.u32 %0, [%1];" : "=r"(v) : "l"(p) : "memory");
        SPIN_CHECK(60 + (target & 3))
    } while (!__all_sync(0xffffffffu, v >= target));
    asm volatile("fence.acquire.gpu;" ::: "memory");
}
#define X_FENCE 0
__device__ __forceinline__ void signal_cnt(unsigned* p, int lane, int n, bool nofence = false) {
    if (nofence) { if (lane < n) asm volatile("red.relaxed.gpu.global.add.u32 [%0], 1;" ::"l"(p) : "memory"); }
    else if (lane < n) asm volatile("red.release.gpu.global.add.u32 [%0], 1;" ::"l"(p) : "memory");
    __syncwarp();
}
__device__ __forceinline__ void wait_clock(long long c0, int t) {
    while (clock64() - c0 < t) __nanosleep(20);
    __syncwarp();
}
__device__ __forceinline__ void tma_ld2(uint32_t dst, const CUtensorMap* m, int c0, int c1, uint32_t bar) {
    asm volatile("cp.async.bulk.tensor.2d.shared::cluster.global.mbarrier::complete_tx::bytes [%0], [%1, {%3, %4}], [%2];"
                 ::"r"(dst), "l"(m), "r"(bar), "r"(c0), "r"(c1) : "memory");
}
__device__ __forceinline__ void tma_ld3(uint32_t dst, const CUtensorMap* m, int c0, int c1, int c2, uint32_t bar) {
    asm volatile("cp.async.bulk.tensor.3d.shared::cluster.global.mbarrier::complete_tx::bytes [%0], [%1, {%3, %4, %5}], [%2];"
                 ::"r"(dst), "l"(m), "r"(bar), "r"(c0), "r"(c1), "r"(c2) : "memory");
}
__device__ __forceinline__ void tma_ld5(uint32_t dst, const CUtensorMap* m, int col, int blk, uint32_t bar) {
    asm volatile("cp.async.bulk.tensor.5d.shared::cluster.global.mbarrier::complete_tx::bytes [%0], [%1, {%3, %4, %4, %4, %5}], [%2];"
                 ::"r"(dst), "l"(m), "r"(bar), "r"(col), "r"(0), "r"(blk) : "memory");
}
__device__ __forceinline__ void bulk_ld(uint32_t dst, const void* src, uint32_t bytes, uint32_t bar) {
    asm volatile("cp.async.bulk.shared::cluster.global.mbarrier::complete_tx::bytes [%0], [%1], %2, [%3];" ::"r"(dst), "l"(src), "r"(bytes), "r"(bar) : "memory");
}
__device__ __forceinline__ void l2_prefetch(const void* p, uint32_t bytes) {
    asm volatile("cp.async.bulk.prefetch.L2.global [%0], %1;" ::"l"(p), "r"(bytes) : "memory");
}
__device__ __forceinline__ void wg_fence() { asm volatile("wgmma.fence.sync.aligned;" ::: "memory"); }
__device__ __forceinline__ void wg_commit() { asm volatile("wgmma.commit_group.sync.aligned;" ::: "memory"); }
template <int N> __device__ __forceinline__ void wg_wait() { asm volatile("wgmma.wait_group.sync.aligned %0;" ::"n"(N) : "memory"); }
template <int N> __device__ __forceinline__ void reg_fence(float (&d)[N]) {
#pragma unroll
    for (int i = 0; i < N; i++) asm volatile("" : "+f"(d[i])::"memory");
}
template <int N> __device__ __forceinline__ void zero(float (&d)[N]) {
#pragma unroll
    for (int i = 0; i < N; i++) asm volatile("mov.b32 %0, 0;" : "=f"(d[i]));
}
__device__ __forceinline__ uint32_t lds32(uint32_t a) { uint32_t v; asm volatile("ld.shared.b32 %0, [%1];" : "=r"(v) : "r"(a)); return v; }
__device__ __forceinline__ uint2 lds64(uint32_t a) { uint2 v; asm volatile("ld.shared.v2.b32 {%0,%1}, [%2];" : "=r"(v.x), "=r"(v.y) : "r"(a)); return v; }
__device__ __forceinline__ float2 lds64f(uint32_t a) { float2 v; asm volatile("ld.shared.v2.f32 {%0,%1}, [%2];" : "=f"(v.x), "=f"(v.y) : "r"(a)); return v; }
__device__ __forceinline__ void sts32(uint32_t a, uint32_t v) { asm volatile("st.shared.b32 [%0], %1;" ::"r"(a), "r"(v) : "memory"); }
__device__ __forceinline__ void sts64f(uint32_t a, float x, float y) { asm volatile("st.shared.v2.f32 [%0], {%1,%2};" ::"r"(a), "f"(x), "f"(y) : "memory"); }
__device__ __forceinline__ void sts128(uint32_t a, uint32_t x, uint32_t y, uint32_t z, uint32_t w) {
    asm volatile("st.shared.v4.b32 [%0], {%1,%2,%3,%4};" ::"r"(a), "r"(x), "r"(y), "r"(z), "r"(w) : "memory");
}
__device__ __forceinline__ void sts128f(uint32_t a, float x, float y, float z, float w) {
    asm volatile("st.shared.v4.f32 [%0], {%1,%2,%3,%4};" ::"r"(a), "f"(x), "f"(y), "f"(z), "f"(w) : "memory");
}
__device__ __forceinline__ uint4 lds128(uint32_t a) {
    uint4 v;
    asm volatile("ld.shared.v4.b32 {%0,%1,%2,%3}, [%4];" : "=r"(v.x), "=r"(v.y), "=r"(v.z), "=r"(v.w) : "r"(a) : "memory");
    return v;
}
__device__ __forceinline__ float4 lds128f(uint32_t a) {
    float4 v;
    asm volatile("ld.shared.v4.f32 {%0,%1,%2,%3}, [%4];" : "=f"(v.x), "=f"(v.y), "=f"(v.z), "=f"(v.w) : "r"(a) : "memory");
    return v;
}
__device__ __forceinline__ void stg128(void* p, uint32_t x, uint32_t y, uint32_t z, uint32_t w) {
    asm volatile("st.global.v4.b32 [%0], {%1,%2,%3,%4};" ::"l"(p), "r"(x), "r"(y), "r"(z), "r"(w) : "memory");
}
__device__ __forceinline__ void stg128(void* p, uint4 v) { stg128(p, v.x, v.y, v.z, v.w); }
__device__ __forceinline__ void stg128_if(void* p, uint4 v, int on) {
    asm volatile("{\n.reg .pred p;\nsetp.ne.s32 p, %5, 0;\n@p st.global.v4.b32 [%0], {%1,%2,%3,%4};\n}" ::"l"(p), "r"(v.x), "r"(v.y), "r"(v.z), "r"(v.w), "r"(on) : "memory");
}
__device__ __forceinline__ void stg64(void* p, uint32_t x, uint32_t y) { asm volatile("st.global.v2.b32 [%0], {%1,%2};" ::"l"(p), "r"(x), "r"(y) : "memory"); }
__device__ __forceinline__ void stsm4(uint32_t a, uint32_t r0, uint32_t r1, uint32_t r2, uint32_t r3) {
    asm volatile("stmatrix.sync.aligned.m8n8.x4.shared.b16 [%0], {%1,%2,%3,%4};" ::"r"(a), "r"(r0), "r"(r1), "r"(r2), "r"(r3) : "memory");
}
__device__ __forceinline__ void stsm4t(uint32_t a, uint32_t r0, uint32_t r1, uint32_t r2, uint32_t r3) {
    asm volatile("stmatrix.sync.aligned.m8n8.x4.trans.shared.b16 [%0], {%1,%2,%3,%4};" ::"r"(a), "r"(r0), "r"(r1), "r"(r2), "r"(r3) : "memory");
}
__device__ __forceinline__ void ldsm4t(uint32_t a, uint32_t& r0, uint32_t& r1, uint32_t& r2, uint32_t& r3) {
    asm volatile("ldmatrix.sync.aligned.m8n8.x4.trans.shared.b16 {%0,%1,%2,%3}, [%4];" : "=r"(r0), "=r"(r1), "=r"(r2), "=r"(r3) : "r"(a) : "memory");
}
__device__ __forceinline__ uint32_t pack2(float lo, float hi) {
    uint32_t r;
    asm("cvt.rn.bf16x2.f32 %0, %1, %2;" : "=r"(r) : "f"(hi), "f"(lo));
    return r;
}
__device__ __forceinline__ uint32_t mul2(uint32_t a, uint32_t b) { uint32_t r; asm("mul.rn.bf16x2 %0, %1, %2;" : "=r"(r) : "r"(a), "r"(b)); return r; }
__device__ __forceinline__ uint32_t fma2(uint32_t a, uint32_t b, uint32_t c) { uint32_t r; asm("fma.rn.bf16x2 %0, %1, %2, %3;" : "=r"(r) : "r"(a), "r"(b), "r"(c)); return r; }
__device__ __forceinline__ uint32_t add2(uint32_t a, uint32_t b) { uint32_t r; asm("add.rn.bf16x2 %0, %1, %2;" : "=r"(r) : "r"(a), "r"(b)); return r; }
__device__ __forceinline__ void hmma(float (&d)[4], uint32_t a0, uint32_t a1, uint32_t a2, uint32_t a3, uint32_t b0, uint32_t b1) {
    asm volatile("mma.sync.aligned.m16n8k16.row.col.f32.bf16.bf16.f32 {%0,%1,%2,%3}, {%4,%5,%6,%7}, {%8,%9}, {%0,%1,%2,%3};"
        : "+f"(d[0]), "+f"(d[1]), "+f"(d[2]), "+f"(d[3]) : "r"(a0), "r"(a1), "r"(a2), "r"(a3), "r"(b0), "r"(b1));
}
__device__ __forceinline__ float blo(uint32_t w) { return __uint_as_float(w << 16); }
__device__ __forceinline__ float bhi(uint32_t w) { return __uint_as_float(w & 0xffff0000u); }
__device__ __forceinline__ float rbf(float x) { return __bfloat162float(__float2bfloat16_rn(x)); }
__device__ __forceinline__ uint32_t ldg32(const void* p) { uint32_t v; asm volatile("ld.global.nc.b32 %0, [%1];" : "=r"(v) : "l"(p)); return v; }
__device__ __forceinline__ uint2 ldg64(const void* p) { uint2 v; asm volatile("ld.global.nc.v2.b32 {%0,%1}, [%2];" : "=r"(v.x), "=r"(v.y) : "l"(p)); return v; }
__device__ __forceinline__ uint4 ldg128(const void* p) {
    uint4 v;
    asm volatile("ld.global.nc.v4.b32 {%0,%1,%2,%3}, [%4];" : "=r"(v.x), "=r"(v.y), "=r"(v.z), "=r"(v.w) : "l"(p));
    return v;
}
__device__ __forceinline__ uint4 ldcg128(const void* p) {
    uint4 v;
    asm volatile("ld.global.cg.v4.u32 {%0,%1,%2,%3}, [%4];" : "=r"(v.x), "=r"(v.y), "=r"(v.z), "=r"(v.w) : "l"(p) : "memory");
    return v;
}
__device__ __forceinline__ float4 ldcg128f(const void* p) {
    float4 v;
    asm volatile("ld.global.cg.v4.f32 {%0,%1,%2,%3}, [%4];" : "=f"(v.x), "=f"(v.y), "=f"(v.z), "=f"(v.w) : "l"(p) : "memory");
    return v;
}
__device__ __forceinline__ float2 ldcg64f(const void* p) { float2 v; asm volatile("ld.global.cg.v2.f32 {%0,%1}, [%2];" : "=f"(v.x), "=f"(v.y) : "l"(p) : "memory"); return v; }
__device__ __forceinline__ float ldcg32f(const void* p) { float v; asm volatile("ld.global.cg.f32 %0, [%1];" : "=f"(v) : "l"(p) : "memory"); return v; }
__device__ __forceinline__ float2 ld_stat(const float2* p) {
    float2 v;
    asm volatile("{\n.reg .b64 q;\nld.relaxed.gpu.global.b64 q, [%2];\nmov.b64 {%0, %1}, q;\n}" : "=f"(v.x), "=f"(v.y) : "l"(p) : "memory");
    return v;
}
__device__ __forceinline__ uint32_t ld_cold(const unsigned* p) { uint32_t v; asm volatile("ld.relaxed.gpu.global.u32 %0, [%1];" : "=r"(v) : "l"(p) : "memory"); return v; }
__device__ __forceinline__ uint2 ld_mod(const uint2* p) {
    uint64_t v;
    asm volatile("ld.relaxed.gpu.global.b64 %0, [%1];" : "=l"(v) : "l"(p) : "memory");
    return make_uint2((uint32_t)v, (uint32_t)(v >> 32));
}
__device__ __forceinline__ float gelu2(float h) {
    float u = h * fmaf(h * h, 8.f * 0.0356774081f, 2.f * 0.7978845608f);
    float th;
    asm("tanh.approx.f32 %0, %1;" : "=f"(th) : "f"(u));
    return fmaf(h, th, h);
}

__device__ __forceinline__ void conv_channel(float (&d)[64], uint32_t pa, uint64_t db) {
    asm volatile("{\n.reg .b32 a0, a1, a2, a3, b0, b1, b2, b3, t0, t1;\n.reg .b64 d;\nld.shared.b32 a0, [%64];\nld.shared.b32 a1, [%64+128];\nld.shared.b32 a2, [%64+-128];\nmov.b32 a3, a0;\n"
        "ld.shared.b32 t0, [%64+256];\nld.shared.b32 t1, [%64+384];\nadd.s64 d, %65, 0;\nwgmma.fence.sync.aligned;\nwgmma.mma_async.sync.aligned.m64n128k16.f32.bf16.bf16 {%0, %1, %2, %3, %4, %5, %6, %7, %8, %9, %10, %11, %12, %13, %14, %15, %16, %17, %18, %19, %20, %21, %22, %23, %24, %25, %26, %27, %28, %29, %30, %31, %32, %33, %34, %35, %36, %37, %38, %39, %40, %41, %42, %43, %44, %45, %46, %47, %48, %49, %50, %51, %52, %53, %54, %55, %56, %57, %58, %59, %60, %61, %62, %63}, {a0, a1, a2, a3}, d, 0, 1, 1, 0;\nwgmma.commit_group.sync.aligned;\nwgmma.wait_group.sync.aligned 1;\nmov.b32 b2, a1;\nmov.b32 b0, t0;\nmov.b32 b3, t0;\nmov.b32 b1, t1;\n"
        "ld.shared.b32 t0, [%64+512];\nld.shared.b32 t1, [%64+640];\nadd.s64 d, %65, 8;\nwgmma.fence.sync.aligned;\nwgmma.mma_async.sync.aligned.m64n128k16.f32.bf16.bf16 {%0, %1, %2, %3, %4, %5, %6, %7, %8, %9, %10, %11, %12, %13, %14, %15, %16, %17, %18, %19, %20, %21, %22, %23, %24, %25, %26, %27, %28, %29, %30, %31, %32, %33, %34, %35, %36, %37, %38, %39, %40, %41, %42, %43, %44, %45, %46, %47, %48, %49, %50, %51, %52, %53, %54, %55, %56, %57, %58, %59, %60, %61, %62, %63}, {b0, b1, b2, b3}, d, 1, 1, 1, 0;\nwgmma.commit_group.sync.aligned;\nwgmma.wait_group.sync.aligned 1;\nmov.b32 a2, b1;\nmov.b32 a0, t0;\nmov.b32 a3, t0;\nmov.b32 a1, t1;\n"
        "ld.shared.b32 t0, [%64+768];\nld.shared.b32 t1, [%64+896];\nadd.s64 d, %65, 16;\nwgmma.fence.sync.aligned;\nwgmma.mma_async.sync.aligned.m64n128k16.f32.bf16.bf16 {%0, %1, %2, %3, %4, %5, %6, %7, %8, %9, %10, %11, %12, %13, %14, %15, %16, %17, %18, %19, %20, %21, %22, %23, %24, %25, %26, %27, %28, %29, %30, %31, %32, %33, %34, %35, %36, %37, %38, %39, %40, %41, %42, %43, %44, %45, %46, %47, %48, %49, %50, %51, %52, %53, %54, %55, %56, %57, %58, %59, %60, %61, %62, %63}, {a0, a1, a2, a3}, d, 1, 1, 1, 0;\nwgmma.commit_group.sync.aligned;\nwgmma.wait_group.sync.aligned 1;\nmov.b32 b2, a1;\nmov.b32 b0, t0;\nmov.b32 b3, t0;\nmov.b32 b1, t1;\n"
        "ld.shared.b32 t0, [%64+1024];\nld.shared.b32 t1, [%64+1152];\nadd.s64 d, %65, 24;\nwgmma.fence.sync.aligned;\nwgmma.mma_async.sync.aligned.m64n128k16.f32.bf16.bf16 {%0, %1, %2, %3, %4, %5, %6, %7, %8, %9, %10, %11, %12, %13, %14, %15, %16, %17, %18, %19, %20, %21, %22, %23, %24, %25, %26, %27, %28, %29, %30, %31, %32, %33, %34, %35, %36, %37, %38, %39, %40, %41, %42, %43, %44, %45, %46, %47, %48, %49, %50, %51, %52, %53, %54, %55, %56, %57, %58, %59, %60, %61, %62, %63}, {b0, b1, b2, b3}, d, 1, 1, 1, 0;\nwgmma.commit_group.sync.aligned;\nwgmma.wait_group.sync.aligned 1;\nmov.b32 a2, b1;\nmov.b32 a0, t0;\nmov.b32 a3, t0;\nmov.b32 a1, t1;\n"
        "ld.shared.b32 t0, [%64+1280];\nld.shared.b32 t1, [%64+1408];\nadd.s64 d, %65, 32;\nwgmma.fence.sync.aligned;\nwgmma.mma_async.sync.aligned.m64n128k16.f32.bf16.bf16 {%0, %1, %2, %3, %4, %5, %6, %7, %8, %9, %10, %11, %12, %13, %14, %15, %16, %17, %18, %19, %20, %21, %22, %23, %24, %25, %26, %27, %28, %29, %30, %31, %32, %33, %34, %35, %36, %37, %38, %39, %40, %41, %42, %43, %44, %45, %46, %47, %48, %49, %50, %51, %52, %53, %54, %55, %56, %57, %58, %59, %60, %61, %62, %63}, {a0, a1, a2, a3}, d, 1, 1, 1, 0;\nwgmma.commit_group.sync.aligned;\nwgmma.wait_group.sync.aligned 1;\nmov.b32 b2, a1;\nmov.b32 b0, t0;\nmov.b32 b3, t0;\nmov.b32 b1, t1;\n"
        "ld.shared.b32 t0, [%64+1536];\nld.shared.b32 t1, [%64+1664];\nadd.s64 d, %65, 40;\nwgmma.fence.sync.aligned;\nwgmma.mma_async.sync.aligned.m64n128k16.f32.bf16.bf16 {%0, %1, %2, %3, %4, %5, %6, %7, %8, %9, %10, %11, %12, %13, %14, %15, %16, %17, %18, %19, %20, %21, %22, %23, %24, %25, %26, %27, %28, %29, %30, %31, %32, %33, %34, %35, %36, %37, %38, %39, %40, %41, %42, %43, %44, %45, %46, %47, %48, %49, %50, %51, %52, %53, %54, %55, %56, %57, %58, %59, %60, %61, %62, %63}, {b0, b1, b2, b3}, d, 1, 1, 1, 0;\nwgmma.commit_group.sync.aligned;\nwgmma.wait_group.sync.aligned 1;\nmov.b32 a2, b1;\nmov.b32 a0, t0;\nmov.b32 a3, t0;\nmov.b32 a1, t1;\n"
        "ld.shared.b32 t0, [%64+1792];\nld.shared.b32 t1, [%64+1920];\nadd.s64 d, %65, 48;\nwgmma.fence.sync.aligned;\nwgmma.mma_async.sync.aligned.m64n128k16.f32.bf16.bf16 {%0, %1, %2, %3, %4, %5, %6, %7, %8, %9, %10, %11, %12, %13, %14, %15, %16, %17, %18, %19, %20, %21, %22, %23, %24, %25, %26, %27, %28, %29, %30, %31, %32, %33, %34, %35, %36, %37, %38, %39, %40, %41, %42, %43, %44, %45, %46, %47, %48, %49, %50, %51, %52, %53, %54, %55, %56, %57, %58, %59, %60, %61, %62, %63}, {a0, a1, a2, a3}, d, 1, 1, 1, 0;\nwgmma.commit_group.sync.aligned;\nwgmma.wait_group.sync.aligned 1;\nmov.b32 b2, a1;\nmov.b32 b0, t0;\nmov.b32 b3, t0;\nmov.b32 b1, t1;\n"
        "ld.shared.b32 t0, [%64+2048];\nld.shared.b32 t1, [%64+2176];\nadd.s64 d, %65, 56;\nwgmma.fence.sync.aligned;\nwgmma.mma_async.sync.aligned.m64n128k16.f32.bf16.bf16 {%0, %1, %2, %3, %4, %5, %6, %7, %8, %9, %10, %11, %12, %13, %14, %15, %16, %17, %18, %19, %20, %21, %22, %23, %24, %25, %26, %27, %28, %29, %30, %31, %32, %33, %34, %35, %36, %37, %38, %39, %40, %41, %42, %43, %44, %45, %46, %47, %48, %49, %50, %51, %52, %53, %54, %55, %56, %57, %58, %59, %60, %61, %62, %63}, {b0, b1, b2, b3}, d, 1, 1, 1, 0;\nwgmma.commit_group.sync.aligned;\nwgmma.wait_group.sync.aligned 1;\nmov.b32 a2, b1;\nmov.b32 a0, t0;\nmov.b32 a3, t0;\nmov.b32 a1, t1;\n"
        "ld.shared.b32 t0, [%64+2304];\nld.shared.b32 t1, [%64+2432];\nadd.s64 d, %65, 64;\nwgmma.fence.sync.aligned;\nwgmma.mma_async.sync.aligned.m64n96k16.f32.bf16.bf16 {%0, %1, %2, %3, %4, %5, %6, %7, %8, %9, %10, %11, %12, %13, %14, %15, %16, %17, %18, %19, %20, %21, %22, %23, %24, %25, %26, %27, %28, %29, %30, %31, %32, %33, %34, %35, %36, %37, %38, %39, %40, %41, %42, %43, %44, %45, %46, %47}, {a0, a1, a2, a3}, d, 1, 1, 1, 0;\nwgmma.commit_group.sync.aligned;\nwgmma.wait_group.sync.aligned 1;\nmov.b32 b2, a1;\nmov.b32 b0, t0;\nmov.b32 b3, t0;\nmov.b32 b1, t1;\n"
        "ld.shared.b32 t0, [%64+2560];\nld.shared.b32 t1, [%64+2688];\nadd.s64 d, %65, 72;\nwgmma.fence.sync.aligned;\nwgmma.mma_async.sync.aligned.m64n96k16.f32.bf16.bf16 {%0, %1, %2, %3, %4, %5, %6, %7, %8, %9, %10, %11, %12, %13, %14, %15, %16, %17, %18, %19, %20, %21, %22, %23, %24, %25, %26, %27, %28, %29, %30, %31, %32, %33, %34, %35, %36, %37, %38, %39, %40, %41, %42, %43, %44, %45, %46, %47}, {b0, b1, b2, b3}, d, 1, 1, 1, 0;\nwgmma.commit_group.sync.aligned;\nwgmma.wait_group.sync.aligned 1;\nmov.b32 a2, b1;\nmov.b32 a0, t0;\nmov.b32 a3, t0;\nmov.b32 a1, t1;\n"
        "ld.shared.b32 t0, [%64+2816];\nld.shared.b32 t1, [%64+2944];\nadd.s64 d, %65, 80;\nwgmma.fence.sync.aligned;\nwgmma.mma_async.sync.aligned.m64n88k16.f32.bf16.bf16 {%0, %1, %2, %3, %4, %5, %6, %7, %8, %9, %10, %11, %12, %13, %14, %15, %16, %17, %18, %19, %20, %21, %22, %23, %24, %25, %26, %27, %28, %29, %30, %31, %32, %33, %34, %35, %36, %37, %38, %39, %40, %41, %42, %43}, {a0, a1, a2, a3}, d, 1, 1, 1, 0;\nwgmma.commit_group.sync.aligned;\nwgmma.wait_group.sync.aligned 1;\nmov.b32 b2, a1;\nmov.b32 b0, t0;\nmov.b32 b3, t0;\nmov.b32 b1, t1;\n"
        "ld.shared.b32 t0, [%64+3072];\nld.shared.b32 t1, [%64+3200];\nadd.s64 d, %65, 88;\nwgmma.fence.sync.aligned;\nwgmma.mma_async.sync.aligned.m64n88k16.f32.bf16.bf16 {%0, %1, %2, %3, %4, %5, %6, %7, %8, %9, %10, %11, %12, %13, %14, %15, %16, %17, %18, %19, %20, %21, %22, %23, %24, %25, %26, %27, %28, %29, %30, %31, %32, %33, %34, %35, %36, %37, %38, %39, %40, %41, %42, %43}, {b0, b1, b2, b3}, d, 1, 1, 1, 0;\nwgmma.commit_group.sync.aligned;\nwgmma.wait_group.sync.aligned 1;\nmov.b32 a2, b1;\nmov.b32 a0, t0;\nmov.b32 a3, t0;\nmov.b32 a1, t1;\n"
        "ld.shared.b32 t0, [%64+3328];\nld.shared.b32 t1, [%64+3456];\nadd.s64 d, %65, 96;\nwgmma.fence.sync.aligned;\nwgmma.mma_async.sync.aligned.m64n80k16.f32.bf16.bf16 {%0, %1, %2, %3, %4, %5, %6, %7, %8, %9, %10, %11, %12, %13, %14, %15, %16, %17, %18, %19, %20, %21, %22, %23, %24, %25, %26, %27, %28, %29, %30, %31, %32, %33, %34, %35, %36, %37, %38, %39}, {a0, a1, a2, a3}, d, 1, 1, 1, 0;\nwgmma.commit_group.sync.aligned;\nwgmma.wait_group.sync.aligned 1;\nmov.b32 b2, a1;\nmov.b32 b0, t0;\nmov.b32 b3, t0;\nmov.b32 b1, t1;\n"
        "ld.shared.b32 t0, [%64+3584];\nld.shared.b32 t1, [%64+3712];\nadd.s64 d, %65, 104;\nwgmma.fence.sync.aligned;\nwgmma.mma_async.sync.aligned.m64n80k16.f32.bf16.bf16 {%0, %1, %2, %3, %4, %5, %6, %7, %8, %9, %10, %11, %12, %13, %14, %15, %16, %17, %18, %19, %20, %21, %22, %23, %24, %25, %26, %27, %28, %29, %30, %31, %32, %33, %34, %35, %36, %37, %38, %39}, {b0, b1, b2, b3}, d, 1, 1, 1, 0;\nwgmma.commit_group.sync.aligned;\nwgmma.wait_group.sync.aligned 1;\nmov.b32 a2, b1;\nmov.b32 a0, t0;\nmov.b32 a3, t0;\nmov.b32 a1, t1;\n"
        "ld.shared.b32 t0, [%64+3840];\nld.shared.b32 t1, [%64+3968];\nadd.s64 d, %65, 112;\nwgmma.fence.sync.aligned;\nwgmma.mma_async.sync.aligned.m64n72k16.f32.bf16.bf16 {%0, %1, %2, %3, %4, %5, %6, %7, %8, %9, %10, %11, %12, %13, %14, %15, %16, %17, %18, %19, %20, %21, %22, %23, %24, %25, %26, %27, %28, %29, %30, %31, %32, %33, %34, %35}, {a0, a1, a2, a3}, d, 1, 1, 1, 0;\nwgmma.commit_group.sync.aligned;\nwgmma.wait_group.sync.aligned 1;\nmov.b32 b2, a1;\nmov.b32 b0, t0;\nmov.b32 b3, t0;\nmov.b32 b1, t1;\n"
        "ld.shared.b32 t0, [%64+4096];\nld.shared.b32 t1, [%64+4224];\nadd.s64 d, %65, 120;\nwgmma.fence.sync.aligned;\nwgmma.mma_async.sync.aligned.m64n72k16.f32.bf16.bf16 {%0, %1, %2, %3, %4, %5, %6, %7, %8, %9, %10, %11, %12, %13, %14, %15, %16, %17, %18, %19, %20, %21, %22, %23, %24, %25, %26, %27, %28, %29, %30, %31, %32, %33, %34, %35}, {b0, b1, b2, b3}, d, 1, 1, 1, 0;\nwgmma.commit_group.sync.aligned;\nwgmma.wait_group.sync.aligned 1;\nmov.b32 a2, b1;\nmov.b32 a0, t0;\nmov.b32 a3, t0;\nmov.b32 a1, t1;\n"
        "ld.shared.b32 t0, [%64+4352];\nld.shared.b32 t1, [%64+4480];\nadd.s64 d, %65, 128;\nwgmma.fence.sync.aligned;\nwgmma.mma_async.sync.aligned.m64n64k16.f32.bf16.bf16 {%0, %1, %2, %3, %4, %5, %6, %7, %8, %9, %10, %11, %12, %13, %14, %15, %16, %17, %18, %19, %20, %21, %22, %23, %24, %25, %26, %27, %28, %29, %30, %31}, {a0, a1, a2, a3}, d, 1, 1, 1, 0;\nwgmma.commit_group.sync.aligned;\nwgmma.wait_group.sync.aligned 1;\nmov.b32 b2, a1;\nmov.b32 b0, t0;\nmov.b32 b3, t0;\nmov.b32 b1, t1;\n"
        "ld.shared.b32 t0, [%64+4608];\nld.shared.b32 t1, [%64+4736];\nadd.s64 d, %65, 136;\nwgmma.fence.sync.aligned;\nwgmma.mma_async.sync.aligned.m64n64k16.f32.bf16.bf16 {%0, %1, %2, %3, %4, %5, %6, %7, %8, %9, %10, %11, %12, %13, %14, %15, %16, %17, %18, %19, %20, %21, %22, %23, %24, %25, %26, %27, %28, %29, %30, %31}, {b0, b1, b2, b3}, d, 1, 1, 1, 0;\nwgmma.commit_group.sync.aligned;\nwgmma.wait_group.sync.aligned 1;\nmov.b32 a2, b1;\nmov.b32 a0, t0;\nmov.b32 a3, t0;\nmov.b32 a1, t1;\n"
        "ld.shared.b32 t0, [%64+4864];\nld.shared.b32 t1, [%64+4992];\nadd.s64 d, %65, 144;\nwgmma.fence.sync.aligned;\nwgmma.mma_async.sync.aligned.m64n56k16.f32.bf16.bf16 {%0, %1, %2, %3, %4, %5, %6, %7, %8, %9, %10, %11, %12, %13, %14, %15, %16, %17, %18, %19, %20, %21, %22, %23, %24, %25, %26, %27}, {a0, a1, a2, a3}, d, 1, 1, 1, 0;\nwgmma.commit_group.sync.aligned;\nwgmma.wait_group.sync.aligned 1;\nmov.b32 b2, a1;\nmov.b32 b0, t0;\nmov.b32 b3, t0;\nmov.b32 b1, t1;\n"
        "ld.shared.b32 t0, [%64+5120];\nld.shared.b32 t1, [%64+5248];\nadd.s64 d, %65, 152;\nwgmma.fence.sync.aligned;\nwgmma.mma_async.sync.aligned.m64n56k16.f32.bf16.bf16 {%0, %1, %2, %3, %4, %5, %6, %7, %8, %9, %10, %11, %12, %13, %14, %15, %16, %17, %18, %19, %20, %21, %22, %23, %24, %25, %26, %27}, {b0, b1, b2, b3}, d, 1, 1, 1, 0;\nwgmma.commit_group.sync.aligned;\nwgmma.wait_group.sync.aligned 1;\nmov.b32 a2, b1;\nmov.b32 a0, t0;\nmov.b32 a3, t0;\nmov.b32 a1, t1;\n"
        "ld.shared.b32 t0, [%64+5376];\nld.shared.b32 t1, [%64+5504];\nadd.s64 d, %65, 160;\nwgmma.fence.sync.aligned;\nwgmma.mma_async.sync.aligned.m64n48k16.f32.bf16.bf16 {%0, %1, %2, %3, %4, %5, %6, %7, %8, %9, %10, %11, %12, %13, %14, %15, %16, %17, %18, %19, %20, %21, %22, %23}, {a0, a1, a2, a3}, d, 1, 1, 1, 0;\nwgmma.commit_group.sync.aligned;\nwgmma.wait_group.sync.aligned 1;\nmov.b32 b2, a1;\nmov.b32 b0, t0;\nmov.b32 b3, t0;\nmov.b32 b1, t1;\n"
        "ld.shared.b32 t0, [%64+5632];\nld.shared.b32 t1, [%64+5760];\nadd.s64 d, %65, 168;\nwgmma.fence.sync.aligned;\nwgmma.mma_async.sync.aligned.m64n48k16.f32.bf16.bf16 {%0, %1, %2, %3, %4, %5, %6, %7, %8, %9, %10, %11, %12, %13, %14, %15, %16, %17, %18, %19, %20, %21, %22, %23}, {b0, b1, b2, b3}, d, 1, 1, 1, 0;\nwgmma.commit_group.sync.aligned;\nwgmma.wait_group.sync.aligned 1;\nmov.b32 a2, b1;\nmov.b32 a0, t0;\nmov.b32 a3, t0;\nmov.b32 a1, t1;\n"
        "ld.shared.b32 t0, [%64+5888];\nld.shared.b32 t1, [%64+6016];\nadd.s64 d, %65, 176;\nwgmma.fence.sync.aligned;\nwgmma.mma_async.sync.aligned.m64n40k16.f32.bf16.bf16 {%0, %1, %2, %3, %4, %5, %6, %7, %8, %9, %10, %11, %12, %13, %14, %15, %16, %17, %18, %19}, {a0, a1, a2, a3}, d, 1, 1, 1, 0;\nwgmma.commit_group.sync.aligned;\nwgmma.wait_group.sync.aligned 1;\nmov.b32 b2, a1;\nmov.b32 b0, t0;\nmov.b32 b3, t0;\nmov.b32 b1, t1;\n"
        "ld.shared.b32 t0, [%64+6144];\nld.shared.b32 t1, [%64+6272];\nadd.s64 d, %65, 184;\nwgmma.fence.sync.aligned;\nwgmma.mma_async.sync.aligned.m64n40k16.f32.bf16.bf16 {%0, %1, %2, %3, %4, %5, %6, %7, %8, %9, %10, %11, %12, %13, %14, %15, %16, %17, %18, %19}, {b0, b1, b2, b3}, d, 1, 1, 1, 0;\nwgmma.commit_group.sync.aligned;\nwgmma.wait_group.sync.aligned 1;\nmov.b32 a2, b1;\nmov.b32 a0, t0;\nmov.b32 a3, t0;\nmov.b32 a1, t1;\n"
        "ld.shared.b32 t0, [%64+6400];\nld.shared.b32 t1, [%64+6528];\nadd.s64 d, %65, 192;\nwgmma.fence.sync.aligned;\nwgmma.mma_async.sync.aligned.m64n32k16.f32.bf16.bf16 {%0, %1, %2, %3, %4, %5, %6, %7, %8, %9, %10, %11, %12, %13, %14, %15}, {a0, a1, a2, a3}, d, 1, 1, 1, 0;\nwgmma.commit_group.sync.aligned;\nwgmma.wait_group.sync.aligned 1;\nmov.b32 b2, a1;\nmov.b32 b0, t0;\nmov.b32 b3, t0;\nmov.b32 b1, t1;\n"
        "ld.shared.b32 t0, [%64+6656];\nld.shared.b32 t1, [%64+6784];\nadd.s64 d, %65, 200;\nwgmma.fence.sync.aligned;\nwgmma.mma_async.sync.aligned.m64n32k16.f32.bf16.bf16 {%0, %1, %2, %3, %4, %5, %6, %7, %8, %9, %10, %11, %12, %13, %14, %15}, {b0, b1, b2, b3}, d, 1, 1, 1, 0;\nwgmma.commit_group.sync.aligned;\nwgmma.wait_group.sync.aligned 1;\nmov.b32 a2, b1;\nmov.b32 a0, t0;\nmov.b32 a3, t0;\nmov.b32 a1, t1;\n"
        "ld.shared.b32 t0, [%64+6912];\nld.shared.b32 t1, [%64+7040];\nadd.s64 d, %65, 208;\nwgmma.fence.sync.aligned;\nwgmma.mma_async.sync.aligned.m64n24k16.f32.bf16.bf16 {%0, %1, %2, %3, %4, %5, %6, %7, %8, %9, %10, %11}, {a0, a1, a2, a3}, d, 1, 1, 1, 0;\nwgmma.commit_group.sync.aligned;\nwgmma.wait_group.sync.aligned 1;\nmov.b32 b2, a1;\nmov.b32 b0, t0;\nmov.b32 b3, t0;\nmov.b32 b1, t1;\n"
        "ld.shared.b32 t0, [%64+7168];\nld.shared.b32 t1, [%64+7296];\nadd.s64 d, %65, 216;\nwgmma.fence.sync.aligned;\nwgmma.mma_async.sync.aligned.m64n24k16.f32.bf16.bf16 {%0, %1, %2, %3, %4, %5, %6, %7, %8, %9, %10, %11}, {b0, b1, b2, b3}, d, 1, 1, 1, 0;\nwgmma.commit_group.sync.aligned;\nwgmma.wait_group.sync.aligned 1;\nmov.b32 a2, b1;\nmov.b32 a0, t0;\nmov.b32 a3, t0;\nmov.b32 a1, t1;\n"
        "ld.shared.b32 t0, [%64+7424];\nld.shared.b32 t1, [%64+7552];\nadd.s64 d, %65, 224;\nwgmma.fence.sync.aligned;\nwgmma.mma_async.sync.aligned.m64n16k16.f32.bf16.bf16 {%0, %1, %2, %3, %4, %5, %6, %7}, {a0, a1, a2, a3}, d, 1, 1, 1, 0;\nwgmma.commit_group.sync.aligned;\nwgmma.wait_group.sync.aligned 1;\nmov.b32 b2, a1;\nmov.b32 b0, t0;\nmov.b32 b3, t0;\nmov.b32 b1, t1;\n"
        "ld.shared.b32 t0, [%64+7680];\nld.shared.b32 t1, [%64+7808];\nadd.s64 d, %65, 232;\nwgmma.fence.sync.aligned;\nwgmma.mma_async.sync.aligned.m64n16k16.f32.bf16.bf16 {%0, %1, %2, %3, %4, %5, %6, %7}, {b0, b1, b2, b3}, d, 1, 1, 1, 0;\nwgmma.commit_group.sync.aligned;\nwgmma.wait_group.sync.aligned 1;\nmov.b32 a2, b1;\nmov.b32 a0, t0;\nmov.b32 a3, t0;\nmov.b32 a1, t1;\n"
        "ld.shared.b32 t0, [%64+7936];\nld.shared.b32 t1, [%64+8064];\nadd.s64 d, %65, 240;\nwgmma.fence.sync.aligned;\nwgmma.mma_async.sync.aligned.m64n8k16.f32.bf16.bf16 {%0, %1, %2, %3}, {a0, a1, a2, a3}, d, 1, 1, 1, 0;\nwgmma.commit_group.sync.aligned;\nwgmma.wait_group.sync.aligned 1;\nmov.b32 b2, a1;\nmov.b32 b0, t0;\nmov.b32 b3, t0;\nmov.b32 b1, t1;\n"
        "add.s64 d, %65, 248;\nwgmma.fence.sync.aligned;\nwgmma.mma_async.sync.aligned.m64n8k16.f32.bf16.bf16 {%0, %1, %2, %3}, {b0, b1, b2, b3}, d, 1, 1, 1, 0;\nwgmma.commit_group.sync.aligned;\nwgmma.wait_group.sync.aligned 0;\n"
        "}" : "+f"(d[0]), "+f"(d[1]), "+f"(d[2]), "+f"(d[3]), "+f"(d[4]), "+f"(d[5]), "+f"(d[6]), "+f"(d[7]), "+f"(d[8]), "+f"(d[9]), "+f"(d[10]), "+f"(d[11]), "+f"(d[12]), "+f"(d[13]), "+f"(d[14]), "+f"(d[15]), "+f"(d[16]), "+f"(d[17]), "+f"(d[18]), "+f"(d[19]), "+f"(d[20]), "+f"(d[21]), "+f"(d[22]), "+f"(d[23]), "+f"(d[24]), "+f"(d[25]), "+f"(d[26]), "+f"(d[27]), "+f"(d[28]), "+f"(d[29]), "+f"(d[30]), "+f"(d[31]), "+f"(d[32]), "+f"(d[33]), "+f"(d[34]), "+f"(d[35]), "+f"(d[36]), "+f"(d[37]), "+f"(d[38]), "+f"(d[39]), "+f"(d[40]), "+f"(d[41]), "+f"(d[42]), "+f"(d[43]), "+f"(d[44]), "+f"(d[45]), "+f"(d[46]), "+f"(d[47]), "+f"(d[48]), "+f"(d[49]), "+f"(d[50]), "+f"(d[51]), "+f"(d[52]), "+f"(d[53]), "+f"(d[54]), "+f"(d[55]), "+f"(d[56]), "+f"(d[57]), "+f"(d[58]), "+f"(d[59]), "+f"(d[60]), "+f"(d[61]), "+f"(d[62]), "+f"(d[63]) : "r"(pa), "l"(db) : "memory");
}
__device__ __forceinline__ void wgmma_rs80(float (&d)[40], uint32_t a0, uint32_t a1, uint32_t a2, uint32_t a3, uint64_t db, int sc) {
    asm volatile("{\n.reg .pred p;\nsetp.ne.b32 p, %45, 0;\n"
        "wgmma.mma_async.sync.aligned.m64n80k16.f32.bf16.bf16 {%0, %1, %2, %3, %4, %5, %6, %7, %8, %9, %10, %11, %12, %13, %14, %15, %16, %17, %18, %19, %20, %21, %22, %23, %24, %25, %26, %27, %28, %29, %30, %31, %32, %33, %34, %35, %36, %37, %38, %39}, {%40, %41, %42, %43}, %44, p, 1, 1, 1;\n}\n"
        : "+f"(d[0]), "+f"(d[1]), "+f"(d[2]), "+f"(d[3]), "+f"(d[4]), "+f"(d[5]), "+f"(d[6]), "+f"(d[7]), "+f"(d[8]), "+f"(d[9]), "+f"(d[10]), "+f"(d[11]), "+f"(d[12]), "+f"(d[13]), "+f"(d[14]), "+f"(d[15]), "+f"(d[16]), "+f"(d[17]), "+f"(d[18]), "+f"(d[19]), "+f"(d[20]), "+f"(d[21]), "+f"(d[22]), "+f"(d[23]), "+f"(d[24]), "+f"(d[25]), "+f"(d[26]), "+f"(d[27]), "+f"(d[28]), "+f"(d[29]), "+f"(d[30]), "+f"(d[31]), "+f"(d[32]), "+f"(d[33]), "+f"(d[34]), "+f"(d[35]), "+f"(d[36]), "+f"(d[37]), "+f"(d[38]), "+f"(d[39]) : "r"(a0), "r"(a1), "r"(a2), "r"(a3), "l"(db), "r"(sc));
}
__device__ __forceinline__ void wgmma_ss80(float (&d)[40], uint64_t da, uint64_t db, int sc) {
    asm volatile("{\n.reg .pred p;\nsetp.ne.b32 p, %42, 0;\n"
        "wgmma.mma_async.sync.aligned.m64n80k16.f32.bf16.bf16 {%0, %1, %2, %3, %4, %5, %6, %7, %8, %9, %10, %11, %12, %13, %14, %15, %16, %17, %18, %19, %20, %21, %22, %23, %24, %25, %26, %27, %28, %29, %30, %31, %32, %33, %34, %35, %36, %37, %38, %39}, %40, %41, p, 1, 1, 0, 1;\n}\n"
        : "+f"(d[0]), "+f"(d[1]), "+f"(d[2]), "+f"(d[3]), "+f"(d[4]), "+f"(d[5]), "+f"(d[6]), "+f"(d[7]), "+f"(d[8]), "+f"(d[9]), "+f"(d[10]), "+f"(d[11]), "+f"(d[12]), "+f"(d[13]), "+f"(d[14]), "+f"(d[15]), "+f"(d[16]), "+f"(d[17]), "+f"(d[18]), "+f"(d[19]), "+f"(d[20]), "+f"(d[21]), "+f"(d[22]), "+f"(d[23]), "+f"(d[24]), "+f"(d[25]), "+f"(d[26]), "+f"(d[27]), "+f"(d[28]), "+f"(d[29]), "+f"(d[30]), "+f"(d[31]), "+f"(d[32]), "+f"(d[33]), "+f"(d[34]), "+f"(d[35]), "+f"(d[36]), "+f"(d[37]), "+f"(d[38]), "+f"(d[39]) : "l"(da), "l"(db), "r"(sc));
}
__device__ __forceinline__ void wgmma_ss80t(float (&d)[40], uint64_t da, uint64_t db, int sc) {
    asm volatile("{\n.reg .pred p;\nsetp.ne.b32 p, %42, 0;\n"
        "wgmma.mma_async.sync.aligned.m64n80k16.f32.bf16.bf16 {%0, %1, %2, %3, %4, %5, %6, %7, %8, %9, %10, %11, %12, %13, %14, %15, %16, %17, %18, %19, %20, %21, %22, %23, %24, %25, %26, %27, %28, %29, %30, %31, %32, %33, %34, %35, %36, %37, %38, %39}, %40, %41, p, 1, 1, 1, 1;\n}\n"
        : "+f"(d[0]), "+f"(d[1]), "+f"(d[2]), "+f"(d[3]), "+f"(d[4]), "+f"(d[5]), "+f"(d[6]), "+f"(d[7]), "+f"(d[8]), "+f"(d[9]), "+f"(d[10]), "+f"(d[11]), "+f"(d[12]), "+f"(d[13]), "+f"(d[14]), "+f"(d[15]), "+f"(d[16]), "+f"(d[17]), "+f"(d[18]), "+f"(d[19]), "+f"(d[20]), "+f"(d[21]), "+f"(d[22]), "+f"(d[23]), "+f"(d[24]), "+f"(d[25]), "+f"(d[26]), "+f"(d[27]), "+f"(d[28]), "+f"(d[29]), "+f"(d[30]), "+f"(d[31]), "+f"(d[32]), "+f"(d[33]), "+f"(d[34]), "+f"(d[35]), "+f"(d[36]), "+f"(d[37]), "+f"(d[38]), "+f"(d[39]) : "l"(da), "l"(db), "r"(sc));
}
__device__ __forceinline__ void wgmma_ss8_ta(float (&d)[4], uint64_t da, uint64_t db, int sc) {
    asm volatile("{\n.reg .pred p;\nsetp.ne.b32 p, %6, 0;\n"
        "wgmma.mma_async.sync.aligned.m64n8k16.f32.bf16.bf16 {%0, %1, %2, %3}, %4, %5, p, 1, 1, 1, 0;\n}\n"
        : "+f"(d[0]), "+f"(d[1]), "+f"(d[2]), "+f"(d[3]) : "l"(da), "l"(db), "r"(sc));
}
__device__ __forceinline__ void wgmma_rs8(float (&d)[4], uint32_t a0, uint32_t a1, uint32_t a2, uint32_t a3, uint64_t db, int sc) {
    asm volatile("{\n.reg .pred p;\nsetp.ne.b32 p, %9, 0;\n"
        "wgmma.mma_async.sync.aligned.m64n8k16.f32.bf16.bf16 {%0, %1, %2, %3}, {%4, %5, %6, %7}, %8, p, 1, 1, 0;\n}\n"
        : "+f"(d[0]), "+f"(d[1]), "+f"(d[2]), "+f"(d[3]) : "r"(a0), "r"(a1), "r"(a2), "r"(a3), "l"(db), "r"(sc));
}
__device__ __forceinline__ void wgmma_rs128(float (&d)[64], uint32_t a0, uint32_t a1, uint32_t a2, uint32_t a3, uint64_t db, int sc) {
    asm volatile("{\n.reg .pred p;\nsetp.ne.b32 p, %69, 0;\n"
        "wgmma.mma_async.sync.aligned.m64n128k16.f32.bf16.bf16 {%0, %1, %2, %3, %4, %5, %6, %7, %8, %9, %10, %11, %12, %13, %14, %15, %16, %17, %18, %19, %20, %21, %22, %23, %24, %25, %26, %27, %28, %29, %30, %31, %32, %33, %34, %35, %36, %37, %38, %39, %40, %41, %42, %43, %44, %45, %46, %47, %48, %49, %50, %51, %52, %53, %54, %55, %56, %57, %58, %59, %60, %61, %62, %63}, {%64, %65, %66, %67}, %68, p, 1, 1, 1;\n}\n"
        : "+f"(d[0]), "+f"(d[1]), "+f"(d[2]), "+f"(d[3]), "+f"(d[4]), "+f"(d[5]), "+f"(d[6]), "+f"(d[7]), "+f"(d[8]), "+f"(d[9]), "+f"(d[10]), "+f"(d[11]), "+f"(d[12]), "+f"(d[13]), "+f"(d[14]), "+f"(d[15]), "+f"(d[16]), "+f"(d[17]), "+f"(d[18]), "+f"(d[19]), "+f"(d[20]), "+f"(d[21]), "+f"(d[22]), "+f"(d[23]), "+f"(d[24]), "+f"(d[25]), "+f"(d[26]), "+f"(d[27]), "+f"(d[28]), "+f"(d[29]), "+f"(d[30]), "+f"(d[31]), "+f"(d[32]), "+f"(d[33]), "+f"(d[34]), "+f"(d[35]), "+f"(d[36]), "+f"(d[37]), "+f"(d[38]), "+f"(d[39]), "+f"(d[40]), "+f"(d[41]), "+f"(d[42]), "+f"(d[43]), "+f"(d[44]), "+f"(d[45]), "+f"(d[46]), "+f"(d[47]), "+f"(d[48]), "+f"(d[49]), "+f"(d[50]), "+f"(d[51]), "+f"(d[52]), "+f"(d[53]), "+f"(d[54]), "+f"(d[55]), "+f"(d[56]), "+f"(d[57]), "+f"(d[58]), "+f"(d[59]), "+f"(d[60]), "+f"(d[61]), "+f"(d[62]), "+f"(d[63]) : "r"(a0), "r"(a1), "r"(a2), "r"(a3), "l"(db), "r"(sc));
}
__device__ __forceinline__ void wgmma_rs88(float (&d)[44], uint32_t a0, uint32_t a1, uint32_t a2, uint32_t a3, uint64_t db, int sc) {
    asm volatile("{\n.reg .pred p;\nsetp.ne.b32 p, %49, 0;\n"
        "wgmma.mma_async.sync.aligned.m64n88k16.f32.bf16.bf16 {%0, %1, %2, %3, %4, %5, %6, %7, %8, %9, %10, %11, %12, %13, %14, %15, %16, %17, %18, %19, %20, %21, %22, %23, %24, %25, %26, %27, %28, %29, %30, %31, %32, %33, %34, %35, %36, %37, %38, %39, %40, %41, %42, %43}, {%44, %45, %46, %47}, %48, p, 1, 1, 1;\n}\n"
        : "+f"(d[0]), "+f"(d[1]), "+f"(d[2]), "+f"(d[3]), "+f"(d[4]), "+f"(d[5]), "+f"(d[6]), "+f"(d[7]), "+f"(d[8]), "+f"(d[9]), "+f"(d[10]), "+f"(d[11]), "+f"(d[12]), "+f"(d[13]), "+f"(d[14]), "+f"(d[15]), "+f"(d[16]), "+f"(d[17]), "+f"(d[18]), "+f"(d[19]), "+f"(d[20]), "+f"(d[21]), "+f"(d[22]), "+f"(d[23]), "+f"(d[24]), "+f"(d[25]), "+f"(d[26]), "+f"(d[27]), "+f"(d[28]), "+f"(d[29]), "+f"(d[30]), "+f"(d[31]), "+f"(d[32]), "+f"(d[33]), "+f"(d[34]), "+f"(d[35]), "+f"(d[36]), "+f"(d[37]), "+f"(d[38]), "+f"(d[39]), "+f"(d[40]), "+f"(d[41]), "+f"(d[42]), "+f"(d[43]) : "r"(a0), "r"(a1), "r"(a2), "r"(a3), "l"(db), "r"(sc));
}
__device__ __forceinline__ void wgmma_rs128k(float (&d)[64], uint32_t a0, uint32_t a1, uint32_t a2, uint32_t a3, uint64_t db, int sc) {
    asm volatile("{\n.reg .pred p;\nsetp.ne.b32 p, %69, 0;\n"
        "wgmma.mma_async.sync.aligned.m64n128k16.f32.bf16.bf16 {%0, %1, %2, %3, %4, %5, %6, %7, %8, %9, %10, %11, %12, %13, %14, %15, %16, %17, %18, %19, %20, %21, %22, %23, %24, %25, %26, %27, %28, %29, %30, %31, %32, %33, %34, %35, %36, %37, %38, %39, %40, %41, %42, %43, %44, %45, %46, %47, %48, %49, %50, %51, %52, %53, %54, %55, %56, %57, %58, %59, %60, %61, %62, %63}, {%64, %65, %66, %67}, %68, p, 1, 1, 0;\n}\n"
        : "+f"(d[0]), "+f"(d[1]), "+f"(d[2]), "+f"(d[3]), "+f"(d[4]), "+f"(d[5]), "+f"(d[6]), "+f"(d[7]), "+f"(d[8]), "+f"(d[9]), "+f"(d[10]), "+f"(d[11]), "+f"(d[12]), "+f"(d[13]), "+f"(d[14]), "+f"(d[15]), "+f"(d[16]), "+f"(d[17]), "+f"(d[18]), "+f"(d[19]), "+f"(d[20]), "+f"(d[21]), "+f"(d[22]), "+f"(d[23]), "+f"(d[24]), "+f"(d[25]), "+f"(d[26]), "+f"(d[27]), "+f"(d[28]), "+f"(d[29]), "+f"(d[30]), "+f"(d[31]), "+f"(d[32]), "+f"(d[33]), "+f"(d[34]), "+f"(d[35]), "+f"(d[36]), "+f"(d[37]), "+f"(d[38]), "+f"(d[39]), "+f"(d[40]), "+f"(d[41]), "+f"(d[42]), "+f"(d[43]), "+f"(d[44]), "+f"(d[45]), "+f"(d[46]), "+f"(d[47]), "+f"(d[48]), "+f"(d[49]), "+f"(d[50]), "+f"(d[51]), "+f"(d[52]), "+f"(d[53]), "+f"(d[54]), "+f"(d[55]), "+f"(d[56]), "+f"(d[57]), "+f"(d[58]), "+f"(d[59]), "+f"(d[60]), "+f"(d[61]), "+f"(d[62]), "+f"(d[63]) : "r"(a0), "r"(a1), "r"(a2), "r"(a3), "l"(db), "r"(sc));
}
__device__ __forceinline__ void wgmma_rs88k(float (&d)[44], uint32_t a0, uint32_t a1, uint32_t a2, uint32_t a3, uint64_t db, int sc) {
    asm volatile("{\n.reg .pred p;\nsetp.ne.b32 p, %49, 0;\n"
        "wgmma.mma_async.sync.aligned.m64n88k16.f32.bf16.bf16 {%0, %1, %2, %3, %4, %5, %6, %7, %8, %9, %10, %11, %12, %13, %14, %15, %16, %17, %18, %19, %20, %21, %22, %23, %24, %25, %26, %27, %28, %29, %30, %31, %32, %33, %34, %35, %36, %37, %38, %39, %40, %41, %42, %43}, {%44, %45, %46, %47}, %48, p, 1, 1, 0;\n}\n"
        : "+f"(d[0]), "+f"(d[1]), "+f"(d[2]), "+f"(d[3]), "+f"(d[4]), "+f"(d[5]), "+f"(d[6]), "+f"(d[7]), "+f"(d[8]), "+f"(d[9]), "+f"(d[10]), "+f"(d[11]), "+f"(d[12]), "+f"(d[13]), "+f"(d[14]), "+f"(d[15]), "+f"(d[16]), "+f"(d[17]), "+f"(d[18]), "+f"(d[19]), "+f"(d[20]), "+f"(d[21]), "+f"(d[22]), "+f"(d[23]), "+f"(d[24]), "+f"(d[25]), "+f"(d[26]), "+f"(d[27]), "+f"(d[28]), "+f"(d[29]), "+f"(d[30]), "+f"(d[31]), "+f"(d[32]), "+f"(d[33]), "+f"(d[34]), "+f"(d[35]), "+f"(d[36]), "+f"(d[37]), "+f"(d[38]), "+f"(d[39]), "+f"(d[40]), "+f"(d[41]), "+f"(d[42]), "+f"(d[43]) : "r"(a0), "r"(a1), "r"(a2), "r"(a3), "l"(db), "r"(sc));
}
__device__ __forceinline__ void wgmma_rs80k(float (&d)[40], uint32_t a0, uint32_t a1, uint32_t a2, uint32_t a3, uint64_t db, int sc) {
    asm volatile("{\n.reg .pred p;\nsetp.ne.b32 p, %45, 0;\n"
        "wgmma.mma_async.sync.aligned.m64n80k16.f32.bf16.bf16 {%0, %1, %2, %3, %4, %5, %6, %7, %8, %9, %10, %11, %12, %13, %14, %15, %16, %17, %18, %19, %20, %21, %22, %23, %24, %25, %26, %27, %28, %29, %30, %31, %32, %33, %34, %35, %36, %37, %38, %39}, {%40, %41, %42, %43}, %44, p, 1, 1, 0;\n}\n"
        : "+f"(d[0]), "+f"(d[1]), "+f"(d[2]), "+f"(d[3]), "+f"(d[4]), "+f"(d[5]), "+f"(d[6]), "+f"(d[7]), "+f"(d[8]), "+f"(d[9]), "+f"(d[10]), "+f"(d[11]), "+f"(d[12]), "+f"(d[13]), "+f"(d[14]), "+f"(d[15]), "+f"(d[16]), "+f"(d[17]), "+f"(d[18]), "+f"(d[19]), "+f"(d[20]), "+f"(d[21]), "+f"(d[22]), "+f"(d[23]), "+f"(d[24]), "+f"(d[25]), "+f"(d[26]), "+f"(d[27]), "+f"(d[28]), "+f"(d[29]), "+f"(d[30]), "+f"(d[31]), "+f"(d[32]), "+f"(d[33]), "+f"(d[34]), "+f"(d[35]), "+f"(d[36]), "+f"(d[37]), "+f"(d[38]), "+f"(d[39]) : "r"(a0), "r"(a1), "r"(a2), "r"(a3), "l"(db), "r"(sc));
}
__device__ __forceinline__ void wgmma_rs64(float (&d)[32], uint32_t a0, uint32_t a1, uint32_t a2, uint32_t a3, uint64_t db, int sc) {
    asm volatile("{\n.reg .pred p;\nsetp.ne.b32 p, %37, 0;\n"
        "wgmma.mma_async.sync.aligned.m64n64k16.f32.bf16.bf16 {%0, %1, %2, %3, %4, %5, %6, %7, %8, %9, %10, %11, %12, %13, %14, %15, %16, %17, %18, %19, %20, %21, %22, %23, %24, %25, %26, %27, %28, %29, %30, %31}, {%32, %33, %34, %35}, %36, p, 1, 1, 1;\n}\n"
        : "+f"(d[0]), "+f"(d[1]), "+f"(d[2]), "+f"(d[3]), "+f"(d[4]), "+f"(d[5]), "+f"(d[6]), "+f"(d[7]), "+f"(d[8]), "+f"(d[9]), "+f"(d[10]), "+f"(d[11]), "+f"(d[12]), "+f"(d[13]), "+f"(d[14]), "+f"(d[15]), "+f"(d[16]), "+f"(d[17]), "+f"(d[18]), "+f"(d[19]), "+f"(d[20]), "+f"(d[21]), "+f"(d[22]), "+f"(d[23]), "+f"(d[24]), "+f"(d[25]), "+f"(d[26]), "+f"(d[27]), "+f"(d[28]), "+f"(d[29]), "+f"(d[30]), "+f"(d[31]) : "r"(a0), "r"(a1), "r"(a2), "r"(a3), "l"(db), "r"(sc));
}

__device__ __forceinline__ uint64_t mkdesc(uint32_t lo) { return ((uint64_t)0x40000040u << 32) | lo; }
template <int F> __device__ __forceinline__ uint32_t lop3(uint32_t a, uint32_t b, uint32_t c) { uint32_t r; asm("lop3.b32 %0, %1, %2, %3, %4;" : "=r"(r) : "r"(a), "r"(b), "r"(c), "n"(F)); return r; }
__device__ __forceinline__ void stg128_tag(void* p, uint32_t x, uint32_t y, uint32_t z, uint32_t u, uint32_t ep, int w) {
    stg128(p, lop3<0xB8>(x, w == 0, ep), lop3<0xB8>(y, w == 1, ep), lop3<0xB8>(z, w == 2, ep), lop3<0xB8>(u, w == 3, ep));
}
__device__ __forceinline__ uint32_t tag(uint32_t w, uint32_t ep) { asm("lop3.b32 %0, %0, 1, %1, 0xB8;" : "+r"(w) : "r"(ep)); return w; }
template <int N> __device__ __forceinline__ void pack_part(uint32_t (&p)[32], const float (&v)[N], uint32_t ep) {
#pragma unroll
    for (int i = 0; i < N / 2; i++) p[i] = (i & 3) ? pack2(v[2 * i], v[2 * i + 1]) : tag(pack2(v[2 * i], v[2 * i + 1]), ep);
#pragma unroll
    for (int i = 0; i < N / 2; i++) asm volatile("" : "+r"(p[i]));
}
__device__ __forceinline__ void st_part(uint4* p, const uint32_t* v) {
    asm volatile("{\n.reg .b64 l, h;\n.reg .b128 q;\nmov.b64 l, {%1, %2};\nmov.b64 h, {%3, %4};\nmov.b128 q, {l, h};\nst.relaxed.gpu.global.b128 [%0], q;\n}"
                 ::"l"(p), "r"(v[0]), "r"(v[1]), "r"(v[2]), "r"(v[3]) : "memory");
}
__device__ __forceinline__ void st_peer(uint32_t a, uint32_t x, uint32_t y, uint32_t z, uint32_t w, uint32_t bar) {
    asm volatile("st.async.shared::cluster.mbarrier::complete_tx::bytes.v4.b32 [%0], {%1, %2, %3, %4}, [%5];" ::"r"(a), "r"(x), "r"(y), "r"(z), "r"(w), "r"(bar) : "memory");
}
__device__ __forceinline__ int g4_block(int c, int j) { return c ? j ^ (8 - 2 * c) : 8 + (j & 1); }
__device__ __forceinline__ uint32_t recv_off(int w) { return w ? OFF_XR : OFF_REM; }
__device__ __forceinline__ uint4 ld_part(const void* p) {
    uint4 v;
    asm volatile("{\n.reg .b64 l, h;\n.reg .b128 q;\nld.relaxed.gpu.global.b128 q, [%4];\nmov.b128 {l, h}, q;\nmov.b64 {%0, %1}, l;\nmov.b64 {%2, %3}, h;\n}"
                 : "=r"(v.x), "=r"(v.y), "=r"(v.z), "=r"(v.w) : "l"(p) : "memory");
    return v;
}
__device__ __forceinline__ void ld_part4(uint4 (&u)[4], const uint4* p, int st) {
#pragma unroll
    for (int i = 0; i < 4; i++) u[i] = ld_part(p + i * st);
}
__device__ __forceinline__ uint32_t stale4(const uint4 (&u)[4], uint32_t ep) { return (u[0].x ^ ep) | (u[1].x ^ ep) | (u[2].x ^ ep) | (u[3].x ^ ep); }
__device__ __forceinline__ void fix4(uint4 (&u)[4], const uint4* p, uint32_t ep, int code) {
    unsigned it = 0;
    while (__any_sync(~0u, stale4(u, ep) & 1)) {
        ld_part4(u, p, 128);
        STALE(code)
        SPIN_CHECK(58)
    }
}
__device__ __forceinline__ void add8(float* v, uint4 u) {
    v[0] += blo(u.x); v[1] += bhi(u.x); v[2] += blo(u.y); v[3] += bhi(u.y);
    v[4] += blo(u.z); v[5] += bhi(u.z); v[6] += blo(u.w); v[7] += bhi(u.w);
}
__device__ __forceinline__ void unpack8(float* v, uint4 u) {
    v[0] = blo(u.x); v[1] = bhi(u.x); v[2] = blo(u.y); v[3] = bhi(u.y); v[4] = blo(u.z); v[5] = bhi(u.z); v[6] = blo(u.w); v[7] = bhi(u.w);
}
__device__ __forceinline__ uint4 add2(uint4 a, uint4 b) { return make_uint4(add2(a.x, b.x), add2(a.y, b.y), add2(a.z, b.z), add2(a.w, b.w)); }
__device__ __forceinline__ void base16(float* v, uint4 b, float2 c, float2 d) {
    v[0] = fmaf(c.x, v[0], blo(b.x)); v[1] = fmaf(c.y, v[1], bhi(b.x)); v[2] = fmaf(c.x, v[2], blo(b.y)); v[3] = fmaf(c.y, v[3], bhi(b.y));
    v[4] = fmaf(d.x, v[4], blo(b.z)); v[5] = fmaf(d.y, v[5], bhi(b.z)); v[6] = fmaf(d.x, v[6], blo(b.w)); v[7] = fmaf(d.y, v[7], bhi(b.w));
}
__device__ __forceinline__ uint32_t split2(float x) { const float h = rbf(x); return pack2(h, x - h); }
__device__ __forceinline__ uint32_t b80_desc(uint32_t dsb, uint32_t wn, uint32_t rn, uint32_t h) {
    const uint32_t wb = dsb + OFF_W + (wn & 7) * 16384 + h * 8192, rm = dsb + OFF_REM + rn * 4096 + h * 2048;
    return (wb >> 4) | ((rm - wb) << 12);
}
constexpr int64_t B80_STEP = 128 - (126 << 16), B80_HALF = 512 - (384 << 16);
__device__ __forceinline__ int g3_stream(int i) { return i < XLEAD ? 0 : i >= 20 - XLEAD ? 1 : ((i - XLEAD) & 1) ^ 1; }
__device__ __forceinline__ int g3_block(int i) { return i < XLEAD ? i : i >= 20 - XLEAD ? i - 10 : (i + (g3_stream(i) ? -XLEAD : XLEAD)) >> 1; }
__device__ __forceinline__ int g1_block(int n, int j) { return n < 5 ? 2 * n + (j & 1) : 2 * n - 9 - (j & 1); }

template <int OCT>
__device__ __forceinline__ void gemv_tile(float (&d)[4], uint32_t a, uint32_t b, int kb0) {
    uint32_t alo = ((a & 0x3FFFF) >> 4) | 0x10000u, blo_ = ((b & 0x3FFFF) >> 4) | (OCT << 16);
#pragma unroll 1
    for (int s = 0; s < 20; s += 4) {
        const int kb = kb0 + (s >> 2);
        const uint32_t bk = blo_ + (OCT == 7 ? (kb & 1) * 288 + (kb >> 1) * 56 : kb * 64);
        wg_fence();
#pragma unroll
        for (int q = 0; q < 4; q++) wgmma_ss8_ta(d, mkdesc(alo + (s + q) * 128), ((uint64_t)8 << 32) | (bk + q * 2 * OCT), s + q);
        wg_commit();
    }
    wg_wait<0>();
    reg_fence(d);
}

__device__ __forceinline__ void flush_tile(uint32_t st, bf16* dst, int u) {
#pragma unroll
    for (int i = 0; i < 2; i++) {
        const int idx = u + 320 * i, row = idx >> 3, c = idx & 7;
        stg128(dst + (size_t)row * S_ + 8 * c, lds128(st + row * 128 + ((c ^ ((row >> 1) & 7)) << 4)));
    }
}

__device__ __forceinline__ int tid_now() { int t; asm volatile("mov.u32 %0, %%tid.x;" : "=r"(t)); return t; }
__device__ __forceinline__ float zscale(float c) { return c == 0.f ? 0x1p-30f : c; }
__device__ __forceinline__ bool bar_any(int id, bool p) {
    uint32_t r;
    asm volatile("{\n.reg .pred a, b;\nsetp.ne.u32 a, %2, 0;\nbarrier.red.or.pred.aligned b, %1, 128, a;\nselp.u32 %0, 1, 0, b;\n}" : "=r"(r) : "r"(id), "r"((uint32_t)p) : "memory");
    return r != 0;
}

__global__ void __launch_bounds__(NTHR, 1) fused_kernel(const __grid_constant__ Ptrs pp, bf16* __restrict__ out, const __grid_constant__ Maps mp) {
    extern __shared__ __align__(1024) uint8_t smem_raw[];
    const uint32_t sb = s2u(smem_raw), bars = sb + M_BAR, dsb = sb & 0x3FFFF;
    const int id = blockIdx.x, warp = __shfl_sync(0xffffffffu, (int)threadIdx.x >> 5, 0), wg = warp >> 2;
    const long long c0 = clock64();
#define TIDS const int tid = tid_now(), lane = tid & 31, wt = tid & 127, g = lane >> 2, t = lane & 3; (void)wt; (void)g; (void)t;
    TS(threadIdx.x == 0, 0) TG(threadIdx.x == 0, 62)

    if (id >= 128) {
        TIDS
        if (sb & 1023) __trap();
        const int hs = id - 128;
        constexpr int H_B = 204800;
        static_assert(H_B + TAB_BYTES + 8 * VEC_BYTES <= OFF_M, "helper map");
        if (warp < 10 && elect()) { mbar_init(bars + warp * 8, 1); mbar_init(bars + 80 + warp * 8, 1); asm volatile("fence.mbarrier_init.release.cluster;" ::: "memory"); }
        __syncthreads();
        const uint32_t e0 = ld_cold(&g_epoch);
        wait_clock(c0, HELP_T);
        uint4 wr[10];
#pragma unroll
        for (int u = 0; u < 10; u++) wr[u] = ldg128(((hs >> 1) ? pp.w2 : pp.w1) + (size_t)(320 * (hs & 1) + (tid >> 4) + 32 * u) * D_ + 512 + 8 * (tid & 15));
        {
            const int r = tid >> 4, c = tid & 15;
            uint4* dst[2];
#pragma unroll
            for (int e = 0; e < 2; e++) {
                const int p = !(hs >> 1) ? r : e && (hs & 1) ? (r & ~14) | ((r & 6) << 1) | ((r & 8) >> 2) : (r & ~30) | ((r & 6) << 2) | ((r & 24) >> 2);
                dst[e] = &g_wr[(((hs >> 1) * 8 + (c >> 1)) * 10 + 5 * (hs & 1)) * 128 + (p & 15) * 8 + ((2 * (p >> 4) + (c & 1)) ^ (p & 7))];
            }
#pragma unroll
            for (int u = 0; u < 10; u++) stg128(reinterpret_cast<uint4*>(reinterpret_cast<uintptr_t>(dst[u >= 6]) ^ (64 * (u & 1))) + (u >> 1) * 128, wr[u]);
        }
        __syncthreads();
        if (warp == 0) signal_cnt(&g_cnt.wr[0], lane, 1);
        __syncthreads();
        if (warp < 5 && elect()) {
            const int un = 5 * hs + warp;
            mbar_expect(bars + warp * 8, 40960);
            tma_ld2(sb + warp * 40960, &mp.w1h, 64 * (un >> 1), 320 * (un & 1), bars + warp * 8);
            tma_ld2(sb + warp * 40960 + 20480, &mp.w1h, 64 * (un >> 1), 320 * (un & 1) + 160, bars + warp * 8);
        }
        if (tid < 320) {
            const uint4* gm = reinterpret_cast<const uint4*>(g_mod + 3 * D_) + tid;
            const unsigned epoch = e0 + 1;
            uint4 r[6];
            unsigned it = 0;
            for (;;) {
                uint32_t bad = 0;
#pragma unroll
                for (int i = 0; i < 6; i++) { r[i] = ld_part(gm + (i >> 1) * (D_ / 2) + (i & 1) * 3 * D_); bad |= (r[i].y ^ epoch) | (r[i].w ^ epoch); }
                if (__all_sync(~0u, !bad)) break;
                if (++it > SPIN_LIMIT) SPIN_FAIL(54)
            }
            uint32_t mv[3];
#pragma unroll
            for (int i = 0; i < 3; i++) mv[i] = pack2(__uint_as_float(r[2 * i].x) + __uint_as_float(r[2 * i + 1].x), __uint_as_float(r[2 * i].z) + __uint_as_float(r[2 * i + 1].z));
            const uint32_t sw2 = mv[0], cw = add2(mv[1], 0x3f803f80u), gw = mv[2];
            const float c0 = blo(cw), c1 = bhi(cw), s0 = blo(sw2), s1 = bhi(sw2);
            const float i0 = __frcp_rn(zscale(c0)), i1 = __frcp_rn(zscale(c1));
            const uint32_t ci = pack2(i0, i1), cq = pack2(i0 * i0, i1 * i1);
            const uint32_t a = sb + H_B + ((tid >> 5) & 1) * 4608 + (tid >> 6) * 896 + ((tid >> 2) & 7) * 112 + (tid & 3) * 4;
            sts32(a, ci); sts32(a + 16, pack2(i0 - blo(ci), i1 - bhi(ci)));
            sts32(a + 32, cq); sts32(a + 48, pack2(fmaf(i0, i0, -blo(cq)), fmaf(i1, i1, -bhi(cq))));
            sts32(a + 64, cw); sts32(a + 80, sw2); sts32(a + 96, 0x3f803f80u);
            if ((tid & ~35) == 284) sts32(a + 112, 0);
            const uint32_t v = sb + H_B + TAB_BYTES + (tid < 256 ? (tid >> 5) * VEC_BYTES + (tid & 31) * 8 : ((tid - 256) >> 3) * VEC_BYTES + 256 + (tid & 7) * 8);
            sts64f(v, blo(gw), bhi(gw)); sts64f(v + 320, c0, c1); sts64f(v + 640, s0, s1); sts64f(v + 960, i0, i1);
            float k[5] = {c0 + c1, s0 + s1, fmaf(c0, c0, c1 * c1), fmaf(c0, s0, c1 * s1), fmaf(s0, s0, s1 * s1)};
#pragma unroll 1
            for (int o = 16; o; o >>= 1) {
#pragma unroll
                for (int e = 0; e < 5; e++) k[e] += __shfl_xor_sync(~0u, k[e], o);
            }
            const uint32_t ks = sb + H_B + TAB_BYTES + (lane & 7) * VEC_BYTES + 1280 + (warp >> 1) * 32;
            if ((warp & 1) && lane < 8) { sts128f(ks, k[0], k[1], k[2], k[3]); sts128f(ks + 16, k[4], 0.f, 0.f, 0.f); }
            bar_sync(3, 320);
            if (!(warp & 1) && lane < 8) {
                const float4 o = lds128f(ks);
                sts128f(ks, k[0] + o.x, k[1] + o.y, k[2] + o.z, k[3] + o.w); sts32(ks + 16, __float_as_uint(k[4] + __uint_as_float(lds32(ks + 16))));
            }
            fence_async_smem();
        }
        __syncthreads();
        if (hs == 0 && warp == 15 && elect()) {
            asm volatile("cp.async.bulk.global.shared::cta.bulk_group [%0], [%1], %2;\ncp.async.bulk.commit_group;\ncp.async.bulk.wait_group 0;"
                         ::"l"(g_tab), "r"(sb + H_B), "n"(TAB_BYTES + 8 * VEC_BYTES) : "memory");
            asm volatile("red.release.gpu.global.add.u32 [%0], 1;" ::"l"(&g_cnt.tab[0]) : "memory");
        }
        __syncwarp();
#pragma unroll 1
        for (int i = wg; i < 20; i += 4) {
            const int r = i / 5, b = i - 5 * r, un = 5 * hs + b, u3 = 20 * r + un;
            auto refill = [&](int e, int u, uint32_t fb) {
                mbar_expect(fb, 40960);
                tma_ld2(sb + e * 40960, &mp.w3h, 64 * (u >> 1), 320 * (u & 1), fb);
                tma_ld2(sb + e * 40960 + 20480, &mp.w3h, 64 * (u >> 1), 320 * (u & 1) + 160, fb);
            };
            if (i > 4 && i < 9) {
                bar_sync(1, 512);
                if (warp == 0) {
                    signal_cnt(&g_cnt.uv[0], lane, 1);
                    if (elect()) {
#pragma unroll 1
                        for (int e = 0; e < 5; e++) refill(e, 5 * hs + e, bars + (5 + e) * 8);
                        l2_prefetch(pp.w2 + (size_t)160 * hs * D_, 160 * D_ * 2);
                    }
                    __syncwarp();
                }
            }
            mbar_wait(bars + i * 8, 0);
            float d[4];
            gemv_tile<7>(d, sb + b * 40960, sb + H_B, 5 * (un & 1));
            const int col = 16 * (warp & 3) + g;
            float* dst = r ? g_cs3 + (un & 1) * 1920 + 64 * ((u3 >> 1) - 10) + col : g_uv + (un & 1) * 3 * D_ + 2 * D_ + 64 * (un >> 1) + col;
            if (t == 3) { dst[0] = d[0]; dst[8] = d[2]; }
            if (r == 0 && t == 2) { dst[-2 * D_] = d[0]; dst[8 - 2 * D_] = d[2]; dst[-D_] = d[1]; dst[8 - D_] = d[3]; }
            if (r == 1 || r == 2) {
                bar_sync(4 + wg, 128);
                if (wt == 0) refill(b, u3, bars + (i + 5) * 8);
            }
        }
        __syncthreads();
        if (warp == 0) signal_cnt(&g_cnt.cs[0], lane, 1);
        if (tid == 511) l2_prefetch(pp.w4 + (size_t)432 * hs * D_, 432 * D_ * 2);
        if (tid == 0 && hs == 3) {
            uint32_t it = 0;
            while (ld_cold(&g_epoch) == e0) { __nanosleep(256); if (++it > (1u << 20)) SPIN_FAIL(48) }
        }
        return;
    }

    if (elect()) {
        if (warp == 15) {
            mbar_init(bars + B_IN * 8, 1); mbar_init(bars + B_IN * 8 + 8, 1);
            asm volatile("fence.mbarrier_init.release.cluster;" ::: "memory");
            mbar_expect(bars + B_IN * 8, 131 * 160);
            tma_ld2(sb + OFF_KIN, &mp.k, 80 * (id & 7), 64 * (id >> 3) - 3, bars + B_IN * 8);
            tma_ld2(sb + OFF_VIN, &mp.v, 80 * (id & 7), 64 * (id >> 3), bars + B_IN * 8);
        } else if (warp < 13) {
            const uint32_t n = (0x1C14111111881ull >> (4 * warp)) & 15;
#pragma unroll
            for (int i = 0; i < 4; i++) mbar_init(bars + warp * 64 + i * 8, n);
            if (warp == 11) { mbar_init(bars + B_XFREE * 8, 16); mbar_init(bars + B_OWN * 8, 8); }
            else if (warp < 11) {
#pragma unroll
                for (int i = 4; i < 8; i++) mbar_init(bars + warp * 64 + i * 8, n);
            }
            asm volatile("fence.mbarrier_init.release.cluster;" ::: "memory");
        }
    }
    asm volatile("" ::"l"(pp.s), "l"(pp.c), "l"(out));
    TR4((threadIdx.x & 31) == 0, warp)
    const int pr = id >> 1;
    const int grp = pr < 4 ? 15 : pr < 36 ? (pr - 4) & 7 : 8 + (pr - 36) % 7;
    const int j = 2 * (pr < 4 ? pr : pr < 36 ? (pr - 4) >> 3 : (pr - 36) / 7) + (id & 1);

    if (wg == 3) {
        TIDS
        const int sw = warp - 12;
        uint32_t ep = ld_cold(&g_epoch);
        TR4(lane == 0, 20 + sw)
        __syncthreads();
        TR4(lane == 0, 30 + sw)
        asm volatile("barrier.cluster.arrive.relaxed.aligned;" ::: "memory");
        if (sw == 0) {
#pragma unroll 1
            for (int n = PF_N0; n < PF_N; n++) {
                wait_clock(c0, PF_T0 + PF_DT * (n - PF_N0));
                if (elect()) {
                    if (n < 8) l2_prefetch((const char*)(n < 4 ? pp.ssm_k : pp.q) + (size_t)id * 20480 + (n & 3) * 5120, 5120);
                    else l2_prefetch((const char*)pp.w_mod + (size_t)id * 38400 + (n - 8) * 4800, 4800);
                }
            }
        } else if (sw == 1) {
            wait_clock(c0, T_SSM);
            if (elect()) {
                mbar_expect(bars + B_SSM * 8, 20480);
                bulk_ld(sb + OFF_SSM, pp.ssm_k + (size_t)5 * id * S_, 20480, bars + B_SSM * 8);
            }
            mbar_spin(bars + B_KVS * 8, 0);
            signal_cnt(&g_cnt.kv[(id & 7) * 32], lane, 1, true);
            TS(lane == 0, 2)
            if (T_Q) wait_clock(c0, T_Q); else mbar_spin(bars + B_RAW * 8, 0);
            if (elect()) {
                mbar_expect(bars + B_QIN * 8, 20480);
                tma_ld3(sb + OFF_QIN, &mp.q, 0, 16 * id, 0, bars + B_QIN * 8);
            }
        } else if (sw == 2) {
            if (elect()) {
#pragma unroll 1
                for (int i = 2; i < (int)(sizeof(Maps) / sizeof(CUtensorMap)); i++) asm volatile("prefetch.tensormap [%0];" ::"l"(&mp.k + i) : "memory");
#pragma unroll 1
                for (int i = B_SUMS; i < B_SIG; i++) mbar_expect(bars + i * 8, i < B_RECV ? 2048 : (i & 3) < 3 ? 8192 : 3072);
            }
            wait_cnt(&g_cnt.kv[(id >> 4) * 32], 16, POLL_NS);
            TS(lane == 0, 4)
            if (elect()) {
                mbar_expect(bars + B_RAW * 8, 12288);
                mbar_expect(bars + B_RAW2 * 8, 8192);
#pragma unroll
                for (int c = 0; c < 5; c++) bulk_ld(sb + OFF_CH + c * CH_BYTES, g_kvT + (size_t)(5 * id + c) * S_, 4096, bars + (c < 3 ? B_RAW : B_RAW2) * 8);
            }
            mbar_spin(bars + B_BK * 8, 0);
            mbar_spin(bars + B_RAW2 * 8, 0);
            if (!T_Q) mbar_spin(bars + B_QIN * 8, 0);
            if (id < 120 && elect()) {
                mbar_expect(bars + B_WM * 8, 40960);
                tma_ld2(sb + OFF_WM, &mp.wmod, 64 * pr, 320 * (id & 1), bars + B_WM * 8);
                tma_ld2(sb + OFF_WM + 20480, &mp.wmod, 64 * pr, 320 * (id & 1) + 160, bars + B_WM * 8);
            }
            TS(lane == 0, 57)
        } else {
            wait_clock(c0, T_KVB);
            if (elect()) {
                mbar_expect(bars + (B_IN + 1) * 8, 131 * 160);
                tma_ld2(sb + OFF_KIN + 10752, &mp.k, 80 * (id & 7), 64 * (id >> 3) + 1021, bars + (B_IN + 1) * 8);
                tma_ld2(sb + OFF_VIN + 10240, &mp.v, 80 * (id & 7), 64 * (id >> 3) + 1024, bars + (B_IN + 1) * 8);
            }
            TS(lane == 0, 53)
            if (lane == 0) sts32(sb + M_EP, ep + 1);
            sts32(sb + M_NUL + lane * 4, 0);
#pragma unroll 1
            for (int m = lane; m < 40; m += 32) {
                const uint4 c = ldg128(pp.c + 320 * (id & 1) + 8 * m);
                uint32_t w[4] = {c.x, c.y, c.z, c.w};
#pragma unroll
                for (int i = 0; i < 4; i++) { const float a = blo(w[i]), b = bhi(w[i]); w[i] = pack2(__fdividef(a, 1.f + __expf(-a)), __fdividef(b, 1.f + __expf(-b))); }
                sts128(sb + OFF_Z + m * 128, w[0], w[1], w[2], w[3]);
#pragma unroll 1
                for (int r = 1; r < 8; r++) sts128(sb + OFF_Z + m * 128 + r * 16, 0, 0, 0, 0);
            }
            fence_async_smem();
        }
        {
            mbar_spin(bars + B_QIN * 8, 0);
            asm volatile("add.u32 %0, %0, 1;" : "+r"(ep));
            TS(wt == 0, 54)
            const int tk = 8 * ((lane >> 1) & 1) + 2 * (lane >> 3) + (lane & 1), ck = 4 * (sw & 1) + ((lane >> 1) & 2);
            const uint32_t src = sb + OFF_QIN + (sw >> 1) * 2048 + tk * 128;
            bf16* dst = g_qT + (size_t)id * 16 * D_ + (32 * sw + 8 * (t & 2) + g) * 16 + 8 * (t & 1);
#pragma unroll
            for (int i = 0; i < 5; i++) {
                uint32_t r[8];
                ldsm4t(src + i * 4096 + ((ck ^ (tk & 7)) << 4), r[0], r[1], r[2], r[3]);
                ldsm4t(src + i * 4096 + (((ck + 1) ^ (tk & 7)) << 4), r[4], r[5], r[6], r[7]);
                stg128(dst + i * 2048, tag(r[0], ep), r[1], r[2], r[3]);
                stg128(dst + i * 2048 + 128, tag(r[4], ep), r[5], r[6], r[7]);
            }
            float s1 = 0.f, s2 = 0.f;
#pragma unroll 2
            for (int i = 0; i < 10; i++) {
                const uint4 w4 = lds128(sb + OFF_QIN + i * 2048 + wt * 16);
                const uint32_t w[4] = {w4.x, w4.y, w4.z, w4.w};
#pragma unroll
                for (int e = 0; e < 4; e++) { const float a = blo(w[e]), b = bhi(w[e]); s1 += a + b; s2 = fmaf(a, a, fmaf(b, b, s2)); }
            }
#pragma unroll
            for (int o = 1; o < 8; o *= 2) { s1 += __shfl_xor_sync(~0u, s1, o); s2 += __shfl_xor_sync(~0u, s2, o); }
            s1 *= 1.f / D_;
            uint32_t rs = pack2(rsqrtf(fmaxf(s2 * (1.f / D_) - s1 * s1, 0.f) + 1e-5f), 0.f);
            if (lane < 8) rs = tag(rs, ep);
            rs = pack2(blo(rs), -s1 * blo(rs));
            const uint32_t sel = lane ? 0x7632 : 0x5410;
            const uint32_t a0 = __shfl_sync(~0u, rs, 0), a1 = __shfl_sync(~0u, rs, 8), a2 = __shfl_sync(~0u, rs, 16), a3 = __shfl_sync(~0u, rs, 24);
            if (lane < 2) stg64(g_qst + lane * S_ + 16 * id + 4 * sw, tag(__byte_perm(a0, a1, sel), ep), __byte_perm(a2, a3, sel));
            TS(wt == 0, 55)
        }
        bar_sync(6, 128);
        if (sw == 3) {
            signal_cnt(&g_cnt.q[(lane & 3) * 32], lane, 4, true);
            TS(lane == 0, 3)
        }
        if (id < 120) {
            mbar_spin(bars + B_WM * 8, 0);
            TS(wt == 0, 56)
            float d[4];
            gemv_tile<8>(d, sb + OFF_WM, sb + OFF_Z, 0);
            const float d2 = __shfl_up_sync(~0u, d[2], 1);
            TS(wt == 0, 7)
            if (t < 2) asm volatile("{\n.reg .b64 v;\nmov.b64 v, {%1, %2};\nst.relaxed.gpu.global.b64 [%0], v;\n}" ::"l"(g_mod + (id & 1) * 6 * D_ + 64 * pr + 16 * sw + g + 8 * t),
                                    "r"(__float_as_uint(t ? d2 : d[0])), "r"(ep) : "memory");
        }
        bar_sync(6, 128);
        asm volatile("setmaxnreg.dec.sync.aligned.u32 32;");
        asm volatile("barrier.cluster.wait.aligned;" ::: "memory");
        if (sw == 2) {
            wait_cnt(&g_cnt.tab[0], 1);
            if (elect()) {
                mbar_expect(bars + B_TAB * 8, TAB_BYTES / 2 + VEC_BYTES);
                bulk_ld(sb + OFF_TAB, g_tab + (j & 1) * (TAB_BYTES / 32), TAB_BYTES / 2, bars + B_TAB * 8);
                bulk_ld(sb + M_GB, g_tab + (TAB_BYTES + j * VEC_BYTES) / 16, VEC_BYTES, bars + B_TAB * 8);
            }
            TS(lane == 0, 5)
            int n = 0;
            auto xslot = [&]() {
                mbar_spin(bars + (B_XEMPTY + (n & 7)) * 8, ((n >> 3) & 1) ^ 1);
                return bars + (B_LAND + (n & 7)) * 8;
            };
#pragma unroll 1
            for (int e = 0; e < 4; e++) {
                const int w = e & 1, tile = grp + 16 * w;
                if (e < 2) wait_cnt(&g_cnt.x[(4 * w + (id & 3)) * 32], 128);
                else wait_cnt(&g_cnt.g1[min(max(tile + min(lane, 2) - 1, 0), 31) * 32], 32);
                TS(lane == 0, 26 + e)
                if (e == 0) mbar_spin(bars + (B_XS + 1) * 8, 0);
#pragma unroll 1
                for (int kb = 0; kb < 10; kb++, n++) {
                    const uint32_t fb = xslot();
                    TR2(lane == 0, 20 + 10 * e + kb)
                    if (elect()) {
                        mbar_expect(fb, 8192);
                        tma_ld2(sb + OFF_XR + (n & 7) * 8192, e < 2 ? &mp.x1_ld : &mp.t_ld, 64 * (e < 2 ? tile : kb), 64 * (e < 2 ? g1_block(kb, j) : tile), fb);
                    }
                }
            }
#pragma unroll 1
            for (int i = 0; i < 20; i++, n++) {
                const int w = g3_stream(i), kb = g3_block(i);
                if (kb == 0) { wait_cnt(&g_cnt.g2[(grp + 16 * w) * 32], 32); TS(lane == 0, 30 + w) }
                const uint32_t fb = xslot();
                if (elect()) {
                    mbar_expect(fb, 8192);
                    bulk_ld(sb + OFF_XR + (n & 7) * 8192, &g_x2f[((grp + 16 * w) * 10 + kb) * 512], 8192, fb);
                }
            }
            mbar_spin(bars + B_VEC3 * 8, 0);
            unsigned old = 0;
            if (lane == 0) old = atomicAdd(&g_cnt.done[0], 1u);
            if (__shfl_sync(~0u, old, 0) == 127) {
#pragma unroll 1
                for (int i = lane; i < (int)(sizeof(Counters) / 128); i += 32) reinterpret_cast<unsigned*>(&g_cnt)[i * 32] = 0;
                if (lane == 0) atomicAdd(&g_epoch, 1u);
            }
        } else if (sw == 0) {
            wait_cnt(&g_cnt.wr[0], 4);
            mbar_spin(bars + B_QRDY * 8, 0);
            const uint32_t wf = bars + B_WFULL * 8, we = bars + B_WEMPTY * 8;
#pragma unroll 1
            for (int n = 0; n < 5; n++) {
                if (n == 3) mbar_spin(bars + (B_XS + 1) * 8, 0);
                TR2(lane == 0, 70 + n)
                if (elect()) {
                    const uint32_t fb = wf + n * 8, dst = sb + OFF_W + n * 16384;
                    mbar_expect(fb, 20480);
#pragma unroll 1
                    for (int h = 0; h < 2; h++) {
                        const int kb = g1_block(2 * n + h, j);
                        tma_ld2(dst + h * 8192, &mp.w1, 64 * j, 64 * kb, fb);
                        bulk_ld(sb + OFF_REM + n * 4096 + h * 2048, &g_wr[(j * 10 + kb) * 128], 2048, fb);
                    }
                }
            }
            mbar_spin(bars + B_GATE * 8, 0);
#pragma unroll 1
            for (int i = -3; i < 5; i++) {
                const int n = i < 0 ? 8 + i : 5 + i;
                const uint32_t fb = wf + (n & 7) * 8;
                if (i >= 0) mbar_spin(we + i * 8, 0);
                TR2(lane == 0 && i >= 0, 70 + n)
                if (elect()) {
                    if (i < 0 || i >= 3) { mbar_expect(fb, 20480); tma_ld5(sb + OFF_W + (n & 7) * 16384, n < 9 ? &mp.w2a : &mp.w2b, 64 * j, n < 9 ? 4 * (n - 5) : 0, fb); }
                    if (i >= 0) bulk_ld(sb + OFF_REM + i * 4096, &g_wr[((8 + j) * 10 + 2 * i) * 128], 4096, fb);
                }
            }
            mbar_spin(bars + (B_GATE + 1) * 8, 0);
#pragma unroll 1
            for (int n = 10; n < 30; n++) {
                if (n == W3_N2) mbar_spin(bars + (B_GATE + 2) * 8, 0);
                mbar_spin(we + (n & 7) * 8, ((n >> 3) & 1) ^ 1);
                TR2(lane == 0, 70 + n)
                if (elect()) {
                    const uint32_t dst = sb + OFF_W + (n & 7) * 16384, fb = wf + (n & 7) * 8;
                    mbar_expect(fb, 13824);
                    tma_ld3(dst, &mp.w3a, 0, 32 * (n - 10), 3 * j, fb);
                    tma_ld2(dst + 12288, &mp.w3b, 1536 + 24 * j, 32 * (n - 10), fb);
                }
            }
            mbar_spin(we + 6 * 8, 0);
            if (elect()) mbar_arrive(bars + B_S30 * 8);
#pragma unroll 1
            for (int n = 31; n < 50; n++) {
                const int rem = 96 + 3 * (j >> 1);
                int m0, m1, r0, r1, c0_, c1_;
                if (n < 38) {
                    c0_ = g4_block(0, j); c1_ = g4_block(1, j);
                    m0 = m1 = n == 35;
                    r0 = r1 = n == 35 ? rem : 6 * (j ^ (n >= 34)) + ((0x2004204 >> (4 * (n - 31))) & 15);
                } else {
                    const int e = (n - 38) & 3;
                    c0_ = c1_ = g4_block(2 + ((n - 38) >> 2), j);
                    m0 = 0; m1 = e == 1 ? 1 : e == 3 ? -1 : 0;
                    r0 = 6 * (j ^ (e >> 1)) + 4 * (e & 1); r1 = e == 1 ? rem : r0 + 2;
                }
                mbar_spin(we + (n & 7) * 8, ((n >> 3) & 1) ^ 1);
                if (elect()) {
                    const uint32_t dst = sb + OFF_W + (n & 7) * 16384, fb = wf + (n & 7) * 8;
                    mbar_expect(fb, m1 < 0 ? 8192 : 16384 - 2048 * (m0 + m1));
                    tma_ld2(dst, &mp.w4[m0], 64 * c0_, r0 * (32 >> m0), fb);
                    if (m1 >= 0) tma_ld2(dst + 8192, &mp.w4[m1], 64 * c1_, r1 * (32 >> m1), fb);
                }
            }
#pragma unroll 1
            for (int w = 0; w < 2; w++) {
                const uint4* src = g_part + (size_t)(grp + 16 * w) * 40960;
                mbar_spin(bars + (B_RING + w) * 8, 1);
                if (elect()) {
                    const uint32_t fb = bars + (B_IN + w) * 8, rem = sb + OFF_OUT + w * 10240;
                    mbar_expect(fb, 10240);
                    bulk_ld(rem + 8192, &g_x1f[((grp + 16 * w) * 8 + j) * 640 + 512], 2048, fb);
#pragma unroll 1
                    for (int i = 0; i < 4; i++) bulk_ld(rem + i * 2048, src + ((j >> 2) + 2 * i) * 5120 + 4096 + j * 128, 2048, fb);
                }
            }
        } else {
            const int w = sw >> 1;
            mbar_spin(bars + (B_XS + w) * 8, 0);
            signal_cnt(&g_cnt.x[(4 * w + (lane & 3)) * 32], lane, 4, true);
            TS(lane == 0, 20 + w)
            wait_cnt(w ? &g_cnt.cs[0] : &g_cnt.uv[0], 4);
            if (!w) {
#pragma unroll 1
                for (int c = lane; c < 80; c += 32) {
                    const float* src = g_uv + (c < 64 ? 64 * j + c : 448 + 16 * j + c);
                    const uint32_t u = split2(ldcg32f(src) + ldcg32f(src + 3 * D_)), v = split2(ldcg32f(src + D_) + ldcg32f(src + 4 * D_));
                    const uint32_t s = split2(ldcg32f(src + 2 * D_) + ldcg32f(src + 5 * D_));
                    sts128(sb + OFF_F1 + c * 16, u, __byte_perm(u, v, 0x5410), __byte_perm(v, 0, 0x1032), s);
                    sts128(sb + M_F1 + c * 16, s & 0xffffu, 0, 0, 0);
                }
            } else {
                if (elect()) mbar_arrive(bars + B_VEC3 * 8);
                uint32_t s[7];
#pragma unroll
                for (int i = 0; i < 7; i++) {
                    const int c = min(lane + 32 * i, 215);
                    const float* src = g_cs3 + (i < 6 ? 192 * j + c : 1344 + 24 * j + c);
                    s[i] = split2(ldcg32f(src) + ldcg32f(src + 1920));
                }
                TS(lane == 0, 19)
                mbar_spin(bars + B_S30 * 8, 0);
#pragma unroll
                for (int i = 0; i < 7; i++) sts128(sb + OFF_W + 6 * 16384 + min(lane + 32 * i, 215) * 16, s[i], s[i] & 0xffffu, 0, 0);
            }
            fence_async_smem();
            warp_arrive(bars + (w ? B_WFULL + 6 : B_VEC) * 8);
            TS(lane == 0 && !w, 9)
        }
        return;
    }

    {
        uint32_t ep;
        {
            TIDS
            ep = ld_cold(&g_epoch);
            const int cp = (tid + 16) % 40, cp1 = tid % 40;
            const uint4 sh0 = ldg128(pp.shift_k + (80 * (id & 7) + 2 * cp1) * 4), sh1 = ldg128(pp.shift_k + (80 * (id & 7) + 2 * cp) * 4);
            uint32_t dd;
            asm volatile("ld.global.nc.u16 %0, [%1];" : "=r"(dd) : "l"(pp.ssm_D + 5 * id + min(wg + 3 * lane, 4)));
            TR4(lane == 0, 40 + warp)
            __syncthreads();
            asm volatile("barrier.cluster.arrive.relaxed.aligned;" ::: "memory");
            asm volatile("add.u32 %0, %0, 1;" : "+r"(ep));
#pragma unroll 1
            for (int hw = 0; hw < 2; hw++) {
                if ((unsigned)(warp - 2 * hw) >= 10) continue;
                const int u = tid - 64 * hw;
                const int c = hw ? cp : cp1, oc = u / 40, line = 31 - 16 * hw - (id >> 3);
                const uint4 sh = hw ? sh1 : sh0;
                const uint32_t st = sb + OFF_ST + hw * 10240, sta = st + c * 256 + ((((6 - 2 * (oc & 3)) ^ (oc >> 2) ^ (line & 1)) ^ (c & 7)) << 4), in = oc * 1280 + c * 4;
                const uint32_t f0 = __byte_perm(sh.x, sh.z, 0x5410), f1 = __byte_perm(sh.x, sh.z, 0x7632), f2 = __byte_perm(sh.y, sh.w, 0x5410), f3 = __byte_perm(sh.y, sh.w, 0x7632);
                uint32_t kk[11], vv[8];
                mbar_spin(bars + (B_IN + hw) * 8, 0);
                TS(tid == 64, 18 + 42 * hw)
#pragma unroll
                for (int i = 0; i < 11; i++) kk[i] = lds32(sb + OFF_KIN + hw * 10752 + in + i * 160);
#pragma unroll
                for (int i = 0; i < 8; i++) vv[i] = lds32(sb + OFF_VIN + hw * 10240 + in + i * 160);
#pragma unroll
                for (int i = 0; i < 8; i++) vv[i] = mul2(fma2(kk[i + 3], f0, fma2(kk[i + 2], f1, fma2(kk[i + 1], f2, mul2(kk[i], f3)))), vv[i]);
                sts128(sta, tag(__byte_perm(vv[0], vv[1], 0x5410), ep), __byte_perm(vv[2], vv[3], 0x5410), __byte_perm(vv[4], vv[5], 0x5410), __byte_perm(vv[6], vv[7], 0x5410));
                sts128(sta + 128, tag(__byte_perm(vv[0], vv[1], 0x7632), ep), __byte_perm(vv[2], vv[3], 0x7632), __byte_perm(vv[4], vv[5], 0x7632), __byte_perm(vv[6], vv[7], 0x7632));
                bar_sync(7 + hw, 320);
                flush_tile(st, g_kvT + (size_t)(80 * (id & 7)) * S_ + 64 * line, u);
                TS(tid == 64 && hw, 1)
            }
            warp_arrive(bars + B_KVS * 8);
            if (tid < 320) sts128(sb + OFF_CH + (tid >> 6) * CH_BYTES + 4096 + (tid & 63) * 16, 0, 0, 0, 0);
            mbar_spin(bars + B_SSM * 8, 0);
            TS(tid == 0, 14)
            uint2 w[7];
            uint32_t pv[7];
#pragma unroll
            for (int i = 0; i < 7; i++) {
                const uint32_t a = sb + OFF_SSM + min(wg + 3 * i, 19) * 1024 + wt * 8;
                w[i] = lds64(a); pv[i] = lds32(a - 4);
            }
#pragma unroll
            for (int i = 0; i < 7; i++) {
                const int un = min(wg + 3 * i, 19);
                sts128(sb + OFF_CH + (un >> 2) * CH_BYTES + OFF_P + (un & 3) * 2048 + wt * 16, __byte_perm(w[i].x, pv[i], 0x7610), __byte_perm(w[i].x, 0, 0x1032), __byte_perm(w[i].y, w[i].x, 0x7610), __byte_perm(w[i].y, 0, 0x1032));
            }
            __syncwarp();
            if (wt < 2 - (wg >> 1)) {
                const uint32_t h = lds32(sb + OFF_SSM + (wg + 3 * wt) * 4096), h0 = pack2(blo(h) + blo(dd), 0.f);
                sts64f(sb + OFF_CH + (wg + 3 * wt) * CH_BYTES + OFF_P, __uint_as_float(h0), __uint_as_float(__byte_perm(h, h0, 0x5432)));
            }
            fence_async_smem();
            warp_arrive(bars + B_BK * 8);
            asm volatile("barrier.cluster.wait.aligned;" ::: "memory");
            mbar_spin(bars + B_BK * 8, 0);
            TS(tid == 0, 15)
        }

#pragma unroll 1
        for (int c = wg; c < 5; c += 3) {
            const uint32_t kvb = sb + OFF_CH + c * CH_BYTES;
            mbar_spin(bars + (c < 3 ? B_RAW : B_RAW2) * 8, 0);
            if (CH2_DELAY && wg == 2) wait_clock(clock64(), CH2_DELAY);
            for (uint32_t it = 0;;) {
                const int wt = tid_now() & 127;
                if (!bar_any(1 + wg, ((lds32(kvb + wt * 16) ^ ep) | (lds32(kvb + 2048 + wt * 16) ^ ep)) & 1)) break;
                if (wt == 0) { mbar_expect(bars + (B_RETRY + wg) * 8, 4096); bulk_ld(kvb, g_kvT + (size_t)(5 * id + c) * S_, 4096, bars + (B_RETRY + wg) * 8); }
                mbar_spin(bars + (B_RETRY + wg) * 8, ep >> 31);
                ep ^= 0x80000000u;
                STALE(0)
                SPIN_CHECK(57)
            }
            TS(threadIdx.x == 0, c ? 13 : 11)
            float acc[64];
            {
                const int l = tid_now() & 31;
                conv_channel(acc, kvb + OFF_P + (8 * (warp & 3) + (l >> 2) - 2 * (l & 3)) * 4, (((uint64_t)0xC0000010u << 32) | ((kvb & 0x3FFFF) >> 4) | 0x10000u) + pp.nil);
            }
            TS(threadIdx.x == 0, c ? 16 : 12)
            if (c >= 3) {
#pragma unroll 1
                for (int e = 0; e < 3; e++) mbar_spin(bars + (B_RING + e) * 8, 0);
            }
            TIDS
            const int e = 127 - 8 * (lane >> 4) - (lane & 7), u0 = (warp & 3) + 8 * (e >> 2) + (e & 3) + 4 * ((lane >> 3) & 1);
            const uint32_t ring = sb + OFF_RING + c * 16384 + (warp & 3) * 4096, wa = ring + (u0 ^ ((u0 >> 1) & 4)) * 16;
            if (lane < (warp & 3)) sts128(ring + lane * 16, 0, 0, 0, 0);
#pragma unroll
            for (int i = 0; i < 8; i++)
                stsm4t(i == 0 && u0 >= 256 ? sb + M_SINK : wa - 512 * i, pack2(acc[8 * i], acc[8 * i + 1]), pack2(acc[8 * i + 2], acc[8 * i + 3]),
                       pack2(acc[8 * i + 4], acc[8 * i + 5]), pack2(acc[8 * i + 6], acc[8 * i + 7]));
            warp_arrive(bars + (B_RING + c) * 8);
        }
        fence_async_smem();
        TIDS
        if (warp == 8) {
            wait_cnt(&g_cnt.q[(id & 3) * 32], 128);
            if (elect()) {
                mbar_expect(bars + B_QRDY * 8, 28672);
                tma_ld2(sb + OFF_QT, &mp.qT, 80 * id, 0, bars + B_QRDY * 8);
                bulk_ld(sb + OFF_QT + 20480, g_qst, 8192, bars + B_QRDY * 8);
            }
            TS(lane == 0, 8)
        } else if (warp == 9) {
            const int v = min(lane / 5, 3);
            const uint2* gm = g_mod + (v + (v == 3)) * D_ + 5 * id + lane % 5;
            const unsigned epoch = lds32(sb + M_EP);
            uint2 r0, r1;
            unsigned it = 0;
            do {
                r0 = ld_mod(gm); r1 = ld_mod(gm + 6 * D_);
                SPIN_CHECK(55)
            } while (!__all_sync(~0u, r0.y == epoch && r1.y == epoch));
            const float m0 = __uint_as_float(r0.x), m1 = __uint_as_float(r1.x);
            const float m = rbf(m0 + m1), p = rbf(1.f + m);
            const float cz = zscale(__shfl_sync(~0u, p, 15 + lane % 5)), ga = __shfl_sync(~0u, m, 10 + lane % 5);
            if (lane < 15) sts32(sb + M_AB + lane % 5 * 16 + v * 4, lane < 10 ? __float_as_uint(cz * ga * (lane < 5 ? m : p)) : pack2(cz, cz));
            warp_arrive(bars + B_MODR * 8);
            TS(lane == 0, 6)
        }
        mbar_spin(bars + B_QRDY * 8, 0);
        mbar_spin(bars + B_MODR * 8, 0);
#pragma unroll 1
        for (int hf = 0; hf < 2; hf++) {
            const int u = wt + 128 * hf;
            uint4 rs = lds128(sb + OFF_QT + 20480 + u * 16), nm = lds128(sb + OFF_QT + 24576 + u * 16);
            uint32_t it = 0;
            while (__any_sync(~0u, ((rs.x ^ ep) | (rs.z ^ ep) | (nm.x ^ ep) | (nm.z ^ ep)) & 1)) {
                rs = ld_part(g_qst + 8 * u); nm = ld_part(g_qst + S_ + 8 * u);
                STALE(1)
                SPIN_CHECK(53)
            }
            const int c1 = wg == 2 ? 2 + !EPI_SPLIT : 5;
#pragma unroll 1
            for (int c = wg == 2 ? 0 : EPI_SPLIT && wg == hf ? 2 : 3 + wg; c < c1; c += wg == 2 ? 1 : c == 2 ? 1 + wg : 2) {
                uint4 q = lds128(sb + OFF_QT + (u >> 1) * 160 + c * 32 + (u & 1) * 16);
                const float4 ab = lds128f(sb + M_AB + c * 16);
                mbar_spin(bars + (B_RING + c) * 8, 0);
                const uint32_t ra = sb + OFF_RING + c * 16384 + (u ^ ((u >> 1) & 4)) * 16;
                const uint4 p0 = lds128(ra), p1 = lds128(ra + 4096), p2 = lds128(ra + 8192), p3 = lds128(ra + 12288);
                while (__any_sync(~0u, (q.x ^ ep) & 1)) {
                    q = ld_part(g_qT + ((u >> 1) * D_ + 5 * id + c) * 16 + 8 * (u & 1));
                    STALE(2)
                    SPIN_CHECK(52)
                }
                uint32_t gq[4] = {q.x, q.y, q.z, q.w}, gg[4] = {fma2(q.x, rs.x, nm.x), fma2(q.y, rs.y, nm.y), fma2(q.z, rs.z, nm.z), fma2(q.w, rs.w, nm.w)};
#pragma unroll
                for (int i = 0; i < 4; i++) {
                    gg[i] = pack2(fmaf(blo(gg[i]), ab.y, ab.x), fmaf(bhi(gg[i]), ab.y, ab.x));
                    gq[i] = mul2(gq[i], __float_as_uint(ab.z));
                }
                stg128_tag(g_x1T + (size_t)(5 * id + c) * S_ + 8 * u,
                           fma2(gg[0], add2(add2(p0.x, p1.x), add2(p2.x, p3.x)), gq[0]), fma2(gg[1], add2(add2(p0.y, p1.y), add2(p2.y, p3.y)), gq[1]),
                           fma2(gg[2], add2(add2(p0.z, p1.z), add2(p2.z, p3.z)), gq[2]), fma2(gg[3], add2(add2(p0.w, p1.w), add2(p2.w, p3.w)), gq[3]), ep, ((5 * id + c) >> 3) & 3);
            }
            warp_arrive(bars + (B_XS + hf) * 8);
            TS(tid == 0, hf ? 17 : 58)
            TS(tid == 256 && hf, 52)
        }
    }

    const uint32_t nil = pp.nil;
    const int wq = warp & 3;
    if (wg == 2) {
        TIDS
        asm volatile("setmaxnreg.dec.sync.aligned.u32 32;");
        {
            const uint32_t ep = lds32(sb + M_EP);
            uint32_t ph = 0;
#pragma unroll 1
            for (int n = wq; n < 60; n += 4) {
                const int e = n / 20, w = e < 2 ? n - 20 * e >= 10 : g3_stream(n - 40), kb = e < 2 ? n - 20 * e - 10 * w : g3_block(n - 40), tile = grp + 16 * w;
                const uint32_t a = sb + OFF_XR + (n & 7) * 8192;
                const uint32_t ta = a + (e == 0 ? lane * 128 + ((lane & 7) << 4) + (lane >> 3) * 4
                                       : e == 1 ? (lane & 15) * 128 + (((lane >> 4 << 1) ^ (lane & 7)) << 4) + (lane & 8) + (lane >> 4) * 4
                                                : lane * 32 + (lane >> 2) * 4);
                const uint32_t tb = e == 0 ? ta ^ 32 : ta + 2048, tc = e == 2 ? ta + 1024 : ta ^ 64, td = e == 2 ? tb + 1024 : tb ^ 64;
                mbar_spin(bars + (B_LAND + (n & 7)) * 8, (n >> 3) & 1);
                while (true) {
                    uint32_t v[8];
#pragma unroll
                    for (int i = 0; i < 8; i++) v[i] = lds32(((i & 2) ? ((i & 1) ? td : tc) : (i & 1) ? tb : ta) + (i >> 2) * 4096);
                    if (!__any_sync(~0u, (lop3<0x7E>(v[0], ep, v[1]) | lop3<0x7E>(v[2], ep, v[3]) | lop3<0x7E>(v[4], ep, v[5]) | lop3<0x7E>(v[6], ep, v[7])) & 1)) break;
                    if (elect()) {
                        mbar_expect(bars + (B_AGAIN + wq) * 8, 8192);
                        if (e == 2) bulk_ld(a, &g_x2f[(tile * 10 + kb) * 512], 8192, bars + (B_AGAIN + wq) * 8);
                        else tma_ld2(a, e ? &mp.t_ld : &mp.x1_ld, 64 * (e ? kb : tile), 64 * (e ? tile : g1_block(kb, j)), bars + (B_AGAIN + wq) * 8);
                    }
                    mbar_spin(bars + (B_AGAIN + wq) * 8, ph);
                    ph ^= 1;
                    STALE1(e)
                }
                if (elect()) {
                    mbar_arrive(bars + (B_XFULL + 8 * w + ((10 * e + kb) & 7)) * 8);
                    if (n == GATE_W2 || n == GATE_W3 || n == GATE_W3B) mbar_arrive(bars + (B_GATE + (n >= GATE_W3) + (n >= GATE_W3B)) * 8);
                }
            }
        }
#pragma unroll 1
        for (int uw = 0; uw < 2; uw++) {
            const int tile = grp + 16 * uw;
            const uint32_t ep = lds32(sb + M_EP), in = sb + OFF_OUT + uw * 10240 + wt * 16, sr = in - lane * 16;
            mbar_wait(bars + (B_IN + uw) * 8, 1);
            float r[8];
#pragma unroll
            for (int h = 0; h < 2; h++) {
                uint4 a = lds128(in + h * 4096), b = lds128(in + h * 4096 + 2048);
                uint32_t it = 0;
                while (__any_sync(~0u, ((a.x ^ ep) | (b.x ^ ep)) & 1)) {
                    const uint4* p = g_part + (size_t)tile * 40960 + ((j >> 2) + 4 * h) * 5120 + 4096 + j * 128 + wt;
                    a = ld_part(p); b = ld_part(p + 10240);
                    STALE(3)
                    if (++it > SPIN_LIMIT) SPIN_FAIL(58)
                }
                if (h) add8(r, add2(a, b)); else unpack8(r, add2(a, b));
            }
            base16(r, lds128(in + 8192), lds64f(sb + M_GB + (64 + 2 * t) * 4), lds64f(sb + M_GB + (72 + 2 * t) * 4));
            __syncwarp();
            stsm4(sr + (lane & 15) * 32 + (((lane >> 4) ^ ((lane >> 2) & 1)) << 4), pack2(r[0], r[1]), pack2(r[2], r[3]), pack2(r[4], r[5]), pack2(r[6], r[7]));
            __syncwarp();
            stg128(out + (size_t)(64 * tile + 16 * wq + (lane >> 1)) * D_ + 512 + 16 * j + 8 * (lane & 1), lds128(sr + (lane >> 1) * 32 + (((lane & 1) ^ ((lane >> 3) & 1)) << 4)));
            __syncwarp();
        }
        if (wq == 0) {
            uint32_t it = 0;
            while (!mbar_try(bars + B_OWN * 8, 0)) { if (++it > SPIN_LIMIT) SPIN_FAIL(56) }
        }
        return;
    }

    TIDS
    const int uw = wg, tile = grp + 16 * uw, row0 = 64 * tile + 16 * wq;
    const bool leader = wt == 0; (void)leader;
    const uint32_t xfull = bars + (B_XFULL + 8 * uw) * 8, xempty = bars + B_XEMPTY * 8, wfull = bars + B_WFULL * 8, wempty = bars + B_WEMPTY * 8;
    const uint64_t dz = mkdesc(0) + pp.nil;
    auto xwait = [&](uint32_t n) { mbar_spin(xfull + (n & 7) * 8, (n >> 3) & 1); };
    asm volatile("setmaxnreg.inc.sync.aligned.u32 224;");
    const uint32_t ep = lds32(sb + M_EP);
    {
        float acc[40];
        uint4* const own = &g_x1f[(tile * 8 + j) * 640 + wt];
        const uint32_t la = ((lane & 7) + 8 * (lane >> 4)) * 128 + (((2 * wq + ((lane >> 3) & 1)) ^ (lane & 7)) << 4);
        auto slot = [&](uint32_t m) { return sb + OFF_XR + (m & 7) * 8192; };
        auto grab = [&](uint32_t m) {
            uint32_t r0, r1, r2, r3;
            ldsm4t(slot(m) + la + (j & 3) * 2048, r0, r1, r2, r3);
            stg128(own + 512, r0, r1, r2, r3);
        };
        float al[2], r1[2], n1[2];
        {
            float sl[4], sq[4], v[4];
            uint32_t z0[16], z1[16], zz[16];
            uint64_t bd = dz + b80_desc(dsb, 0, 0, 0), tb = (((uint64_t)8 << 32) | ((dsb + OFF_TAB) >> 4) | (7u << 16)) + pp.nil;
            auto ldfrag = [&](uint32_t (&z)[16], int n) {
#pragma unroll
                for (int q = 0; q < 4; q++) ldsm4t(slot(2 * uw + n) + la + q * 2048, z[4 * q], z[4 * q + 1], z[4 * q + 2], z[4 * q + 3]);
            };
            auto tile1 = [&](const uint32_t (&zc)[16], uint32_t (&zn)[16], int n, int h) {
                const bool last = h && n == 5, ok = mbar_test(xfull + (n + 1) * 8, 0), okw = !h || mbar_test(wfull + ((n + 1) >> 1) * 8, 0);
                const int kb = g1_block(n, j);
                wg_fence();
#pragma unroll
                for (int q = 0; q < 2; q++) wgmma_rs80(acc, zc[4 * q], zc[4 * q + 1], zc[4 * q + 2], zc[4 * q + 3], bd + q * B80_STEP, 1);
                wg_commit();
                wg_wait<1>();
                if (!ok) xwait(n + 1);
                if (!last) ldfrag(zn, n + 1);
#pragma unroll
                for (int e = 0; e < 16; e++) zz[e] = mul2(zc[e], zc[e]);
                const uint64_t t0 = last ? ((uint64_t)8 << 32) | ((dsb + M_NUL) >> 4) : tb;
                const uint32_t ts = last ? 0 : 14;
                wg_fence();
#pragma unroll
                for (int q = 0; q < 4; q++) wgmma_rs8(sl, zc[4 * q], zc[4 * q + 1], zc[4 * q + 2], zc[4 * q + 3], t0 + q * ts, 1);
#pragma unroll
                for (int q = 0; q < 4; q++) wgmma_rs8(sq, zz[4 * q], zz[4 * q + 1], zz[4 * q + 2], zz[4 * q + 3], t0 + q * ts, 1);
#pragma unroll
                for (int q = 2; q < 4; q++) wgmma_rs80(acc, zc[4 * q], zc[4 * q + 1], zc[4 * q + 2], zc[4 * q + 3], bd + q * B80_STEP, 1);
                wg_commit();
                if (kb == j) {
#pragma unroll
                    for (int q = 0; q < 4; q++) stg128(own + q * 128, zc[4 * q], zc[4 * q + 1], zc[4 * q + 2], zc[4 * q + 3]);
                }
                if (!h && kb == 8 + (j >> 2)) grab(2 * uw + n);
                if (lane < 2) mbar_arrive(xempty + ((2 * uw + n) & 7) * 8);
                if (!h && n && lane == 0) mbar_arrive(wempty + ((n >> 1) - 1) * 8);
                tb += 56;
                bd = bd + (uint64_t)B80_HALF;
                if (!okw) mbar_spin(wfull + ((n + 1) >> 1) * 8, 0);
                TR(leader, 100 + 10 * uw + n)
            };
            zero(acc); zero(sl); zero(sq);
            mbar_spin(bars + B_TAB * 8, 0);
            mbar_spin(wfull, 0);
            xwait(0);
            TS(leader, 32 + uw)
            ldfrag(z0, 0);
#pragma unroll 1
            for (int n = 0; n < 6; n += 2) { tile1(z0, z1, n, 0); tile1(z1, z0, n + 1, 1); }
#pragma unroll
            for (int n = 6; n < 10; n++) {
                const uint64_t ad = dz + (((dsb + OFF_XR + ((2 * uw + n) & 7) * 8192) >> 4) | 0x10000u);
                const bool ok = n == 9 || mbar_test(xfull + ((n + 1) & 7) * 8, (n + 1) >> 3), okw = n != 7 || mbar_test(wfull + 4 * 8, 0);
                wg_fence();
#pragma unroll
                for (int q = 0; q < 4; q++) wgmma_ss80t(acc, ad + q * 128, bd + q * B80_STEP, 1);
                wg_commit();
                bd = bd + (uint64_t)B80_HALF;
                if (n == 9 && 9 - (j & 1) == 8 + (j >> 2)) grab(2 * uw + 9);
                wg_wait<1>();
                if (n > 6 && lane < 2) mbar_arrive(xempty + ((2 * uw + n - 1) & 7) * 8);
                if (!(n & 1) && lane == 0) mbar_arrive(wempty + ((n >> 1) - 1) * 8);
                if (n == 6) {
                    reg_fence(sl); reg_fence(sq);
#pragma unroll
                    for (int e = 0; e < 2; e++) {
                        v[2 * e] = t == 0 ? sl[2 * e] + sl[2 * e + 1] : t == 1 ? sq[2 * e] + sq[2 * e + 1] : sl[2 * e];
                        v[2 * e + 1] = t == 2 ? sl[2 * e + 1] : sq[2 * e];
                    }
                    st_peer(peer_addr(sb + OFF_ROW + uw * 2048 + wt * 16), __float_as_uint(v[0]), __float_as_uint(v[1]), __float_as_uint(v[2]), __float_as_uint(v[3]), peer_addr(bars + (B_SUMS + uw) * 8));
                    TS(leader && !uw, 59)
                }
                if (!ok) xwait(n + 1);
                if (!okw) mbar_spin(wfull + 4 * 8, 0);
                TR(leader, 100 + 10 * uw + n)
            }
            float4 k = lds128f(sb + M_KS);
            float k4 = __uint_as_float(lds32(sb + M_KS + 16));
#pragma unroll
            for (int w = 1; w < 5; w++) {
                const float4 o = lds128f(sb + M_KS + w * 32);
                k.x += o.x; k.y += o.y; k.z += o.z; k.w += o.w; k4 += __uint_as_float(lds32(sb + M_KS + w * 32 + 16));
            }
            mbar_spin(bars + (B_SUMS + uw) * 8, 0);
            TS(leader && !uw, 10)
            const float4 o = lds128f(sb + OFF_ROW + uw * 2048 + wt * 16);
            v[0] += o.x; v[1] += o.y; v[2] += o.z; v[3] += o.w;
            uint32_t fa[4];
#pragma unroll
            for (int h = 0; h < 2; h++) {
                const int l0 = lane & ~3;
                const float s1 = __shfl_sync(~0u, v[2 * h], l0), s2 = __shfl_sync(~0u, v[2 * h], l0 + 1), scc = __shfl_sync(~0u, v[2 * h], l0 + 2);
                const float scs = __shfl_sync(~0u, v[2 * h + 1], l0 + 2), sc = __shfl_sync(~0u, v[2 * h], l0 + 3), sqq = __shfl_sync(~0u, v[2 * h + 1], l0 + 3);
                const float m1 = s1 * (1.f / D_), va = fmaxf(s2 * (1.f / D_) - m1 * m1, 0.f) + 1e-5f, r = rsqrtf(va);
                const float m2 = (r * (sc - m1 * k.x) + k.y) * (1.f / D_);
                const float e2 = (r * (r * (sqq + m1 * (m1 * k.z - 2.f * scc)) + 2.f * (scs - m1 * k.w)) + k4) * (1.f / D_);
                al[h] = r * 0.5f * rsqrtf(fmaxf(e2 - m2 * m2, 0.f) + 1e-5f); r1[h] = r; n1[h] = -m1 * r;
                const uint32_t fb = split2(va * r), fx = split2(t == 3 ? -m2 * va * r : -m1), fc = __shfl_sync(~0u, fx, lane | 3);
                fa[h] = __byte_perm(fx, fb, t == 1 ? 0x5432 : t == 2 ? 0x7654 : 0x1010);
                fa[2 + h] = t ? 0 : fc >> 16;
            }
            mbar_spin(bars + B_VEC * 8, 0);
            wg_fence();
            wgmma_rs80k(acc, fa[0], fa[1], fa[2], fa[3], ((uint64_t)8 << 32) | ((dsb + OFF_F1) >> 4) | (((M_F1 - OFF_F1) >> 4) << 16), 1);
            wg_commit();
        }
        wg_wait<0>();
        reg_fence(acc);
        if (lane < 2) mbar_arrive(xempty + ((2 * uw + 9) & 7) * 8);
        if (lane == 0) mbar_arrive(wempty + 4 * 8);
        TS(leader, 34 + uw)
        {
            bf16* const trow = g_t + (size_t)(row0 + g + 2) * D_;
#pragma unroll
            for (int b = 0; b < 3; b++) {
                uint32_t p[8];
#pragma unroll
                for (int ii = 0; ii < 4; ii++) {
                    const int i = 4 * b + ii;
                    if (i >= 10) continue;
#pragma unroll
                    for (int h = 0; h < 2; h++) p[(i & 3) + 4 * h] = pack2(gelu2(acc[4 * i + 2 * h] * al[h]), gelu2(acc[4 * i + 2 * h + 1] * al[h]));
                }
                if (b < 2) {
                    const int gr = (2 * j + b) / 5, sh = (gr & 1) ? -1 - (gr >> 1) : 1 + (gr >> 1);
                    bf16* dst = trow + 64 * j + 32 * b + 8 * t;
                    const int w = (((g + sh) >> 2) & 2) + (t >> 1);
                    stg128_tag(dst + sh * D_, p[0], p[1], p[2], p[3], ep, w);
                    stg128_tag(dst + (sh + 8) * D_, p[4], p[5], p[6], p[7], ep, w ^ 2);
                    if (row0 + g < sh || row0 + g + 8 >= S_ + sh) stg128_tag(dst + (sh > 0 ? 0 : 8) * D_, 0, 0, 0, 0, ep, (sh > 0 ? 0 : 2) + (t >> 1));
                } else {
                    bf16* dst = trow + 512 + 16 * j + 4 * t;
                    const uint32_t lo = t == (g < 2), hi = t == (g >= 2), o = j & 1;
                    stg64(dst - 2 * D_, lop3<0xB8>(p[0], lo & ~o, ep), lop3<0xB8>(p[1], lo & o, ep));
                    stg64(dst + 6 * D_, lop3<0xB8>(p[4], hi & ~o, ep), lop3<0xB8>(p[5], hi & o, ep));
                    if (row0 + g + 8 >= S_ - 2) stg64(dst + 8 * D_, ep & (t == 1) & ~o, ep & (t == 1) & o);
                }
            }
        }
        signal_cnt(&g_cnt.g1[tile * 32], lane, 1, true);
        TS(leader, 36 + uw)
        uint32_t res[20];
        auto ld_own = [&]() {
#pragma unroll
            for (int i = 0; i < 5; i++) { const uint4 v = ldcg128(own + i * 128); res[4 * i] = v.x; res[4 * i + 1] = v.y; res[4 * i + 2] = v.z; res[4 * i + 3] = v.w; }
        };
        ld_own();
#pragma unroll
        for (int i = 0; i < 10; i++) {
            const float2 c = lds64f(sb + M_C + (8 * i + 2 * t) * 4), s = lds64f(sb + M_SB + (8 * i + 2 * t) * 4);
#pragma unroll
            for (int h = 0; h < 2; h++) {
                acc[4 * i + 2 * h] = fmaf(blo(res[2 * i + h]), r1[h], fmaf(n1[h], c.x, s.x));
                acc[4 * i + 2 * h + 1] = fmaf(bhi(res[2 * i + h]), r1[h], fmaf(n1[h], c.y, s.y));
            }
        }
        mbar_spin(wfull + 5 * 8, 0);
        xwait(10);
#pragma unroll 1
        for (int i = 0; i < 5; i++) {
            const uint32_t wn = 5 + i, xs = (4 + 2 * uw + 2 * i) & 7;
            const uint64_t alo = dz + (((dsb + OFF_XR + xs * 8192) >> 4) | 0x10000u), bd = dz + b80_desc(dsb, wn, i, 0);
#pragma unroll
            for (int h = 0; h < 2; h++) {
                const uint32_t nn = min(11 + 2 * i + h, 19), wx = min(wn + 1, 9u);
                const bool ok = mbar_test(xfull + (nn & 7) * 8, (nn >> 3) & 1), okw = !h || mbar_test(wfull + (wx & 7) * 8, wx >> 3);
                wg_fence();
#pragma unroll
                for (int q = 0; q < 4; q++) wgmma_ss80(acc, alo + h * 512 + q * 2, bd + h * B80_HALF + q * B80_STEP, 1);
                wg_commit();
                wg_wait<1>();
                if (lane < 2 && (h || i)) mbar_arrive(xempty + ((xs + h - 1) & 7) * 8);
                if (!h && i && lane == 0) mbar_arrive(wempty + ((wn - 1) & 7) * 8);
                if (!ok) xwait(nn);
                if (!okw) mbar_spin(wfull + (wx & 7) * 8, wx >> 3);
                TR(leader, (uw ? 86 : 20) + 2 * i + h)
            }
        }
        wg_wait<0>();
        reg_fence(acc);
        if (lane < 2) mbar_arrive(xempty + ((29 + 10 * uw) & 7) * 8);
        if (lane == 0) mbar_arrive(wempty + (9 & 7) * 8);
        TS(leader, 38 + uw)
        float a0 = 0.f, b0 = 0.f, a1 = 0.f, b1 = 0.f;
        uint32_t x2[20];
#pragma unroll
        for (int i = 0; i < 5; i++) {
            uint32_t* p = &x2[4 * i];
#pragma unroll
            for (int e = 0; e < 4; e++) p[e] = pack2(acc[8 * i + 2 * e], acc[8 * i + 2 * e + 1]);
#pragma unroll
            for (int e = 0; e < 4; e++) p[e] = lop3<0xB8>(p[e], (((wt >> 3) ^ (wt << 2)) & 7) == e, ep);
            stg128(&g_x2f[(tile * 40 + (i < 4 ? 4 * j + i : 32 + j)) * 128 + wt], p[0], p[1], p[2], p[3]);
#pragma unroll
            for (int e = 0; e < 4; e += 2) {
                const float u0 = blo(p[e]), u1 = bhi(p[e]), v0 = blo(p[e + 1]), v1 = bhi(p[e + 1]);
                a0 += u0 + u1; b0 = fmaf(u0, u0, fmaf(u1, u1, b0));
                a1 += v0 + v1; b1 = fmaf(v0, v0, fmaf(v1, v1, b1));
            }
        }
#pragma unroll
        for (int o = 1; o < 4; o *= 2) {
            a0 += __shfl_xor_sync(~0u, a0, o); b0 += __shfl_xor_sync(~0u, b0, o);
            a1 += __shfl_xor_sync(~0u, a1, o); b1 += __shfl_xor_sync(~0u, b1, o);
        }
        if (t < 2) stg64(&g_stats[(tile * 8 + j) * 64 + 16 * wq + g + 8 * t], tag(__float_as_uint(t ? a1 : a0), ep), __float_as_uint(t ? b1 : b0));
        signal_cnt(&g_cnt.g2[tile * 32], lane, 1, true);
        TS(leader, 40 + uw)
        ld_own();
#pragma unroll
        for (int i = 0; i < 10; i++) {
            const float2 c = lds64f(sb + M_GB + (8 * i + 2 * t) * 4), e = lds64f(sb + M_CI + (8 * i + 2 * t) * 4);
#pragma unroll
            for (int h = 0; h < 2; h++)
                res[2 * i + h] = fma2(pack2(c.x, c.y), x2[2 * i + h], pack2(e.x * blo(res[2 * i + h]), e.y * bhi(res[2 * i + h])));
        }
#pragma unroll
        for (int i = 0; i < 5; i++) stg128(own + i * 128, res[4 * i], res[4 * i + 1], res[4 * i + 2], res[4 * i + 3]);
        asm volatile("fence.proxy.async.global;" ::: "memory");
    }
    float acc0[64], acc1[44];
    float2 q[4];
    {
        uint4 f0, f1, f2, f3;
        auto xseq = [&](int kb) { return (uint32_t)(40 + (uw ? (kb < 10 - XLEAD ? XLEAD + 2 * kb : 10 + kb) : (kb < XLEAD ? kb : 2 * kb - XLEAD + 1))) & 7; };
        auto step = [&](const uint4& f, uint64_t bd) {
            wg_fence();
            wgmma_rs128(acc0, f.x, f.y, f.z, f.w, bd, 1);
            wgmma_rs88(acc1, f.x, f.y, f.z, f.w, bd + 512, 1);
            wg_commit();
        };
        const uint32_t xa = sb + OFF_XR + wt * 16;
        const float2* const gs = &g_stats[(tile * 8 + 2 * t) * 64 + 16 * wq + g];
        zero(acc0); zero(acc1);
        uint32_t xs = xseq(0);
        xwait(20);
        TS(leader, 42 + uw)
        f0 = lds128(xa + xs * 8192); f1 = lds128(xa + xs * 8192 + 2048);
#pragma unroll
        for (int i = 0; i < 4; i++) q[i] = ld_stat(gs + (i & 1) * 64 + 8 * (i >> 1));
        mbar_spin(wfull + (10 & 7) * 8, (10 >> 3) & 1);
#pragma unroll 1
        for (int kb = 0; kb < 10; kb++) {
            const uint32_t wn = 10 + 2 * kb;
            const uint64_t bd = dz + (((dsb + OFF_W + (wn & 7) * 16384) >> 4) | (256u << 16));
            step(f0, bd);
            wg_wait<1>();
            if (kb && lane == 0) mbar_arrive(wempty + ((wn - 1) & 7) * 8);
            f2 = lds128(xa + xs * 8192 + 4096); f3 = lds128(xa + xs * 8192 + 6144);
            const bool w1 = mbar_test(wfull + ((wn + 1) & 7) * 8, (wn >> 3) & 1), x1 = mbar_test(xfull + ((21 + kb) & 7) * 8, ((21 + kb) >> 3) & 1);
            step(f1, bd + 128);
            if (!w1) mbar_spin(wfull + ((wn + 1) & 7) * 8, (wn >> 3) & 1);
            step(f2, bd + 1024);
            if (lane < 2) mbar_arrive_after(xempty + xs * 8, f2.x, f3.x, nil);
            wg_wait<1>();
            if (lane == 0) mbar_arrive(wempty + (wn & 7) * 8);
            xs = xseq(kb + 1);
            if (x1) { f0 = lds128(xa + xs * 8192); f1 = lds128(xa + xs * 8192 + 2048); }
            const bool w2 = mbar_test(wfull + ((wn + 2) & 7) * 8, ((wn + 2) >> 3) & 1);
            step(f3, bd + 1152);
            if (kb < 9 && !x1) { xwait(21 + kb); f0 = lds128(xa + xs * 8192); f1 = lds128(xa + xs * 8192 + 2048); }
            if (!w2) mbar_spin(wfull + ((wn + 2) & 7) * 8, ((wn + 2) >> 3) & 1);
            if (kb == 4) {
                uint32_t it = 0;
                while (__any_sync(~0u, ((__float_as_uint(q[0].x) ^ ep) | (__float_as_uint(q[1].x) ^ ep) | (__float_as_uint(q[2].x) ^ ep) | (__float_as_uint(q[3].x) ^ ep)) & 1)) {
#pragma unroll
                    for (int i = 0; i < 4; i++) q[i] = ld_stat(gs + (i & 1) * 64 + 8 * (i >> 1));
                    SPIN_CHECK(49)
                }
                float a0 = q[0].x + q[1].x, b0 = q[0].y + q[1].y, a1 = q[2].x + q[3].x, b1 = q[2].y + q[3].y;
#pragma unroll
                for (int o = 1; o < 4; o *= 2) {
                    a0 += __shfl_xor_sync(~0u, a0, o); b0 += __shfl_xor_sync(~0u, b0, o);
                    a1 += __shfl_xor_sync(~0u, a1, o); b1 += __shfl_xor_sync(~0u, b1, o);
                }
                a0 *= 1.f / D_; a1 *= 1.f / D_;
                const float r0 = 0.5f * rsqrtf(fmaxf(b0 * (1.f / D_) - a0 * a0, 0.f) + 1e-5f), r1 = 0.5f * rsqrtf(fmaxf(b1 * (1.f / D_) - a1 * a1, 0.f) + 1e-5f);
                const uint32_t sel = t == 0 ? 0x1010 : t == 1 ? 0x4432 : 0x4444;
                q[0] = make_float2(r0, r1);
                q[1] = make_float2(__uint_as_float(__byte_perm(split2(-a0), 0, sel)), __uint_as_float(__byte_perm(split2(-a1), 0, sel)));
            }
            TR(leader, 10 * uw + kb)
        }
        const uint64_t fd = ((uint64_t)8 << 32) | ((dsb + OFF_W + 6 * 16384) >> 4);
        wg_fence();
        wgmma_rs128k(acc0, __float_as_uint(q[1].x), __float_as_uint(q[1].y), 0, 0, fd, 1);
        wgmma_rs88k(acc1, __float_as_uint(q[1].x), __float_as_uint(q[1].y), 0, 0, fd + 128, 1);
        wg_commit();
        if (lane == 0) {
            mbar_arrive(bars + B_XFREE * 8);
            asm volatile("mbarrier.arrive.shared::cluster.b64 _, [%0];" ::"r"(peer_addr(bars + B_XFREE * 8)) : "memory");
        }
    }
    const uint32_t recv = sb + recv_off(uw) + wt * 16;
    uint32_t ha[48] = {}, hb[48], hx[12];
    uint64_t wb = dz + (((dsb + OFF_W) >> 4) | (512u << 16));
    auto wdesc = [&](int n) { return wb + (n & 7) * 1024; };
    auto wwait = [&](int n) { mbar_spin(wfull + (n & 7) * 8, (n >> 3) & 1); };
    auto wfree = [&](int n) { if (lane == 0) mbar_arrive(wempty + (n & 7) * 8); };
    auto fresh = [&]() { wb += pp.nil; asm volatile("" : "+l"(wb)); };
    uint32_t pk[32];
    {
        float P0[64];
        const float r0 = q[0].x, r1 = q[0].y;
        const uint32_t ra = peer_addr(recv), rb = peer_addr(bars + (B_RECV + 4 * uw) * 8);
        auto conv32 = [&](const float* v, int b) {
#pragma unroll
            for (int i = 0; i < 4; i++) {
                ha[8 * b + 2 * i] = pack2(gelu2(v[4 * i] * r0), gelu2(v[4 * i + 1] * r0));
                ha[8 * b + 2 * i + 1] = pack2(gelu2(v[4 * i + 2] * r1), gelu2(v[4 * i + 3] * r1));
            }
#pragma unroll
            for (int s = 2 * b; s < 2 * b + 2; s++) st_peer(ra + s * 2048, ha[4 * s], ha[4 * s + 1], ha[4 * s + 2], ha[4 * s + 3], rb + (b >> 1) * 8);
        };
        auto fetch = [&](int k) {
            mbar_spin(bars + (B_RECV + 4 * uw + k) * 8, 0);
#pragma unroll
            for (int s = 4 * k; s < 4 * k + 4; s++) { const uint4 x = lds128(recv + s * 2048); hb[4 * s] = x.x; hb[4 * s + 1] = x.y; hb[4 * s + 2] = x.z; hb[4 * s + 3] = x.w; }
        };
        auto stage = [&](int n, const uint32_t* a, int steps, int sc) {
            wwait(n);
            wg_fence();
#pragma unroll
            for (int s = 0; s < steps; s++) wgmma_rs128(P0, a[4 * s], a[4 * s + 1], a[4 * s + 2], a[4 * s + 3], wdesc(n) + s * 128, sc || s);
            wg_commit();
        };
        wg_wait<0>();
        reg_fence(acc0); reg_fence(acc1);
        wfree(29); wfree(30);
        TS(leader, 44 + uw)
        uint32_t hr[6];
#pragma unroll
        for (int i = 0; i < 6; i++) {
            const float r = (i & 1) ? r1 : r0;
            hr[i] = pack2(gelu2(acc1[32 + 2 * i] * r), gelu2(acc1[33 + 2 * i] * r));
        }
        if (uw) mbar_spin(bars + B_XFREE * 8, 0);
        st_peer(ra + 24576, hr[0], hr[1], hr[2], hr[3], rb + 24);
        asm volatile("st.async.shared::cluster.mbarrier::complete_tx::bytes.v2.b32 [%0], {%1, %2}, [%3];" ::"r"(ra + 26624 - wt * 8), "r"(hr[4]), "r"(hr[5]), "r"(rb + 24) : "memory");
        conv32(&acc1[0], 4);
        conv32(&acc1[16], 5);
        TS(leader, 46 + uw)
        stage(31, &ha[32], 4, 0);
#pragma unroll
        for (int b = 0; b < 4; b++) {
            conv32(&acc0[16 * b], b);
            if (b == 3) {
                fetch(2);
                mbar_spin(bars + (B_RECV + 4 * uw + 3) * 8, 0);
                const uint4 x = lds128(recv + 24576);
                const uint2 y = lds64(recv + 26624 - wt * 8);
                const uint32_t hp[6] = {x.x, x.y, x.z, x.w, y.x, y.y};
#pragma unroll
                for (int i = 0; i < 6; i++) { hx[i] = (j & 1) ? hp[i] : hr[i]; hx[6 + i] = (j & 1) ? hr[i] : hp[i]; }
            }
            if (!(b & 1)) wwait(32 + (b >> 1));
            wg_fence();
#pragma unroll
            for (int s = 0; s < 2; s++) wgmma_rs128(P0, ha[8 * b + 4 * s], ha[8 * b + 4 * s + 1], ha[8 * b + 4 * s + 2], ha[8 * b + 4 * s + 3], wdesc(32 + (b >> 1)) + (2 * (b & 1) + s) * 128, 1);
            wg_commit();
            if (!(b & 1)) { wg_wait<1>(); wfree(31 + (b >> 1)); }
        }
        TR(leader, 64 + 10 * uw)
        fresh();
        stage(34, &hb[32], 4, 1); wg_wait<1>(); wfree(33);
        fetch(0);
        stage(35, hx, 3, 1); wg_wait<1>(); wfree(34);
        fetch(1);
        stage(36, &hb[0], 4, 1); wg_wait<1>(); wfree(35);
        stage(37, &hb[16], 4, 1); wg_wait<1>(); wfree(36);
        wg_wait<0>();
        reg_fence(P0);
        pack_part<64>(pk, P0, ep);
        uint32_t all = 0;
#pragma unroll
        for (int i = 0; i < 32; i++) all |= pk[i];
        if (lane == 0) mbar_arrive_after(wempty + (37 & 7) * 8, all, 0, nil);
        TR(leader, 65 + 10 * uw)
    }
    {
        uint4* const dst = g_part + (size_t)(tile * 8 + j) * 5120 + wt;
        const uint4* const src = g_part + (size_t)tile * 40960 + j * 512 + wt;
        float F[2][32];
        float2 gb[8];
        uint4 base[4], u1[4], u2[4], u3[4];
#pragma unroll
        for (int c = 2; c < 5; c++) {
            float (&P)[32] = F[c & 1];
            fresh();
#pragma unroll
            for (int s = 0; s < 27; s++) {
                const int e = s < 8 ? 0 : s < 15 ? 1 : s < 23 ? 2 : 3, o = s - (e == 0 ? 0 : e == 1 ? 8 : e == 2 ? 15 : 23), n = 30 + 4 * c + e;
                const uint32_t* a = s < 12 ? &ha[4 * s] : s < 15 ? &hx[4 * (s - 12)] : &hb[4 * (s - 15)];
                if (o == 0) wwait(n);
                if (o == 0 || s == 1) wg_fence();
                wgmma_rs64(P, a[0], a[1], a[2], a[3], wdesc(n) + o * 128, s);
                if (o == 0) { wg_commit(); wg_wait<1>(); if (c > 2 || s) wfree(n - 1); }
                if (s == 0 && c > 2) { reg_fence(F[~c & 1]); pack_part<32>(pk, F[~c & 1], ep); }
                if (c == 2 && s % 3 == 0 && s < 24) st_part(dst + g4_block(s / 12, j) * 512 + (s / 3 & 3) * 128, &pk[4 * (s / 3)]);
                if (c == 3 && s % 4 == 1 && s < 16) st_part(dst + g4_block(2, j) * 512 + s / 4 * 128, &pk[4 * (s / 4)]);
                if (c == 4 && s % ST3 == 0 && s < 4 * ST3) st_part(dst + g4_block(3, j) * 512 + s / ST3 * 128, &pk[4 * (s / ST3)]);
                if (c == 4 && s >= 4 && s < 8) base[s - 4] = ldcg128(&g_x1f[(tile * 8 + j) * 640 + (s - 4) * 128 + wt]);
                if (c == 4 && s >= 19 && s < 23) { gb[2 * s - 38] = lds64f(sb + M_GB + (16 * (s - 19) + 2 * t) * 4); gb[2 * s - 37] = lds64f(sb + M_GB + (16 * (s - 19) + 8 + 2 * t) * 4); }
                if (c == 4 && s >= 8 && s < 12) u1[s - 8] = ld_part(src + (j ^ 6) * 5120 + (s - 8) * 128);
                if (c == 4 && s >= 15 && s < 19) u2[s - 15] = ld_part(src + (j ^ 4) * 5120 + (s - 15) * 128);
                if (c == 4 && s >= LD3 && s < LD3 + 4) u3[s - LD3] = ld_part(src + (j ^ 2) * 5120 + (s - LD3) * 128);
                if (s == 7 || s == 14 || s == 22 || s == 26) wg_commit();
                if (c == 4) { TR(leader && s == 7, 68 + 10 * uw) TR(leader && s == 14, 69 + 10 * uw) TR(leader && s == 22, 70 + 10 * uw) }
            }
            if (c == 2 && lane == 0) mbar_arrive(bars + (B_RING + uw) * 8);
            TR(leader, 64 + c + (c == 4 ? 3 : 0) + 10 * uw)
        }
        float (&O)[32] = F[0];
        float v[32];
        fix4(u1, src + (j ^ 6) * 5120, ep, 4);
        fix4(u2, src + (j ^ 4) * 5120, ep, 5);
        TR(leader, 72 + 10 * uw)
        fix4(u3, src + (j ^ 2) * 5120, ep, 6);
        TR(leader, 73 + 10 * uw)
#pragma unroll
        for (int i = 0; i < 4; i++) { unpack8(&v[8 * i], add2(add2(u1[i], u2[i]), u3[i])); base16(&v[8 * i], base[i], gb[2 * i], gb[2 * i + 1]); }
        reg_fence(v);
        TS(leader, 50 + uw)
        wg_wait<0>();
        reg_fence(O);
        TS(leader, 48 + uw)
        const uint32_t so = sb + recv_off(uw) + wq * 2048;
#pragma unroll
        for (int i = 0; i < 4; i++) {
            float* o = &O[8 * i];
#pragma unroll
            for (int e = 0; e < 8; e++) o[e] = fmaf((e & 1) ? gb[2 * i + (e >> 2)].y : gb[2 * i + (e >> 2)].x, o[e], v[8 * i + e]);
            stsm4(so + (lane & 15) * 128 + (((2 * i + (lane >> 4)) ^ (lane & 7)) << 4), pack2(o[0], o[1]), pack2(o[2], o[3]), pack2(o[4], o[5]), pack2(o[6], o[7]));
        }
        __syncwarp();
#pragma unroll
        for (int i = 0; i < 4; i++) {
            const int row = (lane >> 3) + 4 * i;
            stg128(out + (size_t)(row0 + row) * D_ + 64 * j + 8 * (lane & 7), lds128(so + row * 128 + (((lane & 7) ^ (row & 7)) << 4)));
        }
        warp_arrive(bars + B_OWN * 8);
    }
}

typedef CUresult (*EncFn)(CUtensorMap*, CUtensorMapDataType, cuuint32_t, void*, const cuuint64_t*, const cuuint64_t*, const cuuint32_t*,
                          const cuuint32_t*, CUtensorMapInterleave, CUtensorMapSwizzle, CUtensorMapL2promotion, CUtensorMapFloatOOBfill);

static void enc(EncFn fn, CUtensorMap* m, void* p, int rank, const cuuint64_t* dims, const cuuint64_t* strides, const cuuint32_t* box) {
    const CUtensorMapSwizzle sw = box[0] > 64 ? CU_TENSOR_MAP_SWIZZLE_NONE : CU_TENSOR_MAP_SWIZZLE_128B;
    cuuint32_t es[5] = {1, 1, 1, 1, 1};
    CUresult r = fn(m, CU_TENSOR_MAP_DATA_TYPE_BFLOAT16, rank, p, dims, strides, box, es, CU_TENSOR_MAP_INTERLEAVE_NONE, sw,
                    CU_TENSOR_MAP_L2_PROMOTION_L2_128B, CU_TENSOR_MAP_FLOAT_OOB_FILL_NONE);
    (void)r;
}
static void enc2(EncFn fn, CUtensorMap* m, void* p, uint64_t cols, uint64_t rows, uint32_t bc, uint32_t br) {
    cuuint64_t dims[2] = {cols, rows}, st[1] = {cols * 2};
    cuuint32_t box[2] = {bc, br};
    enc(fn, m, p, 2, dims, st, box);
}

extern "C" void kernel_launch(void* const* d_in, const int* in_sizes, int n_in, void* d_out, int out_size) {
    static Maps mp;
    static Ptrs pp;
    static void* cached[13];
    bool same = true;
    for (int i = 0; i < 13; i++) same = same && (cached[i] == d_in[i]);
    if (!same) {
        void* fnp = nullptr;
        cudaDriverEntryPointQueryResult qr;
        cudaGetDriverEntryPoint("cuTensorMapEncodeTiled", &fnp, cudaEnableDefault, &qr);
        EncFn fn = (EncFn)fnp;
        cudaGetSymbolAddress((void**)&pp.s, g_scratch);
        void *x1T = g_x1T, *t = g_t;
        cuuint64_t dq[3] = {64, S_, 10}, sq[2] = {D_ * 2, 128};
        cuuint32_t bq[3] = {64, 16, 10};
        enc(fn, &mp.q, d_in[0], 3, dq, sq, bq);
        enc2(fn, &mp.k, d_in[1], D_, S_, 80, 67); enc2(fn, &mp.v, d_in[2], D_, S_, 80, 64);
        enc2(fn, &mp.qT, g_qT, 16 * D_, 128, 80, 128);
        enc2(fn, &mp.x1_ld, x1T, S_, D_, 64, 64); enc2(fn, &mp.t_ld, (bf16*)t + 2 * D_, D_, S_, 64, 64);
        enc2(fn, &mp.w1, d_in[7], D_, D_, 64, 64); enc2(fn, &mp.w1h, d_in[7], D_, D_, 64, 160); enc2(fn, &mp.w3h, d_in[9], F_, D_, 64, 160);
        enc2(fn, &mp.wmod, d_in[12], 6 * D_, D_, 64, 160);
        const cuuint64_t R = D_ * 2;
        cuuint64_t da[5] = {D_, 2, 4, 4, 16}, sa[4] = {R, 8 * R, 2 * R, 32 * R}, db[5] = {D_, 2, 2, 4, 8}, sb[4] = {R, 8 * R, 2 * R, 16 * R};
        cuuint32_t ba[5] = {64, 2, 4, 4, 4}, bb[5] = {64, 2, 2, 4, 8};
        enc(fn, &mp.w2a, d_in[8], 5, da, sa, ba); enc(fn, &mp.w2b, (bf16*)d_in[8] + 512 * D_, 5, db, sb, bb);
        cuuint64_t dw[3] = {64, D_, 27}, sw[2] = {F_ * 2, 128};
        cuuint32_t bw[3] = {64, 32, 3};
        enc(fn, &mp.w3a, d_in[9], 3, dw, sw, bw);
        enc2(fn, &mp.w3b, d_in[9], F_, D_, 24, 32);
        enc2(fn, &mp.w4[0], d_in[10], D_, F_, 64, 64); enc2(fn, &mp.w4[1], d_in[10], D_, F_, 64, 48);
        pp.q = (const bf16*)d_in[0]; pp.w_mod = (const bf16*)d_in[12]; pp.shift_k = (const bf16*)d_in[3];
        pp.ssm_k = (const bf16*)d_in[4]; pp.ssm_D = (const bf16*)d_in[5]; pp.w1 = (const bf16*)d_in[7]; pp.w2 = (const bf16*)d_in[8];
        pp.w4 = (const bf16*)d_in[10]; pp.c = (const bf16*)d_in[11];
        cudaFuncSetAttribute(fused_kernel, cudaFuncAttributeMaxDynamicSharedMemorySize, SMEM_BYTES);
        for (int i = 0; i < 13; i++) cached[i] = d_in[i];
    }
    cudaLaunchConfig_t cfg = {};
    cfg.gridDim = dim3(NCTA); cfg.blockDim = dim3(NTHR); cfg.dynamicSmemBytes = SMEM_BYTES; cfg.stream = cudaStreamPerThread;
    cudaLaunchAttribute at[1];
    at[0].id = cudaLaunchAttributeClusterDimension; at[0].val.clusterDim.x = 2; at[0].val.clusterDim.y = 1; at[0].val.clusterDim.z = 1;
    cfg.attrs = at; cfg.numAttrs = 1;
    cudaLaunchKernelEx(&cfg, fused_kernel, pp, (bf16*)d_out, mp);
}
```

```cpp
#include <cuda_runtime.h>
#include <cuda_bf16.h>
#include <cuda.h>
#include <stdint.h>
#include <stdio.h>

typedef __nv_bfloat16 bf16;

constexpr int S_ = 2048, D_ = 640, F_ = 1728;
constexpr int NCTA = 132, NTHR = 512;

constexpr int TAB_BYTES = 9216, VEC_BYTES = 1440;
struct Counters {
    unsigned kv[8 * 32];
    unsigned q[4 * 32], x[2 * 4 * 32];
    unsigned wr[32], tab[32], uv[32], cs[32], done[32];
    unsigned g1[32 * 32];
    unsigned g2[32 * 32];
};
struct Scratch {
    Counters cnt;
    unsigned epoch;
    alignas(1024) bf16 qst[2 * S_];
    alignas(1024) uint4 wr[2 * 8 * 10 * 128];
    alignas(1024) uint2 mod[2 * 6 * D_];
    alignas(1024) uint4 tab[(TAB_BYTES + 8 * VEC_BYTES) / 16];
    alignas(1024) float uv[2 * 3 * D_];
    alignas(1024) float cs3[2 * 1920];
    alignas(1024) float2 stats[32 * 8 * 64];
    alignas(1024) bf16 kvT[D_ * S_];
    alignas(1024) bf16 qT[D_ * S_];
    alignas(1024) bf16 x1T[D_ * S_];
    alignas(1024) bf16 t[(S_ + 4) * D_];
    alignas(1024) uint4 x2f[32 * 40 * 128];
    alignas(1024) uint4 x1f[32 * 8 * 5 * 128];
    alignas(1024) uint4 part[32 * 8 * 10 * 4 * 128];
};
__device__ Scratch g_scratch;
#define g_kvT (pp.s->kvT)
#define g_qT (pp.s->qT)
#define g_x1T (pp.s->x1T)
#define g_qst (pp.s->qst)
#define g_t (pp.s->t)
#define g_x2f (pp.s->x2f)
#define g_x1f (pp.s->x1f)
#define g_part (pp.s->part)
#define g_wr (pp.s->wr)
#define g_mod (pp.s->mod)
#define g_tab (pp.s->tab)
#define g_uv (pp.s->uv)
#define g_cs3 (pp.s->cs3)
#define g_stats (pp.s->stats)
#define g_cnt (pp.s->cnt)
#define g_epoch (pp.s->epoch)

struct Maps {
    CUtensorMap k, v, q;
    CUtensorMap qT;
    CUtensorMap x1_ld, t_ld;
    CUtensorMap w1, w1h, w3h, wmod;
    CUtensorMap w2a, w2b;
    CUtensorMap w3a, w3b;
    CUtensorMap w4[2];
};

struct Ptrs {
    Scratch* s;
    uint64_t nil;
    const bf16 *q, *w_mod, *shift_k, *ssm_k, *ssm_D, *w1, *w2, *w4, *c;
};

constexpr int OFF_W = 0;
constexpr int OFF_XR = 131072;
constexpr int OFF_REM = 196608;
constexpr int OFF_TAB = OFF_REM + 5 * 4096;
constexpr int OFF_ROW = OFF_TAB + 4608;
constexpr int OFF_F1 = OFF_ROW + 4096;
constexpr int RECV_BYTES = 30720;
constexpr int OFF_M = OFF_REM + RECV_BYTES;
constexpr int OFF_OUT = OFF_XR + 32768;
static_assert(OFF_F1 + 1280 <= OFF_M, "G1 map");
constexpr int OFF_ST = 0;
constexpr int OFF_SSM = 20480;
constexpr int OFF_WM = 0;
constexpr int OFF_QIN = 49152;
constexpr int OFF_QT = 49152;
constexpr int OFF_Z = OFF_TAB;
constexpr int OFF_RING = 80896;
constexpr int OFF_KIN = OFF_RING, OFF_VIN = OFF_KIN + 2 * 10752;
constexpr int OFF_CH = OFF_RING + 3 * 16384, CH_BYTES = 13312, OFF_P = 5120;
static_assert(OFF_RING + 5 * 16384 <= OFF_CH + 3 * CH_BYTES && OFF_CH + 5 * CH_BYTES <= OFF_REM, "the last two rings replace channels 0..2");
constexpr int M_BAR = OFF_M;
constexpr int M_F1 = OFF_M + 800;
constexpr int M_GB = M_F1 + 1280, M_C = M_GB + 320, M_SB = M_C + 320, M_CI = M_SB + 320;
constexpr int M_KS = M_CI + 320;
constexpr int M_AB = M_KS + 160;
constexpr int M_EP = M_AB + 80;
constexpr int M_SINK = M_EP + 16;
constexpr int M_NUL = M_SINK + 16;
constexpr int M_TS = M_NUL + 128;
constexpr int SMEM_BYTES = M_TS;
static_assert(SMEM_BYTES <= 232448, "smem");

enum { B_WFULL = 0, B_WEMPTY = 8, B_XEMPTY = 16, B_XFULL = 24  ,
       B_RAW = 40, B_QIN = 41, B_SSM = 42, B_VEC = 43, B_VEC3 = 44, B_WM = 45, B_TAB = 46, B_QRDY = 47,
       B_MODR = 48, B_GATE = 49, B_RETRY = 55, B_S30 = 58, B_RAW2 = 59, B_SUMS = 62, B_RECV = 64  ,
       B_SIG = 72, B_RING = 74  ,
       B_LAND = 80,
       B_XS = 88, B_BK = 90, B_KVS = 91,
       B_XFREE = 92, B_OWN = 93,
       B_IN = 94, B_AGAIN = 96 };
#define T_KVB 1800
#define T_SSM 3300
#define T_Q 0
#define PF_T0 4800
#define PF_DT 420
#define PF_N0 4
#define PF_N 16
#define CH2_DELAY 0
#define HELP_T 1000
#define EPI_SPLIT 1
#define ST3 1
#define LD3 23
#define GATE_W2 7
#define GATE_W3 27
#define GATE_W3B 37
#define W3_N2 13
#define LEAD1 6
#define XLEAD 3

#define SPIN_FAIL(code) __trap();
#define SPIN_LIMIT (1u << 22)
#define STALE(c)
#define STALE1(c)
#define TS(c, i)
#define TG(c, i)
#define TR(c, i)
#define TR2(c, i)
#define TR4(c, i)
#define TR5(c, i)
#define SPIN_CHECK(code) asm volatile("" ::"r"(it));
__device__ __forceinline__ uint32_t s2u(const void* p) { return (uint32_t)__cvta_generic_to_shared(p); }
__device__ __forceinline__ bool elect() {
    uint32_t p;
    asm volatile("{.reg .pred P; elect.sync _|P, 0xffffffff; selp.u32 %0,1,0,P;}" : "=r"(p));
    return p != 0;
}
__device__ __forceinline__ void mbar_init(uint32_t b, uint32_t n) { asm volatile("mbarrier.init.shared.b64 [%0], %1;" ::"r"(b), "r"(n)); }
__device__ __forceinline__ void mbar_expect(uint32_t b, uint32_t bytes) {
    asm volatile("mbarrier.arrive.expect_tx.shared.b64 _, [%0], %1;" ::"r"(b), "r"(bytes) : "memory");
}
__device__ __forceinline__ void mbar_arrive(uint32_t b) { asm volatile("mbarrier.arrive.shared.b64 _, [%0];" ::"r"(b) : "memory"); }
__device__ __forceinline__ void mbar_arrive_after(uint32_t b, uint32_t v0, uint32_t v1, uint32_t nil) { mbar_arrive(b + ((v0 | v1) & nil)); }
__device__ __forceinline__ void warp_arrive(uint32_t b) { __syncwarp(); if (elect()) mbar_arrive(b); }
__device__ __forceinline__ uint32_t peer_addr(uint32_t a) {
    uint32_t r;
    asm("{\n.reg .b32 q;\nmov.u32 q, %%cluster_ctarank;\nxor.b32 q, q, 1;\nmapa.shared::cluster.u32 %0, %1, q;\n}" : "=r"(r) : "r"(a));
    return r;
}
__device__ __forceinline__ bool mbar_test(uint32_t b, uint32_t parity) {
    uint32_t ok;
    asm volatile("{.reg .pred P; mbarrier.test_wait.parity.shared.b64 P, [%1], %2; selp.u32 %0,1,0,P;}" : "=r"(ok) : "r"(b), "r"(parity) : "memory");
    return ok != 0;
}
__device__ __forceinline__ bool mbar_try(uint32_t b, uint32_t parity) {
    uint32_t ok;
    asm volatile("{.reg .pred P; mbarrier.try_wait.parity.shared.b64 P, [%1], %2; selp.u32 %0,1,0,P;}" : "=r"(ok) : "r"(b), "r"(parity) : "memory");
    return ok != 0;
}
__device__ __forceinline__ void mbar_wait(uint32_t b, uint32_t parity) {
    if (__all_sync(0xffffffffu, mbar_try(b, parity))) return;
    uint32_t it = 0;
    while (!__all_sync(0xffffffffu, mbar_try(b, parity))) { if (++it > SPIN_LIMIT) SPIN_FAIL((b >> 3) & 63) }
}
__device__ __forceinline__ void mbar_spin(uint32_t b, uint32_t parity) {
    asm volatile("{\n.reg .pred P;\nSPIN:\nmbarrier.try_wait.parity.shared.b64 P, [%0], %1;\n@!P bra.uni SPIN;\n}" ::"r"(b), "r"(parity) : "memory");
}
__device__ __forceinline__ void bar_sync(int id, int n) { asm volatile("bar.sync %0, %1;" ::"r"(id), "r"(n) : "memory"); }
__device__ __forceinline__ void fence_async_smem() { asm volatile("fence.proxy.async.shared::cta;" ::: "memory"); }
__device__ __forceinline__ void wait_cnt(const unsigned* p, unsigned target, bool tagged = false) {
    unsigned v, it = 0;
    do {
        asm volatile("ld.relaxed.gpu.global.u32 %0, [%1];" : "=r"(v) : "l"(p) : "memory");
        SPIN_CHECK(60 + (target & 3))
    } while (!__all_sync(0xffffffffu, v >= target));
    if (!tagged) asm volatile("fence.acquire.gpu;" ::: "memory");
}
#define X_FENCE 0
__device__ __forceinline__ void signal_cnt(unsigned* p, int lane, int n, bool nofence = false) {
    if (nofence) { if (lane < n) asm volatile("red.relaxed.gpu.global.add.u32 [%0], 1;" ::"l"(p) : "memory"); }
    else if (lane < n) asm volatile("red.release.gpu.global.add.u32 [%0], 1;" ::"l"(p) : "memory");
    __syncwarp();
}
__device__ __forceinline__ void wait_clock(long long c0, int t) {
    while (clock64() - c0 < t) __nanosleep(20);
    __syncwarp();
}
__device__ __forceinline__ void tma_ld2(uint32_t dst, const CUtensorMap* m, int c0, int c1, uint32_t bar) {
    asm volatile("cp.async.bulk.tensor.2d.shared::cluster.global.mbarrier::complete_tx::bytes [%0], [%1, {%3, %4}], [%2];"
                 ::"r"(dst), "l"(m), "r"(bar), "r"(c0), "r"(c1) : "memory");
}
__device__ __forceinline__ void tma_ld3(uint32_t dst, const CUtensorMap* m, int c0, int c1, int c2, uint32_t bar) {
    asm volatile("cp.async.bulk.tensor.3d.shared::cluster.global.mbarrier::complete_tx::bytes [%0], [%1, {%3, %4, %5}], [%2];"
                 ::"r"(dst), "l"(m), "r"(bar), "r"(c0), "r"(c1), "r"(c2) : "memory");
}
__device__ __forceinline__ void tma_ld5(uint32_t dst, const CUtensorMap* m, int col, int blk, uint32_t bar) {
    asm volatile("cp.async.bulk.tensor.5d.shared::cluster.global.mbarrier::complete_tx::bytes [%0], [%1, {%3, %4, %4, %4, %5}], [%2];"
                 ::"r"(dst), "l"(m), "r"(bar), "r"(col), "r"(0), "r"(blk) : "memory");
}
__device__ __forceinline__ void bulk_ld(uint32_t dst, const void* src, uint32_t bytes, uint32_t bar) {
    asm volatile("cp.async.bulk.shared::cluster.global.mbarrier::complete_tx::bytes [%0], [%1], %2, [%3];" ::"r"(dst), "l"(src), "r"(bytes), "r"(bar) : "memory");
}
__device__ __forceinline__ void l2_prefetch(const void* p, uint32_t bytes) {
    asm volatile("cp.async.bulk.prefetch.L2.global [%0], %1;" ::"l"(p), "r"(bytes) : "memory");
}
__device__ __forceinline__ void wg_fence() { asm volatile("wgmma.fence.sync.aligned;" ::: "memory"); }
__device__ __forceinline__ void wg_commit() { asm volatile("wgmma.commit_group.sync.aligned;" ::: "memory"); }
template <int N> __device__ __forceinline__ void wg_wait() { asm volatile("wgmma.wait_group.sync.aligned %0;" ::"n"(N) : "memory"); }
template <int N> __device__ __forceinline__ void reg_fence(float (&d)[N]) {
#pragma unroll
    for (int i = 0; i < N; i++) asm volatile("" : "+f"(d[i])::"memory");
}
template <int N> __device__ __forceinline__ void zero(float (&d)[N]) {
#pragma unroll
    for (int i = 0; i < N; i++) asm volatile("mov.b32 %0, 0;" : "=f"(d[i]));
}
__device__ __forceinline__ uint32_t lds32(uint32_t a) { uint32_t v; asm volatile("ld.shared.b32 %0, [%1];" : "=r"(v) : "r"(a)); return v; }
__device__ __forceinline__ uint2 lds64(uint32_t a) { uint2 v; asm volatile("ld.shared.v2.b32 {%0,%1}, [%2];" : "=r"(v.x), "=r"(v.y) : "r"(a)); return v; }
__device__ __forceinline__ float2 lds64f(uint32_t a) { float2 v; asm volatile("ld.shared.v2.f32 {%0,%1}, [%2];" : "=f"(v.x), "=f"(v.y) : "r"(a)); return v; }
__device__ __forceinline__ void sts32(uint32_t a, uint32_t v) { asm volatile("st.shared.b32 [%0], %1;" ::"r"(a), "r"(v) : "memory"); }
__device__ __forceinline__ void sts64f(uint32_t a, float x, float y) { asm volatile("st.shared.v2.f32 [%0], {%1,%2};" ::"r"(a), "f"(x), "f"(y) : "memory"); }
__device__ __forceinline__ void sts128(uint32_t a, uint32_t x, uint32_t y, uint32_t z, uint32_t w) {
    asm volatile("st.shared.v4.b32 [%0], {%1,%2,%3,%4};" ::"r"(a), "r"(x), "r"(y), "r"(z), "r"(w) : "memory");
}
__device__ __forceinline__ void sts128f(uint32_t a, float x, float y, float z, float w) {
    asm volatile("st.shared.v4.f32 [%0], {%1,%2,%3,%4};" ::"r"(a), "f"(x), "f"(y), "f"(z), "f"(w) : "memory");
}
__device__ __forceinline__ uint4 lds128(uint32_t a) {
    uint4 v;
    asm volatile("ld.shared.v4.b32 {%0,%1,%2,%3}, [%4];" : "=r"(v.x), "=r"(v.y), "=r"(v.z), "=r"(v.w) : "r"(a) : "memory");
    return v;
}
__device__ __forceinline__ float4 lds128f(uint32_t a) {
    float4 v;
    asm volatile("ld.shared.v4.f32 {%0,%1,%2,%3}, [%4];" : "=f"(v.x), "=f"(v.y), "=f"(v.z), "=f"(v.w) : "r"(a) : "memory");
    return v;
}
__device__ __forceinline__ void stg128(void* p, uint32_t x, uint32_t y, uint32_t z, uint32_t w) {
    asm volatile("st.global.v4.b32 [%0], {%1,%2,%3,%4};" ::"l"(p), "r"(x), "r"(y), "r"(z), "r"(w) : "memory");
}
__device__ __forceinline__ void stg128(void* p, uint4 v) { stg128(p, v.x, v.y, v.z, v.w); }
__device__ __forceinline__ void stg128_if(void* p, uint4 v, int on) {
    asm volatile("{\n.reg .pred p;\nsetp.ne.s32 p, %5, 0;\n@p st.global.v4.b32 [%0], {%1,%2,%3,%4};\n}" ::"l"(p), "r"(v.x), "r"(v.y), "r"(v.z), "r"(v.w), "r"(on) : "memory");
}
__device__ __forceinline__ void stg64(void* p, uint32_t x, uint32_t y) { asm volatile("st.global.v2.b32 [%0], {%1,%2};" ::"l"(p), "r"(x), "r"(y) : "memory"); }
__device__ __forceinline__ void stsm4(uint32_t a, uint32_t r0, uint32_t r1, uint32_t r2, uint32_t r3) {
    asm volatile("stmatrix.sync.aligned.m8n8.x4.shared.b16 [%0], {%1,%2,%3,%4};" ::"r"(a), "r"(r0), "r"(r1), "r"(r2), "r"(r3) : "memory");
}
__device__ __forceinline__ void stsm4t(uint32_t a, uint32_t r0, uint32_t r1, uint32_t r2, uint32_t r3) {
    asm volatile("stmatrix.sync.aligned.m8n8.x4.trans.shared.b16 [%0], {%1,%2,%3,%4};" ::"r"(a), "r"(r0), "r"(r1), "r"(r2), "r"(r3) : "memory");
}
__device__ __forceinline__ void ldsm4t(uint32_t a, uint32_t& r0, uint32_t& r1, uint32_t& r2, uint32_t& r3) {
    asm volatile("ldmatrix.sync.aligned.m8n8.x4.trans.shared.b16 {%0,%1,%2,%3}, [%4];" : "=r"(r0), "=r"(r1), "=r"(r2), "=r"(r3) : "r"(a) : "memory");
}
__device__ __forceinline__ uint32_t pack2(float lo, float hi) {
    uint32_t r;
    asm("cvt.rn.bf16x2.f32 %0, %1, %2;" : "=r"(r) : "f"(hi), "f"(lo));
    return r;
}
__device__ __forceinline__ uint32_t mul2(uint32_t a, uint32_t b) { uint32_t r; asm("mul.rn.bf16x2 %0, %1, %2;" : "=r"(r) : "r"(a), "r"(b)); return r; }
__device__ __forceinline__ uint32_t fma2(uint32_t a, uint32_t b, uint32_t c) { uint32_t r; asm("fma.rn.bf16x2 %0, %1, %2, %3;" : "=r"(r) : "r"(a), "r"(b), "r"(c)); return r; }
__device__ __forceinline__ uint32_t add2(uint32_t a, uint32_t b) { uint32_t r; asm("add.rn.bf16x2 %0, %1, %2;" : "=r"(r) : "r"(a), "r"(b)); return r; }
__device__ __forceinline__ void hmma(float (&d)[4], uint32_t a0, uint32_t a1, uint32_t a2, uint32_t a3, uint32_t b0, uint32_t b1) {
    asm volatile("mma.sync.aligned.m16n8k16.row.col.f32.bf16.bf16.f32 {%0,%1,%2,%3}, {%4,%5,%6,%7}, {%8,%9}, {%0,%1,%2,%3};"
        : "+f"(d[0]), "+f"(d[1]), "+f"(d[2]), "+f"(d[3]) : "r"(a0), "r"(a1), "r"(a2), "r"(a3), "r"(b0), "r"(b1));
}
__device__ __forceinline__ float blo(uint32_t w) { return __uint_as_float(w << 16); }
__device__ __forceinline__ float bhi(uint32_t w) { return __uint_as_float(w & 0xffff0000u); }
__device__ __forceinline__ float rbf(float x) { return __bfloat162float(__float2bfloat16_rn(x)); }
__device__ __forceinline__ uint32_t ldg32(const void* p) { uint32_t v; asm volatile("ld.global.nc.b32 %0, [%1];" : "=r"(v) : "l"(p)); return v; }
__device__ __forceinline__ uint2 ldg64(const void* p) { uint2 v; asm volatile("ld.global.nc.v2.b32 {%0,%1}, [%2];" : "=r"(v.x), "=r"(v.y) : "l"(p)); return v; }
__device__ __forceinline__ uint4 ldg128(const void* p) {
    uint4 v;
    asm volatile("ld.global.nc.v4.b32 {%0,%1,%2,%3}, [%4];" : "=r"(v.x), "=r"(v.y), "=r"(v.z), "=r"(v.w) : "l"(p));
    return v;
}
__device__ __forceinline__ uint4 ldcg128(const void* p) {
    uint4 v;
    asm volatile("ld.global.cg.v4.u32 {%0,%1,%2,%3}, [%4];" : "=r"(v.x), "=r"(v.y), "=r"(v.z), "=r"(v.w) : "l"(p) : "memory");
    return v;
}
__device__ __forceinline__ float4 ldcg128f(const void* p) {
    float4 v;
    asm volatile("ld.global.cg.v4.f32 {%0,%1,%2,%3}, [%4];" : "=f"(v.x), "=f"(v.y), "=f"(v.z), "=f"(v.w) : "l"(p) : "memory");
    return v;
}
__device__ __forceinline__ float2 ldcg64f(const void* p) { float2 v; asm volatile("ld.global.cg.v2.f32 {%0,%1}, [%2];" : "=f"(v.x), "=f"(v.y) : "l"(p) : "memory"); return v; }
__device__ __forceinline__ float ldcg32f(const void* p) { float v; asm volatile("ld.global.cg.f32 %0, [%1];" : "=f"(v) : "l"(p) : "memory"); return v; }
__device__ __forceinline__ float2 ld_stat(const float2* p) {
    float2 v;
    asm volatile("{\n.reg .b64 q;\nld.relaxed.gpu.global.b64 q, [%2];\nmov.b64 {%0, %1}, q;\n}" : "=f"(v.x), "=f"(v.y) : "l"(p) : "memory");
    return v;
}
__device__ __forceinline__ uint32_t ld_cold(const unsigned* p) { uint32_t v; asm volatile("ld.relaxed.gpu.global.u32 %0, [%1];" : "=r"(v) : "l"(p) : "memory"); return v; }
__device__ __forceinline__ uint2 ld_mod(const uint2* p) {
    uint64_t v;
    asm volatile("ld.relaxed.gpu.global.b64 %0, [%1];" : "=l"(v) : "l"(p) : "memory");
    return make_uint2((uint32_t)v, (uint32_t)(v >> 32));
}
__device__ __forceinline__ float gelu2(float h) {
    float u = h * fmaf(h * h, 8.f * 0.0356774081f, 2.f * 0.7978845608f);
    float th;
    asm("tanh.approx.f32 %0, %1;" : "=f"(th) : "f"(u));
    return fmaf(h, th, h);
}

__device__ __forceinline__ void conv_channel(float (&d)[64], uint32_t pa, uint64_t db) {
    asm volatile("{\n.reg .b32 a0, a1, a2, a3, b0, b1, b2, b3, t0, t1;\n.reg .b64 d;\nld.shared.b32 a0, [%64];\nld.shared.b32 a1, [%64+128];\nld.shared.b32 a2, [%64+-128];\nmov.b32 a3, a0;\n"
        "ld.shared.b32 t0, [%64+256];\nld.shared.b32 t1, [%64+384];\nadd.s64 d, %65, 0;\nwgmma.fence.sync.aligned;\nwgmma.mma_async.sync.aligned.m64n128k16.f32.bf16.bf16 {%0, %1, %2, %3, %4, %5, %6, %7, %8, %9, %10, %11, %12, %13, %14, %15, %16, %17, %18, %19, %20, %21, %22, %23, %24, %25, %26, %27, %28, %29, %30, %31, %32, %33, %34, %35, %36, %37, %38, %39, %40, %41, %42, %43, %44, %45, %46, %47, %48, %49, %50, %51, %52, %53, %54, %55, %56, %57, %58, %59, %60, %61, %62, %63}, {a0, a1, a2, a3}, d, 0, 1, 1, 0;\nwgmma.commit_group.sync.aligned;\nwgmma.wait_group.sync.aligned 1;\nmov.b32 b2, a1;\nmov.b32 b0, t0;\nmov.b32 b3, t0;\nmov.b32 b1, t1;\n"
        "ld.shared.b32 t0, [%64+512];\nld.shared.b32 t1, [%64+640];\nadd.s64 d, %65, 8;\nwgmma.fence.sync.aligned;\nwgmma.mma_async.sync.aligned.m64n128k16.f32.bf16.bf16 {%0, %1, %2, %3, %4, %5, %6, %7, %8, %9, %10, %11, %12, %13, %14, %15, %16, %17, %18, %19, %20, %21, %22, %23, %24, %25, %26, %27, %28, %29, %30, %31, %32, %33, %34, %35, %36, %37, %38, %39, %40, %41, %42, %43, %44, %45, %46, %47, %48, %49, %50, %51, %52, %53, %54, %55, %56, %57, %58, %59, %60, %61, %62, %63}, {b0, b1, b2, b3}, d, 1, 1, 1, 0;\nwgmma.commit_group.sync.aligned;\nwgmma.wait_group.sync.aligned 1;\nmov.b32 a2, b1;\nmov.b32 a0, t0;\nmov.b32 a3, t0;\nmov.b32 a1, t1;\n"
        "ld.shared.b32 t0, [%64+768];\nld.shared.b32 t1, [%64+896];\nadd.s64 d, %65, 16;\nwgmma.fence.sync.aligned;\nwgmma.mma_async.sync.aligned.m64n128k16.f32.bf16.bf16 {%0, %1, %2, %3, %4, %5, %6, %7, %8, %9, %10, %11, %12, %13, %14, %15, %16, %17, %18, %19, %20, %21, %22, %23, %24, %25, %26, %27, %28, %29, %30, %31, %32, %33, %34, %35, %36, %37, %38, %39, %40, %41, %42, %43, %44, %45, %46, %47, %48, %49, %50, %51, %52, %53, %54, %55, %56, %57, %58, %59, %60, %61, %62, %63}, {a0, a1, a2, a3}, d, 1, 1, 1, 0;\nwgmma.commit_group.sync.aligned;\nwgmma.wait_group.sync.aligned 1;\nmov.b32 b2, a1;\nmov.b32 b0, t0;\nmov.b32 b3, t0;\nmov.b32 b1, t1;\n"
        "ld.shared.b32 t0, [%64+1024];\nld.shared.b32 t1, [%64+1152];\nadd.s64 d, %65, 24;\nwgmma.fence.sync.aligned;\nwgmma.mma_async.sync.aligned.m64n128k16.f32.bf16.bf16 {%0, %1, %2, %3, %4, %5, %6, %7, %8, %9, %10, %11, %12, %13, %14, %15, %16, %17, %18, %19, %20, %21, %22, %23, %24, %25, %26, %27, %28, %29, %30, %31, %32, %33, %34, %35, %36, %37, %38, %39, %40, %41, %42, %43, %44, %45, %46, %47, %48, %49, %50, %51, %52, %53, %54, %55, %56, %57, %58, %59, %60, %61, %62, %63}, {b0, b1, b2, b3}, d, 1, 1, 1, 0;\nwgmma.commit_group.sync.aligned;\nwgmma.wait_group.sync.aligned 1;\nmov.b32 a2, b1;\nmov.b32 a0, t0;\nmov.b32 a3, t0;\nmov.b32 a1, t1;\n"
        "ld.shared.b32 t0, [%64+1280];\nld.shared.b32 t1, [%64+1408];\nadd.s64 d, %65, 32;\nwgmma.fence.sync.aligned;\nwgmma.mma_async.sync.aligned.m64n128k16.f32.bf16.bf16 {%0, %1, %2, %3, %4, %5, %6, %7, %8, %9, %10, %11, %12, %13, %14, %15, %16, %17, %18, %19, %20, %21, %22, %23, %24, %25, %26, %27, %28, %29, %30, %31, %32, %33, %34, %35, %36, %37, %38, %39, %40, %41, %42, %43, %44, %45, %46, %47, %48, %49, %50, %51, %52, %53, %54, %55, %56, %57, %58, %59, %60, %61, %62, %63}, {a0, a1, a2, a3}, d, 1, 1, 1, 0;\nwgmma.commit_group.sync.aligned;\nwgmma.wait_group.sync.aligned 1;\nmov.b32 b2, a1;\nmov.b32 b0, t0;\nmov.b32 b3, t0;\nmov.b32 b1, t1;\n"
        "ld.shared.b32 t0, [%64+1536];\nld.shared.b32 t1, [%64+1664];\nadd.s64 d, %65, 40;\nwgmma.fence.sync.aligned;\nwgmma.mma_async.sync.aligned.m64n128k16.f32.bf16.bf16 {%0, %1, %2, %3, %4, %5, %6, %7, %8, %9, %10, %11, %12, %13, %14, %15, %16, %17, %18, %19, %20, %21, %22, %23, %24, %25, %26, %27, %28, %29, %30, %31, %32, %33, %34, %35, %36, %37, %38, %39, %40, %41, %42, %43, %44, %45, %46, %47, %48, %49, %50, %51, %52, %53, %54, %55, %56, %57, %58, %59, %60, %61, %62, %63}, {b0, b1, b2, b3}, d, 1, 1, 1, 0;\nwgmma.commit_group.sync.aligned;\nwgmma.wait_group.sync.aligned 1;\nmov.b32 a2, b1;\nmov.b32 a0, t0;\nmov.b32 a3, t0;\nmov.b32 a1, t1;\n"
        "ld.shared.b32 t0, [%64+1792];\nld.shared.b32 t1, [%64+1920];\nadd.s64 d, %65, 48;\nwgmma.fence.sync.aligned;\nwgmma.mma_async.sync.aligned.m64n128k16.f32.bf16.bf16 {%0, %1, %2, %3, %4, %5, %6, %7, %8, %9, %10, %11, %12, %13, %14, %15, %16, %17, %18, %19, %20, %21, %22, %23, %24, %25, %26, %27, %28, %29, %30, %31, %32, %33, %34, %35, %36, %37, %38, %39, %40, %41, %42, %43, %44, %45, %46, %47, %48, %49, %50, %51, %52, %53, %54, %55, %56, %57, %58, %59, %60, %61, %62, %63}, {a0, a1, a2, a3}, d, 1, 1, 1, 0;\nwgmma.commit_group.sync.aligned;\nwgmma.wait_group.sync.aligned 1;\nmov.b32 b2, a1;\nmov.b32 b0, t0;\nmov.b32 b3, t0;\nmov.b32 b1, t1;\n"
        "ld.shared.b32 t0, [%64+2048];\nld.shared.b32 t1, [%64+2176];\nadd.s64 d, %65, 56;\nwgmma.fence.sync.aligned;\nwgmma.mma_async.sync.aligned.m64n128k16.f32.bf16.bf16 {%0, %1, %2, %3, %4, %5, %6, %7, %8, %9, %10, %11, %12, %13, %14, %15, %16, %17, %18, %19, %20, %21, %22, %23, %24, %25, %26, %27, %28, %29, %30, %31, %32, %33, %34, %35, %36, %37, %38, %39, %40, %41, %42, %43, %44, %45, %46, %47, %48, %49, %50, %51, %52, %53, %54, %55, %56, %57, %58, %59, %60, %61, %62, %63}, {b0, b1, b2, b3}, d, 1, 1, 1, 0;\nwgmma.commit_group.sync.aligned;\nwgmma.wait_group.sync.aligned 1;\nmov.b32 a2, b1;\nmov.b32 a0, t0;\nmov.b32 a3, t0;\nmov.b32 a1, t1;\n"
        "ld.shared.b32 t0, [%64+2304];\nld.shared.b32 t1, [%64+2432];\nadd.s64 d, %65, 64;\nwgmma.fence.sync.aligned;\nwgmma.mma_async.sync.aligned.m64n96k16.f32.bf16.bf16 {%0, %1, %2, %3, %4, %5, %6, %7, %8, %9, %10, %11, %12, %13, %14, %15, %16, %17, %18, %19, %20, %21, %22, %23, %24, %25, %26, %27, %28, %29, %30, %31, %32, %33, %34, %35, %36, %37, %38, %39, %40, %41, %42, %43, %44, %45, %46, %47}, {a0, a1, a2, a3}, d, 1, 1, 1, 0;\nwgmma.commit_group.sync.aligned;\nwgmma.wait_group.sync.aligned 1;\nmov.b32 b2, a1;\nmov.b32 b0, t0;\nmov.b32 b3, t0;\nmov.b32 b1, t1;\n"
        "ld.shared.b32 t0, [%64+2560];\nld.shared.b32 t1, [%64+2688];\nadd.s64 d, %65, 72;\nwgmma.fence.sync.aligned;\nwgmma.mma_async.sync.aligned.m64n96k16.f32.bf16.bf16 {%0, %1, %2, %3, %4, %5, %6, %7, %8, %9, %10, %11, %12, %13, %14, %15, %16, %17, %18, %19, %20, %21, %22, %23, %24, %25, %26, %27, %28, %29, %30, %31, %32, %33, %34, %35, %36, %37, %38, %39, %40, %41, %42, %43, %44, %45, %46, %47}, {b0, b1, b2, b3}, d, 1, 1, 1, 0;\nwgmma.commit_group.sync.aligned;\nwgmma.wait_group.sync.aligned 1;\nmov.b32 a2, b1;\nmov.b32 a0, t0;\nmov.b32 a3, t0;\nmov.b32 a1, t1;\n"
        "ld.shared.b32 t0, [%64+2816];\nld.shared.b32 t1, [%64+2944];\nadd.s64 d, %65, 80;\nwgmma.fence.sync.aligned;\nwgmma.mma_async.sync.aligned.m64n88k16.f32.bf16.bf16 {%0, %1, %2, %3, %4, %5, %6, %7, %8, %9, %10, %11, %12, %13, %14, %15, %16, %17, %18, %19, %20, %21, %22, %23, %24, %25, %26, %27, %28, %29, %30, %31, %32, %33, %34, %35, %36, %37, %38, %39, %40, %41, %42, %43}, {a0, a1, a2, a3}, d, 1, 1, 1, 0;\nwgmma.commit_group.sync.aligned;\nwgmma.wait_group.sync.aligned 1;\nmov.b32 b2, a1;\nmov.b32 b0, t0;\nmov.b32 b3, t0;\nmov.b32 b1, t1;\n"
        "ld.shared.b32 t0, [%64+3072];\nld.shared.b32 t1, [%64+3200];\nadd.s64 d, %65, 88;\nwgmma.fence.sync.aligned;\nwgmma.mma_async.sync.aligned.m64n88k16.f32.bf16.bf16 {%0, %1, %2, %3, %4, %5, %6, %7, %8, %9, %10, %11, %12, %13, %14, %15, %16, %17, %18, %19, %20, %21, %22, %23, %24, %25, %26, %27, %28, %29, %30, %31, %32, %33, %34, %35, %36, %37, %38, %39, %40, %41, %42, %43}, {b0, b1, b2, b3}, d, 1, 1, 1, 0;\nwgmma.commit_group.sync.aligned;\nwgmma.wait_group.sync.aligned 1;\nmov.b32 a2, b1;\nmov.b32 a0, t0;\nmov.b32 a3, t0;\nmov.b32 a1, t1;\n"
        "ld.shared.b32 t0, [%64+3328];\nld.shared.b32 t1, [%64+3456];\nadd.s64 d, %65, 96;\nwgmma.fence.sync.aligned;\nwgmma.mma_async.sync.aligned.m64n80k16.f32.bf16.bf16 {%0, %1, %2, %3, %4, %5, %6, %7, %8, %9, %10, %11, %12, %13, %14, %15, %16, %17, %18, %19, %20, %21, %22, %23, %24, %25, %26, %27, %28, %29, %30, %31, %32, %33, %34, %35, %36, %37, %38, %39}, {a0, a1, a2, a3}, d, 1, 1, 1, 0;\nwgmma.commit_group.sync.aligned;\nwgmma.wait_group.sync.aligned 1;\nmov.b32 b2, a1;\nmov.b32 b0, t0;\nmov.b32 b3, t0;\nmov.b32 b1, t1;\n"
        "ld.shared.b32 t0, [%64+3584];\nld.shared.b32 t1, [%64+3712];\nadd.s64 d, %65, 104;\nwgmma.fence.sync.aligned;\nwgmma.mma_async.sync.aligned.m64n80k16.f32.bf16.bf16 {%0, %1, %2, %3, %4, %5, %6, %7, %8, %9, %10, %11, %12, %13, %14, %15, %16, %17, %18, %19, %20, %21, %22, %23, %24, %25, %26, %27, %28, %29, %30, %31, %32, %33, %34, %35, %36, %37, %38, %39}, {b0, b1, b2, b3}, d, 1, 1, 1, 0;\nwgmma.commit_group.sync.aligned;\nwgmma.wait_group.sync.aligned 1;\nmov.b32 a2, b1;\nmov.b32 a0, t0;\nmov.b32 a3, t0;\nmov.b32 a1, t1;\n"
        "ld.shared.b32 t0, [%64+3840];\nld.shared.b32 t1, [%64+3968];\nadd.s64 d, %65, 112;\nwgmma.fence.sync.aligned;\nwgmma.mma_async.sync.aligned.m64n72k16.f32.bf16.bf16 {%0, %1, %2, %3, %4, %5, %6, %7, %8, %9, %10, %11, %12, %13, %14, %15, %16, %17, %18, %19, %20, %21, %22, %23, %24, %25, %26, %27, %28, %29, %30, %31, %32, %33, %34, %35}, {a0, a1, a2, a3}, d, 1, 1, 1, 0;\nwgmma.commit_group.sync.aligned;\nwgmma.wait_group.sync.aligned 1;\nmov.b32 b2, a1;\nmov.b32 b0, t0;\nmov.b32 b3, t0;\nmov.b32 b1, t1;\n"
        "ld.shared.b32 t0, [%64+4096];\nld.shared.b32 t1, [%64+4224];\nadd.s64 d, %65, 120;\nwgmma.fence.sync.aligned;\nwgmma.mma_async.sync.aligned.m64n72k16.f32.bf16.bf16 {%0, %1, %2, %3, %4, %5, %6, %7, %8, %9, %10, %11, %12, %13, %14, %15, %16, %17, %18, %19, %20, %21, %22, %23, %24, %25, %26, %27, %28, %29, %30, %31, %32, %33, %34, %35}, {b0, b1, b2, b3}, d, 1, 1, 1, 0;\nwgmma.commit_group.sync.aligned;\nwgmma.wait_group.sync.aligned 1;\nmov.b32 a2, b1;\nmov.b32 a0, t0;\nmov.b32 a3, t0;\nmov.b32 a1, t1;\n"
        "ld.shared.b32 t0, [%64+4352];\nld.shared.b32 t1, [%64+4480];\nadd.s64 d, %65, 128;\nwgmma.fence.sync.aligned;\nwgmma.mma_async.sync.aligned.m64n64k16.f32.bf16.bf16 {%0, %1, %2, %3, %4, %5, %6, %7, %8, %9, %10, %11, %12, %13, %14, %15, %16, %17, %18, %19, %20, %21, %22, %23, %24, %25, %26, %27, %28, %29, %30, %31}, {a0, a1, a2, a3}, d, 1, 1, 1, 0;\nwgmma.commit_group.sync.aligned;\nwgmma.wait_group.sync.aligned 1;\nmov.b32 b2, a1;\nmov.b32 b0, t0;\nmov.b32 b3, t0;\nmov.b32 b1, t1;\n"
        "ld.shared.b32 t0, [%64+4608];\nld.shared.b32 t1, [%64+4736];\nadd.s64 d, %65, 136;\nwgmma.fence.sync.aligned;\nwgmma.mma_async.sync.aligned.m64n64k16.f32.bf16.bf16 {%0, %1, %2, %3, %4, %5, %6, %7, %8, %9, %10, %11, %12, %13, %14, %15, %16, %17, %18, %19, %20, %21, %22, %23, %24, %25, %26, %27, %28, %29, %30, %31}, {b0, b1, b2, b3}, d, 1, 1, 1, 0;\nwgmma.commit_group.sync.aligned;\nwgmma.wait_group.sync.aligned 1;\nmov.b32 a2, b1;\nmov.b32 a0, t0;\nmov.b32 a3, t0;\nmov.b32 a1, t1;\n"
        "ld.shared.b32 t0, [%64+4864];\nld.shared.b32 t1, [%64+4992];\nadd.s64 d, %65, 144;\nwgmma.fence.sync.aligned;\nwgmma.mma_async.sync.aligned.m64n56k16.f32.bf16.bf16 {%0, %1, %2, %3, %4, %5, %6, %7, %8, %9, %10, %11, %12, %13, %14, %15, %16, %17, %18, %19, %20, %21, %22, %23, %24, %25, %26, %27}, {a0, a1, a2, a3}, d, 1, 1, 1, 0;\nwgmma.commit_group.sync.aligned;\nwgmma.wait_group.sync.aligned 1;\nmov.b32 b2, a1;\nmov.b32 b0, t0;\nmov.b32 b3, t0;\nmov.b32 b1, t1;\n"
        "ld.shared.b32 t0, [%64+5120];\nld.shared.b32 t1, [%64+5248];\nadd.s64 d, %65, 152;\nwgmma.fence.sync.aligned;\nwgmma.mma_async.sync.aligned.m64n56k16.f32.bf16.bf16 {%0, %1, %2, %3, %4, %5, %6, %7, %8, %9, %10, %11, %12, %13, %14, %15, %16, %17, %18, %19, %20, %21, %22, %23, %24, %25, %26, %27}, {b0, b1, b2, b3}, d, 1, 1, 1, 0;\nwgmma.commit_group.sync.aligned;\nwgmma.wait_group.sync.aligned 1;\nmov.b32 a2, b1;\nmov.b32 a0, t0;\nmov.b32 a3, t0;\nmov.b32 a1, t1;\n"
        "ld.shared.b32 t0, [%64+5376];\nld.shared.b32 t1, [%64+5504];\nadd.s64 d, %65, 160;\nwgmma.fence.sync.aligned;\nwgmma.mma_async.sync.aligned.m64n48k16.f32.bf16.bf16 {%0, %1, %2, %3, %4, %5, %6, %7, %8, %9, %10, %11, %12, %13, %14, %15, %16, %17, %18, %19, %20, %21, %22, %23}, {a0, a1, a2, a3}, d, 1, 1, 1, 0;\nwgmma.commit_group.sync.aligned;\nwgmma.wait_group.sync.aligned 1;\nmov.b32 b2, a1;\nmov.b32 b0, t0;\nmov.b32 b3, t0;\nmov.b32 b1, t1;\n"
        "ld.shared.b32 t0, [%64+5632];\nld.shared.b32 t1, [%64+5760];\nadd.s64 d, %65, 168;\nwgmma.fence.sync.aligned;\nwgmma.mma_async.sync.aligned.m64n48k16.f32.bf16.bf16 {%0, %1, %2, %3, %4, %5, %6, %7, %8, %9, %10, %11, %12, %13, %14, %15, %16, %17, %18, %19, %20, %21, %22, %23}, {b0, b1, b2, b3}, d, 1, 1, 1, 0;\nwgmma.commit_group.sync.aligned;\nwgmma.wait_group.sync.aligned 1;\nmov.b32 a2, b1;\nmov.b32 a0, t0;\nmov.b32 a3, t0;\nmov.b32 a1, t1;\n"
        "ld.shared.b32 t0, [%64+5888];\nld.shared.b32 t1, [%64+6016];\nadd.s64 d, %65, 176;\nwgmma.fence.sync.aligned;\nwgmma.mma_async.sync.aligned.m64n40k16.f32.bf16.bf16 {%0, %1, %2, %3, %4, %5, %6, %7, %8, %9, %10, %11, %12, %13, %14, %15, %16, %17, %18, %19}, {a0, a1, a2, a3}, d, 1, 1, 1, 0;\nwgmma.commit_group.sync.aligned;\nwgmma.wait_group.sync.aligned 1;\nmov.b32 b2, a1;\nmov.b32 b0, t0;\nmov.b32 b3, t0;\nmov.b32 b1, t1;\n"
        "ld.shared.b32 t0, [%64+6144];\nld.shared.b32 t1, [%64+6272];\nadd.s64 d, %65, 184;\nwgmma.fence.sync.aligned;\nwgmma.mma_async.sync.aligned.m64n40k16.f32.bf16.bf16 {%0, %1, %2, %3, %4, %5, %6, %7, %8, %9, %10, %11, %12, %13, %14, %15, %16, %17, %18, %19}, {b0, b1, b2, b3}, d, 1, 1, 1, 0;\nwgmma.commit_group.sync.aligned;\nwgmma.wait_group.sync.aligned 1;\nmov.b32 a2, b1;\nmov.b32 a0, t0;\nmov.b32 a3, t0;\nmov.b32 a1, t1;\n"
        "ld.shared.b32 t0, [%64+6400];\nld.shared.b32 t1, [%64+6528];\nadd.s64 d, %65, 192;\nwgmma.fence.sync.aligned;\nwgmma.mma_async.sync.aligned.m64n32k16.f32.bf16.bf16 {%0, %1, %2, %3, %4, %5, %6, %7, %8, %9, %10, %11, %12, %13, %14, %15}, {a0, a1, a2, a3}, d, 1, 1, 1, 0;\nwgmma.commit_group.sync.aligned;\nwgmma.wait_group.sync.aligned 1;\nmov.b32 b2, a1;\nmov.b32 b0, t0;\nmov.b32 b3, t0;\nmov.b32 b1, t1;\n"
        "ld.shared.b32 t0, [%64+6656];\nld.shared.b32 t1, [%64+6784];\nadd.s64 d, %65, 200;\nwgmma.fence.sync.aligned;\nwgmma.mma_async.sync.aligned.m64n32k16.f32.bf16.bf16 {%0, %1, %2, %3, %4, %5, %6, %7, %8, %9, %10, %11, %12, %13, %14, %15}, {b0, b1, b2, b3}, d, 1, 1, 1, 0;\nwgmma.commit_group.sync.aligned;\nwgmma.wait_group.sync.aligned 1;\nmov.b32 a2, b1;\nmov.b32 a0, t0;\nmov.b32 a3, t0;\nmov.b32 a1, t1;\n"
        "ld.shared.b32 t0, [%64+6912];\nld.shared.b32 t1, [%64+7040];\nadd.s64 d, %65, 208;\nwgmma.fence.sync.aligned;\nwgmma.mma_async.sync.aligned.m64n24k16.f32.bf16.bf16 {%0, %1, %2, %3, %4, %5, %6, %7, %8, %9, %10, %11}, {a0, a1, a2, a3}, d, 1, 1, 1, 0;\nwgmma.commit_group.sync.aligned;\nwgmma.wait_group.sync.aligned 1;\nmov.b32 b2, a1;\nmov.b32 b0, t0;\nmov.b32 b3, t0;\nmov.b32 b1, t1;\n"
        "ld.shared.b32 t0, [%64+7168];\nld.shared.b32 t1, [%64+7296];\nadd.s64 d, %65, 216;\nwgmma.fence.sync.aligned;\nwgmma.mma_async.sync.aligned.m64n24k16.f32.bf16.bf16 {%0, %1, %2, %3, %4, %5, %6, %7, %8, %9, %10, %11}, {b0, b1, b2, b3}, d, 1, 1, 1, 0;\nwgmma.commit_group.sync.aligned;\nwgmma.wait_group.sync.aligned 1;\nmov.b32 a2, b1;\nmov.b32 a0, t0;\nmov.b32 a3, t0;\nmov.b32 a1, t1;\n"
        "ld.shared.b32 t0, [%64+7424];\nld.shared.b32 t1, [%64+7552];\nadd.s64 d, %65, 224;\nwgmma.fence.sync.aligned;\nwgmma.mma_async.sync.aligned.m64n16k16.f32.bf16.bf16 {%0, %1, %2, %3, %4, %5, %6, %7}, {a0, a1, a2, a3}, d, 1, 1, 1, 0;\nwgmma.commit_group.sync.aligned;\nwgmma.wait_group.sync.aligned 1;\nmov.b32 b2, a1;\nmov.b32 b0, t0;\nmov.b32 b3, t0;\nmov.b32 b1, t1;\n"
        "ld.shared.b32 t0, [%64+7680];\nld.shared.b32 t1, [%64+7808];\nadd.s64 d, %65, 232;\nwgmma.fence.sync.aligned;\nwgmma.mma_async.sync.aligned.m64n16k16.f32.bf16.bf16 {%0, %1, %2, %3, %4, %5, %6, %7}, {b0, b1, b2, b3}, d, 1, 1, 1, 0;\nwgmma.commit_group.sync.aligned;\nwgmma.wait_group.sync.aligned 1;\nmov.b32 a2, b1;\nmov.b32 a0, t0;\nmov.b32 a3, t0;\nmov.b32 a1, t1;\n"
        "ld.shared.b32 t0, [%64+7936];\nld.shared.b32 t1, [%64+8064];\nadd.s64 d, %65, 240;\nwgmma.fence.sync.aligned;\nwgmma.mma_async.sync.aligned.m64n8k16.f32.bf16.bf16 {%0, %1, %2, %3}, {a0, a1, a2, a3}, d, 1, 1, 1, 0;\nwgmma.commit_group.sync.aligned;\nwgmma.wait_group.sync.aligned 1;\nmov.b32 b2, a1;\nmov.b32 b0, t0;\nmov.b32 b3, t0;\nmov.b32 b1, t1;\n"
        "add.s64 d, %65, 248;\nwgmma.fence.sync.aligned;\nwgmma.mma_async.sync.aligned.m64n8k16.f32.bf16.bf16 {%0, %1, %2, %3}, {b0, b1, b2, b3}, d, 1, 1, 1, 0;\nwgmma.commit_group.sync.aligned;\nwgmma.wait_group.sync.aligned 0;\n"
        "}" : "+f"(d[0]), "+f"(d[1]), "+f"(d[2]), "+f"(d[3]), "+f"(d[4]), "+f"(d[5]), "+f"(d[6]), "+f"(d[7]), "+f"(d[8]), "+f"(d[9]), "+f"(d[10]), "+f"(d[11]), "+f"(d[12]), "+f"(d[13]), "+f"(d[14]), "+f"(d[15]), "+f"(d[16]), "+f"(d[17]), "+f"(d[18]), "+f"(d[19]), "+f"(d[20]), "+f"(d[21]), "+f"(d[22]), "+f"(d[23]), "+f"(d[24]), "+f"(d[25]), "+f"(d[26]), "+f"(d[27]), "+f"(d[28]), "+f"(d[29]), "+f"(d[30]), "+f"(d[31]), "+f"(d[32]), "+f"(d[33]), "+f"(d[34]), "+f"(d[35]), "+f"(d[36]), "+f"(d[37]), "+f"(d[38]), "+f"(d[39]), "+f"(d[40]), "+f"(d[41]), "+f"(d[42]), "+f"(d[43]), "+f"(d[44]), "+f"(d[45]), "+f"(d[46]), "+f"(d[47]), "+f"(d[48]), "+f"(d[49]), "+f"(d[50]), "+f"(d[51]), "+f"(d[52]), "+f"(d[53]), "+f"(d[54]), "+f"(d[55]), "+f"(d[56]), "+f"(d[57]), "+f"(d[58]), "+f"(d[59]), "+f"(d[60]), "+f"(d[61]), "+f"(d[62]), "+f"(d[63]) : "r"(pa), "l"(db) : "memory");
}
__device__ __forceinline__ void wgmma_rs80(float (&d)[40], uint32_t a0, uint32_t a1, uint32_t a2, uint32_t a3, uint64_t db, int sc) {
    asm volatile("{\n.reg .pred p;\nsetp.ne.b32 p, %45, 0;\n"
        "wgmma.mma_async.sync.aligned.m64n80k16.f32.bf16.bf16 {%0, %1, %2, %3, %4, %5, %6, %7, %8, %9, %10, %11, %12, %13, %14, %15, %16, %17, %18, %19, %20, %21, %22, %23, %24, %25, %26, %27, %28, %29, %30, %31, %32, %33, %34, %35, %36, %37, %38, %39}, {%40, %41, %42, %43}, %44, p, 1, 1, 1;\n}\n"
        : "+f"(d[0]), "+f"(d[1]), "+f"(d[2]), "+f"(d[3]), "+f"(d[4]), "+f"(d[5]), "+f"(d[6]), "+f"(d[7]), "+f"(d[8]), "+f"(d[9]), "+f"(d[10]), "+f"(d[11]), "+f"(d[12]), "+f"(d[13]), "+f"(d[14]), "+f"(d[15]), "+f"(d[16]), "+f"(d[17]), "+f"(d[18]), "+f"(d[19]), "+f"(d[20]), "+f"(d[21]), "+f"(d[22]), "+f"(d[23]), "+f"(d[24]), "+f"(d[25]), "+f"(d[26]), "+f"(d[27]), "+f"(d[28]), "+f"(d[29]), "+f"(d[30]), "+f"(d[31]), "+f"(d[32]), "+f"(d[33]), "+f"(d[34]), "+f"(d[35]), "+f"(d[36]), "+f"(d[37]), "+f"(d[38]), "+f"(d[39]) : "r"(a0), "r"(a1), "r"(a2), "r"(a3), "l"(db), "r"(sc));
}
__device__ __forceinline__ void wgmma_ss80(float (&d)[40], uint64_t da, uint64_t db, int sc) {
    asm volatile("{\n.reg .pred p;\nsetp.ne.b32 p, %42, 0;\n"
        "wgmma.mma_async.sync.aligned.m64n80k16.f32.bf16.bf16 {%0, %1, %2, %3, %4, %5, %6, %7, %8, %9, %10, %11, %12, %13, %14, %15, %16, %17, %18, %19, %20, %21, %22, %23, %24, %25, %26, %27, %28, %29, %30, %31, %32, %33, %34, %35, %36, %37, %38, %39}, %40, %41, p, 1, 1, 0, 1;\n}\n"
        : "+f"(d[0]), "+f"(d[1]), "+f"(d[2]), "+f"(d[3]), "+f"(d[4]), "+f"(d[5]), "+f"(d[6]), "+f"(d[7]), "+f"(d[8]), "+f"(d[9]), "+f"(d[10]), "+f"(d[11]), "+f"(d[12]), "+f"(d[13]), "+f"(d[14]), "+f"(d[15]), "+f"(d[16]), "+f"(d[17]), "+f"(d[18]), "+f"(d[19]), "+f"(d[20]), "+f"(d[21]), "+f"(d[22]), "+f"(d[23]), "+f"(d[24]), "+f"(d[25]), "+f"(d[26]), "+f"(d[27]), "+f"(d[28]), "+f"(d[29]), "+f"(d[30]), "+f"(d[31]), "+f"(d[32]), "+f"(d[33]), "+f"(d[34]), "+f"(d[35]), "+f"(d[36]), "+f"(d[37]), "+f"(d[38]), "+f"(d[39]) : "l"(da), "l"(db), "r"(sc));
}
__device__ __forceinline__ void wgmma_ss80t(float (&d)[40], uint64_t da, uint64_t db, int sc) {
    asm volatile("{\n.reg .pred p;\nsetp.ne.b32 p, %42, 0;\n"
        "wgmma.mma_async.sync.aligned.m64n80k16.f32.bf16.bf16 {%0, %1, %2, %3, %4, %5, %6, %7, %8, %9, %10, %11, %12, %13, %14, %15, %16, %17, %18, %19, %20, %21, %22, %23, %24, %25, %26, %27, %28, %29, %30, %31, %32, %33, %34, %35, %36, %37, %38, %39}, %40, %41, p, 1, 1, 1, 1;\n}\n"
        : "+f"(d[0]), "+f"(d[1]), "+f"(d[2]), "+f"(d[3]), "+f"(d[4]), "+f"(d[5]), "+f"(d[6]), "+f"(d[7]), "+f"(d[8]), "+f"(d[9]), "+f"(d[10]), "+f"(d[11]), "+f"(d[12]), "+f"(d[13]), "+f"(d[14]), "+f"(d[15]), "+f"(d[16]), "+f"(d[17]), "+f"(d[18]), "+f"(d[19]), "+f"(d[20]), "+f"(d[21]), "+f"(d[22]), "+f"(d[23]), "+f"(d[24]), "+f"(d[25]), "+f"(d[26]), "+f"(d[27]), "+f"(d[28]), "+f"(d[29]), "+f"(d[30]), "+f"(d[31]), "+f"(d[32]), "+f"(d[33]), "+f"(d[34]), "+f"(d[35]), "+f"(d[36]), "+f"(d[37]), "+f"(d[38]), "+f"(d[39]) : "l"(da), "l"(db), "r"(sc));
}
__device__ __forceinline__ void wgmma_ss8_ta(float (&d)[4], uint64_t da, uint64_t db, int sc) {
    asm volatile("{\n.reg .pred p;\nsetp.ne.b32 p, %6, 0;\n"
        "wgmma.mma_async.sync.aligned.m64n8k16.f32.bf16.bf16 {%0, %1, %2, %3}, %4, %5, p, 1, 1, 1, 0;\n}\n"
        : "+f"(d[0]), "+f"(d[1]), "+f"(d[2]), "+f"(d[3]) : "l"(da), "l"(db), "r"(sc));
}
__device__ __forceinline__ void wgmma_rs8(float (&d)[4], uint32_t a0, uint32_t a1, uint32_t a2, uint32_t a3, uint64_t db, int sc) {
    asm volatile("{\n.reg .pred p;\nsetp.ne.b32 p, %9, 0;\n"
        "wgmma.mma_async.sync.aligned.m64n8k16.f32.bf16.bf16 {%0, %1, %2, %3}, {%4, %5, %6, %7}, %8, p, 1, 1, 0;\n}\n"
        : "+f"(d[0]), "+f"(d[1]), "+f"(d[2]), "+f"(d[3]) : "r"(a0), "r"(a1), "r"(a2), "r"(a3), "l"(db), "r"(sc));
}
__device__ __forceinline__ void wgmma_rs128(float (&d)[64], uint32_t a0, uint32_t a1, uint32_t a2, uint32_t a3, uint64_t db, int sc) {
    asm volatile("{\n.reg .pred p;\nsetp.ne.b32 p, %69, 0;\n"
        "wgmma.mma_async.sync.aligned.m64n128k16.f32.bf16.bf16 {%0, %1, %2, %3, %4, %5, %6, %7, %8, %9, %10, %11, %12, %13, %14, %15, %16, %17, %18, %19, %20, %21, %22, %23, %24, %25, %26, %27, %28, %29, %30, %31, %32, %33, %34, %35, %36, %37, %38, %39, %40, %41, %42, %43, %44, %45, %46, %47, %48, %49, %50, %51, %52, %53, %54, %55, %56, %57, %58, %59, %60, %61, %62, %63}, {%64, %65, %66, %67}, %68, p, 1, 1, 1;\n}\n"
        : "+f"(d[0]), "+f"(d[1]), "+f"(d[2]), "+f"(d[3]), "+f"(d[4]), "+f"(d[5]), "+f"(d[6]), "+f"(d[7]), "+f"(d[8]), "+f"(d[9]), "+f"(d[10]), "+f"(d[11]), "+f"(d[12]), "+f"(d[13]), "+f"(d[14]), "+f"(d[15]), "+f"(d[16]), "+f"(d[17]), "+f"(d[18]), "+f"(d[19]), "+f"(d[20]), "+f"(d[21]), "+f"(d[22]), "+f"(d[23]), "+f"(d[24]), "+f"(d[25]), "+f"(d[26]), "+f"(d[27]), "+f"(d[28]), "+f"(d[29]), "+f"(d[30]), "+f"(d[31]), "+f"(d[32]), "+f"(d[33]), "+f"(d[34]), "+f"(d[35]), "+f"(d[36]), "+f"(d[37]), "+f"(d[38]), "+f"(d[39]), "+f"(d[40]), "+f"(d[41]), "+f"(d[42]), "+f"(d[43]), "+f"(d[44]), "+f"(d[45]), "+f"(d[46]), "+f"(d[47]), "+f"(d[48]), "+f"(d[49]), "+f"(d[50]), "+f"(d[51]), "+f"(d[52]), "+f"(d[53]), "+f"(d[54]), "+f"(d[55]), "+f"(d[56]), "+f"(d[57]), "+f"(d[58]), "+f"(d[59]), "+f"(d[60]), "+f"(d[61]), "+f"(d[62]), "+f"(d[63]) : "r"(a0), "r"(a1), "r"(a2), "r"(a3), "l"(db), "r"(sc));
}
__device__ __forceinline__ void wgmma_rs88(float (&d)[44], uint32_t a0, uint32_t a1, uint32_t a2, uint32_t a3, uint64_t db, int sc) {
    asm volatile("{\n.reg .pred p;\nsetp.ne.b32 p, %49, 0;\n"
        "wgmma.mma_async.sync.aligned.m64n88k16.f32.bf16.bf16 {%0, %1, %2, %3, %4, %5, %6, %7, %8, %9, %10, %11, %12, %13, %14, %15, %16, %17, %18, %19, %20, %21, %22, %23, %24, %25, %26, %27, %28, %29, %30, %31, %32, %33, %34, %35, %36, %37, %38, %39, %40, %41, %42, %43}, {%44, %45, %46, %47}, %48, p, 1, 1, 1;\n}\n"
        : "+f"(d[0]), "+f"(d[1]), "+f"(d[2]), "+f"(d[3]), "+f"(d[4]), "+f"(d[5]), "+f"(d[6]), "+f"(d[7]), "+f"(d[8]), "+f"(d[9]), "+f"(d[10]), "+f"(d[11]), "+f"(d[12]), "+f"(d[13]), "+f"(d[14]), "+f"(d[15]), "+f"(d[16]), "+f"(d[17]), "+f"(d[18]), "+f"(d[19]), "+f"(d[20]), "+f"(d[21]), "+f"(d[22]), "+f"(d[23]), "+f"(d[24]), "+f"(d[25]), "+f"(d[26]), "+f"(d[27]), "+f"(d[28]), "+f"(d[29]), "+f"(d[30]), "+f"(d[31]), "+f"(d[32]), "+f"(d[33]), "+f"(d[34]), "+f"(d[35]), "+f"(d[36]), "+f"(d[37]), "+f"(d[38]), "+f"(d[39]), "+f"(d[40]), "+f"(d[41]), "+f"(d[42]), "+f"(d[43]) : "r"(a0), "r"(a1), "r"(a2), "r"(a3), "l"(db), "r"(sc));
}
__device__ __forceinline__ void wgmma_rs128k(float (&d)[64], uint32_t a0, uint32_t a1, uint32_t a2, uint32_t a3, uint64_t db, int sc) {
    asm volatile("{\n.reg .pred p;\nsetp.ne.b32 p, %69, 0;\n"
        "wgmma.mma_async.sync.aligned.m64n128k16.f32.bf16.bf16 {%0, %1, %2, %3, %4, %5, %6, %7, %8, %9, %10, %11, %12, %13, %14, %15, %16, %17, %18, %19, %20, %21, %22, %23, %24, %25, %26, %27, %28, %29, %30, %31, %32, %33, %34, %35, %36, %37, %38, %39, %40, %41, %42, %43, %44, %45, %46, %47, %48, %49, %50, %51, %52, %53, %54, %55, %56, %57, %58, %59, %60, %61, %62, %63}, {%64, %65, %66, %67}, %68, p, 1, 1, 0;\n}\n"
        : "+f"(d[0]), "+f"(d[1]), "+f"(d[2]), "+f"(d[3]), "+f"(d[4]), "+f"(d[5]), "+f"(d[6]), "+f"(d[7]), "+f"(d[8]), "+f"(d[9]), "+f"(d[10]), "+f"(d[11]), "+f"(d[12]), "+f"(d[13]), "+f"(d[14]), "+f"(d[15]), "+f"(d[16]), "+f"(d[17]), "+f"(d[18]), "+f"(d[19]), "+f"(d[20]), "+f"(d[21]), "+f"(d[22]), "+f"(d[23]), "+f"(d[24]), "+f"(d[25]), "+f"(d[26]), "+f"(d[27]), "+f"(d[28]), "+f"(d[29]), "+f"(d[30]), "+f"(d[31]), "+f"(d[32]), "+f"(d[33]), "+f"(d[34]), "+f"(d[35]), "+f"(d[36]), "+f"(d[37]), "+f"(d[38]), "+f"(d[39]), "+f"(d[40]), "+f"(d[41]), "+f"(d[42]), "+f"(d[43]), "+f"(d[44]), "+f"(d[45]), "+f"(d[46]), "+f"(d[47]), "+f"(d[48]), "+f"(d[49]), "+f"(d[50]), "+f"(d[51]), "+f"(d[52]), "+f"(d[53]), "+f"(d[54]), "+f"(d[55]), "+f"(d[56]), "+f"(d[57]), "+f"(d[58]), "+f"(d[59]), "+f"(d[60]), "+f"(d[61]), "+f"(d[62]), "+f"(d[63]) : "r"(a0), "r"(a1), "r"(a2), "r"(a3), "l"(db), "r"(sc));
}
__device__ __forceinline__ void wgmma_rs88k(float (&d)[44], uint32_t a0, uint32_t a1, uint32_t a2, uint32_t a3, uint64_t db, int sc) {
    asm volatile("{\n.reg .pred p;\nsetp.ne.b32 p, %49, 0;\n"
        "wgmma.mma_async.sync.aligned.m64n88k16.f32.bf16.bf16 {%0, %1, %2, %3, %4, %5, %6, %7, %8, %9, %10, %11, %12, %13, %14, %15, %16, %17, %18, %19, %20, %21, %22, %23, %24, %25, %26, %27, %28, %29, %30, %31, %32, %33, %34, %35, %36, %37, %38, %39, %40, %41, %42, %43}, {%44, %45, %46, %47}, %48, p, 1, 1, 0;\n}\n"
        : "+f"(d[0]), "+f"(d[1]), "+f"(d[2]), "+f"(d[3]), "+f"(d[4]), "+f"(d[5]), "+f"(d[6]), "+f"(d[7]), "+f"(d[8]), "+f"(d[9]), "+f"(d[10]), "+f"(d[11]), "+f"(d[12]), "+f"(d[13]), "+f"(d[14]), "+f"(d[15]), "+f"(d[16]), "+f"(d[17]), "+f"(d[18]), "+f"(d[19]), "+f"(d[20]), "+f"(d[21]), "+f"(d[22]), "+f"(d[23]), "+f"(d[24]), "+f"(d[25]), "+f"(d[26]), "+f"(d[27]), "+f"(d[28]), "+f"(d[29]), "+f"(d[30]), "+f"(d[31]), "+f"(d[32]), "+f"(d[33]), "+f"(d[34]), "+f"(d[35]), "+f"(d[36]), "+f"(d[37]), "+f"(d[38]), "+f"(d[39]), "+f"(d[40]), "+f"(d[41]), "+f"(d[42]), "+f"(d[43]) : "r"(a0), "r"(a1), "r"(a2), "r"(a3), "l"(db), "r"(sc));
}
__device__ __forceinline__ void wgmma_rs80k(float (&d)[40], uint32_t a0, uint32_t a1, uint32_t a2, uint32_t a3, uint64_t db, int sc) {
    asm volatile("{\n.reg .pred p;\nsetp.ne.b32 p, %45, 0;\n"
        "wgmma.mma_async.sync.aligned.m64n80k16.f32.bf16.bf16 {%0, %1, %2, %3, %4, %5, %6, %7, %8, %9, %10, %11, %12, %13, %14, %15, %16, %17, %18, %19, %20, %21, %22, %23, %24, %25, %26, %27, %28, %29, %30, %31, %32, %33, %34, %35, %36, %37, %38, %39}, {%40, %41, %42, %43}, %44, p, 1, 1, 0;\n}\n"
        : "+f"(d[0]), "+f"(d[1]), "+f"(d[2]), "+f"(d[3]), "+f"(d[4]), "+f"(d[5]), "+f"(d[6]), "+f"(d[7]), "+f"(d[8]), "+f"(d[9]), "+f"(d[10]), "+f"(d[11]), "+f"(d[12]), "+f"(d[13]), "+f"(d[14]), "+f"(d[15]), "+f"(d[16]), "+f"(d[17]), "+f"(d[18]), "+f"(d[19]), "+f"(d[20]), "+f"(d[21]), "+f"(d[22]), "+f"(d[23]), "+f"(d[24]), "+f"(d[25]), "+f"(d[26]), "+f"(d[27]), "+f"(d[28]), "+f"(d[29]), "+f"(d[30]), "+f"(d[31]), "+f"(d[32]), "+f"(d[33]), "+f"(d[34]), "+f"(d[35]), "+f"(d[36]), "+f"(d[37]), "+f"(d[38]), "+f"(d[39]) : "r"(a0), "r"(a1), "r"(a2), "r"(a3), "l"(db), "r"(sc));
}
__device__ __forceinline__ void wgmma_rs64(float (&d)[32], uint32_t a0, uint32_t a1, uint32_t a2, uint32_t a3, uint64_t db, int sc) {
    asm volatile("{\n.reg .pred p;\nsetp.ne.b32 p, %37, 0;\n"
        "wgmma.mma_async.sync.aligned.m64n64k16.f32.bf16.bf16 {%0, %1, %2, %3, %4, %5, %6, %7, %8, %9, %10, %11, %12, %13, %14, %15, %16, %17, %18, %19, %20, %21, %22, %23, %24, %25, %26, %27, %28, %29, %30, %31}, {%32, %33, %34, %35}, %36, p, 1, 1, 1;\n}\n"
        : "+f"(d[0]), "+f"(d[1]), "+f"(d[2]), "+f"(d[3]), "+f"(d[4]), "+f"(d[5]), "+f"(d[6]), "+f"(d[7]), "+f"(d[8]), "+f"(d[9]), "+f"(d[10]), "+f"(d[11]), "+f"(d[12]), "+f"(d[13]), "+f"(d[14]), "+f"(d[15]), "+f"(d[16]), "+f"(d[17]), "+f"(d[18]), "+f"(d[19]), "+f"(d[20]), "+f"(d[21]), "+f"(d[22]), "+f"(d[23]), "+f"(d[24]), "+f"(d[25]), "+f"(d[26]), "+f"(d[27]), "+f"(d[28]), "+f"(d[29]), "+f"(d[30]), "+f"(d[31]) : "r"(a0), "r"(a1), "r"(a2), "r"(a3), "l"(db), "r"(sc));
}

__device__ __forceinline__ uint64_t mkdesc(uint32_t lo) { return ((uint64_t)0x40000040u << 32) | lo; }
template <int F> __device__ __forceinline__ uint32_t lop3(uint32_t a, uint32_t b, uint32_t c) { uint32_t r; asm("lop3.b32 %0, %1, %2, %3, %4;" : "=r"(r) : "r"(a), "r"(b), "r"(c), "n"(F)); return r; }
__device__ __forceinline__ void stg128_tag(void* p, uint32_t x, uint32_t y, uint32_t z, uint32_t u, uint32_t ep, int w) {
    stg128(p, lop3<0xB8>(x, w == 0, ep), lop3<0xB8>(y, w == 1, ep), lop3<0xB8>(z, w == 2, ep), lop3<0xB8>(u, w == 3, ep));
}
__device__ __forceinline__ uint32_t tag(uint32_t w, uint32_t ep) { asm("lop3.b32 %0, %0, 1, %1, 0xB8;" : "+r"(w) : "r"(ep)); return w; }
template <int N> __device__ __forceinline__ void pack_part(uint32_t (&p)[32], const float (&v)[N], uint32_t ep) {
#pragma unroll
    for (int i = 0; i < N / 2; i++) p[i] = (i & 3) ? pack2(v[2 * i], v[2 * i + 1]) : tag(pack2(v[2 * i], v[2 * i + 1]), ep);
#pragma unroll
    for (int i = 0; i < N / 2; i++) asm volatile("" : "+r"(p[i]));
}
__device__ __forceinline__ void st_part(uint4* p, const uint32_t* v) {
    asm volatile("{\n.reg .b64 l, h;\n.reg .b128 q;\nmov.b64 l, {%1, %2};\nmov.b64 h, {%3, %4};\nmov.b128 q, {l, h};\nst.relaxed.gpu.global.b128 [%0], q;\n}"
                 ::"l"(p), "r"(v[0]), "r"(v[1]), "r"(v[2]), "r"(v[3]) : "memory");
}
__device__ __forceinline__ void st_peer(uint32_t a, uint32_t x, uint32_t y, uint32_t z, uint32_t w, uint32_t bar) {
    asm volatile("st.async.shared::cluster.mbarrier::complete_tx::bytes.v4.b32 [%0], {%1, %2, %3, %4}, [%5];" ::"r"(a), "r"(x), "r"(y), "r"(z), "r"(w), "r"(bar) : "memory");
}
__device__ __forceinline__ int g4_block(int c, int j) { return c ? j ^ (8 - 2 * c) : 8 + (j & 1); }
__device__ __forceinline__ uint32_t recv_off(int w) { return w ? OFF_XR : OFF_REM; }
__device__ __forceinline__ uint4 ld_part(const void* p) {
    uint4 v;
    asm volatile("{\n.reg .b64 l, h;\n.reg .b128 q;\nld.relaxed.gpu.global.b128 q, [%4];\nmov.b128 {l, h}, q;\nmov.b64 {%0, %1}, l;\nmov.b64 {%2, %3}, h;\n}"
                 : "=r"(v.x), "=r"(v.y), "=r"(v.z), "=r"(v.w) : "l"(p) : "memory");
    return v;
}
__device__ __forceinline__ void ld_part4(uint4 (&u)[4], const uint4* p, int st) {
#pragma unroll
    for (int i = 0; i < 4; i++) u[i] = ld_part(p + i * st);
}
__device__ __forceinline__ uint32_t stale4(const uint4 (&u)[4], uint32_t ep) { return (u[0].x ^ ep) | (u[1].x ^ ep) | (u[2].x ^ ep) | (u[3].x ^ ep); }
__device__ __forceinline__ void fix4(uint4 (&u)[4], const uint4* p, uint32_t ep, int code) {
    unsigned it = 0;
    while (__any_sync(~0u, stale4(u, ep) & 1)) {
        ld_part4(u, p, 128);
        STALE(code)
        SPIN_CHECK(58)
    }
}
__device__ __forceinline__ void add8(float* v, uint4 u) {
    v[0] += blo(u.x); v[1] += bhi(u.x); v[2] += blo(u.y); v[3] += bhi(u.y);
    v[4] += blo(u.z); v[5] += bhi(u.z); v[6] += blo(u.w); v[7] += bhi(u.w);
}
__device__ __forceinline__ void unpack8(float* v, uint4 u) {
    v[0] = blo(u.x); v[1] = bhi(u.x); v[2] = blo(u.y); v[3] = bhi(u.y); v[4] = blo(u.z); v[5] = bhi(u.z); v[6] = blo(u.w); v[7] = bhi(u.w);
}
__device__ __forceinline__ uint4 add2(uint4 a, uint4 b) { return make_uint4(add2(a.x, b.x), add2(a.y, b.y), add2(a.z, b.z), add2(a.w, b.w)); }
__device__ __forceinline__ void base16(float* v, uint4 b, float2 c, float2 d) {
    v[0] = fmaf(c.x, v[0], blo(b.x)); v[1] = fmaf(c.y, v[1], bhi(b.x)); v[2] = fmaf(c.x, v[2], blo(b.y)); v[3] = fmaf(c.y, v[3], bhi(b.y));
    v[4] = fmaf(d.x, v[4], blo(b.z)); v[5] = fmaf(d.y, v[5], bhi(b.z)); v[6] = fmaf(d.x, v[6], blo(b.w)); v[7] = fmaf(d.y, v[7], bhi(b.w));
}
__device__ __forceinline__ uint32_t split2(float x) { const float h = rbf(x); return pack2(h, x - h); }
__device__ __forceinline__ uint32_t b80_desc(uint32_t dsb, uint32_t wn, uint32_t rn, uint32_t h) {
    const uint32_t wb = dsb + OFF_W + (wn & 7) * 16384 + h * 8192, rm = dsb + OFF_REM + rn * 4096 + h * 2048;
    return (wb >> 4) | ((rm - wb) << 12);
}
constexpr int64_t B80_STEP = 128 - (126 << 16), B80_HALF = 512 - (384 << 16);
constexpr uint32_t ring_mask(int L) {
    uint32_t m = 0;
    for (int i = L; i < 20; i++) m |= (uint32_t)(i >= 20 - L || !((i - L) & 1)) << i;
    return m;
}
constexpr uint32_t M0 = ring_mask(LEAD1), M1 = ring_mask(10), M2 = ring_mask(XLEAD);
__device__ __forceinline__ uint32_t ring_pos(int w, int n, int L) { return w ? (n < 10 - L ? L + 2 * n : 10 + n) : (n < L ? n : 2 * n - L + 1); }
__device__ __forceinline__ int g1_block(int n, int j) { return n < 5 ? 2 * n + (j & 1) : 2 * n - 9 - (j & 1); }

__device__ __forceinline__ void load_tile(const Ptrs& pp, const Maps& mp, uint32_t dst, int e, int tile, int kb, int j, uint32_t bar) {
    mbar_expect(bar, 8192);
    if (e == 2) bulk_ld(dst, &g_x2f[(tile * 10 + kb) * 512], 8192, bar);
    else tma_ld2(dst, e ? &mp.t_ld : &mp.x1_ld, 64 * (e ? kb : tile), 64 * (e ? tile : g1_block(kb, j)), bar);
}

template <int OCT>
__device__ __forceinline__ void gemv_tile(float (&d)[4], uint32_t a, uint32_t b, int kb0) {
    uint32_t alo = ((a & 0x3FFFF) >> 4) | 0x10000u, blo_ = ((b & 0x3FFFF) >> 4) | (OCT << 16);
#pragma unroll 1
    for (int s = 0; s < 20; s += 4) {
        const int kb = kb0 + (s >> 2);
        const uint32_t bk = blo_ + (OCT == 7 ? (kb & 1) * 288 + (kb >> 1) * 56 : kb * 64);
        wg_fence();
#pragma unroll
        for (int q = 0; q < 4; q++) wgmma_ss8_ta(d, mkdesc(alo + (s + q) * 128), ((uint64_t)8 << 32) | (bk + q * 2 * OCT), s + q);
        wg_commit();
    }
    wg_wait<0>();
    reg_fence(d);
}

__device__ __forceinline__ void flush_tile(uint32_t st, bf16* dst, int u) {
#pragma unroll
    for (int i = 0; i < 2; i++) {
        const int idx = u + 320 * i, row = idx >> 3, c = idx & 7;
        stg128(dst + (size_t)row * S_ + 8 * c, lds128(st + row * 128 + ((c ^ ((row >> 1) & 7)) << 4)));
    }
}

__device__ __forceinline__ int tid_now() { int t; asm volatile("mov.u32 %0, %%tid.x;" : "=r"(t)); return t; }
__device__ __forceinline__ float zscale(float c) { return c == 0.f ? 0x1p-30f : c; }
__device__ __forceinline__ bool bar_any(int id, bool p) {
    uint32_t r;
    asm volatile("{\n.reg .pred a, b;\nsetp.ne.u32 a, %2, 0;\nbarrier.red.or.pred.aligned b, %1, 128, a;\nselp.u32 %0, 1, 0, b;\n}" : "=r"(r) : "r"(id), "r"((uint32_t)p) : "memory");
    return r != 0;
}

__global__ void __launch_bounds__(NTHR, 1) fused_kernel(const __grid_constant__ Ptrs pp, bf16* __restrict__ out, const __grid_constant__ Maps mp) {
    extern __shared__ __align__(1024) uint8_t smem_raw[];
    const uint32_t sb = s2u(smem_raw), bars = sb + M_BAR, dsb = sb & 0x3FFFF;
    const int id = blockIdx.x, warp = __shfl_sync(0xffffffffu, (int)threadIdx.x >> 5, 0), wg = warp >> 2;
    const long long c0 = clock64();
#define TIDS const int tid = tid_now(), lane = tid & 31, wt = tid & 127, g = lane >> 2, t = lane & 3; (void)wt; (void)g; (void)t;
    TS(threadIdx.x == 0, 0) TG(threadIdx.x == 0, 62)

    if (id >= 128) {
        TIDS
        if (sb & 1023) __trap();
        const int hs = id - 128;
        constexpr int H_B = 204800;
        static_assert(H_B + TAB_BYTES + 8 * VEC_BYTES <= OFF_M, "helper map");
        if (warp < 10 && elect()) { mbar_init(bars + warp * 8, 1); mbar_init(bars + 80 + warp * 8, 1); asm volatile("fence.mbarrier_init.release.cluster;" ::: "memory"); }
        __syncthreads();
        const uint32_t e0 = ld_cold(&g_epoch);
        wait_clock(c0, HELP_T);
        uint4 wr[10];
#pragma unroll
        for (int u = 0; u < 10; u++) wr[u] = ldg128(((hs >> 1) ? pp.w2 : pp.w1) + (size_t)(320 * (hs & 1) + (tid >> 4) + 32 * u) * D_ + 512 + 8 * (tid & 15));
        {
            const int r = tid >> 4, c = tid & 15;
            uint4* dst[2];
#pragma unroll
            for (int e = 0; e < 2; e++) {
                const int p = !(hs >> 1) ? r : e && (hs & 1) ? (r & ~14) | ((r & 6) << 1) | ((r & 8) >> 2) : (r & ~30) | ((r & 6) << 2) | ((r & 24) >> 2);
                dst[e] = &g_wr[(((hs >> 1) * 8 + (c >> 1)) * 10 + 5 * (hs & 1)) * 128 + (p & 15) * 8 + ((2 * (p >> 4) + (c & 1)) ^ (p & 7))];
            }
#pragma unroll
            for (int u = 0; u < 10; u++) stg128(reinterpret_cast<uint4*>(reinterpret_cast<uintptr_t>(dst[u >= 6]) ^ (64 * (u & 1))) + (u >> 1) * 128, wr[u]);
        }
        __syncthreads();
        if (warp == 0) signal_cnt(&g_cnt.wr[0], lane, 1);
        __syncthreads();
        if (warp < 5 && elect()) {
            const int un = 5 * hs + warp;
            mbar_expect(bars + warp * 8, 40960);
            tma_ld2(sb + warp * 40960, &mp.w1h, 64 * (un >> 1), 320 * (un & 1), bars + warp * 8);
            tma_ld2(sb + warp * 40960 + 20480, &mp.w1h, 64 * (un >> 1), 320 * (un & 1) + 160, bars + warp * 8);
        }
        if (tid < 320) {
            const uint4* gm = reinterpret_cast<const uint4*>(g_mod + 3 * D_) + tid;
            const unsigned epoch = e0 + 1;
            uint4 r[6];
            unsigned it = 0;
            for (;;) {
                uint32_t bad = 0;
#pragma unroll
                for (int i = 0; i < 6; i++) { r[i] = ld_part(gm + (i >> 1) * (D_ / 2) + (i & 1) * 3 * D_); bad |= (r[i].y ^ epoch) | (r[i].w ^ epoch); }
                if (__all_sync(~0u, !bad)) break;
                if (++it > SPIN_LIMIT) SPIN_FAIL(54)
            }
            uint32_t mv[3];
#pragma unroll
            for (int i = 0; i < 3; i++) mv[i] = pack2(__uint_as_float(r[2 * i].x) + __uint_as_float(r[2 * i + 1].x), __uint_as_float(r[2 * i].z) + __uint_as_float(r[2 * i + 1].z));
            const uint32_t sw2 = mv[0], cw = add2(mv[1], 0x3f803f80u), gw = mv[2];
            const float c0 = blo(cw), c1 = bhi(cw), s0 = blo(sw2), s1 = bhi(sw2);
            const float i0 = __frcp_rn(zscale(c0)), i1 = __frcp_rn(zscale(c1));
            const uint32_t ci = pack2(i0, i1), cq = pack2(i0 * i0, i1 * i1);
            const uint32_t a = sb + H_B + ((tid >> 5) & 1) * 4608 + (tid >> 6) * 896 + ((tid >> 2) & 7) * 112 + (tid & 3) * 4;
            sts32(a, ci); sts32(a + 16, pack2(i0 - blo(ci), i1 - bhi(ci)));
            sts32(a + 32, cq); sts32(a + 48, pack2(fmaf(i0, i0, -blo(cq)), fmaf(i1, i1, -bhi(cq))));
            sts32(a + 64, cw); sts32(a + 80, sw2); sts32(a + 96, 0x3f803f80u);
            if ((tid & ~35) == 284) sts32(a + 112, 0);
            const uint32_t v = sb + H_B + TAB_BYTES + (tid < 256 ? (tid >> 5) * VEC_BYTES + (tid & 31) * 8 : ((tid - 256) >> 3) * VEC_BYTES + 256 + (tid & 7) * 8);
            sts64f(v, blo(gw), bhi(gw)); sts64f(v + 320, c0, c1); sts64f(v + 640, s0, s1); sts64f(v + 960, i0, i1);
            float k[5] = {c0 + c1, s0 + s1, fmaf(c0, c0, c1 * c1), fmaf(c0, s0, c1 * s1), fmaf(s0, s0, s1 * s1)};
#pragma unroll 1
            for (int o = 16; o; o >>= 1) {
#pragma unroll
                for (int e = 0; e < 5; e++) k[e] += __shfl_xor_sync(~0u, k[e], o);
            }
            const uint32_t ks = sb + H_B + TAB_BYTES + (lane & 7) * VEC_BYTES + 1280 + (warp >> 1) * 32;
            if ((warp & 1) && lane < 8) { sts128f(ks, k[0], k[1], k[2], k[3]); sts128f(ks + 16, k[4], 0.f, 0.f, 0.f); }
            bar_sync(3, 320);
            if (!(warp & 1) && lane < 8) {
                const float4 o = lds128f(ks);
                sts128f(ks, k[0] + o.x, k[1] + o.y, k[2] + o.z, k[3] + o.w); sts32(ks + 16, __float_as_uint(k[4] + __uint_as_float(lds32(ks + 16))));
            }
            fence_async_smem();
        }
        __syncthreads();
        if (hs == 0 && warp == 15 && elect()) {
            asm volatile("cp.async.bulk.global.shared::cta.bulk_group [%0], [%1], %2;\ncp.async.bulk.commit_group;\ncp.async.bulk.wait_group 0;"
                         ::"l"(g_tab), "r"(sb + H_B), "n"(TAB_BYTES + 8 * VEC_BYTES) : "memory");
            asm volatile("red.release.gpu.global.add.u32 [%0], 1;" ::"l"(&g_cnt.tab[0]) : "memory");
        }
        __syncwarp();
#pragma unroll 1
        for (int i = wg; i < 20; i += 4) {
            const int r = i / 5, b = i - 5 * r, un = 5 * hs + b, u3 = 20 * r + un;
            auto refill = [&](int e, int u, uint32_t fb) {
                mbar_expect(fb, 40960);
                tma_ld2(sb + e * 40960, &mp.w3h, 64 * (u >> 1), 320 * (u & 1), fb);
                tma_ld2(sb + e * 40960 + 20480, &mp.w3h, 64 * (u >> 1), 320 * (u & 1) + 160, fb);
            };
            if (i > 4 && i < 9) {
                bar_sync(1, 512);
                if (warp == 0) {
                    signal_cnt(&g_cnt.uv[0], lane, 1);
                    if (elect()) {
#pragma unroll 1
                        for (int e = 0; e < 5; e++) refill(e, 5 * hs + e, bars + (5 + e) * 8);
                        l2_prefetch(pp.w2 + (size_t)160 * hs * D_, 160 * D_ * 2);
                    }
                    __syncwarp();
                }
            }
            mbar_wait(bars + i * 8, 0);
            float d[4];
            gemv_tile<7>(d, sb + b * 40960, sb + H_B, 5 * (un & 1));
            const int col = 16 * (warp & 3) + g;
            float* dst = r ? g_cs3 + (un & 1) * 1920 + 64 * ((u3 >> 1) - 10) + col : g_uv + (un & 1) * 3 * D_ + 2 * D_ + 64 * (un >> 1) + col;
            if (t == 3) { dst[0] = d[0]; dst[8] = d[2]; }
            if (r == 0 && t == 2) { dst[-2 * D_] = d[0]; dst[8 - 2 * D_] = d[2]; dst[-D_] = d[1]; dst[8 - D_] = d[3]; }
            if (r == 1 || r == 2) {
                bar_sync(4 + wg, 128);
                if (wt == 0) refill(b, u3, bars + (i + 5) * 8);
            }
        }
        __syncthreads();
        if (warp == 0) signal_cnt(&g_cnt.cs[0], lane, 1);
        if (tid == 511) l2_prefetch(pp.w4 + (size_t)432 * hs * D_, 432 * D_ * 2);
        if (tid == 0 && hs == 3) {
            uint32_t it = 0;
            while (ld_cold(&g_epoch) == e0) { __nanosleep(256); if (++it > (1u << 20)) SPIN_FAIL(48) }
        }
        return;
    }

    if (elect()) {
        if (warp == 15) {
            mbar_init(bars + B_IN * 8, 1); mbar_init(bars + B_IN * 8 + 8, 1);
            asm volatile("fence.mbarrier_init.release.cluster;" ::: "memory");
            mbar_expect(bars + B_IN * 8, 131 * 160);
            tma_ld2(sb + OFF_KIN, &mp.k, 80 * (id & 7), 64 * (id >> 3) - 3, bars + B_IN * 8);
            tma_ld2(sb + OFF_VIN, &mp.v, 80 * (id & 7), 64 * (id >> 3), bars + B_IN * 8);
        } else if (warp < 13) {
            const uint32_t n = (0x1C14111111881ull >> (4 * warp)) & 15;
#pragma unroll
            for (int i = 0; i < 4; i++) mbar_init(bars + warp * 64 + i * 8, n);
            if (warp == 11) { mbar_init(bars + B_XFREE * 8, 16); mbar_init(bars + B_OWN * 8, 8); }
            else if (warp < 11) {
#pragma unroll
                for (int i = 4; i < 8; i++) mbar_init(bars + warp * 64 + i * 8, n);
            }
            asm volatile("fence.mbarrier_init.release.cluster;" ::: "memory");
        }
    }
    asm volatile("" ::"l"(pp.s), "l"(pp.c), "l"(out));
    TR4((threadIdx.x & 31) == 0, warp)
    const int pr = id >> 1;
    const int grp = pr < 4 ? 15 : pr < 36 ? (pr - 4) & 7 : 8 + (pr - 36) % 7;
    const int j = 2 * (pr < 4 ? pr : pr < 36 ? (pr - 4) >> 3 : (pr - 36) / 7) + (id & 1);

    if (wg == 3) {
        TIDS
        const int sw = warp - 12;
        uint32_t ep = ld_cold(&g_epoch);
        TR4(lane == 0, 20 + sw)
        __syncthreads();
        TR4(lane == 0, 30 + sw)
        asm volatile("barrier.cluster.arrive.relaxed.aligned;" ::: "memory");
        if (sw == 0) {
#pragma unroll 1
            for (int n = PF_N0; n < PF_N; n++) {
                wait_clock(c0, PF_T0 + PF_DT * (n - PF_N0));
                if (elect()) {
                    if (n < 8) l2_prefetch((const char*)(n < 4 ? pp.ssm_k : pp.q) + (size_t)id * 20480 + (n & 3) * 5120, 5120);
                    else l2_prefetch((const char*)pp.w_mod + (size_t)id * 38400 + (n - 8) * 4800, 4800);
                }
            }
        } else if (sw == 1) {
            wait_clock(c0, T_SSM);
            if (elect()) {
                mbar_expect(bars + B_SSM * 8, 20480);
                bulk_ld(sb + OFF_SSM, pp.ssm_k + (size_t)5 * id * S_, 20480, bars + B_SSM * 8);
            }
            mbar_spin(bars + B_KVS * 8, 0);
            signal_cnt(&g_cnt.kv[(id & 7) * 32], lane, 1, true);
            TS(lane == 0, 2)
            if (T_Q) wait_clock(c0, T_Q); else mbar_spin(bars + B_RAW * 8, 0);
            if (elect()) {
                mbar_expect(bars + B_QIN * 8, 20480);
                tma_ld3(sb + OFF_QIN, &mp.q, 0, 16 * id, 0, bars + B_QIN * 8);
            }
        } else if (sw == 2) {
            if (elect()) {
#pragma unroll 1
                for (int i = 2; i < (int)(sizeof(Maps) / sizeof(CUtensorMap)); i++) asm volatile("prefetch.tensormap [%0];" ::"l"(&mp.k + i) : "memory");
#pragma unroll 1
                for (int i = B_SUMS; i < B_SIG; i++) mbar_expect(bars + i * 8, i < B_RECV ? 2048 : (i & 3) < 3 ? 8192 : 3072);
            }
            wait_cnt(&g_cnt.kv[(id >> 4) * 32], 16, true);
            TS(lane == 0, 4)
            if (elect()) {
                mbar_expect(bars + B_RAW * 8, 12288);
                mbar_expect(bars + B_RAW2 * 8, 8192);
#pragma unroll
                for (int c = 0; c < 5; c++) bulk_ld(sb + OFF_CH + c * CH_BYTES, g_kvT + (size_t)(5 * id + c) * S_, 4096, bars + (c < 3 ? B_RAW : B_RAW2) * 8);
            }
            mbar_spin(bars + B_BK * 8, 0);
            mbar_spin(bars + B_RAW2 * 8, 0);
            if (!T_Q) mbar_spin(bars + B_QIN * 8, 0);
            if (id < 120 && elect()) {
                mbar_expect(bars + B_WM * 8, 40960);
                tma_ld2(sb + OFF_WM, &mp.wmod, 64 * pr, 320 * (id & 1), bars + B_WM * 8);
                tma_ld2(sb + OFF_WM + 20480, &mp.wmod, 64 * pr, 320 * (id & 1) + 160, bars + B_WM * 8);
            }
            TS(lane == 0, 57)
        } else {
            wait_clock(c0, T_KVB);
            if (elect()) {
                mbar_expect(bars + (B_IN + 1) * 8, 131 * 160);
                tma_ld2(sb + OFF_KIN + 10752, &mp.k, 80 * (id & 7), 64 * (id >> 3) + 1021, bars + (B_IN + 1) * 8);
                tma_ld2(sb + OFF_VIN + 10240, &mp.v, 80 * (id & 7), 64 * (id >> 3) + 1024, bars + (B_IN + 1) * 8);
            }
            TS(lane == 0, 53)
            if (lane == 0) sts32(sb + M_EP, ep + 1);
            sts32(sb + M_NUL + lane * 4, 0);
#pragma unroll 1
            for (int m = lane; m < 40; m += 32) {
                const uint4 c = ldg128(pp.c + 320 * (id & 1) + 8 * m);
                uint32_t w[4] = {c.x, c.y, c.z, c.w};
#pragma unroll
                for (int i = 0; i < 4; i++) { const float a = blo(w[i]), b = bhi(w[i]); w[i] = pack2(__fdividef(a, 1.f + __expf(-a)), __fdividef(b, 1.f + __expf(-b))); }
                sts128(sb + OFF_Z + m * 128, w[0], w[1], w[2], w[3]);
#pragma unroll 1
                for (int r = 1; r < 8; r++) sts128(sb + OFF_Z + m * 128 + r * 16, 0, 0, 0, 0);
            }
            fence_async_smem();
        }
        {
            mbar_spin(bars + B_QIN * 8, 0);
            asm volatile("add.u32 %0, %0, 1;" : "+r"(ep));
            TS(wt == 0, 54)
            const int tk = 8 * ((lane >> 1) & 1) + 2 * (lane >> 3) + (lane & 1), ck = 4 * (sw & 1) + ((lane >> 1) & 2);
            const uint32_t src = sb + OFF_QIN + (sw >> 1) * 2048 + tk * 128;
            bf16* dst = g_qT + (size_t)id * 16 * D_ + (32 * sw + 8 * (t & 2) + g) * 16 + 8 * (t & 1);
#pragma unroll
            for (int i = 0; i < 5; i++) {
                uint32_t r[8];
                ldsm4t(src + i * 4096 + ((ck ^ (tk & 7)) << 4), r[0], r[1], r[2], r[3]);
                ldsm4t(src + i * 4096 + (((ck + 1) ^ (tk & 7)) << 4), r[4], r[5], r[6], r[7]);
                stg128(dst + i * 2048, tag(r[0], ep), r[1], r[2], r[3]);
                stg128(dst + i * 2048 + 128, tag(r[4], ep), r[5], r[6], r[7]);
            }
            float s1 = 0.f, s2 = 0.f;
#pragma unroll 2
            for (int i = 0; i < 10; i++) {
                const uint4 w4 = lds128(sb + OFF_QIN + i * 2048 + wt * 16);
                const uint32_t w[4] = {w4.x, w4.y, w4.z, w4.w};
#pragma unroll
                for (int e = 0; e < 4; e++) { const float a = blo(w[e]), b = bhi(w[e]); s1 += a + b; s2 = fmaf(a, a, fmaf(b, b, s2)); }
            }
#pragma unroll
            for (int o = 1; o < 8; o *= 2) { s1 += __shfl_xor_sync(~0u, s1, o); s2 += __shfl_xor_sync(~0u, s2, o); }
            s1 *= 1.f / D_;
            uint32_t rs = pack2(rsqrtf(fmaxf(s2 * (1.f / D_) - s1 * s1, 0.f) + 1e-5f), 0.f);
            if (lane < 8) rs = tag(rs, ep);
            rs = pack2(blo(rs), -s1 * blo(rs));
            const uint32_t sel = lane ? 0x7632 : 0x5410;
            const uint32_t a0 = __shfl_sync(~0u, rs, 0), a1 = __shfl_sync(~0u, rs, 8), a2 = __shfl_sync(~0u, rs, 16), a3 = __shfl_sync(~0u, rs, 24);
            if (lane < 2) stg64(g_qst + lane * S_ + 16 * id + 4 * sw, tag(__byte_perm(a0, a1, sel), ep), __byte_perm(a2, a3, sel));
            TS(wt == 0, 55)
        }
        bar_sync(6, 128);
        if (sw == 3) {
            signal_cnt(&g_cnt.q[(lane & 3) * 32], lane, 4, true);
            TS(lane == 0, 3)
        }
        if (id < 120) {
            mbar_spin(bars + B_WM * 8, 0);
            TS(wt == 0, 56)
            float d[4];
            gemv_tile<8>(d, sb + OFF_WM, sb + OFF_Z, 0);
            const float d2 = __shfl_up_sync(~0u, d[2], 1);
            TS(wt == 0, 7)
            if (t < 2) asm volatile("{\n.reg .b64 v;\nmov.b64 v, {%1, %2};\nst.relaxed.gpu.global.b64 [%0], v;\n}" ::"l"(g_mod + (id & 1) * 6 * D_ + 64 * pr + 16 * sw + g + 8 * t),
                                    "r"(__float_as_uint(t ? d2 : d[0])), "r"(ep) : "memory");
        }
        bar_sync(6, 128);
        asm volatile("setmaxnreg.dec.sync.aligned.u32 32;");
        asm volatile("barrier.cluster.wait.aligned;" ::: "memory");
        if (sw & 1) {
            mbar_spin(bars + (B_XS + (sw >> 1)) * 8, 0);
            signal_cnt(&g_cnt.x[(2 * (sw & 2) + (lane & 3)) * 32], lane, 4, true);
            TS(lane == 0, 20 + (sw >> 1))
        }
        if (sw == 1) return;
        if (sw == 2) {
            {
                wait_cnt(&g_cnt.tab[0], 1);
                if (elect()) {
                    mbar_expect(bars + B_TAB * 8, TAB_BYTES / 2 + VEC_BYTES);
                    bulk_ld(sb + OFF_TAB, g_tab + (j & 1) * (TAB_BYTES / 32), TAB_BYTES / 2, bars + B_TAB * 8);
                    bulk_ld(sb + M_GB, g_tab + (TAB_BYTES + j * VEC_BYTES) / 16, VEC_BYTES, bars + B_TAB * 8);
                }
                TS(lane == 0, 5)
            }
            mbar_spin(bars + (B_XS + 1) * 8, 0);
#pragma unroll
            for (int e = 0; e < 3; e++) {
                uint32_t m = e == 0 ? M0 : e == 1 ? M1 : M2;
                int k0 = 0, k1 = 0;
#pragma unroll 1
                for (int n = 20 * e; n < 20 * e + 20; n++, m >>= 1) {
                    const int w = m & 1, kb = w ? k1 : k0, tile = grp + 16 * w;
                    k0 += 1 - w; k1 += w;
                    if (kb == 0) {
                        wait_cnt(e == 0 ? &g_cnt.x[(4 * w + (id & 3)) * 32] : e == 1 ? &g_cnt.g1[min(max(tile + min(lane, 2) - 1, 0), 31) * 32] : &g_cnt.g2[tile * 32], e ? 32 : 128, true);
                        TS(lane == 0, 26 + 2 * e + w)
                    }
                    mbar_spin(bars + (B_XEMPTY + (n & 7)) * 8, ((n >> 3) & 1) ^ 1);
                    TR2(lane == 0 && n < 40, 20 + n)
                    if (elect()) load_tile(pp, mp, sb + OFF_XR + (n & 7) * 8192, e, tile, kb, j, bars + (B_LAND + (n & 7)) * 8);
                }
            }
            mbar_spin(bars + B_VEC3 * 8, 0);
            unsigned old = 0;
            if (lane == 0) old = atomicAdd(&g_cnt.done[0], 1u);
            if (__shfl_sync(~0u, old, 0) == 127) {
#pragma unroll 1
                for (int i = lane; i < (int)(sizeof(Counters) / 128); i += 32) reinterpret_cast<unsigned*>(&g_cnt)[i * 32] = 0;
                if (lane == 0) atomicAdd(&g_epoch, 1u);
            }
        } else if (sw == 0) {
            wait_cnt(&g_cnt.wr[0], 4);
            mbar_spin(bars + B_QRDY * 8, 0);
            const uint32_t wf = bars + B_WFULL * 8, we = bars + B_WEMPTY * 8;
#pragma unroll 1
            for (int n = 0; n < 5; n++) {
                if (n == 3) mbar_spin(bars + (B_XS + 1) * 8, 0);
                TR2(lane == 0, 70 + n)
                if (elect()) {
                    const uint32_t fb = wf + n * 8, dst = sb + OFF_W + n * 16384;
                    mbar_expect(fb, 20480);
#pragma unroll 1
                    for (int h = 0; h < 2; h++) {
                        const int kb = g1_block(2 * n + h, j);
                        tma_ld2(dst + h * 8192, &mp.w1, 64 * j, 64 * kb, fb);
                        bulk_ld(sb + OFF_REM + n * 4096 + h * 2048, &g_wr[(j * 10 + kb) * 128], 2048, fb);
                    }
                }
            }
            mbar_spin(bars + B_GATE * 8, 0);
#pragma unroll 1
            for (int i = -3; i < 5; i++) {
                const int n = i < 0 ? 8 + i : 5 + i;
                const uint32_t fb = wf + (n & 7) * 8;
                if (i >= 0) mbar_spin(we + i * 8, 0);
                TR2(lane == 0 && i >= 0, 70 + n)
                if (elect()) {
                    if (i < 0 || i >= 3) { mbar_expect(fb, 20480); tma_ld5(sb + OFF_W + (n & 7) * 16384, n < 9 ? &mp.w2a : &mp.w2b, 64 * j, n < 9 ? 4 * (n - 5) : 0, fb); }
                    if (i >= 0) bulk_ld(sb + OFF_REM + i * 4096, &g_wr[((8 + j) * 10 + 2 * i) * 128], 4096, fb);
                }
            }
            mbar_spin(bars + (B_GATE + 1) * 8, 0);
#pragma unroll 1
            for (int n = 10; n < 30; n++) {
                if (n == W3_N2) mbar_spin(bars + (B_GATE + 2) * 8, 0);
                mbar_spin(we + (n & 7) * 8, ((n >> 3) & 1) ^ 1);
                TR2(lane == 0, 70 + n)
                if (elect()) {
                    const uint32_t dst = sb + OFF_W + (n & 7) * 16384, fb = wf + (n & 7) * 8;
                    mbar_expect(fb, 13824);
                    tma_ld3(dst, &mp.w3a, 0, 32 * (n - 10), 3 * j, fb);
                    tma_ld2(dst + 12288, &mp.w3b, 1536 + 24 * j, 32 * (n - 10), fb);
                }
            }
            mbar_spin(we + 6 * 8, 0);
            if (elect()) mbar_arrive(bars + B_S30 * 8);
#pragma unroll 1
            for (int n = 31; n < 50; n++) {
                const int rem = 96 + 3 * (j >> 1);
                int m0, m1, r0, r1, c0_, c1_;
                if (n < 38) {
                    c0_ = g4_block(0, j); c1_ = g4_block(1, j);
                    m0 = m1 = n == 35;
                    r0 = r1 = n == 35 ? rem : 6 * (j ^ (n >= 34)) + ((0x2004204 >> (4 * (n - 31))) & 15);
                } else {
                    const int e = (n - 38) & 3;
                    c0_ = c1_ = g4_block(2 + ((n - 38) >> 2), j);
                    m0 = 0; m1 = e == 1 ? 1 : e == 3 ? -1 : 0;
                    r0 = 6 * (j ^ (e >> 1)) + 4 * (e & 1); r1 = e == 1 ? rem : r0 + 2;
                }
                mbar_spin(we + (n & 7) * 8, ((n >> 3) & 1) ^ 1);
                if (elect()) {
                    const uint32_t dst = sb + OFF_W + (n & 7) * 16384, fb = wf + (n & 7) * 8;
                    mbar_expect(fb, m1 < 0 ? 8192 : 16384 - 2048 * (m0 + m1));
                    tma_ld2(dst, &mp.w4[m0], 64 * c0_, r0 * (32 >> m0), fb);
                    if (m1 >= 0) tma_ld2(dst + 8192, &mp.w4[m1], 64 * c1_, r1 * (32 >> m1), fb);
                }
            }
#pragma unroll 1
            for (int w = 0; w < 2; w++) {
                const uint4* src = g_part + (size_t)(grp + 16 * w) * 40960;
                mbar_spin(bars + (B_RING + w) * 8, 1);
                if (elect()) {
                    const uint32_t fb = bars + (B_IN + w) * 8, rem = sb + OFF_OUT + w * 10240;
                    mbar_expect(fb, 10240);
                    bulk_ld(rem + 8192, &g_x1f[((grp + 16 * w) * 8 + j) * 640 + 512], 2048, fb);
#pragma unroll 1
                    for (int i = 0; i < 4; i++) bulk_ld(rem + i * 2048, src + ((j >> 2) + 2 * i) * 5120 + 4096 + j * 128, 2048, fb);
                }
            }
        } else {
            wait_cnt(&g_cnt.uv[0], 4);
#pragma unroll 1
            for (int c = lane; c < 80; c += 32) {
                const float* src = g_uv + (c < 64 ? 64 * j + c : 448 + 16 * j + c);
                const uint32_t u = split2(ldcg32f(src) + ldcg32f(src + 3 * D_)), v = split2(ldcg32f(src + D_) + ldcg32f(src + 4 * D_));
                const uint32_t s = split2(ldcg32f(src + 2 * D_) + ldcg32f(src + 5 * D_));
                sts128(sb + OFF_F1 + c * 16, u, __byte_perm(u, v, 0x5410), __byte_perm(v, 0, 0x1032), s);
                sts128(sb + M_F1 + c * 16, s & 0xffffu, 0, 0, 0);
            }
            fence_async_smem();
            warp_arrive(bars + B_VEC * 8);
            TS(lane == 0, 9)
            wait_cnt(&g_cnt.cs[0], 4);
            if (elect()) mbar_arrive(bars + B_VEC3 * 8);
            uint32_t s[7];
#pragma unroll
            for (int i = 0; i < 7; i++) {
                const int c = min(lane + 32 * i, 215);
                const float* src = g_cs3 + (i < 6 ? 192 * j + c : 1344 + 24 * j + c);
                s[i] = split2(ldcg32f(src) + ldcg32f(src + 1920));
            }
            TS(lane == 0, 19)
            mbar_spin(bars + B_S30 * 8, 0);
#pragma unroll
            for (int i = 0; i < 7; i++) sts128(sb + OFF_W + 6 * 16384 + min(lane + 32 * i, 215) * 16, s[i], s[i] & 0xffffu, 0, 0);
            fence_async_smem();
            warp_arrive(bars + (B_WFULL + 6) * 8);
        }
        return;
    }

    {
        uint32_t ep;
        {
            TIDS
            ep = ld_cold(&g_epoch);
            const int cp = (tid + 16) % 40, cp1 = tid % 40;
            const uint4 sh0 = ldg128(pp.shift_k + (80 * (id & 7) + 2 * cp1) * 4), sh1 = ldg128(pp.shift_k + (80 * (id & 7) + 2 * cp) * 4);
            uint32_t dd;
            asm volatile("ld.global.nc.u16 %0, [%1];" : "=r"(dd) : "l"(pp.ssm_D + 5 * id + min(wg + 3 * lane, 4)));
            TR4(lane == 0, 40 + warp)
            __syncthreads();
            asm volatile("barrier.cluster.arrive.relaxed.aligned;" ::: "memory");
            asm volatile("add.u32 %0, %0, 1;" : "+r"(ep));
#pragma unroll 1
            for (int hw = 0; hw < 2; hw++) {
                if ((unsigned)(warp - 2 * hw) >= 10) continue;
                const int u = tid - 64 * hw;
                const int c = hw ? cp : cp1, oc = u / 40, line = 31 - 16 * hw - (id >> 3);
                const uint4 sh = hw ? sh1 : sh0;
                const uint32_t st = sb + OFF_ST + hw * 10240, sta = st + c * 256 + ((((6 - 2 * (oc & 3)) ^ (oc >> 2) ^ (line & 1)) ^ (c & 7)) << 4), in = oc * 1280 + c * 4;
                const uint32_t f0 = __byte_perm(sh.x, sh.z, 0x5410), f1 = __byte_perm(sh.x, sh.z, 0x7632), f2 = __byte_perm(sh.y, sh.w, 0x5410), f3 = __byte_perm(sh.y, sh.w, 0x7632);
                uint32_t kk[11], vv[8];
                mbar_spin(bars + (B_IN + hw) * 8, 0);
                TS(tid == 64, 18 + 42 * hw)
#pragma unroll
                for (int i = 0; i < 11; i++) kk[i] = lds32(sb + OFF_KIN + hw * 10752 + in + i * 160);
#pragma unroll
                for (int i = 0; i < 8; i++) vv[i] = lds32(sb + OFF_VIN + hw * 10240 + in + i * 160);
#pragma unroll
                for (int i = 0; i < 8; i++) vv[i] = mul2(fma2(kk[i + 3], f0, fma2(kk[i + 2], f1, fma2(kk[i + 1], f2, mul2(kk[i], f3)))), vv[i]);
                sts128(sta, tag(__byte_perm(vv[0], vv[1], 0x5410), ep), __byte_perm(vv[2], vv[3], 0x5410), __byte_perm(vv[4], vv[5], 0x5410), __byte_perm(vv[6], vv[7], 0x5410));
                sts128(sta + 128, tag(__byte_perm(vv[0], vv[1], 0x7632), ep), __byte_perm(vv[2], vv[3], 0x7632), __byte_perm(vv[4], vv[5], 0x7632), __byte_perm(vv[6], vv[7], 0x7632));
                bar_sync(7 + hw, 320);
                flush_tile(st, g_kvT + (size_t)(80 * (id & 7)) * S_ + 64 * line, u);
                TS(tid == 64 && hw, 1)
            }
            warp_arrive(bars + B_KVS * 8);
            if (tid < 320) sts128(sb + OFF_CH + (tid >> 6) * CH_BYTES + 4096 + (tid & 63) * 16, 0, 0, 0, 0);
            mbar_spin(bars + B_SSM * 8, 0);
            TS(tid == 0, 14)
            uint2 w[7];
            uint32_t pv[7];
#pragma unroll
            for (int i = 0; i < 7; i++) {
                const uint32_t a = sb + OFF_SSM + min(wg + 3 * i, 19) * 1024 + wt * 8;
                w[i] = lds64(a); pv[i] = lds32(a - 4);
            }
#pragma unroll
            for (int i = 0; i < 7; i++) {
                const int un = min(wg + 3 * i, 19);
                sts128(sb + OFF_CH + (un >> 2) * CH_BYTES + OFF_P + (un & 3) * 2048 + wt * 16, __byte_perm(w[i].x, pv[i], 0x7610), __byte_perm(w[i].x, 0, 0x1032), __byte_perm(w[i].y, w[i].x, 0x7610), __byte_perm(w[i].y, 0, 0x1032));
            }
            __syncwarp();
            if (wt < 2 - (wg >> 1)) {
                const uint32_t h = lds32(sb + OFF_SSM + (wg + 3 * wt) * 4096), h0 = pack2(blo(h) + blo(dd), 0.f);
                sts64f(sb + OFF_CH + (wg + 3 * wt) * CH_BYTES + OFF_P, __uint_as_float(h0), __uint_as_float(__byte_perm(h, h0, 0x5432)));
            }
            fence_async_smem();
            warp_arrive(bars + B_BK * 8);
            asm volatile("barrier.cluster.wait.aligned;" ::: "memory");
            mbar_spin(bars + B_BK * 8, 0);
            TS(tid == 0, 15)
        }

#pragma unroll 1
        for (int c = wg; c < 5; c += 3) {
            const uint32_t kvb = sb + OFF_CH + c * CH_BYTES;
            mbar_spin(bars + (c < 3 ? B_RAW : B_RAW2) * 8, 0);
            if (CH2_DELAY && wg == 2) wait_clock(clock64(), CH2_DELAY);
            for (uint32_t it = 0;;) {
                const int wt = tid_now() & 127;
                if (!bar_any(1 + wg, ((lds32(kvb + wt * 16) ^ ep) | (lds32(kvb + 2048 + wt * 16) ^ ep)) & 1)) break;
                if (wt == 0) { mbar_expect(bars + (B_RETRY + wg) * 8, 4096); bulk_ld(kvb, g_kvT + (size_t)(5 * id + c) * S_, 4096, bars + (B_RETRY + wg) * 8); }
                mbar_spin(bars + (B_RETRY + wg) * 8, ep >> 31);
                ep ^= 0x80000000u;
                STALE(0)
                SPIN_CHECK(57)
            }
            TS(threadIdx.x == 0, c ? 13 : 11)
            float acc[64];
            {
                const int l = tid_now() & 31;
                conv_channel(acc, kvb + OFF_P + (8 * (warp & 3) + (l >> 2) - 2 * (l & 3)) * 4, (((uint64_t)0xC0000010u << 32) | ((kvb & 0x3FFFF) >> 4) | 0x10000u) + pp.nil);
            }
            TS(threadIdx.x == 0, c ? 16 : 12)
            if (c >= 3) {
#pragma unroll 1
                for (int e = 0; e < 3; e++) mbar_spin(bars + (B_RING + e) * 8, 0);
            }
            TIDS
            const int e = 127 - 8 * (lane >> 4) - (lane & 7), u0 = (warp & 3) + 8 * (e >> 2) + (e & 3) + 4 * ((lane >> 3) & 1);
            const uint32_t ring = sb + OFF_RING + c * 16384 + (warp & 3) * 4096, wa = ring + (u0 ^ ((u0 >> 1) & 4)) * 16;
            if (lane < (warp & 3)) sts128(ring + lane * 16, 0, 0, 0, 0);
#pragma unroll
            for (int i = 0; i < 8; i++)
                stsm4t(i == 0 && u0 >= 256 ? sb + M_SINK : wa - 512 * i, pack2(acc[8 * i], acc[8 * i + 1]), pack2(acc[8 * i + 2], acc[8 * i + 3]),
                       pack2(acc[8 * i + 4], acc[8 * i + 5]), pack2(acc[8 * i + 6], acc[8 * i + 7]));
            warp_arrive(bars + (B_RING + c) * 8);
        }
        fence_async_smem();
        TIDS
        if (warp == 8) {
            wait_cnt(&g_cnt.q[(id & 3) * 32], 128, true);
            if (elect()) {
                mbar_expect(bars + B_QRDY * 8, 28672);
                tma_ld2(sb + OFF_QT, &mp.qT, 80 * id, 0, bars + B_QRDY * 8);
                bulk_ld(sb + OFF_QT + 20480, g_qst, 8192, bars + B_QRDY * 8);
            }
            TS(lane == 0, 8)
        } else if (warp == 9) {
            const int v = min(lane / 5, 3);
            const uint2* gm = g_mod + (v + (v == 3)) * D_ + 5 * id + lane % 5;
            const unsigned epoch = lds32(sb + M_EP);
            uint2 r0, r1;
            unsigned it = 0;
            do {
                r0 = ld_mod(gm); r1 = ld_mod(gm + 6 * D_);
                SPIN_CHECK(55)
            } while (!__all_sync(~0u, r0.y == epoch && r1.y == epoch));
            const float m0 = __uint_as_float(r0.x), m1 = __uint_as_float(r1.x);
            const float m = rbf(m0 + m1), p = rbf(1.f + m);
            const float cz = zscale(__shfl_sync(~0u, p, 15 + lane % 5)), ga = __shfl_sync(~0u, m, 10 + lane % 5);
            if (lane < 15) sts32(sb + M_AB + lane % 5 * 16 + v * 4, lane < 10 ? __float_as_uint(cz * ga * (lane < 5 ? m : p)) : pack2(cz, cz));
            warp_arrive(bars + B_MODR * 8);
            TS(lane == 0, 6)
        }
        mbar_spin(bars + B_QRDY * 8, 0);
        mbar_spin(bars + B_MODR * 8, 0);
#pragma unroll 1
        for (int hf = 0; hf < 2; hf++) {
            const int u = wt + 128 * hf;
            uint4 rs = lds128(sb + OFF_QT + 20480 + u * 16), nm = lds128(sb + OFF_QT + 24576 + u * 16);
            uint32_t it = 0;
            while (__any_sync(~0u, ((rs.x ^ ep) | (rs.z ^ ep) | (nm.x ^ ep) | (nm.z ^ ep)) & 1)) {
                rs = ld_part(g_qst + 8 * u); nm = ld_part(g_qst + S_ + 8 * u);
                STALE(1)
                SPIN_CHECK(53)
            }
            const int c1 = wg == 2 ? 2 + !EPI_SPLIT : 5;
#pragma unroll 1
            for (int c = wg == 2 ? 0 : EPI_SPLIT && wg == hf ? 2 : 3 + wg; c < c1; c += wg == 2 ? 1 : c == 2 ? 1 + wg : 2) {
                uint4 q = lds128(sb + OFF_QT + (u >> 1) * 160 + c * 32 + (u & 1) * 16);
                const float4 ab = lds128f(sb + M_AB + c * 16);
                mbar_spin(bars + (B_RING + c) * 8, 0);
                const uint32_t ra = sb + OFF_RING + c * 16384 + (u ^ ((u >> 1) & 4)) * 16;
                const uint4 p0 = lds128(ra), p1 = lds128(ra + 4096), p2 = lds128(ra + 8192), p3 = lds128(ra + 12288);
                while (__any_sync(~0u, (q.x ^ ep) & 1)) {
                    q = ld_part(g_qT + ((u >> 1) * D_ + 5 * id + c) * 16 + 8 * (u & 1));
                    STALE(2)
                    SPIN_CHECK(52)
                }
                uint32_t gq[4] = {q.x, q.y, q.z, q.w}, gg[4] = {fma2(q.x, rs.x, nm.x), fma2(q.y, rs.y, nm.y), fma2(q.z, rs.z, nm.z), fma2(q.w, rs.w, nm.w)};
#pragma unroll
                for (int i = 0; i < 4; i++) {
                    gg[i] = pack2(fmaf(blo(gg[i]), ab.y, ab.x), fmaf(bhi(gg[i]), ab.y, ab.x));
                    gq[i] = mul2(gq[i], __float_as_uint(ab.z));
                }
                stg128_tag(g_x1T + (size_t)(5 * id + c) * S_ + 8 * u,
                           fma2(gg[0], add2(add2(p0.x, p1.x), add2(p2.x, p3.x)), gq[0]), fma2(gg[1], add2(add2(p0.y, p1.y), add2(p2.y, p3.y)), gq[1]),
                           fma2(gg[2], add2(add2(p0.z, p1.z), add2(p2.z, p3.z)), gq[2]), fma2(gg[3], add2(add2(p0.w, p1.w), add2(p2.w, p3.w)), gq[3]), ep, ((5 * id + c) >> 3) & 3);
            }
            warp_arrive(bars + (B_XS + hf) * 8);
            TS(tid == 0, hf ? 17 : 58)
            TS(tid == 256 && hf, 52)
        }
    }

    const uint32_t nil = pp.nil;
    const int wq = warp & 3;
    if (wg == 2) {
        TIDS
        asm volatile("setmaxnreg.dec.sync.aligned.u32 32;");
        {
            const uint32_t ep = lds32(sb + M_EP);
            uint32_t ph = 0;
#pragma unroll 1
            for (int m = wq - 4; m < 60; m += 4) {
                const int n = max(m, 0);
                const int e = (n >= 20) + (n >= 40), i = n - 20 * e;
                const uint32_t M = e == 0 ? M0 : e == 1 ? M1 : M2;
                const int w = (M >> i) & 1, c = __popc(M & ((1u << i) - 1)), kb = w ? c : i - c;
                const uint32_t a = sb + OFF_XR + (n & 7) * 8192;
                uint32_t ta = a + (e == 0 ? lane * 128 + ((lane & 7) << 4) + (lane >> 3) * 4
                                 : e == 1 ? (lane & 15) * 128 + (((lane >> 4 << 1) ^ (lane & 7)) << 4) + (lane & 8) + (lane >> 4) * 4
                                          : lane * 32 + (lane >> 2) * 4);
                uint32_t tb = e == 0 ? ta ^ 32 : ta + 2048, tc = e == 2 ? ta + 1024 : ta ^ 64, td = e == 2 ? tb + 1024 : tb ^ 64;
                uint32_t live = m >= 0,
                    f0 = bars + (B_XFULL + 8 * w + ((10 * e + kb) & 7)) * 8;
                uint32_t f1 = m == GATE_W2 || m == GATE_W3 || m == GATE_W3B ? bars + (B_GATE + (m >= GATE_W3) + (m >= GATE_W3B)) * 8 : 0;
                if (lane) f0 = f1;
                if (lane > 1 || m < 0) f0 = 0;
                asm volatile("" : "+r"(ta), "+r"(tb), "+r"(tc), "+r"(td), "+r"(live), "+r"(f0));
                mbar_spin(bars + (m < 0 ? B_BK : B_LAND + (n & 7)) * 8, (n >> 3) & 1);
                TR5(lane == 0, n)
                while (true) {
                    uint32_t v[8];
#pragma unroll
                    for (int i = 0; i < 8; i++) v[i] = lds32(((i & 2) ? ((i & 1) ? td : tc) : (i & 1) ? tb : ta) + (i >> 2) * 4096);
                    const uint32_t bad = lop3<0xFE>(lop3<0x7E>(v[0], ep, v[1]), lop3<0x7E>(v[2], ep, v[3]), lop3<0x7E>(v[4], ep, v[5]));
                    if (!__any_sync(~0u, lop3<0xA8>(bad, lop3<0x7E>(v[6], ep, v[7]), live))) break;
                    if (elect()) load_tile(pp, mp, a, e, grp + 16 * w, kb, j, bars + (B_AGAIN + wq) * 8);
                    mbar_spin(bars + (B_AGAIN + wq) * 8, ph);
                    ph ^= 1;
                    STALE1(e)
                }
                TR5(lane == 0, 60 + n)
                if (f0) mbar_arrive(f0);
            }
        }
#pragma unroll 1
        for (int uw = 0; uw < 2; uw++) {
            const int tile = grp + 16 * uw;
            const uint32_t ep = lds32(sb + M_EP), in = sb + OFF_OUT + uw * 10240 + wt * 16, sr = in - lane * 16;
            mbar_wait(bars + (B_IN + uw) * 8, 1);
            float r[8];
#pragma unroll
            for (int h = 0; h < 2; h++) {
                uint4 a = lds128(in + h * 4096), b = lds128(in + h * 4096 + 2048);
                uint32_t it = 0;
                while (__any_sync(~0u, ((a.x ^ ep) | (b.x ^ ep)) & 1)) {
                    const uint4* p = g_part + (size_t)tile * 40960 + ((j >> 2) + 4 * h) * 5120 + 4096 + j * 128 + wt;
                    a = ld_part(p); b = ld_part(p + 10240);
                    STALE(3)
                    if (++it > SPIN_LIMIT) SPIN_FAIL(58)
                }
                if (h) add8(r, add2(a, b)); else unpack8(r, add2(a, b));
            }
            base16(r, lds128(in + 8192), lds64f(sb + M_GB + (64 + 2 * t) * 4), lds64f(sb + M_GB + (72 + 2 * t) * 4));
            __syncwarp();
            stsm4(sr + (lane & 15) * 32 + (((lane >> 4) ^ ((lane >> 2) & 1)) << 4), pack2(r[0], r[1]), pack2(r[2], r[3]), pack2(r[4], r[5]), pack2(r[6], r[7]));
            __syncwarp();
            stg128(out + (size_t)(64 * tile + 16 * wq + (lane >> 1)) * D_ + 512 + 16 * j + 8 * (lane & 1), lds128(sr + (lane >> 1) * 32 + (((lane & 1) ^ ((lane >> 3) & 1)) << 4)));
            __syncwarp();
        }
        if (wq == 0) {
            uint32_t it = 0;
            while (!mbar_try(bars + B_OWN * 8, 0)) { if (++it > SPIN_LIMIT) SPIN_FAIL(56) }
        }
        return;
    }

    TIDS
    const int uw = wg, tile = grp + 16 * uw, row0 = 64 * tile + 16 * wq;
    const bool leader = wt == 0; (void)leader;
    const uint32_t xfull = bars + (B_XFULL + 8 * uw) * 8, xempty = bars + B_XEMPTY * 8, wfull = bars + B_WFULL * 8, wempty = bars + B_WEMPTY * 8;
    const uint64_t dz = mkdesc(0) + pp.nil;
    auto xwait = [&](uint32_t n) { mbar_spin(xfull + (n & 7) * 8, (n >> 3) & 1); };
    asm volatile("setmaxnreg.inc.sync.aligned.u32 224;");
    const uint32_t ep = lds32(sb + M_EP);
    {
        float acc[40];
        uint4* const own = &g_x1f[(tile * 8 + j) * 640 + wt];
        const uint32_t la = ((lane & 7) + 8 * (lane >> 4)) * 128 + (((2 * wq + ((lane >> 3) & 1)) ^ (lane & 7)) << 4);
        auto pos = [&](int n) { return ring_pos(uw, n, LEAD1) & 7; };
        auto slot = [&](int n) { return sb + OFF_XR + pos(n) * 8192; };
        auto grab = [&](int m) {
            uint32_t r0, r1, r2, r3;
            ldsm4t(slot(m) + la + (j & 3) * 2048, r0, r1, r2, r3);
            stg128(own + 512, r0, r1, r2, r3);
        };
        float al[2], r1[2], n1[2];
        {
            float sl[4], sq[4], v[4];
            uint32_t z0[16], z1[16], zz[16];
            uint64_t bd = dz + b80_desc(dsb, 0, 0, 0), tb = (((uint64_t)8 << 32) | ((dsb + OFF_TAB) >> 4) | (7u << 16)) + pp.nil;
            auto ldfrag = [&](uint32_t (&z)[16], int n) {
#pragma unroll
                for (int q = 0; q < 4; q++) ldsm4t(slot(n) + la + q * 2048, z[4 * q], z[4 * q + 1], z[4 * q + 2], z[4 * q + 3]);
            };
            auto tile1 = [&](const uint32_t (&zc)[16], uint32_t (&zn)[16], int n, int h) {
                const bool last = h && n == 5, ok = mbar_test(xfull + (n + 1) * 8, 0), okw = !h || mbar_test(wfull + ((n + 1) >> 1) * 8, 0);
                const int kb = g1_block(n, j);
                wg_fence();
#pragma unroll
                for (int q = 0; q < 2; q++) wgmma_rs80(acc, zc[4 * q], zc[4 * q + 1], zc[4 * q + 2], zc[4 * q + 3], bd + q * B80_STEP, 1);
                wg_commit();
                wg_wait<1>();
                if (!ok) xwait(n + 1);
                if (!last) ldfrag(zn, n + 1);
#pragma unroll
                for (int e = 0; e < 16; e++) zz[e] = mul2(zc[e], zc[e]);
                const uint64_t t0 = last ? ((uint64_t)8 << 32) | ((dsb + M_NUL) >> 4) : tb;
                const uint32_t ts = last ? 0 : 14;
                wg_fence();
#pragma unroll
                for (int q = 0; q < 4; q++) wgmma_rs8(sl, zc[4 * q], zc[4 * q + 1], zc[4 * q + 2], zc[4 * q + 3], t0 + q * ts, 1);
#pragma unroll
                for (int q = 0; q < 4; q++) wgmma_rs8(sq, zz[4 * q], zz[4 * q + 1], zz[4 * q + 2], zz[4 * q + 3], t0 + q * ts, 1);
#pragma unroll
                for (int q = 2; q < 4; q++) wgmma_rs80(acc, zc[4 * q], zc[4 * q + 1], zc[4 * q + 2], zc[4 * q + 3], bd + q * B80_STEP, 1);
                wg_commit();
                if (kb == j) {
#pragma unroll
                    for (int q = 0; q < 4; q++) stg128(own + q * 128, zc[4 * q], zc[4 * q + 1], zc[4 * q + 2], zc[4 * q + 3]);
                }
                if (!h && kb == 8 + (j >> 2)) grab(n);
                if (lane < 2) mbar_arrive(xempty + pos(n) * 8);
                if (!h && n && lane == 0) mbar_arrive(wempty + ((n >> 1) - 1) * 8);
                tb += 56;
                bd = bd + (uint64_t)B80_HALF;
                if (!okw) mbar_spin(wfull + ((n + 1) >> 1) * 8, 0);
                TR(leader, 100 + 10 * uw + n)
            };
            zero(acc); zero(sl); zero(sq);
            mbar_spin(bars + B_TAB * 8, 0);
            mbar_spin(wfull, 0);
            xwait(0);
            TS(leader, 32 + uw)
            ldfrag(z0, 0);
#pragma unroll 1
            for (int n = 0; n < 6; n += 2) { tile1(z0, z1, n, 0); tile1(z1, z0, n + 1, 1); }
#pragma unroll
            for (int n = 6; n < 10; n++) {
                const uint64_t ad = dz + (((dsb + OFF_XR + pos(n) * 8192) >> 4) | 0x10000u);
                const bool ok = n == 9 || mbar_test(xfull + ((n + 1) & 7) * 8, (n + 1) >> 3), okw = n != 7 || mbar_test(wfull + 4 * 8, 0);
                wg_fence();
#pragma unroll
                for (int q = 0; q < 4; q++) wgmma_ss80t(acc, ad + q * 128, bd + q * B80_STEP, 1);
                wg_commit();
                bd = bd + (uint64_t)B80_HALF;
                if (n == 9 && 9 - (j & 1) == 8 + (j >> 2)) grab(9);
                wg_wait<1>();
                if (n > 6 && lane < 2) mbar_arrive(xempty + pos(n - 1) * 8);
                if (!(n & 1) && lane == 0) mbar_arrive(wempty + ((n >> 1) - 1) * 8);
                if (n == 6) {
                    reg_fence(sl); reg_fence(sq);
#pragma unroll
                    for (int e = 0; e < 2; e++) {
                        v[2 * e] = t == 0 ? sl[2 * e] + sl[2 * e + 1] : t == 1 ? sq[2 * e] + sq[2 * e + 1] : sl[2 * e];
                        v[2 * e + 1] = t == 2 ? sl[2 * e + 1] : sq[2 * e];
                    }
                    st_peer(peer_addr(sb + OFF_ROW + uw * 2048 + wt * 16), __float_as_uint(v[0]), __float_as_uint(v[1]), __float_as_uint(v[2]), __float_as_uint(v[3]), peer_addr(bars + (B_SUMS + uw) * 8));
                    TS(leader && !uw, 59)
                }
                if (!ok) xwait(n + 1);
                if (!okw) mbar_spin(wfull + 4 * 8, 0);
                TR(leader, 100 + 10 * uw + n)
            }
            float4 k = lds128f(sb + M_KS);
            float k4 = __uint_as_float(lds32(sb + M_KS + 16));
#pragma unroll
            for (int w = 1; w < 5; w++) {
                const float4 o = lds128f(sb + M_KS + w * 32);
                k.x += o.x; k.y += o.y; k.z += o.z; k.w += o.w; k4 += __uint_as_float(lds32(sb + M_KS + w * 32 + 16));
            }
            mbar_spin(bars + (B_SUMS + uw) * 8, 0);
            TS(leader && !uw, 10)
            const float4 o = lds128f(sb + OFF_ROW + uw * 2048 + wt * 16);
            v[0] += o.x; v[1] += o.y; v[2] += o.z; v[3] += o.w;
            uint32_t fa[4];
#pragma unroll
            for (int h = 0; h < 2; h++) {
                const int l0 = lane & ~3;
                const float s1 = __shfl_sync(~0u, v[2 * h], l0), s2 = __shfl_sync(~0u, v[2 * h], l0 + 1), scc = __shfl_sync(~0u, v[2 * h], l0 + 2);
                const float scs = __shfl_sync(~0u, v[2 * h + 1], l0 + 2), sc = __shfl_sync(~0u, v[2 * h], l0 + 3), sqq = __shfl_sync(~0u, v[2 * h + 1], l0 + 3);
                const float m1 = s1 * (1.f / D_), va = fmaxf(s2 * (1.f / D_) - m1 * m1, 0.f) + 1e-5f, r = rsqrtf(va);
                const float m2 = (r * (sc - m1 * k.x) + k.y) * (1.f / D_);
                const float e2 = (r * (r * (sqq + m1 * (m1 * k.z - 2.f * scc)) + 2.f * (scs - m1 * k.w)) + k4) * (1.f / D_);
                al[h] = r * 0.5f * rsqrtf(fmaxf(e2 - m2 * m2, 0.f) + 1e-5f); r1[h] = r; n1[h] = -m1 * r;
                const uint32_t fb = split2(va * r), fx = split2(t == 3 ? -m2 * va * r : -m1), fc = __shfl_sync(~0u, fx, lane | 3);
                fa[h] = __byte_perm(fx, fb, t == 1 ? 0x5432 : t == 2 ? 0x7654 : 0x1010);
                fa[2 + h] = t ? 0 : fc >> 16;
            }
            mbar_spin(bars + B_VEC * 8, 0);
            wg_fence();
            wgmma_rs80k(acc, fa[0], fa[1], fa[2], fa[3], ((uint64_t)8 << 32) | ((dsb + OFF_F1) >> 4) | (((M_F1 - OFF_F1) >> 4) << 16), 1);
            wg_commit();
        }
        wg_wait<0>();
        reg_fence(acc);
        if (lane < 2) mbar_arrive(xempty + pos(9) * 8);
        if (lane == 0) mbar_arrive(wempty + 4 * 8);
        TS(leader, 34 + uw)
        {
            bf16* const trow = g_t + (size_t)(row0 + g + 2) * D_;
#pragma unroll
            for (int b = 0; b < 3; b++) {
                uint32_t p[8];
#pragma unroll
                for (int ii = 0; ii < 4; ii++) {
                    const int i = 4 * b + ii;
                    if (i >= 10) continue;
#pragma unroll
                    for (int h = 0; h < 2; h++) p[(i & 3) + 4 * h] = pack2(gelu2(acc[4 * i + 2 * h] * al[h]), gelu2(acc[4 * i + 2 * h + 1] * al[h]));
                }
                if (b < 2) {
                    const int gr = (2 * j + b) / 5, sh = (gr & 1) ? -1 - (gr >> 1) : 1 + (gr >> 1);
                    bf16* dst = trow + 64 * j + 32 * b + 8 * t;
                    const int w = (((g + sh) >> 2) & 2) + (t >> 1);
                    stg128_tag(dst + sh * D_, p[0], p[1], p[2], p[3], ep, w);
                    stg128_tag(dst + (sh + 8) * D_, p[4], p[5], p[6], p[7], ep, w ^ 2);
                    if (row0 + g < sh || row0 + g + 8 >= S_ + sh) stg128_tag(dst + (sh > 0 ? 0 : 8) * D_, 0, 0, 0, 0, ep, (sh > 0 ? 0 : 2) + (t >> 1));
                } else {
                    bf16* dst = trow + 512 + 16 * j + 4 * t;
                    const uint32_t lo = t == (g < 2), hi = t == (g >= 2), o = j & 1;
                    stg64(dst - 2 * D_, lop3<0xB8>(p[0], lo & ~o, ep), lop3<0xB8>(p[1], lo & o, ep));
                    stg64(dst + 6 * D_, lop3<0xB8>(p[4], hi & ~o, ep), lop3<0xB8>(p[5], hi & o, ep));
                    if (row0 + g + 8 >= S_ - 2) stg64(dst + 8 * D_, ep & (t == 1) & ~o, ep & (t == 1) & o);
                }
            }
        }
        signal_cnt(&g_cnt.g1[tile * 32], lane, 1, true);
        TS(leader, 36 + uw)
        uint32_t res[20];
        auto ld_own = [&]() {
#pragma unroll
            for (int i = 0; i < 5; i++) { const uint4 v = ldcg128(own + i * 128); res[4 * i] = v.x; res[4 * i + 1] = v.y; res[4 * i + 2] = v.z; res[4 * i + 3] = v.w; }
        };
        ld_own();
#pragma unroll
        for (int i = 0; i < 10; i++) {
            const float2 c = lds64f(sb + M_C + (8 * i + 2 * t) * 4), s = lds64f(sb + M_SB + (8 * i + 2 * t) * 4);
#pragma unroll
            for (int h = 0; h < 2; h++) {
                acc[4 * i + 2 * h] = fmaf(blo(res[2 * i + h]), r1[h], fmaf(n1[h], c.x, s.x));
                acc[4 * i + 2 * h + 1] = fmaf(bhi(res[2 * i + h]), r1[h], fmaf(n1[h], c.y, s.y));
            }
        }
        mbar_spin(wfull + 5 * 8, 0);
        xwait(10);
        TS(leader, 22 + uw)
        uint32_t xo = (4 + 2 * uw) * 8, xp = 0;
        uint64_t ad = dz + (((dsb + OFF_XR) >> 4) | 0x10000u) + xo * 64, bd = dz + b80_desc(dsb, 5, 0, 0);
#pragma unroll 1
        for (int i = 0; i < 5; i++) {
            const uint32_t x1 = xfull + ((3 + 2 * i) & 7) * 8, p1 = i < 3, x2 = xfull + (min(4 + 2 * i, 11) & 7) * 8, p2 = i < 2;
            const uint32_t w2 = wfull + (min(6 + i, 9) & 7) * 8, pw = i >= 2;
            const bool ok1 = mbar_test(x1, p1);
            wg_fence();
#pragma unroll
            for (int q = 0; q < 4; q++) wgmma_ss80(acc, ad + q * 2, bd + q * B80_STEP, 1);
            wg_commit();
            wg_wait<1>();
            if (lane < 2 && i) mbar_arrive(xempty + xp);
            if (lane == 0 && i) mbar_arrive(wempty + ((4 + i) & 7) * 8);
            if (!ok1) mbar_spin(x1, p1);
            const bool ok2 = mbar_test(x2, p2), okw = mbar_test(w2, pw);
            wg_fence();
#pragma unroll
            for (int q = 0; q < 4; q++) wgmma_ss80(acc, ad + 512 + q * 2, bd + B80_HALF + q * B80_STEP, 1);
            wg_commit();
            const uint32_t xc = xo;
            xp = xo + 8; xo = (xo + 16) & 56;
            ad += xo ? 1024 : 1024 - 4096;
            bd += i == 2 ? 2 * B80_HALF - 8192 + (8192ll << 16) : 2 * B80_HALF;
            asm volatile("" : "+l"(ad), "+l"(bd));
            wg_wait<1>();
            if (lane < 2) mbar_arrive(xempty + xc);
            if (!ok2) mbar_spin(x2, p2);
            if (!okw) mbar_spin(w2, pw);
            TR(leader, (uw ? 86 : 20) + 2 * i)
        }
        wg_wait<0>();
        reg_fence(acc);
        if (lane < 2) mbar_arrive(xempty + xp);
        if (lane == 0) mbar_arrive(wempty + (9 & 7) * 8);
        TS(leader, 38 + uw)
        float a0 = 0.f, b0 = 0.f, a1 = 0.f, b1 = 0.f;
        uint32_t x2[20];
#pragma unroll
        for (int i = 0; i < 5; i++) {
            uint32_t* p = &x2[4 * i];
#pragma unroll
            for (int e = 0; e < 4; e++) p[e] = pack2(acc[8 * i + 2 * e], acc[8 * i + 2 * e + 1]);
#pragma unroll
            for (int e = 0; e < 4; e++) p[e] = lop3<0xB8>(p[e], (((wt >> 3) ^ (wt << 2)) & 7) == e, ep);
            stg128(&g_x2f[(tile * 40 + (i < 4 ? 4 * j + i : 32 + j)) * 128 + wt], p[0], p[1], p[2], p[3]);
#pragma unroll
            for (int e = 0; e < 4; e += 2) {
                const float u0 = blo(p[e]), u1 = bhi(p[e]), v0 = blo(p[e + 1]), v1 = bhi(p[e + 1]);
                a0 += u0 + u1; b0 = fmaf(u0, u0, fmaf(u1, u1, b0));
                a1 += v0 + v1; b1 = fmaf(v0, v0, fmaf(v1, v1, b1));
            }
        }
#pragma unroll
        for (int o = 1; o < 4; o *= 2) {
            a0 += __shfl_xor_sync(~0u, a0, o); b0 += __shfl_xor_sync(~0u, b0, o);
            a1 += __shfl_xor_sync(~0u, a1, o); b1 += __shfl_xor_sync(~0u, b1, o);
        }
        if (t < 2) stg64(&g_stats[(tile * 8 + j) * 64 + 16 * wq + g + 8 * t], tag(__float_as_uint(t ? a1 : a0), ep), __float_as_uint(t ? b1 : b0));
        signal_cnt(&g_cnt.g2[tile * 32], lane, 1, true);
        TS(leader, 40 + uw)
        ld_own();
#pragma unroll
        for (int i = 0; i < 10; i++) {
            const float2 c = lds64f(sb + M_GB + (8 * i + 2 * t) * 4), e = lds64f(sb + M_CI + (8 * i + 2 * t) * 4);
#pragma unroll
            for (int h = 0; h < 2; h++)
                res[2 * i + h] = fma2(pack2(c.x, c.y), x2[2 * i + h], pack2(e.x * blo(res[2 * i + h]), e.y * bhi(res[2 * i + h])));
        }
#pragma unroll
        for (int i = 0; i < 5; i++) stg128(own + i * 128, res[4 * i], res[4 * i + 1], res[4 * i + 2], res[4 * i + 3]);
        asm volatile("fence.proxy.async.global;" ::: "memory");
    }
    float acc0[64], acc1[44];
    float2 q[4];
    {
        uint4 f0, f1, f2, f3;
        auto xseq = [&](int kb) { return ring_pos(uw, kb, XLEAD) & 7; };
        auto step = [&](const uint4& f, uint64_t bd) {
            wg_fence();
            wgmma_rs128(acc0, f.x, f.y, f.z, f.w, bd, 1);
            wgmma_rs88(acc1, f.x, f.y, f.z, f.w, bd + 512, 1);
            wg_commit();
        };
        const uint32_t xa = sb + OFF_XR + wt * 16;
        const float2* const gs = &g_stats[(tile * 8 + 2 * t) * 64 + 16 * wq + g];
        zero(acc0); zero(acc1);
        uint32_t xs = xseq(0);
        xwait(20);
        TS(leader, 42 + uw)
        f0 = lds128(xa + xs * 8192); f1 = lds128(xa + xs * 8192 + 2048);
#pragma unroll
        for (int i = 0; i < 4; i++) q[i] = ld_stat(gs + (i & 1) * 64 + 8 * (i >> 1));
        mbar_spin(wfull + (10 & 7) * 8, (10 >> 3) & 1);
#pragma unroll 1
        for (int kb = 0; kb < 10; kb++) {
            const uint32_t wn = 10 + 2 * kb;
            const uint64_t bd = dz + (((dsb + OFF_W + (wn & 7) * 16384) >> 4) | (256u << 16));
            step(f0, bd);
            wg_wait<1>();
            if (kb && lane == 0) mbar_arrive(wempty + ((wn - 1) & 7) * 8);
            f2 = lds128(xa + xs * 8192 + 4096); f3 = lds128(xa + xs * 8192 + 6144);
            const bool w1 = mbar_test(wfull + ((wn + 1) & 7) * 8, (wn >> 3) & 1), x1 = mbar_test(xfull + ((21 + kb) & 7) * 8, ((21 + kb) >> 3) & 1);
            step(f1, bd + 128);
            if (!w1) mbar_spin(wfull + ((wn + 1) & 7) * 8, (wn >> 3) & 1);
            step(f2, bd + 1024);
            if (lane < 2) mbar_arrive_after(xempty + xs * 8, f2.x, f3.x, nil);
            wg_wait<1>();
            if (lane == 0) mbar_arrive(wempty + (wn & 7) * 8);
            xs = xseq(kb + 1);
            if (x1) { f0 = lds128(xa + xs * 8192); f1 = lds128(xa + xs * 8192 + 2048); }
            const bool w2 = mbar_test(wfull + ((wn + 2) & 7) * 8, ((wn + 2) >> 3) & 1);
            step(f3, bd + 1152);
            if (kb < 9 && !x1) { xwait(21 + kb); f0 = lds128(xa + xs * 8192); f1 = lds128(xa + xs * 8192 + 2048); }
            if (!w2) mbar_spin(wfull + ((wn + 2) & 7) * 8, ((wn + 2) >> 3) & 1);
            if (kb == 4) {
                uint32_t it = 0;
                while (__any_sync(~0u, ((__float_as_uint(q[0].x) ^ ep) | (__float_as_uint(q[1].x) ^ ep) | (__float_as_uint(q[2].x) ^ ep) | (__float_as_uint(q[3].x) ^ ep)) & 1)) {
#pragma unroll
                    for (int i = 0; i < 4; i++) q[i] = ld_stat(gs + (i & 1) * 64 + 8 * (i >> 1));
                    SPIN_CHECK(49)
                }
                float a0 = q[0].x + q[1].x, b0 = q[0].y + q[1].y, a1 = q[2].x + q[3].x, b1 = q[2].y + q[3].y;
#pragma unroll
                for (int o = 1; o < 4; o *= 2) {
                    a0 += __shfl_xor_sync(~0u, a0, o); b0 += __shfl_xor_sync(~0u, b0, o);
                    a1 += __shfl_xor_sync(~0u, a1, o); b1 += __shfl_xor_sync(~0u, b1, o);
                }
                a0 *= 1.f / D_; a1 *= 1.f / D_;
                const float r0 = 0.5f * rsqrtf(fmaxf(b0 * (1.f / D_) - a0 * a0, 0.f) + 1e-5f), r1 = 0.5f * rsqrtf(fmaxf(b1 * (1.f / D_) - a1 * a1, 0.f) + 1e-5f);
                const uint32_t sel = t == 0 ? 0x1010 : t == 1 ? 0x4432 : 0x4444;
                q[0] = make_float2(r0, r1);
                q[1] = make_float2(__uint_as_float(__byte_perm(split2(-a0), 0, sel)), __uint_as_float(__byte_perm(split2(-a1), 0, sel)));
            }
            TR(leader, 10 * uw + kb)
        }
        const uint64_t fd = ((uint64_t)8 << 32) | ((dsb + OFF_W + 6 * 16384) >> 4);
        wg_fence();
        wgmma_rs128k(acc0, __float_as_uint(q[1].x), __float_as_uint(q[1].y), 0, 0, fd, 1);
        wgmma_rs88k(acc1, __float_as_uint(q[1].x), __float_as_uint(q[1].y), 0, 0, fd + 128, 1);
        wg_commit();
        if (lane == 0) {
            mbar_arrive(bars + B_XFREE * 8);
            asm volatile("mbarrier.arrive.shared::cluster.b64 _, [%0];" ::"r"(peer_addr(bars + B_XFREE * 8)) : "memory");
        }
    }
    const uint32_t recv = sb + recv_off(uw) + wt * 16;
    uint32_t ha[48] = {}, hb[48], hx[12];
    uint64_t wb = dz + (((dsb + OFF_W) >> 4) | (512u << 16));
    auto wdesc = [&](int n) { return wb + (n & 7) * 1024; };
    auto wwait = [&](int n) { mbar_spin(wfull + (n & 7) * 8, (n >> 3) & 1); };
    auto wfree = [&](int n) { if (lane == 0) mbar_arrive(wempty + (n & 7) * 8); };
    auto fresh = [&]() { wb += pp.nil; asm volatile("" : "+l"(wb)); };
    uint32_t pk[32];
    {
        float P0[64];
        const float r0 = q[0].x, r1 = q[0].y;
        const uint32_t ra = peer_addr(recv), rb = peer_addr(bars + (B_RECV + 4 * uw) * 8);
        auto conv32 = [&](const float* v, int b) {
#pragma unroll
            for (int i = 0; i < 4; i++) {
                ha[8 * b + 2 * i] = pack2(gelu2(v[4 * i] * r0), gelu2(v[4 * i + 1] * r0));
                ha[8 * b + 2 * i + 1] = pack2(gelu2(v[4 * i + 2] * r1), gelu2(v[4 * i + 3] * r1));
            }
#pragma unroll
            for (int s = 2 * b; s < 2 * b + 2; s++) st_peer(ra + s * 2048, ha[4 * s], ha[4 * s + 1], ha[4 * s + 2], ha[4 * s + 3], rb + (b >> 1) * 8);
        };
        auto fetch = [&](int k) {
            mbar_spin(bars + (B_RECV + 4 * uw + k) * 8, 0);
#pragma unroll
            for (int s = 4 * k; s < 4 * k + 4; s++) { const uint4 x = lds128(recv + s * 2048); hb[4 * s] = x.x; hb[4 * s + 1] = x.y; hb[4 * s + 2] = x.z; hb[4 * s + 3] = x.w; }
        };
        auto stage = [&](int n, const uint32_t* a, int steps, int sc) {
            wwait(n);
            wg_fence();
#pragma unroll
            for (int s = 0; s < steps; s++) wgmma_rs128(P0, a[4 * s], a[4 * s + 1], a[4 * s + 2], a[4 * s + 3], wdesc(n) + s * 128, sc || s);
            wg_commit();
        };
        wg_wait<0>();
        reg_fence(acc0); reg_fence(acc1);
        wfree(29); wfree(30);
        TS(leader, 44 + uw)
        uint32_t hr[6];
#pragma unroll
        for (int i = 0; i < 6; i++) {
            const float r = (i & 1) ? r1 : r0;
            hr[i] = pack2(gelu2(acc1[32 + 2 * i] * r), gelu2(acc1[33 + 2 * i] * r));
        }
        if (uw) mbar_spin(bars + B_XFREE * 8, 0);
        st_peer(ra + 24576, hr[0], hr[1], hr[2], hr[3], rb + 24);
        asm volatile("st.async.shared::cluster.mbarrier::complete_tx::bytes.v2.b32 [%0], {%1, %2}, [%3];" ::"r"(ra + 26624 - wt * 8), "r"(hr[4]), "r"(hr[5]), "r"(rb + 24) : "memory");
        conv32(&acc1[0], 4);
        conv32(&acc1[16], 5);
        TS(leader, 46 + uw)
        stage(31, &ha[32], 4, 0);
#pragma unroll
        for (int b = 0; b < 4; b++) {
            conv32(&acc0[16 * b], b);
            if (b == 3) {
                fetch(2);
                mbar_spin(bars + (B_RECV + 4 * uw + 3) * 8, 0);
                const uint4 x = lds128(recv + 24576);
                const uint2 y = lds64(recv + 26624 - wt * 8);
                const uint32_t hp[6] = {x.x, x.y, x.z, x.w, y.x, y.y};
#pragma unroll
                for (int i = 0; i < 6; i++) { hx[i] = (j & 1) ? hp[i] : hr[i]; hx[6 + i] = (j & 1) ? hr[i] : hp[i]; }
            }
            if (!(b & 1)) wwait(32 + (b >> 1));
            wg_fence();
#pragma unroll
            for (int s = 0; s < 2; s++) wgmma_rs128(P0, ha[8 * b + 4 * s], ha[8 * b + 4 * s + 1], ha[8 * b + 4 * s + 2], ha[8 * b + 4 * s + 3], wdesc(32 + (b >> 1)) + (2 * (b & 1) + s) * 128, 1);
            wg_commit();
            if (!(b & 1)) { wg_wait<1>(); wfree(31 + (b >> 1)); }
        }
        TR(leader, 64 + 10 * uw)
        fresh();
        stage(34, &hb[32], 4, 1); wg_wait<1>(); wfree(33);
        fetch(0);
        stage(35, hx, 3, 1); wg_wait<1>(); wfree(34);
        fetch(1);
        stage(36, &hb[0], 4, 1); wg_wait<1>(); wfree(35);
        stage(37, &hb[16], 4, 1); wg_wait<1>(); wfree(36);
        wg_wait<0>();
        reg_fence(P0);
        pack_part<64>(pk, P0, ep);
        uint32_t all = 0;
#pragma unroll
        for (int i = 0; i < 32; i++) all |= pk[i];
        if (lane == 0) mbar_arrive_after(wempty + (37 & 7) * 8, all, 0, nil);
        TR(leader, 65 + 10 * uw)
    }
    {
        uint4* const dst = g_part + (size_t)(tile * 8 + j) * 5120 + wt;
        const uint4* const src = g_part + (size_t)tile * 40960 + j * 512 + wt;
        float F[2][32];
        float2 gb[8];
        uint4 base[4], u1[4], u2[4], u3[4];
#pragma unroll
        for (int c = 2; c < 5; c++) {
            float (&P)[32] = F[c & 1];
            fresh();
#pragma unroll
            for (int s = 0; s < 27; s++) {
                const int e = s < 8 ? 0 : s < 15 ? 1 : s < 23 ? 2 : 3, o = s - (e == 0 ? 0 : e == 1 ? 8 : e == 2 ? 15 : 23), n = 30 + 4 * c + e;
                const uint32_t* a = s < 12 ? &ha[4 * s] : s < 15 ? &hx[4 * (s - 12)] : &hb[4 * (s - 15)];
                if (o == 0) wwait(n);
                if (o == 0 || s == 1) wg_fence();
                wgmma_rs64(P, a[0], a[1], a[2], a[3], wdesc(n) + o * 128, s);
                if (o == 0) { wg_commit(); wg_wait<1>(); if (c > 2 || s) wfree(n - 1); }
                if (s == 0 && c > 2) { reg_fence(F[~c & 1]); pack_part<32>(pk, F[~c & 1], ep); }
                if (c == 2 && s % 3 == 0 && s < 24) st_part(dst + g4_block(s / 12, j) * 512 + (s / 3 & 3) * 128, &pk[4 * (s / 3)]);
                if (c == 3 && s % 4 == 1 && s < 16) st_part(dst + g4_block(2, j) * 512 + s / 4 * 128, &pk[4 * (s / 4)]);
                if (c == 4 && s % ST3 == 0 && s < 4 * ST3) st_part(dst + g4_block(3, j) * 512 + s / ST3 * 128, &pk[4 * (s / ST3)]);
                if (c == 4 && s >= 4 && s < 8) base[s - 4] = ldcg128(&g_x1f[(tile * 8 + j) * 640 + (s - 4) * 128 + wt]);
                if (c == 4 && s >= 19 && s < 23) { gb[2 * s - 38] = lds64f(sb + M_GB + (16 * (s - 19) + 2 * t) * 4); gb[2 * s - 37] = lds64f(sb + M_GB + (16 * (s - 19) + 8 + 2 * t) * 4); }
                if (c == 4 && s >= 8 && s < 12) u1[s - 8] = ld_part(src + (j ^ 6) * 5120 + (s - 8) * 128);
                if (c == 4 && s >= 15 && s < 19) u2[s - 15] = ld_part(src + (j ^ 4) * 5120 + (s - 15) * 128);
                if (c == 4 && s >= LD3 && s < LD3 + 4) u3[s - LD3] = ld_part(src + (j ^ 2) * 5120 + (s - LD3) * 128);
                if (s == 7 || s == 14 || s == 22 || s == 26) wg_commit();
                if (c == 4) { TR(leader && s == 7, 68 + 10 * uw) TR(leader && s == 14, 69 + 10 * uw) TR(leader && s == 22, 70 + 10 * uw) }
            }
            if (c == 2 && lane == 0) mbar_arrive(bars + (B_RING + uw) * 8);
            TR(leader, 64 + c + (c == 4 ? 3 : 0) + 10 * uw)
        }
        float (&O)[32] = F[0];
        float v[32];
        fix4(u1, src + (j ^ 6) * 5120, ep, 4);
        fix4(u2, src + (j ^ 4) * 5120, ep, 5);
        TR(leader, 72 + 10 * uw)
        fix4(u3, src + (j ^ 2) * 5120, ep, 6);
        TR(leader, 73 + 10 * uw)
#pragma unroll
        for (int i = 0; i < 4; i++) { unpack8(&v[8 * i], add2(add2(u1[i], u2[i]), u3[i])); base16(&v[8 * i], base[i], gb[2 * i], gb[2 * i + 1]); }
        reg_fence(v);
        TS(leader, 50 + uw)
        wg_wait<0>();
        reg_fence(O);
        TS(leader, 48 + uw)
        const uint32_t so = sb + recv_off(uw) + wq * 2048;
#pragma unroll
        for (int i = 0; i < 4; i++) {
            float* o = &O[8 * i];
#pragma unroll
            for (int e = 0; e < 8; e++) o[e] = fmaf((e & 1) ? gb[2 * i + (e >> 2)].y : gb[2 * i + (e >> 2)].x, o[e], v[8 * i + e]);
            stsm4(so + (lane & 15) * 128 + (((2 * i + (lane >> 4)) ^ (lane & 7)) << 4), pack2(o[0], o[1]), pack2(o[2], o[3]), pack2(o[4], o[5]), pack2(o[6], o[7]));
        }
        __syncwarp();
#pragma unroll
        for (int i = 0; i < 4; i++) {
            const int row = (lane >> 3) + 4 * i;
            stg128(out + (size_t)(row0 + row) * D_ + 64 * j + 8 * (lane & 7), lds128(so + row * 128 + (((lane & 7) ^ (row & 7)) << 4)));
        }
        warp_arrive(bars + B_OWN * 8);
    }
}

typedef CUresult (*EncFn)(CUtensorMap*, CUtensorMapDataType, cuuint32_t, void*, const cuuint64_t*, const cuuint64_t*, const cuuint32_t*,
                          const cuuint32_t*, CUtensorMapInterleave, CUtensorMapSwizzle, CUtensorMapL2promotion, CUtensorMapFloatOOBfill);

static void enc(EncFn fn, CUtensorMap* m, void* p, int rank, const cuuint64_t* dims, const cuuint64_t* strides, const cuuint32_t* box) {
    const CUtensorMapSwizzle sw = box[0] > 64 ? CU_TENSOR_MAP_SWIZZLE_NONE : CU_TENSOR_MAP_SWIZZLE_128B;
    cuuint32_t es[5] = {1, 1, 1, 1, 1};
    CUresult r = fn(m, CU_TENSOR_MAP_DATA_TYPE_BFLOAT16, rank, p, dims, strides, box, es, CU_TENSOR_MAP_INTERLEAVE_NONE, sw,
                    CU_TENSOR_MAP_L2_PROMOTION_L2_128B, CU_TENSOR_MAP_FLOAT_OOB_FILL_NONE);
    (void)r;
}
static void enc2(EncFn fn, CUtensorMap* m, void* p, uint64_t cols, uint64_t rows, uint32_t bc, uint32_t br) {
    cuuint64_t dims[2] = {cols, rows}, st[1] = {cols * 2};
    cuuint32_t box[2] = {bc, br};
    enc(fn, m, p, 2, dims, st, box);
}

extern "C" void kernel_launch(void* const* d_in, const int* in_sizes, int n_in, void* d_out, int out_size) {
    static Maps mp;
    static Ptrs pp;
    static void* cached[13];
    bool same = true;
    for (int i = 0; i < 13; i++) same = same && (cached[i] == d_in[i]);
    if (!same) {
        void* fnp = nullptr;
        cudaDriverEntryPointQueryResult qr;
        cudaGetDriverEntryPoint("cuTensorMapEncodeTiled", &fnp, cudaEnableDefault, &qr);
        EncFn fn = (EncFn)fnp;
        cudaGetSymbolAddress((void**)&pp.s, g_scratch);
        void *x1T = g_x1T, *t = g_t;
        cuuint64_t dq[3] = {64, S_, 10}, sq[2] = {D_ * 2, 128};
        cuuint32_t bq[3] = {64, 16, 10};
        enc(fn, &mp.q, d_in[0], 3, dq, sq, bq);
        enc2(fn, &mp.k, d_in[1], D_, S_, 80, 67); enc2(fn, &mp.v, d_in[2], D_, S_, 80, 64);
        enc2(fn, &mp.qT, g_qT, 16 * D_, 128, 80, 128);
        enc2(fn, &mp.x1_ld, x1T, S_, D_, 64, 64); enc2(fn, &mp.t_ld, (bf16*)t + 2 * D_, D_, S_, 64, 64);
        enc2(fn, &mp.w1, d_in[7], D_, D_, 64, 64); enc2(fn, &mp.w1h, d_in[7], D_, D_, 64, 160); enc2(fn, &mp.w3h, d_in[9], F_, D_, 64, 160);
        enc2(fn, &mp.wmod, d_in[12], 6 * D_, D_, 64, 160);
        const cuuint64_t R = D_ * 2;
        cuuint64_t da[5] = {D_, 2, 4, 4, 16}, sa[4] = {R, 8 * R, 2 * R, 32 * R}, db[5] = {D_, 2, 2, 4, 8}, sb[4] = {R, 8 * R, 2 * R, 16 * R};
        cuuint32_t ba[5] = {64, 2, 4, 4, 4}, bb[5] = {64, 2, 2, 4, 8};
        enc(fn, &mp.w2a, d_in[8], 5, da, sa, ba); enc(fn, &mp.w2b, (bf16*)d_in[8] + 512 * D_, 5, db, sb, bb);
        cuuint64_t dw[3] = {64, D_, 27}, sw[2] = {F_ * 2, 128};
        cuuint32_t bw[3] = {64, 32, 3};
        enc(fn, &mp.w3a, d_in[9], 3, dw, sw, bw);
        enc2(fn, &mp.w3b, d_in[9], F_, D_, 24, 32);
        enc2(fn, &mp.w4[0], d_in[10], D_, F_, 64, 64); enc2(fn, &mp.w4[1], d_in[10], D_, F_, 64, 48);
        pp.q = (const bf16*)d_in[0]; pp.w_mod = (const bf16*)d_in[12]; pp.shift_k = (const bf16*)d_in[3];
        pp.ssm_k = (const bf16*)d_in[4]; pp.ssm_D = (const bf16*)d_in[5]; pp.w1 = (const bf16*)d_in[7]; pp.w2 = (const bf16*)d_in[8];
        pp.w4 = (const bf16*)d_in[10]; pp.c = (const bf16*)d_in[11];
        cudaFuncSetAttribute(fused_kernel, cudaFuncAttributeMaxDynamicSharedMemorySize, SMEM_BYTES);
        for (int i = 0; i < 13; i++) cached[i] = d_in[i];
    }
    cudaLaunchConfig_t cfg = {};
    cfg.gridDim = dim3(NCTA); cfg.blockDim = dim3(NTHR); cfg.dynamicSmemBytes = SMEM_BYTES; cfg.stream = cudaStreamPerThread;
    cudaLaunchAttribute at[1];
    at[0].id = cudaLaunchAttributeClusterDimension; at[0].val.clusterDim.x = 2; at[0].val.clusterDim.y = 1; at[0].val.clusterDim.z = 1;
    cfg.attrs = at; cfg.numAttrs = 1;
    cudaLaunchKernelEx(&cfg, fused_kernel, pp, (bf16*)d_out, mp);
}
```

```cpp
#include <cuda_runtime.h>
#include <cuda_bf16.h>
#include <cuda.h>
#include <stdint.h>
#include <stdio.h>

typedef __nv_bfloat16 bf16;

constexpr int S_ = 2048, D_ = 640, F_ = 1728;
constexpr int NCTA = 132, NTHR = 512;

constexpr int TAB_BYTES = 9216, VEC_BYTES = 1440;
struct Counters {
    unsigned kv[8 * 32];
    unsigned q[4 * 32], x[4 * 32];
    unsigned wr[32], tab[32], uv[32], cs[32], done[32];
    unsigned g1[32 * 32];
    unsigned g2[32 * 32];
};
struct Scratch {
    Counters cnt;
    unsigned epoch;
    alignas(1024) bf16 qst[2 * S_];
    alignas(1024) uint4 wr[2 * 8 * 10 * 128];
    alignas(1024) uint2 mod[2 * 6 * D_];
    alignas(1024) uint4 tab[(TAB_BYTES + 8 * VEC_BYTES) / 16];
    alignas(1024) float uv[2 * 3 * D_];
    alignas(1024) float cs3[2 * 1920];
    alignas(1024) float2 stats[32 * 8 * 64];
    alignas(1024) bf16 kvT[D_ * S_];
    alignas(1024) bf16 qT[D_ * S_];
    alignas(1024) bf16 x1T[D_ * S_];
    alignas(1024) bf16 t[(S_ + 4) * D_];
    alignas(1024) uint4 x2f[32 * 40 * 128];
    alignas(1024) uint4 x1f[32 * 8 * 5 * 128];
    alignas(1024) uint4 part[32 * 8 * 10 * 4 * 128];
};
__device__ Scratch g_scratch;
#define g_kvT (pp.s->kvT)
#define g_qT (pp.s->qT)
#define g_x1T (pp.s->x1T)
#define g_qst (pp.s->qst)
#define g_t (pp.s->t)
#define g_x2f (pp.s->x2f)
#define g_x1f (pp.s->x1f)
#define g_part (pp.s->part)
#define g_wr (pp.s->wr)
#define g_mod (pp.s->mod)
#define g_tab (pp.s->tab)
#define g_uv (pp.s->uv)
#define g_cs3 (pp.s->cs3)
#define g_stats (pp.s->stats)
#define g_cnt (pp.s->cnt)
#define g_epoch (pp.s->epoch)

struct Maps {
    CUtensorMap k, v, q;
    CUtensorMap qT;
    CUtensorMap x1_ld, t_ld;
    CUtensorMap w1, w1h, w3h, wmod;
    CUtensorMap w2a, w2b;
    CUtensorMap w3a, w3b;
    CUtensorMap w4[2];
};

struct Ptrs {
    Scratch* s;
    uint64_t nil;
    const bf16 *q, *w_mod, *shift_k, *ssm_k, *ssm_D, *w1, *w2, *w4, *c;
};

constexpr int OFF_W = 0;
constexpr int OFF_XR = 131072;
constexpr int OFF_REM = 196608;
constexpr int OFF_TAB = OFF_REM + 5 * 4096;
constexpr int OFF_ROW = OFF_TAB + 4608;
constexpr int OFF_F1 = OFF_ROW + 4096;
constexpr int RECV_BYTES = 30720;
constexpr int OFF_M = OFF_REM + RECV_BYTES;
constexpr int OFF_OUT = OFF_XR + 32768;
static_assert(OFF_F1 + 1280 <= OFF_M, "G1 map");
constexpr int OFF_ST = 0;
constexpr int OFF_SSM = 20480;
constexpr int OFF_WM = 0;
constexpr int OFF_QIN = 49152;
constexpr int OFF_QT = 49152;
constexpr int OFF_Z = OFF_TAB;
constexpr int OFF_RING = 80896;
constexpr int OFF_KIN = OFF_RING, OFF_VIN = OFF_KIN + 2 * 10752;
constexpr int OFF_CH = OFF_RING + 3 * 16384, CH_BYTES = 13312, OFF_P = 5120;
static_assert(OFF_RING + 5 * 16384 <= OFF_CH + 3 * CH_BYTES && OFF_CH + 5 * CH_BYTES <= OFF_REM, "the last two rings replace channels 0..2");
constexpr int M_BAR = OFF_M;
constexpr int M_F1 = OFF_M + 800;
constexpr int M_GB = M_F1 + 1280, M_C = M_GB + 320, M_SB = M_C + 320, M_CI = M_SB + 320;
constexpr int M_KS = M_CI + 320;
constexpr int M_AB = M_KS + 160;
constexpr int M_EP = M_AB + 80;
constexpr int M_SINK = M_EP + 16;
constexpr int M_NUL = M_SINK + 16;
constexpr int M_TS = M_NUL + 128;
constexpr int SMEM_BYTES = M_TS;
static_assert(SMEM_BYTES <= 232448, "smem");

enum { B_WFULL = 0, B_WEMPTY = 8, B_XEMPTY = 16, B_XFULL = 24  ,
       B_RAW = 40, B_QIN = 41, B_SSM = 42, B_VEC = 43, B_VEC3 = 44, B_WM = 45, B_TAB = 46, B_QRDY = 47,
       B_MODR = 48, B_GATE = 49, B_RETRY = 55, B_S30 = 58, B_RAW2 = 59, B_RAW3 = 60, B_SUMS = 62, B_RECV = 64  ,
       B_SIG = 72, B_RING = 74  ,
       B_LAND = 80,
       B_XS = 88, B_R1 = 89, B_BK = 90, B_KVS = 91,
       B_XFREE = 92, B_OWN = 93,
       B_IN = 94, B_AGAIN = 96 };
#define T_KVB 1800
#define T_SSM 3300
#define T_Q 0
#define PF_T0 4800
#define PF_DT 420
#define PF_N0 4
#define PF_N 16
#define HELP_T 1000
#define ST3 1
#define LD3 23
#define GATE_W2 7
#define GATE_W3 27
#define GATE_W3B 37
#define W3_N2 13
#define LEAD1 4
#define XLEAD 3

#define SPIN_FAIL(code) __trap();
#define SPIN_LIMIT (1u << 22)
#define STALE(c)
#define STALE1(c)
#define TS(c, i)
#define TG(c, i)
#define TR(c, i)
#define TR2(c, i)
#define TR4(c, i)
#define TR5(c, i)
#define SPIN_CHECK(code) asm volatile("" ::"r"(it));
__device__ __forceinline__ uint32_t s2u(const void* p) { return (uint32_t)__cvta_generic_to_shared(p); }
__device__ __forceinline__ bool elect() {
    uint32_t p;
    asm volatile("{.reg .pred P; elect.sync _|P, 0xffffffff; selp.u32 %0,1,0,P;}" : "=r"(p));
    return p != 0;
}
__device__ __forceinline__ void mbar_init(uint32_t b, uint32_t n) { asm volatile("mbarrier.init.shared.b64 [%0], %1;" ::"r"(b), "r"(n)); }
__device__ __forceinline__ void mbar_expect(uint32_t b, uint32_t bytes) {
    asm volatile("mbarrier.arrive.expect_tx.shared.b64 _, [%0], %1;" ::"r"(b), "r"(bytes) : "memory");
}
__device__ __forceinline__ void mbar_arrive(uint32_t b) { asm volatile("mbarrier.arrive.shared.b64 _, [%0];" ::"r"(b) : "memory"); }
__device__ __forceinline__ void mbar_arrive_after(uint32_t b, uint32_t v0, uint32_t v1, uint32_t nil) { mbar_arrive(b + ((v0 | v1) & nil)); }
__device__ __forceinline__ void warp_arrive(uint32_t b) { __syncwarp(); if (elect()) mbar_arrive(b); }
__device__ __forceinline__ uint32_t peer_addr(uint32_t a) {
    uint32_t r;
    asm("{\n.reg .b32 q;\nmov.u32 q, %%cluster_ctarank;\nxor.b32 q, q, 1;\nmapa.shared::cluster.u32 %0, %1, q;\n}" : "=r"(r) : "r"(a));
    return r;
}
__device__ __forceinline__ bool mbar_test(uint32_t b, uint32_t parity) {
    uint32_t ok;
    asm volatile("{.reg .pred P; mbarrier.test_wait.parity.shared.b64 P, [%1], %2; selp.u32 %0,1,0,P;}" : "=r"(ok) : "r"(b), "r"(parity) : "memory");
    return ok != 0;
}
__device__ __forceinline__ bool mbar_try(uint32_t b, uint32_t parity) {
    uint32_t ok;
    asm volatile("{.reg .pred P; mbarrier.try_wait.parity.shared.b64 P, [%1], %2; selp.u32 %0,1,0,P;}" : "=r"(ok) : "r"(b), "r"(parity) : "memory");
    return ok != 0;
}
__device__ __forceinline__ void mbar_wait(uint32_t b, uint32_t parity) {
    if (__all_sync(0xffffffffu, mbar_try(b, parity))) return;
    uint32_t it = 0;
    while (!__all_sync(0xffffffffu, mbar_try(b, parity))) { if (++it > SPIN_LIMIT) SPIN_FAIL((b >> 3) & 63) }
}
__device__ __forceinline__ void mbar_spin(uint32_t b, uint32_t parity) {
    asm volatile("{\n.reg .pred P;\nSPIN:\nmbarrier.try_wait.parity.shared.b64 P, [%0], %1;\n@!P bra.uni SPIN;\n}" ::"r"(b), "r"(parity) : "memory");
}
__device__ __forceinline__ void bar_sync(int id, int n) { asm volatile("bar.sync %0, %1;" ::"r"(id), "r"(n) : "memory"); }
__device__ __forceinline__ void fence_async_smem() { asm volatile("fence.proxy.async.shared::cta;" ::: "memory"); }
__device__ __forceinline__ void wait_cnt(const unsigned* p, unsigned target, bool tagged = false) {
    unsigned v, it = 0;
    do {
        asm volatile("ld.relaxed.gpu.global.u32 %0, [%1];" : "=r"(v) : "l"(p) : "memory");
        SPIN_CHECK(60 + (target & 3))
    } while (!__all_sync(0xffffffffu, v >= target));
    if (!tagged) asm volatile("fence.acquire.gpu;" ::: "memory");
}
#define X_FENCE 0
__device__ __forceinline__ void signal_cnt(unsigned* p, int lane, int n, bool nofence = false) {
    if (nofence) { if (lane < n) asm volatile("red.relaxed.gpu.global.add.u32 [%0], 1;" ::"l"(p) : "memory"); }
    else if (lane < n) asm volatile("red.release.gpu.global.add.u32 [%0], 1;" ::"l"(p) : "memory");
    __syncwarp();
}
__device__ __forceinline__ void wait_clock(long long c0, int t) {
    while (clock64() - c0 < t) __nanosleep(20);
    __syncwarp();
}
__device__ __forceinline__ void tma_ld2(uint32_t dst, const CUtensorMap* m, int c0, int c1, uint32_t bar) {
    asm volatile("cp.async.bulk.tensor.2d.shared::cluster.global.mbarrier::complete_tx::bytes [%0], [%1, {%3, %4}], [%2];"
                 ::"r"(dst), "l"(m), "r"(bar), "r"(c0), "r"(c1) : "memory");
}
__device__ __forceinline__ void tma_ld3(uint32_t dst, const CUtensorMap* m, int c0, int c1, int c2, uint32_t bar) {
    asm volatile("cp.async.bulk.tensor.3d.shared::cluster.global.mbarrier::complete_tx::bytes [%0], [%1, {%3, %4, %5}], [%2];"
                 ::"r"(dst), "l"(m), "r"(bar), "r"(c0), "r"(c1), "r"(c2) : "memory");
}
__device__ __forceinline__ void tma_ld5(uint32_t dst, const CUtensorMap* m, int col, int blk, uint32_t bar) {
    asm volatile("cp.async.bulk.tensor.5d.shared::cluster.global.mbarrier::complete_tx::bytes [%0], [%1, {%3, %4, %4, %4, %5}], [%2];"
                 ::"r"(dst), "l"(m), "r"(bar), "r"(col), "r"(0), "r"(blk) : "memory");
}
__device__ __forceinline__ void bulk_ld(uint32_t dst, const void* src, uint32_t bytes, uint32_t bar) {
    asm volatile("cp.async.bulk.shared::cluster.global.mbarrier::complete_tx::bytes [%0], [%1], %2, [%3];" ::"r"(dst), "l"(src), "r"(bytes), "r"(bar) : "memory");
}
__device__ __forceinline__ void l2_prefetch(const void* p, uint32_t bytes) {
    asm volatile("cp.async.bulk.prefetch.L2.global [%0], %1;" ::"l"(p), "r"(bytes) : "memory");
}
__device__ __forceinline__ void wg_fence() { asm volatile("wgmma.fence.sync.aligned;" ::: "memory"); }
__device__ __forceinline__ void wg_commit() { asm volatile("wgmma.commit_group.sync.aligned;" ::: "memory"); }
template <int N> __device__ __forceinline__ void wg_wait() { asm volatile("wgmma.wait_group.sync.aligned %0;" ::"n"(N) : "memory"); }
template <int N> __device__ __forceinline__ void reg_fence(float (&d)[N]) {
#pragma unroll
    for (int i = 0; i < N; i++) asm volatile("" : "+f"(d[i])::"memory");
}
template <int N> __device__ __forceinline__ void zero(float (&d)[N]) {
#pragma unroll
    for (int i = 0; i < N; i++) asm volatile("mov.b32 %0, 0;" : "=f"(d[i]));
}
__device__ __forceinline__ uint32_t lds32(uint32_t a) { uint32_t v; asm volatile("ld.shared.b32 %0, [%1];" : "=r"(v) : "r"(a)); return v; }
__device__ __forceinline__ uint2 lds64(uint32_t a) { uint2 v; asm volatile("ld.shared.v2.b32 {%0,%1}, [%2];" : "=r"(v.x), "=r"(v.y) : "r"(a)); return v; }
__device__ __forceinline__ float2 lds64f(uint32_t a) { float2 v; asm volatile("ld.shared.v2.f32 {%0,%1}, [%2];" : "=f"(v.x), "=f"(v.y) : "r"(a)); return v; }
__device__ __forceinline__ void sts32(uint32_t a, uint32_t v) { asm volatile("st.shared.b32 [%0], %1;" ::"r"(a), "r"(v) : "memory"); }
__device__ __forceinline__ void sts64f(uint32_t a, float x, float y) { asm volatile("st.shared.v2.f32 [%0], {%1,%2};" ::"r"(a), "f"(x), "f"(y) : "memory"); }
__device__ __forceinline__ void sts128(uint32_t a, uint32_t x, uint32_t y, uint32_t z, uint32_t w) {
    asm volatile("st.shared.v4.b32 [%0], {%1,%2,%3,%4};" ::"r"(a), "r"(x), "r"(y), "r"(z), "r"(w) : "memory");
}
__device__ __forceinline__ void sts128f(uint32_t a, float x, float y, float z, float w) {
    asm volatile("st.shared.v4.f32 [%0], {%1,%2,%3,%4};" ::"r"(a), "f"(x), "f"(y), "f"(z), "f"(w) : "memory");
}
__device__ __forceinline__ uint4 lds128(uint32_t a) {
    uint4 v;
    asm volatile("ld.shared.v4.b32 {%0,%1,%2,%3}, [%4];" : "=r"(v.x), "=r"(v.y), "=r"(v.z), "=r"(v.w) : "r"(a) : "memory");
    return v;
}
__device__ __forceinline__ float4 lds128f(uint32_t a) {
    float4 v;
    asm volatile("ld.shared.v4.f32 {%0,%1,%2,%3}, [%4];" : "=f"(v.x), "=f"(v.y), "=f"(v.z), "=f"(v.w) : "r"(a) : "memory");
    return v;
}
__device__ __forceinline__ void stg128(void* p, uint32_t x, uint32_t y, uint32_t z, uint32_t w) {
    asm volatile("st.global.v4.b32 [%0], {%1,%2,%3,%4};" ::"l"(p), "r"(x), "r"(y), "r"(z), "r"(w) : "memory");
}
__device__ __forceinline__ void stg128(void* p, uint4 v) { stg128(p, v.x, v.y, v.z, v.w); }
__device__ __forceinline__ void stg128_if(void* p, uint4 v, int on) {
    asm volatile("{\n.reg .pred p;\nsetp.ne.s32 p, %5, 0;\n@p st.global.v4.b32 [%0], {%1,%2,%3,%4};\n}" ::"l"(p), "r"(v.x), "r"(v.y), "r"(v.z), "r"(v.w), "r"(on) : "memory");
}
__device__ __forceinline__ void stg64(void* p, uint32_t x, uint32_t y) { asm volatile("st.global.v2.b32 [%0], {%1,%2};" ::"l"(p), "r"(x), "r"(y) : "memory"); }
__device__ __forceinline__ void stsm4(uint32_t a, uint32_t r0, uint32_t r1, uint32_t r2, uint32_t r3) {
    asm volatile("stmatrix.sync.aligned.m8n8.x4.shared.b16 [%0], {%1,%2,%3,%4};" ::"r"(a), "r"(r0), "r"(r1), "r"(r2), "r"(r3) : "memory");
}
__device__ __forceinline__ void stsm4t(uint32_t a, uint32_t r0, uint32_t r1, uint32_t r2, uint32_t r3) {
    asm volatile("stmatrix.sync.aligned.m8n8.x4.trans.shared.b16 [%0], {%1,%2,%3,%4};" ::"r"(a), "r"(r0), "r"(r1), "r"(r2), "r"(r3) : "memory");
}
__device__ __forceinline__ void ldsm4t_if(bool p, uint32_t a, uint32_t* r) {
    asm volatile("{\n.reg .pred p;\nsetp.ne.u32 p, %5, 0;\n@p ldmatrix.sync.aligned.m8n8.x4.trans.shared.b16 {%0,%1,%2,%3}, [%4];\n}"
                 : "+r"(r[0]), "+r"(r[1]), "+r"(r[2]), "+r"(r[3]) : "r"(a), "r"((uint32_t)p) : "memory");
}
__device__ __forceinline__ void ldsm4t(uint32_t a, uint32_t& r0, uint32_t& r1, uint32_t& r2, uint32_t& r3) {
    asm volatile("ldmatrix.sync.aligned.m8n8.x4.trans.shared.b16 {%0,%1,%2,%3}, [%4];" : "=r"(r0), "=r"(r1), "=r"(r2), "=r"(r3) : "r"(a) : "memory");
}
__device__ __forceinline__ uint32_t pack2(float lo, float hi) {
    uint32_t r;
    asm("cvt.rn.bf16x2.f32 %0, %1, %2;" : "=r"(r) : "f"(hi), "f"(lo));
    return r;
}
__device__ __forceinline__ uint32_t mul2(uint32_t a, uint32_t b) { uint32_t r; asm("mul.rn.bf16x2 %0, %1, %2;" : "=r"(r) : "r"(a), "r"(b)); return r; }
__device__ __forceinline__ uint32_t fma2(uint32_t a, uint32_t b, uint32_t c) { uint32_t r; asm("fma.rn.bf16x2 %0, %1, %2, %3;" : "=r"(r) : "r"(a), "r"(b), "r"(c)); return r; }
__device__ __forceinline__ uint32_t add2(uint32_t a, uint32_t b) { uint32_t r; asm("add.rn.bf16x2 %0, %1, %2;" : "=r"(r) : "r"(a), "r"(b)); return r; }
__device__ __forceinline__ void hmma(float (&d)[4], uint32_t a0, uint32_t a1, uint32_t a2, uint32_t a3, uint32_t b0, uint32_t b1) {
    asm volatile("mma.sync.aligned.m16n8k16.row.col.f32.bf16.bf16.f32 {%0,%1,%2,%3}, {%4,%5,%6,%7}, {%8,%9}, {%0,%1,%2,%3};"
        : "+f"(d[0]), "+f"(d[1]), "+f"(d[2]), "+f"(d[3]) : "r"(a0), "r"(a1), "r"(a2), "r"(a3), "r"(b0), "r"(b1));
}
__device__ __forceinline__ float blo(uint32_t w) { return __uint_as_float(w << 16); }
__device__ __forceinline__ float bhi(uint32_t w) { return __uint_as_float(w & 0xffff0000u); }
__device__ __forceinline__ float rbf(float x) { return __bfloat162float(__float2bfloat16_rn(x)); }
__device__ __forceinline__ uint32_t ldg32(const void* p) { uint32_t v; asm volatile("ld.global.nc.b32 %0, [%1];" : "=r"(v) : "l"(p)); return v; }
__device__ __forceinline__ uint2 ldg64(const void* p) { uint2 v; asm volatile("ld.global.nc.v2.b32 {%0,%1}, [%2];" : "=r"(v.x), "=r"(v.y) : "l"(p)); return v; }
__device__ __forceinline__ uint4 ldg128(const void* p) {
    uint4 v;
    asm volatile("ld.global.nc.v4.b32 {%0,%1,%2,%3}, [%4];" : "=r"(v.x), "=r"(v.y), "=r"(v.z), "=r"(v.w) : "l"(p));
    return v;
}
__device__ __forceinline__ uint4 ldcg128(const void* p) {
    uint4 v;
    asm volatile("ld.global.cg.v4.u32 {%0,%1,%2,%3}, [%4];" : "=r"(v.x), "=r"(v.y), "=r"(v.z), "=r"(v.w) : "l"(p) : "memory");
    return v;
}
__device__ __forceinline__ float4 ldcg128f(const void* p) {
    float4 v;
    asm volatile("ld.global.cg.v4.f32 {%0,%1,%2,%3}, [%4];" : "=f"(v.x), "=f"(v.y), "=f"(v.z), "=f"(v.w) : "l"(p) : "memory");
    return v;
}
__device__ __forceinline__ float2 ldcg64f(const void* p) { float2 v; asm volatile("ld.global.cg.v2.f32 {%0,%1}, [%2];" : "=f"(v.x), "=f"(v.y) : "l"(p) : "memory"); return v; }
__device__ __forceinline__ float ldcg32f(const void* p) { float v; asm volatile("ld.global.cg.f32 %0, [%1];" : "=f"(v) : "l"(p) : "memory"); return v; }
__device__ __forceinline__ float2 ld_stat(const float2* p) {
    float2 v;
    asm volatile("{\n.reg .b64 q;\nld.relaxed.gpu.global.b64 q, [%2];\nmov.b64 {%0, %1}, q;\n}" : "=f"(v.x), "=f"(v.y) : "l"(p) : "memory");
    return v;
}
__device__ __forceinline__ uint32_t ld_cold(const unsigned* p) { uint32_t v; asm volatile("ld.relaxed.gpu.global.u32 %0, [%1];" : "=r"(v) : "l"(p) : "memory"); return v; }
__device__ __forceinline__ uint2 ld_mod(const uint2* p) {
    uint64_t v;
    asm volatile("ld.relaxed.gpu.global.b64 %0, [%1];" : "=l"(v) : "l"(p) : "memory");
    return make_uint2((uint32_t)v, (uint32_t)(v >> 32));
}
__device__ __forceinline__ float gelu2(float h) {
    float u = h * fmaf(h * h, 8.f * 0.0356774081f, 2.f * 0.7978845608f);
    float th;
    asm("tanh.approx.f32 %0, %1;" : "=f"(th) : "f"(u));
    return fmaf(h, th, h);
}

__device__ __forceinline__ void conv_channel(float (&d)[64], uint32_t pa, uint64_t db) {
    asm volatile("{\n.reg .b32 a0, a1, a2, a3, b0, b1, b2, b3, t0, t1;\n.reg .b64 d;\nld.shared.b32 a0, [%64];\nld.shared.b32 a1, [%64+128];\nld.shared.b32 a2, [%64+-128];\nmov.b32 a3, a0;\n"
        "ld.shared.b32 t0, [%64+256];\nld.shared.b32 t1, [%64+384];\nadd.s64 d, %65, 0;\nwgmma.fence.sync.aligned;\nwgmma.mma_async.sync.aligned.m64n128k16.f32.bf16.bf16 {%0, %1, %2, %3, %4, %5, %6, %7, %8, %9, %10, %11, %12, %13, %14, %15, %16, %17, %18, %19, %20, %21, %22, %23, %24, %25, %26, %27, %28, %29, %30, %31, %32, %33, %34, %35, %36, %37, %38, %39, %40, %41, %42, %43, %44, %45, %46, %47, %48, %49, %50, %51, %52, %53, %54, %55, %56, %57, %58, %59, %60, %61, %62, %63}, {a0, a1, a2, a3}, d, 0, 1, 1, 0;\nwgmma.commit_group.sync.aligned;\nwgmma.wait_group.sync.aligned 1;\nmov.b32 b2, a1;\nmov.b32 b0, t0;\nmov.b32 b3, t0;\nmov.b32 b1, t1;\n"
        "ld.shared.b32 t0, [%64+512];\nld.shared.b32 t1, [%64+640];\nadd.s64 d, %65, 8;\nwgmma.fence.sync.aligned;\nwgmma.mma_async.sync.aligned.m64n128k16.f32.bf16.bf16 {%0, %1, %2, %3, %4, %5, %6, %7, %8, %9, %10, %11, %12, %13, %14, %15, %16, %17, %18, %19, %20, %21, %22, %23, %24, %25, %26, %27, %28, %29, %30, %31, %32, %33, %34, %35, %36, %37, %38, %39, %40, %41, %42, %43, %44, %45, %46, %47, %48, %49, %50, %51, %52, %53, %54, %55, %56, %57, %58, %59, %60, %61, %62, %63}, {b0, b1, b2, b3}, d, 1, 1, 1, 0;\nwgmma.commit_group.sync.aligned;\nwgmma.wait_group.sync.aligned 1;\nmov.b32 a2, b1;\nmov.b32 a0, t0;\nmov.b32 a3, t0;\nmov.b32 a1, t1;\n"
        "ld.shared.b32 t0, [%64+768];\nld.shared.b32 t1, [%64+896];\nadd.s64 d, %65, 16;\nwgmma.fence.sync.aligned;\nwgmma.mma_async.sync.aligned.m64n128k16.f32.bf16.bf16 {%0, %1, %2, %3, %4, %5, %6, %7, %8, %9, %10, %11, %12, %13, %14, %15, %16, %17, %18, %19, %20, %21, %22, %23, %24, %25, %26, %27, %28, %29, %30, %31, %32, %33, %34, %35, %36, %37, %38, %39, %40, %41, %42, %43, %44, %45, %46, %47, %48, %49, %50, %51, %52, %53, %54, %55, %56, %57, %58, %59, %60, %61, %62, %63}, {a0, a1, a2, a3}, d, 1, 1, 1, 0;\nwgmma.commit_group.sync.aligned;\nwgmma.wait_group.sync.aligned 1;\nmov.b32 b2, a1;\nmov.b32 b0, t0;\nmov.b32 b3, t0;\nmov.b32 b1, t1;\n"
        "ld.shared.b32 t0, [%64+1024];\nld.shared.b32 t1, [%64+1152];\nadd.s64 d, %65, 24;\nwgmma.fence.sync.aligned;\nwgmma.mma_async.sync.aligned.m64n128k16.f32.bf16.bf16 {%0, %1, %2, %3, %4, %5, %6, %7, %8, %9, %10, %11, %12, %13, %14, %15, %16, %17, %18, %19, %20, %21, %22, %23, %24, %25, %26, %27, %28, %29, %30, %31, %32, %33, %34, %35, %36, %37, %38, %39, %40, %41, %42, %43, %44, %45, %46, %47, %48, %49, %50, %51, %52, %53, %54, %55, %56, %57, %58, %59, %60, %61, %62, %63}, {b0, b1, b2, b3}, d, 1, 1, 1, 0;\nwgmma.commit_group.sync.aligned;\nwgmma.wait_group.sync.aligned 1;\nmov.b32 a2, b1;\nmov.b32 a0, t0;\nmov.b32 a3, t0;\nmov.b32 a1, t1;\n"
        "ld.shared.b32 t0, [%64+1280];\nld.shared.b32 t1, [%64+1408];\nadd.s64 d, %65, 32;\nwgmma.fence.sync.aligned;\nwgmma.mma_async.sync.aligned.m64n128k16.f32.bf16.bf16 {%0, %1, %2, %3, %4, %5, %6, %7, %8, %9, %10, %11, %12, %13, %14, %15, %16, %17, %18, %19, %20, %21, %22, %23, %24, %25, %26, %27, %28, %29, %30, %31, %32, %33, %34, %35, %36, %37, %38, %39, %40, %41, %42, %43, %44, %45, %46, %47, %48, %49, %50, %51, %52, %53, %54, %55, %56, %57, %58, %59, %60, %61, %62, %63}, {a0, a1, a2, a3}, d, 1, 1, 1, 0;\nwgmma.commit_group.sync.aligned;\nwgmma.wait_group.sync.aligned 1;\nmov.b32 b2, a1;\nmov.b32 b0, t0;\nmov.b32 b3, t0;\nmov.b32 b1, t1;\n"
        "ld.shared.b32 t0, [%64+1536];\nld.shared.b32 t1, [%64+1664];\nadd.s64 d, %65, 40;\nwgmma.fence.sync.aligned;\nwgmma.mma_async.sync.aligned.m64n128k16.f32.bf16.bf16 {%0, %1, %2, %3, %4, %5, %6, %7, %8, %9, %10, %11, %12, %13, %14, %15, %16, %17, %18, %19, %20, %21, %22, %23, %24, %25, %26, %27, %28, %29, %30, %31, %32, %33, %34, %35, %36, %37, %38, %39, %40, %41, %42, %43, %44, %45, %46, %47, %48, %49, %50, %51, %52, %53, %54, %55, %56, %57, %58, %59, %60, %61, %62, %63}, {b0, b1, b2, b3}, d, 1, 1, 1, 0;\nwgmma.commit_group.sync.aligned;\nwgmma.wait_group.sync.aligned 1;\nmov.b32 a2, b1;\nmov.b32 a0, t0;\nmov.b32 a3, t0;\nmov.b32 a1, t1;\n"
        "ld.shared.b32 t0, [%64+1792];\nld.shared.b32 t1, [%64+1920];\nadd.s64 d, %65, 48;\nwgmma.fence.sync.aligned;\nwgmma.mma_async.sync.aligned.m64n128k16.f32.bf16.bf16 {%0, %1, %2, %3, %4, %5, %6, %7, %8, %9, %10, %11, %12, %13, %14, %15, %16, %17, %18, %19, %20, %21, %22, %23, %24, %25, %26, %27, %28, %29, %30, %31, %32, %33, %34, %35, %36, %37, %38, %39, %40, %41, %42, %43, %44, %45, %46, %47, %48, %49, %50, %51, %52, %53, %54, %55, %56, %57, %58, %59, %60, %61, %62, %63}, {a0, a1, a2, a3}, d, 1, 1, 1, 0;\nwgmma.commit_group.sync.aligned;\nwgmma.wait_group.sync.aligned 1;\nmov.b32 b2, a1;\nmov.b32 b0, t0;\nmov.b32 b3, t0;\nmov.b32 b1, t1;\n"
        "ld.shared.b32 t0, [%64+2048];\nld.shared.b32 t1, [%64+2176];\nadd.s64 d, %65, 56;\nwgmma.fence.sync.aligned;\nwgmma.mma_async.sync.aligned.m64n128k16.f32.bf16.bf16 {%0, %1, %2, %3, %4, %5, %6, %7, %8, %9, %10, %11, %12, %13, %14, %15, %16, %17, %18, %19, %20, %21, %22, %23, %24, %25, %26, %27, %28, %29, %30, %31, %32, %33, %34, %35, %36, %37, %38, %39, %40, %41, %42, %43, %44, %45, %46, %47, %48, %49, %50, %51, %52, %53, %54, %55, %56, %57, %58, %59, %60, %61, %62, %63}, {b0, b1, b2, b3}, d, 1, 1, 1, 0;\nwgmma.commit_group.sync.aligned;\nwgmma.wait_group.sync.aligned 1;\nmov.b32 a2, b1;\nmov.b32 a0, t0;\nmov.b32 a3, t0;\nmov.b32 a1, t1;\n"
        "ld.shared.b32 t0, [%64+2304];\nld.shared.b32 t1, [%64+2432];\nadd.s64 d, %65, 64;\nwgmma.fence.sync.aligned;\nwgmma.mma_async.sync.aligned.m64n96k16.f32.bf16.bf16 {%0, %1, %2, %3, %4, %5, %6, %7, %8, %9, %10, %11, %12, %13, %14, %15, %16, %17, %18, %19, %20, %21, %22, %23, %24, %25, %26, %27, %28, %29, %30, %31, %32, %33, %34, %35, %36, %37, %38, %39, %40, %41, %42, %43, %44, %45, %46, %47}, {a0, a1, a2, a3}, d, 1, 1, 1, 0;\nwgmma.commit_group.sync.aligned;\nwgmma.wait_group.sync.aligned 1;\nmov.b32 b2, a1;\nmov.b32 b0, t0;\nmov.b32 b3, t0;\nmov.b32 b1, t1;\n"
        "ld.shared.b32 t0, [%64+2560];\nld.shared.b32 t1, [%64+2688];\nadd.s64 d, %65, 72;\nwgmma.fence.sync.aligned;\nwgmma.mma_async.sync.aligned.m64n96k16.f32.bf16.bf16 {%0, %1, %2, %3, %4, %5, %6, %7, %8, %9, %10, %11, %12, %13, %14, %15, %16, %17, %18, %19, %20, %21, %22, %23, %24, %25, %26, %27, %28, %29, %30, %31, %32, %33, %34, %35, %36, %37, %38, %39, %40, %41, %42, %43, %44, %45, %46, %47}, {b0, b1, b2, b3}, d, 1, 1, 1, 0;\nwgmma.commit_group.sync.aligned;\nwgmma.wait_group.sync.aligned 1;\nmov.b32 a2, b1;\nmov.b32 a0, t0;\nmov.b32 a3, t0;\nmov.b32 a1, t1;\n"
        "ld.shared.b32 t0, [%64+2816];\nld.shared.b32 t1, [%64+2944];\nadd.s64 d, %65, 80;\nwgmma.fence.sync.aligned;\nwgmma.mma_async.sync.aligned.m64n88k16.f32.bf16.bf16 {%0, %1, %2, %3, %4, %5, %6, %7, %8, %9, %10, %11, %12, %13, %14, %15, %16, %17, %18, %19, %20, %21, %22, %23, %24, %25, %26, %27, %28, %29, %30, %31, %32, %33, %34, %35, %36, %37, %38, %39, %40, %41, %42, %43}, {a0, a1, a2, a3}, d, 1, 1, 1, 0;\nwgmma.commit_group.sync.aligned;\nwgmma.wait_group.sync.aligned 1;\nmov.b32 b2, a1;\nmov.b32 b0, t0;\nmov.b32 b3, t0;\nmov.b32 b1, t1;\n"
        "ld.shared.b32 t0, [%64+3072];\nld.shared.b32 t1, [%64+3200];\nadd.s64 d, %65, 88;\nwgmma.fence.sync.aligned;\nwgmma.mma_async.sync.aligned.m64n88k16.f32.bf16.bf16 {%0, %1, %2, %3, %4, %5, %6, %7, %8, %9, %10, %11, %12, %13, %14, %15, %16, %17, %18, %19, %20, %21, %22, %23, %24, %25, %26, %27, %28, %29, %30, %31, %32, %33, %34, %35, %36, %37, %38, %39, %40, %41, %42, %43}, {b0, b1, b2, b3}, d, 1, 1, 1, 0;\nwgmma.commit_group.sync.aligned;\nwgmma.wait_group.sync.aligned 1;\nmov.b32 a2, b1;\nmov.b32 a0, t0;\nmov.b32 a3, t0;\nmov.b32 a1, t1;\n"
        "ld.shared.b32 t0, [%64+3328];\nld.shared.b32 t1, [%64+3456];\nadd.s64 d, %65, 96;\nwgmma.fence.sync.aligned;\nwgmma.mma_async.sync.aligned.m64n80k16.f32.bf16.bf16 {%0, %1, %2, %3, %4, %5, %6, %7, %8, %9, %10, %11, %12, %13, %14, %15, %16, %17, %18, %19, %20, %21, %22, %23, %24, %25, %26, %27, %28, %29, %30, %31, %32, %33, %34, %35, %36, %37, %38, %39}, {a0, a1, a2, a3}, d, 1, 1, 1, 0;\nwgmma.commit_group.sync.aligned;\nwgmma.wait_group.sync.aligned 1;\nmov.b32 b2, a1;\nmov.b32 b0, t0;\nmov.b32 b3, t0;\nmov.b32 b1, t1;\n"
        "ld.shared.b32 t0, [%64+3584];\nld.shared.b32 t1, [%64+3712];\nadd.s64 d, %65, 104;\nwgmma.fence.sync.aligned;\nwgmma.mma_async.sync.aligned.m64n80k16.f32.bf16.bf16 {%0, %1, %2, %3, %4, %5, %6, %7, %8, %9, %10, %11, %12, %13, %14, %15, %16, %17, %18, %19, %20, %21, %22, %23, %24, %25, %26, %27, %28, %29, %30, %31, %32, %33, %34, %35, %36, %37, %38, %39}, {b0, b1, b2, b3}, d, 1, 1, 1, 0;\nwgmma.commit_group.sync.aligned;\nwgmma.wait_group.sync.aligned 1;\nmov.b32 a2, b1;\nmov.b32 a0, t0;\nmov.b32 a3, t0;\nmov.b32 a1, t1;\n"
        "ld.shared.b32 t0, [%64+3840];\nld.shared.b32 t1, [%64+3968];\nadd.s64 d, %65, 112;\nwgmma.fence.sync.aligned;\nwgmma.mma_async.sync.aligned.m64n72k16.f32.bf16.bf16 {%0, %1, %2, %3, %4, %5, %6, %7, %8, %9, %10, %11, %12, %13, %14, %15, %16, %17, %18, %19, %20, %21, %22, %23, %24, %25, %26, %27, %28, %29, %30, %31, %32, %33, %34, %35}, {a0, a1, a2, a3}, d, 1, 1, 1, 0;\nwgmma.commit_group.sync.aligned;\nwgmma.wait_group.sync.aligned 1;\nmov.b32 b2, a1;\nmov.b32 b0, t0;\nmov.b32 b3, t0;\nmov.b32 b1, t1;\n"
        "ld.shared.b32 t0, [%64+4096];\nld.shared.b32 t1, [%64+4224];\nadd.s64 d, %65, 120;\nwgmma.fence.sync.aligned;\nwgmma.mma_async.sync.aligned.m64n72k16.f32.bf16.bf16 {%0, %1, %2, %3, %4, %5, %6, %7, %8, %9, %10, %11, %12, %13, %14, %15, %16, %17, %18, %19, %20, %21, %22, %23, %24, %25, %26, %27, %28, %29, %30, %31, %32, %33, %34, %35}, {b0, b1, b2, b3}, d, 1, 1, 1, 0;\nwgmma.commit_group.sync.aligned;\nwgmma.wait_group.sync.aligned 1;\nmov.b32 a2, b1;\nmov.b32 a0, t0;\nmov.b32 a3, t0;\nmov.b32 a1, t1;\n"
        "ld.shared.b32 t0, [%64+4352];\nld.shared.b32 t1, [%64+4480];\nadd.s64 d, %65, 128;\nwgmma.fence.sync.aligned;\nwgmma.mma_async.sync.aligned.m64n64k16.f32.bf16.bf16 {%0, %1, %2, %3, %4, %5, %6, %7, %8, %9, %10, %11, %12, %13, %14, %15, %16, %17, %18, %19, %20, %21, %22, %23, %24, %25, %26, %27, %28, %29, %30, %31}, {a0, a1, a2, a3}, d, 1, 1, 1, 0;\nwgmma.commit_group.sync.aligned;\nwgmma.wait_group.sync.aligned 1;\nmov.b32 b2, a1;\nmov.b32 b0, t0;\nmov.b32 b3, t0;\nmov.b32 b1, t1;\n"
        "ld.shared.b32 t0, [%64+4608];\nld.shared.b32 t1, [%64+4736];\nadd.s64 d, %65, 136;\nwgmma.fence.sync.aligned;\nwgmma.mma_async.sync.aligned.m64n64k16.f32.bf16.bf16 {%0, %1, %2, %3, %4, %5, %6, %7, %8, %9, %10, %11, %12, %13, %14, %15, %16, %17, %18, %19, %20, %21, %22, %23, %24, %25, %26, %27, %28, %29, %30, %31}, {b0, b1, b2, b3}, d, 1, 1, 1, 0;\nwgmma.commit_group.sync.aligned;\nwgmma.wait_group.sync.aligned 1;\nmov.b32 a2, b1;\nmov.b32 a0, t0;\nmov.b32 a3, t0;\nmov.b32 a1, t1;\n"
        "ld.shared.b32 t0, [%64+4864];\nld.shared.b32 t1, [%64+4992];\nadd.s64 d, %65, 144;\nwgmma.fence.sync.aligned;\nwgmma.mma_async.sync.aligned.m64n56k16.f32.bf16.bf16 {%0, %1, %2, %3, %4, %5, %6, %7, %8, %9, %10, %11, %12, %13, %14, %15, %16, %17, %18, %19, %20, %21, %22, %23, %24, %25, %26, %27}, {a0, a1, a2, a3}, d, 1, 1, 1, 0;\nwgmma.commit_group.sync.aligned;\nwgmma.wait_group.sync.aligned 1;\nmov.b32 b2, a1;\nmov.b32 b0, t0;\nmov.b32 b3, t0;\nmov.b32 b1, t1;\n"
        "ld.shared.b32 t0, [%64+5120];\nld.shared.b32 t1, [%64+5248];\nadd.s64 d, %65, 152;\nwgmma.fence.sync.aligned;\nwgmma.mma_async.sync.aligned.m64n56k16.f32.bf16.bf16 {%0, %1, %2, %3, %4, %5, %6, %7, %8, %9, %10, %11, %12, %13, %14, %15, %16, %17, %18, %19, %20, %21, %22, %23, %24, %25, %26, %27}, {b0, b1, b2, b3}, d, 1, 1, 1, 0;\nwgmma.commit_group.sync.aligned;\nwgmma.wait_group.sync.aligned 1;\nmov.b32 a2, b1;\nmov.b32 a0, t0;\nmov.b32 a3, t0;\nmov.b32 a1, t1;\n"
        "ld.shared.b32 t0, [%64+5376];\nld.shared.b32 t1, [%64+5504];\nadd.s64 d, %65, 160;\nwgmma.fence.sync.aligned;\nwgmma.mma_async.sync.aligned.m64n48k16.f32.bf16.bf16 {%0, %1, %2, %3, %4, %5, %6, %7, %8, %9, %10, %11, %12, %13, %14, %15, %16, %17, %18, %19, %20, %21, %22, %23}, {a0, a1, a2, a3}, d, 1, 1, 1, 0;\nwgmma.commit_group.sync.aligned;\nwgmma.wait_group.sync.aligned 1;\nmov.b32 b2, a1;\nmov.b32 b0, t0;\nmov.b32 b3, t0;\nmov.b32 b1, t1;\n"
        "ld.shared.b32 t0, [%64+5632];\nld.shared.b32 t1, [%64+5760];\nadd.s64 d, %65, 168;\nwgmma.fence.sync.aligned;\nwgmma.mma_async.sync.aligned.m64n48k16.f32.bf16.bf16 {%0, %1, %2, %3, %4, %5, %6, %7, %8, %9, %10, %11, %12, %13, %14, %15, %16, %17, %18, %19, %20, %21, %22, %23}, {b0, b1, b2, b3}, d, 1, 1, 1, 0;\nwgmma.commit_group.sync.aligned;\nwgmma.wait_group.sync.aligned 1;\nmov.b32 a2, b1;\nmov.b32 a0, t0;\nmov.b32 a3, t0;\nmov.b32 a1, t1;\n"
        "ld.shared.b32 t0, [%64+5888];\nld.shared.b32 t1, [%64+6016];\nadd.s64 d, %65, 176;\nwgmma.fence.sync.aligned;\nwgmma.mma_async.sync.aligned.m64n40k16.f32.bf16.bf16 {%0, %1, %2, %3, %4, %5, %6, %7, %8, %9, %10, %11, %12, %13, %14, %15, %16, %17, %18, %19}, {a0, a1, a2, a3}, d, 1, 1, 1, 0;\nwgmma.commit_group.sync.aligned;\nwgmma.wait_group.sync.aligned 1;\nmov.b32 b2, a1;\nmov.b32 b0, t0;\nmov.b32 b3, t0;\nmov.b32 b1, t1;\n"
        "ld.shared.b32 t0, [%64+6144];\nld.shared.b32 t1, [%64+6272];\nadd.s64 d, %65, 184;\nwgmma.fence.sync.aligned;\nwgmma.mma_async.sync.aligned.m64n40k16.f32.bf16.bf16 {%0, %1, %2, %3, %4, %5, %6, %7, %8, %9, %10, %11, %12, %13, %14, %15, %16, %17, %18, %19}, {b0, b1, b2, b3}, d, 1, 1, 1, 0;\nwgmma.commit_group.sync.aligned;\nwgmma.wait_group.sync.aligned 1;\nmov.b32 a2, b1;\nmov.b32 a0, t0;\nmov.b32 a3, t0;\nmov.b32 a1, t1;\n"
        "ld.shared.b32 t0, [%64+6400];\nld.shared.b32 t1, [%64+6528];\nadd.s64 d, %65, 192;\nwgmma.fence.sync.aligned;\nwgmma.mma_async.sync.aligned.m64n32k16.f32.bf16.bf16 {%0, %1, %2, %3, %4, %5, %6, %7, %8, %9, %10, %11, %12, %13, %14, %15}, {a0, a1, a2, a3}, d, 1, 1, 1, 0;\nwgmma.commit_group.sync.aligned;\nwgmma.wait_group.sync.aligned 1;\nmov.b32 b2, a1;\nmov.b32 b0, t0;\nmov.b32 b3, t0;\nmov.b32 b1, t1;\n"
        "ld.shared.b32 t0, [%64+6656];\nld.shared.b32 t1, [%64+6784];\nadd.s64 d, %65, 200;\nwgmma.fence.sync.aligned;\nwgmma.mma_async.sync.aligned.m64n32k16.f32.bf16.bf16 {%0, %1, %2, %3, %4, %5, %6, %7, %8, %9, %10, %11, %12, %13, %14, %15}, {b0, b1, b2, b3}, d, 1, 1, 1, 0;\nwgmma.commit_group.sync.aligned;\nwgmma.wait_group.sync.aligned 1;\nmov.b32 a2, b1;\nmov.b32 a0, t0;\nmov.b32 a3, t0;\nmov.b32 a1, t1;\n"
        "ld.shared.b32 t0, [%64+6912];\nld.shared.b32 t1, [%64+7040];\nadd.s64 d, %65, 208;\nwgmma.fence.sync.aligned;\nwgmma.mma_async.sync.aligned.m64n24k16.f32.bf16.bf16 {%0, %1, %2, %3, %4, %5, %6, %7, %8, %9, %10, %11}, {a0, a1, a2, a3}, d, 1, 1, 1, 0;\nwgmma.commit_group.sync.aligned;\nwgmma.wait_group.sync.aligned 1;\nmov.b32 b2, a1;\nmov.b32 b0, t0;\nmov.b32 b3, t0;\nmov.b32 b1, t1;\n"
        "ld.shared.b32 t0, [%64+7168];\nld.shared.b32 t1, [%64+7296];\nadd.s64 d, %65, 216;\nwgmma.fence.sync.aligned;\nwgmma.mma_async.sync.aligned.m64n24k16.f32.bf16.bf16 {%0, %1, %2, %3, %4, %5, %6, %7, %8, %9, %10, %11}, {b0, b1, b2, b3}, d, 1, 1, 1, 0;\nwgmma.commit_group.sync.aligned;\nwgmma.wait_group.sync.aligned 1;\nmov.b32 a2, b1;\nmov.b32 a0, t0;\nmov.b32 a3, t0;\nmov.b32 a1, t1;\n"
        "ld.shared.b32 t0, [%64+7424];\nld.shared.b32 t1, [%64+7552];\nadd.s64 d, %65, 224;\nwgmma.fence.sync.aligned;\nwgmma.mma_async.sync.aligned.m64n16k16.f32.bf16.bf16 {%0, %1, %2, %3, %4, %5, %6, %7}, {a0, a1, a2, a3}, d, 1, 1, 1, 0;\nwgmma.commit_group.sync.aligned;\nwgmma.wait_group.sync.aligned 1;\nmov.b32 b2, a1;\nmov.b32 b0, t0;\nmov.b32 b3, t0;\nmov.b32 b1, t1;\n"
        "ld.shared.b32 t0, [%64+7680];\nld.shared.b32 t1, [%64+7808];\nadd.s64 d, %65, 232;\nwgmma.fence.sync.aligned;\nwgmma.mma_async.sync.aligned.m64n16k16.f32.bf16.bf16 {%0, %1, %2, %3, %4, %5, %6, %7}, {b0, b1, b2, b3}, d, 1, 1, 1, 0;\nwgmma.commit_group.sync.aligned;\nwgmma.wait_group.sync.aligned 1;\nmov.b32 a2, b1;\nmov.b32 a0, t0;\nmov.b32 a3, t0;\nmov.b32 a1, t1;\n"
        "ld.shared.b32 t0, [%64+7936];\nld.shared.b32 t1, [%64+8064];\nadd.s64 d, %65, 240;\nwgmma.fence.sync.aligned;\nwgmma.mma_async.sync.aligned.m64n8k16.f32.bf16.bf16 {%0, %1, %2, %3}, {a0, a1, a2, a3}, d, 1, 1, 1, 0;\nwgmma.commit_group.sync.aligned;\nwgmma.wait_group.sync.aligned 1;\nmov.b32 b2, a1;\nmov.b32 b0, t0;\nmov.b32 b3, t0;\nmov.b32 b1, t1;\n"
        "add.s64 d, %65, 248;\nwgmma.fence.sync.aligned;\nwgmma.mma_async.sync.aligned.m64n8k16.f32.bf16.bf16 {%0, %1, %2, %3}, {b0, b1, b2, b3}, d, 1, 1, 1, 0;\nwgmma.commit_group.sync.aligned;\nwgmma.wait_group.sync.aligned 0;\n"
        "}" : "+f"(d[0]), "+f"(d[1]), "+f"(d[2]), "+f"(d[3]), "+f"(d[4]), "+f"(d[5]), "+f"(d[6]), "+f"(d[7]), "+f"(d[8]), "+f"(d[9]), "+f"(d[10]), "+f"(d[11]), "+f"(d[12]), "+f"(d[13]), "+f"(d[14]), "+f"(d[15]), "+f"(d[16]), "+f"(d[17]), "+f"(d[18]), "+f"(d[19]), "+f"(d[20]), "+f"(d[21]), "+f"(d[22]), "+f"(d[23]), "+f"(d[24]), "+f"(d[25]), "+f"(d[26]), "+f"(d[27]), "+f"(d[28]), "+f"(d[29]), "+f"(d[30]), "+f"(d[31]), "+f"(d[32]), "+f"(d[33]), "+f"(d[34]), "+f"(d[35]), "+f"(d[36]), "+f"(d[37]), "+f"(d[38]), "+f"(d[39]), "+f"(d[40]), "+f"(d[41]), "+f"(d[42]), "+f"(d[43]), "+f"(d[44]), "+f"(d[45]), "+f"(d[46]), "+f"(d[47]), "+f"(d[48]), "+f"(d[49]), "+f"(d[50]), "+f"(d[51]), "+f"(d[52]), "+f"(d[53]), "+f"(d[54]), "+f"(d[55]), "+f"(d[56]), "+f"(d[57]), "+f"(d[58]), "+f"(d[59]), "+f"(d[60]), "+f"(d[61]), "+f"(d[62]), "+f"(d[63]) : "r"(pa), "l"(db) : "memory");
}
__device__ __forceinline__ void wgmma_rs80(float (&d)[40], uint32_t a0, uint32_t a1, uint32_t a2, uint32_t a3, uint64_t db, int sc) {
    asm volatile("{\n.reg .pred p;\nsetp.ne.b32 p, %45, 0;\n"
        "wgmma.mma_async.sync.aligned.m64n80k16.f32.bf16.bf16 {%0, %1, %2, %3, %4, %5, %6, %7, %8, %9, %10, %11, %12, %13, %14, %15, %16, %17, %18, %19, %20, %21, %22, %23, %24, %25, %26, %27, %28, %29, %30, %31, %32, %33, %34, %35, %36, %37, %38, %39}, {%40, %41, %42, %43}, %44, p, 1, 1, 1;\n}\n"
        : "+f"(d[0]), "+f"(d[1]), "+f"(d[2]), "+f"(d[3]), "+f"(d[4]), "+f"(d[5]), "+f"(d[6]), "+f"(d[7]), "+f"(d[8]), "+f"(d[9]), "+f"(d[10]), "+f"(d[11]), "+f"(d[12]), "+f"(d[13]), "+f"(d[14]), "+f"(d[15]), "+f"(d[16]), "+f"(d[17]), "+f"(d[18]), "+f"(d[19]), "+f"(d[20]), "+f"(d[21]), "+f"(d[22]), "+f"(d[23]), "+f"(d[24]), "+f"(d[25]), "+f"(d[26]), "+f"(d[27]), "+f"(d[28]), "+f"(d[29]), "+f"(d[30]), "+f"(d[31]), "+f"(d[32]), "+f"(d[33]), "+f"(d[34]), "+f"(d[35]), "+f"(d[36]), "+f"(d[37]), "+f"(d[38]), "+f"(d[39]) : "r"(a0), "r"(a1), "r"(a2), "r"(a3), "l"(db), "r"(sc));
}
__device__ __forceinline__ void wgmma_ss80(float (&d)[40], uint64_t da, uint64_t db, int sc) {
    asm volatile("{\n.reg .pred p;\nsetp.ne.b32 p, %42, 0;\n"
        "wgmma.mma_async.sync.aligned.m64n80k16.f32.bf16.bf16 {%0, %1, %2, %3, %4, %5, %6, %7, %8, %9, %10, %11, %12, %13, %14, %15, %16, %17, %18, %19, %20, %21, %22, %23, %24, %25, %26, %27, %28, %29, %30, %31, %32, %33, %34, %35, %36, %37, %38, %39}, %40, %41, p, 1, 1, 0, 1;\n}\n"
        : "+f"(d[0]), "+f"(d[1]), "+f"(d[2]), "+f"(d[3]), "+f"(d[4]), "+f"(d[5]), "+f"(d[6]), "+f"(d[7]), "+f"(d[8]), "+f"(d[9]), "+f"(d[10]), "+f"(d[11]), "+f"(d[12]), "+f"(d[13]), "+f"(d[14]), "+f"(d[15]), "+f"(d[16]), "+f"(d[17]), "+f"(d[18]), "+f"(d[19]), "+f"(d[20]), "+f"(d[21]), "+f"(d[22]), "+f"(d[23]), "+f"(d[24]), "+f"(d[25]), "+f"(d[26]), "+f"(d[27]), "+f"(d[28]), "+f"(d[29]), "+f"(d[30]), "+f"(d[31]), "+f"(d[32]), "+f"(d[33]), "+f"(d[34]), "+f"(d[35]), "+f"(d[36]), "+f"(d[37]), "+f"(d[38]), "+f"(d[39]) : "l"(da), "l"(db), "r"(sc));
}
__device__ __forceinline__ void wgmma_ss80t(float (&d)[40], uint64_t da, uint64_t db, int sc) {
    asm volatile("{\n.reg .pred p;\nsetp.ne.b32 p, %42, 0;\n"
        "wgmma.mma_async.sync.aligned.m64n80k16.f32.bf16.bf16 {%0, %1, %2, %3, %4, %5, %6, %7, %8, %9, %10, %11, %12, %13, %14, %15, %16, %17, %18, %19, %20, %21, %22, %23, %24, %25, %26, %27, %28, %29, %30, %31, %32, %33, %34, %35, %36, %37, %38, %39}, %40, %41, p, 1, 1, 1, 1;\n}\n"
        : "+f"(d[0]), "+f"(d[1]), "+f"(d[2]), "+f"(d[3]), "+f"(d[4]), "+f"(d[5]), "+f"(d[6]), "+f"(d[7]), "+f"(d[8]), "+f"(d[9]), "+f"(d[10]), "+f"(d[11]), "+f"(d[12]), "+f"(d[13]), "+f"(d[14]), "+f"(d[15]), "+f"(d[16]), "+f"(d[17]), "+f"(d[18]), "+f"(d[19]), "+f"(d[20]), "+f"(d[21]), "+f"(d[22]), "+f"(d[23]), "+f"(d[24]), "+f"(d[25]), "+f"(d[26]), "+f"(d[27]), "+f"(d[28]), "+f"(d[29]), "+f"(d[30]), "+f"(d[31]), "+f"(d[32]), "+f"(d[33]), "+f"(d[34]), "+f"(d[35]), "+f"(d[36]), "+f"(d[37]), "+f"(d[38]), "+f"(d[39]) : "l"(da), "l"(db), "r"(sc));
}
__device__ __forceinline__ void wgmma_ss8_ta(float (&d)[4], uint64_t da, uint64_t db, int sc) {
    asm volatile("{\n.reg .pred p;\nsetp.ne.b32 p, %6, 0;\n"
        "wgmma.mma_async.sync.aligned.m64n8k16.f32.bf16.bf16 {%0, %1, %2, %3}, %4, %5, p, 1, 1, 1, 0;\n}\n"
        : "+f"(d[0]), "+f"(d[1]), "+f"(d[2]), "+f"(d[3]) : "l"(da), "l"(db), "r"(sc));
}
__device__ __forceinline__ void wgmma_rs8(float (&d)[4], uint32_t a0, uint32_t a1, uint32_t a2, uint32_t a3, uint64_t db, int sc) {
    asm volatile("{\n.reg .pred p;\nsetp.ne.b32 p, %9, 0;\n"
        "wgmma.mma_async.sync.aligned.m64n8k16.f32.bf16.bf16 {%0, %1, %2, %3}, {%4, %5, %6, %7}, %8, p, 1, 1, 0;\n}\n"
        : "+f"(d[0]), "+f"(d[1]), "+f"(d[2]), "+f"(d[3]) : "r"(a0), "r"(a1), "r"(a2), "r"(a3), "l"(db), "r"(sc));
}
__device__ __forceinline__ void wgmma_rs128(float (&d)[64], uint32_t a0, uint32_t a1, uint32_t a2, uint32_t a3, uint64_t db, int sc) {
    asm volatile("{\n.reg .pred p;\nsetp.ne.b32 p, %69, 0;\n"
        "wgmma.mma_async.sync.aligned.m64n128k16.f32.bf16.bf16 {%0, %1, %2, %3, %4, %5, %6, %7, %8, %9, %10, %11, %12, %13, %14, %15, %16, %17, %18, %19, %20, %21, %22, %23, %24, %25, %26, %27, %28, %29, %30, %31, %32, %33, %34, %35, %36, %37, %38, %39, %40, %41, %42, %43, %44, %45, %46, %47, %48, %49, %50, %51, %52, %53, %54, %55, %56, %57, %58, %59, %60, %61, %62, %63}, {%64, %65, %66, %67}, %68, p, 1, 1, 1;\n}\n"
        : "+f"(d[0]), "+f"(d[1]), "+f"(d[2]), "+f"(d[3]), "+f"(d[4]), "+f"(d[5]), "+f"(d[6]), "+f"(d[7]), "+f"(d[8]), "+f"(d[9]), "+f"(d[10]), "+f"(d[11]), "+f"(d[12]), "+f"(d[13]), "+f"(d[14]), "+f"(d[15]), "+f"(d[16]), "+f"(d[17]), "+f"(d[18]), "+f"(d[19]), "+f"(d[20]), "+f"(d[21]), "+f"(d[22]), "+f"(d[23]), "+f"(d[24]), "+f"(d[25]), "+f"(d[26]), "+f"(d[27]), "+f"(d[28]), "+f"(d[29]), "+f"(d[30]), "+f"(d[31]), "+f"(d[32]), "+f"(d[33]), "+f"(d[34]), "+f"(d[35]), "+f"(d[36]), "+f"(d[37]), "+f"(d[38]), "+f"(d[39]), "+f"(d[40]), "+f"(d[41]), "+f"(d[42]), "+f"(d[43]), "+f"(d[44]), "+f"(d[45]), "+f"(d[46]), "+f"(d[47]), "+f"(d[48]), "+f"(d[49]), "+f"(d[50]), "+f"(d[51]), "+f"(d[52]), "+f"(d[53]), "+f"(d[54]), "+f"(d[55]), "+f"(d[56]), "+f"(d[57]), "+f"(d[58]), "+f"(d[59]), "+f"(d[60]), "+f"(d[61]), "+f"(d[62]), "+f"(d[63]) : "r"(a0), "r"(a1), "r"(a2), "r"(a3), "l"(db), "r"(sc));
}
__device__ __forceinline__ void wgmma_rs88(float (&d)[44], uint32_t a0, uint32_t a1, uint32_t a2, uint32_t a3, uint64_t db, int sc) {
    asm volatile("{\n.reg .pred p;\nsetp.ne.b32 p, %49, 0;\n"
        "wgmma.mma_async.sync.aligned.m64n88k16.f32.bf16.bf16 {%0, %1, %2, %3, %4, %5, %6, %7, %8, %9, %10, %11, %12, %13, %14, %15, %16, %17, %18, %19, %20, %21, %22, %23, %24, %25, %26, %27, %28, %29, %30, %31, %32, %33, %34, %35, %36, %37, %38, %39, %40, %41, %42, %43}, {%44, %45, %46, %47}, %48, p, 1, 1, 1;\n}\n"
        : "+f"(d[0]), "+f"(d[1]), "+f"(d[2]), "+f"(d[3]), "+f"(d[4]), "+f"(d[5]), "+f"(d[6]), "+f"(d[7]), "+f"(d[8]), "+f"(d[9]), "+f"(d[10]), "+f"(d[11]), "+f"(d[12]), "+f"(d[13]), "+f"(d[14]), "+f"(d[15]), "+f"(d[16]), "+f"(d[17]), "+f"(d[18]), "+f"(d[19]), "+f"(d[20]), "+f"(d[21]), "+f"(d[22]), "+f"(d[23]), "+f"(d[24]), "+f"(d[25]), "+f"(d[26]), "+f"(d[27]), "+f"(d[28]), "+f"(d[29]), "+f"(d[30]), "+f"(d[31]), "+f"(d[32]), "+f"(d[33]), "+f"(d[34]), "+f"(d[35]), "+f"(d[36]), "+f"(d[37]), "+f"(d[38]), "+f"(d[39]), "+f"(d[40]), "+f"(d[41]), "+f"(d[42]), "+f"(d[43]) : "r"(a0), "r"(a1), "r"(a2), "r"(a3), "l"(db), "r"(sc));
}
__device__ __forceinline__ void wgmma_rs128k(float (&d)[64], uint32_t a0, uint32_t a1, uint32_t a2, uint32_t a3, uint64_t db, int sc) {
    asm volatile("{\n.reg .pred p;\nsetp.ne.b32 p, %69, 0;\n"
        "wgmma.mma_async.sync.aligned.m64n128k16.f32.bf16.bf16 {%0, %1, %2, %3, %4, %5, %6, %7, %8, %9, %10, %11, %12, %13, %14, %15, %16, %17, %18, %19, %20, %21, %22, %23, %24, %25, %26, %27, %28, %29, %30, %31, %32, %33, %34, %35, %36, %37, %38, %39, %40, %41, %42, %43, %44, %45, %46, %47, %48, %49, %50, %51, %52, %53, %54, %55, %56, %57, %58, %59, %60, %61, %62, %63}, {%64, %65, %66, %67}, %68, p, 1, 1, 0;\n}\n"
        : "+f"(d[0]), "+f"(d[1]), "+f"(d[2]), "+f"(d[3]), "+f"(d[4]), "+f"(d[5]), "+f"(d[6]), "+f"(d[7]), "+f"(d[8]), "+f"(d[9]), "+f"(d[10]), "+f"(d[11]), "+f"(d[12]), "+f"(d[13]), "+f"(d[14]), "+f"(d[15]), "+f"(d[16]), "+f"(d[17]), "+f"(d[18]), "+f"(d[19]), "+f"(d[20]), "+f"(d[21]), "+f"(d[22]), "+f"(d[23]), "+f"(d[24]), "+f"(d[25]), "+f"(d[26]), "+f"(d[27]), "+f"(d[28]), "+f"(d[29]), "+f"(d[30]), "+f"(d[31]), "+f"(d[32]), "+f"(d[33]), "+f"(d[34]), "+f"(d[35]), "+f"(d[36]), "+f"(d[37]), "+f"(d[38]), "+f"(d[39]), "+f"(d[40]), "+f"(d[41]), "+f"(d[42]), "+f"(d[43]), "+f"(d[44]), "+f"(d[45]), "+f"(d[46]), "+f"(d[47]), "+f"(d[48]), "+f"(d[49]), "+f"(d[50]), "+f"(d[51]), "+f"(d[52]), "+f"(d[53]), "+f"(d[54]), "+f"(d[55]), "+f"(d[56]), "+f"(d[57]), "+f"(d[58]), "+f"(d[59]), "+f"(d[60]), "+f"(d[61]), "+f"(d[62]), "+f"(d[63]) : "r"(a0), "r"(a1), "r"(a2), "r"(a3), "l"(db), "r"(sc));
}
__device__ __forceinline__ void wgmma_rs88k(float (&d)[44], uint32_t a0, uint32_t a1, uint32_t a2, uint32_t a3, uint64_t db, int sc) {
    asm volatile("{\n.reg .pred p;\nsetp.ne.b32 p, %49, 0;\n"
        "wgmma.mma_async.sync.aligned.m64n88k16.f32.bf16.bf16 {%0, %1, %2, %3, %4, %5, %6, %7, %8, %9, %10, %11, %12, %13, %14, %15, %16, %17, %18, %19, %20, %21, %22, %23, %24, %25, %26, %27, %28, %29, %30, %31, %32, %33, %34, %35, %36, %37, %38, %39, %40, %41, %42, %43}, {%44, %45, %46, %47}, %48, p, 1, 1, 0;\n}\n"
        : "+f"(d[0]), "+f"(d[1]), "+f"(d[2]), "+f"(d[3]), "+f"(d[4]), "+f"(d[5]), "+f"(d[6]), "+f"(d[7]), "+f"(d[8]), "+f"(d[9]), "+f"(d[10]), "+f"(d[11]), "+f"(d[12]), "+f"(d[13]), "+f"(d[14]), "+f"(d[15]), "+f"(d[16]), "+f"(d[17]), "+f"(d[18]), "+f"(d[19]), "+f"(d[20]), "+f"(d[21]), "+f"(d[22]), "+f"(d[23]), "+f"(d[24]), "+f"(d[25]), "+f"(d[26]), "+f"(d[27]), "+f"(d[28]), "+f"(d[29]), "+f"(d[30]), "+f"(d[31]), "+f"(d[32]), "+f"(d[33]), "+f"(d[34]), "+f"(d[35]), "+f"(d[36]), "+f"(d[37]), "+f"(d[38]), "+f"(d[39]), "+f"(d[40]), "+f"(d[41]), "+f"(d[42]), "+f"(d[43]) : "r"(a0), "r"(a1), "r"(a2), "r"(a3), "l"(db), "r"(sc));
}
__device__ __forceinline__ void wgmma_rs80k(float (&d)[40], uint32_t a0, uint32_t a1, uint32_t a2, uint32_t a3, uint64_t db, int sc) {
    asm volatile("{\n.reg .pred p;\nsetp.ne.b32 p, %45, 0;\n"
        "wgmma.mma_async.sync.aligned.m64n80k16.f32.bf16.bf16 {%0, %1, %2, %3, %4, %5, %6, %7, %8, %9, %10, %11, %12, %13, %14, %15, %16, %17, %18, %19, %20, %21, %22, %23, %24, %25, %26, %27, %28, %29, %30, %31, %32, %33, %34, %35, %36, %37, %38, %39}, {%40, %41, %42, %43}, %44, p, 1, 1, 0;\n}\n"
        : "+f"(d[0]), "+f"(d[1]), "+f"(d[2]), "+f"(d[3]), "+f"(d[4]), "+f"(d[5]), "+f"(d[6]), "+f"(d[7]), "+f"(d[8]), "+f"(d[9]), "+f"(d[10]), "+f"(d[11]), "+f"(d[12]), "+f"(d[13]), "+f"(d[14]), "+f"(d[15]), "+f"(d[16]), "+f"(d[17]), "+f"(d[18]), "+f"(d[19]), "+f"(d[20]), "+f"(d[21]), "+f"(d[22]), "+f"(d[23]), "+f"(d[24]), "+f"(d[25]), "+f"(d[26]), "+f"(d[27]), "+f"(d[28]), "+f"(d[29]), "+f"(d[30]), "+f"(d[31]), "+f"(d[32]), "+f"(d[33]), "+f"(d[34]), "+f"(d[35]), "+f"(d[36]), "+f"(d[37]), "+f"(d[38]), "+f"(d[39]) : "r"(a0), "r"(a1), "r"(a2), "r"(a3), "l"(db), "r"(sc));
}
__device__ __forceinline__ void wgmma_rs64(float (&d)[32], uint32_t a0, uint32_t a1, uint32_t a2, uint32_t a3, uint64_t db, int sc) {
    asm volatile("{\n.reg .pred p;\nsetp.ne.b32 p, %37, 0;\n"
        "wgmma.mma_async.sync.aligned.m64n64k16.f32.bf16.bf16 {%0, %1, %2, %3, %4, %5, %6, %7, %8, %9, %10, %11, %12, %13, %14, %15, %16, %17, %18, %19, %20, %21, %22, %23, %24, %25, %26, %27, %28, %29, %30, %31}, {%32, %33, %34, %35}, %36, p, 1, 1, 1;\n}\n"
        : "+f"(d[0]), "+f"(d[1]), "+f"(d[2]), "+f"(d[3]), "+f"(d[4]), "+f"(d[5]), "+f"(d[6]), "+f"(d[7]), "+f"(d[8]), "+f"(d[9]), "+f"(d[10]), "+f"(d[11]), "+f"(d[12]), "+f"(d[13]), "+f"(d[14]), "+f"(d[15]), "+f"(d[16]), "+f"(d[17]), "+f"(d[18]), "+f"(d[19]), "+f"(d[20]), "+f"(d[21]), "+f"(d[22]), "+f"(d[23]), "+f"(d[24]), "+f"(d[25]), "+f"(d[26]), "+f"(d[27]), "+f"(d[28]), "+f"(d[29]), "+f"(d[30]), "+f"(d[31]) : "r"(a0), "r"(a1), "r"(a2), "r"(a3), "l"(db), "r"(sc));
}

__device__ __forceinline__ uint64_t mkdesc(uint32_t lo) { return ((uint64_t)0x40000040u << 32) | lo; }
template <int F> __device__ __forceinline__ uint32_t lop3(uint32_t a, uint32_t b, uint32_t c) { uint32_t r; asm("lop3.b32 %0, %1, %2, %3, %4;" : "=r"(r) : "r"(a), "r"(b), "r"(c), "n"(F)); return r; }
__device__ __forceinline__ void stg128_tag(void* p, uint32_t x, uint32_t y, uint32_t z, uint32_t u, uint32_t ep, int w) {
    stg128(p, lop3<0xB8>(x, w == 0, ep), lop3<0xB8>(y, w == 1, ep), lop3<0xB8>(z, w == 2, ep), lop3<0xB8>(u, w == 3, ep));
}
__device__ __forceinline__ uint32_t tag(uint32_t w, uint32_t ep) { asm("lop3.b32 %0, %0, 1, %1, 0xB8;" : "+r"(w) : "r"(ep)); return w; }
template <int N> __device__ __forceinline__ void pack_part(uint32_t (&p)[32], const float (&v)[N], uint32_t ep) {
#pragma unroll
    for (int i = 0; i < N / 2; i++) p[i] = (i & 3) ? pack2(v[2 * i], v[2 * i + 1]) : tag(pack2(v[2 * i], v[2 * i + 1]), ep);
#pragma unroll
    for (int i = 0; i < N / 2; i++) asm volatile("" : "+r"(p[i]));
}
__device__ __forceinline__ void st_part(uint4* p, const uint32_t* v) {
    asm volatile("{\n.reg .b64 l, h;\n.reg .b128 q;\nmov.b64 l, {%1, %2};\nmov.b64 h, {%3, %4};\nmov.b128 q, {l, h};\nst.relaxed.gpu.global.b128 [%0], q;\n}"
                 ::"l"(p), "r"(v[0]), "r"(v[1]), "r"(v[2]), "r"(v[3]) : "memory");
}
__device__ __forceinline__ void st_peer(uint32_t a, uint32_t x, uint32_t y, uint32_t z, uint32_t w, uint32_t bar) {
    asm volatile("st.async.shared::cluster.mbarrier::complete_tx::bytes.v4.b32 [%0], {%1, %2, %3, %4}, [%5];" ::"r"(a), "r"(x), "r"(y), "r"(z), "r"(w), "r"(bar) : "memory");
}
__device__ __forceinline__ int g4_block(int c, int j) { return c ? j ^ (8 - 2 * c) : 8 + (j & 1); }
__device__ __forceinline__ uint32_t recv_off(int w) { return w ? OFF_XR : OFF_REM; }
__device__ __forceinline__ uint4 ld_part(const void* p) {
    uint4 v;
    asm volatile("{\n.reg .b64 l, h;\n.reg .b128 q;\nld.relaxed.gpu.global.b128 q, [%4];\nmov.b128 {l, h}, q;\nmov.b64 {%0, %1}, l;\nmov.b64 {%2, %3}, h;\n}"
                 : "=r"(v.x), "=r"(v.y), "=r"(v.z), "=r"(v.w) : "l"(p) : "memory");
    return v;
}
__device__ __forceinline__ void ld_part4(uint4 (&u)[4], const uint4* p, int st) {
#pragma unroll
    for (int i = 0; i < 4; i++) u[i] = ld_part(p + i * st);
}
__device__ __forceinline__ uint32_t stale4(const uint4 (&u)[4], uint32_t ep) { return (u[0].x ^ ep) | (u[1].x ^ ep) | (u[2].x ^ ep) | (u[3].x ^ ep); }
__device__ __forceinline__ void fix4(uint4 (&u)[4], const uint4* p, uint32_t ep, int code) {
    unsigned it = 0;
    while (__any_sync(~0u, stale4(u, ep) & 1)) {
        ld_part4(u, p, 128);
        STALE(code)
        SPIN_CHECK(58)
    }
}
__device__ __forceinline__ void add8(float* v, uint4 u) {
    v[0] += blo(u.x); v[1] += bhi(u.x); v[2] += blo(u.y); v[3] += bhi(u.y);
    v[4] += blo(u.z); v[5] += bhi(u.z); v[6] += blo(u.w); v[7] += bhi(u.w);
}
__device__ __forceinline__ void unpack8(float* v, uint4 u) {
    v[0] = blo(u.x); v[1] = bhi(u.x); v[2] = blo(u.y); v[3] = bhi(u.y); v[4] = blo(u.z); v[5] = bhi(u.z); v[6] = blo(u.w); v[7] = bhi(u.w);
}
__device__ __forceinline__ uint4 add2(uint4 a, uint4 b) { return make_uint4(add2(a.x, b.x), add2(a.y, b.y), add2(a.z, b.z), add2(a.w, b.w)); }
__device__ __forceinline__ void base16(float* v, uint4 b, float2 c, float2 d) {
    v[0] = fmaf(c.x, v[0], blo(b.x)); v[1] = fmaf(c.y, v[1], bhi(b.x)); v[2] = fmaf(c.x, v[2], blo(b.y)); v[3] = fmaf(c.y, v[3], bhi(b.y));
    v[4] = fmaf(d.x, v[4], blo(b.z)); v[5] = fmaf(d.y, v[5], bhi(b.z)); v[6] = fmaf(d.x, v[6], blo(b.w)); v[7] = fmaf(d.y, v[7], bhi(b.w));
}
__device__ __forceinline__ uint32_t split2(float x) { const float h = rbf(x); return pack2(h, x - h); }
__device__ __forceinline__ uint32_t b80_desc(uint32_t dsb, uint32_t wn, uint32_t rn, uint32_t h) {
    const uint32_t wb = dsb + OFF_W + (wn & 7) * 16384 + h * 8192, rm = dsb + OFF_REM + rn * 4096 + h * 2048;
    return (wb >> 4) | ((rm - wb) << 12);
}
constexpr int64_t B80_STEP = 128 - (126 << 16), B80_HALF = 512 - (384 << 16);
constexpr uint32_t ring_mask(int L) {
    uint32_t m = 0;
    for (int i = L; i < 20; i++) m |= (uint32_t)(i >= 20 - L || !((i - L) & 1)) << i;
    return m;
}
constexpr uint32_t M0 = ring_mask(LEAD1), M1 = ring_mask(10), M2 = ring_mask(XLEAD);
__device__ __forceinline__ uint32_t ring_pos(int w, int n, int L) { return w ? (n < 10 - L ? L + 2 * n : 10 + n) : (n < L ? n : 2 * n - L + 1); }
__device__ __forceinline__ int g1_block(int n, int j) { return n < 5 ? 2 * n + (j & 1) : 2 * n - 9 - (j & 1); }

__device__ __forceinline__ void load_tile(const Ptrs& pp, const Maps& mp, uint32_t dst, int e, int tile, int kb, int j, uint32_t bar) {
    mbar_expect(bar, 8192);
    if (e == 2) bulk_ld(dst, &g_x2f[(tile * 10 + kb) * 512], 8192, bar);
    else tma_ld2(dst, e ? &mp.t_ld : &mp.x1_ld, 64 * (e ? kb : tile), 64 * (e ? tile : g1_block(kb, j)), bar);
}

template <int OCT>
__device__ __forceinline__ void gemv_tile(float (&d)[4], uint32_t a, uint32_t b, int kb0) {
    uint32_t alo = ((a & 0x3FFFF) >> 4) | 0x10000u, blo_ = ((b & 0x3FFFF) >> 4) | (OCT << 16);
#pragma unroll 1
    for (int s = 0; s < 20; s += 4) {
        const int kb = kb0 + (s >> 2);
        const uint32_t bk = blo_ + (OCT == 7 ? (kb & 1) * 288 + (kb >> 1) * 56 : kb * 64);
        wg_fence();
#pragma unroll
        for (int q = 0; q < 4; q++) wgmma_ss8_ta(d, mkdesc(alo + (s + q) * 128), ((uint64_t)8 << 32) | (bk + q * 2 * OCT), s + q);
        wg_commit();
    }
    wg_wait<0>();
    reg_fence(d);
}

__device__ __forceinline__ void flush_tile(uint32_t st, bf16* dst, int u) {
#pragma unroll
    for (int i = 0; i < 2; i++) {
        const int idx = u + 320 * i, row = idx >> 3, c = idx & 7;
        stg128(dst + (size_t)row * S_ + 8 * c, lds128(st + row * 128 + ((c ^ ((row >> 1) & 7)) << 4)));
    }
}

__device__ __forceinline__ int tid_now() { int t; asm volatile("mov.u32 %0, %%tid.x;" : "=r"(t)); return t; }
__device__ __forceinline__ float zscale(float c) { return c == 0.f ? 0x1p-30f : c; }
__device__ __forceinline__ bool bar_any(int id, bool p) {
    uint32_t r;
    asm volatile("{\n.reg .pred a, b;\nsetp.ne.u32 a, %2, 0;\nbarrier.red.or.pred.aligned b, %1, 128, a;\nselp.u32 %0, 1, 0, b;\n}" : "=r"(r) : "r"(id), "r"((uint32_t)p) : "memory");
    return r != 0;
}

__global__ void __launch_bounds__(NTHR, 1) fused_kernel(const __grid_constant__ Ptrs pp, bf16* __restrict__ out, const __grid_constant__ Maps mp) {
    extern __shared__ __align__(1024) uint8_t smem_raw[];
    const uint32_t sb = s2u(smem_raw), bars = sb + M_BAR, dsb = sb & 0x3FFFF;
    const int id = blockIdx.x, warp = __shfl_sync(0xffffffffu, (int)threadIdx.x >> 5, 0), wg = warp >> 2;
    const long long c0 = clock64();
#define TIDS const int tid = tid_now(), lane = tid & 31, wt = tid & 127, g = lane >> 2, t = lane & 3; (void)wt; (void)g; (void)t;
    TS(threadIdx.x == 0, 0) TG(threadIdx.x == 0, 62)

    if (id >= 128) {
        TIDS
        if (sb & 1023) __trap();
        const int hs = id - 128;
        constexpr int H_B = 204800;
        static_assert(H_B + TAB_BYTES + 8 * VEC_BYTES <= OFF_M, "helper map");
        if (warp < 10 && elect()) { mbar_init(bars + warp * 8, 1); mbar_init(bars + 80 + warp * 8, 1); asm volatile("fence.mbarrier_init.release.cluster;" ::: "memory"); }
        __syncthreads();
        const uint32_t e0 = ld_cold(&g_epoch);
        wait_clock(c0, HELP_T);
        uint4 wr[10];
#pragma unroll
        for (int u = 0; u < 10; u++) wr[u] = ldg128(((hs >> 1) ? pp.w2 : pp.w1) + (size_t)(320 * (hs & 1) + (tid >> 4) + 32 * u) * D_ + 512 + 8 * (tid & 15));
        {
            const int r = tid >> 4, c = tid & 15;
            uint4* dst[2];
#pragma unroll
            for (int e = 0; e < 2; e++) {
                const int p = !(hs >> 1) ? r : e && (hs & 1) ? (r & ~14) | ((r & 6) << 1) | ((r & 8) >> 2) : (r & ~30) | ((r & 6) << 2) | ((r & 24) >> 2);
                dst[e] = &g_wr[(((hs >> 1) * 8 + (c >> 1)) * 10 + 5 * (hs & 1)) * 128 + (p & 15) * 8 + ((2 * (p >> 4) + (c & 1)) ^ (p & 7))];
            }
#pragma unroll
            for (int u = 0; u < 10; u++) stg128(reinterpret_cast<uint4*>(reinterpret_cast<uintptr_t>(dst[u >= 6]) ^ (64 * (u & 1))) + (u >> 1) * 128, wr[u]);
        }
        __syncthreads();
        if (warp == 0) signal_cnt(&g_cnt.wr[0], lane, 1);
        __syncthreads();
        if (warp < 5 && elect()) {
            const int un = 5 * hs + warp;
            mbar_expect(bars + warp * 8, 40960);
            tma_ld2(sb + warp * 40960, &mp.w1h, 64 * (un >> 1), 320 * (un & 1), bars + warp * 8);
            tma_ld2(sb + warp * 40960 + 20480, &mp.w1h, 64 * (un >> 1), 320 * (un & 1) + 160, bars + warp * 8);
        }
        if (tid < 320) {
            const uint4* gm = reinterpret_cast<const uint4*>(g_mod + 3 * D_) + tid;
            const unsigned epoch = e0 + 1;
            uint4 r[6];
            unsigned it = 0;
            for (;;) {
                uint32_t bad = 0;
#pragma unroll
                for (int i = 0; i < 6; i++) { r[i] = ld_part(gm + (i >> 1) * (D_ / 2) + (i & 1) * 3 * D_); bad |= (r[i].y ^ epoch) | (r[i].w ^ epoch); }
                if (__all_sync(~0u, !bad)) break;
                if (++it > SPIN_LIMIT) SPIN_FAIL(54)
            }
            uint32_t mv[3];
#pragma unroll
            for (int i = 0; i < 3; i++) mv[i] = pack2(__uint_as_float(r[2 * i].x) + __uint_as_float(r[2 * i + 1].x), __uint_as_float(r[2 * i].z) + __uint_as_float(r[2 * i + 1].z));
            const uint32_t sw2 = mv[0], cw = add2(mv[1], 0x3f803f80u), gw = mv[2];
            const float c0 = blo(cw), c1 = bhi(cw), s0 = blo(sw2), s1 = bhi(sw2);
            const float i0 = __frcp_rn(zscale(c0)), i1 = __frcp_rn(zscale(c1));
            const uint32_t ci = pack2(i0, i1), cq = pack2(i0 * i0, i1 * i1);
            const uint32_t a = sb + H_B + ((tid >> 5) & 1) * 4608 + (tid >> 6) * 896 + ((tid >> 2) & 7) * 112 + (tid & 3) * 4;
            sts32(a, ci); sts32(a + 16, pack2(i0 - blo(ci), i1 - bhi(ci)));
            sts32(a + 32, cq); sts32(a + 48, pack2(fmaf(i0, i0, -blo(cq)), fmaf(i1, i1, -bhi(cq))));
            sts32(a + 64, cw); sts32(a + 80, sw2); sts32(a + 96, 0x3f803f80u);
            if ((tid & ~35) == 284) sts32(a + 112, 0);
            const uint32_t v = sb + H_B + TAB_BYTES + (tid < 256 ? (tid >> 5) * VEC_BYTES + (tid & 31) * 8 : ((tid - 256) >> 3) * VEC_BYTES + 256 + (tid & 7) * 8);
            sts64f(v, blo(gw), bhi(gw)); sts64f(v + 320, c0, c1); sts64f(v + 640, s0, s1); sts64f(v + 960, i0, i1);
            float k[5] = {c0 + c1, s0 + s1, fmaf(c0, c0, c1 * c1), fmaf(c0, s0, c1 * s1), fmaf(s0, s0, s1 * s1)};
#pragma unroll 1
            for (int o = 16; o; o >>= 1) {
#pragma unroll
                for (int e = 0; e < 5; e++) k[e] += __shfl_xor_sync(~0u, k[e], o);
            }
            const uint32_t ks = sb + H_B + TAB_BYTES + (lane & 7) * VEC_BYTES + 1280 + (warp >> 1) * 32;
            if ((warp & 1) && lane < 8) { sts128f(ks, k[0], k[1], k[2], k[3]); sts128f(ks + 16, k[4], 0.f, 0.f, 0.f); }
            bar_sync(3, 320);
            if (!(warp & 1) && lane < 8) {
                const float4 o = lds128f(ks);
                sts128f(ks, k[0] + o.x, k[1] + o.y, k[2] + o.z, k[3] + o.w); sts32(ks + 16, __float_as_uint(k[4] + __uint_as_float(lds32(ks + 16))));
            }
            fence_async_smem();
        }
        __syncthreads();
        if (hs == 0 && warp == 15 && elect()) {
            asm volatile("cp.async.bulk.global.shared::cta.bulk_group [%0], [%1], %2;\ncp.async.bulk.commit_group;\ncp.async.bulk.wait_group 0;"
                         ::"l"(g_tab), "r"(sb + H_B), "n"(TAB_BYTES + 8 * VEC_BYTES) : "memory");
            asm volatile("red.release.gpu.global.add.u32 [%0], 1;" ::"l"(&g_cnt.tab[0]) : "memory");
        }
        __syncwarp();
#pragma unroll 1
        for (int i = wg; i < 20; i += 4) {
            const int r = i / 5, b = i - 5 * r, un = 5 * hs + b, u3 = 20 * r + un;
            auto refill = [&](int e, int u, uint32_t fb) {
                mbar_expect(fb, 40960);
                tma_ld2(sb + e * 40960, &mp.w3h, 64 * (u >> 1), 320 * (u & 1), fb);
                tma_ld2(sb + e * 40960 + 20480, &mp.w3h, 64 * (u >> 1), 320 * (u & 1) + 160, fb);
            };
            if (i > 4 && i < 9) {
                bar_sync(1, 512);
                if (warp == 0) {
                    signal_cnt(&g_cnt.uv[0], lane, 1);
                    if (elect()) {
#pragma unroll 1
                        for (int e = 0; e < 5; e++) refill(e, 5 * hs + e, bars + (5 + e) * 8);
                        l2_prefetch(pp.w2 + (size_t)160 * hs * D_, 160 * D_ * 2);
                    }
                    __syncwarp();
                }
            }
            mbar_wait(bars + i * 8, 0);
            float d[4];
            gemv_tile<7>(d, sb + b * 40960, sb + H_B, 5 * (un & 1));
            const int col = 16 * (warp & 3) + g;
            float* dst = r ? g_cs3 + (un & 1) * 1920 + 64 * ((u3 >> 1) - 10) + col : g_uv + (un & 1) * 3 * D_ + 2 * D_ + 64 * (un >> 1) + col;
            if (t == 3) { dst[0] = d[0]; dst[8] = d[2]; }
            if (r == 0 && t == 2) { dst[-2 * D_] = d[0]; dst[8 - 2 * D_] = d[2]; dst[-D_] = d[1]; dst[8 - D_] = d[3]; }
            if (r == 1 || r == 2) {
                bar_sync(4 + wg, 128);
                if (wt == 0) refill(b, u3, bars + (i + 5) * 8);
            }
        }
        __syncthreads();
        if (warp == 0) signal_cnt(&g_cnt.cs[0], lane, 1);
        if (tid == 511) l2_prefetch(pp.w4 + (size_t)432 * hs * D_, 432 * D_ * 2);
        if (tid == 0 && hs == 3) {
            uint32_t it = 0;
            while (ld_cold(&g_epoch) == e0) { __nanosleep(256); if (++it > (1u << 20)) SPIN_FAIL(48) }
        }
        return;
    }

    if (elect()) {
        if (warp == 15) {
            mbar_init(bars + B_IN * 8, 1); mbar_init(bars + B_IN * 8 + 8, 1);
            asm volatile("fence.mbarrier_init.release.cluster;" ::: "memory");
            mbar_expect(bars + B_IN * 8, 131 * 160);
            tma_ld2(sb + OFF_KIN, &mp.k, 80 * (id & 7), 64 * (id >> 3) - 3, bars + B_IN * 8);
            tma_ld2(sb + OFF_VIN, &mp.v, 80 * (id & 7), 64 * (id >> 3), bars + B_IN * 8);
        } else if (warp < 13) {
            const uint32_t n = (0x1C14111111881ull >> (4 * warp)) & 15;
#pragma unroll
            for (int i = 0; i < 4; i++) mbar_init(bars + warp * 64 + i * 8, n);
            if (warp == 11) { mbar_init(bars + B_XFREE * 8, 16); mbar_init(bars + B_OWN * 8, 8); }
            else if (warp < 11) {
#pragma unroll
                for (int i = 4; i < 8; i++) mbar_init(bars + warp * 64 + i * 8, n);
            }
            asm volatile("fence.mbarrier_init.release.cluster;" ::: "memory");
        }
    }
    asm volatile("" ::"l"(pp.s), "l"(pp.c), "l"(out));
    TR4((threadIdx.x & 31) == 0, warp)
    const int pr = id >> 1;
    const int grp = pr < 4 ? 15 : pr < 36 ? (pr - 4) & 7 : 8 + (pr - 36) % 7;
    const int j = 2 * (pr < 4 ? pr : pr < 36 ? (pr - 4) >> 3 : (pr - 36) / 7) + (id & 1);

    if (wg == 3) {
        TIDS
        const int sw = warp - 12;
        uint32_t ep = ld_cold(&g_epoch);
        TR4(lane == 0, 20 + sw)
        __syncthreads();
        TR4(lane == 0, 30 + sw)
        asm volatile("barrier.cluster.arrive.relaxed.aligned;" ::: "memory");
        if (sw == 0) {
#pragma unroll 1
            for (int n = PF_N0; n < PF_N; n++) {
                wait_clock(c0, PF_T0 + PF_DT * (n - PF_N0));
                if (elect()) {
                    if (n < 8) l2_prefetch((const char*)(n < 4 ? pp.ssm_k : pp.q) + (size_t)id * 20480 + (n & 3) * 5120, 5120);
                    else l2_prefetch((const char*)pp.w_mod + (size_t)id * 38400 + (n - 8) * 4800, 4800);
                }
            }
        } else if (sw == 1) {
            wait_clock(c0, T_SSM);
            if (elect()) {
                mbar_expect(bars + B_SSM * 8, 20480);
                bulk_ld(sb + OFF_SSM, pp.ssm_k + (size_t)5 * id * S_, 20480, bars + B_SSM * 8);
            }
            mbar_spin(bars + B_KVS * 8, 0);
            signal_cnt(&g_cnt.kv[(id & 7) * 32], lane, 1, true);
            TS(lane == 0, 2)
            if (T_Q) wait_clock(c0, T_Q); else mbar_spin(bars + B_RAW * 8, 0);
            if (elect()) {
                mbar_expect(bars + B_QIN * 8, 20480);
                tma_ld3(sb + OFF_QIN, &mp.q, 0, 16 * id, 0, bars + B_QIN * 8);
            }
        } else if (sw == 2) {
            if (elect()) {
#pragma unroll 1
                for (int i = 2; i < (int)(sizeof(Maps) / sizeof(CUtensorMap)); i++) asm volatile("prefetch.tensormap [%0];" ::"l"(&mp.k + i) : "memory");
#pragma unroll 1
                for (int i = B_SUMS; i < B_SIG; i++) mbar_expect(bars + i * 8, i < B_RECV ? 2048 : (i & 3) < 3 ? 8192 : 3072);
            }
            wait_cnt(&g_cnt.kv[(id >> 4) * 32], 16, true);
            TS(lane == 0, 4)
            if (elect()) {
                mbar_expect(bars + B_RAW * 8, 12288);
                mbar_expect(bars + B_RAW2 * 8, 8192);
#pragma unroll
                for (int c = 0; c < 5; c++) bulk_ld(sb + OFF_CH + c * CH_BYTES, g_kvT + (size_t)(5 * id + c) * S_, 4096, bars + (c < 3 ? B_RAW : B_RAW2) * 8);
            }
            mbar_spin(bars + B_BK * 8, 0);
            mbar_spin(bars + B_RAW3 * 8, 0);
            if (!T_Q) mbar_spin(bars + B_QIN * 8, 0);
            if (id < 120 && elect()) {
                mbar_expect(bars + B_WM * 8, 40960);
                tma_ld2(sb + OFF_WM, &mp.wmod, 64 * pr, 320 * (id & 1), bars + B_WM * 8);
                tma_ld2(sb + OFF_WM + 20480, &mp.wmod, 64 * pr, 320 * (id & 1) + 160, bars + B_WM * 8);
            }
            TS(lane == 0, 57)
        } else {
            wait_clock(c0, T_KVB);
            if (elect()) {
                mbar_expect(bars + (B_IN + 1) * 8, 131 * 160);
                tma_ld2(sb + OFF_KIN + 10752, &mp.k, 80 * (id & 7), 64 * (id >> 3) + 1021, bars + (B_IN + 1) * 8);
                tma_ld2(sb + OFF_VIN + 10240, &mp.v, 80 * (id & 7), 64 * (id >> 3) + 1024, bars + (B_IN + 1) * 8);
            }
            TS(lane == 0, 53)
            if (lane == 0) sts32(sb + M_EP, ep + 1);
            sts32(sb + M_NUL + lane * 4, 0);
#pragma unroll 1
            for (int m = lane; m < 40; m += 32) {
                const uint4 c = ldg128(pp.c + 320 * (id & 1) + 8 * m);
                uint32_t w[4] = {c.x, c.y, c.z, c.w};
#pragma unroll
                for (int i = 0; i < 4; i++) { const float a = blo(w[i]), b = bhi(w[i]); w[i] = pack2(__fdividef(a, 1.f + __expf(-a)), __fdividef(b, 1.f + __expf(-b))); }
                sts128(sb + OFF_Z + m * 128, w[0], w[1], w[2], w[3]);
#pragma unroll 1
                for (int r = 1; r < 8; r++) sts128(sb + OFF_Z + m * 128 + r * 16, 0, 0, 0, 0);
            }
            fence_async_smem();
            mbar_spin(bars + B_RAW2 * 8, 0);
            for (uint32_t ph = 1;; ph ^= 1) {
                uint32_t bad = 0;
#pragma unroll 4
                for (int i = 0; i < 16; i++) bad |= lds32(sb + OFF_CH + (3 + (i >> 3)) * CH_BYTES + (i & 7) * 512 + lane * 16) ^ ~ep;
                if (!__any_sync(~0u, bad & 1)) break;
                if (elect()) {
                    mbar_expect(bars + B_RAW2 * 8, 8192);
#pragma unroll
                    for (int c = 3; c < 5; c++) bulk_ld(sb + OFF_CH + c * CH_BYTES, g_kvT + (size_t)(5 * id + c) * S_, 4096, bars + B_RAW2 * 8);
                }
                mbar_spin(bars + B_RAW2 * 8, ph);
            }
            if (elect()) mbar_arrive(bars + B_RAW3 * 8);
        }
        {
            mbar_spin(bars + B_QIN * 8, 0);
            asm volatile("add.u32 %0, %0, 1;" : "+r"(ep));
            TS(wt == 0, 54)
            const int tk = 8 * ((lane >> 1) & 1) + 2 * (lane >> 3) + (lane & 1), ck = 4 * (sw & 1) + ((lane >> 1) & 2);
            const uint32_t src = sb + OFF_QIN + (sw >> 1) * 2048 + tk * 128;
            bf16* dst = g_qT + (size_t)id * 16 * D_ + (32 * sw + 8 * (t & 2) + g) * 16 + 8 * (t & 1);
#pragma unroll
            for (int i = 0; i < 5; i++) {
                uint32_t r[8];
                ldsm4t(src + i * 4096 + ((ck ^ (tk & 7)) << 4), r[0], r[1], r[2], r[3]);
                ldsm4t(src + i * 4096 + (((ck + 1) ^ (tk & 7)) << 4), r[4], r[5], r[6], r[7]);
                stg128(dst + i * 2048, tag(r[0], ep), r[1], r[2], r[3]);
                stg128(dst + i * 2048 + 128, tag(r[4], ep), r[5], r[6], r[7]);
            }
            float s1 = 0.f, s2 = 0.f;
#pragma unroll 2
            for (int i = 0; i < 10; i++) {
                const uint4 w4 = lds128(sb + OFF_QIN + i * 2048 + wt * 16);
                const uint32_t w[4] = {w4.x, w4.y, w4.z, w4.w};
#pragma unroll
                for (int e = 0; e < 4; e++) { const float a = blo(w[e]), b = bhi(w[e]); s1 += a + b; s2 = fmaf(a, a, fmaf(b, b, s2)); }
            }
#pragma unroll
            for (int o = 1; o < 8; o *= 2) { s1 += __shfl_xor_sync(~0u, s1, o); s2 += __shfl_xor_sync(~0u, s2, o); }
            s1 *= 1.f / D_;
            uint32_t rs = pack2(rsqrtf(fmaxf(s2 * (1.f / D_) - s1 * s1, 0.f) + 1e-5f), 0.f);
            if (lane < 8) rs = tag(rs, ep);
            rs = pack2(blo(rs), -s1 * blo(rs));
            const uint32_t sel = lane ? 0x7632 : 0x5410;
            const uint32_t a0 = __shfl_sync(~0u, rs, 0), a1 = __shfl_sync(~0u, rs, 8), a2 = __shfl_sync(~0u, rs, 16), a3 = __shfl_sync(~0u, rs, 24);
            if (lane < 2) stg64(g_qst + lane * S_ + 16 * id + 4 * sw, tag(__byte_perm(a0, a1, sel), ep), __byte_perm(a2, a3, sel));
            TS(wt == 0, 55)
        }
        bar_sync(6, 128);
        if (sw == 3) {
            signal_cnt(&g_cnt.q[(lane & 3) * 32], lane, 4, true);
            TS(lane == 0, 3)
        }
        if (id < 120) {
            mbar_spin(bars + B_WM * 8, 0);
            TS(wt == 0, 56)
            float d[4];
            gemv_tile<8>(d, sb + OFF_WM, sb + OFF_Z, 0);
            const float d2 = __shfl_up_sync(~0u, d[2], 1);
            TS(wt == 0, 7)
            if (t < 2) asm volatile("{\n.reg .b64 v;\nmov.b64 v, {%1, %2};\nst.relaxed.gpu.global.b64 [%0], v;\n}" ::"l"(g_mod + (id & 1) * 6 * D_ + 64 * pr + 16 * sw + g + 8 * t),
                                    "r"(__float_as_uint(t ? d2 : d[0])), "r"(ep) : "memory");
        }
        bar_sync(6, 128);
        asm volatile("setmaxnreg.dec.sync.aligned.u32 32;");
        asm volatile("barrier.cluster.wait.aligned;" ::: "memory");
        if (sw == 1) {
            mbar_spin(bars + B_XS * 8, 0);
            signal_cnt(&g_cnt.x[(lane & 3) * 32], lane, 4, true);
            TS(lane == 0, 20)
#pragma unroll 1
            for (int e = 1; e < 3; e++) {
                wait_cnt(e == 1 ? &g_cnt.g1[min(grp + 15 + min(lane, 2), 31) * 32] : &g_cnt.g2[(grp + 16) * 32], 32, true);
                if (elect()) mbar_arrive(bars + (B_GATE + 2 + e) * 8);
                TS(lane == 0, 27 + 2 * e)
            }
            return;
        }
        if (sw == 2) {
            {
                wait_cnt(&g_cnt.tab[0], 1);
                if (elect()) {
                    mbar_expect(bars + B_TAB * 8, TAB_BYTES / 2 + VEC_BYTES);
                    bulk_ld(sb + OFF_TAB, g_tab + (j & 1) * (TAB_BYTES / 32), TAB_BYTES / 2, bars + B_TAB * 8);
                    bulk_ld(sb + M_GB, g_tab + (TAB_BYTES + j * VEC_BYTES) / 16, VEC_BYTES, bars + B_TAB * 8);
                }
                TS(lane == 0, 5)
            }
            mbar_spin(bars + B_XS * 8, 0);
            fence_async_smem();
#pragma unroll
            for (int e = 0; e < 3; e++) {
                uint32_t m = e == 0 ? M0 : e == 1 ? M1 : M2;
                int k0 = 0, k1 = 0;
#pragma unroll 1
                for (int n = 20 * e; n < 20 * e + 20; n++, m >>= 1) {
                    const int w = m & 1, kb = w ? k1 : k0, tile = grp + 16 * w;
                    k0 += 1 - w; k1 += w;
                    if (n == 20 * e) {
                        wait_cnt(e == 0 ? &g_cnt.x[(id & 3) * 32] : e == 1 ? &g_cnt.g1[max(grp - 1 + min(lane, 2), 0) * 32] : &g_cnt.g2[grp * 32], e ? 32 : 128, true);
                        TS(lane == 0, 26 + 2 * e)
                    }
                    if (e && w && kb == 0) mbar_spin(bars + (B_GATE + 2 + e) * 8, 0);
                    mbar_spin(bars + (B_XEMPTY + (n & 7)) * 8, ((n >> 3) & 1) ^ 1);
                    TR2(lane == 0 && n < 40, 20 + n)
                    if (elect()) load_tile(pp, mp, sb + OFF_XR + (n & 7) * 8192, e, tile, kb, j, bars + (B_LAND + (n & 7)) * 8);
                }
            }
            mbar_spin(bars + B_VEC3 * 8, 0);
            unsigned old = 0;
            if (lane == 0) old = atomicAdd(&g_cnt.done[0], 1u);
            if (__shfl_sync(~0u, old, 0) == 127) {
#pragma unroll 1
                for (int i = lane; i < (int)(sizeof(Counters) / 128); i += 32) reinterpret_cast<unsigned*>(&g_cnt)[i * 32] = 0;
                if (lane == 0) atomicAdd(&g_epoch, 1u);
            }
        } else if (sw == 0) {
            wait_cnt(&g_cnt.wr[0], 4);
            mbar_spin(bars + B_QRDY * 8, 0);
            const uint32_t wf = bars + B_WFULL * 8, we = bars + B_WEMPTY * 8;
#pragma unroll 1
            for (int n = 0; n < 5; n++) {
                if (n == 3) { mbar_spin(bars + B_XS * 8, 0); fence_async_smem(); }
                TR2(lane == 0, 70 + n)
                if (elect()) {
                    const uint32_t fb = wf + n * 8, dst = sb + OFF_W + n * 16384;
                    mbar_expect(fb, 20480);
#pragma unroll 1
                    for (int h = 0; h < 2; h++) {
                        const int kb = g1_block(2 * n + h, j);
                        tma_ld2(dst + h * 8192, &mp.w1, 64 * j, 64 * kb, fb);
                        bulk_ld(sb + OFF_REM + n * 4096 + h * 2048, &g_wr[(j * 10 + kb) * 128], 2048, fb);
                    }
                }
            }
            mbar_spin(bars + B_GATE * 8, 0);
#pragma unroll 1
            for (int i = -3; i < 5; i++) {
                const int n = i < 0 ? 8 + i : 5 + i;
                const uint32_t fb = wf + (n & 7) * 8;
                if (i >= 0) mbar_spin(we + i * 8, 0);
                TR2(lane == 0 && i >= 0, 70 + n)
                if (elect()) {
                    if (i < 0 || i >= 3) { mbar_expect(fb, 20480); tma_ld5(sb + OFF_W + (n & 7) * 16384, n < 9 ? &mp.w2a : &mp.w2b, 64 * j, n < 9 ? 4 * (n - 5) : 0, fb); }
                    if (i >= 0) bulk_ld(sb + OFF_REM + i * 4096, &g_wr[((8 + j) * 10 + 2 * i) * 128], 4096, fb);
                }
            }
            mbar_spin(bars + (B_GATE + 1) * 8, 0);
#pragma unroll 1
            for (int n = 10; n < 30; n++) {
                if (n == W3_N2) mbar_spin(bars + (B_GATE + 2) * 8, 0);
                mbar_spin(we + (n & 7) * 8, ((n >> 3) & 1) ^ 1);
                TR2(lane == 0, 70 + n)
                if (elect()) {
                    const uint32_t dst = sb + OFF_W + (n & 7) * 16384, fb = wf + (n & 7) * 8;
                    mbar_expect(fb, 13824);
                    tma_ld3(dst, &mp.w3a, 0, 32 * (n - 10), 3 * j, fb);
                    tma_ld2(dst + 12288, &mp.w3b, 1536 + 24 * j, 32 * (n - 10), fb);
                }
            }
            mbar_spin(we + 6 * 8, 0);
            if (elect()) mbar_arrive(bars + B_S30 * 8);
#pragma unroll 1
            for (int n = 31; n < 50; n++) {
                const int rem = 96 + 3 * (j >> 1);
                int m0, m1, r0, r1, c0_, c1_;
                if (n < 38) {
                    c0_ = g4_block(0, j); c1_ = g4_block(1, j);
                    m0 = m1 = n == 35;
                    r0 = r1 = n == 35 ? rem : 6 * (j ^ (n >= 34)) + ((0x2004204 >> (4 * (n - 31))) & 15);
                } else {
                    const int e = (n - 38) & 3;
                    c0_ = c1_ = g4_block(2 + ((n - 38) >> 2), j);
                    m0 = 0; m1 = e == 1 ? 1 : e == 3 ? -1 : 0;
                    r0 = 6 * (j ^ (e >> 1)) + 4 * (e & 1); r1 = e == 1 ? rem : r0 + 2;
                }
                mbar_spin(we + (n & 7) * 8, ((n >> 3) & 1) ^ 1);
                if (elect()) {
                    const uint32_t dst = sb + OFF_W + (n & 7) * 16384, fb = wf + (n & 7) * 8;
                    mbar_expect(fb, m1 < 0 ? 8192 : 16384 - 2048 * (m0 + m1));
                    tma_ld2(dst, &mp.w4[m0], 64 * c0_, r0 * (32 >> m0), fb);
                    if (m1 >= 0) tma_ld2(dst + 8192, &mp.w4[m1], 64 * c1_, r1 * (32 >> m1), fb);
                }
            }
#pragma unroll 1
            for (int w = 0; w < 2; w++) {
                const uint4* src = g_part + (size_t)(grp + 16 * w) * 40960;
                mbar_spin(bars + (B_RING + w) * 8, 1);
                if (elect()) {
                    const uint32_t fb = bars + (B_IN + w) * 8, rem = sb + OFF_OUT + w * 10240;
                    mbar_expect(fb, 10240);
                    bulk_ld(rem + 8192, &g_x1f[((grp + 16 * w) * 8 + j) * 640 + 512], 2048, fb);
#pragma unroll 1
                    for (int i = 0; i < 4; i++) bulk_ld(rem + i * 2048, src + ((j >> 2) + 2 * i) * 5120 + 4096 + j * 128, 2048, fb);
                }
            }
        } else {
            wait_cnt(&g_cnt.uv[0], 4);
#pragma unroll 1
            for (int c = lane; c < 80; c += 32) {
                const float* src = g_uv + (c < 64 ? 64 * j + c : 448 + 16 * j + c);
                const uint32_t u = split2(ldcg32f(src) + ldcg32f(src + 3 * D_)), v = split2(ldcg32f(src + D_) + ldcg32f(src + 4 * D_));
                const uint32_t s = split2(ldcg32f(src + 2 * D_) + ldcg32f(src + 5 * D_));
                sts128(sb + OFF_F1 + c * 16, u, __byte_perm(u, v, 0x5410), __byte_perm(v, 0, 0x1032), s);
                sts128(sb + M_F1 + c * 16, s & 0xffffu, 0, 0, 0);
            }
            fence_async_smem();
            warp_arrive(bars + B_VEC * 8);
            TS(lane == 0, 9)
            wait_cnt(&g_cnt.cs[0], 4);
            if (elect()) mbar_arrive(bars + B_VEC3 * 8);
            uint32_t s[7];
#pragma unroll
            for (int i = 0; i < 7; i++) {
                const int c = min(lane + 32 * i, 215);
                const float* src = g_cs3 + (i < 6 ? 192 * j + c : 1344 + 24 * j + c);
                s[i] = split2(ldcg32f(src) + ldcg32f(src + 1920));
            }
            TS(lane == 0, 19)
            mbar_spin(bars + B_S30 * 8, 0);
#pragma unroll
            for (int i = 0; i < 7; i++) sts128(sb + OFF_W + 6 * 16384 + min(lane + 32 * i, 215) * 16, s[i], s[i] & 0xffffu, 0, 0);
            fence_async_smem();
            warp_arrive(bars + (B_WFULL + 6) * 8);
        }
        return;
    }

    {
        uint32_t ep;
        {
            TIDS
            ep = ld_cold(&g_epoch);
            const int cp = (tid + 16) % 40, cp1 = tid % 40;
            const uint4 sh0 = ldg128(pp.shift_k + (80 * (id & 7) + 2 * cp1) * 4), sh1 = ldg128(pp.shift_k + (80 * (id & 7) + 2 * cp) * 4);
            uint32_t dd;
            asm volatile("ld.global.nc.u16 %0, [%1];" : "=r"(dd) : "l"(pp.ssm_D + 5 * id + min(wg + 3 * lane, 4)));
            TR4(lane == 0, 40 + warp)
            __syncthreads();
            asm volatile("barrier.cluster.arrive.relaxed.aligned;" ::: "memory");
            asm volatile("add.u32 %0, %0, 1;" : "+r"(ep));
#pragma unroll 1
            for (int hw = 0; hw < 2; hw++) {
                if ((unsigned)(warp - 2 * hw) >= 10) continue;
                const int u = tid - 64 * hw;
                const int c = hw ? cp : cp1, oc = u / 40, line = 31 - 16 * hw - (id >> 3);
                const uint4 sh = hw ? sh1 : sh0;
                const uint32_t st = sb + OFF_ST + hw * 10240, sta = st + c * 256 + ((((6 - 2 * (oc & 3)) ^ (oc >> 2) ^ (line & 1)) ^ (c & 7)) << 4), in = oc * 1280 + c * 4;
                const uint32_t f0 = __byte_perm(sh.x, sh.z, 0x5410), f1 = __byte_perm(sh.x, sh.z, 0x7632), f2 = __byte_perm(sh.y, sh.w, 0x5410), f3 = __byte_perm(sh.y, sh.w, 0x7632);
                uint32_t kk[11], vv[8];
                mbar_spin(bars + (B_IN + hw) * 8, 0);
                TS(tid == 64, 18 + 42 * hw)
#pragma unroll
                for (int i = 0; i < 11; i++) kk[i] = lds32(sb + OFF_KIN + hw * 10752 + in + i * 160);
#pragma unroll
                for (int i = 0; i < 8; i++) vv[i] = lds32(sb + OFF_VIN + hw * 10240 + in + i * 160);
#pragma unroll
                for (int i = 0; i < 8; i++) vv[i] = mul2(fma2(kk[i + 3], f0, fma2(kk[i + 2], f1, fma2(kk[i + 1], f2, mul2(kk[i], f3)))), vv[i]);
                sts128(sta, tag(__byte_perm(vv[0], vv[1], 0x5410), ep), __byte_perm(vv[2], vv[3], 0x5410), __byte_perm(vv[4], vv[5], 0x5410), __byte_perm(vv[6], vv[7], 0x5410));
                sts128(sta + 128, tag(__byte_perm(vv[0], vv[1], 0x7632), ep), __byte_perm(vv[2], vv[3], 0x7632), __byte_perm(vv[4], vv[5], 0x7632), __byte_perm(vv[6], vv[7], 0x7632));
                bar_sync(7 + hw, 320);
                flush_tile(st, g_kvT + (size_t)(80 * (id & 7)) * S_ + 64 * line, u);
                TS(tid == 64 && hw, 1)
            }
            warp_arrive(bars + B_KVS * 8);
            if (tid < 320) sts128(sb + OFF_CH + (tid >> 6) * CH_BYTES + 4096 + (tid & 63) * 16, 0, 0, 0, 0);
            mbar_spin(bars + B_SSM * 8, 0);
            TS(tid == 0, 14)
            uint2 w[7];
            uint32_t pv[7];
#pragma unroll
            for (int i = 0; i < 7; i++) {
                const uint32_t a = sb + OFF_SSM + min(wg + 3 * i, 19) * 1024 + wt * 8;
                w[i] = lds64(a); pv[i] = lds32(a - 4);
            }
#pragma unroll
            for (int i = 0; i < 7; i++) {
                const int un = min(wg + 3 * i, 19);
                sts128(sb + OFF_CH + (un >> 2) * CH_BYTES + OFF_P + (un & 3) * 2048 + wt * 16, __byte_perm(w[i].x, pv[i], 0x7610), __byte_perm(w[i].x, 0, 0x1032), __byte_perm(w[i].y, w[i].x, 0x7610), __byte_perm(w[i].y, 0, 0x1032));
            }
            __syncwarp();
            if (wt < 2 - (wg >> 1)) {
                const uint32_t h = lds32(sb + OFF_SSM + (wg + 3 * wt) * 4096), h0 = pack2(blo(h) + blo(dd), 0.f);
                sts64f(sb + OFF_CH + (wg + 3 * wt) * CH_BYTES + OFF_P, __uint_as_float(h0), __uint_as_float(__byte_perm(h, h0, 0x5432)));
            }
            fence_async_smem();
            warp_arrive(bars + B_BK * 8);
            asm volatile("barrier.cluster.wait.aligned;" ::: "memory");
            mbar_spin(bars + B_BK * 8, 0);
            TS(tid == 0, 15)
        }

        uint4 rs[2], nm[2];
        auto ld_stats = [&]() {
            const int wt = tid_now() & 127;
            mbar_spin(bars + B_QRDY * 8, 0);
#pragma unroll
            for (int h = 0; h < 2; h++) { rs[h] = lds128(sb + OFF_QT + 20480 + h * 2048 + wt * 16); nm[h] = lds128(sb + OFF_QT + 24576 + h * 2048 + wt * 16); }
        };
#pragma unroll
        for (int h = 0; h < 2; h++) rs[h] = nm[h] = make_uint4(0, 0, 0, 0);
#pragma unroll 1
        for (int c = wg; c < 5; c += 3) {
            const uint32_t kvb = sb + OFF_CH + c * CH_BYTES;
            mbar_spin(bars + (c < 3 ? B_RAW : B_RAW3) * 8, 0);
            for (uint32_t it = 0; c < 3;) {
                const int wt = tid_now() & 127;
                if (!bar_any(1 + wg, ((lds32(kvb + wt * 16) ^ ep) | (lds32(kvb + 2048 + wt * 16) ^ ep)) & 1)) break;
                if (wt == 0) { mbar_expect(bars + (B_RETRY + wg) * 8, 4096); bulk_ld(kvb, g_kvT + (size_t)(5 * id + c) * S_, 4096, bars + (B_RETRY + wg) * 8); }
                mbar_spin(bars + (B_RETRY + wg) * 8, ep >> 31);
                ep ^= 0x80000000u;
                STALE(0)
                SPIN_CHECK(57)
            }
            TS(threadIdx.x == 0, c ? 13 : 11)
            float acc[64];
            {
                const int l = tid_now() & 31;
                conv_channel(acc, kvb + OFF_P + (8 * (warp & 3) + (l >> 2) - 2 * (l & 3)) * 4, (((uint64_t)0xC0000010u << 32) | ((kvb & 0x3FFFF) >> 4) | 0x10000u) + pp.nil);
            }
            TS(threadIdx.x == 0, c ? 16 : 12)
            if (c < 3) warp_arrive(bars + B_R1 * 8);
            else { mbar_spin(bars + B_R1 * 8, 0); ld_stats(); }
            TR4(threadIdx.x == 0, 60 + (c >= 3) * 10)
            TIDS
            const int e = 127 - 8 * (lane >> 4) - (lane & 7), u0 = (warp & 3) + 8 * (e >> 2) + (e & 3) + 4 * ((lane >> 3) & 1);
            const uint32_t ring = sb + OFF_RING + c * 16384 + (warp & 3) * 4096, wa = ring + (u0 ^ ((u0 >> 1) & 4)) * 16;
            if (lane < (warp & 3)) sts128(ring + lane * 16, 0, 0, 0, 0);
#pragma unroll
            for (int i = 0; i < 8; i++)
                stsm4t(i == 0 && u0 >= 256 ? sb + M_SINK : wa - 512 * i, pack2(acc[8 * i], acc[8 * i + 1]), pack2(acc[8 * i + 2], acc[8 * i + 3]),
                       pack2(acc[8 * i + 4], acc[8 * i + 5]), pack2(acc[8 * i + 6], acc[8 * i + 7]));
            warp_arrive(bars + (B_RING + c) * 8);
            TR4(threadIdx.x == 0, 61 + (c >= 3) * 10)
        }
        TIDS
        if (warp == 8) {
            wait_cnt(&g_cnt.q[(id & 3) * 32], 128, true);
            if (elect()) {
                mbar_expect(bars + B_QRDY * 8, 28672);
                tma_ld2(sb + OFF_QT, &mp.qT, 80 * id, 0, bars + B_QRDY * 8);
                bulk_ld(sb + OFF_QT + 20480, g_qst, 8192, bars + B_QRDY * 8);
            }
            TS(lane == 0, 8)
        } else if (warp == 9) {
            const int v = min(lane / 5, 3);
            const uint2* gm = g_mod + (v + (v == 3)) * D_ + 5 * id + lane % 5;
            const unsigned epoch = lds32(sb + M_EP);
            uint2 r0, r1;
            unsigned it = 0;
            do {
                r0 = ld_mod(gm); r1 = ld_mod(gm + 6 * D_);
                SPIN_CHECK(55)
            } while (!__all_sync(~0u, r0.y == epoch && r1.y == epoch));
            const float m0 = __uint_as_float(r0.x), m1 = __uint_as_float(r1.x);
            const float m = rbf(m0 + m1), p = rbf(1.f + m);
            const float cz = zscale(__shfl_sync(~0u, p, 15 + lane % 5)), ga = __shfl_sync(~0u, m, 10 + lane % 5);
            if (lane < 15) sts32(sb + M_AB + lane % 5 * 16 + v * 4, lane < 10 ? __float_as_uint(cz * ga * (lane < 5 ? m : p)) : pack2(cz, cz));
            warp_arrive(bars + B_MODR * 8);
            TS(lane == 0, 6)
        }
        if (wg == 2) ld_stats();
        mbar_spin(bars + B_MODR * 8, 0);
        TR4(threadIdx.x == 0, 72)
        uint32_t it = 0;
        while (__any_sync(~0u, (lop3<0x7E>(rs[0].x, ep, rs[0].z) | lop3<0x7E>(nm[0].x, ep, nm[0].z) | lop3<0x7E>(rs[1].x, ep, rs[1].z) | lop3<0x7E>(nm[1].x, ep, nm[1].z)) & 1)) {
#pragma unroll
            for (int h = 0; h < 2; h++) { rs[h] = ld_part(g_qst + 1024 * h + 8 * wt); nm[h] = ld_part(g_qst + S_ + 1024 * h + 8 * wt); }
            STALE(1)
            SPIN_CHECK(53)
        }
        TR4(threadIdx.x == 0, 73)
#pragma unroll 1
        for (int c = wg == 2 ? 0 : 3 + wg; c < (wg == 2 ? 3 : 4 + wg); c++) {
            uint4 q[2], p[2][4];
#pragma unroll
            for (int h = 0; h < 2; h++) q[h] = lds128(sb + OFF_QT + h * 10240 + (wt >> 1) * 160 + c * 32 + (wt & 1) * 16);
            const float4 ab = lds128f(sb + M_AB + c * 16);
            mbar_spin(bars + (B_RING + c) * 8, 0);
            TR4(wt == 0, wg == 2 ? 80 + 2 * c : 74)
#pragma unroll
            for (int i = 0; i < 8; i++) p[i >> 2][i & 3] = lds128(sb + OFF_RING + c * 16384 + (i & 3) * 4096 + (i >> 2) * 2048 + (wt ^ ((wt >> 1) & 4)) * 16);
            while (__any_sync(~0u, lop3<0x7E>(q[0].x, ep, q[1].x) & 1)) {
#pragma unroll
                for (int h = 0; h < 2; h++) q[h] = ld_part(g_qT + ((64 * h + (wt >> 1)) * D_ + 5 * id + c) * 16 + 8 * (wt & 1));
                STALE(2)
                SPIN_CHECK(52)
            }
            TR4(wt == 0, wg == 2 ? 81 + 2 * c : 75)
#pragma unroll
            for (int h = 0; h < 2; h++) {
                const uint32_t qq[4] = {q[h].x, q[h].y, q[h].z, q[h].w}, r4[4] = {rs[h].x, rs[h].y, rs[h].z, rs[h].w}, n4[4] = {nm[h].x, nm[h].y, nm[h].z, nm[h].w};
                const uint4 y = add2(add2(p[h][0], p[h][1]), add2(p[h][2], p[h][3]));
                const uint32_t yy[4] = {y.x, y.y, y.z, y.w};
                uint32_t o[4];
#pragma unroll
                for (int i = 0; i < 4; i++) {
                    const uint32_t n = fma2(qq[i], r4[i], n4[i]);
                    o[i] = fma2(pack2(fmaf(blo(n), ab.y, ab.x), fmaf(bhi(n), ab.y, ab.x)), yy[i], mul2(qq[i], __float_as_uint(ab.z)));
                }
                stg128_tag(g_x1T + (size_t)(5 * id + c) * S_ + 1024 * h + 8 * wt, o[0], o[1], o[2], o[3], ep, ((5 * id + c) >> 3) & 3);
            }
        }
        warp_arrive(bars + B_XS * 8);
        TS(tid == 0, 17)
        TS(tid == 256, 52)
    }

    const uint32_t nil = pp.nil;
    const int wq = warp & 3;
    if (wg == 2) {
        TIDS
        asm volatile("setmaxnreg.dec.sync.aligned.u32 32;");
        {
            const uint32_t ep = lds32(sb + M_EP);
            uint32_t ph = 0;
#pragma unroll 1
            for (int m = wq - 4; m < 60; m += 4) {
                const int n = max(m, 0);
                const int e = (n >= 20) + (n >= 40), i = n - 20 * e;
                const uint32_t M = e == 0 ? M0 : e == 1 ? M1 : M2;
                const int w = (M >> i) & 1, c = __popc(M & ((1u << i) - 1)), kb = w ? c : i - c;
                const uint32_t a = sb + OFF_XR + (n & 7) * 8192;
                uint32_t ta = a + (e == 0 ? lane * 128 + ((lane & 7) << 4) + (lane >> 3) * 4
                                 : e == 1 ? (lane & 15) * 128 + (((lane >> 4 << 1) ^ (lane & 7)) << 4) + (lane & 8) + (lane >> 4) * 4
                                          : lane * 32 + (lane >> 2) * 4);
                uint32_t tb = e == 0 ? ta ^ 32 : ta + 2048, tc = e == 2 ? ta + 1024 : ta ^ 64, td = e == 2 ? tb + 1024 : tb ^ 64;
                uint32_t live = m >= 0,
                    f0 = bars + (B_XFULL + 8 * w + ((10 * e + kb) & 7)) * 8;
                uint32_t f1 = m == GATE_W2 || m == GATE_W3 || m == GATE_W3B ? bars + (B_GATE + (m >= GATE_W3) + (m >= GATE_W3B)) * 8 : 0;
                if (lane) f0 = f1;
                if (lane > 1 || m < 0) f0 = 0;
                asm volatile("" : "+r"(ta), "+r"(tb), "+r"(tc), "+r"(td), "+r"(live), "+r"(f0));
                mbar_spin(bars + (m < 0 ? B_BK : B_LAND + (n & 7)) * 8, (n >> 3) & 1);
                TR5(lane == 0, n)
                while (true) {
                    uint32_t v[8];
#pragma unroll
                    for (int i = 0; i < 8; i++) v[i] = lds32(((i & 2) ? ((i & 1) ? td : tc) : (i & 1) ? tb : ta) + (i >> 2) * 4096);
                    const uint32_t bad = lop3<0xFE>(lop3<0x7E>(v[0], ep, v[1]), lop3<0x7E>(v[2], ep, v[3]), lop3<0x7E>(v[4], ep, v[5]));
                    if (!__any_sync(~0u, lop3<0xA8>(bad, lop3<0x7E>(v[6], ep, v[7]), live))) break;
                    if (elect()) load_tile(pp, mp, a, e, grp + 16 * w, kb, j, bars + (B_AGAIN + wq) * 8);
                    mbar_spin(bars + (B_AGAIN + wq) * 8, ph);
                    ph ^= 1;
                    STALE1(e)
                }
                TR5(lane == 0, 60 + n)
                if (f0) mbar_arrive(f0);
            }
        }
#pragma unroll 1
        for (int uw = 0; uw < 2; uw++) {
            const int tile = grp + 16 * uw;
            const uint32_t ep = lds32(sb + M_EP), in = sb + OFF_OUT + uw * 10240 + wt * 16, sr = in - lane * 16;
            mbar_wait(bars + (B_IN + uw) * 8, 1);
            float r[8];
#pragma unroll
            for (int h = 0; h < 2; h++) {
                uint4 a = lds128(in + h * 4096), b = lds128(in + h * 4096 + 2048);
                uint32_t it = 0;
                while (__any_sync(~0u, ((a.x ^ ep) | (b.x ^ ep)) & 1)) {
                    const uint4* p = g_part + (size_t)tile * 40960 + ((j >> 2) + 4 * h) * 5120 + 4096 + j * 128 + wt;
                    a = ld_part(p); b = ld_part(p + 10240);
                    STALE(3)
                    if (++it > SPIN_LIMIT) SPIN_FAIL(58)
                }
                if (h) add8(r, add2(a, b)); else unpack8(r, add2(a, b));
            }
            base16(r, lds128(in + 8192), lds64f(sb + M_GB + (64 + 2 * t) * 4), lds64f(sb + M_GB + (72 + 2 * t) * 4));
            __syncwarp();
            stsm4(sr + (lane & 15) * 32 + (((lane >> 4) ^ ((lane >> 2) & 1)) << 4), pack2(r[0], r[1]), pack2(r[2], r[3]), pack2(r[4], r[5]), pack2(r[6], r[7]));
            __syncwarp();
            stg128(out + (size_t)(64 * tile + 16 * wq + (lane >> 1)) * D_ + 512 + 16 * j + 8 * (lane & 1), lds128(sr + (lane >> 1) * 32 + (((lane & 1) ^ ((lane >> 3) & 1)) << 4)));
            __syncwarp();
        }
        if (wq == 0) {
            uint32_t it = 0;
            while (!mbar_try(bars + B_OWN * 8, 0)) { if (++it > SPIN_LIMIT) SPIN_FAIL(56) }
        }
        return;
    }

    TIDS
    const int uw = wg, tile = grp + 16 * uw, row0 = 64 * tile + 16 * wq;
    const bool leader = wt == 0; (void)leader;
    const uint32_t xfull = bars + (B_XFULL + 8 * uw) * 8, xempty = bars + B_XEMPTY * 8, wfull = bars + B_WFULL * 8, wempty = bars + B_WEMPTY * 8;
    const uint64_t dz = mkdesc(0) + pp.nil;
    auto xwait = [&](uint32_t n) { mbar_spin(xfull + (n & 7) * 8, (n >> 3) & 1); };
    asm volatile("setmaxnreg.inc.sync.aligned.u32 224;");
    const uint32_t ep = lds32(sb + M_EP);
    uint32_t res[20] = {};
    {
        float acc[40];
        const uint32_t la = ((lane & 7) + 8 * (lane >> 4)) * 128 + (((2 * wq + ((lane >> 3) & 1)) ^ (lane & 7)) << 4);
        auto pos = [&](int n) { return ring_pos(uw, n, LEAD1) & 7; };
        auto slot = [&](int n) { return sb + OFF_XR + pos(n) * 8192; };
        float al[2], r1[2], n1[2];
        {
            float sl[4], sq[4], v[4];
            uint32_t z0[16], z1[16], zz[16];
            uint64_t bd = dz + b80_desc(dsb, 0, 0, 0), tb = (((uint64_t)8 << 32) | ((dsb + OFF_TAB) >> 4) | (7u << 16)) + pp.nil;
            auto ldfrag = [&](uint32_t (&z)[16], int n) {
#pragma unroll
                for (int q = 0; q < 4; q++) ldsm4t(slot(n) + la + q * 2048, z[4 * q], z[4 * q + 1], z[4 * q + 2], z[4 * q + 3]);
            };
            auto tile1 = [&](const uint32_t (&zc)[16], uint32_t (&zn)[16], int n, int h) {
                const bool last = h && n == 5, ok = mbar_test(xfull + (n + 1) * 8, 0), okw = !h || mbar_test(wfull + ((n + 1) >> 1) * 8, 0);
                const int kb = g1_block(n, j);
                wg_fence();
#pragma unroll
                for (int q = 0; q < 2; q++) wgmma_rs80(acc, zc[4 * q], zc[4 * q + 1], zc[4 * q + 2], zc[4 * q + 3], bd + q * B80_STEP, 1);
                wg_commit();
                wg_wait<1>();
                if (!ok) xwait(n + 1);
                if (!last) ldfrag(zn, n + 1);
#pragma unroll
                for (int e = 0; e < 16; e++) zz[e] = mul2(zc[e], zc[e]);
                const uint64_t t0 = last ? ((uint64_t)8 << 32) | ((dsb + M_NUL) >> 4) : tb;
                const uint32_t ts = last ? 0 : 14;
                wg_fence();
#pragma unroll
                for (int q = 0; q < 4; q++) wgmma_rs8(sl, zc[4 * q], zc[4 * q + 1], zc[4 * q + 2], zc[4 * q + 3], t0 + q * ts, 1);
#pragma unroll
                for (int q = 0; q < 4; q++) wgmma_rs8(sq, zz[4 * q], zz[4 * q + 1], zz[4 * q + 2], zz[4 * q + 3], t0 + q * ts, 1);
#pragma unroll
                for (int q = 2; q < 4; q++) wgmma_rs80(acc, zc[4 * q], zc[4 * q + 1], zc[4 * q + 2], zc[4 * q + 3], bd + q * B80_STEP, 1);
                wg_commit();
#pragma unroll
                for (int e = 0; e < 16; e++) res[e] = kb == j ? zc[e] : res[e];
                if (!h) {
                    ldsm4t_if(kb == 8 + (j >> 2), slot(n) + la + (j & 3) * 2048, &res[16]);
                    if (lane < 2) mbar_arrive_after(xempty + pos(n) * 8, res[16], 0, nil);
                } else if (lane < 2) mbar_arrive(xempty + pos(n) * 8);
                if (!h && n && lane == 0) mbar_arrive(wempty + ((n >> 1) - 1) * 8);
                tb += 56;
                bd = bd + (uint64_t)B80_HALF;
                if (!okw) mbar_spin(wfull + ((n + 1) >> 1) * 8, 0);
                TR(leader, 100 + 10 * uw + n)
            };
            zero(acc); zero(sl); zero(sq);
            mbar_spin(bars + B_TAB * 8, 0);
            mbar_spin(wfull, 0);
            xwait(0);
            TS(leader, 32 + uw)
            ldfrag(z0, 0);
#pragma unroll 1
            for (int n = 0; n < 6; n += 2) { tile1(z0, z1, n, 0); tile1(z1, z0, n + 1, 1); }
#pragma unroll
            for (int n = 6; n < 10; n++) {
                const uint64_t ad = dz + (((dsb + OFF_XR + pos(n) * 8192) >> 4) | 0x10000u);
                const bool ok = n == 9 || mbar_test(xfull + ((n + 1) & 7) * 8, (n + 1) >> 3), okw = n != 7 || mbar_test(wfull + 4 * 8, 0);
                wg_fence();
#pragma unroll
                for (int q = 0; q < 4; q++) wgmma_ss80t(acc, ad + q * 128, bd + q * B80_STEP, 1);
                wg_commit();
                bd = bd + (uint64_t)B80_HALF;
                if (n == 9) ldsm4t_if(9 - (j & 1) == 8 + (j >> 2), slot(9) + la + (j & 3) * 2048, &res[16]);
                wg_wait<1>();
                if (n > 6 && lane < 2) mbar_arrive(xempty + pos(n - 1) * 8);
                if (!(n & 1) && lane == 0) mbar_arrive(wempty + ((n >> 1) - 1) * 8);
                if (n == 6) {
                    reg_fence(sl); reg_fence(sq);
#pragma unroll
                    for (int e = 0; e < 2; e++) {
                        v[2 * e] = t == 0 ? sl[2 * e] + sl[2 * e + 1] : t == 1 ? sq[2 * e] + sq[2 * e + 1] : sl[2 * e];
                        v[2 * e + 1] = t == 2 ? sl[2 * e + 1] : sq[2 * e];
                    }
                    st_peer(peer_addr(sb + OFF_ROW + uw * 2048 + wt * 16), __float_as_uint(v[0]), __float_as_uint(v[1]), __float_as_uint(v[2]), __float_as_uint(v[3]), peer_addr(bars + (B_SUMS + uw) * 8));
                    TS(leader && !uw, 59)
                }
                if (!ok) xwait(n + 1);
                if (!okw) mbar_spin(wfull + 4 * 8, 0);
                TR(leader, 100 + 10 * uw + n)
            }
            float4 k = lds128f(sb + M_KS);
            float k4 = __uint_as_float(lds32(sb + M_KS + 16));
#pragma unroll
            for (int w = 1; w < 5; w++) {
                const float4 o = lds128f(sb + M_KS + w * 32);
                k.x += o.x; k.y += o.y; k.z += o.z; k.w += o.w; k4 += __uint_as_float(lds32(sb + M_KS + w * 32 + 16));
            }
            mbar_spin(bars + (B_SUMS + uw) * 8, 0);
            TS(leader && !uw, 10)
            const float4 o = lds128f(sb + OFF_ROW + uw * 2048 + wt * 16);
            v[0] += o.x; v[1] += o.y; v[2] += o.z; v[3] += o.w;
            uint32_t fa[4];
#pragma unroll
            for (int h = 0; h < 2; h++) {
                const int l0 = lane & ~3;
                const float s1 = __shfl_sync(~0u, v[2 * h], l0), s2 = __shfl_sync(~0u, v[2 * h], l0 + 1), scc = __shfl_sync(~0u, v[2 * h], l0 + 2);
                const float scs = __shfl_sync(~0u, v[2 * h + 1], l0 + 2), sc = __shfl_sync(~0u, v[2 * h], l0 + 3), sqq = __shfl_sync(~0u, v[2 * h + 1], l0 + 3);
                const float m1 = s1 * (1.f / D_), va = fmaxf(s2 * (1.f / D_) - m1 * m1, 0.f) + 1e-5f, r = rsqrtf(va);
                const float m2 = (r * (sc - m1 * k.x) + k.y) * (1.f / D_);
                const float e2 = (r * (r * (sqq + m1 * (m1 * k.z - 2.f * scc)) + 2.f * (scs - m1 * k.w)) + k4) * (1.f / D_);
                al[h] = r * 0.5f * rsqrtf(fmaxf(e2 - m2 * m2, 0.f) + 1e-5f); r1[h] = r; n1[h] = -m1 * r;
                const uint32_t fb = split2(va * r), fx = split2(t == 3 ? -m2 * va * r : -m1), fc = __shfl_sync(~0u, fx, lane | 3);
                fa[h] = __byte_perm(fx, fb, t == 1 ? 0x5432 : t == 2 ? 0x7654 : 0x1010);
                fa[2 + h] = t ? 0 : fc >> 16;
            }
            mbar_spin(bars + B_VEC * 8, 0);
            wg_fence();
            wgmma_rs80k(acc, fa[0], fa[1], fa[2], fa[3], ((uint64_t)8 << 32) | ((dsb + OFF_F1) >> 4) | (((M_F1 - OFF_F1) >> 4) << 16), 1);
            wg_commit();
        }
        wg_wait<0>();
        reg_fence(acc);
        if (lane < 2) mbar_arrive_after(xempty + pos(9) * 8, res[16], 0, nil);
        if (lane == 0) mbar_arrive(wempty + 4 * 8);
        TS(leader, 34 + uw)
        {
            bf16* const trow = g_t + (size_t)(row0 + g + 2) * D_;
#pragma unroll
            for (int b = 0; b < 3; b++) {
                uint32_t p[8];
#pragma unroll
                for (int ii = 0; ii < 4; ii++) {
                    const int i = 4 * b + ii;
                    if (i >= 10) continue;
#pragma unroll
                    for (int h = 0; h < 2; h++) p[(i & 3) + 4 * h] = pack2(gelu2(acc[4 * i + 2 * h] * al[h]), gelu2(acc[4 * i + 2 * h + 1] * al[h]));
                }
                if (b < 2) {
                    const int gr = (2 * j + b) / 5, sh = (gr & 1) ? -1 - (gr >> 1) : 1 + (gr >> 1);
                    bf16* dst = trow + 64 * j + 32 * b + 8 * t;
                    const int w = (((g + sh) >> 2) & 2) + (t >> 1);
                    stg128_tag(dst + sh * D_, p[0], p[1], p[2], p[3], ep, w);
                    stg128_tag(dst + (sh + 8) * D_, p[4], p[5], p[6], p[7], ep, w ^ 2);
                    if (row0 + g < sh || row0 + g + 8 >= S_ + sh) stg128_tag(dst + (sh > 0 ? 0 : 8) * D_, 0, 0, 0, 0, ep, (sh > 0 ? 0 : 2) + (t >> 1));
                } else {
                    bf16* dst = trow + 512 + 16 * j + 4 * t;
                    const uint32_t lo = t == (g < 2), hi = t == (g >= 2), o = j & 1;
                    stg64(dst - 2 * D_, lop3<0xB8>(p[0], lo & ~o, ep), lop3<0xB8>(p[1], lo & o, ep));
                    stg64(dst + 6 * D_, lop3<0xB8>(p[4], hi & ~o, ep), lop3<0xB8>(p[5], hi & o, ep));
                    if (row0 + g + 8 >= S_ - 2) stg64(dst + 8 * D_, ep & (t == 1) & ~o, ep & (t == 1) & o);
                }
            }
        }
        signal_cnt(&g_cnt.g1[tile * 32], lane, 1, true);
        TS(leader, 36 + uw)
#pragma unroll
        for (int i = 0; i < 10; i++) {
            const float2 c = lds64f(sb + M_C + (8 * i + 2 * t) * 4), s = lds64f(sb + M_SB + (8 * i + 2 * t) * 4);
#pragma unroll
            for (int h = 0; h < 2; h++) {
                acc[4 * i + 2 * h] = fmaf(blo(res[2 * i + h]), r1[h], fmaf(n1[h], c.x, s.x));
                acc[4 * i + 2 * h + 1] = fmaf(bhi(res[2 * i + h]), r1[h], fmaf(n1[h], c.y, s.y));
            }
        }
        mbar_spin(wfull + 5 * 8, 0);
        xwait(10);
        TS(leader, 22 + uw)
        uint32_t xo = (4 + 2 * uw) * 8, xp = 0;
        uint64_t ad = dz + (((dsb + OFF_XR) >> 4) | 0x10000u) + xo * 64, bd = dz + b80_desc(dsb, 5, 0, 0);
#pragma unroll 1
        for (int i = 0; i < 5; i++) {
            const uint32_t x1 = xfull + ((3 + 2 * i) & 7) * 8, p1 = i < 3, x2 = xfull + (min(4 + 2 * i, 11) & 7) * 8, p2 = i < 2;
            const uint32_t w2 = wfull + (min(6 + i, 9) & 7) * 8, pw = i >= 2;
            const bool ok1 = mbar_test(x1, p1);
            wg_fence();
#pragma unroll
            for (int q = 0; q < 4; q++) wgmma_ss80(acc, ad + q * 2, bd + q * B80_STEP, 1);
            wg_commit();
            wg_wait<1>();
            if (lane < 2 && i) mbar_arrive(xempty + xp);
            if (lane == 0 && i) mbar_arrive(wempty + ((4 + i) & 7) * 8);
            if (!ok1) mbar_spin(x1, p1);
            const bool ok2 = mbar_test(x2, p2), okw = mbar_test(w2, pw);
            wg_fence();
#pragma unroll
            for (int q = 0; q < 4; q++) wgmma_ss80(acc, ad + 512 + q * 2, bd + B80_HALF + q * B80_STEP, 1);
            wg_commit();
            const uint32_t xc = xo;
            xp = xo + 8; xo = (xo + 16) & 56;
            ad += xo ? 1024 : 1024 - 4096;
            bd += i == 2 ? 2 * B80_HALF - 8192 + (8192ll << 16) : 2 * B80_HALF;
            asm volatile("" : "+l"(ad), "+l"(bd));
            wg_wait<1>();
            if (lane < 2) mbar_arrive(xempty + xc);
            if (!ok2) mbar_spin(x2, p2);
            if (!okw) mbar_spin(w2, pw);
            TR(leader, (uw ? 86 : 20) + 2 * i)
        }
        wg_wait<0>();
        reg_fence(acc);
        if (lane < 2) mbar_arrive(xempty + xp);
        if (lane == 0) mbar_arrive(wempty + (9 & 7) * 8);
        TS(leader, 38 + uw)
        float a0 = 0.f, b0 = 0.f, a1 = 0.f, b1 = 0.f;
        uint32_t x2[20];
#pragma unroll
        for (int i = 0; i < 5; i++) {
            uint32_t* p = &x2[4 * i];
#pragma unroll
            for (int e = 0; e < 4; e++) p[e] = pack2(acc[8 * i + 2 * e], acc[8 * i + 2 * e + 1]);
#pragma unroll
            for (int e = 0; e < 4; e++) p[e] = lop3<0xB8>(p[e], (((wt >> 3) ^ (wt << 2)) & 7) == e, ep);
            stg128(&g_x2f[(tile * 40 + (i < 4 ? 4 * j + i : 32 + j)) * 128 + wt], p[0], p[1], p[2], p[3]);
#pragma unroll
            for (int e = 0; e < 4; e += 2) {
                const float u0 = blo(p[e]), u1 = bhi(p[e]), v0 = blo(p[e + 1]), v1 = bhi(p[e + 1]);
                a0 += u0 + u1; b0 = fmaf(u0, u0, fmaf(u1, u1, b0));
                a1 += v0 + v1; b1 = fmaf(v0, v0, fmaf(v1, v1, b1));
            }
        }
#pragma unroll
        for (int o = 1; o < 4; o *= 2) {
            a0 += __shfl_xor_sync(~0u, a0, o); b0 += __shfl_xor_sync(~0u, b0, o);
            a1 += __shfl_xor_sync(~0u, a1, o); b1 += __shfl_xor_sync(~0u, b1, o);
        }
        if (t < 2) stg64(&g_stats[(tile * 8 + j) * 64 + 16 * wq + g + 8 * t], tag(__float_as_uint(t ? a1 : a0), ep), __float_as_uint(t ? b1 : b0));
        signal_cnt(&g_cnt.g2[tile * 32], lane, 1, true);
        TS(leader, 40 + uw)
#pragma unroll
        for (int i = 0; i < 10; i++) {
            const float2 c = lds64f(sb + M_GB + (8 * i + 2 * t) * 4), e = lds64f(sb + M_CI + (8 * i + 2 * t) * 4);
#pragma unroll
            for (int h = 0; h < 2; h++)
                res[2 * i + h] = fma2(pack2(c.x, c.y), x2[2 * i + h], pack2(e.x * blo(res[2 * i + h]), e.y * bhi(res[2 * i + h])));
        }
#pragma unroll
        for (int i = 0; i < 20; i++) asm volatile("" : "+r"(res[i]));
    }
    float acc0[64], acc1[44];
    float2 q[4];
    {
        uint4 f0, f1, f2, f3;
        auto xseq = [&](int kb) { return ring_pos(uw, kb, XLEAD) & 7; };
        auto step = [&](const uint4& f, uint64_t bd) {
            wg_fence();
            wgmma_rs128(acc0, f.x, f.y, f.z, f.w, bd, 1);
            wgmma_rs88(acc1, f.x, f.y, f.z, f.w, bd + 512, 1);
            wg_commit();
        };
        const uint32_t xa = sb + OFF_XR + wt * 16;
        const float2* const gs = &g_stats[(tile * 8 + 2 * t) * 64 + 16 * wq + g];
        zero(acc0); zero(acc1);
        uint32_t xs = xseq(0);
        xwait(20);
        TS(leader, 42 + uw)
        f0 = lds128(xa + xs * 8192); f1 = lds128(xa + xs * 8192 + 2048);
#pragma unroll
        for (int i = 0; i < 4; i++) q[i] = ld_stat(gs + (i & 1) * 64 + 8 * (i >> 1));
        mbar_spin(wfull + (10 & 7) * 8, (10 >> 3) & 1);
#pragma unroll 1
        for (int kb = 0; kb < 10; kb++) {
            const uint32_t wn = 10 + 2 * kb;
            const uint64_t bd = dz + (((dsb + OFF_W + (wn & 7) * 16384) >> 4) | (256u << 16));
            step(f0, bd);
            wg_wait<1>();
            if (kb && lane == 0) mbar_arrive(wempty + ((wn - 1) & 7) * 8);
            f2 = lds128(xa + xs * 8192 + 4096); f3 = lds128(xa + xs * 8192 + 6144);
            const bool w1 = mbar_test(wfull + ((wn + 1) & 7) * 8, (wn >> 3) & 1), x1 = mbar_test(xfull + ((21 + kb) & 7) * 8, ((21 + kb) >> 3) & 1);
            step(f1, bd + 128);
            if (!w1) mbar_spin(wfull + ((wn + 1) & 7) * 8, (wn >> 3) & 1);
            step(f2, bd + 1024);
            if (lane < 2) mbar_arrive_after(xempty + xs * 8, f2.x, f3.x, nil);
            wg_wait<1>();
            if (lane == 0) mbar_arrive(wempty + (wn & 7) * 8);
            xs = xseq(kb + 1);
            if (x1) { f0 = lds128(xa + xs * 8192); f1 = lds128(xa + xs * 8192 + 2048); }
            const bool w2 = mbar_test(wfull + ((wn + 2) & 7) * 8, ((wn + 2) >> 3) & 1);
            step(f3, bd + 1152);
            if (kb < 9 && !x1) { xwait(21 + kb); f0 = lds128(xa + xs * 8192); f1 = lds128(xa + xs * 8192 + 2048); }
            if (!w2) mbar_spin(wfull + ((wn + 2) & 7) * 8, ((wn + 2) >> 3) & 1);
            if (kb == 4) {
                uint32_t it = 0;
                while (__any_sync(~0u, ((__float_as_uint(q[0].x) ^ ep) | (__float_as_uint(q[1].x) ^ ep) | (__float_as_uint(q[2].x) ^ ep) | (__float_as_uint(q[3].x) ^ ep)) & 1)) {
#pragma unroll
                    for (int i = 0; i < 4; i++) q[i] = ld_stat(gs + (i & 1) * 64 + 8 * (i >> 1));
                    SPIN_CHECK(49)
                }
                float a0 = q[0].x + q[1].x, b0 = q[0].y + q[1].y, a1 = q[2].x + q[3].x, b1 = q[2].y + q[3].y;
#pragma unroll
                for (int o = 1; o < 4; o *= 2) {
                    a0 += __shfl_xor_sync(~0u, a0, o); b0 += __shfl_xor_sync(~0u, b0, o);
                    a1 += __shfl_xor_sync(~0u, a1, o); b1 += __shfl_xor_sync(~0u, b1, o);
                }
                a0 *= 1.f / D_; a1 *= 1.f / D_;
                const float r0 = 0.5f * rsqrtf(fmaxf(b0 * (1.f / D_) - a0 * a0, 0.f) + 1e-5f), r1 = 0.5f * rsqrtf(fmaxf(b1 * (1.f / D_) - a1 * a1, 0.f) + 1e-5f);
                const uint32_t sel = t == 0 ? 0x1010 : t == 1 ? 0x4432 : 0x4444;
                q[0] = make_float2(r0, r1);
                q[1] = make_float2(__uint_as_float(__byte_perm(split2(-a0), 0, sel)), __uint_as_float(__byte_perm(split2(-a1), 0, sel)));
            }
            if (kb == 6) {
#pragma unroll
                for (int i = 0; i < 5; i++) stg128(&g_x1f[(tile * 8 + j) * 640 + i * 128 + wt], res[4 * i], res[4 * i + 1], res[4 * i + 2], res[4 * i + 3]);
            }
            if (kb == 8) asm volatile("fence.proxy.async.global;" ::: "memory");
            TR(leader, 10 * uw + kb)
        }
        const uint64_t fd = ((uint64_t)8 << 32) | ((dsb + OFF_W + 6 * 16384) >> 4);
        wg_fence();
        wgmma_rs128k(acc0, __float_as_uint(q[1].x), __float_as_uint(q[1].y), 0, 0, fd, 1);
        wgmma_rs88k(acc1, __float_as_uint(q[1].x), __float_as_uint(q[1].y), 0, 0, fd + 128, 1);
        wg_commit();
        if (lane == 0) {
            mbar_arrive(bars + B_XFREE * 8);
            asm volatile("mbarrier.arrive.shared::cluster.b64 _, [%0];" ::"r"(peer_addr(bars + B_XFREE * 8)) : "memory");
        }
    }
    const uint32_t recv = sb + recv_off(uw) + wt * 16;
    uint32_t ha[48] = {}, hb[48], hx[12];
    uint64_t wb = dz + (((dsb + OFF_W) >> 4) | (512u << 16));
    auto wdesc = [&](int n) { return wb + (n & 7) * 1024; };
    auto wwait = [&](int n) { mbar_spin(wfull + (n & 7) * 8, (n >> 3) & 1); };
    auto wfree = [&](int n) { if (lane == 0) mbar_arrive(wempty + (n & 7) * 8); };
    auto fresh = [&]() { wb += pp.nil; asm volatile("" : "+l"(wb)); };
    uint32_t pk[32];
    {
        float P0[64];
        const float r0 = q[0].x, r1 = q[0].y;
        const uint32_t ra = peer_addr(recv), rb = peer_addr(bars + (B_RECV + 4 * uw) * 8);
        auto conv32 = [&](const float* v, int b) {
#pragma unroll
            for (int i = 0; i < 4; i++) {
                ha[8 * b + 2 * i] = pack2(gelu2(v[4 * i] * r0), gelu2(v[4 * i + 1] * r0));
                ha[8 * b + 2 * i + 1] = pack2(gelu2(v[4 * i + 2] * r1), gelu2(v[4 * i + 3] * r1));
            }
#pragma unroll
            for (int s = 2 * b; s < 2 * b + 2; s++) st_peer(ra + s * 2048, ha[4 * s], ha[4 * s + 1], ha[4 * s + 2], ha[4 * s + 3], rb + (b >> 1) * 8);
        };
        auto fetch = [&](int k) {
            mbar_spin(bars + (B_RECV + 4 * uw + k) * 8, 0);
#pragma unroll
            for (int s = 4 * k; s < 4 * k + 4; s++) { const uint4 x = lds128(recv + s * 2048); hb[4 * s] = x.x; hb[4 * s + 1] = x.y; hb[4 * s + 2] = x.z; hb[4 * s + 3] = x.w; }
        };
        auto stage = [&](int n, const uint32_t* a, int steps, int sc) {
            wwait(n);
            wg_fence();
#pragma unroll
            for (int s = 0; s < steps; s++) wgmma_rs128(P0, a[4 * s], a[4 * s + 1], a[4 * s + 2], a[4 * s + 3], wdesc(n) + s * 128, sc || s);
            wg_commit();
        };
        wg_wait<0>();
        reg_fence(acc0); reg_fence(acc1);
        wfree(29); wfree(30);
        TS(leader, 44 + uw)
        uint32_t hr[6];
#pragma unroll
        for (int i = 0; i < 6; i++) {
            const float r = (i & 1) ? r1 : r0;
            hr[i] = pack2(gelu2(acc1[32 + 2 * i] * r), gelu2(acc1[33 + 2 * i] * r));
        }
        if (uw) mbar_spin(bars + B_XFREE * 8, 0);
        st_peer(ra + 24576, hr[0], hr[1], hr[2], hr[3], rb + 24);
        asm volatile("st.async.shared::cluster.mbarrier::complete_tx::bytes.v2.b32 [%0], {%1, %2}, [%3];" ::"r"(ra + 26624 - wt * 8), "r"(hr[4]), "r"(hr[5]), "r"(rb + 24) : "memory");
        conv32(&acc1[0], 4);
        conv32(&acc1[16], 5);
        TS(leader, 46 + uw)
        stage(31, &ha[32], 4, 0);
#pragma unroll
        for (int b = 0; b < 4; b++) {
            conv32(&acc0[16 * b], b);
            if (b == 3) {
                fetch(2);
                mbar_spin(bars + (B_RECV + 4 * uw + 3) * 8, 0);
                const uint4 x = lds128(recv + 24576);
                const uint2 y = lds64(recv + 26624 - wt * 8);
                const uint32_t hp[6] = {x.x, x.y, x.z, x.w, y.x, y.y};
#pragma unroll
                for (int i = 0; i < 6; i++) { hx[i] = (j & 1) ? hp[i] : hr[i]; hx[6 + i] = (j & 1) ? hr[i] : hp[i]; }
            }
            if (!(b & 1)) wwait(32 + (b >> 1));
            wg_fence();
#pragma unroll
            for (int s = 0; s < 2; s++) wgmma_rs128(P0, ha[8 * b + 4 * s], ha[8 * b + 4 * s + 1], ha[8 * b + 4 * s + 2], ha[8 * b + 4 * s + 3], wdesc(32 + (b >> 1)) + (2 * (b & 1) + s) * 128, 1);
            wg_commit();
            if (!(b & 1)) { wg_wait<1>(); wfree(31 + (b >> 1)); }
        }
        TR(leader, 64 + 10 * uw)
        fresh();
        stage(34, &hb[32], 4, 1); wg_wait<1>(); wfree(33);
        fetch(0);
        stage(35, hx, 3, 1); wg_wait<1>(); wfree(34);
        fetch(1);
        stage(36, &hb[0], 4, 1); wg_wait<1>(); wfree(35);
        stage(37, &hb[16], 4, 1); wg_wait<1>(); wfree(36);
        wg_wait<0>();
        reg_fence(P0);
        pack_part<64>(pk, P0, ep);
        uint32_t all = 0;
#pragma unroll
        for (int i = 0; i < 32; i++) all |= pk[i];
        if (lane == 0) mbar_arrive_after(wempty + (37 & 7) * 8, all, 0, nil);
        TR(leader, 65 + 10 * uw)
    }
    {
        uint4* const dst = g_part + (size_t)(tile * 8 + j) * 5120 + wt;
        const uint4* const src = g_part + (size_t)tile * 40960 + j * 512 + wt;
        float F[2][32];
        float2 gb[8];
        uint4 base[4], u1[4], u2[4], u3[4];
#pragma unroll
        for (int c = 2; c < 5; c++) {
            float (&P)[32] = F[c & 1];
            fresh();
#pragma unroll
            for (int s = 0; s < 27; s++) {
                const int e = s < 8 ? 0 : s < 15 ? 1 : s < 23 ? 2 : 3, o = s - (e == 0 ? 0 : e == 1 ? 8 : e == 2 ? 15 : 23), n = 30 + 4 * c + e;
                const uint32_t* a = s < 12 ? &ha[4 * s] : s < 15 ? &hx[4 * (s - 12)] : &hb[4 * (s - 15)];
                if (o == 0) wwait(n);
                if (o == 0 || s == 1) wg_fence();
                wgmma_rs64(P, a[0], a[1], a[2], a[3], wdesc(n) + o * 128, s);
                if (o == 0) { wg_commit(); wg_wait<1>(); if (c > 2 || s) wfree(n - 1); }
                if (s == 0 && c > 2) { reg_fence(F[~c & 1]); pack_part<32>(pk, F[~c & 1], ep); }
                if (c == 2 && s % 3 == 0 && s < 24) st_part(dst + g4_block(s / 12, j) * 512 + (s / 3 & 3) * 128, &pk[4 * (s / 3)]);
                if (c == 3 && s % 4 == 1 && s < 16) st_part(dst + g4_block(2, j) * 512 + s / 4 * 128, &pk[4 * (s / 4)]);
                if (c == 4 && s % ST3 == 0 && s < 4 * ST3) st_part(dst + g4_block(3, j) * 512 + s / ST3 * 128, &pk[4 * (s / ST3)]);
                if (c == 4 && s >= 4 && s < 8) base[s - 4] = ldcg128(&g_x1f[(tile * 8 + j) * 640 + (s - 4) * 128 + wt]);
                if (c == 4 && s >= 19 && s < 23) { gb[2 * s - 38] = lds64f(sb + M_GB + (16 * (s - 19) + 2 * t) * 4); gb[2 * s - 37] = lds64f(sb + M_GB + (16 * (s - 19) + 8 + 2 * t) * 4); }
                if (c == 4 && s >= 8 && s < 12) u1[s - 8] = ld_part(src + (j ^ 6) * 5120 + (s - 8) * 128);
                if (c == 4 && s >= 15 && s < 19) u2[s - 15] = ld_part(src + (j ^ 4) * 5120 + (s - 15) * 128);
                if (c == 4 && s >= LD3 && s < LD3 + 4) u3[s - LD3] = ld_part(src + (j ^ 2) * 5120 + (s - LD3) * 128);
                if (s == 7 || s == 14 || s == 22 || s == 26) wg_commit();
                if (c == 4) { TR(leader && s == 7, 68 + 10 * uw) TR(leader && s == 14, 69 + 10 * uw) TR(leader && s == 22, 70 + 10 * uw) }
            }
            if (c == 2 && lane == 0) mbar_arrive(bars + (B_RING + uw) * 8);
            TR(leader, 64 + c + (c == 4 ? 3 : 0) + 10 * uw)
        }
        float (&O)[32] = F[0];
        float v[32];
        fix4(u1, src + (j ^ 6) * 5120, ep, 4);
        fix4(u2, src + (j ^ 4) * 5120, ep, 5);
        TR(leader, 72 + 10 * uw)
        fix4(u3, src + (j ^ 2) * 5120, ep, 6);
        TR(leader, 73 + 10 * uw)
#pragma unroll
        for (int i = 0; i < 4; i++) { unpack8(&v[8 * i], add2(add2(u1[i], u2[i]), u3[i])); base16(&v[8 * i], base[i], gb[2 * i], gb[2 * i + 1]); }
        reg_fence(v);
        TS(leader, 50 + uw)
        wg_wait<0>();
        reg_fence(O);
        TS(leader, 48 + uw)
        const uint32_t so = sb + recv_off(uw) + wq * 2048;
#pragma unroll
        for (int i = 0; i < 4; i++) {
            float* o = &O[8 * i];
#pragma unroll
            for (int e = 0; e < 8; e++) o[e] = fmaf((e & 1) ? gb[2 * i + (e >> 2)].y : gb[2 * i + (e >> 2)].x, o[e], v[8 * i + e]);
            stsm4(so + (lane & 15) * 128 + (((2 * i + (lane >> 4)) ^ (lane & 7)) << 4), pack2(o[0], o[1]), pack2(o[2], o[3]), pack2(o[4], o[5]), pack2(o[6], o[7]));
        }
        __syncwarp();
#pragma unroll
        for (int i = 0; i < 4; i++) {
            const int row = (lane >> 3) + 4 * i;
            stg128(out + (size_t)(row0 + row) * D_ + 64 * j + 8 * (lane & 7), lds128(so + row * 128 + (((lane & 7) ^ (row & 7)) << 4)));
        }
        warp_arrive(bars + B_OWN * 8);
    }
}

typedef CUresult (*EncFn)(CUtensorMap*, CUtensorMapDataType, cuuint32_t, void*, const cuuint64_t*, const cuuint64_t*, const cuuint32_t*,
                          const cuuint32_t*, CUtensorMapInterleave, CUtensorMapSwizzle, CUtensorMapL2promotion, CUtensorMapFloatOOBfill);

static void enc(EncFn fn, CUtensorMap* m, void* p, int rank, const cuuint64_t* dims, const cuuint64_t* strides, const cuuint32_t* box) {
    const CUtensorMapSwizzle sw = box[0] > 64 ? CU_TENSOR_MAP_SWIZZLE_NONE : CU_TENSOR_MAP_SWIZZLE_128B;
    cuuint32_t es[5] = {1, 1, 1, 1, 1};
    CUresult r = fn(m, CU_TENSOR_MAP_DATA_TYPE_BFLOAT16, rank, p, dims, strides, box, es, CU_TENSOR_MAP_INTERLEAVE_NONE, sw,
                    CU_TENSOR_MAP_L2_PROMOTION_L2_128B, CU_TENSOR_MAP_FLOAT_OOB_FILL_NONE);
    (void)r;
}
static void enc2(EncFn fn, CUtensorMap* m, void* p, uint64_t cols, uint64_t rows, uint32_t bc, uint32_t br) {
    cuuint64_t dims[2] = {cols, rows}, st[1] = {cols * 2};
    cuuint32_t box[2] = {bc, br};
    enc(fn, m, p, 2, dims, st, box);
}

extern "C" void kernel_launch(void* const* d_in, const int* in_sizes, int n_in, void* d_out, int out_size) {
    static Maps mp;
    static Ptrs pp;
    static void* cached[13];
    bool same = true;
    for (int i = 0; i < 13; i++) same = same && (cached[i] == d_in[i]);
    if (!same) {
        void* fnp = nullptr;
        cudaDriverEntryPointQueryResult qr;
        cudaGetDriverEntryPoint("cuTensorMapEncodeTiled", &fnp, cudaEnableDefault, &qr);
        EncFn fn = (EncFn)fnp;
        cudaGetSymbolAddress((void**)&pp.s, g_scratch);
        void *x1T = g_x1T, *t = g_t;
        cuuint64_t dq[3] = {64, S_, 10}, sq[2] = {D_ * 2, 128};
        cuuint32_t bq[3] = {64, 16, 10};
        enc(fn, &mp.q, d_in[0], 3, dq, sq, bq);
        enc2(fn, &mp.k, d_in[1], D_, S_, 80, 67); enc2(fn, &mp.v, d_in[2], D_, S_, 80, 64);
        enc2(fn, &mp.qT, g_qT, 16 * D_, 128, 80, 128);
        enc2(fn, &mp.x1_ld, x1T, S_, D_, 64, 64); enc2(fn, &mp.t_ld, (bf16*)t + 2 * D_, D_, S_, 64, 64);
        enc2(fn, &mp.w1, d_in[7], D_, D_, 64, 64); enc2(fn, &mp.w1h, d_in[7], D_, D_, 64, 160); enc2(fn, &mp.w3h, d_in[9], F_, D_, 64, 160);
        enc2(fn, &mp.wmod, d_in[12], 6 * D_, D_, 64, 160);
        const cuuint64_t R = D_ * 2;
        cuuint64_t da[5] = {D_, 2, 4, 4, 16}, sa[4] = {R, 8 * R, 2 * R, 32 * R}, db[5] = {D_, 2, 2, 4, 8}, sb[4] = {R, 8 * R, 2 * R, 16 * R};
        cuuint32_t ba[5] = {64, 2, 4, 4, 4}, bb[5] = {64, 2, 2, 4, 8};
        enc(fn, &mp.w2a, d_in[8], 5, da, sa, ba); enc(fn, &mp.w2b, (bf16*)d_in[8] + 512 * D_, 5, db, sb, bb);
        cuuint64_t dw[3] = {64, D_, 27}, sw[2] = {F_ * 2, 128};
        cuuint32_t bw[3] = {64, 32, 3};
        enc(fn, &mp.w3a, d_in[9], 3, dw, sw, bw);
        enc2(fn, &mp.w3b, d_in[9], F_, D_, 24, 32);
        enc2(fn, &mp.w4[0], d_in[10], D_, F_, 64, 64); enc2(fn, &mp.w4[1], d_in[10], D_, F_, 64, 48);
        pp.q = (const bf16*)d_in[0]; pp.w_mod = (const bf16*)d_in[12]; pp.shift_k = (const bf16*)d_in[3];
        pp.ssm_k = (const bf16*)d_in[4]; pp.ssm_D = (const bf16*)d_in[5]; pp.w1 = (const bf16*)d_in[7]; pp.w2 = (const bf16*)d_in[8];
        pp.w4 = (const bf16*)d_in[10]; pp.c = (const bf16*)d_in[11];
        cudaFuncSetAttribute(fused_kernel, cudaFuncAttributeMaxDynamicSharedMemorySize, SMEM_BYTES);
        for (int i = 0; i < 13; i++) cached[i] = d_in[i];
    }
    cudaLaunchConfig_t cfg = {};
    cfg.gridDim = dim3(NCTA); cfg.blockDim = dim3(NTHR); cfg.dynamicSmemBytes = SMEM_BYTES; cfg.stream = cudaStreamPerThread;
    cudaLaunchAttribute at[1];
    at[0].id = cudaLaunchAttributeClusterDimension; at[0].val.clusterDim.x = 2; at[0].val.clusterDim.y = 1; at[0].val.clusterDim.z = 1;
    cfg.attrs = at; cfg.numAttrs = 1;
    cudaLaunchKernelEx(&cfg, fused_kernel, pp, (bf16*)d_out, mp);
}
```

```cpp
#include <cuda_runtime.h>
#include <cuda_bf16.h>
#include <cuda.h>
#include <stdint.h>
#include <stdio.h>

typedef __nv_bfloat16 bf16;

constexpr int S_ = 2048, D_ = 640, F_ = 1728;
constexpr int NCTA = 132, NTHR = 512;

constexpr int TAB_BYTES = 9216, VEC_BYTES = 1440;
struct Counters {
    unsigned kv[8 * 32];
    unsigned q[4 * 32], x[4 * 32];
    unsigned wr[32], tab[32], uv[32], cs[32], cs2[32], done[32];
    unsigned g1[32 * 32];
    unsigned g2[32 * 32];
};
struct Scratch {
    Counters cnt;
    unsigned epoch;
    alignas(1024) bf16 qst[2 * S_];
    alignas(1024) uint4 wr[2 * 8 * 10 * 128];
    alignas(1024) uint2 mod[2 * 6 * D_];
    alignas(1024) uint4 tab[(TAB_BYTES + 8 * VEC_BYTES) / 16];
    alignas(1024) float uv[2 * 3 * D_];
    alignas(1024) float cs3[2 * 1920];
    alignas(1024) uint4 cs3b[8 * 216];
    alignas(1024) float2 stats[32 * 8 * 64];
    alignas(1024) bf16 kvT[D_ * S_];
    alignas(1024) bf16 qT[D_ * S_];
    alignas(1024) bf16 x1T[D_ * S_];
    alignas(1024) bf16 t[(S_ + 4) * D_];
    alignas(1024) uint4 x2f[32 * 40 * 128];
    alignas(1024) uint4 x1f[32 * 8 * 5 * 128];
    alignas(1024) uint4 part[32 * 8 * 10 * 4 * 128];
};
__device__ Scratch g_scratch;
#define g_kvT (pp.s->kvT)
#define g_qT (pp.s->qT)
#define g_x1T (pp.s->x1T)
#define g_qst (pp.s->qst)
#define g_t (pp.s->t)
#define g_x2f (pp.s->x2f)
#define g_x1f (pp.s->x1f)
#define g_part (pp.s->part)
#define g_wr (pp.s->wr)
#define g_mod (pp.s->mod)
#define g_tab (pp.s->tab)
#define g_uv (pp.s->uv)
#define g_cs3 (pp.s->cs3)
#define g_cs3b (pp.s->cs3b)
#define g_stats (pp.s->stats)
#define g_cnt (pp.s->cnt)
#define g_epoch (pp.s->epoch)

struct Maps {
    CUtensorMap k, v, q;
    CUtensorMap qT;
    CUtensorMap x[3];
    CUtensorMap w1, w1h, w3h, wmod;
    CUtensorMap w2a, w2b;
    CUtensorMap w3a, w3b;
    CUtensorMap w4[2];
};

struct Ptrs {
    Scratch* s;
    uint64_t nil;
    const bf16 *q, *w_mod, *shift_k, *ssm_k, *ssm_D, *w1, *w2, *w4, *c;
};

constexpr int OFF_W = 0;
constexpr int OFF_XR = 131072;
constexpr int OFF_REM = 196608;
constexpr int OFF_TAB = OFF_REM + 5 * 4096;
constexpr int OFF_ROW = OFF_TAB + 4608;
constexpr int OFF_F1 = OFF_ROW + 4096;
constexpr int RECV_BYTES = 30720;
constexpr int OFF_M = OFF_REM + RECV_BYTES;
constexpr int OFF_OUT = OFF_XR + 32768;
static_assert(OFF_F1 + 1280 <= OFF_M, "G1 map");
constexpr int OFF_ST = 0;
constexpr int OFF_SSM = 20480;
constexpr int OFF_WM = 0;
constexpr int OFF_QIN = 49152;
constexpr int OFF_QT = 49152;
constexpr int OFF_Z = OFF_TAB;
constexpr int OFF_RING = 80896;
constexpr int OFF_KIN = OFF_RING, OFF_VIN = OFF_KIN + 2 * 10752;
constexpr int OFF_CH = OFF_RING + 3 * 16384, CH_BYTES = 13312, OFF_P = 5120;
static_assert(OFF_RING + 5 * 16384 <= OFF_CH + 3 * CH_BYTES && OFF_CH + 5 * CH_BYTES <= OFF_REM, "the last two rings replace channels 0..2");
constexpr int M_BAR = OFF_M;
constexpr int M_F1 = OFF_M + 800;
constexpr int M_GB = M_F1 + 1280, M_C = M_GB + 320, M_SB = M_C + 320, M_CI = M_SB + 320;
constexpr int M_KS = M_CI + 320;
constexpr int M_AB = M_KS + 160;
constexpr int M_EP = M_AB + 80;
constexpr int M_SINK = M_EP + 16;
constexpr int M_NUL = M_SINK + 16;
constexpr int M_TS = M_NUL + 128;
constexpr int SMEM_BYTES = M_TS;
static_assert(SMEM_BYTES <= 232448, "smem");

enum { B_WFULL = 0, B_WEMPTY = 8, B_XEMPTY = 16, B_XFULL = 24  ,
       B_RAW = 40, B_QIN = 41, B_SSM = 42, B_VEC = 43, B_VEC3 = 44, B_WM = 45, B_TAB = 46, B_QRDY = 47,
       B_MODR = 48, B_GATE = 49, B_RETRY = 55, B_RAW2 = 59, B_RAW3 = 60, B_SUMS = 62, B_RECV = 64  ,
       B_SIG = 72, B_RING = 74  ,
       B_LAND = 80,
       B_XS = 88, B_R1 = 89, B_BK = 90, B_KVS = 91,
       B_XFREE = 92, B_OWN = 93,
       B_IN = 94, B_AGAIN = 96 };
#define T_KVB 1800
#define T_SSM 3300
#define PF_T0 4800
#define PF_DT 420
#define Q_UNROLL 5
#define HELP_T 1000
#define ST3 1
#define LD3 23
#define GATE_W2 7
#define GATE_W3 27
#define GATE_W3B 37
#define W3_N2 13
#define LEAD1 4
#define XLEAD 3

#define SPIN_FAIL(code) __trap();
#define SPIN_LIMIT (1u << 22)
#define STALE(c)
#define STALE1(c)
#define TS(c, i)
#define TG(c, i)
#define TR(c, i)
#define TR2(c, i)
#define TR4(c, i)
#define TR5(c, i)
#define SPIN_CHECK(code) asm volatile("" ::"r"(it));
#define RARE(x) __builtin_expect((x) != 0, 0)
__device__ __forceinline__ uint32_t s2u(const void* p) { return (uint32_t)__cvta_generic_to_shared(p); }
__device__ __forceinline__ bool elect() {
    uint32_t p;
    asm volatile("{.reg .pred P; elect.sync _|P, 0xffffffff; selp.u32 %0,1,0,P;}" : "=r"(p));
    return p != 0;
}
__device__ __forceinline__ void mbar_init(uint32_t b, uint32_t n) { asm volatile("mbarrier.init.shared.b64 [%0], %1;" ::"r"(b), "r"(n)); }
__device__ __forceinline__ void mbar_expect(uint32_t b, uint32_t bytes) {
    asm volatile("mbarrier.arrive.expect_tx.shared.b64 _, [%0], %1;" ::"r"(b), "r"(bytes) : "memory");
}
__device__ __forceinline__ void mbar_arrive(uint32_t b) { asm volatile("mbarrier.arrive.shared.b64 _, [%0];" ::"r"(b) : "memory"); }
__device__ __forceinline__ void mbar_arrive_after(uint32_t b, uint32_t v0, uint32_t v1, uint32_t nil) { mbar_arrive(b + ((v0 | v1) & nil)); }
__device__ __forceinline__ void warp_arrive(uint32_t b) { __syncwarp(); if (elect()) mbar_arrive(b); }
__device__ __forceinline__ uint32_t peer_addr(uint32_t a) {
    uint32_t r;
    asm("{\n.reg .b32 q;\nmov.u32 q, %%cluster_ctarank;\nxor.b32 q, q, 1;\nmapa.shared::cluster.u32 %0, %1, q;\n}" : "=r"(r) : "r"(a));
    return r;
}
__device__ __forceinline__ bool mbar_test(uint32_t b, uint32_t parity) {
    uint32_t ok;
    asm volatile("{.reg .pred P; mbarrier.test_wait.parity.shared.b64 P, [%1], %2; selp.u32 %0,1,0,P;}" : "=r"(ok) : "r"(b), "r"(parity) : "memory");
    return ok != 0;
}
__device__ __forceinline__ bool mbar_try(uint32_t b, uint32_t parity) {
    uint32_t ok;
    asm volatile("{.reg .pred P; mbarrier.try_wait.parity.shared.b64 P, [%1], %2; selp.u32 %0,1,0,P;}" : "=r"(ok) : "r"(b), "r"(parity) : "memory");
    return ok != 0;
}
__device__ __forceinline__ void mbar_wait(uint32_t b, uint32_t parity) {
    if (__all_sync(0xffffffffu, mbar_try(b, parity))) return;
    uint32_t it = 0;
    while (!__all_sync(0xffffffffu, mbar_try(b, parity))) { if (++it > SPIN_LIMIT) SPIN_FAIL((b >> 3) & 63) }
}
__device__ __forceinline__ void mbar_spin(uint32_t b, uint32_t parity) {
    asm volatile("{\n.reg .pred P;\nSPIN:\nmbarrier.try_wait.parity.shared.b64 P, [%0], %1;\n@!P bra.uni SPIN;\n}" ::"r"(b), "r"(parity) : "memory");
}
__device__ __forceinline__ void bar_sync(int id, int n) { asm volatile("bar.sync %0, %1;" ::"r"(id), "r"(n) : "memory"); }
__device__ __forceinline__ void fence_async_smem() { asm volatile("fence.proxy.async.shared::cta;" ::: "memory"); }
__device__ __forceinline__ void wait_cnt(const unsigned* p, unsigned target, bool tagged = false) {
    unsigned v, it = 0;
    do {
        asm volatile("ld.relaxed.gpu.global.u32 %0, [%1];" : "=r"(v) : "l"(p) : "memory");
        SPIN_CHECK(60 + (target & 3))
    } while (!__all_sync(0xffffffffu, v >= target));
    if (!tagged) asm volatile("fence.acquire.gpu;" ::: "memory");
}
__device__ __forceinline__ void signal_cnt(unsigned* p, int lane, int n, bool tagged = false) {
    if (tagged) asm volatile("{\n.reg .pred P;\nsetp.lt.s32 P, %1, %2;\n@P red.relaxed.gpu.global.add.u32 [%0], %3;\n}" ::"l"(p), "r"(lane), "r"(n), "r"(1) : "memory");
    else if (lane < n) asm volatile("red.release.gpu.global.add.u32 [%0], 1;" ::"l"(p) : "memory");
    __syncwarp();
}
__device__ __forceinline__ uint32_t clock_lo() { uint32_t c; asm volatile("mov.u32 %0, %%clock;" : "=r"(c)); return c; }
__device__ __forceinline__ void wait_clock(uint32_t c0, uint32_t t) {
    asm volatile("{\n.reg .pred P;\n.reg .b32 c;\nWAIT:\nnanosleep.u32 20;\nmov.u32 c, %%clock;\nsub.u32 c, c, %0;\nsetp.lt.u32 P, c, %1;\n@P bra.uni WAIT;\n}" ::"r"(c0), "r"(t) : "memory");
}
__device__ __forceinline__ void tma_ld2(uint32_t dst, const CUtensorMap* m, int c0, int c1, uint32_t bar) {
    asm volatile("cp.async.bulk.tensor.2d.shared::cluster.global.mbarrier::complete_tx::bytes [%0], [%1, {%3, %4}], [%2];"
                 ::"r"(dst), "l"(m), "r"(bar), "r"(c0), "r"(c1) : "memory");
}
__device__ __forceinline__ void tma_ld3(uint32_t dst, const CUtensorMap* m, int c0, int c1, int c2, uint32_t bar) {
    asm volatile("cp.async.bulk.tensor.3d.shared::cluster.global.mbarrier::complete_tx::bytes [%0], [%1, {%3, %4, %5}], [%2];"
                 ::"r"(dst), "l"(m), "r"(bar), "r"(c0), "r"(c1), "r"(c2) : "memory");
}
__device__ __forceinline__ void tma_ld5(uint32_t dst, const CUtensorMap* m, int col, int blk, uint32_t bar) {
    asm volatile("cp.async.bulk.tensor.5d.shared::cluster.global.mbarrier::complete_tx::bytes [%0], [%1, {%3, %4, %4, %4, %5}], [%2];"
                 ::"r"(dst), "l"(m), "r"(bar), "r"(col), "r"(0), "r"(blk) : "memory");
}
__device__ __forceinline__ void bulk_ld(uint32_t dst, const void* src, uint32_t bytes, uint32_t bar) {
    asm volatile("cp.async.bulk.shared::cluster.global.mbarrier::complete_tx::bytes [%0], [%1], %2, [%3];" ::"r"(dst), "l"(src), "r"(bytes), "r"(bar) : "memory");
}
__device__ __forceinline__ void l2_prefetch(const void* p, uint32_t bytes) {
    asm volatile("cp.async.bulk.prefetch.L2.global [%0], %1;" ::"l"(p), "r"(bytes) : "memory");
}
__device__ __forceinline__ void wg_fence() { asm volatile("wgmma.fence.sync.aligned;" ::: "memory"); }
__device__ __forceinline__ void wg_commit() { asm volatile("wgmma.commit_group.sync.aligned;" ::: "memory"); }
template <int N> __device__ __forceinline__ void wg_wait() { asm volatile("wgmma.wait_group.sync.aligned %0;" ::"n"(N) : "memory"); }
template <int N> __device__ __forceinline__ void reg_fence(float (&d)[N]) {
#pragma unroll
    for (int i = 0; i < N; i++) asm volatile("" : "+f"(d[i])::"memory");
}
template <int N> __device__ __forceinline__ void zero(float (&d)[N]) {
#pragma unroll
    for (int i = 0; i < N; i++) asm volatile("mov.b32 %0, 0;" : "=f"(d[i]));
}
__device__ __forceinline__ uint32_t lds32(uint32_t a) { uint32_t v; asm volatile("ld.shared.b32 %0, [%1];" : "=r"(v) : "r"(a)); return v; }
__device__ __forceinline__ uint2 lds64(uint32_t a) { uint2 v; asm volatile("ld.shared.v2.b32 {%0,%1}, [%2];" : "=r"(v.x), "=r"(v.y) : "r"(a)); return v; }
__device__ __forceinline__ float2 lds64f(uint32_t a) { float2 v; asm volatile("ld.shared.v2.f32 {%0,%1}, [%2];" : "=f"(v.x), "=f"(v.y) : "r"(a)); return v; }
__device__ __forceinline__ void sts32(uint32_t a, uint32_t v) { asm volatile("st.shared.b32 [%0], %1;" ::"r"(a), "r"(v) : "memory"); }
__device__ __forceinline__ void sts64f(uint32_t a, float x, float y) { asm volatile("st.shared.v2.f32 [%0], {%1,%2};" ::"r"(a), "f"(x), "f"(y) : "memory"); }
__device__ __forceinline__ void sts128(uint32_t a, uint32_t x, uint32_t y, uint32_t z, uint32_t w) {
    asm volatile("st.shared.v4.b32 [%0], {%1,%2,%3,%4};" ::"r"(a), "r"(x), "r"(y), "r"(z), "r"(w) : "memory");
}
__device__ __forceinline__ void sts128f(uint32_t a, float x, float y, float z, float w) {
    asm volatile("st.shared.v4.f32 [%0], {%1,%2,%3,%4};" ::"r"(a), "f"(x), "f"(y), "f"(z), "f"(w) : "memory");
}
__device__ __forceinline__ uint4 lds128(uint32_t a) {
    uint4 v;
    asm volatile("ld.shared.v4.b32 {%0,%1,%2,%3}, [%4];" : "=r"(v.x), "=r"(v.y), "=r"(v.z), "=r"(v.w) : "r"(a) : "memory");
    return v;
}
__device__ __forceinline__ float4 lds128f(uint32_t a) {
    float4 v;
    asm volatile("ld.shared.v4.f32 {%0,%1,%2,%3}, [%4];" : "=f"(v.x), "=f"(v.y), "=f"(v.z), "=f"(v.w) : "r"(a) : "memory");
    return v;
}
__device__ __forceinline__ void stg128(void* p, uint32_t x, uint32_t y, uint32_t z, uint32_t w) {
    asm volatile("st.global.v4.b32 [%0], {%1,%2,%3,%4};" ::"l"(p), "r"(x), "r"(y), "r"(z), "r"(w) : "memory");
}
__device__ __forceinline__ void stg128(void* p, uint4 v) { stg128(p, v.x, v.y, v.z, v.w); }
__device__ __forceinline__ void stg128_if(void* p, uint4 v, int on) {
    asm volatile("{\n.reg .pred p;\nsetp.ne.s32 p, %5, 0;\n@p st.global.v4.b32 [%0], {%1,%2,%3,%4};\n}" ::"l"(p), "r"(v.x), "r"(v.y), "r"(v.z), "r"(v.w), "r"(on) : "memory");
}
__device__ __forceinline__ void stg64(void* p, uint32_t x, uint32_t y) { asm volatile("st.global.v2.b32 [%0], {%1,%2};" ::"l"(p), "r"(x), "r"(y) : "memory"); }
__device__ __forceinline__ void stsm4(uint32_t a, uint32_t r0, uint32_t r1, uint32_t r2, uint32_t r3) {
    asm volatile("stmatrix.sync.aligned.m8n8.x4.shared.b16 [%0], {%1,%2,%3,%4};" ::"r"(a), "r"(r0), "r"(r1), "r"(r2), "r"(r3) : "memory");
}
__device__ __forceinline__ void stsm4t(uint32_t a, uint32_t r0, uint32_t r1, uint32_t r2, uint32_t r3) {
    asm volatile("stmatrix.sync.aligned.m8n8.x4.trans.shared.b16 [%0], {%1,%2,%3,%4};" ::"r"(a), "r"(r0), "r"(r1), "r"(r2), "r"(r3) : "memory");
}
__device__ __forceinline__ void ldsm4t_if(bool p, uint32_t a, uint32_t* r) {
    asm volatile("{\n.reg .pred p;\nsetp.ne.u32 p, %5, 0;\n@p ldmatrix.sync.aligned.m8n8.x4.trans.shared.b16 {%0,%1,%2,%3}, [%4];\n}"
                 : "+r"(r[0]), "+r"(r[1]), "+r"(r[2]), "+r"(r[3]) : "r"(a), "r"((uint32_t)p) : "memory");
}
__device__ __forceinline__ void ldsm4t(uint32_t a, uint32_t& r0, uint32_t& r1, uint32_t& r2, uint32_t& r3) {
    asm volatile("ldmatrix.sync.aligned.m8n8.x4.trans.shared.b16 {%0,%1,%2,%3}, [%4];" : "=r"(r0), "=r"(r1), "=r"(r2), "=r"(r3) : "r"(a) : "memory");
}
__device__ __forceinline__ uint32_t pack2(float lo, float hi) {
    uint32_t r;
    asm("cvt.rn.bf16x2.f32 %0, %1, %2;" : "=r"(r) : "f"(hi), "f"(lo));
    return r;
}
__device__ __forceinline__ uint32_t mul2(uint32_t a, uint32_t b) { uint32_t r; asm("mul.rn.bf16x2 %0, %1, %2;" : "=r"(r) : "r"(a), "r"(b)); return r; }
__device__ __forceinline__ uint32_t fma2(uint32_t a, uint32_t b, uint32_t c) { uint32_t r; asm("fma.rn.bf16x2 %0, %1, %2, %3;" : "=r"(r) : "r"(a), "r"(b), "r"(c)); return r; }
__device__ __forceinline__ uint32_t add2(uint32_t a, uint32_t b) { uint32_t r; asm("add.rn.bf16x2 %0, %1, %2;" : "=r"(r) : "r"(a), "r"(b)); return r; }
__device__ __forceinline__ void hmma(float (&d)[4], uint32_t a0, uint32_t a1, uint32_t a2, uint32_t a3, uint32_t b0, uint32_t b1) {
    asm volatile("mma.sync.aligned.m16n8k16.row.col.f32.bf16.bf16.f32 {%0,%1,%2,%3}, {%4,%5,%6,%7}, {%8,%9}, {%0,%1,%2,%3};"
        : "+f"(d[0]), "+f"(d[1]), "+f"(d[2]), "+f"(d[3]) : "r"(a0), "r"(a1), "r"(a2), "r"(a3), "r"(b0), "r"(b1));
}
__device__ __forceinline__ float blo(uint32_t w) { return __uint_as_float(w << 16); }
__device__ __forceinline__ float bhi(uint32_t w) { return __uint_as_float(w & 0xffff0000u); }
__device__ __forceinline__ float rbf(float x) { return __bfloat162float(__float2bfloat16_rn(x)); }
__device__ __forceinline__ uint32_t ldg32(const void* p) { uint32_t v; asm volatile("ld.global.nc.b32 %0, [%1];" : "=r"(v) : "l"(p)); return v; }
__device__ __forceinline__ uint2 ldg64(const void* p) { uint2 v; asm volatile("ld.global.nc.v2.b32 {%0,%1}, [%2];" : "=r"(v.x), "=r"(v.y) : "l"(p)); return v; }
__device__ __forceinline__ uint4 ldg128(const void* p) {
    uint4 v;
    asm volatile("ld.global.nc.v4.b32 {%0,%1,%2,%3}, [%4];" : "=r"(v.x), "=r"(v.y), "=r"(v.z), "=r"(v.w) : "l"(p));
    return v;
}
__device__ __forceinline__ uint4 ldcg128(const void* p) {
    uint4 v;
    asm volatile("ld.global.cg.v4.u32 {%0,%1,%2,%3}, [%4];" : "=r"(v.x), "=r"(v.y), "=r"(v.z), "=r"(v.w) : "l"(p) : "memory");
    return v;
}
__device__ __forceinline__ float4 ldcg128f(const void* p) {
    float4 v;
    asm volatile("ld.global.cg.v4.f32 {%0,%1,%2,%3}, [%4];" : "=f"(v.x), "=f"(v.y), "=f"(v.z), "=f"(v.w) : "l"(p) : "memory");
    return v;
}
__device__ __forceinline__ float2 ldcg64f(const void* p) { float2 v; asm volatile("ld.global.cg.v2.f32 {%0,%1}, [%2];" : "=f"(v.x), "=f"(v.y) : "l"(p) : "memory"); return v; }
__device__ __forceinline__ float ldcg32f(const void* p) { float v; asm volatile("ld.global.cg.f32 %0, [%1];" : "=f"(v) : "l"(p) : "memory"); return v; }
__device__ __forceinline__ float2 ld_stat(const float2* p) {
    float2 v;
    asm volatile("{\n.reg .b64 q;\nld.relaxed.gpu.global.b64 q, [%2];\nmov.b64 {%0, %1}, q;\n}" : "=f"(v.x), "=f"(v.y) : "l"(p) : "memory");
    return v;
}
__device__ __forceinline__ uint32_t ld_cold(const unsigned* p) { uint32_t v; asm volatile("ld.relaxed.gpu.global.u32 %0, [%1];" : "=r"(v) : "l"(p) : "memory"); return v; }
__device__ __forceinline__ uint2 ld_mod(const uint2* p) {
    uint64_t v;
    asm volatile("ld.relaxed.gpu.global.b64 %0, [%1];" : "=l"(v) : "l"(p) : "memory");
    return make_uint2((uint32_t)v, (uint32_t)(v >> 32));
}
__device__ __forceinline__ float silu(float x) {
    float e, r;
    asm("ex2.approx.ftz.f32 %0, %1;" : "=f"(e) : "f"(x * -1.4426950408889634f));
    asm("rcp.approx.ftz.f32 %0, %1;" : "=f"(r) : "f"(1.f + e));
    return x * r;
}
__device__ __forceinline__ float gelu2(float h) {
    float u = h * fmaf(h * h, 8.f * 0.0356774081f, 2.f * 0.7978845608f);
    float th;
    asm("tanh.approx.f32 %0, %1;" : "=f"(th) : "f"(u));
    return fmaf(h, th, h);
}

__device__ __forceinline__ void conv_channel(float (&d)[64], uint32_t pa, uint64_t db) {
    asm volatile("{\n.reg .b32 a0, a1, a2, a3, b0, b1, b2, b3, t0, t1;\n.reg .b64 d;\nld.shared.b32 a0, [%64];\nld.shared.b32 a1, [%64+128];\nld.shared.b32 a2, [%64+-128];\nmov.b32 a3, a0;\n"
        "ld.shared.b32 t0, [%64+256];\nld.shared.b32 t1, [%64+384];\nadd.s64 d, %65, 0;\nwgmma.fence.sync.aligned;\nwgmma.mma_async.sync.aligned.m64n128k16.f32.bf16.bf16 {%0, %1, %2, %3, %4, %5, %6, %7, %8, %9, %10, %11, %12, %13, %14, %15, %16, %17, %18, %19, %20, %21, %22, %23, %24, %25, %26, %27, %28, %29, %30, %31, %32, %33, %34, %35, %36, %37, %38, %39, %40, %41, %42, %43, %44, %45, %46, %47, %48, %49, %50, %51, %52, %53, %54, %55, %56, %57, %58, %59, %60, %61, %62, %63}, {a0, a1, a2, a3}, d, 0, 1, 1, 0;\nwgmma.commit_group.sync.aligned;\nwgmma.wait_group.sync.aligned 1;\nmov.b32 b2, a1;\nmov.b32 b0, t0;\nmov.b32 b3, t0;\nmov.b32 b1, t1;\n"
        "ld.shared.b32 t0, [%64+512];\nld.shared.b32 t1, [%64+640];\nadd.s64 d, %65, 8;\nwgmma.fence.sync.aligned;\nwgmma.mma_async.sync.aligned.m64n128k16.f32.bf16.bf16 {%0, %1, %2, %3, %4, %5, %6, %7, %8, %9, %10, %11, %12, %13, %14, %15, %16, %17, %18, %19, %20, %21, %22, %23, %24, %25, %26, %27, %28, %29, %30, %31, %32, %33, %34, %35, %36, %37, %38, %39, %40, %41, %42, %43, %44, %45, %46, %47, %48, %49, %50, %51, %52, %53, %54, %55, %56, %57, %58, %59, %60, %61, %62, %63}, {b0, b1, b2, b3}, d, 1, 1, 1, 0;\nwgmma.commit_group.sync.aligned;\nwgmma.wait_group.sync.aligned 1;\nmov.b32 a2, b1;\nmov.b32 a0, t0;\nmov.b32 a3, t0;\nmov.b32 a1, t1;\n"
        "ld.shared.b32 t0, [%64+768];\nld.shared.b32 t1, [%64+896];\nadd.s64 d, %65, 16;\nwgmma.fence.sync.aligned;\nwgmma.mma_async.sync.aligned.m64n128k16.f32.bf16.bf16 {%0, %1, %2, %3, %4, %5, %6, %7, %8, %9, %10, %11, %12, %13, %14, %15, %16, %17, %18, %19, %20, %21, %22, %23, %24, %25, %26, %27, %28, %29, %30, %31, %32, %33, %34, %35, %36, %37, %38, %39, %40, %41, %42, %43, %44, %45, %46, %47, %48, %49, %50, %51, %52, %53, %54, %55, %56, %57, %58, %59, %60, %61, %62, %63}, {a0, a1, a2, a3}, d, 1, 1, 1, 0;\nwgmma.commit_group.sync.aligned;\nwgmma.wait_group.sync.aligned 1;\nmov.b32 b2, a1;\nmov.b32 b0, t0;\nmov.b32 b3, t0;\nmov.b32 b1, t1;\n"
        "ld.shared.b32 t0, [%64+1024];\nld.shared.b32 t1, [%64+1152];\nadd.s64 d, %65, 24;\nwgmma.fence.sync.aligned;\nwgmma.mma_async.sync.aligned.m64n128k16.f32.bf16.bf16 {%0, %1, %2, %3, %4, %5, %6, %7, %8, %9, %10, %11, %12, %13, %14, %15, %16, %17, %18, %19, %20, %21, %22, %23, %24, %25, %26, %27, %28, %29, %30, %31, %32, %33, %34, %35, %36, %37, %38, %39, %40, %41, %42, %43, %44, %45, %46, %47, %48, %49, %50, %51, %52, %53, %54, %55, %56, %57, %58, %59, %60, %61, %62, %63}, {b0, b1, b2, b3}, d, 1, 1, 1, 0;\nwgmma.commit_group.sync.aligned;\nwgmma.wait_group.sync.aligned 1;\nmov.b32 a2, b1;\nmov.b32 a0, t0;\nmov.b32 a3, t0;\nmov.b32 a1, t1;\n"
        "ld.shared.b32 t0, [%64+1280];\nld.shared.b32 t1, [%64+1408];\nadd.s64 d, %65, 32;\nwgmma.fence.sync.aligned;\nwgmma.mma_async.sync.aligned.m64n128k16.f32.bf16.bf16 {%0, %1, %2, %3, %4, %5, %6, %7, %8, %9, %10, %11, %12, %13, %14, %15, %16, %17, %18, %19, %20, %21, %22, %23, %24, %25, %26, %27, %28, %29, %30, %31, %32, %33, %34, %35, %36, %37, %38, %39, %40, %41, %42, %43, %44, %45, %46, %47, %48, %49, %50, %51, %52, %53, %54, %55, %56, %57, %58, %59, %60, %61, %62, %63}, {a0, a1, a2, a3}, d, 1, 1, 1, 0;\nwgmma.commit_group.sync.aligned;\nwgmma.wait_group.sync.aligned 1;\nmov.b32 b2, a1;\nmov.b32 b0, t0;\nmov.b32 b3, t0;\nmov.b32 b1, t1;\n"
        "ld.shared.b32 t0, [%64+1536];\nld.shared.b32 t1, [%64+1664];\nadd.s64 d, %65, 40;\nwgmma.fence.sync.aligned;\nwgmma.mma_async.sync.aligned.m64n128k16.f32.bf16.bf16 {%0, %1, %2, %3, %4, %5, %6, %7, %8, %9, %10, %11, %12, %13, %14, %15, %16, %17, %18, %19, %20, %21, %22, %23, %24, %25, %26, %27, %28, %29, %30, %31, %32, %33, %34, %35, %36, %37, %38, %39, %40, %41, %42, %43, %44, %45, %46, %47, %48, %49, %50, %51, %52, %53, %54, %55, %56, %57, %58, %59, %60, %61, %62, %63}, {b0, b1, b2, b3}, d, 1, 1, 1, 0;\nwgmma.commit_group.sync.aligned;\nwgmma.wait_group.sync.aligned 1;\nmov.b32 a2, b1;\nmov.b32 a0, t0;\nmov.b32 a3, t0;\nmov.b32 a1, t1;\n"
        "ld.shared.b32 t0, [%64+1792];\nld.shared.b32 t1, [%64+1920];\nadd.s64 d, %65, 48;\nwgmma.fence.sync.aligned;\nwgmma.mma_async.sync.aligned.m64n128k16.f32.bf16.bf16 {%0, %1, %2, %3, %4, %5, %6, %7, %8, %9, %10, %11, %12, %13, %14, %15, %16, %17, %18, %19, %20, %21, %22, %23, %24, %25, %26, %27, %28, %29, %30, %31, %32, %33, %34, %35, %36, %37, %38, %39, %40, %41, %42, %43, %44, %45, %46, %47, %48, %49, %50, %51, %52, %53, %54, %55, %56, %57, %58, %59, %60, %61, %62, %63}, {a0, a1, a2, a3}, d, 1, 1, 1, 0;\nwgmma.commit_group.sync.aligned;\nwgmma.wait_group.sync.aligned 1;\nmov.b32 b2, a1;\nmov.b32 b0, t0;\nmov.b32 b3, t0;\nmov.b32 b1, t1;\n"
        "ld.shared.b32 t0, [%64+2048];\nld.shared.b32 t1, [%64+2176];\nadd.s64 d, %65, 56;\nwgmma.fence.sync.aligned;\nwgmma.mma_async.sync.aligned.m64n128k16.f32.bf16.bf16 {%0, %1, %2, %3, %4, %5, %6, %7, %8, %9, %10, %11, %12, %13, %14, %15, %16, %17, %18, %19, %20, %21, %22, %23, %24, %25, %26, %27, %28, %29, %30, %31, %32, %33, %34, %35, %36, %37, %38, %39, %40, %41, %42, %43, %44, %45, %46, %47, %48, %49, %50, %51, %52, %53, %54, %55, %56, %57, %58, %59, %60, %61, %62, %63}, {b0, b1, b2, b3}, d, 1, 1, 1, 0;\nwgmma.commit_group.sync.aligned;\nwgmma.wait_group.sync.aligned 1;\nmov.b32 a2, b1;\nmov.b32 a0, t0;\nmov.b32 a3, t0;\nmov.b32 a1, t1;\n"
        "ld.shared.b32 t0, [%64+2304];\nld.shared.b32 t1, [%64+2432];\nadd.s64 d, %65, 64;\nwgmma.fence.sync.aligned;\nwgmma.mma_async.sync.aligned.m64n96k16.f32.bf16.bf16 {%0, %1, %2, %3, %4, %5, %6, %7, %8, %9, %10, %11, %12, %13, %14, %15, %16, %17, %18, %19, %20, %21, %22, %23, %24, %25, %26, %27, %28, %29, %30, %31, %32, %33, %34, %35, %36, %37, %38, %39, %40, %41, %42, %43, %44, %45, %46, %47}, {a0, a1, a2, a3}, d, 1, 1, 1, 0;\nwgmma.commit_group.sync.aligned;\nwgmma.wait_group.sync.aligned 1;\nmov.b32 b2, a1;\nmov.b32 b0, t0;\nmov.b32 b3, t0;\nmov.b32 b1, t1;\n"
        "ld.shared.b32 t0, [%64+2560];\nld.shared.b32 t1, [%64+2688];\nadd.s64 d, %65, 72;\nwgmma.fence.sync.aligned;\nwgmma.mma_async.sync.aligned.m64n96k16.f32.bf16.bf16 {%0, %1, %2, %3, %4, %5, %6, %7, %8, %9, %10, %11, %12, %13, %14, %15, %16, %17, %18, %19, %20, %21, %22, %23, %24, %25, %26, %27, %28, %29, %30, %31, %32, %33, %34, %35, %36, %37, %38, %39, %40, %41, %42, %43, %44, %45, %46, %47}, {b0, b1, b2, b3}, d, 1, 1, 1, 0;\nwgmma.commit_group.sync.aligned;\nwgmma.wait_group.sync.aligned 1;\nmov.b32 a2, b1;\nmov.b32 a0, t0;\nmov.b32 a3, t0;\nmov.b32 a1, t1;\n"
        "ld.shared.b32 t0, [%64+2816];\nld.shared.b32 t1, [%64+2944];\nadd.s64 d, %65, 80;\nwgmma.fence.sync.aligned;\nwgmma.mma_async.sync.aligned.m64n88k16.f32.bf16.bf16 {%0, %1, %2, %3, %4, %5, %6, %7, %8, %9, %10, %11, %12, %13, %14, %15, %16, %17, %18, %19, %20, %21, %22, %23, %24, %25, %26, %27, %28, %29, %30, %31, %32, %33, %34, %35, %36, %37, %38, %39, %40, %41, %42, %43}, {a0, a1, a2, a3}, d, 1, 1, 1, 0;\nwgmma.commit_group.sync.aligned;\nwgmma.wait_group.sync.aligned 1;\nmov.b32 b2, a1;\nmov.b32 b0, t0;\nmov.b32 b3, t0;\nmov.b32 b1, t1;\n"
        "ld.shared.b32 t0, [%64+3072];\nld.shared.b32 t1, [%64+3200];\nadd.s64 d, %65, 88;\nwgmma.fence.sync.aligned;\nwgmma.mma_async.sync.aligned.m64n88k16.f32.bf16.bf16 {%0, %1, %2, %3, %4, %5, %6, %7, %8, %9, %10, %11, %12, %13, %14, %15, %16, %17, %18, %19, %20, %21, %22, %23, %24, %25, %26, %27, %28, %29, %30, %31, %32, %33, %34, %35, %36, %37, %38, %39, %40, %41, %42, %43}, {b0, b1, b2, b3}, d, 1, 1, 1, 0;\nwgmma.commit_group.sync.aligned;\nwgmma.wait_group.sync.aligned 1;\nmov.b32 a2, b1;\nmov.b32 a0, t0;\nmov.b32 a3, t0;\nmov.b32 a1, t1;\n"
        "ld.shared.b32 t0, [%64+3328];\nld.shared.b32 t1, [%64+3456];\nadd.s64 d, %65, 96;\nwgmma.fence.sync.aligned;\nwgmma.mma_async.sync.aligned.m64n80k16.f32.bf16.bf16 {%0, %1, %2, %3, %4, %5, %6, %7, %8, %9, %10, %11, %12, %13, %14, %15, %16, %17, %18, %19, %20, %21, %22, %23, %24, %25, %26, %27, %28, %29, %30, %31, %32, %33, %34, %35, %36, %37, %38, %39}, {a0, a1, a2, a3}, d, 1, 1, 1, 0;\nwgmma.commit_group.sync.aligned;\nwgmma.wait_group.sync.aligned 1;\nmov.b32 b2, a1;\nmov.b32 b0, t0;\nmov.b32 b3, t0;\nmov.b32 b1, t1;\n"
        "ld.shared.b32 t0, [%64+3584];\nld.shared.b32 t1, [%64+3712];\nadd.s64 d, %65, 104;\nwgmma.fence.sync.aligned;\nwgmma.mma_async.sync.aligned.m64n80k16.f32.bf16.bf16 {%0, %1, %2, %3, %4, %5, %6, %7, %8, %9, %10, %11, %12, %13, %14, %15, %16, %17, %18, %19, %20, %21, %22, %23, %24, %25, %26, %27, %28, %29, %30, %31, %32, %33, %34, %35, %36, %37, %38, %39}, {b0, b1, b2, b3}, d, 1, 1, 1, 0;\nwgmma.commit_group.sync.aligned;\nwgmma.wait_group.sync.aligned 1;\nmov.b32 a2, b1;\nmov.b32 a0, t0;\nmov.b32 a3, t0;\nmov.b32 a1, t1;\n"
        "ld.shared.b32 t0, [%64+3840];\nld.shared.b32 t1, [%64+3968];\nadd.s64 d, %65, 112;\nwgmma.fence.sync.aligned;\nwgmma.mma_async.sync.aligned.m64n72k16.f32.bf16.bf16 {%0, %1, %2, %3, %4, %5, %6, %7, %8, %9, %10, %11, %12, %13, %14, %15, %16, %17, %18, %19, %20, %21, %22, %23, %24, %25, %26, %27, %28, %29, %30, %31, %32, %33, %34, %35}, {a0, a1, a2, a3}, d, 1, 1, 1, 0;\nwgmma.commit_group.sync.aligned;\nwgmma.wait_group.sync.aligned 1;\nmov.b32 b2, a1;\nmov.b32 b0, t0;\nmov.b32 b3, t0;\nmov.b32 b1, t1;\n"
        "ld.shared.b32 t0, [%64+4096];\nld.shared.b32 t1, [%64+4224];\nadd.s64 d, %65, 120;\nwgmma.fence.sync.aligned;\nwgmma.mma_async.sync.aligned.m64n72k16.f32.bf16.bf16 {%0, %1, %2, %3, %4, %5, %6, %7, %8, %9, %10, %11, %12, %13, %14, %15, %16, %17, %18, %19, %20, %21, %22, %23, %24, %25, %26, %27, %28, %29, %30, %31, %32, %33, %34, %35}, {b0, b1, b2, b3}, d, 1, 1, 1, 0;\nwgmma.commit_group.sync.aligned;\nwgmma.wait_group.sync.aligned 1;\nmov.b32 a2, b1;\nmov.b32 a0, t0;\nmov.b32 a3, t0;\nmov.b32 a1, t1;\n"
        "ld.shared.b32 t0, [%64+4352];\nld.shared.b32 t1, [%64+4480];\nadd.s64 d, %65, 128;\nwgmma.fence.sync.aligned;\nwgmma.mma_async.sync.aligned.m64n64k16.f32.bf16.bf16 {%0, %1, %2, %3, %4, %5, %6, %7, %8, %9, %10, %11, %12, %13, %14, %15, %16, %17, %18, %19, %20, %21, %22, %23, %24, %25, %26, %27, %28, %29, %30, %31}, {a0, a1, a2, a3}, d, 1, 1, 1, 0;\nwgmma.commit_group.sync.aligned;\nwgmma.wait_group.sync.aligned 1;\nmov.b32 b2, a1;\nmov.b32 b0, t0;\nmov.b32 b3, t0;\nmov.b32 b1, t1;\n"
        "ld.shared.b32 t0, [%64+4608];\nld.shared.b32 t1, [%64+4736];\nadd.s64 d, %65, 136;\nwgmma.fence.sync.aligned;\nwgmma.mma_async.sync.aligned.m64n64k16.f32.bf16.bf16 {%0, %1, %2, %3, %4, %5, %6, %7, %8, %9, %10, %11, %12, %13, %14, %15, %16, %17, %18, %19, %20, %21, %22, %23, %24, %25, %26, %27, %28, %29, %30, %31}, {b0, b1, b2, b3}, d, 1, 1, 1, 0;\nwgmma.commit_group.sync.aligned;\nwgmma.wait_group.sync.aligned 1;\nmov.b32 a2, b1;\nmov.b32 a0, t0;\nmov.b32 a3, t0;\nmov.b32 a1, t1;\n"
        "ld.shared.b32 t0, [%64+4864];\nld.shared.b32 t1, [%64+4992];\nadd.s64 d, %65, 144;\nwgmma.fence.sync.aligned;\nwgmma.mma_async.sync.aligned.m64n56k16.f32.bf16.bf16 {%0, %1, %2, %3, %4, %5, %6, %7, %8, %9, %10, %11, %12, %13, %14, %15, %16, %17, %18, %19, %20, %21, %22, %23, %24, %25, %26, %27}, {a0, a1, a2, a3}, d, 1, 1, 1, 0;\nwgmma.commit_group.sync.aligned;\nwgmma.wait_group.sync.aligned 1;\nmov.b32 b2, a1;\nmov.b32 b0, t0;\nmov.b32 b3, t0;\nmov.b32 b1, t1;\n"
        "ld.shared.b32 t0, [%64+5120];\nld.shared.b32 t1, [%64+5248];\nadd.s64 d, %65, 152;\nwgmma.fence.sync.aligned;\nwgmma.mma_async.sync.aligned.m64n56k16.f32.bf16.bf16 {%0, %1, %2, %3, %4, %5, %6, %7, %8, %9, %10, %11, %12, %13, %14, %15, %16, %17, %18, %19, %20, %21, %22, %23, %24, %25, %26, %27}, {b0, b1, b2, b3}, d, 1, 1, 1, 0;\nwgmma.commit_group.sync.aligned;\nwgmma.wait_group.sync.aligned 1;\nmov.b32 a2, b1;\nmov.b32 a0, t0;\nmov.b32 a3, t0;\nmov.b32 a1, t1;\n"
        "ld.shared.b32 t0, [%64+5376];\nld.shared.b32 t1, [%64+5504];\nadd.s64 d, %65, 160;\nwgmma.fence.sync.aligned;\nwgmma.mma_async.sync.aligned.m64n48k16.f32.bf16.bf16 {%0, %1, %2, %3, %4, %5, %6, %7, %8, %9, %10, %11, %12, %13, %14, %15, %16, %17, %18, %19, %20, %21, %22, %23}, {a0, a1, a2, a3}, d, 1, 1, 1, 0;\nwgmma.commit_group.sync.aligned;\nwgmma.wait_group.sync.aligned 1;\nmov.b32 b2, a1;\nmov.b32 b0, t0;\nmov.b32 b3, t0;\nmov.b32 b1, t1;\n"
        "ld.shared.b32 t0, [%64+5632];\nld.shared.b32 t1, [%64+5760];\nadd.s64 d, %65, 168;\nwgmma.fence.sync.aligned;\nwgmma.mma_async.sync.aligned.m64n48k16.f32.bf16.bf16 {%0, %1, %2, %3, %4, %5, %6, %7, %8, %9, %10, %11, %12, %13, %14, %15, %16, %17, %18, %19, %20, %21, %22, %23}, {b0, b1, b2, b3}, d, 1, 1, 1, 0;\nwgmma.commit_group.sync.aligned;\nwgmma.wait_group.sync.aligned 1;\nmov.b32 a2, b1;\nmov.b32 a0, t0;\nmov.b32 a3, t0;\nmov.b32 a1, t1;\n"
        "ld.shared.b32 t0, [%64+5888];\nld.shared.b32 t1, [%64+6016];\nadd.s64 d, %65, 176;\nwgmma.fence.sync.aligned;\nwgmma.mma_async.sync.aligned.m64n40k16.f32.bf16.bf16 {%0, %1, %2, %3, %4, %5, %6, %7, %8, %9, %10, %11, %12, %13, %14, %15, %16, %17, %18, %19}, {a0, a1, a2, a3}, d, 1, 1, 1, 0;\nwgmma.commit_group.sync.aligned;\nwgmma.wait_group.sync.aligned 1;\nmov.b32 b2, a1;\nmov.b32 b0, t0;\nmov.b32 b3, t0;\nmov.b32 b1, t1;\n"
        "ld.shared.b32 t0, [%64+6144];\nld.shared.b32 t1, [%64+6272];\nadd.s64 d, %65, 184;\nwgmma.fence.sync.aligned;\nwgmma.mma_async.sync.aligned.m64n40k16.f32.bf16.bf16 {%0, %1, %2, %3, %4, %5, %6, %7, %8, %9, %10, %11, %12, %13, %14, %15, %16, %17, %18, %19}, {b0, b1, b2, b3}, d, 1, 1, 1, 0;\nwgmma.commit_group.sync.aligned;\nwgmma.wait_group.sync.aligned 1;\nmov.b32 a2, b1;\nmov.b32 a0, t0;\nmov.b32 a3, t0;\nmov.b32 a1, t1;\n"
        "ld.shared.b32 t0, [%64+6400];\nld.shared.b32 t1, [%64+6528];\nadd.s64 d, %65, 192;\nwgmma.fence.sync.aligned;\nwgmma.mma_async.sync.aligned.m64n32k16.f32.bf16.bf16 {%0, %1, %2, %3, %4, %5, %6, %7, %8, %9, %10, %11, %12, %13, %14, %15}, {a0, a1, a2, a3}, d, 1, 1, 1, 0;\nwgmma.commit_group.sync.aligned;\nwgmma.wait_group.sync.aligned 1;\nmov.b32 b2, a1;\nmov.b32 b0, t0;\nmov.b32 b3, t0;\nmov.b32 b1, t1;\n"
        "ld.shared.b32 t0, [%64+6656];\nld.shared.b32 t1, [%64+6784];\nadd.s64 d, %65, 200;\nwgmma.fence.sync.aligned;\nwgmma.mma_async.sync.aligned.m64n32k16.f32.bf16.bf16 {%0, %1, %2, %3, %4, %5, %6, %7, %8, %9, %10, %11, %12, %13, %14, %15}, {b0, b1, b2, b3}, d, 1, 1, 1, 0;\nwgmma.commit_group.sync.aligned;\nwgmma.wait_group.sync.aligned 1;\nmov.b32 a2, b1;\nmov.b32 a0, t0;\nmov.b32 a3, t0;\nmov.b32 a1, t1;\n"
        "ld.shared.b32 t0, [%64+6912];\nld.shared.b32 t1, [%64+7040];\nadd.s64 d, %65, 208;\nwgmma.fence.sync.aligned;\nwgmma.mma_async.sync.aligned.m64n24k16.f32.bf16.bf16 {%0, %1, %2, %3, %4, %5, %6, %7, %8, %9, %10, %11}, {a0, a1, a2, a3}, d, 1, 1, 1, 0;\nwgmma.commit_group.sync.aligned;\nwgmma.wait_group.sync.aligned 1;\nmov.b32 b2, a1;\nmov.b32 b0, t0;\nmov.b32 b3, t0;\nmov.b32 b1, t1;\n"
        "ld.shared.b32 t0, [%64+7168];\nld.shared.b32 t1, [%64+7296];\nadd.s64 d, %65, 216;\nwgmma.fence.sync.aligned;\nwgmma.mma_async.sync.aligned.m64n24k16.f32.bf16.bf16 {%0, %1, %2, %3, %4, %5, %6, %7, %8, %9, %10, %11}, {b0, b1, b2, b3}, d, 1, 1, 1, 0;\nwgmma.commit_group.sync.aligned;\nwgmma.wait_group.sync.aligned 1;\nmov.b32 a2, b1;\nmov.b32 a0, t0;\nmov.b32 a3, t0;\nmov.b32 a1, t1;\n"
        "ld.shared.b32 t0, [%64+7424];\nld.shared.b32 t1, [%64+7552];\nadd.s64 d, %65, 224;\nwgmma.fence.sync.aligned;\nwgmma.mma_async.sync.aligned.m64n16k16.f32.bf16.bf16 {%0, %1, %2, %3, %4, %5, %6, %7}, {a0, a1, a2, a3}, d, 1, 1, 1, 0;\nwgmma.commit_group.sync.aligned;\nwgmma.wait_group.sync.aligned 1;\nmov.b32 b2, a1;\nmov.b32 b0, t0;\nmov.b32 b3, t0;\nmov.b32 b1, t1;\n"
        "ld.shared.b32 t0, [%64+7680];\nld.shared.b32 t1, [%64+7808];\nadd.s64 d, %65, 232;\nwgmma.fence.sync.aligned;\nwgmma.mma_async.sync.aligned.m64n16k16.f32.bf16.bf16 {%0, %1, %2, %3, %4, %5, %6, %7}, {b0, b1, b2, b3}, d, 1, 1, 1, 0;\nwgmma.commit_group.sync.aligned;\nwgmma.wait_group.sync.aligned 1;\nmov.b32 a2, b1;\nmov.b32 a0, t0;\nmov.b32 a3, t0;\nmov.b32 a1, t1;\n"
        "ld.shared.b32 t0, [%64+7936];\nld.shared.b32 t1, [%64+8064];\nadd.s64 d, %65, 240;\nwgmma.fence.sync.aligned;\nwgmma.mma_async.sync.aligned.m64n8k16.f32.bf16.bf16 {%0, %1, %2, %3}, {a0, a1, a2, a3}, d, 1, 1, 1, 0;\nwgmma.commit_group.sync.aligned;\nwgmma.wait_group.sync.aligned 1;\nmov.b32 b2, a1;\nmov.b32 b0, t0;\nmov.b32 b3, t0;\nmov.b32 b1, t1;\n"
        "add.s64 d, %65, 248;\nwgmma.fence.sync.aligned;\nwgmma.mma_async.sync.aligned.m64n8k16.f32.bf16.bf16 {%0, %1, %2, %3}, {b0, b1, b2, b3}, d, 1, 1, 1, 0;\nwgmma.commit_group.sync.aligned;\nwgmma.wait_group.sync.aligned 0;\n"
        "}" : "+f"(d[0]), "+f"(d[1]), "+f"(d[2]), "+f"(d[3]), "+f"(d[4]), "+f"(d[5]), "+f"(d[6]), "+f"(d[7]), "+f"(d[8]), "+f"(d[9]), "+f"(d[10]), "+f"(d[11]), "+f"(d[12]), "+f"(d[13]), "+f"(d[14]), "+f"(d[15]), "+f"(d[16]), "+f"(d[17]), "+f"(d[18]), "+f"(d[19]), "+f"(d[20]), "+f"(d[21]), "+f"(d[22]), "+f"(d[23]), "+f"(d[24]), "+f"(d[25]), "+f"(d[26]), "+f"(d[27]), "+f"(d[28]), "+f"(d[29]), "+f"(d[30]), "+f"(d[31]), "+f"(d[32]), "+f"(d[33]), "+f"(d[34]), "+f"(d[35]), "+f"(d[36]), "+f"(d[37]), "+f"(d[38]), "+f"(d[39]), "+f"(d[40]), "+f"(d[41]), "+f"(d[42]), "+f"(d[43]), "+f"(d[44]), "+f"(d[45]), "+f"(d[46]), "+f"(d[47]), "+f"(d[48]), "+f"(d[49]), "+f"(d[50]), "+f"(d[51]), "+f"(d[52]), "+f"(d[53]), "+f"(d[54]), "+f"(d[55]), "+f"(d[56]), "+f"(d[57]), "+f"(d[58]), "+f"(d[59]), "+f"(d[60]), "+f"(d[61]), "+f"(d[62]), "+f"(d[63]) : "r"(pa), "l"(db) : "memory");
}
__device__ __forceinline__ void wgmma_rs80(float (&d)[40], uint32_t a0, uint32_t a1, uint32_t a2, uint32_t a3, uint64_t db, int sc) {
    asm volatile("{\n.reg .pred p;\nsetp.ne.b32 p, %45, 0;\n"
        "wgmma.mma_async.sync.aligned.m64n80k16.f32.bf16.bf16 {%0, %1, %2, %3, %4, %5, %6, %7, %8, %9, %10, %11, %12, %13, %14, %15, %16, %17, %18, %19, %20, %21, %22, %23, %24, %25, %26, %27, %28, %29, %30, %31, %32, %33, %34, %35, %36, %37, %38, %39}, {%40, %41, %42, %43}, %44, p, 1, 1, 1;\n}\n"
        : "+f"(d[0]), "+f"(d[1]), "+f"(d[2]), "+f"(d[3]), "+f"(d[4]), "+f"(d[5]), "+f"(d[6]), "+f"(d[7]), "+f"(d[8]), "+f"(d[9]), "+f"(d[10]), "+f"(d[11]), "+f"(d[12]), "+f"(d[13]), "+f"(d[14]), "+f"(d[15]), "+f"(d[16]), "+f"(d[17]), "+f"(d[18]), "+f"(d[19]), "+f"(d[20]), "+f"(d[21]), "+f"(d[22]), "+f"(d[23]), "+f"(d[24]), "+f"(d[25]), "+f"(d[26]), "+f"(d[27]), "+f"(d[28]), "+f"(d[29]), "+f"(d[30]), "+f"(d[31]), "+f"(d[32]), "+f"(d[33]), "+f"(d[34]), "+f"(d[35]), "+f"(d[36]), "+f"(d[37]), "+f"(d[38]), "+f"(d[39]) : "r"(a0), "r"(a1), "r"(a2), "r"(a3), "l"(db), "r"(sc));
}
__device__ __forceinline__ void wgmma_ss80(float (&d)[40], uint64_t da, uint64_t db, int sc) {
    asm volatile("{\n.reg .pred p;\nsetp.ne.b32 p, %42, 0;\n"
        "wgmma.mma_async.sync.aligned.m64n80k16.f32.bf16.bf16 {%0, %1, %2, %3, %4, %5, %6, %7, %8, %9, %10, %11, %12, %13, %14, %15, %16, %17, %18, %19, %20, %21, %22, %23, %24, %25, %26, %27, %28, %29, %30, %31, %32, %33, %34, %35, %36, %37, %38, %39}, %40, %41, p, 1, 1, 0, 1;\n}\n"
        : "+f"(d[0]), "+f"(d[1]), "+f"(d[2]), "+f"(d[3]), "+f"(d[4]), "+f"(d[5]), "+f"(d[6]), "+f"(d[7]), "+f"(d[8]), "+f"(d[9]), "+f"(d[10]), "+f"(d[11]), "+f"(d[12]), "+f"(d[13]), "+f"(d[14]), "+f"(d[15]), "+f"(d[16]), "+f"(d[17]), "+f"(d[18]), "+f"(d[19]), "+f"(d[20]), "+f"(d[21]), "+f"(d[22]), "+f"(d[23]), "+f"(d[24]), "+f"(d[25]), "+f"(d[26]), "+f"(d[27]), "+f"(d[28]), "+f"(d[29]), "+f"(d[30]), "+f"(d[31]), "+f"(d[32]), "+f"(d[33]), "+f"(d[34]), "+f"(d[35]), "+f"(d[36]), "+f"(d[37]), "+f"(d[38]), "+f"(d[39]) : "l"(da), "l"(db), "r"(sc));
}
__device__ __forceinline__ void wgmma_ss80t(float (&d)[40], uint64_t da, uint64_t db, int sc) {
    asm volatile("{\n.reg .pred p;\nsetp.ne.b32 p, %42, 0;\n"
        "wgmma.mma_async.sync.aligned.m64n80k16.f32.bf16.bf16 {%0, %1, %2, %3, %4, %5, %6, %7, %8, %9, %10, %11, %12, %13, %14, %15, %16, %17, %18, %19, %20, %21, %22, %23, %24, %25, %26, %27, %28, %29, %30, %31, %32, %33, %34, %35, %36, %37, %38, %39}, %40, %41, p, 1, 1, 1, 1;\n}\n"
        : "+f"(d[0]), "+f"(d[1]), "+f"(d[2]), "+f"(d[3]), "+f"(d[4]), "+f"(d[5]), "+f"(d[6]), "+f"(d[7]), "+f"(d[8]), "+f"(d[9]), "+f"(d[10]), "+f"(d[11]), "+f"(d[12]), "+f"(d[13]), "+f"(d[14]), "+f"(d[15]), "+f"(d[16]), "+f"(d[17]), "+f"(d[18]), "+f"(d[19]), "+f"(d[20]), "+f"(d[21]), "+f"(d[22]), "+f"(d[23]), "+f"(d[24]), "+f"(d[25]), "+f"(d[26]), "+f"(d[27]), "+f"(d[28]), "+f"(d[29]), "+f"(d[30]), "+f"(d[31]), "+f"(d[32]), "+f"(d[33]), "+f"(d[34]), "+f"(d[35]), "+f"(d[36]), "+f"(d[37]), "+f"(d[38]), "+f"(d[39]) : "l"(da), "l"(db), "r"(sc));
}
__device__ __forceinline__ void wgmma_ss8_ta(float (&d)[4], uint64_t da, uint64_t db, int sc) {
    asm volatile("{\n.reg .pred p;\nsetp.ne.b32 p, %6, 0;\n"
        "wgmma.mma_async.sync.aligned.m64n8k16.f32.bf16.bf16 {%0, %1, %2, %3}, %4, %5, p, 1, 1, 1, 0;\n}\n"
        : "+f"(d[0]), "+f"(d[1]), "+f"(d[2]), "+f"(d[3]) : "l"(da), "l"(db), "r"(sc));
}
__device__ __forceinline__ void wgmma_rs8(float (&d)[4], uint32_t a0, uint32_t a1, uint32_t a2, uint32_t a3, uint64_t db, int sc) {
    asm volatile("{\n.reg .pred p;\nsetp.ne.b32 p, %9, 0;\n"
        "wgmma.mma_async.sync.aligned.m64n8k16.f32.bf16.bf16 {%0, %1, %2, %3}, {%4, %5, %6, %7}, %8, p, 1, 1, 0;\n}\n"
        : "+f"(d[0]), "+f"(d[1]), "+f"(d[2]), "+f"(d[3]) : "r"(a0), "r"(a1), "r"(a2), "r"(a3), "l"(db), "r"(sc));
}
__device__ __forceinline__ void wgmma_rs128(float (&d)[64], uint32_t a0, uint32_t a1, uint32_t a2, uint32_t a3, uint64_t db, int sc) {
    asm volatile("{\n.reg .pred p;\nsetp.ne.b32 p, %69, 0;\n"
        "wgmma.mma_async.sync.aligned.m64n128k16.f32.bf16.bf16 {%0, %1, %2, %3, %4, %5, %6, %7, %8, %9, %10, %11, %12, %13, %14, %15, %16, %17, %18, %19, %20, %21, %22, %23, %24, %25, %26, %27, %28, %29, %30, %31, %32, %33, %34, %35, %36, %37, %38, %39, %40, %41, %42, %43, %44, %45, %46, %47, %48, %49, %50, %51, %52, %53, %54, %55, %56, %57, %58, %59, %60, %61, %62, %63}, {%64, %65, %66, %67}, %68, p, 1, 1, 1;\n}\n"
        : "+f"(d[0]), "+f"(d[1]), "+f"(d[2]), "+f"(d[3]), "+f"(d[4]), "+f"(d[5]), "+f"(d[6]), "+f"(d[7]), "+f"(d[8]), "+f"(d[9]), "+f"(d[10]), "+f"(d[11]), "+f"(d[12]), "+f"(d[13]), "+f"(d[14]), "+f"(d[15]), "+f"(d[16]), "+f"(d[17]), "+f"(d[18]), "+f"(d[19]), "+f"(d[20]), "+f"(d[21]), "+f"(d[22]), "+f"(d[23]), "+f"(d[24]), "+f"(d[25]), "+f"(d[26]), "+f"(d[27]), "+f"(d[28]), "+f"(d[29]), "+f"(d[30]), "+f"(d[31]), "+f"(d[32]), "+f"(d[33]), "+f"(d[34]), "+f"(d[35]), "+f"(d[36]), "+f"(d[37]), "+f"(d[38]), "+f"(d[39]), "+f"(d[40]), "+f"(d[41]), "+f"(d[42]), "+f"(d[43]), "+f"(d[44]), "+f"(d[45]), "+f"(d[46]), "+f"(d[47]), "+f"(d[48]), "+f"(d[49]), "+f"(d[50]), "+f"(d[51]), "+f"(d[52]), "+f"(d[53]), "+f"(d[54]), "+f"(d[55]), "+f"(d[56]), "+f"(d[57]), "+f"(d[58]), "+f"(d[59]), "+f"(d[60]), "+f"(d[61]), "+f"(d[62]), "+f"(d[63]) : "r"(a0), "r"(a1), "r"(a2), "r"(a3), "l"(db), "r"(sc));
}
__device__ __forceinline__ void wgmma_rs88(float (&d)[44], uint32_t a0, uint32_t a1, uint32_t a2, uint32_t a3, uint64_t db, int sc) {
    asm volatile("{\n.reg .pred p;\nsetp.ne.b32 p, %49, 0;\n"
        "wgmma.mma_async.sync.aligned.m64n88k16.f32.bf16.bf16 {%0, %1, %2, %3, %4, %5, %6, %7, %8, %9, %10, %11, %12, %13, %14, %15, %16, %17, %18, %19, %20, %21, %22, %23, %24, %25, %26, %27, %28, %29, %30, %31, %32, %33, %34, %35, %36, %37, %38, %39, %40, %41, %42, %43}, {%44, %45, %46, %47}, %48, p, 1, 1, 1;\n}\n"
        : "+f"(d[0]), "+f"(d[1]), "+f"(d[2]), "+f"(d[3]), "+f"(d[4]), "+f"(d[5]), "+f"(d[6]), "+f"(d[7]), "+f"(d[8]), "+f"(d[9]), "+f"(d[10]), "+f"(d[11]), "+f"(d[12]), "+f"(d[13]), "+f"(d[14]), "+f"(d[15]), "+f"(d[16]), "+f"(d[17]), "+f"(d[18]), "+f"(d[19]), "+f"(d[20]), "+f"(d[21]), "+f"(d[22]), "+f"(d[23]), "+f"(d[24]), "+f"(d[25]), "+f"(d[26]), "+f"(d[27]), "+f"(d[28]), "+f"(d[29]), "+f"(d[30]), "+f"(d[31]), "+f"(d[32]), "+f"(d[33]), "+f"(d[34]), "+f"(d[35]), "+f"(d[36]), "+f"(d[37]), "+f"(d[38]), "+f"(d[39]), "+f"(d[40]), "+f"(d[41]), "+f"(d[42]), "+f"(d[43]) : "r"(a0), "r"(a1), "r"(a2), "r"(a3), "l"(db), "r"(sc));
}
__device__ __forceinline__ void wgmma_rs128k(float (&d)[64], uint32_t a0, uint32_t a1, uint32_t a2, uint32_t a3, uint64_t db, int sc) {
    asm volatile("{\n.reg .pred p;\nsetp.ne.b32 p, %69, 0;\n"
        "wgmma.mma_async.sync.aligned.m64n128k16.f32.bf16.bf16 {%0, %1, %2, %3, %4, %5, %6, %7, %8, %9, %10, %11, %12, %13, %14, %15, %16, %17, %18, %19, %20, %21, %22, %23, %24, %25, %26, %27, %28, %29, %30, %31, %32, %33, %34, %35, %36, %37, %38, %39, %40, %41, %42, %43, %44, %45, %46, %47, %48, %49, %50, %51, %52, %53, %54, %55, %56, %57, %58, %59, %60, %61, %62, %63}, {%64, %65, %66, %67}, %68, p, 1, 1, 0;\n}\n"
        : "+f"(d[0]), "+f"(d[1]), "+f"(d[2]), "+f"(d[3]), "+f"(d[4]), "+f"(d[5]), "+f"(d[6]), "+f"(d[7]), "+f"(d[8]), "+f"(d[9]), "+f"(d[10]), "+f"(d[11]), "+f"(d[12]), "+f"(d[13]), "+f"(d[14]), "+f"(d[15]), "+f"(d[16]), "+f"(d[17]), "+f"(d[18]), "+f"(d[19]), "+f"(d[20]), "+f"(d[21]), "+f"(d[22]), "+f"(d[23]), "+f"(d[24]), "+f"(d[25]), "+f"(d[26]), "+f"(d[27]), "+f"(d[28]), "+f"(d[29]), "+f"(d[30]), "+f"(d[31]), "+f"(d[32]), "+f"(d[33]), "+f"(d[34]), "+f"(d[35]), "+f"(d[36]), "+f"(d[37]), "+f"(d[38]), "+f"(d[39]), "+f"(d[40]), "+f"(d[41]), "+f"(d[42]), "+f"(d[43]), "+f"(d[44]), "+f"(d[45]), "+f"(d[46]), "+f"(d[47]), "+f"(d[48]), "+f"(d[49]), "+f"(d[50]), "+f"(d[51]), "+f"(d[52]), "+f"(d[53]), "+f"(d[54]), "+f"(d[55]), "+f"(d[56]), "+f"(d[57]), "+f"(d[58]), "+f"(d[59]), "+f"(d[60]), "+f"(d[61]), "+f"(d[62]), "+f"(d[63]) : "r"(a0), "r"(a1), "r"(a2), "r"(a3), "l"(db), "r"(sc));
}
__device__ __forceinline__ void wgmma_rs88k(float (&d)[44], uint32_t a0, uint32_t a1, uint32_t a2, uint32_t a3, uint64_t db, int sc) {
    asm volatile("{\n.reg .pred p;\nsetp.ne.b32 p, %49, 0;\n"
        "wgmma.mma_async.sync.aligned.m64n88k16.f32.bf16.bf16 {%0, %1, %2, %3, %4, %5, %6, %7, %8, %9, %10, %11, %12, %13, %14, %15, %16, %17, %18, %19, %20, %21, %22, %23, %24, %25, %26, %27, %28, %29, %30, %31, %32, %33, %34, %35, %36, %37, %38, %39, %40, %41, %42, %43}, {%44, %45, %46, %47}, %48, p, 1, 1, 0;\n}\n"
        : "+f"(d[0]), "+f"(d[1]), "+f"(d[2]), "+f"(d[3]), "+f"(d[4]), "+f"(d[5]), "+f"(d[6]), "+f"(d[7]), "+f"(d[8]), "+f"(d[9]), "+f"(d[10]), "+f"(d[11]), "+f"(d[12]), "+f"(d[13]), "+f"(d[14]), "+f"(d[15]), "+f"(d[16]), "+f"(d[17]), "+f"(d[18]), "+f"(d[19]), "+f"(d[20]), "+f"(d[21]), "+f"(d[22]), "+f"(d[23]), "+f"(d[24]), "+f"(d[25]), "+f"(d[26]), "+f"(d[27]), "+f"(d[28]), "+f"(d[29]), "+f"(d[30]), "+f"(d[31]), "+f"(d[32]), "+f"(d[33]), "+f"(d[34]), "+f"(d[35]), "+f"(d[36]), "+f"(d[37]), "+f"(d[38]), "+f"(d[39]), "+f"(d[40]), "+f"(d[41]), "+f"(d[42]), "+f"(d[43]) : "r"(a0), "r"(a1), "r"(a2), "r"(a3), "l"(db), "r"(sc));
}
__device__ __forceinline__ void wgmma_rs80k(float (&d)[40], uint32_t a0, uint32_t a1, uint32_t a2, uint32_t a3, uint64_t db, int sc) {
    asm volatile("{\n.reg .pred p;\nsetp.ne.b32 p, %45, 0;\n"
        "wgmma.mma_async.sync.aligned.m64n80k16.f32.bf16.bf16 {%0, %1, %2, %3, %4, %5, %6, %7, %8, %9, %10, %11, %12, %13, %14, %15, %16, %17, %18, %19, %20, %21, %22, %23, %24, %25, %26, %27, %28, %29, %30, %31, %32, %33, %34, %35, %36, %37, %38, %39}, {%40, %41, %42, %43}, %44, p, 1, 1, 0;\n}\n"
        : "+f"(d[0]), "+f"(d[1]), "+f"(d[2]), "+f"(d[3]), "+f"(d[4]), "+f"(d[5]), "+f"(d[6]), "+f"(d[7]), "+f"(d[8]), "+f"(d[9]), "+f"(d[10]), "+f"(d[11]), "+f"(d[12]), "+f"(d[13]), "+f"(d[14]), "+f"(d[15]), "+f"(d[16]), "+f"(d[17]), "+f"(d[18]), "+f"(d[19]), "+f"(d[20]), "+f"(d[21]), "+f"(d[22]), "+f"(d[23]), "+f"(d[24]), "+f"(d[25]), "+f"(d[26]), "+f"(d[27]), "+f"(d[28]), "+f"(d[29]), "+f"(d[30]), "+f"(d[31]), "+f"(d[32]), "+f"(d[33]), "+f"(d[34]), "+f"(d[35]), "+f"(d[36]), "+f"(d[37]), "+f"(d[38]), "+f"(d[39]) : "r"(a0), "r"(a1), "r"(a2), "r"(a3), "l"(db), "r"(sc));
}
__device__ __forceinline__ void wgmma_rs64(float (&d)[32], uint32_t a0, uint32_t a1, uint32_t a2, uint32_t a3, uint64_t db, int sc) {
    asm volatile("{\n.reg .pred p;\nsetp.ne.b32 p, %37, 0;\n"
        "wgmma.mma_async.sync.aligned.m64n64k16.f32.bf16.bf16 {%0, %1, %2, %3, %4, %5, %6, %7, %8, %9, %10, %11, %12, %13, %14, %15, %16, %17, %18, %19, %20, %21, %22, %23, %24, %25, %26, %27, %28, %29, %30, %31}, {%32, %33, %34, %35}, %36, p, 1, 1, 1;\n}\n"
        : "+f"(d[0]), "+f"(d[1]), "+f"(d[2]), "+f"(d[3]), "+f"(d[4]), "+f"(d[5]), "+f"(d[6]), "+f"(d[7]), "+f"(d[8]), "+f"(d[9]), "+f"(d[10]), "+f"(d[11]), "+f"(d[12]), "+f"(d[13]), "+f"(d[14]), "+f"(d[15]), "+f"(d[16]), "+f"(d[17]), "+f"(d[18]), "+f"(d[19]), "+f"(d[20]), "+f"(d[21]), "+f"(d[22]), "+f"(d[23]), "+f"(d[24]), "+f"(d[25]), "+f"(d[26]), "+f"(d[27]), "+f"(d[28]), "+f"(d[29]), "+f"(d[30]), "+f"(d[31]) : "r"(a0), "r"(a1), "r"(a2), "r"(a3), "l"(db), "r"(sc));
}

__device__ __forceinline__ uint64_t mkdesc(uint32_t lo) { return ((uint64_t)0x40000040u << 32) | lo; }
template <int F> __device__ __forceinline__ uint32_t lop3(uint32_t a, uint32_t b, uint32_t c) { uint32_t r; asm("lop3.b32 %0, %1, %2, %3, %4;" : "=r"(r) : "r"(a), "r"(b), "r"(c), "n"(F)); return r; }
__device__ __forceinline__ void stg128_tag(void* p, uint32_t x, uint32_t y, uint32_t z, uint32_t u, uint32_t ep, int w) {
    stg128(p, lop3<0xB8>(x, w == 0, ep), lop3<0xB8>(y, w == 1, ep), lop3<0xB8>(z, w == 2, ep), lop3<0xB8>(u, w == 3, ep));
}
__device__ __forceinline__ uint32_t tag(uint32_t w, uint32_t ep) { asm("lop3.b32 %0, %0, 1, %1, 0xB8;" : "+r"(w) : "r"(ep)); return w; }
template <int N> __device__ __forceinline__ void pack_part(uint32_t (&p)[32], const float (&v)[N], uint32_t ep) {
#pragma unroll
    for (int i = 0; i < N / 2; i++) p[i] = (i & 3) ? pack2(v[2 * i], v[2 * i + 1]) : tag(pack2(v[2 * i], v[2 * i + 1]), ep);
#pragma unroll
    for (int i = 0; i < N / 2; i++) asm volatile("" : "+r"(p[i]));
}
__device__ __forceinline__ void st_part(uint4* p, const uint32_t* v) {
    asm volatile("{\n.reg .b64 l, h;\n.reg .b128 q;\nmov.b64 l, {%1, %2};\nmov.b64 h, {%3, %4};\nmov.b128 q, {l, h};\nst.relaxed.gpu.global.b128 [%0], q;\n}"
                 ::"l"(p), "r"(v[0]), "r"(v[1]), "r"(v[2]), "r"(v[3]) : "memory");
}
__device__ __forceinline__ void st_peer(uint32_t a, uint32_t x, uint32_t y, uint32_t z, uint32_t w, uint32_t bar) {
    asm volatile("st.async.shared::cluster.mbarrier::complete_tx::bytes.v4.b32 [%0], {%1, %2, %3, %4}, [%5];" ::"r"(a), "r"(x), "r"(y), "r"(z), "r"(w), "r"(bar) : "memory");
}
__device__ __forceinline__ int g4_block(int c, int j) { return c ? j ^ (8 - 2 * c) : 8 + (j & 1); }
__device__ __forceinline__ uint32_t recv_off(int w) { return w ? OFF_XR : OFF_REM; }
__device__ __forceinline__ uint4 ld_part(const void* p) {
    uint4 v;
    asm volatile("{\n.reg .b64 l, h;\n.reg .b128 q;\nld.relaxed.gpu.global.b128 q, [%4];\nmov.b128 {l, h}, q;\nmov.b64 {%0, %1}, l;\nmov.b64 {%2, %3}, h;\n}"
                 : "=r"(v.x), "=r"(v.y), "=r"(v.z), "=r"(v.w) : "l"(p) : "memory");
    return v;
}
__device__ __forceinline__ void ld_part4(uint4 (&u)[4], const uint4* p, int st) {
#pragma unroll
    for (int i = 0; i < 4; i++) u[i] = ld_part(p + i * st);
}
__device__ __forceinline__ uint32_t stale4(const uint4 (&u)[4], uint32_t ep) { return lop3<0x7E>(u[0].x, ep, u[1].x) | lop3<0x7E>(u[2].x, ep, u[3].x); }
__device__ __forceinline__ void add8(float* v, uint4 u) {
    v[0] += blo(u.x); v[1] += bhi(u.x); v[2] += blo(u.y); v[3] += bhi(u.y);
    v[4] += blo(u.z); v[5] += bhi(u.z); v[6] += blo(u.w); v[7] += bhi(u.w);
}
__device__ __forceinline__ void unpack8(float* v, uint4 u) {
    v[0] = blo(u.x); v[1] = bhi(u.x); v[2] = blo(u.y); v[3] = bhi(u.y); v[4] = blo(u.z); v[5] = bhi(u.z); v[6] = blo(u.w); v[7] = bhi(u.w);
}
__device__ __forceinline__ uint4 add2(uint4 a, uint4 b) { return make_uint4(add2(a.x, b.x), add2(a.y, b.y), add2(a.z, b.z), add2(a.w, b.w)); }
__device__ __forceinline__ void base16(float* v, uint4 b, float2 c, float2 d) {
    v[0] = fmaf(c.x, v[0], blo(b.x)); v[1] = fmaf(c.y, v[1], bhi(b.x)); v[2] = fmaf(c.x, v[2], blo(b.y)); v[3] = fmaf(c.y, v[3], bhi(b.y));
    v[4] = fmaf(d.x, v[4], blo(b.z)); v[5] = fmaf(d.y, v[5], bhi(b.z)); v[6] = fmaf(d.x, v[6], blo(b.w)); v[7] = fmaf(d.y, v[7], bhi(b.w));
}
__device__ __forceinline__ uint32_t split2(float x) { const float h = rbf(x); return pack2(h, x - h); }
__device__ __forceinline__ uint32_t b80_desc(uint32_t dsb, uint32_t wn, uint32_t rn, uint32_t h) {
    const uint32_t wb = dsb + OFF_W + (wn & 7) * 16384 + h * 8192, rm = dsb + OFF_REM + rn * 4096 + h * 2048;
    return (wb >> 4) | ((rm - wb) << 12);
}
constexpr int64_t B80_STEP = 128 - (126 << 16), B80_HALF = 512 - (384 << 16);
constexpr uint32_t ring_mask(int L) {
    uint32_t m = 0;
    for (int i = L; i < 20; i++) m |= (uint32_t)(i >= 20 - L || !((i - L) & 1)) << i;
    return m;
}
constexpr uint32_t M0 = ring_mask(LEAD1), M1 = ring_mask(10), M2 = ring_mask(XLEAD);
__device__ __forceinline__ uint32_t ring_pos(int w, int n, int L) { return w ? (n < 10 - L ? L + 2 * n : 10 + n) : (n < L ? n : 2 * n - L + 1); }
__device__ __forceinline__ int g1_block(int n, int j) { return n < 5 ? 2 * n + (j & 1) : 2 * n - 9 - (j & 1); }

__device__ __forceinline__ void load_tile(const Maps& mp, uint32_t dst, int e, int tile, int kb, int j, uint32_t bar) {
    mbar_expect(bar, 8192);
    tma_ld2(dst, &mp.x[e], 64 * (e == 0 ? tile : e == 1 ? kb : 0), 64 * (e == 0 ? g1_block(kb, j) : e == 1 ? tile : 10 * tile + kb), bar);
}

template <int OCT>
__device__ __forceinline__ void gemv_tile(float (&d)[4], uint32_t a, uint32_t b, int kb0) {
    uint32_t alo = ((a & 0x3FFFF) >> 4) | 0x10000u, blo_ = ((b & 0x3FFFF) >> 4) | (OCT << 16);
#pragma unroll 1
    for (int s = 0; s < 20; s += 4) {
        const int kb = kb0 + (s >> 2);
        const uint32_t bk = blo_ + (OCT == 7 ? (kb & 1) * 288 + (kb >> 1) * 56 : kb * 64);
        wg_fence();
#pragma unroll
        for (int q = 0; q < 4; q++) wgmma_ss8_ta(d, mkdesc(alo + (s + q) * 128), ((uint64_t)8 << 32) | (bk + q * 2 * OCT), s + q);
        wg_commit();
    }
    wg_wait<0>();
    reg_fence(d);
}

__device__ __forceinline__ void flush_tile(uint32_t st, bf16* dst, int u) {
#pragma unroll
    for (int i = 0; i < 2; i++) {
        const int idx = u + 320 * i, row = idx >> 3, c = idx & 7;
        stg128(dst + (size_t)row * S_ + 8 * c, lds128(st + row * 128 + ((c ^ ((row >> 1) & 7)) << 4)));
    }
}

__device__ __forceinline__ int tid_now() { int t; asm volatile("mov.u32 %0, %%tid.x;" : "=r"(t)); return t; }
__device__ __forceinline__ float zscale(float c) { return c == 0.f ? 0x1p-30f : c; }
__device__ __forceinline__ bool bar_any(int id, bool p) {
    uint32_t r;
    asm volatile("{\n.reg .pred a, b;\nsetp.ne.u32 a, %2, 0;\nbarrier.red.or.pred.aligned b, %1, 128, a;\nselp.u32 %0, 1, 0, b;\n}" : "=r"(r) : "r"(id), "r"((uint32_t)p) : "memory");
    return r != 0;
}

__global__ void __cluster_dims__(2, 1, 1) __launch_bounds__(NTHR, 1) fused_kernel(const __grid_constant__ Ptrs pp, bf16* __restrict__ out, const __grid_constant__ Maps mp) {
    extern __shared__ __align__(1024) uint8_t smem_raw[];
    const uint32_t sb = s2u(smem_raw), bars = sb + M_BAR, dsb = sb & 0x3FFFF;
    const int id = blockIdx.x, warp = __shfl_sync(0xffffffffu, (int)threadIdx.x >> 5, 0), wg = warp >> 2;
    const uint32_t c0 = clock_lo();
#define TIDS const int tid = tid_now(), lane = tid & 31, wt = tid & 127, g = lane >> 2, t = lane & 3; (void)wt; (void)g; (void)t;
    TS(threadIdx.x == 0, 0) TG(threadIdx.x == 0, 62)

    if (id >= 128) {
        TIDS
        if (sb & 1023) __trap();
        const int hs = id - 128;
        constexpr int H_B = 204800;
        static_assert(H_B + TAB_BYTES + 8 * VEC_BYTES <= OFF_M, "helper map");
        if (warp < 10 && elect()) { mbar_init(bars + warp * 8, 1); mbar_init(bars + 80 + warp * 8, 1); asm volatile("fence.mbarrier_init.release.cluster;" ::: "memory"); }
        __syncthreads();
        const uint32_t e0 = ld_cold(&g_epoch);
        wait_clock(c0, HELP_T);
        uint4 wr[10];
#pragma unroll
        for (int u = 0; u < 10; u++) wr[u] = ldg128(((hs >> 1) ? pp.w2 : pp.w1) + (size_t)(320 * (hs & 1) + (tid >> 4) + 32 * u) * D_ + 512 + 8 * (tid & 15));
        {
            const int r = tid >> 4, c = tid & 15;
            uint4* dst[2];
#pragma unroll
            for (int e = 0; e < 2; e++) {
                const int p = !(hs >> 1) ? r : e && (hs & 1) ? (r & ~14) | ((r & 6) << 1) | ((r & 8) >> 2) : (r & ~30) | ((r & 6) << 2) | ((r & 24) >> 2);
                dst[e] = &g_wr[(((hs >> 1) * 8 + (c >> 1)) * 10 + 5 * (hs & 1)) * 128 + (p & 15) * 8 + ((2 * (p >> 4) + (c & 1)) ^ (p & 7))];
            }
#pragma unroll
            for (int u = 0; u < 10; u++) stg128(reinterpret_cast<uint4*>(reinterpret_cast<uintptr_t>(dst[u >= 6]) ^ (64 * (u & 1))) + (u >> 1) * 128, wr[u]);
        }
        __syncthreads();
        if (warp == 0) signal_cnt(&g_cnt.wr[0], lane, 1);
        __syncthreads();
        if (warp < 5 && elect()) {
            const int un = 5 * hs + warp;
            mbar_expect(bars + warp * 8, 40960);
            tma_ld2(sb + warp * 40960, &mp.w1h, 64 * (un >> 1), 320 * (un & 1), bars + warp * 8);
            tma_ld2(sb + warp * 40960 + 20480, &mp.w1h, 64 * (un >> 1), 320 * (un & 1) + 160, bars + warp * 8);
        }
        if (tid < 320) {
            const uint4* gm = reinterpret_cast<const uint4*>(g_mod + 3 * D_) + tid;
            const unsigned epoch = e0 + 1;
            uint4 r[6];
            unsigned it = 0;
            for (;;) {
                uint32_t bad = 0;
#pragma unroll
                for (int i = 0; i < 6; i++) { r[i] = ld_part(gm + (i >> 1) * (D_ / 2) + (i & 1) * 3 * D_); bad |= (r[i].y ^ epoch) | (r[i].w ^ epoch); }
                if (__all_sync(~0u, !bad)) break;
                if (++it > SPIN_LIMIT) SPIN_FAIL(54)
            }
            uint32_t mv[3];
#pragma unroll
            for (int i = 0; i < 3; i++) mv[i] = pack2(__uint_as_float(r[2 * i].x) + __uint_as_float(r[2 * i + 1].x), __uint_as_float(r[2 * i].z) + __uint_as_float(r[2 * i + 1].z));
            const uint32_t sw2 = mv[0], cw = add2(mv[1], 0x3f803f80u), gw = mv[2];
            const float c0 = blo(cw), c1 = bhi(cw), s0 = blo(sw2), s1 = bhi(sw2);
            const float i0 = __frcp_rn(zscale(c0)), i1 = __frcp_rn(zscale(c1));
            const uint32_t ci = pack2(i0, i1), cq = pack2(i0 * i0, i1 * i1);
            const uint32_t a = sb + H_B + ((tid >> 5) & 1) * 4608 + (tid >> 6) * 896 + ((tid >> 2) & 7) * 112 + (tid & 3) * 4;
            sts32(a, ci); sts32(a + 16, pack2(i0 - blo(ci), i1 - bhi(ci)));
            sts32(a + 32, cq); sts32(a + 48, pack2(fmaf(i0, i0, -blo(cq)), fmaf(i1, i1, -bhi(cq))));
            sts32(a + 64, cw); sts32(a + 80, sw2); sts32(a + 96, 0x3f803f80u);
            if ((tid & ~35) == 284) sts32(a + 112, 0);
            const uint32_t v = sb + H_B + TAB_BYTES + (tid < 256 ? (tid >> 5) * VEC_BYTES + (tid & 31) * 8 : ((tid - 256) >> 3) * VEC_BYTES + 256 + (tid & 7) * 8);
            sts64f(v, blo(gw), bhi(gw)); sts64f(v + 320, c0, c1); sts64f(v + 640, s0, s1); sts64f(v + 960, i0, i1);
            float k[5] = {c0 + c1, s0 + s1, fmaf(c0, c0, c1 * c1), fmaf(c0, s0, c1 * s1), fmaf(s0, s0, s1 * s1)};
#pragma unroll 1
            for (int o = 16; o; o >>= 1) {
#pragma unroll
                for (int e = 0; e < 5; e++) k[e] += __shfl_xor_sync(~0u, k[e], o);
            }
            const uint32_t ks = sb + H_B + TAB_BYTES + (lane & 7) * VEC_BYTES + 1280 + (warp >> 1) * 32;
            if ((warp & 1) && lane < 8) { sts128f(ks, k[0], k[1], k[2], k[3]); sts128f(ks + 16, k[4], 0.f, 0.f, 0.f); }
            bar_sync(3, 320);
            if (!(warp & 1) && lane < 8) {
                const float4 o = lds128f(ks);
                sts128f(ks, k[0] + o.x, k[1] + o.y, k[2] + o.z, k[3] + o.w); sts32(ks + 16, __float_as_uint(k[4] + __uint_as_float(lds32(ks + 16))));
            }
            fence_async_smem();
        }
        __syncthreads();
        if (hs == 0 && warp == 15 && elect()) {
            asm volatile("cp.async.bulk.global.shared::cta.bulk_group [%0], [%1], %2;\ncp.async.bulk.commit_group;\ncp.async.bulk.wait_group 0;"
                         ::"l"(g_tab), "r"(sb + H_B), "n"(TAB_BYTES + 8 * VEC_BYTES) : "memory");
            asm volatile("red.release.gpu.global.add.u32 [%0], 1;" ::"l"(&g_cnt.tab[0]) : "memory");
        }
        __syncwarp();
#pragma unroll 1
        for (int i = wg; i < 20; i += 4) {
            const int r = i / 5, b = i - 5 * r, un = 5 * hs + b, u3 = 20 * r + un;
            auto refill = [&](int e, int u, uint32_t fb) {
                mbar_expect(fb, 40960);
                tma_ld2(sb + e * 40960, &mp.w3h, 64 * (u >> 1), 320 * (u & 1), fb);
                tma_ld2(sb + e * 40960 + 20480, &mp.w3h, 64 * (u >> 1), 320 * (u & 1) + 160, fb);
            };
            if (i > 4 && i < 9) {
                bar_sync(1, 512);
                if (warp == 0) {
                    signal_cnt(&g_cnt.uv[0], lane, 1);
                    if (elect()) {
#pragma unroll 1
                        for (int e = 0; e < 5; e++) refill(e, 5 * hs + e, bars + (5 + e) * 8);
                        l2_prefetch(pp.w2 + (size_t)160 * hs * D_, 160 * D_ * 2);
                    }
                    __syncwarp();
                }
            }
            mbar_wait(bars + i * 8, 0);
            float d[4];
            gemv_tile<7>(d, sb + b * 40960, sb + H_B, 5 * (un & 1));
            const int col = 16 * (warp & 3) + g;
            float* dst = r ? g_cs3 + (un & 1) * 1920 + 64 * ((u3 >> 1) - 10) + col : g_uv + (un & 1) * 3 * D_ + 2 * D_ + 64 * (un >> 1) + col;
            if (t == 3) { dst[0] = d[0]; dst[8] = d[2]; }
            if (r == 0 && t == 2) { dst[-2 * D_] = d[0]; dst[8 - 2 * D_] = d[2]; dst[-D_] = d[1]; dst[8 - D_] = d[3]; }
            if (r == 1 || r == 2) {
                bar_sync(4 + wg, 128);
                if (wt == 0) refill(b, u3, bars + (i + 5) * 8);
            }
        }
        __syncthreads();
        if (warp == 0) signal_cnt(&g_cnt.cs[0], lane, 1);
        if (tid == 511) l2_prefetch(pp.w4 + (size_t)432 * hs * D_, 432 * D_ * 2);
        for (uint32_t it = 0; ld_cold(&g_cnt.cs[0]) < 4;) { if (++it > SPIN_LIMIT) SPIN_FAIL(47) }
        asm volatile("fence.acquire.gpu;" ::: "memory");
        if (tid < 432) {
            const int jj = 2 * hs + (tid >= 216), c = tid % 216;
            const float* src = g_cs3 + (c < 192 ? 192 * jj + c : 1344 + 24 * jj + c);
            const uint32_t s = split2(ldcg32f(src) + ldcg32f(src + 1920));
            stg128(&g_cs3b[432 * hs + tid], s, s & 0xffffu, 0, 0);
        }
        __syncthreads();
        if (warp == 0) signal_cnt(&g_cnt.cs2[0], lane, 1);
        if (tid == 0 && hs == 3) {
            uint32_t it = 0;
            while (ld_cold(&g_epoch) == e0) { __nanosleep(256); if (++it > (1u << 20)) SPIN_FAIL(48) }
        }
        return;
    }

    if (elect()) {
        if (warp == 15) {
            mbar_init(bars + B_IN * 8, 1); mbar_init(bars + B_IN * 8 + 8, 1);
            asm volatile("fence.mbarrier_init.release.cluster;" ::: "memory");
            mbar_expect(bars + B_IN * 8, 131 * 160);
            tma_ld2(sb + OFF_KIN, &mp.k, 80 * (id & 7), 64 * (id >> 3) - 3, bars + B_IN * 8);
            tma_ld2(sb + OFF_VIN, &mp.v, 80 * (id & 7), 64 * (id >> 3), bars + B_IN * 8);
        } else if (warp < 13) {
            const uint32_t n = (0x1C14111111881ull >> (4 * warp)) & 15;
#pragma unroll
            for (int i = 0; i < 4; i++) mbar_init(bars + warp * 64 + i * 8, n);
            if (warp == 11) { mbar_init(bars + B_XFREE * 8, 16); mbar_init(bars + B_OWN * 8, 8); }
            else if (warp < 11) {
#pragma unroll
                for (int i = 4; i < 8; i++) mbar_init(bars + warp * 64 + i * 8, n);
            }
            asm volatile("fence.mbarrier_init.release.cluster;" ::: "memory");
        }
    }
    asm volatile("" ::"l"(pp.s), "l"(pp.c), "l"(out));
    TR4((threadIdx.x & 31) == 0, warp)
    const int pr = id >> 1;
    const int grp = pr < 4 ? 15 : pr < 36 ? (pr - 4) & 7 : 8 + (pr - 36) % 7;
    const int j = 2 * (pr < 4 ? pr : pr < 36 ? (pr - 4) >> 3 : (pr - 36) / 7) + (id & 1);

    if (wg == 3) {
        TIDS
        const int sw = warp - 12;
        uint32_t ep = ld_cold(&g_epoch);
        TR4(lane == 0, 20 + sw)
        __syncthreads();
        TR4(lane == 0, 30 + sw)
        asm volatile("barrier.cluster.arrive.relaxed.aligned;" ::: "memory");
        if (sw == 0) {
#pragma unroll 1
            for (int n = 0; n < 12; n++) {
                wait_clock(c0, PF_T0 + PF_DT * n);
                if (elect()) l2_prefetch(n < 4 ? (const char*)pp.q + id * 20480 + n * 5120 : (const char*)pp.w_mod + id * 38400 + (n - 4) * 4800, n < 4 ? 5120 : 4800);
            }
        } else if (sw == 1) {
            wait_clock(c0, T_SSM);
            if (elect()) {
                mbar_expect(bars + B_SSM * 8, 20480);
                bulk_ld(sb + OFF_SSM, pp.ssm_k + (size_t)5 * id * S_, 20480, bars + B_SSM * 8);
            }
            mbar_spin(bars + B_KVS * 8, 0);
            signal_cnt(&g_cnt.kv[(id & 7) * 32], lane, 1, true);
            TS(lane == 0, 2)
            mbar_spin(bars + B_RAW * 8, 0);
            if (elect()) {
                mbar_expect(bars + B_QIN * 8, 20480);
                tma_ld3(sb + OFF_QIN, &mp.q, 0, 16 * id, 0, bars + B_QIN * 8);
            }
        } else if (sw == 2) {
            if (elect()) {
#pragma unroll 1
                for (int i = 2; i < (int)(sizeof(Maps) / sizeof(CUtensorMap)); i++) asm volatile("prefetch.tensormap [%0];" ::"l"(&mp.k + i) : "memory");
#pragma unroll 1
                for (int i = B_SUMS; i < B_SIG; i++) mbar_expect(bars + i * 8, i < B_RECV ? 2048 : (i & 3) < 3 ? 8192 : 3072);
            }
            wait_cnt(&g_cnt.kv[(id >> 4) * 32], 16, true);
            TS(lane == 0, 4)
            if (elect()) {
                mbar_expect(bars + B_RAW * 8, 12288);
                mbar_expect(bars + B_RAW2 * 8, 8192);
#pragma unroll
                for (int c = 0; c < 5; c++) bulk_ld(sb + OFF_CH + c * CH_BYTES, g_kvT + (size_t)(5 * id + c) * S_, 4096, bars + (c < 3 ? B_RAW : B_RAW2) * 8);
            }
            mbar_spin(bars + B_BK * 8, 0);
            mbar_spin(bars + B_QIN * 8, 0);
            if (id < 120 && elect()) {
                mbar_expect(bars + B_WM * 8, 40960);
                tma_ld2(sb + OFF_WM, &mp.wmod, 64 * pr, 320 * (id & 1), bars + B_WM * 8);
                tma_ld2(sb + OFF_WM + 20480, &mp.wmod, 64 * pr, 320 * (id & 1) + 160, bars + B_WM * 8);
            }
            TS(lane == 0, 57)
        } else {
            wait_clock(c0, T_KVB);
            if (elect()) {
                mbar_expect(bars + (B_IN + 1) * 8, 131 * 160);
                tma_ld2(sb + OFF_KIN + 10752, &mp.k, 80 * (id & 7), 64 * (id >> 3) + 1021, bars + (B_IN + 1) * 8);
                tma_ld2(sb + OFF_VIN + 10240, &mp.v, 80 * (id & 7), 64 * (id >> 3) + 1024, bars + (B_IN + 1) * 8);
            }
            TS(lane == 0, 53)
            if (lane == 0) sts32(sb + M_EP, ep + 1);
            sts32(sb + M_NUL + lane * 4, 0);
#pragma unroll 1
            for (int i = 0; i < 10; i++) sts128(sb + OFF_Z + i * 512 + lane * 16, 0, 0, 0, 0);
            __syncwarp();
#pragma unroll 1
            for (int i = lane; i < 160; i += 32) {
                const uint32_t c = ldg32(pp.c + 320 * (id & 1) + 2 * i);
                sts32(sb + OFF_Z + (i >> 2) * 128 + (i & 3) * 4, pack2(silu(blo(c)), silu(bhi(c))));
            }
            fence_async_smem();
            for (uint32_t ph = 0, again = 1; again; ph ^= 1) {
                mbar_spin(bars + B_RAW2 * 8, ph);
                uint32_t bad = 0;
#pragma unroll
                for (int i = 0; i < 8; i++) bad |= lop3<0x7E>(lds32(sb + OFF_CH + 3 * CH_BYTES + i * 512 + lane * 16), ~ep, lds32(sb + OFF_CH + 4 * CH_BYTES + i * 512 + lane * 16));
                again = __any_sync(~0u, bad & 1);
                if (again && elect()) {
                    mbar_expect(bars + B_RAW2 * 8, 8192);
#pragma unroll
                    for (int c = 3; c < 5; c++) bulk_ld(sb + OFF_CH + c * CH_BYTES, g_kvT + (size_t)(5 * id + c) * S_, 4096, bars + B_RAW2 * 8);
                }
            }
            if (elect()) mbar_arrive(bars + B_RAW3 * 8);
        }
        {
            mbar_spin(bars + B_QIN * 8, 0);
            asm volatile("add.u32 %0, %0, 1;" : "+r"(ep));
            TS(wt == 0, 54)
            const int tk = 8 * ((lane >> 1) & 1) + 2 * (lane >> 3) + (lane & 1), ck = 4 * (sw & 1) + ((lane >> 1) & 2);
            const uint32_t src = sb + OFF_QIN + (sw >> 1) * 2048 + tk * 128;
            bf16* dst = g_qT + (size_t)id * 16 * D_ + (32 * sw + 8 * (t & 2) + g) * 16 + 8 * (t & 1);
constexpr int QU = Q_UNROLL;
#pragma unroll QU
            for (int i = 0; i < 5; i++) {
                uint32_t r[8];
                ldsm4t(src + i * 4096 + ((ck ^ (tk & 7)) << 4), r[0], r[1], r[2], r[3]);
                ldsm4t(src + i * 4096 + (((ck + 1) ^ (tk & 7)) << 4), r[4], r[5], r[6], r[7]);
                stg128(dst + i * 2048, tag(r[0], ep), r[1], r[2], r[3]);
                stg128(dst + i * 2048 + 128, tag(r[4], ep), r[5], r[6], r[7]);
            }
            float s1 = 0.f, s2 = 0.f;
#pragma unroll 2
            for (int i = 0; i < 10; i++) {
                const uint4 w4 = lds128(sb + OFF_QIN + i * 2048 + wt * 16);
                const uint32_t w[4] = {w4.x, w4.y, w4.z, w4.w};
#pragma unroll
                for (int e = 0; e < 4; e++) { const float a = blo(w[e]), b = bhi(w[e]); s1 += a + b; s2 = fmaf(a, a, fmaf(b, b, s2)); }
            }
#pragma unroll
            for (int o = 1; o < 8; o *= 2) { s1 += __shfl_xor_sync(~0u, s1, o); s2 += __shfl_xor_sync(~0u, s2, o); }
            s1 *= 1.f / D_;
            uint32_t rs = pack2(rsqrtf(fmaxf(s2 * (1.f / D_) - s1 * s1, 0.f) + 1e-5f), 0.f);
            if (lane < 8) rs = tag(rs, ep);
            rs = pack2(blo(rs), -s1 * blo(rs));
            const uint32_t sel = lane ? 0x7632 : 0x5410;
            const uint32_t a0 = __shfl_sync(~0u, rs, 0), a1 = __shfl_sync(~0u, rs, 8), a2 = __shfl_sync(~0u, rs, 16), a3 = __shfl_sync(~0u, rs, 24);
            if (lane < 2) stg64(g_qst + lane * S_ + 16 * id + 4 * sw, tag(__byte_perm(a0, a1, sel), ep), __byte_perm(a2, a3, sel));
            TS(wt == 0, 55)
        }
        bar_sync(6, 128);
        if (sw == 3) {
            signal_cnt(&g_cnt.q[(lane & 3) * 32], lane, 4, true);
            TS(lane == 0, 3)
        }
        asm volatile("setmaxnreg.dec.sync.aligned.u32 32;");
        asm volatile("barrier.cluster.wait.aligned;" ::: "memory");
        if (sw == 1) {
            mbar_spin(bars + B_XS * 8, 0);
            signal_cnt(&g_cnt.x[(lane & 3) * 32], lane, 4, true);
            TS(lane == 0, 20)
#pragma unroll 1
            for (int e = 1; e < 3; e++) {
                wait_cnt(e == 1 ? &g_cnt.g1[min(grp + 15 + min(lane, 2), 31) * 32] : &g_cnt.g2[(grp + 16) * 32], 32, true);
                if (elect()) mbar_arrive(bars + (B_GATE + 2 + e) * 8);
                TS(lane == 0, 27 + 2 * e)
            }
            return;
        }
        if (sw == 2) {
            mbar_spin(bars + B_XS * 8, 0);
            fence_async_smem();
            const unsigned* flag = &g_cnt.x[(id & 3) * 32];
            uint32_t m = 0;
            int n = 0, a0 = 0, a1 = 0;
            uint32_t k = 0;
#pragma unroll 1
            for (int s = 0; s < 6; s++) {
                const int e = s >> 1, end = 20 * e + ((s & 1) ? 20 : e == 0 ? LEAD1 : e == 1 ? 10 : XLEAD);
                if (s & 1) mbar_spin(bars + (B_GATE + 2 + e) * 8, !e);
                else {
                    wait_cnt(flag, e ? 32 : 128, true);
                    flag = e ? &g_cnt.g2[grp * 32] : &g_cnt.g1[max(grp - 1 + min(lane, 2), 0) * 32];
                    m = e == 0 ? M0 : e == 1 ? M1 : M2;
                    k = e ? 0 : (j & 1) * 0x400040;
                    a0 = e ? 0 : 64 * grp; a1 = e == 0 ? 0 : e == 1 ? 64 * grp : 640 * grp;
                    TS(lane == 0, 26 + 2 * e)
                }
                const int b0 = e ? 0 : 1024, b1 = e == 0 ? 0 : e == 1 ? 1024 : 10240, step = e ? 64 : 128;
                const uint32_t turn = e ? 1 : 512 + 64 * (j & 1), back = -448 - 128 * (j & 1);
#pragma unroll 1
                for (; n < end; n++, m >>= 1) {
                    const uint32_t w = m & 1, sh = 16 * w, kc = (k >> sh) & 0xffff;
                    k += (kc == turn ? back : step) << sh;
                    const uint32_t fb = bars + (B_LAND + (n & 7)) * 8;
                    mbar_spin(fb - (B_LAND - B_XEMPTY) * 8, ((n >> 3) & 1) ^ 1);
                    TR2(lane == 0 && n < 40, 20 + n)
                    if (elect()) {
                        mbar_expect(fb, 8192);
                        tma_ld2(sb + OFF_XR + (n & 7) * 8192, &mp.x[e], a0 + w * b0 + (e == 1 ? kc : 0), a1 + w * b1 + (e == 1 ? 0 : kc), fb);
                    }
                }
            }
            mbar_spin(bars + B_VEC3 * 8, 0);
            unsigned old = 0;
            asm volatile("{\n.reg .pred P;\nsetp.eq.s32 P, %2, 0;\n@P atom.relaxed.gpu.global.add.u32 %0, [%1], %3;\n}" : "+r"(old) : "l"(&g_cnt.done[0]), "r"(lane), "r"(1) : "memory");
            if (__any_sync(~0u, old == 127)) {
#pragma unroll 1
                for (int i = lane; i < (int)(sizeof(Counters) / 128); i += 32) reinterpret_cast<unsigned*>(&g_cnt)[i * 32] = 0;
                signal_cnt(&g_epoch, lane, 1, true);
            }
        } else if (sw == 0) {
            wait_cnt(&g_cnt.wr[0], 4);
            mbar_spin(bars + B_QRDY * 8, 0);
            const uint32_t wf = bars + B_WFULL * 8, we = bars + B_WEMPTY * 8;
#pragma unroll 1
            for (int n = 0; n < 5; n++) {
                if (n == 3) { mbar_spin(bars + B_XS * 8, 0); fence_async_smem(); }
                TR2(lane == 0, 70 + n)
                if (elect()) {
                    const uint32_t fb = wf + n * 8, dst = sb + OFF_W + n * 16384;
                    mbar_expect(fb, 20480);
#pragma unroll 1
                    for (int h = 0; h < 2; h++) {
                        const int kb = g1_block(2 * n + h, j);
                        tma_ld2(dst + h * 8192, &mp.w1, 64 * j, 64 * kb, fb);
                        bulk_ld(sb + OFF_REM + n * 4096 + h * 2048, &g_wr[(j * 10 + kb) * 128], 2048, fb);
                    }
                }
            }
            mbar_spin(bars + B_GATE * 8, 0);
#pragma unroll 1
            for (int i = -3; i < 5; i++) {
                const int n = i < 0 ? 8 + i : 5 + i;
                const uint32_t fb = wf + (n & 7) * 8;
                if (i >= 0) mbar_spin(we + i * 8, 0);
                TR2(lane == 0 && i >= 0, 70 + n)
                if (elect()) {
                    if (i < 0 || i >= 3) { mbar_expect(fb, 20480); tma_ld5(sb + OFF_W + (n & 7) * 16384, n < 9 ? &mp.w2a : &mp.w2b, 64 * j, n < 9 ? 4 * (n - 5) : 0, fb); }
                    if (i >= 0) bulk_ld(sb + OFF_REM + i * 4096, &g_wr[((8 + j) * 10 + 2 * i) * 128], 4096, fb);
                }
            }
            mbar_spin(bars + (B_GATE + 1) * 8, 0);
#pragma unroll 1
            for (int n = 10; n < 30; n++) {
                if (n == W3_N2) mbar_spin(bars + (B_GATE + 2) * 8, 0);
                mbar_spin(we + (n & 7) * 8, ((n >> 3) & 1) ^ 1);
                TR2(lane == 0, 70 + n)
                if (elect()) {
                    const uint32_t dst = sb + OFF_W + (n & 7) * 16384, fb = wf + (n & 7) * 8;
                    mbar_expect(fb, 13824);
                    tma_ld3(dst, &mp.w3a, 0, 32 * (n - 10), 3 * j, fb);
                    tma_ld2(dst + 12288, &mp.w3b, 1536 + 24 * j, 32 * (n - 10), fb);
                }
            }
            mbar_spin(we + 6 * 8, 0);
            mbar_spin(bars + B_VEC3 * 8, 0);
            if (elect()) { mbar_expect(wf + 6 * 8, 3456); bulk_ld(sb + OFF_W + 6 * 16384, &g_cs3b[216 * j], 3456, wf + 6 * 8); }
#pragma unroll 1
            for (int n = 31; n < 50; n++) {
                const int e = n < 38 ? 4 : (n - 38) & 3, m0 = n == 35, m1 = e == 3 ? -1 : m0 | (e == 1), rem = 96 + 3 * (j >> 1);
                const int c1_ = j ^ (n < 38 ? 6 : 4 >> ((n - 38) >> 2) & 6), c0_ = n < 38 ? 8 + (j & 1) : c1_;
                const int f = (0xC840A80C204ull >> (4 * min(n - 31, e + 7))) & 15;
                const int r0 = m0 ? rem : 6 * (j ^ (f >> 3)) + (f & 6), r1 = m1 ? rem : r0 + (n < 38 ? 0 : 2);
                mbar_spin(we + (n & 7) * 8, ((n >> 3) & 1) ^ 1);
                if (elect()) {
                    const uint32_t dst = sb + OFF_W + (n & 7) * 16384, fb = wf + (n & 7) * 8;
                    mbar_expect(fb, m1 < 0 ? 8192 : 16384 - 2048 * (m0 + m1));
                    tma_ld2(dst, &mp.w4[m0], 64 * c0_, r0 * (32 >> m0), fb);
                    if (m1 >= 0) tma_ld2(dst + 8192, &mp.w4[m1], 64 * c1_, r1 * (32 >> m1), fb);
                }
            }
#pragma unroll 1
            for (int w = 0; w < 2; w++) {
                const uint4* src = g_part + (size_t)(grp + 16 * w) * 40960;
                mbar_spin(bars + (B_RING + w) * 8, 1);
                if (elect()) {
                    const uint32_t fb = bars + (B_IN + w) * 8, rem = sb + OFF_OUT + w * 10240;
                    mbar_expect(fb, 10240);
                    bulk_ld(rem + 8192, &g_x1f[((grp + 16 * w) * 8 + j) * 640 + 512], 2048, fb);
#pragma unroll 1
                    for (int i = 0; i < 4; i++) bulk_ld(rem + i * 2048, src + ((j >> 2) + 2 * i) * 5120 + 4096 + j * 128, 2048, fb);
                }
            }
        } else {
            {
                wait_cnt(&g_cnt.tab[0], 1);
                mbar_spin(bars + B_QRDY * 8, 0);
                if (elect()) {
                    mbar_expect(bars + B_TAB * 8, TAB_BYTES / 2 + VEC_BYTES);
                    bulk_ld(sb + OFF_TAB, g_tab + (j & 1) * (TAB_BYTES / 32), TAB_BYTES / 2, bars + B_TAB * 8);
                    bulk_ld(sb + M_GB, g_tab + (TAB_BYTES + j * VEC_BYTES) / 16, VEC_BYTES, bars + B_TAB * 8);
                }
                TS(lane == 0, 5)
            }
            wait_cnt(&g_cnt.uv[0], 4);
#pragma unroll 1
            for (int c = lane; c < 80; c += 32) {
                const float* src = g_uv + (c < 64 ? 64 * j + c : 448 + 16 * j + c);
                const uint32_t u = split2(ldcg32f(src) + ldcg32f(src + 3 * D_)), v = split2(ldcg32f(src + D_) + ldcg32f(src + 4 * D_));
                const uint32_t s = split2(ldcg32f(src + 2 * D_) + ldcg32f(src + 5 * D_));
                sts128(sb + OFF_F1 + c * 16, u, __byte_perm(u, v, 0x5410), __byte_perm(v, 0, 0x1032), s);
                sts128(sb + M_F1 + c * 16, s & 0xffffu, 0, 0, 0);
            }
            fence_async_smem();
            warp_arrive(bars + B_VEC * 8);
            TS(lane == 0, 9)
            wait_cnt(&g_cnt.cs2[0], 4);
            if (elect()) mbar_arrive(bars + B_VEC3 * 8);
            TS(lane == 0, 19)
        }
        return;
    }

    {
        uint32_t ep;
        {
            TIDS
            ep = ld_cold(&g_epoch);
            const int cp = (tid + 16) % 40, cp1 = tid % 40;
            const uint4 sh0 = ldg128(pp.shift_k + (80 * (id & 7) + 2 * cp1) * 4), sh1 = ldg128(pp.shift_k + (80 * (id & 7) + 2 * cp) * 4);
            uint32_t dd;
            asm volatile("ld.global.nc.u16 %0, [%1];" : "=r"(dd) : "l"(pp.ssm_D + 5 * id + min(wg + 3 * lane, 4)));
            TR4(lane == 0, 40 + warp)
            __syncthreads();
            asm volatile("barrier.cluster.arrive.relaxed.aligned;" ::: "memory");
            asm volatile("add.u32 %0, %0, 1;" : "+r"(ep));
#pragma unroll 1
            for (int hw = 0; hw < 2; hw++) {
                if ((unsigned)(warp - 2 * hw) >= 10) continue;
                const int u = tid - 64 * hw;
                const int c = hw ? cp : cp1, oc = u / 40, line = 31 - 16 * hw - (id >> 3);
                const uint4 sh = hw ? sh1 : sh0;
                const uint32_t st = sb + OFF_ST + hw * 10240, sta = st + c * 256 + ((((6 - 2 * (oc & 3)) ^ (oc >> 2) ^ (line & 1)) ^ (c & 7)) << 4), in = oc * 1280 + c * 4;
                const uint32_t f0 = __byte_perm(sh.x, sh.z, 0x5410), f1 = __byte_perm(sh.x, sh.z, 0x7632), f2 = __byte_perm(sh.y, sh.w, 0x5410), f3 = __byte_perm(sh.y, sh.w, 0x7632);
                uint32_t kk[11], vv[8];
                mbar_spin(bars + (B_IN + hw) * 8, 0);
                TS(tid == 64, 18 + 42 * hw)
#pragma unroll
                for (int i = 0; i < 11; i++) kk[i] = lds32(sb + OFF_KIN + hw * 10752 + in + i * 160);
#pragma unroll
                for (int i = 0; i < 8; i++) vv[i] = lds32(sb + OFF_VIN + hw * 10240 + in + i * 160);
#pragma unroll
                for (int i = 0; i < 8; i++) vv[i] = mul2(fma2(kk[i + 3], f0, fma2(kk[i + 2], f1, fma2(kk[i + 1], f2, mul2(kk[i], f3)))), vv[i]);
                sts128(sta, tag(__byte_perm(vv[0], vv[1], 0x5410), ep), __byte_perm(vv[2], vv[3], 0x5410), __byte_perm(vv[4], vv[5], 0x5410), __byte_perm(vv[6], vv[7], 0x5410));
                sts128(sta + 128, tag(__byte_perm(vv[0], vv[1], 0x7632), ep), __byte_perm(vv[2], vv[3], 0x7632), __byte_perm(vv[4], vv[5], 0x7632), __byte_perm(vv[6], vv[7], 0x7632));
                bar_sync(7 + hw, 320);
                flush_tile(st, g_kvT + (size_t)(80 * (id & 7)) * S_ + 64 * line, u);
                TS(tid == 64 && hw, 1)
            }
            warp_arrive(bars + B_KVS * 8);
            if (tid < 320) sts128(sb + OFF_CH + (tid >> 6) * CH_BYTES + 4096 + (tid & 63) * 16, 0, 0, 0, 0);
            mbar_spin(bars + B_SSM * 8, 0);
            TS(tid == 0, 14)
            uint2 w[7];
            uint32_t pv[7];
#pragma unroll
            for (int i = 0; i < 7; i++) {
                const uint32_t a = sb + OFF_SSM + min(wg + 3 * i, 19) * 1024 + wt * 8;
                w[i] = lds64(a); pv[i] = lds32(a - 4);
            }
#pragma unroll
            for (int i = 0; i < 7; i++) {
                const int un = min(wg + 3 * i, 19);
                sts128(sb + OFF_CH + (un >> 2) * CH_BYTES + OFF_P + (un & 3) * 2048 + wt * 16, __byte_perm(w[i].x, pv[i], 0x7610), __byte_perm(w[i].x, 0, 0x1032), __byte_perm(w[i].y, w[i].x, 0x7610), __byte_perm(w[i].y, 0, 0x1032));
            }
            __syncwarp();
            if (wt < 2 - (wg >> 1)) {
                const uint32_t h = lds32(sb + OFF_SSM + (wg + 3 * wt) * 4096), h0 = pack2(blo(h) + blo(dd), 0.f);
                sts64f(sb + OFF_CH + (wg + 3 * wt) * CH_BYTES + OFF_P, __uint_as_float(h0), __uint_as_float(__byte_perm(h, h0, 0x5432)));
            }
            fence_async_smem();
            warp_arrive(bars + B_BK * 8);
            asm volatile("barrier.cluster.wait.aligned;" ::: "memory");
            mbar_spin(bars + B_BK * 8, 0);
            TS(tid == 0, 15)
        }

#pragma unroll 1
        for (int c = wg; c < 5; c += 3) {
            const uint32_t kvb = sb + OFF_CH + c * CH_BYTES;
            mbar_spin(bars + (c < 3 ? B_RAW : B_RAW3) * 8, 0);
            for (uint32_t ph = 0; c < 3; ph ^= 1) {
                const int wt = tid_now() & 127;
                if (!RARE(bar_any(1 + wg, lop3<0x7E>(lds32(kvb + wt * 16), ep, lds32(kvb + 2048 + wt * 16)) & 1))) break;
                if (wt == 0) { mbar_expect(bars + (B_RETRY + wg) * 8, 4096); bulk_ld(kvb, g_kvT + (size_t)(5 * id + c) * S_, 4096, bars + (B_RETRY + wg) * 8); }
                mbar_spin(bars + (B_RETRY + wg) * 8, ph);
                STALE1(3)
            }
            TS(threadIdx.x == 0, c ? 13 : 11)
            float acc[64];
            {
                const int l = tid_now() & 31;
                conv_channel(acc, kvb + OFF_P + (8 * (warp & 3) + (l >> 2) - 2 * (l & 3)) * 4, (((uint64_t)0xC0000010u << 32) | ((kvb & 0x3FFFF) >> 4) | 0x10000u) + pp.nil);
            }
            TS(threadIdx.x == 0, c ? 16 : 12)
            if (c < 3) warp_arrive(bars + B_R1 * 8);
            else mbar_spin(bars + B_R1 * 8, 0);
            if (wg == 2 && id < 120) {
                TIDS
                mbar_spin(bars + B_RAW3 * 8, 0);
                mbar_spin(bars + B_WM * 8, 0);
                TS(wt == 0, 56)
                float d[4];
                gemv_tile<8>(d, sb + OFF_WM, sb + OFF_Z, 0);
                const float d2 = __shfl_up_sync(~0u, d[2], 1);
                TS(wt == 0, 7)
                if (t < 2) asm volatile("{\n.reg .b64 v;\nmov.b64 v, {%1, %2};\nst.relaxed.gpu.global.b64 [%0], v;\n}" ::"l"(g_mod + (id & 1) * 6 * D_ + 64 * pr + 16 * (warp & 3) + g + 8 * t),
                                        "r"(__float_as_uint(t ? d2 : d[0])), "r"(lds32(sb + M_EP)) : "memory");
            }
            TR4(threadIdx.x == 0, 60 + (c >= 3) * 10)
            TIDS
            const int e = 127 - 8 * (lane >> 4) - (lane & 7), u0 = (warp & 3) + 8 * (e >> 2) + (e & 3) + 4 * ((lane >> 3) & 1);
            const uint32_t ring = sb + OFF_RING + c * 16384 + (warp & 3) * 4096, wa = ring + (u0 ^ ((u0 >> 1) & 4)) * 16;
            if (lane < (warp & 3)) sts128(ring + lane * 16, 0, 0, 0, 0);
#pragma unroll
            for (int i = 0; i < 8; i++)
                stsm4t(i == 0 && u0 >= 256 ? sb + M_SINK : wa - 512 * i, pack2(acc[8 * i], acc[8 * i + 1]), pack2(acc[8 * i + 2], acc[8 * i + 3]),
                       pack2(acc[8 * i + 4], acc[8 * i + 5]), pack2(acc[8 * i + 6], acc[8 * i + 7]));
            warp_arrive(bars + (B_RING + c) * 8);
            TR4(threadIdx.x == 0, 61 + (c >= 3) * 10)
        }
        TIDS
        if (wg == 2) bar_sync(3, 128);
        if (warp == 8) {
            wait_cnt(&g_cnt.q[(id & 3) * 32], 128, true);
            if (elect()) {
                mbar_expect(bars + B_QRDY * 8, 28672);
                tma_ld2(sb + OFF_QT, &mp.qT, 80 * id, 0, bars + B_QRDY * 8);
                bulk_ld(sb + OFF_QT + 20480, g_qst, 8192, bars + B_QRDY * 8);
            }
            TS(lane == 0, 8)
        } else if (warp == 9) {
            const int v = min(lane / 5, 3);
            const uint2* gm = g_mod + (v + (v == 3)) * D_ + 5 * id + lane % 5;
            const unsigned epoch = lds32(sb + M_EP);
            uint2 r0, r1;
            unsigned it = 0;
            do {
                r0 = ld_mod(gm); r1 = ld_mod(gm + 6 * D_);
                SPIN_CHECK(55)
            } while (!__all_sync(~0u, r0.y == epoch && r1.y == epoch));
            const float m0 = __uint_as_float(r0.x), m1 = __uint_as_float(r1.x);
            const float m = rbf(m0 + m1), p = rbf(1.f + m);
            const float cz = zscale(__shfl_sync(~0u, p, 15 + lane % 5)), ga = __shfl_sync(~0u, m, 10 + lane % 5);
            if (lane < 15) sts32(sb + M_AB + lane % 5 * 16 + v * 4, lane < 10 ? __float_as_uint(cz * ga * (lane < 5 ? m : p)) : pack2(cz, cz));
            warp_arrive(bars + B_MODR * 8);
            TS(lane == 0, 6)
        }
        mbar_spin(bars + B_QRDY * 8, 0);
        uint4 rs[2], nm[2];
#pragma unroll
        for (int h = 0; h < 2; h++) { rs[h] = lds128(sb + OFF_QT + 20480 + h * 2048 + wt * 16); nm[h] = lds128(sb + OFF_QT + 24576 + h * 2048 + wt * 16); }
        mbar_spin(bars + B_MODR * 8, 0);
        TR4(threadIdx.x == 0, 72)
        uint32_t it = 0;
        while (RARE(__any_sync(~0u, (lop3<0x7E>(rs[0].x, ep, rs[0].z) | lop3<0x7E>(nm[0].x, ep, nm[0].z) | lop3<0x7E>(rs[1].x, ep, rs[1].z) | lop3<0x7E>(nm[1].x, ep, nm[1].z)) & 1))) {
#pragma unroll
            for (int h = 0; h < 2; h++) { rs[h] = ld_part(g_qst + 1024 * h + 8 * wt); nm[h] = ld_part(g_qst + S_ + 1024 * h + 8 * wt); }
            STALE(1)
            SPIN_CHECK(53)
        }
        TR4(threadIdx.x == 0, 73)
#pragma unroll 1
        for (int c = wg == 2 ? 0 : 3 + wg; c < (wg == 2 ? 3 : 4 + wg); c++) {
            uint4 q[2], p[2][4];
#pragma unroll
            for (int h = 0; h < 2; h++) q[h] = lds128(sb + OFF_QT + h * 10240 + (wt >> 1) * 160 + c * 32 + (wt & 1) * 16);
            const float4 ab = lds128f(sb + M_AB + c * 16);
            mbar_spin(bars + (B_RING + c) * 8, 0);
            TR4(wt == 0, wg == 2 ? 80 + 2 * c : 74)
#pragma unroll
            for (int i = 0; i < 8; i++) p[i >> 2][i & 3] = lds128(sb + OFF_RING + c * 16384 + (i & 3) * 4096 + (i >> 2) * 2048 + (wt ^ ((wt >> 1) & 4)) * 16);
            while (RARE(__any_sync(~0u, lop3<0x7E>(q[0].x, ep, q[1].x) & 1))) {
#pragma unroll
                for (int h = 0; h < 2; h++) q[h] = ld_part(g_qT + ((64 * h + (wt >> 1)) * D_ + 5 * id + c) * 16 + 8 * (wt & 1));
                STALE(2)
                SPIN_CHECK(52)
            }
            TR4(wt == 0, wg == 2 ? 81 + 2 * c : 75)
#pragma unroll
            for (int h = 0; h < 2; h++) {
                const uint32_t qq[4] = {q[h].x, q[h].y, q[h].z, q[h].w}, r4[4] = {rs[h].x, rs[h].y, rs[h].z, rs[h].w}, n4[4] = {nm[h].x, nm[h].y, nm[h].z, nm[h].w};
                const uint4 y = add2(add2(p[h][0], p[h][1]), add2(p[h][2], p[h][3]));
                const uint32_t yy[4] = {y.x, y.y, y.z, y.w};
                uint32_t o[4];
#pragma unroll
                for (int i = 0; i < 4; i++) {
                    const uint32_t n = fma2(qq[i], r4[i], n4[i]);
                    o[i] = fma2(pack2(fmaf(blo(n), ab.y, ab.x), fmaf(bhi(n), ab.y, ab.x)), yy[i], mul2(qq[i], __float_as_uint(ab.z)));
                }
                stg128_tag(g_x1T + (size_t)(5 * id + c) * S_ + 1024 * h + 8 * wt, o[0], o[1], o[2], o[3], ep, ((5 * id + c) >> 3) & 3);
            }
        }
        warp_arrive(bars + B_XS * 8);
        TS(tid == 0, 17)
        TS(tid == 256, 52)
    }

    const uint32_t nil = pp.nil;
    const int wq = warp & 3;
    if (wg == 2) {
        TIDS
        asm volatile("setmaxnreg.dec.sync.aligned.u32 32;");
        {
            const uint32_t ep = lds32(sb + M_EP);
            uint32_t ph = 0;
#pragma unroll 1
            for (int m = wq - 4; m < 60; m += 4) {
                const int n = max(m, 0);
                const int e = (n >= 20) + (n >= 40), i = n - 20 * e;
                const uint32_t M = e == 0 ? M0 : e == 1 ? M1 : M2;
                const int w = (M >> i) & 1, c = __popc(M & ((1u << i) - 1)), kb = w ? c : i - c;
                const uint32_t a = sb + OFF_XR + (n & 7) * 8192;
                uint32_t ta = a + (e == 0 ? lane * 128 + ((lane & 7) << 4) + (lane >> 3) * 4
                                 : e == 1 ? (lane & 15) * 128 + (((lane >> 4 << 1) ^ (lane & 7)) << 4) + (lane & 8) + (lane >> 4) * 4
                                          : lane * 32 + (lane >> 2) * 4);
                uint32_t tb = e == 0 ? ta ^ 32 : ta + 2048, tc = e == 2 ? ta + 1024 : ta ^ 64, td = e == 2 ? tb + 1024 : tb ^ 64;
                uint32_t live = m >= 0,
                    f0 = bars + (B_XFULL + 8 * w + ((10 * e + kb) & 7)) * 8;
                uint32_t f1 = m == GATE_W2 || m == GATE_W3 || m == GATE_W3B ? bars + (B_GATE + (m >= GATE_W3) + (m >= GATE_W3B)) * 8 : 0;
                if (lane) f0 = f1;
                if (lane > 1 || m < 0) f0 = 0;
                asm volatile("" : "+r"(ta), "+r"(tb), "+r"(tc), "+r"(td), "+r"(live), "+r"(f0));
                mbar_spin(bars + (m < 0 ? B_BK : B_LAND + (n & 7)) * 8, (n >> 3) & 1);
                TR5(lane == 0, n)
                while (true) {
                    uint32_t v[8];
#pragma unroll
                    for (int i = 0; i < 8; i++) v[i] = lds32(((i & 2) ? ((i & 1) ? td : tc) : (i & 1) ? tb : ta) + (i >> 2) * 4096);
                    const uint32_t bad = lop3<0xFE>(lop3<0x7E>(v[0], ep, v[1]), lop3<0x7E>(v[2], ep, v[3]), lop3<0x7E>(v[4], ep, v[5]));
                    if (!RARE(__any_sync(~0u, lop3<0xA8>(bad, lop3<0x7E>(v[6], ep, v[7]), live)))) break;
                    if (elect()) load_tile(mp, a, e, grp + 16 * w, kb, j, bars + (B_AGAIN + wq) * 8);
                    mbar_spin(bars + (B_AGAIN + wq) * 8, ph);
                    ph ^= 1;
                    STALE1(e)
                }
                TR5(lane == 0, 60 + n)
                if (f0) mbar_arrive(f0);
            }
        }
#pragma unroll 1
        for (int uw = 0; uw < 2; uw++) {
            const int tile = grp + 16 * uw;
            const uint32_t ep = lds32(sb + M_EP), in = sb + OFF_OUT + uw * 10240 + wt * 16, sr = in - lane * 16;
            mbar_wait(bars + (B_IN + uw) * 8, 1);
            float r[8] = {};
#pragma unroll 1
            for (int h = 0; h < 2; h++) {
                uint4 a = lds128(in + h * 4096), b = lds128(in + h * 4096 + 2048);
                uint32_t it = 0;
                while (RARE(__any_sync(~0u, ((a.x ^ ep) | (b.x ^ ep)) & 1))) {
                    const uint4* p = g_part + (size_t)tile * 40960 + ((j >> 2) + 4 * h) * 5120 + 4096 + j * 128 + wt;
                    a = ld_part(p); b = ld_part(p + 10240);
                    STALE(3)
                    if (++it > SPIN_LIMIT) SPIN_FAIL(58)
                }
                add8(r, add2(a, b));
            }
            base16(r, lds128(in + 8192), lds64f(sb + M_GB + (64 + 2 * t) * 4), lds64f(sb + M_GB + (72 + 2 * t) * 4));
            __syncwarp();
            stsm4(sr + (lane & 15) * 32 + (((lane >> 4) ^ ((lane >> 2) & 1)) << 4), pack2(r[0], r[1]), pack2(r[2], r[3]), pack2(r[4], r[5]), pack2(r[6], r[7]));
            __syncwarp();
            stg128(out + (size_t)(64 * tile + 16 * wq + (lane >> 1)) * D_ + 512 + 16 * j + 8 * (lane & 1), lds128(sr + (lane >> 1) * 32 + (((lane & 1) ^ ((lane >> 3) & 1)) << 4)));
            __syncwarp();
        }
        if (wq == 0) {
            uint32_t it = 0;
            while (!mbar_try(bars + B_OWN * 8, 0)) { if (++it > SPIN_LIMIT) SPIN_FAIL(56) }
        }
        return;
    }

    TIDS
    const int uw = wg, tile = grp + 16 * uw, row0 = 64 * tile + 16 * wq;
    const bool leader = wt == 0; (void)leader;
    const uint32_t xfull = bars + (B_XFULL + 8 * uw) * 8, xempty = bars + B_XEMPTY * 8, wfull = bars + B_WFULL * 8, wempty = bars + B_WEMPTY * 8;
    const uint64_t dz = mkdesc(0) + pp.nil;
    auto xwait = [&](uint32_t n) { mbar_spin(xfull + (n & 7) * 8, (n >> 3) & 1); };
    asm volatile("setmaxnreg.inc.sync.aligned.u32 224;");
    const uint32_t ep = lds32(sb + M_EP);
    uint32_t res[20] = {};
    {
        float acc[40];
        const uint32_t la = ((lane & 7) + 8 * (lane >> 4)) * 128 + (((2 * wq + ((lane >> 3) & 1)) ^ (lane & 7)) << 4);
        auto pos = [&](int n) { return ring_pos(uw, n, LEAD1) & 7; };
        auto slot = [&](int n) { return sb + OFF_XR + pos(n) * 8192; };
        float al[2], r1[2], n1[2];
        {
            float sl[4], sq[4], v[4];
            uint32_t z0[16], z1[16], zz[16];
            uint64_t bd = dz + b80_desc(dsb, 0, 0, 0), tb = (((uint64_t)8 << 32) | ((dsb + OFF_TAB) >> 4) | (7u << 16)) + pp.nil;
            auto ldfrag = [&](uint32_t (&z)[16], int n) {
#pragma unroll
                for (int q = 0; q < 4; q++) ldsm4t(slot(n) + la + q * 2048, z[4 * q], z[4 * q + 1], z[4 * q + 2], z[4 * q + 3]);
            };
            auto tile1 = [&](const uint32_t (&zc)[16], uint32_t (&zn)[16], int n, int h) {
                const bool last = h && n == 5, ok = mbar_test(xfull + (n + 1) * 8, 0), okw = !h || mbar_test(wfull + ((n + 1) >> 1) * 8, 0);
                const int kb = g1_block(n, j);
                wg_fence();
#pragma unroll
                for (int q = 0; q < 2; q++) wgmma_rs80(acc, zc[4 * q], zc[4 * q + 1], zc[4 * q + 2], zc[4 * q + 3], bd + q * B80_STEP, 1);
                wg_commit();
                wg_wait<1>();
                if (!ok) xwait(n + 1);
                if (!last) ldfrag(zn, n + 1);
#pragma unroll
                for (int e = 0; e < 16; e++) zz[e] = mul2(zc[e], zc[e]);
                const uint64_t t0 = last ? ((uint64_t)8 << 32) | ((dsb + M_NUL) >> 4) : tb;
                const uint32_t ts = last ? 0 : 14;
                wg_fence();
#pragma unroll
                for (int q = 0; q < 4; q++) wgmma_rs8(sl, zc[4 * q], zc[4 * q + 1], zc[4 * q + 2], zc[4 * q + 3], t0 + q * ts, 1);
#pragma unroll
                for (int q = 0; q < 4; q++) wgmma_rs8(sq, zz[4 * q], zz[4 * q + 1], zz[4 * q + 2], zz[4 * q + 3], t0 + q * ts, 1);
#pragma unroll
                for (int q = 2; q < 4; q++) wgmma_rs80(acc, zc[4 * q], zc[4 * q + 1], zc[4 * q + 2], zc[4 * q + 3], bd + q * B80_STEP, 1);
                wg_commit();
#pragma unroll
                for (int q = 0; q < 4; q++) ldsm4t_if(kb == j, slot(n) + la + q * 2048, &res[4 * q]);
                if (!h) ldsm4t_if(kb == 8 + (j >> 2), slot(n) + la + (j & 3) * 2048, &res[16]);
                if (lane < 2) mbar_arrive_after(xempty + pos(n) * 8, res[12], res[16], nil);
                if (!h && n && lane == 0) mbar_arrive(wempty + ((n >> 1) - 1) * 8);
                tb += 56;
                bd = bd + (uint64_t)B80_HALF;
                if (!okw) mbar_spin(wfull + ((n + 1) >> 1) * 8, 0);
                TR(leader, 100 + 10 * uw + n)
            };
            zero(acc); zero(sl); zero(sq);
            mbar_spin(bars + B_TAB * 8, 0);
            mbar_spin(wfull, 0);
            xwait(0);
            TS(leader, 32 + uw)
            ldfrag(z0, 0);
#pragma unroll 1
            for (int n = 0; n < 6; n += 2) { tile1(z0, z1, n, 0); tile1(z1, z0, n + 1, 1); }
#pragma unroll
            for (int n = 6; n < 10; n++) {
                const uint64_t ad = dz + (((dsb + OFF_XR + pos(n) * 8192) >> 4) | 0x10000u);
                const bool ok = n == 9 || mbar_test(xfull + ((n + 1) & 7) * 8, (n + 1) >> 3), okw = n != 7 || mbar_test(wfull + 4 * 8, 0);
                wg_fence();
#pragma unroll
                for (int q = 0; q < 4; q++) wgmma_ss80t(acc, ad + q * 128, bd + q * B80_STEP, 1);
                wg_commit();
                bd = bd + (uint64_t)B80_HALF;
                if (n == 9) ldsm4t_if(9 - (j & 1) == 8 + (j >> 2), slot(9) + la + (j & 3) * 2048, &res[16]);
                wg_wait<1>();
                if (n > 6 && lane < 2) mbar_arrive(xempty + pos(n - 1) * 8);
                if (!(n & 1) && lane == 0) mbar_arrive(wempty + ((n >> 1) - 1) * 8);
                if (n == 6) {
                    reg_fence(sl); reg_fence(sq);
#pragma unroll
                    for (int e = 0; e < 2; e++) {
                        v[2 * e] = t == 0 ? sl[2 * e] + sl[2 * e + 1] : t == 1 ? sq[2 * e] + sq[2 * e + 1] : sl[2 * e];
                        v[2 * e + 1] = t == 2 ? sl[2 * e + 1] : sq[2 * e];
                    }
                    st_peer(peer_addr(sb + OFF_ROW + uw * 2048 + wt * 16), __float_as_uint(v[0]), __float_as_uint(v[1]), __float_as_uint(v[2]), __float_as_uint(v[3]), peer_addr(bars + (B_SUMS + uw) * 8));
                    TS(leader && !uw, 59)
                }
                if (!ok) xwait(n + 1);
                if (!okw) mbar_spin(wfull + 4 * 8, 0);
                TR(leader, 100 + 10 * uw + n)
            }
            float4 k = lds128f(sb + M_KS);
            float k4 = __uint_as_float(lds32(sb + M_KS + 16));
#pragma unroll
            for (int w = 1; w < 5; w++) {
                const float4 o = lds128f(sb + M_KS + w * 32);
                k.x += o.x; k.y += o.y; k.z += o.z; k.w += o.w; k4 += __uint_as_float(lds32(sb + M_KS + w * 32 + 16));
            }
            mbar_spin(bars + (B_SUMS + uw) * 8, 0);
            TS(leader && !uw, 10)
            const float4 o = lds128f(sb + OFF_ROW + uw * 2048 + wt * 16);
            v[0] += o.x; v[1] += o.y; v[2] += o.z; v[3] += o.w;
            uint32_t fa[4];
#pragma unroll
            for (int h = 0; h < 2; h++) {
                const int l0 = lane & ~3;
                const float s1 = __shfl_sync(~0u, v[2 * h], l0), s2 = __shfl_sync(~0u, v[2 * h], l0 + 1), scc = __shfl_sync(~0u, v[2 * h], l0 + 2);
                const float scs = __shfl_sync(~0u, v[2 * h + 1], l0 + 2), sc = __shfl_sync(~0u, v[2 * h], l0 + 3), sqq = __shfl_sync(~0u, v[2 * h + 1], l0 + 3);
                const float m1 = s1 * (1.f / D_), va = fmaxf(s2 * (1.f / D_) - m1 * m1, 0.f) + 1e-5f, r = rsqrtf(va);
                const float m2 = (r * (sc - m1 * k.x) + k.y) * (1.f / D_);
                const float e2 = (r * (r * (sqq + m1 * (m1 * k.z - 2.f * scc)) + 2.f * (scs - m1 * k.w)) + k4) * (1.f / D_);
                al[h] = r * 0.5f * rsqrtf(fmaxf(e2 - m2 * m2, 0.f) + 1e-5f); r1[h] = r; n1[h] = -m1 * r;
                const uint32_t fb = split2(va * r), fx = split2(t == 3 ? -m2 * va * r : -m1), fc = __shfl_sync(~0u, fx, lane | 3);
                fa[h] = __byte_perm(fx, fb, t == 1 ? 0x5432 : t == 2 ? 0x7654 : 0x1010);
                fa[2 + h] = t ? 0 : fc >> 16;
            }
            mbar_spin(bars + B_VEC * 8, 0);
            wg_fence();
            wgmma_rs80k(acc, fa[0], fa[1], fa[2], fa[3], ((uint64_t)8 << 32) | ((dsb + OFF_F1) >> 4) | (((M_F1 - OFF_F1) >> 4) << 16), 1);
            wg_commit();
        }
        wg_wait<0>();
        reg_fence(acc);
        if (lane < 2) mbar_arrive_after(xempty + pos(9) * 8, res[16], 0, nil);
        if (lane == 0) mbar_arrive(wempty + 4 * 8);
        TS(leader, 34 + uw)
        {
            bf16* const trow = g_t + (size_t)(row0 + g + 2) * D_;
#pragma unroll
            for (int b = 0; b < 3; b++) {
                uint32_t p[8];
#pragma unroll
                for (int ii = 0; ii < 4; ii++) {
                    const int i = 4 * b + ii;
                    if (i >= 10) continue;
#pragma unroll
                    for (int h = 0; h < 2; h++) p[(i & 3) + 4 * h] = pack2(gelu2(acc[4 * i + 2 * h] * al[h]), gelu2(acc[4 * i + 2 * h + 1] * al[h]));
                }
                if (b < 2) {
                    const int gr = (2 * j + b) / 5, sh = (gr & 1) ? -1 - (gr >> 1) : 1 + (gr >> 1);
                    bf16* dst = trow + 64 * j + 32 * b + 8 * t;
                    const int w = (((g + sh) >> 2) & 2) + (t >> 1);
                    stg128_tag(dst + sh * D_, p[0], p[1], p[2], p[3], ep, w);
                    stg128_tag(dst + (sh + 8) * D_, p[4], p[5], p[6], p[7], ep, w ^ 2);
                    if (row0 + g < sh || row0 + g + 8 >= S_ + sh) stg128_tag(dst + (sh > 0 ? 0 : 8) * D_, 0, 0, 0, 0, ep, (sh > 0 ? 0 : 2) + (t >> 1));
                } else {
                    bf16* dst = trow + 512 + 16 * j + 4 * t;
                    const uint32_t lo = t == (g < 2), hi = t == (g >= 2), o = j & 1;
                    stg64(dst - 2 * D_, lop3<0xB8>(p[0], lo & ~o, ep), lop3<0xB8>(p[1], lo & o, ep));
                    stg64(dst + 6 * D_, lop3<0xB8>(p[4], hi & ~o, ep), lop3<0xB8>(p[5], hi & o, ep));
                    if (row0 + g + 8 >= S_ - 2) stg64(dst + 8 * D_, ep & (t == 1) & ~o, ep & (t == 1) & o);
                }
            }
        }
        signal_cnt(&g_cnt.g1[tile * 32], lane, 1, true);
        TS(leader, 36 + uw)
#pragma unroll
        for (int i = 0; i < 10; i++) {
            const float2 c = lds64f(sb + M_C + (8 * i + 2 * t) * 4), s = lds64f(sb + M_SB + (8 * i + 2 * t) * 4);
#pragma unroll
            for (int h = 0; h < 2; h++) {
                acc[4 * i + 2 * h] = fmaf(blo(res[2 * i + h]), r1[h], fmaf(n1[h], c.x, s.x));
                acc[4 * i + 2 * h + 1] = fmaf(bhi(res[2 * i + h]), r1[h], fmaf(n1[h], c.y, s.y));
            }
        }
        mbar_spin(wfull + 5 * 8, 0);
        xwait(10);
        TS(leader, 22 + uw)
        uint32_t xo = (4 + 2 * uw) * 8, xp = 0;
        uint64_t ad = dz + (((dsb + OFF_XR) >> 4) | 0x10000u) + xo * 64, bd = dz + b80_desc(dsb, 5, 0, 0);
#pragma unroll 1
        for (int i = 0; i < 5; i++) {
            const uint32_t x1 = xfull + ((3 + 2 * i) & 7) * 8, p1 = i < 3, x2 = xfull + (min(4 + 2 * i, 11) & 7) * 8, p2 = i < 2;
            const uint32_t w2 = wfull + (min(6 + i, 9) & 7) * 8, pw = i >= 2;
            const bool ok1 = mbar_test(x1, p1);
            wg_fence();
#pragma unroll
            for (int q = 0; q < 4; q++) wgmma_ss80(acc, ad + q * 2, bd + q * B80_STEP, 1);
            wg_commit();
            wg_wait<1>();
            if (lane < 2 && i) mbar_arrive(xempty + xp);
            if (lane == 0 && i) mbar_arrive(wempty + ((4 + i) & 7) * 8);
            if (!ok1) mbar_spin(x1, p1);
            const bool ok2 = mbar_test(x2, p2), okw = mbar_test(w2, pw);
            wg_fence();
#pragma unroll
            for (int q = 0; q < 4; q++) wgmma_ss80(acc, ad + 512 + q * 2, bd + B80_HALF + q * B80_STEP, 1);
            wg_commit();
            const uint32_t xc = xo;
            xp = xo + 8; xo = (xo + 16) & 56;
            ad += xo ? 1024 : 1024 - 4096;
            bd += i == 2 ? 2 * B80_HALF - 8192 + (8192ll << 16) : 2 * B80_HALF;
            asm volatile("" : "+l"(ad), "+l"(bd));
            wg_wait<1>();
            if (lane < 2) mbar_arrive(xempty + xc);
            if (!ok2) mbar_spin(x2, p2);
            if (!okw) mbar_spin(w2, pw);
            TR(leader, (uw ? 86 : 20) + 2 * i)
        }
        wg_wait<0>();
        reg_fence(acc);
        if (lane < 2) mbar_arrive(xempty + xp);
        if (lane == 0) mbar_arrive(wempty + (9 & 7) * 8);
        TS(leader, 38 + uw)
        float a0 = 0.f, b0 = 0.f, a1 = 0.f, b1 = 0.f;
        uint32_t x2[20];
#pragma unroll
        for (int i = 0; i < 5; i++) {
            uint32_t* p = &x2[4 * i];
#pragma unroll
            for (int e = 0; e < 4; e++) p[e] = pack2(acc[8 * i + 2 * e], acc[8 * i + 2 * e + 1]);
#pragma unroll
            for (int e = 0; e < 4; e++) p[e] = lop3<0xB8>(p[e], (((wt >> 3) ^ (wt << 2)) & 7) == e, ep);
            stg128(&g_x2f[(tile * 40 + (i < 4 ? 4 * j + i : 32 + j)) * 128 + wt], p[0], p[1], p[2], p[3]);
#pragma unroll
            for (int e = 0; e < 4; e += 2) {
                const float u0 = blo(p[e]), u1 = bhi(p[e]), v0 = blo(p[e + 1]), v1 = bhi(p[e + 1]);
                a0 += u0 + u1; b0 = fmaf(u0, u0, fmaf(u1, u1, b0));
                a1 += v0 + v1; b1 = fmaf(v0, v0, fmaf(v1, v1, b1));
            }
        }
#pragma unroll
        for (int o = 1; o < 4; o *= 2) {
            a0 += __shfl_xor_sync(~0u, a0, o); b0 += __shfl_xor_sync(~0u, b0, o);
            a1 += __shfl_xor_sync(~0u, a1, o); b1 += __shfl_xor_sync(~0u, b1, o);
        }
        if (t < 2) stg64(&g_stats[(tile * 8 + j) * 64 + 16 * wq + g + 8 * t], tag(__float_as_uint(t ? a1 : a0), ep), __float_as_uint(t ? b1 : b0));
        signal_cnt(&g_cnt.g2[tile * 32], lane, 1, true);
        TS(leader, 40 + uw)
#pragma unroll
        for (int i = 0; i < 10; i++) {
            const float2 c = lds64f(sb + M_GB + (8 * i + 2 * t) * 4), e = lds64f(sb + M_CI + (8 * i + 2 * t) * 4);
#pragma unroll
            for (int h = 0; h < 2; h++)
                res[2 * i + h] = fma2(pack2(c.x, c.y), x2[2 * i + h], pack2(e.x * blo(res[2 * i + h]), e.y * bhi(res[2 * i + h])));
        }
#pragma unroll
        for (int i = 0; i < 20; i++) asm volatile("" : "+r"(res[i]));
    }
    float acc0[64], acc1[44];
    float2 q[4];
    {
        uint4 f0, f1, f2, f3;
        auto xseq = [&](int kb) { return ring_pos(uw, kb, XLEAD) & 7; };
        auto step = [&](const uint4& f, uint64_t bd) {
            wg_fence();
            wgmma_rs128(acc0, f.x, f.y, f.z, f.w, bd, 1);
            wgmma_rs88(acc1, f.x, f.y, f.z, f.w, bd + 512, 1);
            wg_commit();
        };
        const uint32_t xa = sb + OFF_XR + wt * 16;
        const float2* const gs = &g_stats[(tile * 8 + 2 * t) * 64 + 16 * wq + g];
        zero(acc0); zero(acc1);
        uint32_t xs = xseq(0);
        xwait(20);
        TS(leader, 42 + uw)
        f0 = lds128(xa + xs * 8192); f1 = lds128(xa + xs * 8192 + 2048);
#pragma unroll
        for (int i = 0; i < 4; i++) q[i] = ld_stat(gs + (i & 1) * 64 + 8 * (i >> 1));
        mbar_spin(wfull + (10 & 7) * 8, (10 >> 3) & 1);
#pragma unroll 1
        for (int kb = 0; kb < 10; kb++) {
            const uint32_t wn = 10 + 2 * kb;
            const uint64_t bd = dz + (((dsb + OFF_W + (wn & 7) * 16384) >> 4) | (256u << 16));
            step(f0, bd);
            wg_wait<1>();
            if (kb && lane == 0) mbar_arrive(wempty + ((wn - 1) & 7) * 8);
            f2 = lds128(xa + xs * 8192 + 4096); f3 = lds128(xa + xs * 8192 + 6144);
            const bool w1 = mbar_test(wfull + ((wn + 1) & 7) * 8, (wn >> 3) & 1), x1 = mbar_test(xfull + ((21 + kb) & 7) * 8, ((21 + kb) >> 3) & 1);
            step(f1, bd + 128);
            if (!w1) mbar_spin(wfull + ((wn + 1) & 7) * 8, (wn >> 3) & 1);
            step(f2, bd + 1024);
            if (lane < 2) mbar_arrive_after(xempty + xs * 8, f2.x, f3.x, nil);
            wg_wait<1>();
            if (lane == 0) mbar_arrive(wempty + (wn & 7) * 8);
            xs = xseq(kb + 1);
            if (x1) { f0 = lds128(xa + xs * 8192); f1 = lds128(xa + xs * 8192 + 2048); }
            const bool w2 = mbar_test(wfull + ((wn + 2) & 7) * 8, ((wn + 2) >> 3) & 1);
            step(f3, bd + 1152);
            if (kb < 9 && !x1) { xwait(21 + kb); f0 = lds128(xa + xs * 8192); f1 = lds128(xa + xs * 8192 + 2048); }
            if (!w2) mbar_spin(wfull + ((wn + 2) & 7) * 8, ((wn + 2) >> 3) & 1);
            if (kb == 4) {
                uint32_t it = 0;
                while (RARE(__any_sync(~0u, ((__float_as_uint(q[0].x) ^ ep) | (__float_as_uint(q[1].x) ^ ep) | (__float_as_uint(q[2].x) ^ ep) | (__float_as_uint(q[3].x) ^ ep)) & 1))) {
#pragma unroll
                    for (int i = 0; i < 4; i++) q[i] = ld_stat(gs + (i & 1) * 64 + 8 * (i >> 1));
                    SPIN_CHECK(49)
                }
                float a0 = q[0].x + q[1].x, b0 = q[0].y + q[1].y, a1 = q[2].x + q[3].x, b1 = q[2].y + q[3].y;
#pragma unroll
                for (int o = 1; o < 4; o *= 2) {
                    a0 += __shfl_xor_sync(~0u, a0, o); b0 += __shfl_xor_sync(~0u, b0, o);
                    a1 += __shfl_xor_sync(~0u, a1, o); b1 += __shfl_xor_sync(~0u, b1, o);
                }
                a0 *= 1.f / D_; a1 *= 1.f / D_;
                const float r0 = 0.5f * rsqrtf(fmaxf(b0 * (1.f / D_) - a0 * a0, 0.f) + 1e-5f), r1 = 0.5f * rsqrtf(fmaxf(b1 * (1.f / D_) - a1 * a1, 0.f) + 1e-5f);
                const uint32_t sel = t == 0 ? 0x1010 : t == 1 ? 0x4432 : 0x4444;
                q[0] = make_float2(r0, r1);
                q[1] = make_float2(__uint_as_float(__byte_perm(split2(-a0), 0, sel)), __uint_as_float(__byte_perm(split2(-a1), 0, sel)));
            }
            if (kb == 6) {
#pragma unroll
                for (int i = 0; i < 5; i++) stg128(&g_x1f[(tile * 8 + j) * 640 + i * 128 + wt], res[4 * i], res[4 * i + 1], res[4 * i + 2], res[4 * i + 3]);
            }
            if (kb == 8) asm volatile("fence.proxy.async.global;" ::: "memory");
            TR(leader, 10 * uw + kb)
        }
        const uint64_t fd = ((uint64_t)8 << 32) | ((dsb + OFF_W + 6 * 16384) >> 4);
        wg_fence();
        wgmma_rs128k(acc0, __float_as_uint(q[1].x), __float_as_uint(q[1].y), 0, 0, fd, 1);
        wgmma_rs88k(acc1, __float_as_uint(q[1].x), __float_as_uint(q[1].y), 0, 0, fd + 128, 1);
        wg_commit();
        if (lane == 0) {
            mbar_arrive(bars + B_XFREE * 8);
            asm volatile("mbarrier.arrive.shared::cluster.b64 _, [%0];" ::"r"(peer_addr(bars + B_XFREE * 8)) : "memory");
        }
    }
    const uint32_t recv = sb + recv_off(uw) + wt * 16;
    uint32_t ha[48] = {}, hb[48], hx[12];
    uint64_t wb = dz + (((dsb + OFF_W) >> 4) | (512u << 16));
    auto wdesc = [&](int n) { return wb + (n & 7) * 1024; };
    auto wwait = [&](int n) { mbar_spin(wfull + (n & 7) * 8, (n >> 3) & 1); };
    auto wfree = [&](int n) { if (lane == 0) mbar_arrive(wempty + (n & 7) * 8); };
    auto fresh = [&]() { wb += pp.nil; asm volatile("" : "+l"(wb)); };
    uint32_t pk[32];
    {
        float P0[64];
        const float r0 = q[0].x, r1 = q[0].y;
        const uint32_t ra = peer_addr(recv), rb = peer_addr(bars + (B_RECV + 4 * uw) * 8);
        auto conv32 = [&](const float* v, int b) {
#pragma unroll
            for (int i = 0; i < 4; i++) {
                ha[8 * b + 2 * i] = pack2(gelu2(v[4 * i] * r0), gelu2(v[4 * i + 1] * r0));
                ha[8 * b + 2 * i + 1] = pack2(gelu2(v[4 * i + 2] * r1), gelu2(v[4 * i + 3] * r1));
            }
#pragma unroll
            for (int s = 2 * b; s < 2 * b + 2; s++) st_peer(ra + s * 2048, ha[4 * s], ha[4 * s + 1], ha[4 * s + 2], ha[4 * s + 3], rb + (b >> 1) * 8);
        };
        auto fetch = [&](int k) {
            mbar_spin(bars + (B_RECV + 4 * uw + k) * 8, 0);
#pragma unroll
            for (int s = 4 * k; s < 4 * k + 4; s++) { const uint4 x = lds128(recv + s * 2048); hb[4 * s] = x.x; hb[4 * s + 1] = x.y; hb[4 * s + 2] = x.z; hb[4 * s + 3] = x.w; }
        };
        auto stage = [&](int n, const uint32_t* a, int steps, int sc) {
            wwait(n);
            wg_fence();
#pragma unroll
            for (int s = 0; s < steps; s++) wgmma_rs128(P0, a[4 * s], a[4 * s + 1], a[4 * s + 2], a[4 * s + 3], wdesc(n) + s * 128, sc || s);
            wg_commit();
        };
        wg_wait<0>();
        reg_fence(acc0); reg_fence(acc1);
        wfree(29); wfree(30);
        TS(leader, 44 + uw)
        uint32_t hr[6];
#pragma unroll
        for (int i = 0; i < 6; i++) {
            const float r = (i & 1) ? r1 : r0;
            hr[i] = pack2(gelu2(acc1[32 + 2 * i] * r), gelu2(acc1[33 + 2 * i] * r));
        }
        if (uw) mbar_spin(bars + B_XFREE * 8, 0);
        st_peer(ra + 24576, hr[0], hr[1], hr[2], hr[3], rb + 24);
        asm volatile("st.async.shared::cluster.mbarrier::complete_tx::bytes.v2.b32 [%0], {%1, %2}, [%3];" ::"r"(ra + 26624 - wt * 8), "r"(hr[4]), "r"(hr[5]), "r"(rb + 24) : "memory");
        conv32(&acc1[0], 4);
        conv32(&acc1[16], 5);
        TS(leader, 46 + uw)
        stage(31, &ha[32], 4, 0);
#pragma unroll
        for (int b = 0; b < 4; b++) {
            conv32(&acc0[16 * b], b);
            if (b == 3) {
                fetch(2);
                mbar_spin(bars + (B_RECV + 4 * uw + 3) * 8, 0);
                const uint4 x = lds128(recv + 24576);
                const uint2 y = lds64(recv + 26624 - wt * 8);
                const uint32_t hp[6] = {x.x, x.y, x.z, x.w, y.x, y.y};
#pragma unroll
                for (int i = 0; i < 6; i++) { hx[i] = (j & 1) ? hp[i] : hr[i]; hx[6 + i] = (j & 1) ? hr[i] : hp[i]; }
            }
            if (!(b & 1)) wwait(32 + (b >> 1));
            wg_fence();
#pragma unroll
            for (int s = 0; s < 2; s++) wgmma_rs128(P0, ha[8 * b + 4 * s], ha[8 * b + 4 * s + 1], ha[8 * b + 4 * s + 2], ha[8 * b + 4 * s + 3], wdesc(32 + (b >> 1)) + (2 * (b & 1) + s) * 128, 1);
            wg_commit();
            if (!(b & 1)) { wg_wait<1>(); wfree(31 + (b >> 1)); }
        }
        TR(leader, 64 + 10 * uw)
        fresh();
        stage(34, &hb[32], 4, 1); wg_wait<1>(); wfree(33);
        fetch(0);
        stage(35, hx, 3, 1); wg_wait<1>(); wfree(34);
        fetch(1);
        stage(36, &hb[0], 4, 1); wg_wait<1>(); wfree(35);
        stage(37, &hb[16], 4, 1); wg_wait<1>(); wfree(36);
        wg_wait<0>();
        reg_fence(P0);
        pack_part<64>(pk, P0, ep);
        uint32_t all = 0;
#pragma unroll
        for (int i = 0; i < 32; i++) all |= pk[i];
        if (lane == 0) mbar_arrive_after(wempty + (37 & 7) * 8, all, 0, nil);
        TR(leader, 65 + 10 * uw)
    }
    {
        uint4* const dst = g_part + (size_t)(tile * 8 + j) * 5120 + wt;
        const uint4* const src = g_part + (size_t)tile * 40960 + j * 512 + wt;
        float F[2][32];
        float2 gb[8];
        uint4 base[4], u1[4], u2[4], u3[4];
#pragma unroll
        for (int c = 2; c < 5; c++) {
            float (&P)[32] = F[c & 1];
            fresh();
#pragma unroll
            for (int s = 0; s < 27; s++) {
                const int e = s < 8 ? 0 : s < 15 ? 1 : s < 23 ? 2 : 3, o = s - (e == 0 ? 0 : e == 1 ? 8 : e == 2 ? 15 : 23), n = 30 + 4 * c + e;
                const uint32_t* a = s < 12 ? &ha[4 * s] : s < 15 ? &hx[4 * (s - 12)] : &hb[4 * (s - 15)];
                if (o == 0) wwait(n);
                if (o == 0 || s == 1) wg_fence();
                wgmma_rs64(P, a[0], a[1], a[2], a[3], wdesc(n) + o * 128, s);
                if (o == 0) { wg_commit(); wg_wait<1>(); if (c > 2 || s) wfree(n - 1); }
                if (s == 0 && c > 2) { reg_fence(F[~c & 1]); pack_part<32>(pk, F[~c & 1], ep); }
                if (c == 2 && s % 3 == 0 && s < 24) st_part(dst + g4_block(s / 12, j) * 512 + (s / 3 & 3) * 128, &pk[4 * (s / 3)]);
                if (c == 3 && s % 4 == 1 && s < 16) st_part(dst + g4_block(2, j) * 512 + s / 4 * 128, &pk[4 * (s / 4)]);
                if (c == 4 && s % ST3 == 0 && s < 4 * ST3) st_part(dst + g4_block(3, j) * 512 + s / ST3 * 128, &pk[4 * (s / ST3)]);
                if (c == 4 && s >= 4 && s < 8) base[s - 4] = ldcg128(&g_x1f[(tile * 8 + j) * 640 + (s - 4) * 128 + wt]);
                if (c == 4 && s >= 19 && s < 23) { gb[2 * s - 38] = lds64f(sb + M_GB + (16 * (s - 19) + 2 * t) * 4); gb[2 * s - 37] = lds64f(sb + M_GB + (16 * (s - 19) + 8 + 2 * t) * 4); }
                if (c == 4 && s >= 8 && s < 12) u1[s - 8] = ld_part(src + (j ^ 6) * 5120 + (s - 8) * 128);
                if (c == 4 && s >= 15 && s < 19) u2[s - 15] = ld_part(src + (j ^ 4) * 5120 + (s - 15) * 128);
                if (c == 4 && s >= LD3 && s < LD3 + 4) u3[s - LD3] = ld_part(src + (j ^ 2) * 5120 + (s - LD3) * 128);
                if (s == 7 || s == 14 || s == 22 || s == 26) wg_commit();
                if (c == 4) { TR(leader && s == 7, 68 + 10 * uw) TR(leader && s == 14, 69 + 10 * uw) TR(leader && s == 22, 70 + 10 * uw) }
            }
            if (c == 2 && lane == 0) mbar_arrive(bars + (B_RING + uw) * 8);
            TR(leader, 64 + c + (c == 4 ? 3 : 0) + 10 * uw)
        }
        float (&O)[32] = F[0];
        float v[32];
        uint32_t it = 0;
        while (__any_sync(~0u, (stale4(u1, ep) | stale4(u2, ep) | stale4(u3, ep)) & 1)) {
            ld_part4(u1, src + (j ^ 6) * 5120, 128); ld_part4(u2, src + (j ^ 4) * 5120, 128); ld_part4(u3, src + (j ^ 2) * 5120, 128);
            STALE(6)
            SPIN_CHECK(58)
        }
        TR(leader, 73 + 10 * uw)
#pragma unroll
        for (int i = 0; i < 4; i++) { unpack8(&v[8 * i], add2(add2(u1[i], u2[i]), u3[i])); base16(&v[8 * i], base[i], gb[2 * i], gb[2 * i + 1]); }
        reg_fence(v);
        TS(leader, 50 + uw)
        wg_wait<0>();
        reg_fence(O);
        TS(leader, 48 + uw)
        const uint32_t so = sb + recv_off(uw) + wq * 2048;
#pragma unroll
        for (int i = 0; i < 4; i++) {
            float* o = &O[8 * i];
#pragma unroll
            for (int e = 0; e < 8; e++) o[e] = fmaf((e & 1) ? gb[2 * i + (e >> 2)].y : gb[2 * i + (e >> 2)].x, o[e], v[8 * i + e]);
            stsm4(so + (lane & 15) * 128 + (((2 * i + (lane >> 4)) ^ (lane & 7)) << 4), pack2(o[0], o[1]), pack2(o[2], o[3]), pack2(o[4], o[5]), pack2(o[6], o[7]));
        }
        __syncwarp();
#pragma unroll
        for (int i = 0; i < 4; i++) {
            const int row = (lane >> 3) + 4 * i;
            stg128(out + (size_t)(row0 + row) * D_ + 64 * j + 8 * (lane & 7), lds128(so + row * 128 + (((lane & 7) ^ (row & 7)) << 4)));
        }
        warp_arrive(bars + B_OWN * 8);
    }
}

typedef CUresult (*EncFn)(CUtensorMap*, CUtensorMapDataType, cuuint32_t, void*, const cuuint64_t*, const cuuint64_t*, const cuuint32_t*,
                          const cuuint32_t*, CUtensorMapInterleave, CUtensorMapSwizzle, CUtensorMapL2promotion, CUtensorMapFloatOOBfill);

static void enc(EncFn fn, CUtensorMap* m, void* p, int rank, const cuuint64_t* dims, const cuuint64_t* strides, const cuuint32_t* box, bool plain = false) {
    const CUtensorMapSwizzle sw = box[0] > 64 || plain ? CU_TENSOR_MAP_SWIZZLE_NONE : CU_TENSOR_MAP_SWIZZLE_128B;
    cuuint32_t es[5] = {1, 1, 1, 1, 1};
    CUresult r = fn(m, CU_TENSOR_MAP_DATA_TYPE_BFLOAT16, rank, p, dims, strides, box, es, CU_TENSOR_MAP_INTERLEAVE_NONE, sw,
                    CU_TENSOR_MAP_L2_PROMOTION_L2_128B, CU_TENSOR_MAP_FLOAT_OOB_FILL_NONE);
    (void)r;
}
static void enc2(EncFn fn, CUtensorMap* m, void* p, uint64_t cols, uint64_t rows, uint32_t bc, uint32_t br, bool plain = false) {
    cuuint64_t dims[2] = {cols, rows}, st[1] = {cols * 2};
    cuuint32_t box[2] = {bc, br};
    enc(fn, m, p, 2, dims, st, box, plain);
}

extern "C" void kernel_launch(void* const* d_in, const int* in_sizes, int n_in, void* d_out, int out_size) {
    static Maps mp;
    static Ptrs pp;
    static void* cached[13];
    bool same = true;
    for (int i = 0; i < 13; i++) same = same && (cached[i] == d_in[i]);
    if (!same) {
        void* fnp = nullptr;
        cudaDriverEntryPointQueryResult qr;
        cudaGetDriverEntryPoint("cuTensorMapEncodeTiled", &fnp, cudaEnableDefault, &qr);
        EncFn fn = (EncFn)fnp;
        cudaGetSymbolAddress((void**)&pp.s, g_scratch);
        void *x1T = g_x1T, *t = g_t;
        cuuint64_t dq[3] = {64, S_, 10}, sq[2] = {D_ * 2, 128};
        cuuint32_t bq[3] = {64, 16, 10};
        enc(fn, &mp.q, d_in[0], 3, dq, sq, bq);
        enc2(fn, &mp.k, d_in[1], D_, S_, 80, 67); enc2(fn, &mp.v, d_in[2], D_, S_, 80, 64);
        enc2(fn, &mp.qT, g_qT, 16 * D_, 128, 80, 128);
        enc2(fn, &mp.x[0], x1T, S_, D_, 64, 64); enc2(fn, &mp.x[1], (bf16*)t + 2 * D_, D_, S_, 64, 64);
        enc2(fn, &mp.x[2], g_x2f, 64, 320 * 64, 64, 64, true);
        enc2(fn, &mp.w1, d_in[7], D_, D_, 64, 64); enc2(fn, &mp.w1h, d_in[7], D_, D_, 64, 160); enc2(fn, &mp.w3h, d_in[9], F_, D_, 64, 160);
        enc2(fn, &mp.wmod, d_in[12], 6 * D_, D_, 64, 160);
        const cuuint64_t R = D_ * 2;
        cuuint64_t da[5] = {D_, 2, 4, 4, 16}, sa[4] = {R, 8 * R, 2 * R, 32 * R}, db[5] = {D_, 2, 2, 4, 8}, sb[4] = {R, 8 * R, 2 * R, 16 * R};
        cuuint32_t ba[5] = {64, 2, 4, 4, 4}, bb[5] = {64, 2, 2, 4, 8};
        enc(fn, &mp.w2a, d_in[8], 5, da, sa, ba); enc(fn, &mp.w2b, (bf16*)d_in[8] + 512 * D_, 5, db, sb, bb);
        cuuint64_t dw[3] = {64, D_, 27}, sw[2] = {F_ * 2, 128};
        cuuint32_t bw[3] = {64, 32, 3};
        enc(fn, &mp.w3a, d_in[9], 3, dw, sw, bw);
        enc2(fn, &mp.w3b, d_in[9], F_, D_, 24, 32);
        enc2(fn, &mp.w4[0], d_in[10], D_, F_, 64, 64); enc2(fn, &mp.w4[1], d_in[10], D_, F_, 64, 48);
        pp.q = (const bf16*)d_in[0]; pp.w_mod = (const bf16*)d_in[12]; pp.shift_k = (const bf16*)d_in[3];
        pp.ssm_k = (const bf16*)d_in[4]; pp.ssm_D = (const bf16*)d_in[5]; pp.w1 = (const bf16*)d_in[7]; pp.w2 = (const bf16*)d_in[8];
        pp.w4 = (const bf16*)d_in[10]; pp.c = (const bf16*)d_in[11];
        cudaFuncSetAttribute(fused_kernel, cudaFuncAttributeMaxDynamicSharedMemorySize, SMEM_BYTES);
        for (int i = 0; i < 13; i++) cached[i] = d_in[i];
    }
    fused_kernel<<<NCTA, NTHR, SMEM_BYTES, cudaStreamPerThread>>>(pp, (bf16*)d_out, mp);
}
```

```cpp
#include <cuda_runtime.h>
#include <cuda_bf16.h>
#include <cuda.h>
#include <stdint.h>
#include <stdio.h>

typedef __nv_bfloat16 bf16;

constexpr int S_ = 2048, D_ = 640, F_ = 1728;
constexpr int NCTA = 132, NTHR = 512;

constexpr int TAB_BYTES = 9216, VEC_BYTES = 1440;
struct Counters {
    unsigned kv[8 * 32];
    unsigned q[4 * 32], x[4 * 32];
    unsigned wr[32], tab[32], uv[32], cs[32], cs2[32], done[32];
    unsigned g1[32 * 32];
    unsigned g2[32 * 32];
};
struct Scratch {
    Counters cnt;
    unsigned epoch;
    alignas(1024) bf16 qst[2 * S_];
    alignas(1024) uint4 wr[2 * 8 * 10 * 128];
    alignas(1024) uint2 mod[2 * 6 * D_];
    alignas(1024) uint4 tab[(TAB_BYTES + 8 * VEC_BYTES) / 16];
    alignas(1024) float uv[2 * 3 * D_];
    alignas(1024) float cs3[2 * 1920];
    alignas(1024) uint4 cs3b[8 * 216];
    alignas(1024) float2 stats[32 * 8 * 64];
    alignas(1024) bf16 kvT[D_ * S_];
    alignas(1024) bf16 qT[D_ * S_];
    alignas(1024) bf16 x1T[D_ * S_];
    alignas(1024) bf16 t[(S_ + 4) * D_];
    alignas(1024) uint4 x2f[32 * 40 * 128];
    alignas(1024) uint4 x1f[32 * 8 * 5 * 128];
    alignas(1024) uint4 part[32 * 8 * 10 * 4 * 128];
};
__device__ Scratch g_scratch;
#define g_kvT (pp.s->kvT)
#define g_qT (pp.s->qT)
#define g_x1T (pp.s->x1T)
#define g_qst (pp.s->qst)
#define g_t (pp.s->t)
#define g_x2f (pp.s->x2f)
#define g_x1f (pp.s->x1f)
#define g_part (pp.s->part)
#define g_wr (pp.s->wr)
#define g_mod (pp.s->mod)
#define g_tab (pp.s->tab)
#define g_uv (pp.s->uv)
#define g_cs3 (pp.s->cs3)
#define g_cs3b (pp.s->cs3b)
#define g_stats (pp.s->stats)
#define g_cnt (pp.s->cnt)
#define g_epoch (pp.s->epoch)

struct Maps {
    CUtensorMap k, v, q;
    CUtensorMap qT;
    CUtensorMap x[3];
    CUtensorMap w1, w1h, w3h, wmod;
    CUtensorMap w2a, w2b;
    CUtensorMap w3a, w3b;
    CUtensorMap w4[2];
};

struct Ptrs {
    Scratch* s;
    uint64_t nil;
    const bf16 *q, *w_mod, *shift_k, *ssm_k, *ssm_D, *w1, *w2, *w4, *c;
};

constexpr int OFF_W = 0;
constexpr int OFF_XR = 131072;
constexpr int OFF_REM = 196608;
constexpr int OFF_TAB = OFF_REM + 5 * 4096;
constexpr int OFF_ROW = OFF_TAB + 4608;
constexpr int OFF_F1 = OFF_ROW + 4096;
constexpr int RECV_BYTES = 30720;
constexpr int OFF_M = OFF_REM + RECV_BYTES;
constexpr int OFF_OUT = OFF_XR + 32768;
static_assert(OFF_F1 + 1280 <= OFF_M, "G1 map");
constexpr int OFF_ST = 0;
constexpr int OFF_SSM = 20480;
constexpr int OFF_WM = 0;
constexpr int OFF_QIN = 49152;
constexpr int OFF_QT = 49152;
constexpr int OFF_Z = OFF_TAB;
constexpr int OFF_RING = 80896;
constexpr int OFF_KIN = OFF_RING, OFF_VIN = OFF_KIN + 2 * 10752;
constexpr int OFF_CH = OFF_RING + 3 * 16384, CH_BYTES = 13312, OFF_P = 5120;
static_assert(OFF_RING + 5 * 16384 <= OFF_CH + 3 * CH_BYTES && OFF_CH + 5 * CH_BYTES <= OFF_REM, "the last two rings replace channels 0..2");
constexpr int M_BAR = OFF_M;
constexpr int M_F1 = OFF_M + 800;
constexpr int M_GB = M_F1 + 1280, M_C = M_GB + 320, M_SB = M_C + 320, M_CI = M_SB + 320;
constexpr int M_KS = M_CI + 320;
constexpr int M_AB = M_KS + 160;
constexpr int M_EP = M_AB + 80;
constexpr int M_SINK = M_EP + 16;
constexpr int M_NUL = M_SINK + 16;
constexpr int M_TS = M_NUL + 128;
constexpr int SMEM_BYTES = M_TS;
static_assert(SMEM_BYTES <= 232448, "smem");

enum { B_WFULL = 0, B_WEMPTY = 8, B_XEMPTY = 16, B_XFULL = 24  ,
       B_RAW = 40, B_QIN = 41, B_SSM = 42, B_VEC = 43, B_VEC3 = 44, B_WM = 45, B_TAB = 46, B_QRDY = 47,
       B_MODR = 48, B_GATE = 49, B_RETRY = 55, B_RAW2 = 59, B_RAW3 = 60, B_SUMS = 62, B_RECV = 64  ,
       B_SIG = 72, B_RING = 74  ,
       B_LAND = 80,
       B_XS = 88, B_R1 = 89, B_BK = 90, B_KVS = 91,
       B_XFREE = 92, B_OWN = 93,
       B_IN = 94, B_AGAIN = 96 };
#define T_KVB 1800
#define T_SSM 3300
#define PF_T0 4800
#define PF_DT 420
#define Q_UNROLL 1
#define HELP_T 1000
#define ST3 1
#define LD3 23
#define GATE_W2 7
#define GATE_W3 27
#define GATE_W3B 37
#define W3_N2 13
#define LEAD1 4
#define XLEAD 3

#define SPIN_FAIL(code) __trap();
#define SPIN_LIMIT (1u << 22)
#define STALE(c)
#define STALE1(c)
#define TS(c, i)
#define TG(c, i)
#define TR(c, i)
#define TR2(c, i)
#define TR4(c, i)
#define TR5(c, i)
#define SPIN_CHECK(code) asm volatile("" ::"r"(it));
#define RARE(x) __builtin_expect((x) != 0, 0)
__device__ __forceinline__ uint32_t s2u(const void* p) { return (uint32_t)__cvta_generic_to_shared(p); }
__device__ __forceinline__ bool elect() {
    uint32_t p;
    asm volatile("{.reg .pred P; elect.sync _|P, 0xffffffff; selp.u32 %0,1,0,P;}" : "=r"(p));
    return p != 0;
}
__device__ __forceinline__ void mbar_init(uint32_t b, uint32_t n) { asm volatile("mbarrier.init.shared.b64 [%0], %1;" ::"r"(b), "r"(n)); }
__device__ __forceinline__ void mbar_expect(uint32_t b, uint32_t bytes) {
    asm volatile("mbarrier.arrive.expect_tx.shared.b64 _, [%0], %1;" ::"r"(b), "r"(bytes) : "memory");
}
__device__ __forceinline__ void mbar_arrive(uint32_t b) { asm volatile("mbarrier.arrive.shared.b64 _, [%0];" ::"r"(b) : "memory"); }
__device__ __forceinline__ void mbar_arrive_after(uint32_t b, uint32_t v0, uint32_t v1, uint32_t nil) { mbar_arrive(b + ((v0 | v1) & nil)); }
__device__ __forceinline__ void warp_arrive(uint32_t b) { __syncwarp(); if (elect()) mbar_arrive(b); }
__device__ __forceinline__ uint32_t peer_addr(uint32_t a) {
    uint32_t r;
    asm("{\n.reg .b32 q;\nmov.u32 q, %%cluster_ctarank;\nxor.b32 q, q, 1;\nmapa.shared::cluster.u32 %0, %1, q;\n}" : "=r"(r) : "r"(a));
    return r;
}
__device__ __forceinline__ bool mbar_test(uint32_t b, uint32_t parity) {
    uint32_t ok;
    asm volatile("{.reg .pred P; mbarrier.test_wait.parity.shared.b64 P, [%1], %2; selp.u32 %0,1,0,P;}" : "=r"(ok) : "r"(b), "r"(parity) : "memory");
    return ok != 0;
}
__device__ __forceinline__ bool mbar_try(uint32_t b, uint32_t parity) {
    uint32_t ok;
    asm volatile("{.reg .pred P; mbarrier.try_wait.parity.shared.b64 P, [%1], %2; selp.u32 %0,1,0,P;}" : "=r"(ok) : "r"(b), "r"(parity) : "memory");
    return ok != 0;
}
__device__ __forceinline__ void mbar_wait(uint32_t b, uint32_t parity) {
    if (__all_sync(0xffffffffu, mbar_try(b, parity))) return;
    uint32_t it = 0;
    while (!__all_sync(0xffffffffu, mbar_try(b, parity))) { if (++it > SPIN_LIMIT) SPIN_FAIL((b >> 3) & 63) }
}
__device__ __forceinline__ void mbar_spin(uint32_t b, uint32_t parity) {
    asm volatile("{\n.reg .pred P;\nSPIN:\nmbarrier.try_wait.parity.shared.b64 P, [%0], %1;\n@!P bra.uni SPIN;\n}" ::"r"(b), "r"(parity) : "memory");
}
__device__ __forceinline__ void bar_sync(int id, int n) { asm volatile("bar.sync %0, %1;" ::"r"(id), "r"(n) : "memory"); }
__device__ __forceinline__ void fence_async_smem() { asm volatile("fence.proxy.async.shared::cta;" ::: "memory"); }
__device__ __forceinline__ void wait_cnt(const unsigned* p, unsigned target, bool tagged = false) {
    unsigned v, it = 0;
    do {
        asm volatile("ld.relaxed.gpu.global.u32 %0, [%1];" : "=r"(v) : "l"(p) : "memory");
        SPIN_CHECK(60 + (target & 3))
    } while (!__all_sync(0xffffffffu, v >= target));
    if (!tagged) asm volatile("fence.acquire.gpu;" ::: "memory");
}
__device__ __forceinline__ void signal_cnt(unsigned* p, int lane, int n, bool tagged = false) {
    if (tagged) asm volatile("{\n.reg .pred P;\nsetp.lt.s32 P, %1, %2;\n@P red.relaxed.gpu.global.add.u32 [%0], %3;\n}" ::"l"(p), "r"(lane), "r"(n), "r"(1) : "memory");
    else if (lane < n) asm volatile("red.release.gpu.global.add.u32 [%0], 1;" ::"l"(p) : "memory");
    __syncwarp();
}
__device__ __forceinline__ uint32_t clock_lo() { uint32_t c; asm volatile("mov.u32 %0, %%clock;" : "=r"(c)); return c; }
__device__ __forceinline__ void wait_clock(uint32_t c0, uint32_t t) {
    asm volatile("{\n.reg .pred P;\n.reg .b32 c;\nWAIT:\nnanosleep.u32 20;\nmov.u32 c, %%clock;\nsub.u32 c, c, %0;\nsetp.lt.u32 P, c, %1;\n@P bra.uni WAIT;\n}" ::"r"(c0), "r"(t) : "memory");
}
__device__ __forceinline__ void tma_ld2(uint32_t dst, const CUtensorMap* m, int c0, int c1, uint32_t bar) {
    asm volatile("cp.async.bulk.tensor.2d.shared::cluster.global.mbarrier::complete_tx::bytes [%0], [%1, {%3, %4}], [%2];"
                 ::"r"(dst), "l"(m), "r"(bar), "r"(c0), "r"(c1) : "memory");
}
__device__ __forceinline__ void tma_ld3(uint32_t dst, const CUtensorMap* m, int c0, int c1, int c2, uint32_t bar) {
    asm volatile("cp.async.bulk.tensor.3d.shared::cluster.global.mbarrier::complete_tx::bytes [%0], [%1, {%3, %4, %5}], [%2];"
                 ::"r"(dst), "l"(m), "r"(bar), "r"(c0), "r"(c1), "r"(c2) : "memory");
}
__device__ __forceinline__ void tma_ld5(uint32_t dst, const CUtensorMap* m, int col, int blk, uint32_t bar) {
    asm volatile("cp.async.bulk.tensor.5d.shared::cluster.global.mbarrier::complete_tx::bytes [%0], [%1, {%3, %4, %4, %4, %5}], [%2];"
                 ::"r"(dst), "l"(m), "r"(bar), "r"(col), "r"(0), "r"(blk) : "memory");
}
__device__ __forceinline__ void bulk_ld(uint32_t dst, const void* src, uint32_t bytes, uint32_t bar) {
    asm volatile("cp.async.bulk.shared::cluster.global.mbarrier::complete_tx::bytes [%0], [%1], %2, [%3];" ::"r"(dst), "l"(src), "r"(bytes), "r"(bar) : "memory");
}
__device__ __forceinline__ void l2_prefetch(const void* p, uint32_t bytes) {
    asm volatile("cp.async.bulk.prefetch.L2.global [%0], %1;" ::"l"(p), "r"(bytes) : "memory");
}
__device__ __forceinline__ void wg_fence() { asm volatile("wgmma.fence.sync.aligned;" ::: "memory"); }
__device__ __forceinline__ void wg_commit() { asm volatile("wgmma.commit_group.sync.aligned;" ::: "memory"); }
template <int N> __device__ __forceinline__ void wg_wait() { asm volatile("wgmma.wait_group.sync.aligned %0;" ::"n"(N) : "memory"); }
template <int N> __device__ __forceinline__ void reg_fence(float (&d)[N]) {
#pragma unroll
    for (int i = 0; i < N; i++) asm volatile("" : "+f"(d[i])::"memory");
}
template <int N> __device__ __forceinline__ void zero(float (&d)[N]) {
#pragma unroll
    for (int i = 0; i < N; i++) asm volatile("mov.b32 %0, 0;" : "=f"(d[i]));
}
__device__ __forceinline__ uint32_t lds32(uint32_t a) { uint32_t v; asm volatile("ld.shared.b32 %0, [%1];" : "=r"(v) : "r"(a)); return v; }
__device__ __forceinline__ uint2 lds64(uint32_t a) { uint2 v; asm volatile("ld.shared.v2.b32 {%0,%1}, [%2];" : "=r"(v.x), "=r"(v.y) : "r"(a)); return v; }
__device__ __forceinline__ float2 lds64f(uint32_t a) { float2 v; asm volatile("ld.shared.v2.f32 {%0,%1}, [%2];" : "=f"(v.x), "=f"(v.y) : "r"(a)); return v; }
__device__ __forceinline__ void sts32(uint32_t a, uint32_t v) { asm volatile("st.shared.b32 [%0], %1;" ::"r"(a), "r"(v) : "memory"); }
__device__ __forceinline__ void sts64f(uint32_t a, float x, float y) { asm volatile("st.shared.v2.f32 [%0], {%1,%2};" ::"r"(a), "f"(x), "f"(y) : "memory"); }
__device__ __forceinline__ void sts128(uint32_t a, uint32_t x, uint32_t y, uint32_t z, uint32_t w) {
    asm volatile("st.shared.v4.b32 [%0], {%1,%2,%3,%4};" ::"r"(a), "r"(x), "r"(y), "r"(z), "r"(w) : "memory");
}
__device__ __forceinline__ void sts128f(uint32_t a, float x, float y, float z, float w) {
    asm volatile("st.shared.v4.f32 [%0], {%1,%2,%3,%4};" ::"r"(a), "f"(x), "f"(y), "f"(z), "f"(w) : "memory");
}
__device__ __forceinline__ uint4 lds128(uint32_t a) {
    uint4 v;
    asm volatile("ld.shared.v4.b32 {%0,%1,%2,%3}, [%4];" : "=r"(v.x), "=r"(v.y), "=r"(v.z), "=r"(v.w) : "r"(a) : "memory");
    return v;
}
__device__ __forceinline__ float4 lds128f(uint32_t a) {
    float4 v;
    asm volatile("ld.shared.v4.f32 {%0,%1,%2,%3}, [%4];" : "=f"(v.x), "=f"(v.y), "=f"(v.z), "=f"(v.w) : "r"(a) : "memory");
    return v;
}
__device__ __forceinline__ void stg128(void* p, uint32_t x, uint32_t y, uint32_t z, uint32_t w) {
    asm volatile("st.global.v4.b32 [%0], {%1,%2,%3,%4};" ::"l"(p), "r"(x), "r"(y), "r"(z), "r"(w) : "memory");
}
__device__ __forceinline__ void stg128(void* p, uint4 v) { stg128(p, v.x, v.y, v.z, v.w); }
__device__ __forceinline__ void stg128_if(void* p, uint4 v, int on) {
    asm volatile("{\n.reg .pred p;\nsetp.ne.s32 p, %5, 0;\n@p st.global.v4.b32 [%0], {%1,%2,%3,%4};\n}" ::"l"(p), "r"(v.x), "r"(v.y), "r"(v.z), "r"(v.w), "r"(on) : "memory");
}
__device__ __forceinline__ void stg64(void* p, uint32_t x, uint32_t y) { asm volatile("st.global.v2.b32 [%0], {%1,%2};" ::"l"(p), "r"(x), "r"(y) : "memory"); }
__device__ __forceinline__ void stsm4(uint32_t a, uint32_t r0, uint32_t r1, uint32_t r2, uint32_t r3) {
    asm volatile("stmatrix.sync.aligned.m8n8.x4.shared.b16 [%0], {%1,%2,%3,%4};" ::"r"(a), "r"(r0), "r"(r1), "r"(r2), "r"(r3) : "memory");
}
__device__ __forceinline__ void stsm4t(uint32_t a, uint32_t r0, uint32_t r1, uint32_t r2, uint32_t r3) {
    asm volatile("stmatrix.sync.aligned.m8n8.x4.trans.shared.b16 [%0], {%1,%2,%3,%4};" ::"r"(a), "r"(r0), "r"(r1), "r"(r2), "r"(r3) : "memory");
}
__device__ __forceinline__ void ldsm4t_if(bool p, uint32_t a, uint32_t* r) {
    asm volatile("{\n.reg .pred p;\nsetp.ne.u32 p, %5, 0;\n@p ldmatrix.sync.aligned.m8n8.x4.trans.shared.b16 {%0,%1,%2,%3}, [%4];\n}"
                 : "+r"(r[0]), "+r"(r[1]), "+r"(r[2]), "+r"(r[3]) : "r"(a), "r"((uint32_t)p) : "memory");
}
__device__ __forceinline__ void ldsm4t(uint32_t a, uint32_t& r0, uint32_t& r1, uint32_t& r2, uint32_t& r3) {
    asm volatile("ldmatrix.sync.aligned.m8n8.x4.trans.shared.b16 {%0,%1,%2,%3}, [%4];" : "=r"(r0), "=r"(r1), "=r"(r2), "=r"(r3) : "r"(a) : "memory");
}
__device__ __forceinline__ uint32_t pack2(float lo, float hi) {
    uint32_t r;
    asm("cvt.rn.bf16x2.f32 %0, %1, %2;" : "=r"(r) : "f"(hi), "f"(lo));
    return r;
}
__device__ __forceinline__ uint32_t mul2(uint32_t a, uint32_t b) { uint32_t r; asm("mul.rn.bf16x2 %0, %1, %2;" : "=r"(r) : "r"(a), "r"(b)); return r; }
__device__ __forceinline__ uint32_t fma2(uint32_t a, uint32_t b, uint32_t c) { uint32_t r; asm("fma.rn.bf16x2 %0, %1, %2, %3;" : "=r"(r) : "r"(a), "r"(b), "r"(c)); return r; }
__device__ __forceinline__ uint32_t add2(uint32_t a, uint32_t b) { uint32_t r; asm("add.rn.bf16x2 %0, %1, %2;" : "=r"(r) : "r"(a), "r"(b)); return r; }
__device__ __forceinline__ void hmma(float (&d)[4], uint32_t a0, uint32_t a1, uint32_t a2, uint32_t a3, uint32_t b0, uint32_t b1) {
    asm volatile("mma.sync.aligned.m16n8k16.row.col.f32.bf16.bf16.f32 {%0,%1,%2,%3}, {%4,%5,%6,%7}, {%8,%9}, {%0,%1,%2,%3};"
        : "+f"(d[0]), "+f"(d[1]), "+f"(d[2]), "+f"(d[3]) : "r"(a0), "r"(a1), "r"(a2), "r"(a3), "r"(b0), "r"(b1));
}
__device__ __forceinline__ float blo(uint32_t w) { return __uint_as_float(w << 16); }
__device__ __forceinline__ float bhi(uint32_t w) { return __uint_as_float(w & 0xffff0000u); }
__device__ __forceinline__ float rbf(float x) { return __bfloat162float(__float2bfloat16_rn(x)); }
__device__ __forceinline__ uint32_t ldg32(const void* p) { uint32_t v; asm volatile("ld.global.nc.b32 %0, [%1];" : "=r"(v) : "l"(p)); return v; }
__device__ __forceinline__ uint2 ldg64(const void* p) { uint2 v; asm volatile("ld.global.nc.v2.b32 {%0,%1}, [%2];" : "=r"(v.x), "=r"(v.y) : "l"(p)); return v; }
__device__ __forceinline__ uint4 ldg128(const void* p) {
    uint4 v;
    asm volatile("ld.global.nc.v4.b32 {%0,%1,%2,%3}, [%4];" : "=r"(v.x), "=r"(v.y), "=r"(v.z), "=r"(v.w) : "l"(p));
    return v;
}
__device__ __forceinline__ uint4 ldcg128(const void* p) {
    uint4 v;
    asm volatile("ld.global.cg.v4.u32 {%0,%1,%2,%3}, [%4];" : "=r"(v.x), "=r"(v.y), "=r"(v.z), "=r"(v.w) : "l"(p) : "memory");
    return v;
}
__device__ __forceinline__ float4 ldcg128f(const void* p) {
    float4 v;
    asm volatile("ld.global.cg.v4.f32 {%0,%1,%2,%3}, [%4];" : "=f"(v.x), "=f"(v.y), "=f"(v.z), "=f"(v.w) : "l"(p) : "memory");
    return v;
}
__device__ __forceinline__ float2 ldcg64f(const void* p) { float2 v; asm volatile("ld.global.cg.v2.f32 {%0,%1}, [%2];" : "=f"(v.x), "=f"(v.y) : "l"(p) : "memory"); return v; }
__device__ __forceinline__ float ldcg32f(const void* p) { float v; asm volatile("ld.global.cg.f32 %0, [%1];" : "=f"(v) : "l"(p) : "memory"); return v; }
__device__ __forceinline__ float2 ld_stat(const float2* p) {
    float2 v;
    asm volatile("{\n.reg .b64 q;\nld.relaxed.gpu.global.b64 q, [%2];\nmov.b64 {%0, %1}, q;\n}" : "=f"(v.x), "=f"(v.y) : "l"(p) : "memory");
    return v;
}
__device__ __forceinline__ uint32_t ld_cold(const unsigned* p) { uint32_t v; asm volatile("ld.relaxed.gpu.global.u32 %0, [%1];" : "=r"(v) : "l"(p) : "memory"); return v; }
__device__ __forceinline__ uint2 ld_mod(const uint2* p) {
    uint64_t v;
    asm volatile("ld.relaxed.gpu.global.b64 %0, [%1];" : "=l"(v) : "l"(p) : "memory");
    return make_uint2((uint32_t)v, (uint32_t)(v >> 32));
}
__device__ __forceinline__ float silu(float x) {
    float e, r;
    asm("ex2.approx.ftz.f32 %0, %1;" : "=f"(e) : "f"(x * -1.4426950408889634f));
    asm("rcp.approx.ftz.f32 %0, %1;" : "=f"(r) : "f"(1.f + e));
    return x * r;
}
__device__ __forceinline__ float gelu2(float h) {
    float u = h * fmaf(h * h, 8.f * 0.0356774081f, 2.f * 0.7978845608f);
    float th;
    asm("tanh.approx.f32 %0, %1;" : "=f"(th) : "f"(u));
    return fmaf(h, th, h);
}

__device__ __forceinline__ void conv_channel(float (&d)[64], uint32_t pa, uint64_t db) {
    asm volatile("{\n.reg .b32 a0, a1, a2, a3, b0, b1, b2, b3, t0, t1;\n.reg .b64 d;\nld.shared.b32 a0, [%64];\nld.shared.b32 a1, [%64+128];\nld.shared.b32 a2, [%64+-128];\nmov.b32 a3, a0;\n"
        "ld.shared.b32 t0, [%64+256];\nld.shared.b32 t1, [%64+384];\nadd.s64 d, %65, 0;\nwgmma.fence.sync.aligned;\nwgmma.mma_async.sync.aligned.m64n128k16.f32.bf16.bf16 {%0, %1, %2, %3, %4, %5, %6, %7, %8, %9, %10, %11, %12, %13, %14, %15, %16, %17, %18, %19, %20, %21, %22, %23, %24, %25, %26, %27, %28, %29, %30, %31, %32, %33, %34, %35, %36, %37, %38, %39, %40, %41, %42, %43, %44, %45, %46, %47, %48, %49, %50, %51, %52, %53, %54, %55, %56, %57, %58, %59, %60, %61, %62, %63}, {a0, a1, a2, a3}, d, 0, 1, 1, 0;\nwgmma.commit_group.sync.aligned;\nwgmma.wait_group.sync.aligned 1;\nmov.b32 b2, a1;\nmov.b32 b0, t0;\nmov.b32 b3, t0;\nmov.b32 b1, t1;\n"
        "ld.shared.b32 t0, [%64+512];\nld.shared.b32 t1, [%64+640];\nadd.s64 d, %65, 8;\nwgmma.fence.sync.aligned;\nwgmma.mma_async.sync.aligned.m64n128k16.f32.bf16.bf16 {%0, %1, %2, %3, %4, %5, %6, %7, %8, %9, %10, %11, %12, %13, %14, %15, %16, %17, %18, %19, %20, %21, %22, %23, %24, %25, %26, %27, %28, %29, %30, %31, %32, %33, %34, %35, %36, %37, %38, %39, %40, %41, %42, %43, %44, %45, %46, %47, %48, %49, %50, %51, %52, %53, %54, %55, %56, %57, %58, %59, %60, %61, %62, %63}, {b0, b1, b2, b3}, d, 1, 1, 1, 0;\nwgmma.commit_group.sync.aligned;\nwgmma.wait_group.sync.aligned 1;\nmov.b32 a2, b1;\nmov.b32 a0, t0;\nmov.b32 a3, t0;\nmov.b32 a1, t1;\n"
        "ld.shared.b32 t0, [%64+768];\nld.shared.b32 t1, [%64+896];\nadd.s64 d, %65, 16;\nwgmma.fence.sync.aligned;\nwgmma.mma_async.sync.aligned.m64n128k16.f32.bf16.bf16 {%0, %1, %2, %3, %4, %5, %6, %7, %8, %9, %10, %11, %12, %13, %14, %15, %16, %17, %18, %19, %20, %21, %22, %23, %24, %25, %26, %27, %28, %29, %30, %31, %32, %33, %34, %35, %36, %37, %38, %39, %40, %41, %42, %43, %44, %45, %46, %47, %48, %49, %50, %51, %52, %53, %54, %55, %56, %57, %58, %59, %60, %61, %62, %63}, {a0, a1, a2, a3}, d, 1, 1, 1, 0;\nwgmma.commit_group.sync.aligned;\nwgmma.wait_group.sync.aligned 1;\nmov.b32 b2, a1;\nmov.b32 b0, t0;\nmov.b32 b3, t0;\nmov.b32 b1, t1;\n"
        "ld.shared.b32 t0, [%64+1024];\nld.shared.b32 t1, [%64+1152];\nadd.s64 d, %65, 24;\nwgmma.fence.sync.aligned;\nwgmma.mma_async.sync.aligned.m64n128k16.f32.bf16.bf16 {%0, %1, %2, %3, %4, %5, %6, %7, %8, %9, %10, %11, %12, %13, %14, %15, %16, %17, %18, %19, %20, %21, %22, %23, %24, %25, %26, %27, %28, %29, %30, %31, %32, %33, %34, %35, %36, %37, %38, %39, %40, %41, %42, %43, %44, %45, %46, %47, %48, %49, %50, %51, %52, %53, %54, %55, %56, %57, %58, %59, %60, %61, %62, %63}, {b0, b1, b2, b3}, d, 1, 1, 1, 0;\nwgmma.commit_group.sync.aligned;\nwgmma.wait_group.sync.aligned 1;\nmov.b32 a2, b1;\nmov.b32 a0, t0;\nmov.b32 a3, t0;\nmov.b32 a1, t1;\n"
        "ld.shared.b32 t0, [%64+1280];\nld.shared.b32 t1, [%64+1408];\nadd.s64 d, %65, 32;\nwgmma.fence.sync.aligned;\nwgmma.mma_async.sync.aligned.m64n128k16.f32.bf16.bf16 {%0, %1, %2, %3, %4, %5, %6, %7, %8, %9, %10, %11, %12, %13, %14, %15, %16, %17, %18, %19, %20, %21, %22, %23, %24, %25, %26, %27, %28, %29, %30, %31, %32, %33, %34, %35, %36, %37, %38, %39, %40, %41, %42, %43, %44, %45, %46, %47, %48, %49, %50, %51, %52, %53, %54, %55, %56, %57, %58, %59, %60, %61, %62, %63}, {a0, a1, a2, a3}, d, 1, 1, 1, 0;\nwgmma.commit_group.sync.aligned;\nwgmma.wait_group.sync.aligned 1;\nmov.b32 b2, a1;\nmov.b32 b0, t0;\nmov.b32 b3, t0;\nmov.b32 b1, t1;\n"
        "ld.shared.b32 t0, [%64+1536];\nld.shared.b32 t1, [%64+1664];\nadd.s64 d, %65, 40;\nwgmma.fence.sync.aligned;\nwgmma.mma_async.sync.aligned.m64n128k16.f32.bf16.bf16 {%0, %1, %2, %3, %4, %5, %6, %7, %8, %9, %10, %11, %12, %13, %14, %15, %16, %17, %18, %19, %20, %21, %22, %23, %24, %25, %26, %27, %28, %29, %30, %31, %32, %33, %34, %35, %36, %37, %38, %39, %40, %41, %42, %43, %44, %45, %46, %47, %48, %49, %50, %51, %52, %53, %54, %55, %56, %57, %58, %59, %60, %61, %62, %63}, {b0, b1, b2, b3}, d, 1, 1, 1, 0;\nwgmma.commit_group.sync.aligned;\nwgmma.wait_group.sync.aligned 1;\nmov.b32 a2, b1;\nmov.b32 a0, t0;\nmov.b32 a3, t0;\nmov.b32 a1, t1;\n"
        "ld.shared.b32 t0, [%64+1792];\nld.shared.b32 t1, [%64+1920];\nadd.s64 d, %65, 48;\nwgmma.fence.sync.aligned;\nwgmma.mma_async.sync.aligned.m64n128k16.f32.bf16.bf16 {%0, %1, %2, %3, %4, %5, %6, %7, %8, %9, %10, %11, %12, %13, %14, %15, %16, %17, %18, %19, %20, %21, %22, %23, %24, %25, %26, %27, %28, %29, %30, %31, %32, %33, %34, %35, %36, %37, %38, %39, %40, %41, %42, %43, %44, %45, %46, %47, %48, %49, %50, %51, %52, %53, %54, %55, %56, %57, %58, %59, %60, %61, %62, %63}, {a0, a1, a2, a3}, d, 1, 1, 1, 0;\nwgmma.commit_group.sync.aligned;\nwgmma.wait_group.sync.aligned 1;\nmov.b32 b2, a1;\nmov.b32 b0, t0;\nmov.b32 b3, t0;\nmov.b32 b1, t1;\n"
        "ld.shared.b32 t0, [%64+2048];\nld.shared.b32 t1, [%64+2176];\nadd.s64 d, %65, 56;\nwgmma.fence.sync.aligned;\nwgmma.mma_async.sync.aligned.m64n128k16.f32.bf16.bf16 {%0, %1, %2, %3, %4, %5, %6, %7, %8, %9, %10, %11, %12, %13, %14, %15, %16, %17, %18, %19, %20, %21, %22, %23, %24, %25, %26, %27, %28, %29, %30, %31, %32, %33, %34, %35, %36, %37, %38, %39, %40, %41, %42, %43, %44, %45, %46, %47, %48, %49, %50, %51, %52, %53, %54, %55, %56, %57, %58, %59, %60, %61, %62, %63}, {b0, b1, b2, b3}, d, 1, 1, 1, 0;\nwgmma.commit_group.sync.aligned;\nwgmma.wait_group.sync.aligned 1;\nmov.b32 a2, b1;\nmov.b32 a0, t0;\nmov.b32 a3, t0;\nmov.b32 a1, t1;\n"
        "ld.shared.b32 t0, [%64+2304];\nld.shared.b32 t1, [%64+2432];\nadd.s64 d, %65, 64;\nwgmma.fence.sync.aligned;\nwgmma.mma_async.sync.aligned.m64n96k16.f32.bf16.bf16 {%0, %1, %2, %3, %4, %5, %6, %7, %8, %9, %10, %11, %12, %13, %14, %15, %16, %17, %18, %19, %20, %21, %22, %23, %24, %25, %26, %27, %28, %29, %30, %31, %32, %33, %34, %35, %36, %37, %38, %39, %40, %41, %42, %43, %44, %45, %46, %47}, {a0, a1, a2, a3}, d, 1, 1, 1, 0;\nwgmma.commit_group.sync.aligned;\nwgmma.wait_group.sync.aligned 1;\nmov.b32 b2, a1;\nmov.b32 b0, t0;\nmov.b32 b3, t0;\nmov.b32 b1, t1;\n"
        "ld.shared.b32 t0, [%64+2560];\nld.shared.b32 t1, [%64+2688];\nadd.s64 d, %65, 72;\nwgmma.fence.sync.aligned;\nwgmma.mma_async.sync.aligned.m64n96k16.f32.bf16.bf16 {%0, %1, %2, %3, %4, %5, %6, %7, %8, %9, %10, %11, %12, %13, %14, %15, %16, %17, %18, %19, %20, %21, %22, %23, %24, %25, %26, %27, %28, %29, %30, %31, %32, %33, %34, %35, %36, %37, %38, %39, %40, %41, %42, %43, %44, %45, %46, %47}, {b0, b1, b2, b3}, d, 1, 1, 1, 0;\nwgmma.commit_group.sync.aligned;\nwgmma.wait_group.sync.aligned 1;\nmov.b32 a2, b1;\nmov.b32 a0, t0;\nmov.b32 a3, t0;\nmov.b32 a1, t1;\n"
        "ld.shared.b32 t0, [%64+2816];\nld.shared.b32 t1, [%64+2944];\nadd.s64 d, %65, 80;\nwgmma.fence.sync.aligned;\nwgmma.mma_async.sync.aligned.m64n88k16.f32.bf16.bf16 {%0, %1, %2, %3, %4, %5, %6, %7, %8, %9, %10, %11, %12, %13, %14, %15, %16, %17, %18, %19, %20, %21, %22, %23, %24, %25, %26, %27, %28, %29, %30, %31, %32, %33, %34, %35, %36, %37, %38, %39, %40, %41, %42, %43}, {a0, a1, a2, a3}, d, 1, 1, 1, 0;\nwgmma.commit_group.sync.aligned;\nwgmma.wait_group.sync.aligned 1;\nmov.b32 b2, a1;\nmov.b32 b0, t0;\nmov.b32 b3, t0;\nmov.b32 b1, t1;\n"
        "ld.shared.b32 t0, [%64+3072];\nld.shared.b32 t1, [%64+3200];\nadd.s64 d, %65, 88;\nwgmma.fence.sync.aligned;\nwgmma.mma_async.sync.aligned.m64n88k16.f32.bf16.bf16 {%0, %1, %2, %3, %4, %5, %6, %7, %8, %9, %10, %11, %12, %13, %14, %15, %16, %17, %18, %19, %20, %21, %22, %23, %24, %25, %26, %27, %28, %29, %30, %31, %32, %33, %34, %35, %36, %37, %38, %39, %40, %41, %42, %43}, {b0, b1, b2, b3}, d, 1, 1, 1, 0;\nwgmma.commit_group.sync.aligned;\nwgmma.wait_group.sync.aligned 1;\nmov.b32 a2, b1;\nmov.b32 a0, t0;\nmov.b32 a3, t0;\nmov.b32 a1, t1;\n"
        "ld.shared.b32 t0, [%64+3328];\nld.shared.b32 t1, [%64+3456];\nadd.s64 d, %65, 96;\nwgmma.fence.sync.aligned;\nwgmma.mma_async.sync.aligned.m64n80k16.f32.bf16.bf16 {%0, %1, %2, %3, %4, %5, %6, %7, %8, %9, %10, %11, %12, %13, %14, %15, %16, %17, %18, %19, %20, %21, %22, %23, %24, %25, %26, %27, %28, %29, %30, %31, %32, %33, %34, %35, %36, %37, %38, %39}, {a0, a1, a2, a3}, d, 1, 1, 1, 0;\nwgmma.commit_group.sync.aligned;\nwgmma.wait_group.sync.aligned 1;\nmov.b32 b2, a1;\nmov.b32 b0, t0;\nmov.b32 b3, t0;\nmov.b32 b1, t1;\n"
        "ld.shared.b32 t0, [%64+3584];\nld.shared.b32 t1, [%64+3712];\nadd.s64 d, %65, 104;\nwgmma.fence.sync.aligned;\nwgmma.mma_async.sync.aligned.m64n80k16.f32.bf16.bf16 {%0, %1, %2, %3, %4, %5, %6, %7, %8, %9, %10, %11, %12, %13, %14, %15, %16, %17, %18, %19, %20, %21, %22, %23, %24, %25, %26, %27, %28, %29, %30, %31, %32, %33, %34, %35, %36, %37, %38, %39}, {b0, b1, b2, b3}, d, 1, 1, 1, 0;\nwgmma.commit_group.sync.aligned;\nwgmma.wait_group.sync.aligned 1;\nmov.b32 a2, b1;\nmov.b32 a0, t0;\nmov.b32 a3, t0;\nmov.b32 a1, t1;\n"
        "ld.shared.b32 t0, [%64+3840];\nld.shared.b32 t1, [%64+3968];\nadd.s64 d, %65, 112;\nwgmma.fence.sync.aligned;\nwgmma.mma_async.sync.aligned.m64n72k16.f32.bf16.bf16 {%0, %1, %2, %3, %4, %5, %6, %7, %8, %9, %10, %11, %12, %13, %14, %15, %16, %17, %18, %19, %20, %21, %22, %23, %24, %25, %26, %27, %28, %29, %30, %31, %32, %33, %34, %35}, {a0, a1, a2, a3}, d, 1, 1, 1, 0;\nwgmma.commit_group.sync.aligned;\nwgmma.wait_group.sync.aligned 1;\nmov.b32 b2, a1;\nmov.b32 b0, t0;\nmov.b32 b3, t0;\nmov.b32 b1, t1;\n"
        "ld.shared.b32 t0, [%64+4096];\nld.shared.b32 t1, [%64+4224];\nadd.s64 d, %65, 120;\nwgmma.fence.sync.aligned;\nwgmma.mma_async.sync.aligned.m64n72k16.f32.bf16.bf16 {%0, %1, %2, %3, %4, %5, %6, %7, %8, %9, %10, %11, %12, %13, %14, %15, %16, %17, %18, %19, %20, %21, %22, %23, %24, %25, %26, %27, %28, %29, %30, %31, %32, %33, %34, %35}, {b0, b1, b2, b3}, d, 1, 1, 1, 0;\nwgmma.commit_group.sync.aligned;\nwgmma.wait_group.sync.aligned 1;\nmov.b32 a2, b1;\nmov.b32 a0, t0;\nmov.b32 a3, t0;\nmov.b32 a1, t1;\n"
        "ld.shared.b32 t0, [%64+4352];\nld.shared.b32 t1, [%64+4480];\nadd.s64 d, %65, 128;\nwgmma.fence.sync.aligned;\nwgmma.mma_async.sync.aligned.m64n64k16.f32.bf16.bf16 {%0, %1, %2, %3, %4, %5, %6, %7, %8, %9, %10, %11, %12, %13, %14, %15, %16, %17, %18, %19, %20, %21, %22, %23, %24, %25, %26, %27, %28, %29, %30, %31}, {a0, a1, a2, a3}, d, 1, 1, 1, 0;\nwgmma.commit_group.sync.aligned;\nwgmma.wait_group.sync.aligned 1;\nmov.b32 b2, a1;\nmov.b32 b0, t0;\nmov.b32 b3, t0;\nmov.b32 b1, t1;\n"
        "ld.shared.b32 t0, [%64+4608];\nld.shared.b32 t1, [%64+4736];\nadd.s64 d, %65, 136;\nwgmma.fence.sync.aligned;\nwgmma.mma_async.sync.aligned.m64n64k16.f32.bf16.bf16 {%0, %1, %2, %3, %4, %5, %6, %7, %8, %9, %10, %11, %12, %13, %14, %15, %16, %17, %18, %19, %20, %21, %22, %23, %24, %25, %26, %27, %28, %29, %30, %31}, {b0, b1, b2, b3}, d, 1, 1, 1, 0;\nwgmma.commit_group.sync.aligned;\nwgmma.wait_group.sync.aligned 1;\nmov.b32 a2, b1;\nmov.b32 a0, t0;\nmov.b32 a3, t0;\nmov.b32 a1, t1;\n"
        "ld.shared.b32 t0, [%64+4864];\nld.shared.b32 t1, [%64+4992];\nadd.s64 d, %65, 144;\nwgmma.fence.sync.aligned;\nwgmma.mma_async.sync.aligned.m64n56k16.f32.bf16.bf16 {%0, %1, %2, %3, %4, %5, %6, %7, %8, %9, %10, %11, %12, %13, %14, %15, %16, %17, %18, %19, %20, %21, %22, %23, %24, %25, %26, %27}, {a0, a1, a2, a3}, d, 1, 1, 1, 0;\nwgmma.commit_group.sync.aligned;\nwgmma.wait_group.sync.aligned 1;\nmov.b32 b2, a1;\nmov.b32 b0, t0;\nmov.b32 b3, t0;\nmov.b32 b1, t1;\n"
        "ld.shared.b32 t0, [%64+5120];\nld.shared.b32 t1, [%64+5248];\nadd.s64 d, %65, 152;\nwgmma.fence.sync.aligned;\nwgmma.mma_async.sync.aligned.m64n56k16.f32.bf16.bf16 {%0, %1, %2, %3, %4, %5, %6, %7, %8, %9, %10, %11, %12, %13, %14, %15, %16, %17, %18, %19, %20, %21, %22, %23, %24, %25, %26, %27}, {b0, b1, b2, b3}, d, 1, 1, 1, 0;\nwgmma.commit_group.sync.aligned;\nwgmma.wait_group.sync.aligned 1;\nmov.b32 a2, b1;\nmov.b32 a0, t0;\nmov.b32 a3, t0;\nmov.b32 a1, t1;\n"
        "ld.shared.b32 t0, [%64+5376];\nld.shared.b32 t1, [%64+5504];\nadd.s64 d, %65, 160;\nwgmma.fence.sync.aligned;\nwgmma.mma_async.sync.aligned.m64n48k16.f32.bf16.bf16 {%0, %1, %2, %3, %4, %5, %6, %7, %8, %9, %10, %11, %12, %13, %14, %15, %16, %17, %18, %19, %20, %21, %22, %23}, {a0, a1, a2, a3}, d, 1, 1, 1, 0;\nwgmma.commit_group.sync.aligned;\nwgmma.wait_group.sync.aligned 1;\nmov.b32 b2, a1;\nmov.b32 b0, t0;\nmov.b32 b3, t0;\nmov.b32 b1, t1;\n"
        "ld.shared.b32 t0, [%64+5632];\nld.shared.b32 t1, [%64+5760];\nadd.s64 d, %65, 168;\nwgmma.fence.sync.aligned;\nwgmma.mma_async.sync.aligned.m64n48k16.f32.bf16.bf16 {%0, %1, %2, %3, %4, %5, %6, %7, %8, %9, %10, %11, %12, %13, %14, %15, %16, %17, %18, %19, %20, %21, %22, %23}, {b0, b1, b2, b3}, d, 1, 1, 1, 0;\nwgmma.commit_group.sync.aligned;\nwgmma.wait_group.sync.aligned 1;\nmov.b32 a2, b1;\nmov.b32 a0, t0;\nmov.b32 a3, t0;\nmov.b32 a1, t1;\n"
        "ld.shared.b32 t0, [%64+5888];\nld.shared.b32 t1, [%64+6016];\nadd.s64 d, %65, 176;\nwgmma.fence.sync.aligned;\nwgmma.mma_async.sync.aligned.m64n40k16.f32.bf16.bf16 {%0, %1, %2, %3, %4, %5, %6, %7, %8, %9, %10, %11, %12, %13, %14, %15, %16, %17, %18, %19}, {a0, a1, a2, a3}, d, 1, 1, 1, 0;\nwgmma.commit_group.sync.aligned;\nwgmma.wait_group.sync.aligned 1;\nmov.b32 b2, a1;\nmov.b32 b0, t0;\nmov.b32 b3, t0;\nmov.b32 b1, t1;\n"
        "ld.shared.b32 t0, [%64+6144];\nld.shared.b32 t1, [%64+6272];\nadd.s64 d, %65, 184;\nwgmma.fence.sync.aligned;\nwgmma.mma_async.sync.aligned.m64n40k16.f32.bf16.bf16 {%0, %1, %2, %3, %4, %5, %6, %7, %8, %9, %10, %11, %12, %13, %14, %15, %16, %17, %18, %19}, {b0, b1, b2, b3}, d, 1, 1, 1, 0;\nwgmma.commit_group.sync.aligned;\nwgmma.wait_group.sync.aligned 1;\nmov.b32 a2, b1;\nmov.b32 a0, t0;\nmov.b32 a3, t0;\nmov.b32 a1, t1;\n"
        "ld.shared.b32 t0, [%64+6400];\nld.shared.b32 t1, [%64+6528];\nadd.s64 d, %65, 192;\nwgmma.fence.sync.aligned;\nwgmma.mma_async.sync.aligned.m64n32k16.f32.bf16.bf16 {%0, %1, %2, %3, %4, %5, %6, %7, %8, %9, %10, %11, %12, %13, %14, %15}, {a0, a1, a2, a3}, d, 1, 1, 1, 0;\nwgmma.commit_group.sync.aligned;\nwgmma.wait_group.sync.aligned 1;\nmov.b32 b2, a1;\nmov.b32 b0, t0;\nmov.b32 b3, t0;\nmov.b32 b1, t1;\n"
        "ld.shared.b32 t0, [%64+6656];\nld.shared.b32 t1, [%64+6784];\nadd.s64 d, %65, 200;\nwgmma.fence.sync.aligned;\nwgmma.mma_async.sync.aligned.m64n32k16.f32.bf16.bf16 {%0, %1, %2, %3, %4, %5, %6, %7, %8, %9, %10, %11, %12, %13, %14, %15}, {b0, b1, b2, b3}, d, 1, 1, 1, 0;\nwgmma.commit_group.sync.aligned;\nwgmma.wait_group.sync.aligned 1;\nmov.b32 a2, b1;\nmov.b32 a0, t0;\nmov.b32 a3, t0;\nmov.b32 a1, t1;\n"
        "ld.shared.b32 t0, [%64+6912];\nld.shared.b32 t1, [%64+7040];\nadd.s64 d, %65, 208;\nwgmma.fence.sync.aligned;\nwgmma.mma_async.sync.aligned.m64n24k16.f32.bf16.bf16 {%0, %1, %2, %3, %4, %5, %6, %7, %8, %9, %10, %11}, {a0, a1, a2, a3}, d, 1, 1, 1, 0;\nwgmma.commit_group.sync.aligned;\nwgmma.wait_group.sync.aligned 1;\nmov.b32 b2, a1;\nmov.b32 b0, t0;\nmov.b32 b3, t0;\nmov.b32 b1, t1;\n"
        "ld.shared.b32 t0, [%64+7168];\nld.shared.b32 t1, [%64+7296];\nadd.s64 d, %65, 216;\nwgmma.fence.sync.aligned;\nwgmma.mma_async.sync.aligned.m64n24k16.f32.bf16.bf16 {%0, %1, %2, %3, %4, %5, %6, %7, %8, %9, %10, %11}, {b0, b1, b2, b3}, d, 1, 1, 1, 0;\nwgmma.commit_group.sync.aligned;\nwgmma.wait_group.sync.aligned 1;\nmov.b32 a2, b1;\nmov.b32 a0, t0;\nmov.b32 a3, t0;\nmov.b32 a1, t1;\n"
        "ld.shared.b32 t0, [%64+7424];\nld.shared.b32 t1, [%64+7552];\nadd.s64 d, %65, 224;\nwgmma.fence.sync.aligned;\nwgmma.mma_async.sync.aligned.m64n16k16.f32.bf16.bf16 {%0, %1, %2, %3, %4, %5, %6, %7}, {a0, a1, a2, a3}, d, 1, 1, 1, 0;\nwgmma.commit_group.sync.aligned;\nwgmma.wait_group.sync.aligned 1;\nmov.b32 b2, a1;\nmov.b32 b0, t0;\nmov.b32 b3, t0;\nmov.b32 b1, t1;\n"
        "ld.shared.b32 t0, [%64+7680];\nld.shared.b32 t1, [%64+7808];\nadd.s64 d, %65, 232;\nwgmma.fence.sync.aligned;\nwgmma.mma_async.sync.aligned.m64n16k16.f32.bf16.bf16 {%0, %1, %2, %3, %4, %5, %6, %7}, {b0, b1, b2, b3}, d, 1, 1, 1, 0;\nwgmma.commit_group.sync.aligned;\nwgmma.wait_group.sync.aligned 1;\nmov.b32 a2, b1;\nmov.b32 a0, t0;\nmov.b32 a3, t0;\nmov.b32 a1, t1;\n"
        "ld.shared.b32 t0, [%64+7936];\nld.shared.b32 t1, [%64+8064];\nadd.s64 d, %65, 240;\nwgmma.fence.sync.aligned;\nwgmma.mma_async.sync.aligned.m64n8k16.f32.bf16.bf16 {%0, %1, %2, %3}, {a0, a1, a2, a3}, d, 1, 1, 1, 0;\nwgmma.commit_group.sync.aligned;\nwgmma.wait_group.sync.aligned 1;\nmov.b32 b2, a1;\nmov.b32 b0, t0;\nmov.b32 b3, t0;\nmov.b32 b1, t1;\n"
        "add.s64 d, %65, 248;\nwgmma.fence.sync.aligned;\nwgmma.mma_async.sync.aligned.m64n8k16.f32.bf16.bf16 {%0, %1, %2, %3}, {b0, b1, b2, b3}, d, 1, 1, 1, 0;\nwgmma.commit_group.sync.aligned;\nwgmma.wait_group.sync.aligned 0;\n"
        "}" : "+f"(d[0]), "+f"(d[1]), "+f"(d[2]), "+f"(d[3]), "+f"(d[4]), "+f"(d[5]), "+f"(d[6]), "+f"(d[7]), "+f"(d[8]), "+f"(d[9]), "+f"(d[10]), "+f"(d[11]), "+f"(d[12]), "+f"(d[13]), "+f"(d[14]), "+f"(d[15]), "+f"(d[16]), "+f"(d[17]), "+f"(d[18]), "+f"(d[19]), "+f"(d[20]), "+f"(d[21]), "+f"(d[22]), "+f"(d[23]), "+f"(d[24]), "+f"(d[25]), "+f"(d[26]), "+f"(d[27]), "+f"(d[28]), "+f"(d[29]), "+f"(d[30]), "+f"(d[31]), "+f"(d[32]), "+f"(d[33]), "+f"(d[34]), "+f"(d[35]), "+f"(d[36]), "+f"(d[37]), "+f"(d[38]), "+f"(d[39]), "+f"(d[40]), "+f"(d[41]), "+f"(d[42]), "+f"(d[43]), "+f"(d[44]), "+f"(d[45]), "+f"(d[46]), "+f"(d[47]), "+f"(d[48]), "+f"(d[49]), "+f"(d[50]), "+f"(d[51]), "+f"(d[52]), "+f"(d[53]), "+f"(d[54]), "+f"(d[55]), "+f"(d[56]), "+f"(d[57]), "+f"(d[58]), "+f"(d[59]), "+f"(d[60]), "+f"(d[61]), "+f"(d[62]), "+f"(d[63]) : "r"(pa), "l"(db) : "memory");
}
__device__ __forceinline__ void wgmma_rs80(float (&d)[40], uint32_t a0, uint32_t a1, uint32_t a2, uint32_t a3, uint64_t db, int sc) {
    asm volatile("{\n.reg .pred p;\nsetp.ne.b32 p, %45, 0;\n"
        "wgmma.mma_async.sync.aligned.m64n80k16.f32.bf16.bf16 {%0, %1, %2, %3, %4, %5, %6, %7, %8, %9, %10, %11, %12, %13, %14, %15, %16, %17, %18, %19, %20, %21, %22, %23, %24, %25, %26, %27, %28, %29, %30, %31, %32, %33, %34, %35, %36, %37, %38, %39}, {%40, %41, %42, %43}, %44, p, 1, 1, 1;\n}\n"
        : "+f"(d[0]), "+f"(d[1]), "+f"(d[2]), "+f"(d[3]), "+f"(d[4]), "+f"(d[5]), "+f"(d[6]), "+f"(d[7]), "+f"(d[8]), "+f"(d[9]), "+f"(d[10]), "+f"(d[11]), "+f"(d[12]), "+f"(d[13]), "+f"(d[14]), "+f"(d[15]), "+f"(d[16]), "+f"(d[17]), "+f"(d[18]), "+f"(d[19]), "+f"(d[20]), "+f"(d[21]), "+f"(d[22]), "+f"(d[23]), "+f"(d[24]), "+f"(d[25]), "+f"(d[26]), "+f"(d[27]), "+f"(d[28]), "+f"(d[29]), "+f"(d[30]), "+f"(d[31]), "+f"(d[32]), "+f"(d[33]), "+f"(d[34]), "+f"(d[35]), "+f"(d[36]), "+f"(d[37]), "+f"(d[38]), "+f"(d[39]) : "r"(a0), "r"(a1), "r"(a2), "r"(a3), "l"(db), "r"(sc));
}
__device__ __forceinline__ void wgmma_ss80(float (&d)[40], uint64_t da, uint64_t db, int sc) {
    asm volatile("{\n.reg .pred p;\nsetp.ne.b32 p, %42, 0;\n"
        "wgmma.mma_async.sync.aligned.m64n80k16.f32.bf16.bf16 {%0, %1, %2, %3, %4, %5, %6, %7, %8, %9, %10, %11, %12, %13, %14, %15, %16, %17, %18, %19, %20, %21, %22, %23, %24, %25, %26, %27, %28, %29, %30, %31, %32, %33, %34, %35, %36, %37, %38, %39}, %40, %41, p, 1, 1, 0, 1;\n}\n"
        : "+f"(d[0]), "+f"(d[1]), "+f"(d[2]), "+f"(d[3]), "+f"(d[4]), "+f"(d[5]), "+f"(d[6]), "+f"(d[7]), "+f"(d[8]), "+f"(d[9]), "+f"(d[10]), "+f"(d[11]), "+f"(d[12]), "+f"(d[13]), "+f"(d[14]), "+f"(d[15]), "+f"(d[16]), "+f"(d[17]), "+f"(d[18]), "+f"(d[19]), "+f"(d[20]), "+f"(d[21]), "+f"(d[22]), "+f"(d[23]), "+f"(d[24]), "+f"(d[25]), "+f"(d[26]), "+f"(d[27]), "+f"(d[28]), "+f"(d[29]), "+f"(d[30]), "+f"(d[31]), "+f"(d[32]), "+f"(d[33]), "+f"(d[34]), "+f"(d[35]), "+f"(d[36]), "+f"(d[37]), "+f"(d[38]), "+f"(d[39]) : "l"(da), "l"(db), "r"(sc));
}
__device__ __forceinline__ void wgmma_ss80t(float (&d)[40], uint64_t da, uint64_t db, int sc) {
    asm volatile("{\n.reg .pred p;\nsetp.ne.b32 p, %42, 0;\n"
        "wgmma.mma_async.sync.aligned.m64n80k16.f32.bf16.bf16 {%0, %1, %2, %3, %4, %5, %6, %7, %8, %9, %10, %11, %12, %13, %14, %15, %16, %17, %18, %19, %20, %21, %22, %23, %24, %25, %26, %27, %28, %29, %30, %31, %32, %33, %34, %35, %36, %37, %38, %39}, %40, %41, p, 1, 1, 1, 1;\n}\n"
        : "+f"(d[0]), "+f"(d[1]), "+f"(d[2]), "+f"(d[3]), "+f"(d[4]), "+f"(d[5]), "+f"(d[6]), "+f"(d[7]), "+f"(d[8]), "+f"(d[9]), "+f"(d[10]), "+f"(d[11]), "+f"(d[12]), "+f"(d[13]), "+f"(d[14]), "+f"(d[15]), "+f"(d[16]), "+f"(d[17]), "+f"(d[18]), "+f"(d[19]), "+f"(d[20]), "+f"(d[21]), "+f"(d[22]), "+f"(d[23]), "+f"(d[24]), "+f"(d[25]), "+f"(d[26]), "+f"(d[27]), "+f"(d[28]), "+f"(d[29]), "+f"(d[30]), "+f"(d[31]), "+f"(d[32]), "+f"(d[33]), "+f"(d[34]), "+f"(d[35]), "+f"(d[36]), "+f"(d[37]), "+f"(d[38]), "+f"(d[39]) : "l"(da), "l"(db), "r"(sc));
}
__device__ __forceinline__ void wgmma_ss8_ta(float (&d)[4], uint64_t da, uint64_t db, int sc) {
    asm volatile("{\n.reg .pred p;\nsetp.ne.b32 p, %6, 0;\n"
        "wgmma.mma_async.sync.aligned.m64n8k16.f32.bf16.bf16 {%0, %1, %2, %3}, %4, %5, p, 1, 1, 1, 0;\n}\n"
        : "+f"(d[0]), "+f"(d[1]), "+f"(d[2]), "+f"(d[3]) : "l"(da), "l"(db), "r"(sc));
}
__device__ __forceinline__ void wgmma_rs8(float (&d)[4], uint32_t a0, uint32_t a1, uint32_t a2, uint32_t a3, uint64_t db, int sc) {
    asm volatile("{\n.reg .pred p;\nsetp.ne.b32 p, %9, 0;\n"
        "wgmma.mma_async.sync.aligned.m64n8k16.f32.bf16.bf16 {%0, %1, %2, %3}, {%4, %5, %6, %7}, %8, p, 1, 1, 0;\n}\n"
        : "+f"(d[0]), "+f"(d[1]), "+f"(d[2]), "+f"(d[3]) : "r"(a0), "r"(a1), "r"(a2), "r"(a3), "l"(db), "r"(sc));
}
__device__ __forceinline__ void wgmma_rs128(float (&d)[64], uint32_t a0, uint32_t a1, uint32_t a2, uint32_t a3, uint64_t db, int sc) {
    asm volatile("{\n.reg .pred p;\nsetp.ne.b32 p, %69, 0;\n"
        "wgmma.mma_async.sync.aligned.m64n128k16.f32.bf16.bf16 {%0, %1, %2, %3, %4, %5, %6, %7, %8, %9, %10, %11, %12, %13, %14, %15, %16, %17, %18, %19, %20, %21, %22, %23, %24, %25, %26, %27, %28, %29, %30, %31, %32, %33, %34, %35, %36, %37, %38, %39, %40, %41, %42, %43, %44, %45, %46, %47, %48, %49, %50, %51, %52, %53, %54, %55, %56, %57, %58, %59, %60, %61, %62, %63}, {%64, %65, %66, %67}, %68, p, 1, 1, 1;\n}\n"
        : "+f"(d[0]), "+f"(d[1]), "+f"(d[2]), "+f"(d[3]), "+f"(d[4]), "+f"(d[5]), "+f"(d[6]), "+f"(d[7]), "+f"(d[8]), "+f"(d[9]), "+f"(d[10]), "+f"(d[11]), "+f"(d[12]), "+f"(d[13]), "+f"(d[14]), "+f"(d[15]), "+f"(d[16]), "+f"(d[17]), "+f"(d[18]), "+f"(d[19]), "+f"(d[20]), "+f"(d[21]), "+f"(d[22]), "+f"(d[23]), "+f"(d[24]), "+f"(d[25]), "+f"(d[26]), "+f"(d[27]), "+f"(d[28]), "+f"(d[29]), "+f"(d[30]), "+f"(d[31]), "+f"(d[32]), "+f"(d[33]), "+f"(d[34]), "+f"(d[35]), "+f"(d[36]), "+f"(d[37]), "+f"(d[38]), "+f"(d[39]), "+f"(d[40]), "+f"(d[41]), "+f"(d[42]), "+f"(d[43]), "+f"(d[44]), "+f"(d[45]), "+f"(d[46]), "+f"(d[47]), "+f"(d[48]), "+f"(d[49]), "+f"(d[50]), "+f"(d[51]), "+f"(d[52]), "+f"(d[53]), "+f"(d[54]), "+f"(d[55]), "+f"(d[56]), "+f"(d[57]), "+f"(d[58]), "+f"(d[59]), "+f"(d[60]), "+f"(d[61]), "+f"(d[62]), "+f"(d[63]) : "r"(a0), "r"(a1), "r"(a2), "r"(a3), "l"(db), "r"(sc));
}
__device__ __forceinline__ void wgmma_rs88(float (&d)[44], uint32_t a0, uint32_t a1, uint32_t a2, uint32_t a3, uint64_t db, int sc) {
    asm volatile("{\n.reg .pred p;\nsetp.ne.b32 p, %49, 0;\n"
        "wgmma.mma_async.sync.aligned.m64n88k16.f32.bf16.bf16 {%0, %1, %2, %3, %4, %5, %6, %7, %8, %9, %10, %11, %12, %13, %14, %15, %16, %17, %18, %19, %20, %21, %22, %23, %24, %25, %26, %27, %28, %29, %30, %31, %32, %33, %34, %35, %36, %37, %38, %39, %40, %41, %42, %43}, {%44, %45, %46, %47}, %48, p, 1, 1, 1;\n}\n"
        : "+f"(d[0]), "+f"(d[1]), "+f"(d[2]), "+f"(d[3]), "+f"(d[4]), "+f"(d[5]), "+f"(d[6]), "+f"(d[7]), "+f"(d[8]), "+f"(d[9]), "+f"(d[10]), "+f"(d[11]), "+f"(d[12]), "+f"(d[13]), "+f"(d[14]), "+f"(d[15]), "+f"(d[16]), "+f"(d[17]), "+f"(d[18]), "+f"(d[19]), "+f"(d[20]), "+f"(d[21]), "+f"(d[22]), "+f"(d[23]), "+f"(d[24]), "+f"(d[25]), "+f"(d[26]), "+f"(d[27]), "+f"(d[28]), "+f"(d[29]), "+f"(d[30]), "+f"(d[31]), "+f"(d[32]), "+f"(d[33]), "+f"(d[34]), "+f"(d[35]), "+f"(d[36]), "+f"(d[37]), "+f"(d[38]), "+f"(d[39]), "+f"(d[40]), "+f"(d[41]), "+f"(d[42]), "+f"(d[43]) : "r"(a0), "r"(a1), "r"(a2), "r"(a3), "l"(db), "r"(sc));
}
__device__ __forceinline__ void wgmma_rs128k(float (&d)[64], uint32_t a0, uint32_t a1, uint32_t a2, uint32_t a3, uint64_t db, int sc) {
    asm volatile("{\n.reg .pred p;\nsetp.ne.b32 p, %69, 0;\n"
        "wgmma.mma_async.sync.aligned.m64n128k16.f32.bf16.bf16 {%0, %1, %2, %3, %4, %5, %6, %7, %8, %9, %10, %11, %12, %13, %14, %15, %16, %17, %18, %19, %20, %21, %22, %23, %24, %25, %26, %27, %28, %29, %30, %31, %32, %33, %34, %35, %36, %37, %38, %39, %40, %41, %42, %43, %44, %45, %46, %47, %48, %49, %50, %51, %52, %53, %54, %55, %56, %57, %58, %59, %60, %61, %62, %63}, {%64, %65, %66, %67}, %68, p, 1, 1, 0;\n}\n"
        : "+f"(d[0]), "+f"(d[1]), "+f"(d[2]), "+f"(d[3]), "+f"(d[4]), "+f"(d[5]), "+f"(d[6]), "+f"(d[7]), "+f"(d[8]), "+f"(d[9]), "+f"(d[10]), "+f"(d[11]), "+f"(d[12]), "+f"(d[13]), "+f"(d[14]), "+f"(d[15]), "+f"(d[16]), "+f"(d[17]), "+f"(d[18]), "+f"(d[19]), "+f"(d[20]), "+f"(d[21]), "+f"(d[22]), "+f"(d[23]), "+f"(d[24]), "+f"(d[25]), "+f"(d[26]), "+f"(d[27]), "+f"(d[28]), "+f"(d[29]), "+f"(d[30]), "+f"(d[31]), "+f"(d[32]), "+f"(d[33]), "+f"(d[34]), "+f"(d[35]), "+f"(d[36]), "+f"(d[37]), "+f"(d[38]), "+f"(d[39]), "+f"(d[40]), "+f"(d[41]), "+f"(d[42]), "+f"(d[43]), "+f"(d[44]), "+f"(d[45]), "+f"(d[46]), "+f"(d[47]), "+f"(d[48]), "+f"(d[49]), "+f"(d[50]), "+f"(d[51]), "+f"(d[52]), "+f"(d[53]), "+f"(d[54]), "+f"(d[55]), "+f"(d[56]), "+f"(d[57]), "+f"(d[58]), "+f"(d[59]), "+f"(d[60]), "+f"(d[61]), "+f"(d[62]), "+f"(d[63]) : "r"(a0), "r"(a1), "r"(a2), "r"(a3), "l"(db), "r"(sc));
}
__device__ __forceinline__ void wgmma_rs88k(float (&d)[44], uint32_t a0, uint32_t a1, uint32_t a2, uint32_t a3, uint64_t db, int sc) {
    asm volatile("{\n.reg .pred p;\nsetp.ne.b32 p, %49, 0;\n"
        "wgmma.mma_async.sync.aligned.m64n88k16.f32.bf16.bf16 {%0, %1, %2, %3, %4, %5, %6, %7, %8, %9, %10, %11, %12, %13, %14, %15, %16, %17, %18, %19, %20, %21, %22, %23, %24, %25, %26, %27, %28, %29, %30, %31, %32, %33, %34, %35, %36, %37, %38, %39, %40, %41, %42, %43}, {%44, %45, %46, %47}, %48, p, 1, 1, 0;\n}\n"
        : "+f"(d[0]), "+f"(d[1]), "+f"(d[2]), "+f"(d[3]), "+f"(d[4]), "+f"(d[5]), "+f"(d[6]), "+f"(d[7]), "+f"(d[8]), "+f"(d[9]), "+f"(d[10]), "+f"(d[11]), "+f"(d[12]), "+f"(d[13]), "+f"(d[14]), "+f"(d[15]), "+f"(d[16]), "+f"(d[17]), "+f"(d[18]), "+f"(d[19]), "+f"(d[20]), "+f"(d[21]), "+f"(d[22]), "+f"(d[23]), "+f"(d[24]), "+f"(d[25]), "+f"(d[26]), "+f"(d[27]), "+f"(d[28]), "+f"(d[29]), "+f"(d[30]), "+f"(d[31]), "+f"(d[32]), "+f"(d[33]), "+f"(d[34]), "+f"(d[35]), "+f"(d[36]), "+f"(d[37]), "+f"(d[38]), "+f"(d[39]), "+f"(d[40]), "+f"(d[41]), "+f"(d[42]), "+f"(d[43]) : "r"(a0), "r"(a1), "r"(a2), "r"(a3), "l"(db), "r"(sc));
}
__device__ __forceinline__ void wgmma_rs80k(float (&d)[40], uint32_t a0, uint32_t a1, uint32_t a2, uint32_t a3, uint64_t db, int sc) {
    asm volatile("{\n.reg .pred p;\nsetp.ne.b32 p, %45, 0;\n"
        "wgmma.mma_async.sync.aligned.m64n80k16.f32.bf16.bf16 {%0, %1, %2, %3, %4, %5, %6, %7, %8, %9, %10, %11, %12, %13, %14, %15, %16, %17, %18, %19, %20, %21, %22, %23, %24, %25, %26, %27, %28, %29, %30, %31, %32, %33, %34, %35, %36, %37, %38, %39}, {%40, %41, %42, %43}, %44, p, 1, 1, 0;\n}\n"
        : "+f"(d[0]), "+f"(d[1]), "+f"(d[2]), "+f"(d[3]), "+f"(d[4]), "+f"(d[5]), "+f"(d[6]), "+f"(d[7]), "+f"(d[8]), "+f"(d[9]), "+f"(d[10]), "+f"(d[11]), "+f"(d[12]), "+f"(d[13]), "+f"(d[14]), "+f"(d[15]), "+f"(d[16]), "+f"(d[17]), "+f"(d[18]), "+f"(d[19]), "+f"(d[20]), "+f"(d[21]), "+f"(d[22]), "+f"(d[23]), "+f"(d[24]), "+f"(d[25]), "+f"(d[26]), "+f"(d[27]), "+f"(d[28]), "+f"(d[29]), "+f"(d[30]), "+f"(d[31]), "+f"(d[32]), "+f"(d[33]), "+f"(d[34]), "+f"(d[35]), "+f"(d[36]), "+f"(d[37]), "+f"(d[38]), "+f"(d[39]) : "r"(a0), "r"(a1), "r"(a2), "r"(a3), "l"(db), "r"(sc));
}
__device__ __forceinline__ void wgmma_rs64(float (&d)[32], uint32_t a0, uint32_t a1, uint32_t a2, uint32_t a3, uint64_t db, int sc) {
    asm volatile("{\n.reg .pred p;\nsetp.ne.b32 p, %37, 0;\n"
        "wgmma.mma_async.sync.aligned.m64n64k16.f32.bf16.bf16 {%0, %1, %2, %3, %4, %5, %6, %7, %8, %9, %10, %11, %12, %13, %14, %15, %16, %17, %18, %19, %20, %21, %22, %23, %24, %25, %26, %27, %28, %29, %30, %31}, {%32, %33, %34, %35}, %36, p, 1, 1, 1;\n}\n"
        : "+f"(d[0]), "+f"(d[1]), "+f"(d[2]), "+f"(d[3]), "+f"(d[4]), "+f"(d[5]), "+f"(d[6]), "+f"(d[7]), "+f"(d[8]), "+f"(d[9]), "+f"(d[10]), "+f"(d[11]), "+f"(d[12]), "+f"(d[13]), "+f"(d[14]), "+f"(d[15]), "+f"(d[16]), "+f"(d[17]), "+f"(d[18]), "+f"(d[19]), "+f"(d[20]), "+f"(d[21]), "+f"(d[22]), "+f"(d[23]), "+f"(d[24]), "+f"(d[25]), "+f"(d[26]), "+f"(d[27]), "+f"(d[28]), "+f"(d[29]), "+f"(d[30]), "+f"(d[31]) : "r"(a0), "r"(a1), "r"(a2), "r"(a3), "l"(db), "r"(sc));
}

__device__ __forceinline__ uint64_t mkdesc(uint32_t lo) { return ((uint64_t)0x40000040u << 32) | lo; }
template <int F> __device__ __forceinline__ uint32_t lop3(uint32_t a, uint32_t b, uint32_t c) { uint32_t r; asm("lop3.b32 %0, %1, %2, %3, %4;" : "=r"(r) : "r"(a), "r"(b), "r"(c), "n"(F)); return r; }
__device__ __forceinline__ void stg128_tag(void* p, uint32_t x, uint32_t y, uint32_t z, uint32_t u, uint32_t ep, int w) {
    stg128(p, lop3<0xB8>(x, w == 0, ep), lop3<0xB8>(y, w == 1, ep), lop3<0xB8>(z, w == 2, ep), lop3<0xB8>(u, w == 3, ep));
}
__device__ __forceinline__ uint32_t tag(uint32_t w, uint32_t ep) { asm("lop3.b32 %0, %0, 1, %1, 0xB8;" : "+r"(w) : "r"(ep)); return w; }
template <int N> __device__ __forceinline__ void pack_part(uint32_t (&p)[32], const float (&v)[N], uint32_t ep) {
#pragma unroll
    for (int i = 0; i < N / 2; i++) p[i] = (i & 3) ? pack2(v[2 * i], v[2 * i + 1]) : tag(pack2(v[2 * i], v[2 * i + 1]), ep);
#pragma unroll
    for (int i = 0; i < N / 2; i++) asm volatile("" : "+r"(p[i]));
}
__device__ __forceinline__ void st_part(uint4* p, const uint32_t* v) {
    asm volatile("{\n.reg .b64 l, h;\n.reg .b128 q;\nmov.b64 l, {%1, %2};\nmov.b64 h, {%3, %4};\nmov.b128 q, {l, h};\nst.relaxed.gpu.global.b128 [%0], q;\n}"
                 ::"l"(p), "r"(v[0]), "r"(v[1]), "r"(v[2]), "r"(v[3]) : "memory");
}
__device__ __forceinline__ void st_peer(uint32_t a, uint32_t x, uint32_t y, uint32_t z, uint32_t w, uint32_t bar) {
    asm volatile("st.async.shared::cluster.mbarrier::complete_tx::bytes.v4.b32 [%0], {%1, %2, %3, %4}, [%5];" ::"r"(a), "r"(x), "r"(y), "r"(z), "r"(w), "r"(bar) : "memory");
}
__device__ __forceinline__ int g4_block(int c, int j) { return c ? j ^ (8 - 2 * c) : 8 + (j & 1); }
__device__ __forceinline__ uint32_t recv_off(int w) { return w ? OFF_XR : OFF_REM; }
__device__ __forceinline__ uint4 ld_part(const void* p) {
    uint4 v;
    asm volatile("{\n.reg .b64 l, h;\n.reg .b128 q;\nld.relaxed.gpu.global.b128 q, [%4];\nmov.b128 {l, h}, q;\nmov.b64 {%0, %1}, l;\nmov.b64 {%2, %3}, h;\n}"
                 : "=r"(v.x), "=r"(v.y), "=r"(v.z), "=r"(v.w) : "l"(p) : "memory");
    return v;
}
__device__ __forceinline__ void ld_part4(uint4 (&u)[4], const uint4* p, int st) {
#pragma unroll
    for (int i = 0; i < 4; i++) u[i] = ld_part(p + i * st);
}
__device__ __forceinline__ uint32_t stale4(const uint4 (&u)[4], uint32_t ep) { return lop3<0x7E>(u[0].x, ep, u[1].x) | lop3<0x7E>(u[2].x, ep, u[3].x); }
__device__ __forceinline__ void add8(float* v, uint4 u) {
    v[0] += blo(u.x); v[1] += bhi(u.x); v[2] += blo(u.y); v[3] += bhi(u.y);
    v[4] += blo(u.z); v[5] += bhi(u.z); v[6] += blo(u.w); v[7] += bhi(u.w);
}
__device__ __forceinline__ void unpack8(float* v, uint4 u) {
    v[0] = blo(u.x); v[1] = bhi(u.x); v[2] = blo(u.y); v[3] = bhi(u.y); v[4] = blo(u.z); v[5] = bhi(u.z); v[6] = blo(u.w); v[7] = bhi(u.w);
}
__device__ __forceinline__ uint4 add2(uint4 a, uint4 b) { return make_uint4(add2(a.x, b.x), add2(a.y, b.y), add2(a.z, b.z), add2(a.w, b.w)); }
__device__ __forceinline__ void base16(float* v, uint4 b, float2 c, float2 d) {
    v[0] = fmaf(c.x, v[0], blo(b.x)); v[1] = fmaf(c.y, v[1], bhi(b.x)); v[2] = fmaf(c.x, v[2], blo(b.y)); v[3] = fmaf(c.y, v[3], bhi(b.y));
    v[4] = fmaf(d.x, v[4], blo(b.z)); v[5] = fmaf(d.y, v[5], bhi(b.z)); v[6] = fmaf(d.x, v[6], blo(b.w)); v[7] = fmaf(d.y, v[7], bhi(b.w));
}
__device__ __forceinline__ uint32_t split2(float x) { const float h = rbf(x); return pack2(h, x - h); }
__device__ __forceinline__ uint32_t b80_desc(uint32_t dsb, uint32_t wn, uint32_t rn, uint32_t h) {
    const uint32_t wb = dsb + OFF_W + (wn & 7) * 16384 + h * 8192, rm = dsb + OFF_REM + rn * 4096 + h * 2048;
    return (wb >> 4) | ((rm - wb) << 12);
}
constexpr int64_t B80_STEP = 128 - (126 << 16), B80_HALF = 512 - (384 << 16);
constexpr uint32_t ring_mask(int L) {
    uint32_t m = 0;
    for (int i = L; i < 20; i++) m |= (uint32_t)(i >= 20 - L || !((i - L) & 1)) << i;
    return m;
}
constexpr uint32_t M0 = ring_mask(LEAD1), M1 = ring_mask(10), M2 = ring_mask(XLEAD);
__device__ __forceinline__ uint32_t ring_pos(int w, int n, int L) { return w ? (n < 10 - L ? L + 2 * n : 10 + n) : (n < L ? n : 2 * n - L + 1); }
__device__ __forceinline__ int g1_block(int n, int j) { return n < 5 ? 2 * n + (j & 1) : 2 * n - 9 - (j & 1); }

__device__ __forceinline__ void load_tile(const Maps& mp, uint32_t dst, int e, int tile, int kb, int j, uint32_t bar) {
    mbar_expect(bar, 8192);
    tma_ld2(dst, &mp.x[e], 64 * (e == 0 ? tile : e == 1 ? kb : 0), 64 * (e == 0 ? g1_block(kb, j) : e == 1 ? tile : 10 * tile + kb), bar);
}

template <int OCT>
__device__ __forceinline__ void gemv_tile(float (&d)[4], uint32_t a, uint32_t b, int kb0) {
    uint32_t alo = ((a & 0x3FFFF) >> 4) | 0x10000u, blo_ = ((b & 0x3FFFF) >> 4) | (OCT << 16);
#pragma unroll 1
    for (int s = 0; s < 20; s += 4) {
        const int kb = kb0 + (s >> 2);
        const uint32_t bk = blo_ + (OCT == 7 ? (kb & 1) * 288 + (kb >> 1) * 56 : kb * 64);
        wg_fence();
#pragma unroll
        for (int q = 0; q < 4; q++) wgmma_ss8_ta(d, mkdesc(alo + (s + q) * 128), ((uint64_t)8 << 32) | (bk + q * 2 * OCT), s + q);
        wg_commit();
    }
    wg_wait<0>();
    reg_fence(d);
}

__device__ __forceinline__ void flush_tile(uint32_t st, bf16* dst, int u) {
#pragma unroll
    for (int i = 0; i < 2; i++) {
        const int idx = u + 320 * i, row = idx >> 3, c = idx & 7;
        stg128(dst + (size_t)row * S_ + 8 * c, lds128(st + row * 128 + ((c ^ ((row >> 1) & 7)) << 4)));
    }
}

__device__ __forceinline__ int tid_now() { int t; asm volatile("mov.u32 %0, %%tid.x;" : "=r"(t)); return t; }
__device__ __forceinline__ float zscale(float c) { return c == 0.f ? 0x1p-30f : c; }
__device__ __forceinline__ bool bar_any(int id, bool p) {
    uint32_t r;
    asm volatile("{\n.reg .pred a, b;\nsetp.ne.u32 a, %2, 0;\nbarrier.red.or.pred.aligned b, %1, 128, a;\nselp.u32 %0, 1, 0, b;\n}" : "=r"(r) : "r"(id), "r"((uint32_t)p) : "memory");
    return r != 0;
}

__global__ void __cluster_dims__(2, 1, 1) __launch_bounds__(NTHR, 1) fused_kernel(const __grid_constant__ Ptrs pp, bf16* __restrict__ out, const __grid_constant__ Maps mp) {
    extern __shared__ __align__(1024) uint8_t smem_raw[];
    const uint32_t sb = s2u(smem_raw), bars = sb + M_BAR, dsb = sb & 0x3FFFF;
    const int id = blockIdx.x, warp = __shfl_sync(0xffffffffu, (int)threadIdx.x >> 5, 0), wg = warp >> 2;
    const uint32_t c0 = clock_lo();
#define TIDS const int tid = tid_now(), lane = tid & 31, wt = tid & 127, g = lane >> 2, t = lane & 3; (void)wt; (void)g; (void)t;
    TS(threadIdx.x == 0, 0) TG(threadIdx.x == 0, 62)

    if (id >= 128) {
        TIDS
        if (sb & 1023) __trap();
        const int hs = id - 128;
        constexpr int H_B = 204800;
        static_assert(H_B + TAB_BYTES + 8 * VEC_BYTES <= OFF_M, "helper map");
        if (warp < 10 && elect()) { mbar_init(bars + warp * 8, 1); mbar_init(bars + 80 + warp * 8, 1); asm volatile("fence.mbarrier_init.release.cluster;" ::: "memory"); }
        __syncthreads();
        const uint32_t e0 = ld_cold(&g_epoch);
        wait_clock(c0, HELP_T);
        uint4 wr[10];
#pragma unroll
        for (int u = 0; u < 10; u++) wr[u] = ldg128(((hs >> 1) ? pp.w2 : pp.w1) + (size_t)(320 * (hs & 1) + (tid >> 4) + 32 * u) * D_ + 512 + 8 * (tid & 15));
        {
            const int r = tid >> 4, c = tid & 15;
            uint4* dst[2];
#pragma unroll
            for (int e = 0; e < 2; e++) {
                const int p = !(hs >> 1) ? r : e && (hs & 1) ? (r & ~14) | ((r & 6) << 1) | ((r & 8) >> 2) : (r & ~30) | ((r & 6) << 2) | ((r & 24) >> 2);
                dst[e] = &g_wr[(((hs >> 1) * 8 + (c >> 1)) * 10 + 5 * (hs & 1)) * 128 + (p & 15) * 8 + ((2 * (p >> 4) + (c & 1)) ^ (p & 7))];
            }
#pragma unroll
            for (int u = 0; u < 10; u++) stg128(reinterpret_cast<uint4*>(reinterpret_cast<uintptr_t>(dst[u >= 6]) ^ (64 * (u & 1))) + (u >> 1) * 128, wr[u]);
        }
        __syncthreads();
        if (warp == 0) signal_cnt(&g_cnt.wr[0], lane, 1);
        __syncthreads();
        if (warp < 5 && elect()) {
            const int un = 5 * hs + warp;
            mbar_expect(bars + warp * 8, 40960);
            tma_ld2(sb + warp * 40960, &mp.w1h, 64 * (un >> 1), 320 * (un & 1), bars + warp * 8);
            tma_ld2(sb + warp * 40960 + 20480, &mp.w1h, 64 * (un >> 1), 320 * (un & 1) + 160, bars + warp * 8);
        }
        if (tid < 320) {
            const uint4* gm = reinterpret_cast<const uint4*>(g_mod + 3 * D_) + tid;
            const unsigned epoch = e0 + 1;
            uint4 r[6];
            unsigned it = 0;
            for (;;) {
                uint32_t bad = 0;
#pragma unroll
                for (int i = 0; i < 6; i++) { r[i] = ld_part(gm + (i >> 1) * (D_ / 2) + (i & 1) * 3 * D_); bad |= (r[i].y ^ epoch) | (r[i].w ^ epoch); }
                if (__all_sync(~0u, !bad)) break;
                if (++it > SPIN_LIMIT) SPIN_FAIL(54)
            }
            uint32_t mv[3];
#pragma unroll
            for (int i = 0; i < 3; i++) mv[i] = pack2(__uint_as_float(r[2 * i].x) + __uint_as_float(r[2 * i + 1].x), __uint_as_float(r[2 * i].z) + __uint_as_float(r[2 * i + 1].z));
            const uint32_t sw2 = mv[0], cw = add2(mv[1], 0x3f803f80u), gw = mv[2];
            const float c0 = blo(cw), c1 = bhi(cw), s0 = blo(sw2), s1 = bhi(sw2);
            const float i0 = __frcp_rn(zscale(c0)), i1 = __frcp_rn(zscale(c1));
            const uint32_t ci = pack2(i0, i1), cq = pack2(i0 * i0, i1 * i1);
            const uint32_t a = sb + H_B + ((tid >> 5) & 1) * 4608 + (tid >> 6) * 896 + ((tid >> 2) & 7) * 112 + (tid & 3) * 4;
            sts32(a, ci); sts32(a + 16, pack2(i0 - blo(ci), i1 - bhi(ci)));
            sts32(a + 32, cq); sts32(a + 48, pack2(fmaf(i0, i0, -blo(cq)), fmaf(i1, i1, -bhi(cq))));
            sts32(a + 64, cw); sts32(a + 80, sw2); sts32(a + 96, 0x3f803f80u);
            if ((tid & ~35) == 284) sts32(a + 112, 0);
            const uint32_t v = sb + H_B + TAB_BYTES + (tid < 256 ? (tid >> 5) * VEC_BYTES + (tid & 31) * 8 : ((tid - 256) >> 3) * VEC_BYTES + 256 + (tid & 7) * 8);
            sts64f(v, blo(gw), bhi(gw)); sts64f(v + 320, c0, c1); sts64f(v + 640, s0, s1); sts64f(v + 960, i0, i1);
            float k[5] = {c0 + c1, s0 + s1, fmaf(c0, c0, c1 * c1), fmaf(c0, s0, c1 * s1), fmaf(s0, s0, s1 * s1)};
#pragma unroll 1
            for (int o = 16; o; o >>= 1) {
#pragma unroll
                for (int e = 0; e < 5; e++) k[e] += __shfl_xor_sync(~0u, k[e], o);
            }
            const uint32_t ks = sb + H_B + TAB_BYTES + (lane & 7) * VEC_BYTES + 1280 + (warp >> 1) * 32;
            if ((warp & 1) && lane < 8) { sts128f(ks, k[0], k[1], k[2], k[3]); sts128f(ks + 16, k[4], 0.f, 0.f, 0.f); }
            bar_sync(3, 320);
            if (!(warp & 1) && lane < 8) {
                const float4 o = lds128f(ks);
                sts128f(ks, k[0] + o.x, k[1] + o.y, k[2] + o.z, k[3] + o.w); sts32(ks + 16, __float_as_uint(k[4] + __uint_as_float(lds32(ks + 16))));
            }
            fence_async_smem();
        }
        __syncthreads();
        if (hs == 0 && warp == 15 && elect()) {
            asm volatile("cp.async.bulk.global.shared::cta.bulk_group [%0], [%1], %2;\ncp.async.bulk.commit_group;\ncp.async.bulk.wait_group 0;"
                         ::"l"(g_tab), "r"(sb + H_B), "n"(TAB_BYTES + 8 * VEC_BYTES) : "memory");
            asm volatile("red.release.gpu.global.add.u32 [%0], 1;" ::"l"(&g_cnt.tab[0]) : "memory");
        }
        __syncwarp();
#pragma unroll 1
        for (int i = wg; i < 20; i += 4) {
            const int r = i / 5, b = i - 5 * r, un = 5 * hs + b, u3 = 20 * r + un;
            auto refill = [&](int e, int u, uint32_t fb) {
                mbar_expect(fb, 40960);
                tma_ld2(sb + e * 40960, &mp.w3h, 64 * (u >> 1), 320 * (u & 1), fb);
                tma_ld2(sb + e * 40960 + 20480, &mp.w3h, 64 * (u >> 1), 320 * (u & 1) + 160, fb);
            };
            if (i > 4 && i < 9) {
                bar_sync(1, 512);
                if (warp == 0) {
                    signal_cnt(&g_cnt.uv[0], lane, 1);
                    if (elect()) {
#pragma unroll 1
                        for (int e = 0; e < 5; e++) refill(e, 5 * hs + e, bars + (5 + e) * 8);
                        l2_prefetch(pp.w2 + (size_t)160 * hs * D_, 160 * D_ * 2);
                    }
                    __syncwarp();
                }
            }
            mbar_wait(bars + i * 8, 0);
            float d[4];
            gemv_tile<7>(d, sb + b * 40960, sb + H_B, 5 * (un & 1));
            const int col = 16 * (warp & 3) + g;
            float* dst = r ? g_cs3 + (un & 1) * 1920 + 64 * ((u3 >> 1) - 10) + col : g_uv + (un & 1) * 3 * D_ + 2 * D_ + 64 * (un >> 1) + col;
            if (t == 3) { dst[0] = d[0]; dst[8] = d[2]; }
            if (r == 0 && t == 2) { dst[-2 * D_] = d[0]; dst[8 - 2 * D_] = d[2]; dst[-D_] = d[1]; dst[8 - D_] = d[3]; }
            if (r == 1 || r == 2) {
                bar_sync(4 + wg, 128);
                if (wt == 0) refill(b, u3, bars + (i + 5) * 8);
            }
        }
        __syncthreads();
        if (warp == 0) signal_cnt(&g_cnt.cs[0], lane, 1);
        if (tid == 511) l2_prefetch(pp.w4 + (size_t)432 * hs * D_, 432 * D_ * 2);
        for (uint32_t it = 0; ld_cold(&g_cnt.cs[0]) < 4;) { if (++it > SPIN_LIMIT) SPIN_FAIL(47) }
        asm volatile("fence.acquire.gpu;" ::: "memory");
        if (tid < 432) {
            const int jj = 2 * hs + (tid >= 216), c = tid % 216;
            const float* src = g_cs3 + (c < 192 ? 192 * jj + c : 1344 + 24 * jj + c);
            const uint32_t s = split2(ldcg32f(src) + ldcg32f(src + 1920));
            stg128(&g_cs3b[432 * hs + tid], s, s & 0xffffu, 0, 0);
        }
        __syncthreads();
        if (warp == 0) signal_cnt(&g_cnt.cs2[0], lane, 1);
        if (tid == 0 && hs == 3) {
            uint32_t it = 0;
            while (ld_cold(&g_epoch) == e0) { __nanosleep(256); if (++it > (1u << 20)) SPIN_FAIL(48) }
        }
        return;
    }

    if (elect()) {
        if (warp == 15) {
            mbar_init(bars + B_IN * 8, 1); mbar_init(bars + B_IN * 8 + 8, 1);
            asm volatile("fence.mbarrier_init.release.cluster;" ::: "memory");
            mbar_expect(bars + B_IN * 8, 131 * 160);
            tma_ld2(sb + OFF_KIN, &mp.k, 80 * (id & 7), 64 * (id >> 3) - 3, bars + B_IN * 8);
            tma_ld2(sb + OFF_VIN, &mp.v, 80 * (id & 7), 64 * (id >> 3), bars + B_IN * 8);
        } else if (warp < 13) {
            const uint32_t n = (0x1C14111111881ull >> (4 * warp)) & 15;
#pragma unroll
            for (int i = 0; i < 4; i++) mbar_init(bars + warp * 64 + i * 8, n);
            if (warp == 11) { mbar_init(bars + B_XFREE * 8, 16); mbar_init(bars + B_OWN * 8, 8); }
            else if (warp < 11) {
#pragma unroll
                for (int i = 4; i < 8; i++) mbar_init(bars + warp * 64 + i * 8, n);
            }
            asm volatile("fence.mbarrier_init.release.cluster;" ::: "memory");
        }
    }
    asm volatile("" ::"l"(pp.s), "l"(pp.c), "l"(out));
    TR4((threadIdx.x & 31) == 0, warp)
    const int pr = id >> 1;
    const int grp = pr < 4 ? 15 : pr < 36 ? (pr - 4) & 7 : 8 + (pr - 36) % 7;
    const int j = 2 * (pr < 4 ? pr : pr < 36 ? (pr - 4) >> 3 : (pr - 36) / 7) + (id & 1);

    if (wg == 3) {
        TIDS
        const int sw = warp - 12;
        uint32_t ep = ld_cold(&g_epoch);
        TR4(lane == 0, 20 + sw)
        __syncthreads();
        TR4(lane == 0, 30 + sw)
        asm volatile("barrier.cluster.arrive.relaxed.aligned;" ::: "memory");
        if (sw == 0) {
#pragma unroll 1
            for (int n = 0; n < 12; n++) {
                wait_clock(c0, PF_T0 + PF_DT * n);
                if (elect()) l2_prefetch(n < 4 ? (const char*)pp.q + id * 20480 + n * 5120 : (const char*)pp.w_mod + id * 38400 + (n - 4) * 4800, n < 4 ? 5120 : 4800);
            }
        } else if (sw == 1) {
            wait_clock(c0, T_SSM);
            if (elect()) {
                mbar_expect(bars + B_SSM * 8, 20480);
                bulk_ld(sb + OFF_SSM, pp.ssm_k + (size_t)5 * id * S_, 20480, bars + B_SSM * 8);
            }
            mbar_spin(bars + B_KVS * 8, 0);
            signal_cnt(&g_cnt.kv[(id & 7) * 32], lane, 1, true);
            TS(lane == 0, 2)
            mbar_spin(bars + B_RAW * 8, 0);
            if (elect()) {
                mbar_expect(bars + B_QIN * 8, 20480);
                tma_ld3(sb + OFF_QIN, &mp.q, 0, 16 * id, 0, bars + B_QIN * 8);
            }
        } else if (sw == 2) {
            if (elect()) {
#pragma unroll 1
                for (int i = 2; i < (int)(sizeof(Maps) / sizeof(CUtensorMap)); i++) asm volatile("prefetch.tensormap [%0];" ::"l"(&mp.k + i) : "memory");
#pragma unroll 1
                for (int i = B_SUMS; i < B_SIG; i++) mbar_expect(bars + i * 8, i < B_RECV ? 2048 : (i & 3) < 3 ? 8192 : 3072);
            }
            wait_cnt(&g_cnt.kv[(id >> 4) * 32], 16, true);
            TS(lane == 0, 4)
            if (elect()) {
                mbar_expect(bars + B_RAW * 8, 12288);
                mbar_expect(bars + B_RAW2 * 8, 8192);
#pragma unroll
                for (int c = 0; c < 5; c++) bulk_ld(sb + OFF_CH + c * CH_BYTES, g_kvT + (size_t)(5 * id + c) * S_, 4096, bars + (c < 3 ? B_RAW : B_RAW2) * 8);
            }
            mbar_spin(bars + B_BK * 8, 0);
            mbar_spin(bars + B_QIN * 8, 0);
            if (id < 120 && elect()) {
                mbar_expect(bars + B_WM * 8, 40960);
                tma_ld2(sb + OFF_WM, &mp.wmod, 64 * pr, 320 * (id & 1), bars + B_WM * 8);
                tma_ld2(sb + OFF_WM + 20480, &mp.wmod, 64 * pr, 320 * (id & 1) + 160, bars + B_WM * 8);
            }
            TS(lane == 0, 57)
        } else {
            wait_clock(c0, T_KVB);
            if (elect()) {
                mbar_expect(bars + (B_IN + 1) * 8, 131 * 160);
                tma_ld2(sb + OFF_KIN + 10752, &mp.k, 80 * (id & 7), 64 * (id >> 3) + 1021, bars + (B_IN + 1) * 8);
                tma_ld2(sb + OFF_VIN + 10240, &mp.v, 80 * (id & 7), 64 * (id >> 3) + 1024, bars + (B_IN + 1) * 8);
            }
            TS(lane == 0, 53)
            if (lane == 0) sts32(sb + M_EP, ep + 1);
            sts32(sb + M_NUL + lane * 4, 0);
#pragma unroll 1
            for (int i = 0; i < 10; i++) sts128(sb + OFF_Z + i * 512 + lane * 16, 0, 0, 0, 0);
            __syncwarp();
#pragma unroll 1
            for (int i = lane; i < 160; i += 32) {
                const uint32_t c = ldg32(pp.c + 320 * (id & 1) + 2 * i);
                sts32(sb + OFF_Z + (i >> 2) * 128 + (i & 3) * 4, pack2(silu(blo(c)), silu(bhi(c))));
            }
            fence_async_smem();
            for (uint32_t ph = 0, again = 1; again; ph ^= 1) {
                mbar_spin(bars + B_RAW2 * 8, ph);
                uint32_t bad = 0;
#pragma unroll
                for (int i = 0; i < 8; i++) bad |= lop3<0x7E>(lds32(sb + OFF_CH + 3 * CH_BYTES + i * 512 + lane * 16), ~ep, lds32(sb + OFF_CH + 4 * CH_BYTES + i * 512 + lane * 16));
                again = __any_sync(~0u, bad & 1);
                if (again && elect()) {
                    mbar_expect(bars + B_RAW2 * 8, 8192);
#pragma unroll
                    for (int c = 3; c < 5; c++) bulk_ld(sb + OFF_CH + c * CH_BYTES, g_kvT + (size_t)(5 * id + c) * S_, 4096, bars + B_RAW2 * 8);
                }
            }
            if (elect()) mbar_arrive(bars + B_RAW3 * 8);
        }
        {
            mbar_spin(bars + B_QIN * 8, 0);
            asm volatile("add.u32 %0, %0, 1;" : "+r"(ep));
            TS(wt == 0, 54)
            const int tk = 8 * ((lane >> 1) & 1) + 2 * (lane >> 3) + (lane & 1), ck = 4 * (sw & 1) + ((lane >> 1) & 2);
            const uint32_t src = sb + OFF_QIN + (sw >> 1) * 2048 + tk * 128;
            bf16* dst = g_qT + (size_t)id * 16 * D_ + (32 * sw + 8 * (t & 2) + g) * 16 + 8 * (t & 1);
constexpr int QU = Q_UNROLL;
#pragma unroll QU
            for (int i = 0; i < 5; i++) {
                uint32_t r[8];
                ldsm4t(src + i * 4096 + ((ck ^ (tk & 7)) << 4), r[0], r[1], r[2], r[3]);
                ldsm4t(src + i * 4096 + (((ck + 1) ^ (tk & 7)) << 4), r[4], r[5], r[6], r[7]);
                stg128(dst + i * 2048, tag(r[0], ep), r[1], r[2], r[3]);
                stg128(dst + i * 2048 + 128, tag(r[4], ep), r[5], r[6], r[7]);
            }
            float s1 = 0.f, s2 = 0.f;
#pragma unroll 2
            for (int i = 0; i < 10; i++) {
                const uint4 w4 = lds128(sb + OFF_QIN + i * 2048 + wt * 16);
                const uint32_t w[4] = {w4.x, w4.y, w4.z, w4.w};
#pragma unroll
                for (int e = 0; e < 4; e++) { const float a = blo(w[e]), b = bhi(w[e]); s1 += a + b; s2 = fmaf(a, a, fmaf(b, b, s2)); }
            }
#pragma unroll
            for (int o = 1; o < 8; o *= 2) { s1 += __shfl_xor_sync(~0u, s1, o); s2 += __shfl_xor_sync(~0u, s2, o); }
            s1 *= 1.f / D_;
            uint32_t rs = pack2(rsqrtf(fmaxf(s2 * (1.f / D_) - s1 * s1, 0.f) + 1e-5f), 0.f);
            if (lane < 8) rs = tag(rs, ep);
            rs = pack2(blo(rs), -s1 * blo(rs));
            const uint32_t sel = lane ? 0x7632 : 0x5410;
            const uint32_t a0 = __shfl_sync(~0u, rs, 0), a1 = __shfl_sync(~0u, rs, 8), a2 = __shfl_sync(~0u, rs, 16), a3 = __shfl_sync(~0u, rs, 24);
            if (lane < 2) stg64(g_qst + lane * S_ + 16 * id + 4 * sw, tag(__byte_perm(a0, a1, sel), ep), __byte_perm(a2, a3, sel));
            TS(wt == 0, 55)
        }
        bar_sync(6, 128);
        if (sw == 3) {
            signal_cnt(&g_cnt.q[(lane & 3) * 32], lane, 4, true);
            TS(lane == 0, 3)
        }
        asm volatile("setmaxnreg.dec.sync.aligned.u32 32;");
        asm volatile("barrier.cluster.wait.aligned;" ::: "memory");
        if (sw == 1) {
            mbar_spin(bars + B_XS * 8, 0);
            signal_cnt(&g_cnt.x[(lane & 3) * 32], lane, 4, true);
            TS(lane == 0, 20)
#pragma unroll 1
            for (int e = 1; e < 3; e++) {
                wait_cnt(e == 1 ? &g_cnt.g1[min(grp + 15 + min(lane, 2), 31) * 32] : &g_cnt.g2[(grp + 16) * 32], 32, true);
                if (elect()) mbar_arrive(bars + (B_GATE + 2 + e) * 8);
                TS(lane == 0, 27 + 2 * e)
            }
            return;
        }
        if (sw == 2) {
            mbar_spin(bars + B_XS * 8, 0);
            fence_async_smem();
            const unsigned* flag = &g_cnt.x[(id & 3) * 32];
            uint32_t m = 0;
            int n = 0, a0 = 0, a1 = 0;
            uint32_t k = 0;
#pragma unroll 1
            for (int s = 0; s < 6; s++) {
                const int e = s >> 1, end = 20 * e + ((s & 1) ? 20 : e == 0 ? LEAD1 : e == 1 ? 10 : XLEAD);
                if (s & 1) mbar_spin(bars + (B_GATE + 2 + e) * 8, !e);
                else {
                    wait_cnt(flag, e ? 32 : 128, true);
                    flag = e ? &g_cnt.g2[grp * 32] : &g_cnt.g1[max(grp - 1 + min(lane, 2), 0) * 32];
                    m = e == 0 ? M0 : e == 1 ? M1 : M2;
                    k = e ? 0 : (j & 1) * 0x400040;
                    a0 = e ? 0 : 64 * grp; a1 = e == 0 ? 0 : e == 1 ? 64 * grp : 640 * grp;
                    TS(lane == 0, 26 + 2 * e)
                }
                const int b0 = e ? 0 : 1024, b1 = e == 0 ? 0 : e == 1 ? 1024 : 10240, step = e ? 64 : 128;
                const uint32_t turn = e ? 1 : 512 + 64 * (j & 1), back = -448 - 128 * (j & 1);
#pragma unroll 1
                for (; n < end; n++, m >>= 1) {
                    const uint32_t w = m & 1, sh = 16 * w, kc = (k >> sh) & 0xffff;
                    k += (kc == turn ? back : step) << sh;
                    const uint32_t fb = bars + (B_LAND + (n & 7)) * 8;
                    mbar_spin(fb - (B_LAND - B_XEMPTY) * 8, ((n >> 3) & 1) ^ 1);
                    TR2(lane == 0 && n < 40, 20 + n)
                    if (elect()) {
                        mbar_expect(fb, 8192);
                        tma_ld2(sb + OFF_XR + (n & 7) * 8192, &mp.x[e], a0 + w * b0 + (e == 1 ? kc : 0), a1 + w * b1 + (e == 1 ? 0 : kc), fb);
                    }
                }
            }
            mbar_spin(bars + B_VEC3 * 8, 0);
            unsigned old = 0;
            asm volatile("{\n.reg .pred P;\nsetp.eq.s32 P, %2, 0;\n@P atom.relaxed.gpu.global.add.u32 %0, [%1], %3;\n}" : "+r"(old) : "l"(&g_cnt.done[0]), "r"(lane), "r"(1) : "memory");
            if (__any_sync(~0u, old == 127)) {
#pragma unroll 1
                for (int i = lane; i < (int)(sizeof(Counters) / 128); i += 32) reinterpret_cast<unsigned*>(&g_cnt)[i * 32] = 0;
                signal_cnt(&g_epoch, lane, 1, true);
            }
        } else if (sw == 0) {
            wait_cnt(&g_cnt.wr[0], 4);
            mbar_spin(bars + B_QRDY * 8, 0);
            const uint32_t wf = bars + B_WFULL * 8, we = bars + B_WEMPTY * 8;
#pragma unroll 1
            for (int n = 0; n < 5; n++) {
                if (n == 3) { mbar_spin(bars + B_XS * 8, 0); fence_async_smem(); }
                TR2(lane == 0, 70 + n)
                if (elect()) {
                    const uint32_t fb = wf + n * 8, dst = sb + OFF_W + n * 16384;
                    mbar_expect(fb, 20480);
#pragma unroll 1
                    for (int h = 0; h < 2; h++) {
                        const int kb = g1_block(2 * n + h, j);
                        tma_ld2(dst + h * 8192, &mp.w1, 64 * j, 64 * kb, fb);
                        bulk_ld(sb + OFF_REM + n * 4096 + h * 2048, &g_wr[(j * 10 + kb) * 128], 2048, fb);
                    }
                }
            }
            mbar_spin(bars + B_GATE * 8, 0);
#pragma unroll 1
            for (int i = -3; i < 5; i++) {
                const int n = i < 0 ? 8 + i : 5 + i;
                const uint32_t fb = wf + (n & 7) * 8;
                if (i >= 0) mbar_spin(we + i * 8, 0);
                TR2(lane == 0 && i >= 0, 70 + n)
                if (elect()) {
                    if (i < 0 || i >= 3) { mbar_expect(fb, 20480); tma_ld5(sb + OFF_W + (n & 7) * 16384, n < 9 ? &mp.w2a : &mp.w2b, 64 * j, n < 9 ? 4 * (n - 5) : 0, fb); }
                    if (i >= 0) bulk_ld(sb + OFF_REM + i * 4096, &g_wr[((8 + j) * 10 + 2 * i) * 128], 4096, fb);
                }
            }
            mbar_spin(bars + (B_GATE + 1) * 8, 0);
#pragma unroll 1
            for (int n = 10; n < 30; n++) {
                if (n == W3_N2) mbar_spin(bars + (B_GATE + 2) * 8, 0);
                mbar_spin(we + (n & 7) * 8, ((n >> 3) & 1) ^ 1);
                TR2(lane == 0, 70 + n)
                if (elect()) {
                    const uint32_t dst = sb + OFF_W + (n & 7) * 16384, fb = wf + (n & 7) * 8;
                    mbar_expect(fb, 13824);
                    tma_ld3(dst, &mp.w3a, 0, 32 * (n - 10), 3 * j, fb);
                    tma_ld2(dst + 12288, &mp.w3b, 1536 + 24 * j, 32 * (n - 10), fb);
                }
            }
            mbar_spin(we + 6 * 8, 0);
            mbar_spin(bars + B_VEC3 * 8, 0);
            if (elect()) { mbar_expect(wf + 6 * 8, 3456); bulk_ld(sb + OFF_W + 6 * 16384, &g_cs3b[216 * j], 3456, wf + 6 * 8); }
#pragma unroll 1
            for (int n = 31; n < 50; n++) {
                const int e = n < 38 ? 4 : (n - 38) & 3, m0 = n == 35, m1 = e == 3 ? -1 : m0 | (e == 1), rem = 96 + 3 * (j >> 1);
                const int c1_ = j ^ (n < 38 ? 6 : 4 >> ((n - 38) >> 2) & 6), c0_ = n < 38 ? 8 + (j & 1) : c1_;
                const int f = (0xC840A80C204ull >> (4 * min(n - 31, e + 7))) & 15;
                const int r0 = m0 ? rem : 6 * (j ^ (f >> 3)) + (f & 6), r1 = m1 ? rem : r0 + (n < 38 ? 0 : 2);
                mbar_spin(we + (n & 7) * 8, ((n >> 3) & 1) ^ 1);
                if (elect()) {
                    const uint32_t dst = sb + OFF_W + (n & 7) * 16384, fb = wf + (n & 7) * 8;
                    mbar_expect(fb, m1 < 0 ? 8192 : 16384 - 2048 * (m0 + m1));
                    tma_ld2(dst, &mp.w4[m0], 64 * c0_, r0 * (32 >> m0), fb);
                    if (m1 >= 0) tma_ld2(dst + 8192, &mp.w4[m1], 64 * c1_, r1 * (32 >> m1), fb);
                }
            }
#pragma unroll 1
            for (int w = 0; w < 2; w++) {
                const uint4* src = g_part + (size_t)(grp + 16 * w) * 40960;
                mbar_spin(bars + (B_RING + w) * 8, 1);
                if (elect()) {
                    const uint32_t fb = bars + (B_IN + w) * 8, rem = sb + OFF_OUT + w * 10240;
                    mbar_expect(fb, 10240);
                    bulk_ld(rem + 8192, &g_x1f[((grp + 16 * w) * 8 + j) * 640 + 512], 2048, fb);
#pragma unroll 1
                    for (int i = 0; i < 4; i++) bulk_ld(rem + i * 2048, src + ((j >> 2) + 2 * i) * 5120 + 4096 + j * 128, 2048, fb);
                }
            }
        } else {
            {
                wait_cnt(&g_cnt.tab[0], 1);
                mbar_spin(bars + B_QRDY * 8, 0);
                if (elect()) {
                    mbar_expect(bars + B_TAB * 8, TAB_BYTES / 2 + VEC_BYTES);
                    bulk_ld(sb + OFF_TAB, g_tab + (j & 1) * (TAB_BYTES / 32), TAB_BYTES / 2, bars + B_TAB * 8);
                    bulk_ld(sb + M_GB, g_tab + (TAB_BYTES + j * VEC_BYTES) / 16, VEC_BYTES, bars + B_TAB * 8);
                }
                TS(lane == 0, 5)
            }
            wait_cnt(&g_cnt.uv[0], 4);
#pragma unroll 1
            for (int c = lane; c < 80; c += 32) {
                const float* src = g_uv + (c < 64 ? 64 * j + c : 448 + 16 * j + c);
                const uint32_t u = split2(ldcg32f(src) + ldcg32f(src + 3 * D_)), v = split2(ldcg32f(src + D_) + ldcg32f(src + 4 * D_));
                const uint32_t s = split2(ldcg32f(src + 2 * D_) + ldcg32f(src + 5 * D_));
                sts128(sb + OFF_F1 + c * 16, u, __byte_perm(u, v, 0x5410), __byte_perm(v, 0, 0x1032), s);
                sts128(sb + M_F1 + c * 16, s & 0xffffu, 0, 0, 0);
            }
            fence_async_smem();
            warp_arrive(bars + B_VEC * 8);
            TS(lane == 0, 9)
            wait_cnt(&g_cnt.cs2[0], 4);
            if (elect()) mbar_arrive(bars + B_VEC3 * 8);
            TS(lane == 0, 19)
        }
        return;
    }

    {
        uint32_t ep;
        {
            TIDS
            ep = ld_cold(&g_epoch);
            const int cp = (tid + 16) % 40, cp1 = tid % 40;
            const uint4 sh0 = ldg128(pp.shift_k + (80 * (id & 7) + 2 * cp1) * 4), sh1 = ldg128(pp.shift_k + (80 * (id & 7) + 2 * cp) * 4);
            uint32_t dd;
            asm volatile("ld.global.nc.u16 %0, [%1];" : "=r"(dd) : "l"(pp.ssm_D + 5 * id + min(wg + 3 * lane, 4)));
            TR4(lane == 0, 40 + warp)
            __syncthreads();
            asm volatile("barrier.cluster.arrive.relaxed.aligned;" ::: "memory");
            asm volatile("add.u32 %0, %0, 1;" : "+r"(ep));
#pragma unroll 1
            for (int hw = 0; hw < 2; hw++) {
                if ((unsigned)(warp - 2 * hw) >= 10) continue;
                const int u = tid - 64 * hw;
                const int c = hw ? cp : cp1, oc = u / 40, line = 31 - 16 * hw - (id >> 3);
                const uint4 sh = hw ? sh1 : sh0;
                const uint32_t st = sb + OFF_ST + hw * 10240, sta = st + c * 256 + ((((6 - 2 * (oc & 3)) ^ (oc >> 2) ^ (line & 1)) ^ (c & 7)) << 4), in = oc * 1280 + c * 4;
                const uint32_t f0 = __byte_perm(sh.x, sh.z, 0x5410), f1 = __byte_perm(sh.x, sh.z, 0x7632), f2 = __byte_perm(sh.y, sh.w, 0x5410), f3 = __byte_perm(sh.y, sh.w, 0x7632);
                uint32_t kk[11], vv[8];
                mbar_spin(bars + (B_IN + hw) * 8, 0);
                TS(tid == 64, 18 + 42 * hw)
#pragma unroll
                for (int i = 0; i < 11; i++) kk[i] = lds32(sb + OFF_KIN + hw * 10752 + in + i * 160);
#pragma unroll
                for (int i = 0; i < 8; i++) vv[i] = lds32(sb + OFF_VIN + hw * 10240 + in + i * 160);
#pragma unroll
                for (int i = 0; i < 8; i++) vv[i] = mul2(fma2(kk[i + 3], f0, fma2(kk[i + 2], f1, fma2(kk[i + 1], f2, mul2(kk[i], f3)))), vv[i]);
                sts128(sta, tag(__byte_perm(vv[0], vv[1], 0x5410), ep), __byte_perm(vv[2], vv[3], 0x5410), __byte_perm(vv[4], vv[5], 0x5410), __byte_perm(vv[6], vv[7], 0x5410));
                sts128(sta + 128, tag(__byte_perm(vv[0], vv[1], 0x7632), ep), __byte_perm(vv[2], vv[3], 0x7632), __byte_perm(vv[4], vv[5], 0x7632), __byte_perm(vv[6], vv[7], 0x7632));
                bar_sync(7 + hw, 320);
                flush_tile(st, g_kvT + (size_t)(80 * (id & 7)) * S_ + 64 * line, u);
                TS(tid == 64 && hw, 1)
            }
            warp_arrive(bars + B_KVS * 8);
            if (tid < 320) sts128(sb + OFF_CH + (tid >> 6) * CH_BYTES + 4096 + (tid & 63) * 16, 0, 0, 0, 0);
            mbar_spin(bars + B_SSM * 8, 0);
            TS(tid == 0, 14)
#pragma unroll 1
            for (int u0 = wg; u0 < 20; u0 += 12) {
                uint2 w[4];
                uint32_t pv[4];
#pragma unroll
                for (int i = 0; i < 4; i++) {
                    const uint32_t a = sb + OFF_SSM + min(u0 + 3 * i, 19) * 1024 + wt * 8;
                    w[i] = lds64(a); pv[i] = lds32(a - 4);
                }
#pragma unroll
                for (int i = 0; i < 4; i++) {
                    const int un = min(u0 + 3 * i, 19);
                    sts128(sb + OFF_CH + (un >> 2) * CH_BYTES + OFF_P + (un & 3) * 2048 + wt * 16, __byte_perm(w[i].x, pv[i], 0x7610), __byte_perm(w[i].x, 0, 0x1032), __byte_perm(w[i].y, w[i].x, 0x7610), __byte_perm(w[i].y, 0, 0x1032));
                }
            }
            __syncwarp();
            if (wt < 2 - (wg >> 1)) {
                const uint32_t h = lds32(sb + OFF_SSM + (wg + 3 * wt) * 4096), h0 = pack2(blo(h) + blo(dd), 0.f);
                sts64f(sb + OFF_CH + (wg + 3 * wt) * CH_BYTES + OFF_P, __uint_as_float(h0), __uint_as_float(__byte_perm(h, h0, 0x5432)));
            }
            fence_async_smem();
            warp_arrive(bars + B_BK * 8);
            asm volatile("barrier.cluster.wait.aligned;" ::: "memory");
            mbar_spin(bars + B_BK * 8, 0);
            TS(tid == 0, 15)
        }

#pragma unroll 1
        for (int c = wg; c < 5; c += 3) {
            const uint32_t kvb = sb + OFF_CH + c * CH_BYTES;
            mbar_spin(bars + (c < 3 ? B_RAW : B_RAW3) * 8, 0);
            for (uint32_t ph = 0; c < 3; ph ^= 1) {
                const int wt = tid_now() & 127;
                if (!RARE(bar_any(1 + wg, lop3<0x7E>(lds32(kvb + wt * 16), ep, lds32(kvb + 2048 + wt * 16)) & 1))) break;
                if (wt == 0) { mbar_expect(bars + (B_RETRY + wg) * 8, 4096); bulk_ld(kvb, g_kvT + (size_t)(5 * id + c) * S_, 4096, bars + (B_RETRY + wg) * 8); }
                mbar_spin(bars + (B_RETRY + wg) * 8, ph);
                STALE1(3)
            }
            TS(threadIdx.x == 0, c ? 13 : 11)
            float acc[64];
            {
                const int l = tid_now() & 31;
                conv_channel(acc, kvb + OFF_P + (8 * (warp & 3) + (l >> 2) - 2 * (l & 3)) * 4, (((uint64_t)0xC0000010u << 32) | ((kvb & 0x3FFFF) >> 4) | 0x10000u) + pp.nil);
            }
            TS(threadIdx.x == 0, c ? 16 : 12)
            if (c < 3) warp_arrive(bars + B_R1 * 8);
            else mbar_spin(bars + B_R1 * 8, 0);
            if (wg == 2 && id < 120) {
                TIDS
                mbar_spin(bars + B_RAW3 * 8, 0);
                mbar_spin(bars + B_WM * 8, 0);
                TS(wt == 0, 56)
                float d[4];
                gemv_tile<8>(d, sb + OFF_WM, sb + OFF_Z, 0);
                const float d2 = __shfl_up_sync(~0u, d[2], 1);
                TS(wt == 0, 7)
                if (t < 2) asm volatile("{\n.reg .b64 v;\nmov.b64 v, {%1, %2};\nst.relaxed.gpu.global.b64 [%0], v;\n}" ::"l"(g_mod + (id & 1) * 6 * D_ + 64 * pr + 16 * (warp & 3) + g + 8 * t),
                                        "r"(__float_as_uint(t ? d2 : d[0])), "r"(lds32(sb + M_EP)) : "memory");
            }
            TR4(threadIdx.x == 0, 60 + (c >= 3) * 10)
            TIDS
            const int e = 127 - 8 * (lane >> 4) - (lane & 7), u0 = (warp & 3) + 8 * (e >> 2) + (e & 3) + 4 * ((lane >> 3) & 1);
            const uint32_t ring = sb + OFF_RING + c * 16384 + (warp & 3) * 4096, wa = ring + (u0 ^ ((u0 >> 1) & 4)) * 16;
            if (lane < (warp & 3)) sts128(ring + lane * 16, 0, 0, 0, 0);
#pragma unroll
            for (int i = 0; i < 8; i++)
                stsm4t(i == 0 && u0 >= 256 ? sb + M_SINK : wa - 512 * i, pack2(acc[8 * i], acc[8 * i + 1]), pack2(acc[8 * i + 2], acc[8 * i + 3]),
                       pack2(acc[8 * i + 4], acc[8 * i + 5]), pack2(acc[8 * i + 6], acc[8 * i + 7]));
            warp_arrive(bars + (B_RING + c) * 8);
            TR4(threadIdx.x == 0, 61 + (c >= 3) * 10)
        }
        TIDS
        if (wg == 2) bar_sync(3, 128);
        if (warp == 8) {
            wait_cnt(&g_cnt.q[(id & 3) * 32], 128, true);
            if (elect()) {
                mbar_expect(bars + B_QRDY * 8, 28672);
                tma_ld2(sb + OFF_QT, &mp.qT, 80 * id, 0, bars + B_QRDY * 8);
                bulk_ld(sb + OFF_QT + 20480, g_qst, 8192, bars + B_QRDY * 8);
            }
            TS(lane == 0, 8)
        } else if (warp == 9) {
            const int v = min(lane / 5, 3);
            const uint2* gm = g_mod + (v + (v == 3)) * D_ + 5 * id + lane % 5;
            const unsigned epoch = lds32(sb + M_EP);
            uint2 r0, r1;
            unsigned it = 0;
            do {
                r0 = ld_mod(gm); r1 = ld_mod(gm + 6 * D_);
                SPIN_CHECK(55)
            } while (!__all_sync(~0u, r0.y == epoch && r1.y == epoch));
            const float m0 = __uint_as_float(r0.x), m1 = __uint_as_float(r1.x);
            const float m = rbf(m0 + m1), p = rbf(1.f + m);
            const float cz = zscale(__shfl_sync(~0u, p, 15 + lane % 5)), ga = __shfl_sync(~0u, m, 10 + lane % 5);
            if (lane < 15) sts32(sb + M_AB + lane % 5 * 16 + v * 4, lane < 10 ? __float_as_uint(cz * ga * (lane < 5 ? m : p)) : pack2(cz, cz));
            warp_arrive(bars + B_MODR * 8);
            TS(lane == 0, 6)
        }
        mbar_spin(bars + B_QRDY * 8, 0);
        uint4 rs[2], nm[2];
#pragma unroll
        for (int h = 0; h < 2; h++) { rs[h] = lds128(sb + OFF_QT + 20480 + h * 2048 + wt * 16); nm[h] = lds128(sb + OFF_QT + 24576 + h * 2048 + wt * 16); }
        mbar_spin(bars + B_MODR * 8, 0);
        TR4(threadIdx.x == 0, 72)
        uint32_t it = 0;
        while (RARE(__any_sync(~0u, (lop3<0x7E>(rs[0].x, ep, rs[0].z) | lop3<0x7E>(nm[0].x, ep, nm[0].z) | lop3<0x7E>(rs[1].x, ep, rs[1].z) | lop3<0x7E>(nm[1].x, ep, nm[1].z)) & 1))) {
#pragma unroll
            for (int h = 0; h < 2; h++) { rs[h] = ld_part(g_qst + 1024 * h + 8 * wt); nm[h] = ld_part(g_qst + S_ + 1024 * h + 8 * wt); }
            STALE(1)
            SPIN_CHECK(53)
        }
        TR4(threadIdx.x == 0, 73)
#pragma unroll 1
        for (int c = wg == 2 ? 0 : 3 + wg; c < (wg == 2 ? 3 : 4 + wg); c++) {
            uint4 q[2], p[2][4];
#pragma unroll
            for (int h = 0; h < 2; h++) q[h] = lds128(sb + OFF_QT + h * 10240 + (wt >> 1) * 160 + c * 32 + (wt & 1) * 16);
            const float4 ab = lds128f(sb + M_AB + c * 16);
            mbar_spin(bars + (B_RING + c) * 8, 0);
            TR4(wt == 0, wg == 2 ? 80 + 2 * c : 74)
#pragma unroll
            for (int i = 0; i < 8; i++) p[i >> 2][i & 3] = lds128(sb + OFF_RING + c * 16384 + (i & 3) * 4096 + (i >> 2) * 2048 + (wt ^ ((wt >> 1) & 4)) * 16);
            while (RARE(__any_sync(~0u, lop3<0x7E>(q[0].x, ep, q[1].x) & 1))) {
#pragma unroll
                for (int h = 0; h < 2; h++) q[h] = ld_part(g_qT + ((64 * h + (wt >> 1)) * D_ + 5 * id + c) * 16 + 8 * (wt & 1));
                STALE(2)
                SPIN_CHECK(52)
            }
            TR4(wt == 0, wg == 2 ? 81 + 2 * c : 75)
#pragma unroll
            for (int h = 0; h < 2; h++) {
                const uint32_t qq[4] = {q[h].x, q[h].y, q[h].z, q[h].w}, r4[4] = {rs[h].x, rs[h].y, rs[h].z, rs[h].w}, n4[4] = {nm[h].x, nm[h].y, nm[h].z, nm[h].w};
                const uint4 y = add2(add2(p[h][0], p[h][1]), add2(p[h][2], p[h][3]));
                const uint32_t yy[4] = {y.x, y.y, y.z, y.w};
                uint32_t o[4];
#pragma unroll
                for (int i = 0; i < 4; i++) {
                    const uint32_t n = fma2(qq[i], r4[i], n4[i]);
                    o[i] = fma2(pack2(fmaf(blo(n), ab.y, ab.x), fmaf(bhi(n), ab.y, ab.x)), yy[i], mul2(qq[i], __float_as_uint(ab.z)));
                }
                stg128_tag(g_x1T + (size_t)(5 * id + c) * S_ + 1024 * h + 8 * wt, o[0], o[1], o[2], o[3], ep, ((5 * id + c) >> 3) & 3);
            }
        }
        warp_arrive(bars + B_XS * 8);
        TS(tid == 0, 17)
        TS(tid == 256, 52)
    }

    const uint32_t nil = pp.nil;
    const int wq = warp & 3;
    if (wg == 2) {
        TIDS
        asm volatile("setmaxnreg.dec.sync.aligned.u32 32;");
        {
            const uint32_t ep = lds32(sb + M_EP);
            uint32_t ph = 0;
#pragma unroll 1
            for (int m = wq - 4; m < 60; m += 4) {
                const int n = max(m, 0);
                const int e = (n >= 20) + (n >= 40), i = n - 20 * e;
                const uint32_t M = e == 0 ? M0 : e == 1 ? M1 : M2;
                const int w = (M >> i) & 1, c = __popc(M & ((1u << i) - 1)), kb = w ? c : i - c;
                const uint32_t a = sb + OFF_XR + (n & 7) * 8192;
                uint32_t ta = a + (e == 0 ? lane * 128 + ((lane & 7) << 4) + (lane >> 3) * 4
                                 : e == 1 ? (lane & 15) * 128 + (((lane >> 4 << 1) ^ (lane & 7)) << 4) + (lane & 8) + (lane >> 4) * 4
                                          : lane * 32 + (lane >> 2) * 4);
                uint32_t tb = e == 0 ? ta ^ 32 : ta + 2048, tc = e == 2 ? ta + 1024 : ta ^ 64, td = e == 2 ? tb + 1024 : tb ^ 64;
                uint32_t live = m >= 0,
                    f0 = bars + (B_XFULL + 8 * w + ((10 * e + kb) & 7)) * 8;
                uint32_t f1 = m == GATE_W2 || m == GATE_W3 || m == GATE_W3B ? bars + (B_GATE + (m >= GATE_W3) + (m >= GATE_W3B)) * 8 : 0;
                if (lane) f0 = f1;
                if (lane > 1 || m < 0) f0 = 0;
                asm volatile("" : "+r"(ta), "+r"(tb), "+r"(tc), "+r"(td), "+r"(live), "+r"(f0));
                mbar_spin(bars + (m < 0 ? B_BK : B_LAND + (n & 7)) * 8, (n >> 3) & 1);
                TR5(lane == 0, n)
                while (true) {
                    uint32_t v[8];
#pragma unroll
                    for (int i = 0; i < 8; i++) v[i] = lds32(((i & 2) ? ((i & 1) ? td : tc) : (i & 1) ? tb : ta) + (i >> 2) * 4096);
                    const uint32_t bad = lop3<0xFE>(lop3<0x7E>(v[0], ep, v[1]), lop3<0x7E>(v[2], ep, v[3]), lop3<0x7E>(v[4], ep, v[5]));
                    if (!RARE(__any_sync(~0u, lop3<0xA8>(bad, lop3<0x7E>(v[6], ep, v[7]), live)))) break;
                    if (elect()) load_tile(mp, a, e, grp + 16 * w, kb, j, bars + (B_AGAIN + wq) * 8);
                    mbar_spin(bars + (B_AGAIN + wq) * 8, ph);
                    ph ^= 1;
                    STALE1(e)
                }
                TR5(lane == 0, 60 + n)
                if (f0) mbar_arrive(f0);
            }
        }
#pragma unroll 1
        for (int uw = 0; uw < 2; uw++) {
            const int tile = grp + 16 * uw;
            const uint32_t ep = lds32(sb + M_EP), in = sb + OFF_OUT + uw * 10240 + wt * 16, sr = in - lane * 16;
            mbar_wait(bars + (B_IN + uw) * 8, 1);
            float r[8] = {};
#pragma unroll 1
            for (int h = 0; h < 2; h++) {
                uint4 a = lds128(in + h * 4096), b = lds128(in + h * 4096 + 2048);
                uint32_t it = 0;
                while (RARE(__any_sync(~0u, ((a.x ^ ep) | (b.x ^ ep)) & 1))) {
                    const uint4* p = g_part + (size_t)tile * 40960 + ((j >> 2) + 4 * h) * 5120 + 4096 + j * 128 + wt;
                    a = ld_part(p); b = ld_part(p + 10240);
                    STALE(3)
                    if (++it > SPIN_LIMIT) SPIN_FAIL(58)
                }
                add8(r, add2(a, b));
            }
            base16(r, lds128(in + 8192), lds64f(sb + M_GB + (64 + 2 * t) * 4), lds64f(sb + M_GB + (72 + 2 * t) * 4));
            __syncwarp();
            stsm4(sr + (lane & 15) * 32 + (((lane >> 4) ^ ((lane >> 2) & 1)) << 4), pack2(r[0], r[1]), pack2(r[2], r[3]), pack2(r[4], r[5]), pack2(r[6], r[7]));
            __syncwarp();
            stg128(out + (size_t)(64 * tile + 16 * wq + (lane >> 1)) * D_ + 512 + 16 * j + 8 * (lane & 1), lds128(sr + (lane >> 1) * 32 + (((lane & 1) ^ ((lane >> 3) & 1)) << 4)));
            __syncwarp();
        }
        if (wq == 0) {
            uint32_t it = 0;
            while (!mbar_try(bars + B_OWN * 8, 0)) { if (++it > SPIN_LIMIT) SPIN_FAIL(56) }
        }
        return;
    }

    TIDS
    const int uw = wg, tile = grp + 16 * uw, row0 = 64 * tile + 16 * wq;
    const bool leader = wt == 0; (void)leader;
    const uint32_t xfull = bars + (B_XFULL + 8 * uw) * 8, xempty = bars + B_XEMPTY * 8, wfull = bars + B_WFULL * 8, wempty = bars + B_WEMPTY * 8;
    const uint64_t dz = mkdesc(0) + pp.nil;
    auto xwait = [&](uint32_t n) { mbar_spin(xfull + (n & 7) * 8, (n >> 3) & 1); };
    asm volatile("setmaxnreg.inc.sync.aligned.u32 224;");
    const uint32_t ep = lds32(sb + M_EP);
    uint32_t res[20] = {};
    {
        float acc[40];
        const uint32_t la = ((lane & 7) + 8 * (lane >> 4)) * 128 + (((2 * wq + ((lane >> 3) & 1)) ^ (lane & 7)) << 4);
        auto pos = [&](int n) { return ring_pos(uw, n, LEAD1) & 7; };
        auto slot = [&](int n) { return sb + OFF_XR + pos(n) * 8192; };
        float al[2], r1[2], n1[2];
        {
            float sl[4], sq[4], v[4];
            uint32_t z0[16], z1[16], zz[16];
            uint64_t bd = dz + b80_desc(dsb, 0, 0, 0), tb = (((uint64_t)8 << 32) | ((dsb + OFF_TAB) >> 4) | (7u << 16)) + pp.nil;
            auto ldfrag = [&](uint32_t (&z)[16], int n) {
#pragma unroll
                for (int q = 0; q < 4; q++) ldsm4t(slot(n) + la + q * 2048, z[4 * q], z[4 * q + 1], z[4 * q + 2], z[4 * q + 3]);
            };
            auto tile1 = [&](const uint32_t (&zc)[16], uint32_t (&zn)[16], int n, int h) {
                const bool last = h && n == 5, ok = mbar_test(xfull + (n + 1) * 8, 0), okw = !h || mbar_test(wfull + ((n + 1) >> 1) * 8, 0);
                const int kb = g1_block(n, j);
                wg_fence();
#pragma unroll
                for (int q = 0; q < 2; q++) wgmma_rs80(acc, zc[4 * q], zc[4 * q + 1], zc[4 * q + 2], zc[4 * q + 3], bd + q * B80_STEP, 1);
                wg_commit();
                wg_wait<1>();
                if (!ok) xwait(n + 1);
                if (!last) ldfrag(zn, n + 1);
#pragma unroll
                for (int e = 0; e < 16; e++) zz[e] = mul2(zc[e], zc[e]);
                const uint64_t t0 = last ? ((uint64_t)8 << 32) | ((dsb + M_NUL) >> 4) : tb;
                const uint32_t ts = last ? 0 : 14;
                wg_fence();
#pragma unroll
                for (int q = 0; q < 4; q++) wgmma_rs8(sl, zc[4 * q], zc[4 * q + 1], zc[4 * q + 2], zc[4 * q + 3], t0 + q * ts, 1);
#pragma unroll
                for (int q = 0; q < 4; q++) wgmma_rs8(sq, zz[4 * q], zz[4 * q + 1], zz[4 * q + 2], zz[4 * q + 3], t0 + q * ts, 1);
#pragma unroll
                for (int q = 2; q < 4; q++) wgmma_rs80(acc, zc[4 * q], zc[4 * q + 1], zc[4 * q + 2], zc[4 * q + 3], bd + q * B80_STEP, 1);
                wg_commit();
#pragma unroll
                for (int q = 0; q < 4; q++) ldsm4t_if(kb == j, slot(n) + la + q * 2048, &res[4 * q]);
                if (!h) ldsm4t_if(kb == 8 + (j >> 2), slot(n) + la + (j & 3) * 2048, &res[16]);
                if (lane < 2) mbar_arrive_after(xempty + pos(n) * 8, res[12], res[16], nil);
                if (!h && n && lane == 0) mbar_arrive(wempty + ((n >> 1) - 1) * 8);
                tb += 56;
                bd = bd + (uint64_t)B80_HALF;
                if (!okw) mbar_spin(wfull + ((n + 1) >> 1) * 8, 0);
                TR(leader, 100 + 10 * uw + n)
            };
            zero(acc); zero(sl); zero(sq);
            mbar_spin(bars + B_TAB * 8, 0);
            mbar_spin(wfull, 0);
            xwait(0);
            TS(leader, 32 + uw)
            ldfrag(z0, 0);
#pragma unroll 1
            for (int n = 0; n < 6; n += 2) { tile1(z0, z1, n, 0); tile1(z1, z0, n + 1, 1); }
#pragma unroll
            for (int n = 6; n < 10; n++) {
                const uint64_t ad = dz + (((dsb + OFF_XR + pos(n) * 8192) >> 4) | 0x10000u);
                const bool ok = n == 9 || mbar_test(xfull + ((n + 1) & 7) * 8, (n + 1) >> 3), okw = n != 7 || mbar_test(wfull + 4 * 8, 0);
                wg_fence();
#pragma unroll
                for (int q = 0; q < 4; q++) wgmma_ss80t(acc, ad + q * 128, bd + q * B80_STEP, 1);
                wg_commit();
                bd = bd + (uint64_t)B80_HALF;
                if (n == 9) ldsm4t_if(9 - (j & 1) == 8 + (j >> 2), slot(9) + la + (j & 3) * 2048, &res[16]);
                wg_wait<1>();
                if (n > 6 && lane < 2) mbar_arrive(xempty + pos(n - 1) * 8);
                if (!(n & 1) && lane == 0) mbar_arrive(wempty + ((n >> 1) - 1) * 8);
                if (n == 6) {
                    reg_fence(sl); reg_fence(sq);
#pragma unroll
                    for (int e = 0; e < 2; e++) {
                        v[2 * e] = t == 0 ? sl[2 * e] + sl[2 * e + 1] : t == 1 ? sq[2 * e] + sq[2 * e + 1] : sl[2 * e];
                        v[2 * e + 1] = t == 2 ? sl[2 * e + 1] : sq[2 * e];
                    }
                    st_peer(peer_addr(sb + OFF_ROW + uw * 2048 + wt * 16), __float_as_uint(v[0]), __float_as_uint(v[1]), __float_as_uint(v[2]), __float_as_uint(v[3]), peer_addr(bars + (B_SUMS + uw) * 8));
                    TS(leader && !uw, 59)
                }
                if (!ok) xwait(n + 1);
                if (!okw) mbar_spin(wfull + 4 * 8, 0);
                TR(leader, 100 + 10 * uw + n)
            }
            float4 k = lds128f(sb + M_KS);
            float k4 = __uint_as_float(lds32(sb + M_KS + 16));
#pragma unroll
            for (int w = 1; w < 5; w++) {
                const float4 o = lds128f(sb + M_KS + w * 32);
                k.x += o.x; k.y += o.y; k.z += o.z; k.w += o.w; k4 += __uint_as_float(lds32(sb + M_KS + w * 32 + 16));
            }
            mbar_spin(bars + (B_SUMS + uw) * 8, 0);
            TS(leader && !uw, 10)
            const float4 o = lds128f(sb + OFF_ROW + uw * 2048 + wt * 16);
            v[0] += o.x; v[1] += o.y; v[2] += o.z; v[3] += o.w;
            uint32_t fa[4];
#pragma unroll
            for (int h = 0; h < 2; h++) {
                const int l0 = lane & ~3;
                const float s1 = __shfl_sync(~0u, v[2 * h], l0), s2 = __shfl_sync(~0u, v[2 * h], l0 + 1), scc = __shfl_sync(~0u, v[2 * h], l0 + 2);
                const float scs = __shfl_sync(~0u, v[2 * h + 1], l0 + 2), sc = __shfl_sync(~0u, v[2 * h], l0 + 3), sqq = __shfl_sync(~0u, v[2 * h + 1], l0 + 3);
                const float m1 = s1 * (1.f / D_), va = fmaxf(s2 * (1.f / D_) - m1 * m1, 0.f) + 1e-5f, r = rsqrtf(va);
                const float m2 = (r * (sc - m1 * k.x) + k.y) * (1.f / D_);
                const float e2 = (r * (r * (sqq + m1 * (m1 * k.z - 2.f * scc)) + 2.f * (scs - m1 * k.w)) + k4) * (1.f / D_);
                al[h] = r * 0.5f * rsqrtf(fmaxf(e2 - m2 * m2, 0.f) + 1e-5f); r1[h] = r; n1[h] = -m1 * r;
                const uint32_t fb = split2(va * r), fx = split2(t == 3 ? -m2 * va * r : -m1), fc = __shfl_sync(~0u, fx, lane | 3);
                fa[h] = __byte_perm(fx, fb, t == 1 ? 0x5432 : t == 2 ? 0x7654 : 0x1010);
                fa[2 + h] = t ? 0 : fc >> 16;
            }
            mbar_spin(bars + B_VEC * 8, 0);
            wg_fence();
            wgmma_rs80k(acc, fa[0], fa[1], fa[2], fa[3], ((uint64_t)8 << 32) | ((dsb + OFF_F1) >> 4) | (((M_F1 - OFF_F1) >> 4) << 16), 1);
            wg_commit();
        }
        wg_wait<0>();
        reg_fence(acc);
        if (lane < 2) mbar_arrive_after(xempty + pos(9) * 8, res[16], 0, nil);
        if (lane == 0) mbar_arrive(wempty + 4 * 8);
        TS(leader, 34 + uw)
        {
            bf16* const trow = g_t + (size_t)(row0 + g + 2) * D_;
#pragma unroll
            for (int b = 0; b < 3; b++) {
                uint32_t p[8];
#pragma unroll
                for (int ii = 0; ii < 4; ii++) {
                    const int i = 4 * b + ii;
                    if (i >= 10) continue;
#pragma unroll
                    for (int h = 0; h < 2; h++) p[(i & 3) + 4 * h] = pack2(gelu2(acc[4 * i + 2 * h] * al[h]), gelu2(acc[4 * i + 2 * h + 1] * al[h]));
                }
                if (b < 2) {
                    const int gr = (2 * j + b) / 5, sh = (gr & 1) ? -1 - (gr >> 1) : 1 + (gr >> 1);
                    bf16* dst = trow + 64 * j + 32 * b + 8 * t;
                    const int w = (((g + sh) >> 2) & 2) + (t >> 1);
                    stg128_tag(dst + sh * D_, p[0], p[1], p[2], p[3], ep, w);
                    stg128_tag(dst + (sh + 8) * D_, p[4], p[5], p[6], p[7], ep, w ^ 2);
                    if (row0 + g < sh || row0 + g + 8 >= S_ + sh) stg128_tag(dst + (sh > 0 ? 0 : 8) * D_, 0, 0, 0, 0, ep, (sh > 0 ? 0 : 2) + (t >> 1));
                } else {
                    bf16* dst = trow + 512 + 16 * j + 4 * t;
                    const uint32_t lo = t == (g < 2), hi = t == (g >= 2), o = j & 1;
                    stg64(dst - 2 * D_, lop3<0xB8>(p[0], lo & ~o, ep), lop3<0xB8>(p[1], lo & o, ep));
                    stg64(dst + 6 * D_, lop3<0xB8>(p[4], hi & ~o, ep), lop3<0xB8>(p[5], hi & o, ep));
                    if (row0 + g + 8 >= S_ - 2) stg64(dst + 8 * D_, ep & (t == 1) & ~o, ep & (t == 1) & o);
                }
            }
        }
        signal_cnt(&g_cnt.g1[tile * 32], lane, 1, true);
        TS(leader, 36 + uw)
#pragma unroll
        for (int i = 0; i < 10; i++) {
            const float2 c = lds64f(sb + M_C + (8 * i + 2 * t) * 4), s = lds64f(sb + M_SB + (8 * i + 2 * t) * 4);
#pragma unroll
            for (int h = 0; h < 2; h++) {
                acc[4 * i + 2 * h] = fmaf(blo(res[2 * i + h]), r1[h], fmaf(n1[h], c.x, s.x));
                acc[4 * i + 2 * h + 1] = fmaf(bhi(res[2 * i + h]), r1[h], fmaf(n1[h], c.y, s.y));
            }
        }
        mbar_spin(wfull + 5 * 8, 0);
        xwait(10);
        TS(leader, 22 + uw)
        uint32_t xo = (4 + 2 * uw) * 8, xp = 0;
        uint64_t ad = dz + (((dsb + OFF_XR) >> 4) | 0x10000u) + xo * 64, bd = dz + b80_desc(dsb, 5, 0, 0);
#pragma unroll 1
        for (int i = 0; i < 5; i++) {
            const uint32_t x1 = xfull + ((3 + 2 * i) & 7) * 8, p1 = i < 3, x2 = xfull + (min(4 + 2 * i, 11) & 7) * 8, p2 = i < 2;
            const uint32_t w2 = wfull + (min(6 + i, 9) & 7) * 8, pw = i >= 2;
            const bool ok1 = mbar_test(x1, p1);
            wg_fence();
#pragma unroll
            for (int q = 0; q < 4; q++) wgmma_ss80(acc, ad + q * 2, bd + q * B80_STEP, 1);
            wg_commit();
            wg_wait<1>();
            if (lane < 2 && i) mbar_arrive(xempty + xp);
            if (lane == 0 && i) mbar_arrive(wempty + ((4 + i) & 7) * 8);
            if (!ok1) mbar_spin(x1, p1);
            const bool ok2 = mbar_test(x2, p2), okw = mbar_test(w2, pw);
            wg_fence();
#pragma unroll
            for (int q = 0; q < 4; q++) wgmma_ss80(acc, ad + 512 + q * 2, bd + B80_HALF + q * B80_STEP, 1);
            wg_commit();
            const uint32_t xc = xo;
            xp = xo + 8; xo = (xo + 16) & 56;
            ad += xo ? 1024 : 1024 - 4096;
            bd += i == 2 ? 2 * B80_HALF - 8192 + (8192ll << 16) : 2 * B80_HALF;
            asm volatile("" : "+l"(ad), "+l"(bd));
            wg_wait<1>();
            if (lane < 2) mbar_arrive(xempty + xc);
            if (!ok2) mbar_spin(x2, p2);
            if (!okw) mbar_spin(w2, pw);
            TR(leader, (uw ? 86 : 20) + 2 * i)
        }
        wg_wait<0>();
        reg_fence(acc);
        if (lane < 2) mbar_arrive(xempty + xp);
        if (lane == 0) mbar_arrive(wempty + (9 & 7) * 8);
        TS(leader, 38 + uw)
        float a0 = 0.f, b0 = 0.f, a1 = 0.f, b1 = 0.f;
        uint32_t x2[20];
#pragma unroll
        for (int i = 0; i < 5; i++) {
            uint32_t* p = &x2[4 * i];
#pragma unroll
            for (int e = 0; e < 4; e++) p[e] = pack2(acc[8 * i + 2 * e], acc[8 * i + 2 * e + 1]);
#pragma unroll
            for (int e = 0; e < 4; e++) p[e] = lop3<0xB8>(p[e], (((wt >> 3) ^ (wt << 2)) & 7) == e, ep);
            stg128(&g_x2f[(tile * 40 + (i < 4 ? 4 * j + i : 32 + j)) * 128 + wt], p[0], p[1], p[2], p[3]);
#pragma unroll
            for (int e = 0; e < 8; e += 4) {
                const float* u = &acc[8 * i + e];
                a0 += u[0] + u[1]; b0 = fmaf(u[0], u[0], fmaf(u[1], u[1], b0));
                a1 += u[2] + u[3]; b1 = fmaf(u[2], u[2], fmaf(u[3], u[3], b1));
            }
        }
#pragma unroll
        for (int o = 1; o < 4; o *= 2) {
            a0 += __shfl_xor_sync(~0u, a0, o); b0 += __shfl_xor_sync(~0u, b0, o);
            a1 += __shfl_xor_sync(~0u, a1, o); b1 += __shfl_xor_sync(~0u, b1, o);
        }
        if (t < 2) stg64(&g_stats[(tile * 8 + j) * 64 + 16 * wq + g + 8 * t], tag(__float_as_uint(t ? a1 : a0), ep), __float_as_uint(t ? b1 : b0));
        signal_cnt(&g_cnt.g2[tile * 32], lane, 1, true);
        TS(leader, 40 + uw)
#pragma unroll
        for (int i = 0; i < 10; i++) {
            const float2 c = lds64f(sb + M_GB + (8 * i + 2 * t) * 4), e = lds64f(sb + M_CI + (8 * i + 2 * t) * 4);
#pragma unroll
            for (int h = 0; h < 2; h++)
                res[2 * i + h] = fma2(pack2(c.x, c.y), x2[2 * i + h], pack2(e.x * blo(res[2 * i + h]), e.y * bhi(res[2 * i + h])));
        }
#pragma unroll
        for (int i = 0; i < 20; i++) asm volatile("" : "+r"(res[i]));
    }
    float acc0[64], acc1[44];
    float2 q[4];
    {
        uint4 f0, f1, f2, f3;
        auto xseq = [&](int kb) { return ring_pos(uw, kb, XLEAD) & 7; };
        auto step = [&](const uint4& f, uint64_t bd) {
            wg_fence();
            wgmma_rs128(acc0, f.x, f.y, f.z, f.w, bd, 1);
            wgmma_rs88(acc1, f.x, f.y, f.z, f.w, bd + 512, 1);
            wg_commit();
        };
        const uint32_t xa = sb + OFF_XR + wt * 16;
        const float2* const gs = &g_stats[(tile * 8 + 2 * t) * 64 + 16 * wq + g];
        zero(acc0); zero(acc1);
        uint32_t xs = xseq(0);
        xwait(20);
        TS(leader, 42 + uw)
        f0 = lds128(xa + xs * 8192); f1 = lds128(xa + xs * 8192 + 2048);
#pragma unroll
        for (int i = 0; i < 4; i++) q[i] = ld_stat(gs + (i & 1) * 64 + 8 * (i >> 1));
        mbar_spin(wfull + (10 & 7) * 8, (10 >> 3) & 1);
#pragma unroll 1
        for (int kb = 0; kb < 10; kb++) {
            const uint32_t wn = 10 + 2 * kb;
            const uint64_t bd = dz + (((dsb + OFF_W + (wn & 7) * 16384) >> 4) | (256u << 16));
            step(f0, bd);
            wg_wait<1>();
            if (kb && lane == 0) mbar_arrive(wempty + ((wn - 1) & 7) * 8);
            f2 = lds128(xa + xs * 8192 + 4096); f3 = lds128(xa + xs * 8192 + 6144);
            const bool w1 = mbar_test(wfull + ((wn + 1) & 7) * 8, (wn >> 3) & 1), x1 = mbar_test(xfull + ((21 + kb) & 7) * 8, ((21 + kb) >> 3) & 1);
            step(f1, bd + 128);
            if (!w1) mbar_spin(wfull + ((wn + 1) & 7) * 8, (wn >> 3) & 1);
            step(f2, bd + 1024);
            if (lane < 2) mbar_arrive_after(xempty + xs * 8, f2.x, f3.x, nil);
            wg_wait<1>();
            if (lane == 0) mbar_arrive(wempty + (wn & 7) * 8);
            xs = xseq(kb + 1);
            if (x1) { f0 = lds128(xa + xs * 8192); f1 = lds128(xa + xs * 8192 + 2048); }
            const bool w2 = mbar_test(wfull + ((wn + 2) & 7) * 8, ((wn + 2) >> 3) & 1);
            step(f3, bd + 1152);
            if (kb < 9 && !x1) { xwait(21 + kb); f0 = lds128(xa + xs * 8192); f1 = lds128(xa + xs * 8192 + 2048); }
            if (!w2) mbar_spin(wfull + ((wn + 2) & 7) * 8, ((wn + 2) >> 3) & 1);
            if (kb == 4) {
                uint32_t it = 0;
                while (RARE(__any_sync(~0u, ((__float_as_uint(q[0].x) ^ ep) | (__float_as_uint(q[1].x) ^ ep) | (__float_as_uint(q[2].x) ^ ep) | (__float_as_uint(q[3].x) ^ ep)) & 1))) {
#pragma unroll
                    for (int i = 0; i < 4; i++) q[i] = ld_stat(gs + (i & 1) * 64 + 8 * (i >> 1));
                    SPIN_CHECK(49)
                }
                float a0 = q[0].x + q[1].x, b0 = q[0].y + q[1].y, a1 = q[2].x + q[3].x, b1 = q[2].y + q[3].y;
#pragma unroll
                for (int o = 1; o < 4; o *= 2) {
                    a0 += __shfl_xor_sync(~0u, a0, o); b0 += __shfl_xor_sync(~0u, b0, o);
                    a1 += __shfl_xor_sync(~0u, a1, o); b1 += __shfl_xor_sync(~0u, b1, o);
                }
                a0 *= 1.f / D_; a1 *= 1.f / D_;
                const float r0 = 0.5f * rsqrtf(fmaxf(b0 * (1.f / D_) - a0 * a0, 0.f) + 1e-5f), r1 = 0.5f * rsqrtf(fmaxf(b1 * (1.f / D_) - a1 * a1, 0.f) + 1e-5f);
                const uint32_t sel = t == 0 ? 0x1010 : t == 1 ? 0x4432 : 0x4444;
                q[0] = make_float2(r0, r1);
                q[1] = make_float2(__uint_as_float(__byte_perm(split2(-a0), 0, sel)), __uint_as_float(__byte_perm(split2(-a1), 0, sel)));
            }
            if (kb == 6) {
#pragma unroll
                for (int i = 0; i < 5; i++) stg128(&g_x1f[(tile * 8 + j) * 640 + i * 128 + wt], res[4 * i], res[4 * i + 1], res[4 * i + 2], res[4 * i + 3]);
            }
            if (kb == 8) asm volatile("fence.proxy.async.global;" ::: "memory");
            TR(leader, 10 * uw + kb)
        }
        const uint64_t fd = ((uint64_t)8 << 32) | ((dsb + OFF_W + 6 * 16384) >> 4);
        wg_fence();
        wgmma_rs128k(acc0, __float_as_uint(q[1].x), __float_as_uint(q[1].y), 0, 0, fd, 1);
        wgmma_rs88k(acc1, __float_as_uint(q[1].x), __float_as_uint(q[1].y), 0, 0, fd + 128, 1);
        wg_commit();
        if (lane == 0) {
            mbar_arrive(bars + B_XFREE * 8);
            asm volatile("mbarrier.arrive.shared::cluster.b64 _, [%0];" ::"r"(peer_addr(bars + B_XFREE * 8)) : "memory");
        }
    }
    const uint32_t recv = sb + recv_off(uw) + wt * 16;
    uint32_t ha[48] = {}, hb[48], hx[12];
    uint64_t wb = dz + (((dsb + OFF_W) >> 4) | (512u << 16));
    auto wdesc = [&](int n) { return wb + (n & 7) * 1024; };
    auto wwait = [&](int n) { mbar_spin(wfull + (n & 7) * 8, (n >> 3) & 1); };
    auto wfree = [&](int n) { if (lane == 0) mbar_arrive(wempty + (n & 7) * 8); };
    auto fresh = [&]() { wb += pp.nil; asm volatile("" : "+l"(wb)); };
    uint32_t pk[32];
    {
        float P0[64];
        const float r0 = q[0].x, r1 = q[0].y;
        const uint32_t ra = peer_addr(recv), rb = peer_addr(bars + (B_RECV + 4 * uw) * 8);
        auto conv32 = [&](const float* v, int b) {
#pragma unroll
            for (int i = 0; i < 4; i++) {
                ha[8 * b + 2 * i] = pack2(gelu2(v[4 * i] * r0), gelu2(v[4 * i + 1] * r0));
                ha[8 * b + 2 * i + 1] = pack2(gelu2(v[4 * i + 2] * r1), gelu2(v[4 * i + 3] * r1));
            }
#pragma unroll
            for (int s = 2 * b; s < 2 * b + 2; s++) st_peer(ra + s * 2048, ha[4 * s], ha[4 * s + 1], ha[4 * s + 2], ha[4 * s + 3], rb + (b >> 1) * 8);
        };
        auto fetch = [&](int k) {
            mbar_spin(bars + (B_RECV + 4 * uw + k) * 8, 0);
#pragma unroll
            for (int s = 4 * k; s < 4 * k + 4; s++) { const uint4 x = lds128(recv + s * 2048); hb[4 * s] = x.x; hb[4 * s + 1] = x.y; hb[4 * s + 2] = x.z; hb[4 * s + 3] = x.w; }
        };
        auto stage = [&](int n, const uint32_t* a, int steps, int sc) {
            wwait(n);
            wg_fence();
#pragma unroll
            for (int s = 0; s < steps; s++) wgmma_rs128(P0, a[4 * s], a[4 * s + 1], a[4 * s + 2], a[4 * s + 3], wdesc(n) + s * 128, sc || s);
            wg_commit();
        };
        wg_wait<0>();
        reg_fence(acc0); reg_fence(acc1);
        wfree(29); wfree(30);
        TS(leader, 44 + uw)
        uint32_t hr[6];
#pragma unroll
        for (int i = 0; i < 6; i++) {
            const float r = (i & 1) ? r1 : r0;
            hr[i] = pack2(gelu2(acc1[32 + 2 * i] * r), gelu2(acc1[33 + 2 * i] * r));
        }
        if (uw) mbar_spin(bars + B_XFREE * 8, 0);
        st_peer(ra + 24576, hr[0], hr[1], hr[2], hr[3], rb + 24);
        asm volatile("st.async.shared::cluster.mbarrier::complete_tx::bytes.v2.b32 [%0], {%1, %2}, [%3];" ::"r"(ra + 26624 - wt * 8), "r"(hr[4]), "r"(hr[5]), "r"(rb + 24) : "memory");
        conv32(&acc1[0], 4);
        conv32(&acc1[16], 5);
        TS(leader, 46 + uw)
        stage(31, &ha[32], 4, 0);
#pragma unroll
        for (int b = 0; b < 4; b++) {
            conv32(&acc0[16 * b], b);
            if (b == 3) {
                fetch(2);
                mbar_spin(bars + (B_RECV + 4 * uw + 3) * 8, 0);
                const uint4 x = lds128(recv + 24576);
                const uint2 y = lds64(recv + 26624 - wt * 8);
                const uint32_t hp[6] = {x.x, x.y, x.z, x.w, y.x, y.y};
#pragma unroll
                for (int i = 0; i < 6; i++) { hx[i] = (j & 1) ? hp[i] : hr[i]; hx[6 + i] = (j & 1) ? hr[i] : hp[i]; }
            }
            if (!(b & 1)) wwait(32 + (b >> 1));
            wg_fence();
#pragma unroll
            for (int s = 0; s < 2; s++) wgmma_rs128(P0, ha[8 * b + 4 * s], ha[8 * b + 4 * s + 1], ha[8 * b + 4 * s + 2], ha[8 * b + 4 * s + 3], wdesc(32 + (b >> 1)) + (2 * (b & 1) + s) * 128, 1);
            wg_commit();
            if (!(b & 1)) { wg_wait<1>(); wfree(31 + (b >> 1)); }
        }
        TR(leader, 64 + 10 * uw)
        fresh();
        stage(34, &hb[32], 4, 1); wg_wait<1>(); wfree(33);
        fetch(0);
        stage(35, hx, 3, 1); wg_wait<1>(); wfree(34);
        fetch(1);
        stage(36, &hb[0], 4, 1); wg_wait<1>(); wfree(35);
        stage(37, &hb[16], 4, 1); wg_wait<1>(); wfree(36);
        wg_wait<0>();
        reg_fence(P0);
        pack_part<64>(pk, P0, ep);
        uint32_t all = 0;
#pragma unroll
        for (int i = 0; i < 32; i++) all |= pk[i];
        if (lane == 0) mbar_arrive_after(wempty + (37 & 7) * 8, all, 0, nil);
        TR(leader, 65 + 10 * uw)
    }
    {
        uint4* const dst = g_part + (size_t)(tile * 8 + j) * 5120 + wt;
        const uint4* const src = g_part + (size_t)tile * 40960 + j * 512 + wt;
        float F[2][32];
        float2 gb[8];
        uint4 base[4], u1[4], u2[4], u3[4];
#pragma unroll
        for (int c = 2; c < 5; c++) {
            float (&P)[32] = F[c & 1];
            fresh();
#pragma unroll
            for (int s = 0; s < 27; s++) {
                const int e = s < 8 ? 0 : s < 15 ? 1 : s < 23 ? 2 : 3, o = s - (e == 0 ? 0 : e == 1 ? 8 : e == 2 ? 15 : 23), n = 30 + 4 * c + e;
                const uint32_t* a = s < 12 ? &ha[4 * s] : s < 15 ? &hx[4 * (s - 12)] : &hb[4 * (s - 15)];
                if (o == 0) wwait(n);
                if (o == 0 || s == 1) wg_fence();
                wgmma_rs64(P, a[0], a[1], a[2], a[3], wdesc(n) + o * 128, s);
                if (o == 0) { wg_commit(); wg_wait<1>(); if (c > 2 || s) wfree(n - 1); }
                if (s == 0 && c > 2) { reg_fence(F[~c & 1]); pack_part<32>(pk, F[~c & 1], ep); }
                if (c == 2 && s % 3 == 0 && s < 24) st_part(dst + g4_block(s / 12, j) * 512 + (s / 3 & 3) * 128, &pk[4 * (s / 3)]);
                if (c == 3 && s % 4 == 1 && s < 16) st_part(dst + g4_block(2, j) * 512 + s / 4 * 128, &pk[4 * (s / 4)]);
                if (c == 4 && s % ST3 == 0 && s < 4 * ST3) st_part(dst + g4_block(3, j) * 512 + s / ST3 * 128, &pk[4 * (s / ST3)]);
                if (c == 4 && s >= 4 && s < 8) base[s - 4] = ldcg128(&g_x1f[(tile * 8 + j) * 640 + (s - 4) * 128 + wt]);
                if (c == 4 && s >= 19 && s < 23) { gb[2 * s - 38] = lds64f(sb + M_GB + (16 * (s - 19) + 2 * t) * 4); gb[2 * s - 37] = lds64f(sb + M_GB + (16 * (s - 19) + 8 + 2 * t) * 4); }
                if (c == 4 && s >= 8 && s < 12) u1[s - 8] = ld_part(src + (j ^ 6) * 5120 + (s - 8) * 128);
                if (c == 4 && s >= 15 && s < 19) u2[s - 15] = ld_part(src + (j ^ 4) * 5120 + (s - 15) * 128);
                if (c == 4 && s >= LD3 && s < LD3 + 4) u3[s - LD3] = ld_part(src + (j ^ 2) * 5120 + (s - LD3) * 128);
                if (s == 7 || s == 14 || s == 22 || s == 26) wg_commit();
                if (c == 4) { TR(leader && s == 7, 68 + 10 * uw) TR(leader && s == 14, 69 + 10 * uw) TR(leader && s == 22, 70 + 10 * uw) }
            }
            if (c == 2 && lane == 0) mbar_arrive(bars + (B_RING + uw) * 8);
            TR(leader, 64 + c + (c == 4 ? 3 : 0) + 10 * uw)
        }
        float (&O)[32] = F[0];
        float v[32];
        uint32_t it = 0;
        while (__any_sync(~0u, (stale4(u1, ep) | stale4(u2, ep) | stale4(u3, ep)) & 1)) {
            ld_part4(u1, src + (j ^ 6) * 5120, 128); ld_part4(u2, src + (j ^ 4) * 5120, 128); ld_part4(u3, src + (j ^ 2) * 5120, 128);
            STALE(6)
            SPIN_CHECK(58)
        }
        TR(leader, 73 + 10 * uw)
#pragma unroll
        for (int i = 0; i < 4; i++) { unpack8(&v[8 * i], add2(add2(u1[i], u2[i]), u3[i])); base16(&v[8 * i], base[i], gb[2 * i], gb[2 * i + 1]); }
        reg_fence(v);
        TS(leader, 50 + uw)
        wg_wait<0>();
        reg_fence(O);
        TS(leader, 48 + uw)
        const uint32_t so = sb + recv_off(uw) + wq * 2048;
#pragma unroll
        for (int i = 0; i < 4; i++) {
            float* o = &O[8 * i];
#pragma unroll
            for (int e = 0; e < 8; e++) o[e] = fmaf((e & 1) ? gb[2 * i + (e >> 2)].y : gb[2 * i + (e >> 2)].x, o[e], v[8 * i + e]);
            stsm4(so + (lane & 15) * 128 + (((2 * i + (lane >> 4)) ^ (lane & 7)) << 4), pack2(o[0], o[1]), pack2(o[2], o[3]), pack2(o[4], o[5]), pack2(o[6], o[7]));
        }
        __syncwarp();
#pragma unroll
        for (int i = 0; i < 4; i++) {
            const int row = (lane >> 3) + 4 * i;
            stg128(out + (size_t)(row0 + row) * D_ + 64 * j + 8 * (lane & 7), lds128(so + row * 128 + (((lane & 7) ^ (row & 7)) << 4)));
        }
        warp_arrive(bars + B_OWN * 8);
    }
}

typedef CUresult (*EncFn)(CUtensorMap*, CUtensorMapDataType, cuuint32_t, void*, const cuuint64_t*, const cuuint64_t*, const cuuint32_t*,
                          const cuuint32_t*, CUtensorMapInterleave, CUtensorMapSwizzle, CUtensorMapL2promotion, CUtensorMapFloatOOBfill);

static void enc(EncFn fn, CUtensorMap* m, void* p, int rank, const cuuint64_t* dims, const cuuint64_t* strides, const cuuint32_t* box, bool plain = false) {
    const CUtensorMapSwizzle sw = box[0] > 64 || plain ? CU_TENSOR_MAP_SWIZZLE_NONE : CU_TENSOR_MAP_SWIZZLE_128B;
    cuuint32_t es[5] = {1, 1, 1, 1, 1};
    CUresult r = fn(m, CU_TENSOR_MAP_DATA_TYPE_BFLOAT16, rank, p, dims, strides, box, es, CU_TENSOR_MAP_INTERLEAVE_NONE, sw,
                    CU_TENSOR_MAP_L2_PROMOTION_L2_128B, CU_TENSOR_MAP_FLOAT_OOB_FILL_NONE);
    (void)r;
}
static void enc2(EncFn fn, CUtensorMap* m, void* p, uint64_t cols, uint64_t rows, uint32_t bc, uint32_t br, bool plain = false) {
    cuuint64_t dims[2] = {cols, rows}, st[1] = {cols * 2};
    cuuint32_t box[2] = {bc, br};
    enc(fn, m, p, 2, dims, st, box, plain);
}

extern "C" void kernel_launch(void* const* d_in, const int* in_sizes, int n_in, void* d_out, int out_size) {
    static Maps mp;
    static Ptrs pp;
    static void* cached[13];
    bool same = true;
    for (int i = 0; i < 13; i++) same = same && (cached[i] == d_in[i]);
    if (!same) {
        void* fnp = nullptr;
        cudaDriverEntryPointQueryResult qr;
        cudaGetDriverEntryPoint("cuTensorMapEncodeTiled", &fnp, cudaEnableDefault, &qr);
        EncFn fn = (EncFn)fnp;
        cudaGetSymbolAddress((void**)&pp.s, g_scratch);
        void *x1T = g_x1T, *t = g_t;
        cuuint64_t dq[3] = {64, S_, 10}, sq[2] = {D_ * 2, 128};
        cuuint32_t bq[3] = {64, 16, 10};
        enc(fn, &mp.q, d_in[0], 3, dq, sq, bq);
        enc2(fn, &mp.k, d_in[1], D_, S_, 80, 67); enc2(fn, &mp.v, d_in[2], D_, S_, 80, 64);
        enc2(fn, &mp.qT, g_qT, 16 * D_, 128, 80, 128);
        enc2(fn, &mp.x[0], x1T, S_, D_, 64, 64); enc2(fn, &mp.x[1], (bf16*)t + 2 * D_, D_, S_, 64, 64);
        enc2(fn, &mp.x[2], g_x2f, 64, 320 * 64, 64, 64, true);
        enc2(fn, &mp.w1, d_in[7], D_, D_, 64, 64); enc2(fn, &mp.w1h, d_in[7], D_, D_, 64, 160); enc2(fn, &mp.w3h, d_in[9], F_, D_, 64, 160);
        enc2(fn, &mp.wmod, d_in[12], 6 * D_, D_, 64, 160);
        const cuuint64_t R = D_ * 2;
        cuuint64_t da[5] = {D_, 2, 4, 4, 16}, sa[4] = {R, 8 * R, 2 * R, 32 * R}, db[5] = {D_, 2, 2, 4, 8}, sb[4] = {R, 8 * R, 2 * R, 16 * R};
        cuuint32_t ba[5] = {64, 2, 4, 4, 4}, bb[5] = {64, 2, 2, 4, 8};
        enc(fn, &mp.w2a, d_in[8], 5, da, sa, ba); enc(fn, &mp.w2b, (bf16*)d_in[8] + 512 * D_, 5, db, sb, bb);
        cuuint64_t dw[3] = {64, D_, 27}, sw[2] = {F_ * 2, 128};
        cuuint32_t bw[3] = {64, 32, 3};
        enc(fn, &mp.w3a, d_in[9], 3, dw, sw, bw);
        enc2(fn, &mp.w3b, d_in[9], F_, D_, 24, 32);
        enc2(fn, &mp.w4[0], d_in[10], D_, F_, 64, 64); enc2(fn, &mp.w4[1], d_in[10], D_, F_, 64, 48);
        pp.q = (const bf16*)d_in[0]; pp.w_mod = (const bf16*)d_in[12]; pp.shift_k = (const bf16*)d_in[3];
        pp.ssm_k = (const bf16*)d_in[4]; pp.ssm_D = (const bf16*)d_in[5]; pp.w1 = (const bf16*)d_in[7]; pp.w2 = (const bf16*)d_in[8];
        pp.w4 = (const bf16*)d_in[10]; pp.c = (const bf16*)d_in[11];
        cudaFuncSetAttribute(fused_kernel, cudaFuncAttributeMaxDynamicSharedMemorySize, SMEM_BYTES);
        for (int i = 0; i < 13; i++) cached[i] = d_in[i];
    }
    fused_kernel<<<NCTA, NTHR, SMEM_BYTES, cudaStreamPerThread>>>(pp, (bf16*)d_out, mp);
}
```

```cpp
#include <cuda_runtime.h>
#include <cuda_bf16.h>
#include <cuda.h>
#include <stdint.h>
#include <stdio.h>

typedef __nv_bfloat16 bf16;

constexpr int S_ = 2048, D_ = 640, F_ = 1728;
constexpr int NCTA = 132, NTHR = 512;

constexpr int TAB_BYTES = 9216, VEC_BYTES = 1440;
struct Counters {
    unsigned kv[8 * 32];
    unsigned q[4 * 32], x[4 * 32];
    unsigned wr[32], tab[32], uv[32], cs[32], cs2[32], done[32];
    unsigned g1[32 * 32];
    unsigned g2[32 * 32];
};
struct Scratch {
    Counters cnt;
    unsigned epoch;
    alignas(1024) bf16 qst[2 * S_];
    alignas(1024) uint4 wr[2 * 8 * 10 * 128];
    alignas(1024) uint2 mod[2 * 6 * D_];
    alignas(1024) uint4 tab[(TAB_BYTES + 8 * VEC_BYTES) / 16];
    alignas(1024) float uv[2 * 3 * D_];
    alignas(1024) float cs3[2 * 1920];
    alignas(1024) uint4 cs3b[8 * 216];
    alignas(1024) float2 stats[32 * 8 * 64];
    alignas(1024) bf16 kvT[D_ * S_];
    alignas(1024) bf16 qT[D_ * S_];
    alignas(1024) bf16 x1T[D_ * S_];
    alignas(1024) bf16 t[(S_ + 4) * D_];
    alignas(1024) uint4 x2f[32 * 40 * 128];
    alignas(1024) uint4 x1f[32 * 8 * 5 * 128];
    alignas(1024) uint4 part[32 * 8 * 10 * 4 * 128];
};
__device__ Scratch g_scratch;
#define g_kvT (pp.s->kvT)
#define g_qT (pp.s->qT)
#define g_x1T (pp.s->x1T)
#define g_qst (pp.s->qst)
#define g_t (pp.s->t)
#define g_x2f (pp.s->x2f)
#define g_x1f (pp.s->x1f)
#define g_part (pp.s->part)
#define g_wr (pp.s->wr)
#define g_mod (pp.s->mod)
#define g_tab (pp.s->tab)
#define g_uv (pp.s->uv)
#define g_cs3 (pp.s->cs3)
#define g_cs3b (pp.s->cs3b)
#define g_stats (pp.s->stats)
#define g_cnt (pp.s->cnt)
#define g_epoch (pp.s->epoch)

struct Maps {
    CUtensorMap k, v, q;
    CUtensorMap qT;
    CUtensorMap x[3];
    CUtensorMap w1, w1h, w3h, wmod;
    CUtensorMap w2a, w2b;
    CUtensorMap w3a, w3b;
    CUtensorMap w4[2];
};

struct Ptrs {
    Scratch* s;
    uint64_t nil;
    const bf16 *q, *w_mod, *shift_k, *ssm_k, *ssm_D, *w1, *w2, *w4, *c;
};

constexpr int OFF_W = 0;
constexpr int OFF_XR = 131072;
constexpr int OFF_REM = 196608;
constexpr int OFF_TAB = OFF_REM + 5 * 4096;
constexpr int OFF_ROW = OFF_TAB + 4608;
constexpr int OFF_F1 = OFF_ROW + 4096;
constexpr int RECV_BYTES = 30720;
constexpr int OFF_M = OFF_REM + RECV_BYTES;
constexpr int OFF_OUT = OFF_XR + 32768;
static_assert(OFF_F1 + 1280 <= OFF_M, "G1 map");
constexpr int OFF_ST = 0;
constexpr int OFF_SSM = 20480;
constexpr int OFF_WM = 0;
constexpr int OFF_QIN = 49152;
constexpr int OFF_QT = 49152;
constexpr int OFF_Z = OFF_TAB;
constexpr int OFF_RING = 80896;
constexpr int OFF_KIN = OFF_RING, OFF_VIN = OFF_KIN + 2 * 10752;
constexpr int OFF_CH = OFF_RING + 3 * 16384, CH_BYTES = 13312, OFF_P = 5120;
static_assert(OFF_RING + 5 * 16384 <= OFF_CH + 3 * CH_BYTES && OFF_CH + 5 * CH_BYTES <= OFF_REM, "the last two rings replace channels 0..2");
constexpr int M_BAR = OFF_M;
constexpr int M_F1 = OFF_M + 800;
constexpr int M_GB = M_F1 + 1280, M_C = M_GB + 320, M_SB = M_C + 320, M_CI = M_SB + 320;
constexpr int M_KS = M_CI + 320;
constexpr int M_AB = M_KS + 160;
constexpr int M_EP = M_AB + 80;
constexpr int M_SINK = M_EP + 16;
constexpr int M_NUL = M_SINK + 16;
constexpr int M_TS = M_NUL + 128;
constexpr int SMEM_BYTES = M_TS;
static_assert(SMEM_BYTES <= 232448, "smem");

enum { B_WFULL = 0, B_WEMPTY = 8, B_XEMPTY = 16, B_XFULL = 24  ,
       B_RAW = 40, B_QIN = 41, B_SSM = 42, B_VEC = 43, B_VEC3 = 44, B_WM = 45, B_TAB = 46, B_QRDY = 47,
       B_MODR = 48, B_GATE = 49, B_RETRY = 55, B_RAW2 = 59, B_RAW3 = 60, B_SUMS = 62, B_RECV = 64  ,
       B_SIG = 72, B_RING = 74  ,
       B_LAND = 80,
       B_XS = 88, B_R1 = 89, B_BK = 90, B_KVS = 91,
       B_XFREE = 92, B_OWN = 93,
       B_IN = 94, B_AGAIN = 96 };
#define T_KVB 1800
#define T_SSM 3300
#define PF_T0 4800
#define PF_DT 420
#define Q_UNROLL 1
#define HELP_T 1000
#define ST3 1
#define LD3 23
#define GATE_W2 7
#define GATE_W3 27
#define GATE_W3B 37
#define W3_N2 13
#define LEAD1 4
#define XLEAD 3

#define SPIN_FAIL(code) __trap();
#define SPIN_LIMIT (1u << 22)
#define STALE(c)
#define STALE1(c)
#define TS(c, i)
#define TG(c, i)
#define TR(c, i)
#define TR2(c, i)
#define TR4(c, i)
#define TR5(c, i)
#define SPIN_CHECK(code) asm volatile("" ::"r"(it));
#define RARE(x) __builtin_expect((x) != 0, 0)
__device__ __forceinline__ uint32_t s2u(const void* p) { return (uint32_t)__cvta_generic_to_shared(p); }
__device__ __forceinline__ bool elect() {
    uint32_t p;
    asm volatile("{.reg .pred P; elect.sync _|P, 0xffffffff; selp.u32 %0,1,0,P;}" : "=r"(p));
    return p != 0;
}
__device__ __forceinline__ void mbar_init(uint32_t b, uint32_t n) { asm volatile("mbarrier.init.shared.b64 [%0], %1;" ::"r"(b), "r"(n)); }
__device__ __forceinline__ void mbar_expect(uint32_t b, uint32_t bytes) {
    asm volatile("mbarrier.arrive.expect_tx.shared.b64 _, [%0], %1;" ::"r"(b), "r"(bytes) : "memory");
}
__device__ __forceinline__ void mbar_arrive(uint32_t b) { asm volatile("mbarrier.arrive.shared.b64 _, [%0];" ::"r"(b) : "memory"); }
__device__ __forceinline__ void mbar_arrive_after(uint32_t b, uint32_t v0, uint32_t v1, uint32_t nil) { mbar_arrive(b + ((v0 | v1) & nil)); }
__device__ __forceinline__ void warp_arrive(uint32_t b) { __syncwarp(); if (elect()) mbar_arrive(b); }
__device__ __forceinline__ uint32_t peer_addr(uint32_t a) {
    uint32_t r;
    asm("{\n.reg .b32 q;\nmov.u32 q, %%cluster_ctarank;\nxor.b32 q, q, 1;\nmapa.shared::cluster.u32 %0, %1, q;\n}" : "=r"(r) : "r"(a));
    return r;
}
__device__ __forceinline__ bool mbar_test(uint32_t b, uint32_t parity) {
    uint32_t ok;
    asm volatile("{.reg .pred P; mbarrier.test_wait.parity.shared.b64 P, [%1], %2; selp.u32 %0,1,0,P;}" : "=r"(ok) : "r"(b), "r"(parity) : "memory");
    return ok != 0;
}
__device__ __forceinline__ bool mbar_try(uint32_t b, uint32_t parity) {
    uint32_t ok;
    asm volatile("{.reg .pred P; mbarrier.try_wait.parity.shared.b64 P, [%1], %2; selp.u32 %0,1,0,P;}" : "=r"(ok) : "r"(b), "r"(parity) : "memory");
    return ok != 0;
}
__device__ __forceinline__ void mbar_wait(uint32_t b, uint32_t parity) {
    if (__all_sync(0xffffffffu, mbar_try(b, parity))) return;
    uint32_t it = 0;
    while (!__all_sync(0xffffffffu, mbar_try(b, parity))) { if (++it > SPIN_LIMIT) SPIN_FAIL((b >> 3) & 63) }
}
__device__ __forceinline__ void mbar_spin(uint32_t b, uint32_t parity) {
    asm volatile("{\n.reg .pred P;\nSPIN:\nmbarrier.try_wait.parity.shared.b64 P, [%0], %1;\n@!P bra.uni SPIN;\n}" ::"r"(b), "r"(parity) : "memory");
}
__device__ __forceinline__ void bar_sync(int id, int n) { asm volatile("bar.sync %0, %1;" ::"r"(id), "r"(n) : "memory"); }
__device__ __forceinline__ void fence_async_smem() { asm volatile("fence.proxy.async.shared::cta;" ::: "memory"); }
__device__ __forceinline__ void wait_cnt(const unsigned* p, unsigned target, bool tagged = false) {
    unsigned v, it = 0;
    do {
        asm volatile("ld.relaxed.gpu.global.u32 %0, [%1];" : "=r"(v) : "l"(p) : "memory");
        SPIN_CHECK(60 + (target & 3))
    } while (!__all_sync(0xffffffffu, v >= target));
    if (!tagged) asm volatile("fence.acquire.gpu;" ::: "memory");
}
__device__ __forceinline__ void signal_cnt(unsigned* p, int lane, int n, bool tagged = false) {
    if (tagged) asm volatile("{\n.reg .pred P;\nsetp.lt.s32 P, %1, %2;\n@P red.relaxed.gpu.global.add.u32 [%0], %3;\n}" ::"l"(p), "r"(lane), "r"(n), "r"(1) : "memory");
    else if (lane < n) asm volatile("red.release.gpu.global.add.u32 [%0], 1;" ::"l"(p) : "memory");
    __syncwarp();
}
__device__ __forceinline__ uint32_t clock_lo() { uint32_t c; asm volatile("mov.u32 %0, %%clock;" : "=r"(c)); return c; }
__device__ __forceinline__ void wait_clock(uint32_t c0, uint32_t t) {
    asm volatile("{\n.reg .pred P;\n.reg .b32 c;\nWAIT:\nnanosleep.u32 20;\nmov.u32 c, %%clock;\nsub.u32 c, c, %0;\nsetp.lt.u32 P, c, %1;\n@P bra.uni WAIT;\n}" ::"r"(c0), "r"(t) : "memory");
}
__device__ __forceinline__ void tma_ld2(uint32_t dst, const CUtensorMap* m, int c0, int c1, uint32_t bar) {
    asm volatile("cp.async.bulk.tensor.2d.shared::cluster.global.mbarrier::complete_tx::bytes [%0], [%1, {%3, %4}], [%2];"
                 ::"r"(dst), "l"(m), "r"(bar), "r"(c0), "r"(c1) : "memory");
}
__device__ __forceinline__ void tma_ld3(uint32_t dst, const CUtensorMap* m, int c0, int c1, int c2, uint32_t bar) {
    asm volatile("cp.async.bulk.tensor.3d.shared::cluster.global.mbarrier::complete_tx::bytes [%0], [%1, {%3, %4, %5}], [%2];"
                 ::"r"(dst), "l"(m), "r"(bar), "r"(c0), "r"(c1), "r"(c2) : "memory");
}
__device__ __forceinline__ void tma_ld5(uint32_t dst, const CUtensorMap* m, int col, int blk, uint32_t bar) {
    asm volatile("cp.async.bulk.tensor.5d.shared::cluster.global.mbarrier::complete_tx::bytes [%0], [%1, {%3, %4, %4, %4, %5}], [%2];"
                 ::"r"(dst), "l"(m), "r"(bar), "r"(col), "r"(0), "r"(blk) : "memory");
}
__device__ __forceinline__ void bulk_ld(uint32_t dst, const void* src, uint32_t bytes, uint32_t bar) {
    asm volatile("cp.async.bulk.shared::cluster.global.mbarrier::complete_tx::bytes [%0], [%1], %2, [%3];" ::"r"(dst), "l"(src), "r"(bytes), "r"(bar) : "memory");
}
__device__ __forceinline__ void l2_prefetch(const void* p, uint32_t bytes) {
    asm volatile("cp.async.bulk.prefetch.L2.global [%0], %1;" ::"l"(p), "r"(bytes) : "memory");
}
__device__ __forceinline__ void wg_fence() { asm volatile("wgmma.fence.sync.aligned;" ::: "memory"); }
__device__ __forceinline__ void wg_commit() { asm volatile("wgmma.commit_group.sync.aligned;" ::: "memory"); }
template <int N> __device__ __forceinline__ void wg_wait() { asm volatile("wgmma.wait_group.sync.aligned %0;" ::"n"(N) : "memory"); }
template <int N> __device__ __forceinline__ void reg_fence(float (&d)[N]) {
#pragma unroll
    for (int i = 0; i < N; i++) asm volatile("" : "+f"(d[i])::"memory");
}
template <int N> __device__ __forceinline__ void zero(float (&d)[N]) {
#pragma unroll
    for (int i = 0; i < N; i++) asm volatile("mov.b32 %0, 0;" : "=f"(d[i]));
}
__device__ __forceinline__ uint32_t lds32(uint32_t a) { uint32_t v; asm volatile("ld.shared.b32 %0, [%1];" : "=r"(v) : "r"(a)); return v; }
__device__ __forceinline__ uint2 lds64(uint32_t a) { uint2 v; asm volatile("ld.shared.v2.b32 {%0,%1}, [%2];" : "=r"(v.x), "=r"(v.y) : "r"(a)); return v; }
__device__ __forceinline__ float2 lds64f(uint32_t a) { float2 v; asm volatile("ld.shared.v2.f32 {%0,%1}, [%2];" : "=f"(v.x), "=f"(v.y) : "r"(a)); return v; }
__device__ __forceinline__ void sts32(uint32_t a, uint32_t v) { asm volatile("st.shared.b32 [%0], %1;" ::"r"(a), "r"(v) : "memory"); }
__device__ __forceinline__ void sts64f(uint32_t a, float x, float y) { asm volatile("st.shared.v2.f32 [%0], {%1,%2};" ::"r"(a), "f"(x), "f"(y) : "memory"); }
__device__ __forceinline__ void sts128(uint32_t a, uint32_t x, uint32_t y, uint32_t z, uint32_t w) {
    asm volatile("st.shared.v4.b32 [%0], {%1,%2,%3,%4};" ::"r"(a), "r"(x), "r"(y), "r"(z), "r"(w) : "memory");
}
__device__ __forceinline__ void sts128f(uint32_t a, float x, float y, float z, float w) {
    asm volatile("st.shared.v4.f32 [%0], {%1,%2,%3,%4};" ::"r"(a), "f"(x), "f"(y), "f"(z), "f"(w) : "memory");
}
__device__ __forceinline__ uint4 lds128(uint32_t a) {
    uint4 v;
    asm volatile("ld.shared.v4.b32 {%0,%1,%2,%3}, [%4];" : "=r"(v.x), "=r"(v.y), "=r"(v.z), "=r"(v.w) : "r"(a) : "memory");
    return v;
}
__device__ __forceinline__ float4 lds128f(uint32_t a) {
    float4 v;
    asm volatile("ld.shared.v4.f32 {%0,%1,%2,%3}, [%4];" : "=f"(v.x), "=f"(v.y), "=f"(v.z), "=f"(v.w) : "r"(a) : "memory");
    return v;
}
__device__ __forceinline__ void stg128(void* p, uint32_t x, uint32_t y, uint32_t z, uint32_t w) {
    asm volatile("st.global.v4.b32 [%0], {%1,%2,%3,%4};" ::"l"(p), "r"(x), "r"(y), "r"(z), "r"(w) : "memory");
}
__device__ __forceinline__ void stg128(void* p, uint4 v) { stg128(p, v.x, v.y, v.z, v.w); }
__device__ __forceinline__ void stg128_if(void* p, uint4 v, int on) {
    asm volatile("{\n.reg .pred p;\nsetp.ne.s32 p, %5, 0;\n@p st.global.v4.b32 [%0], {%1,%2,%3,%4};\n}" ::"l"(p), "r"(v.x), "r"(v.y), "r"(v.z), "r"(v.w), "r"(on) : "memory");
}
__device__ __forceinline__ void stg64(void* p, uint32_t x, uint32_t y) { asm volatile("st.global.v2.b32 [%0], {%1,%2};" ::"l"(p), "r"(x), "r"(y) : "memory"); }
__device__ __forceinline__ void stsm4(uint32_t a, uint32_t r0, uint32_t r1, uint32_t r2, uint32_t r3) {
    asm volatile("stmatrix.sync.aligned.m8n8.x4.shared.b16 [%0], {%1,%2,%3,%4};" ::"r"(a), "r"(r0), "r"(r1), "r"(r2), "r"(r3) : "memory");
}
__device__ __forceinline__ void stsm4t(uint32_t a, uint32_t r0, uint32_t r1, uint32_t r2, uint32_t r3) {
    asm volatile("stmatrix.sync.aligned.m8n8.x4.trans.shared.b16 [%0], {%1,%2,%3,%4};" ::"r"(a), "r"(r0), "r"(r1), "r"(r2), "r"(r3) : "memory");
}
__device__ __forceinline__ void ldsm4t_if(bool p, uint32_t a, uint32_t* r) {
    asm volatile("{\n.reg .pred p;\nsetp.ne.u32 p, %5, 0;\n@p ldmatrix.sync.aligned.m8n8.x4.trans.shared.b16 {%0,%1,%2,%3}, [%4];\n}"
                 : "+r"(r[0]), "+r"(r[1]), "+r"(r[2]), "+r"(r[3]) : "r"(a), "r"((uint32_t)p) : "memory");
}
__device__ __forceinline__ void ldsm4t(uint32_t a, uint32_t& r0, uint32_t& r1, uint32_t& r2, uint32_t& r3) {
    asm volatile("ldmatrix.sync.aligned.m8n8.x4.trans.shared.b16 {%0,%1,%2,%3}, [%4];" : "=r"(r0), "=r"(r1), "=r"(r2), "=r"(r3) : "r"(a) : "memory");
}
__device__ __forceinline__ uint32_t pack2(float lo, float hi) {
    uint32_t r;
    asm("cvt.rn.bf16x2.f32 %0, %1, %2;" : "=r"(r) : "f"(hi), "f"(lo));
    return r;
}
__device__ __forceinline__ uint32_t mul2(uint32_t a, uint32_t b) { uint32_t r; asm("mul.rn.bf16x2 %0, %1, %2;" : "=r"(r) : "r"(a), "r"(b)); return r; }
__device__ __forceinline__ uint32_t fma2(uint32_t a, uint32_t b, uint32_t c) { uint32_t r; asm("fma.rn.bf16x2 %0, %1, %2, %3;" : "=r"(r) : "r"(a), "r"(b), "r"(c)); return r; }
__device__ __forceinline__ uint32_t add2(uint32_t a, uint32_t b) { uint32_t r; asm("add.rn.bf16x2 %0, %1, %2;" : "=r"(r) : "r"(a), "r"(b)); return r; }
__device__ __forceinline__ void hmma(float (&d)[4], uint32_t a0, uint32_t a1, uint32_t a2, uint32_t a3, uint32_t b0, uint32_t b1) {
    asm volatile("mma.sync.aligned.m16n8k16.row.col.f32.bf16.bf16.f32 {%0,%1,%2,%3}, {%4,%5,%6,%7}, {%8,%9}, {%0,%1,%2,%3};"
        : "+f"(d[0]), "+f"(d[1]), "+f"(d[2]), "+f"(d[3]) : "r"(a0), "r"(a1), "r"(a2), "r"(a3), "r"(b0), "r"(b1));
}
__device__ __forceinline__ float blo(uint32_t w) { return __uint_as_float(w << 16); }
__device__ __forceinline__ float bhi(uint32_t w) { return __uint_as_float(w & 0xffff0000u); }
__device__ __forceinline__ float rbf(float x) { return __bfloat162float(__float2bfloat16_rn(x)); }
__device__ __forceinline__ uint32_t ldg32(const void* p) { uint32_t v; asm volatile("ld.global.nc.b32 %0, [%1];" : "=r"(v) : "l"(p)); return v; }
__device__ __forceinline__ uint2 ldg64(const void* p) { uint2 v; asm volatile("ld.global.nc.v2.b32 {%0,%1}, [%2];" : "=r"(v.x), "=r"(v.y) : "l"(p)); return v; }
__device__ __forceinline__ uint4 ldg128(const void* p) {
    uint4 v;
    asm volatile("ld.global.nc.v4.b32 {%0,%1,%2,%3}, [%4];" : "=r"(v.x), "=r"(v.y), "=r"(v.z), "=r"(v.w) : "l"(p));
    return v;
}
__device__ __forceinline__ uint4 ldcg128(const void* p) {
    uint4 v;
    asm volatile("ld.global.cg.v4.u32 {%0,%1,%2,%3}, [%4];" : "=r"(v.x), "=r"(v.y), "=r"(v.z), "=r"(v.w) : "l"(p) : "memory");
    return v;
}
__device__ __forceinline__ float4 ldcg128f(const void* p) {
    float4 v;
    asm volatile("ld.global.cg.v4.f32 {%0,%1,%2,%3}, [%4];" : "=f"(v.x), "=f"(v.y), "=f"(v.z), "=f"(v.w) : "l"(p) : "memory");
    return v;
}
__device__ __forceinline__ float2 ldcg64f(const void* p) { float2 v; asm volatile("ld.global.cg.v2.f32 {%0,%1}, [%2];" : "=f"(v.x), "=f"(v.y) : "l"(p) : "memory"); return v; }
__device__ __forceinline__ float ldcg32f(const void* p) { float v; asm volatile("ld.global.cg.f32 %0, [%1];" : "=f"(v) : "l"(p) : "memory"); return v; }
__device__ __forceinline__ float2 ld_stat(const float2* p) {
    float2 v;
    asm volatile("{\n.reg .b64 q;\nld.relaxed.gpu.global.b64 q, [%2];\nmov.b64 {%0, %1}, q;\n}" : "=f"(v.x), "=f"(v.y) : "l"(p) : "memory");
    return v;
}
__device__ __forceinline__ uint32_t ld_cold(const unsigned* p) { uint32_t v; asm volatile("ld.relaxed.gpu.global.u32 %0, [%1];" : "=r"(v) : "l"(p) : "memory"); return v; }
__device__ __forceinline__ uint2 ld_mod(const uint2* p) {
    uint64_t v;
    asm volatile("ld.relaxed.gpu.global.b64 %0, [%1];" : "=l"(v) : "l"(p) : "memory");
    return make_uint2((uint32_t)v, (uint32_t)(v >> 32));
}
__device__ __forceinline__ float silu(float x) {
    float e, r;
    asm("ex2.approx.ftz.f32 %0, %1;" : "=f"(e) : "f"(x * -1.4426950408889634f));
    asm("rcp.approx.ftz.f32 %0, %1;" : "=f"(r) : "f"(1.f + e));
    return x * r;
}
__device__ __forceinline__ float gelu2(float h) {
    float u = h * fmaf(h * h, 8.f * 0.0356774081f, 2.f * 0.7978845608f);
    float th;
    asm("tanh.approx.f32 %0, %1;" : "=f"(th) : "f"(u));
    return fmaf(h, th, h);
}

__device__ __forceinline__ void conv_channel(float (&d)[64], uint32_t pa, uint64_t db) {
    asm volatile("{\n.reg .b32 a0, a1, a2, a3, b0, b1, b2, b3, t0, t1;\n.reg .b64 d;\nld.shared.b32 a0, [%64];\nld.shared.b32 a1, [%64+128];\nld.shared.b32 a2, [%64+-128];\nmov.b32 a3, a0;\n"
        "ld.shared.b32 t0, [%64+256];\nld.shared.b32 t1, [%64+384];\nadd.s64 d, %65, 0;\nwgmma.fence.sync.aligned;\nwgmma.mma_async.sync.aligned.m64n128k16.f32.bf16.bf16 {%0, %1, %2, %3, %4, %5, %6, %7, %8, %9, %10, %11, %12, %13, %14, %15, %16, %17, %18, %19, %20, %21, %22, %23, %24, %25, %26, %27, %28, %29, %30, %31, %32, %33, %34, %35, %36, %37, %38, %39, %40, %41, %42, %43, %44, %45, %46, %47, %48, %49, %50, %51, %52, %53, %54, %55, %56, %57, %58, %59, %60, %61, %62, %63}, {a0, a1, a2, a3}, d, 0, 1, 1, 0;\nwgmma.commit_group.sync.aligned;\nwgmma.wait_group.sync.aligned 1;\nmov.b32 b2, a1;\nmov.b32 b0, t0;\nmov.b32 b3, t0;\nmov.b32 b1, t1;\n"
        "ld.shared.b32 t0, [%64+512];\nld.shared.b32 t1, [%64+640];\nadd.s64 d, %65, 8;\nwgmma.fence.sync.aligned;\nwgmma.mma_async.sync.aligned.m64n128k16.f32.bf16.bf16 {%0, %1, %2, %3, %4, %5, %6, %7, %8, %9, %10, %11, %12, %13, %14, %15, %16, %17, %18, %19, %20, %21, %22, %23, %24, %25, %26, %27, %28, %29, %30, %31, %32, %33, %34, %35, %36, %37, %38, %39, %40, %41, %42, %43, %44, %45, %46, %47, %48, %49, %50, %51, %52, %53, %54, %55, %56, %57, %58, %59, %60, %61, %62, %63}, {b0, b1, b2, b3}, d, 1, 1, 1, 0;\nwgmma.commit_group.sync.aligned;\nwgmma.wait_group.sync.aligned 1;\nmov.b32 a2, b1;\nmov.b32 a0, t0;\nmov.b32 a3, t0;\nmov.b32 a1, t1;\n"
        "ld.shared.b32 t0, [%64+768];\nld.shared.b32 t1, [%64+896];\nadd.s64 d, %65, 16;\nwgmma.fence.sync.aligned;\nwgmma.mma_async.sync.aligned.m64n128k16.f32.bf16.bf16 {%0, %1, %2, %3, %4, %5, %6, %7, %8, %9, %10, %11, %12, %13, %14, %15, %16, %17, %18, %19, %20, %21, %22, %23, %24, %25, %26, %27, %28, %29, %30, %31, %32, %33, %34, %35, %36, %37, %38, %39, %40, %41, %42, %43, %44, %45, %46, %47, %48, %49, %50, %51, %52, %53, %54, %55, %56, %57, %58, %59, %60, %61, %62, %63}, {a0, a1, a2, a3}, d, 1, 1, 1, 0;\nwgmma.commit_group.sync.aligned;\nwgmma.wait_group.sync.aligned 1;\nmov.b32 b2, a1;\nmov.b32 b0, t0;\nmov.b32 b3, t0;\nmov.b32 b1, t1;\n"
        "ld.shared.b32 t0, [%64+1024];\nld.shared.b32 t1, [%64+1152];\nadd.s64 d, %65, 24;\nwgmma.fence.sync.aligned;\nwgmma.mma_async.sync.aligned.m64n128k16.f32.bf16.bf16 {%0, %1, %2, %3, %4, %5, %6, %7, %8, %9, %10, %11, %12, %13, %14, %15, %16, %17, %18, %19, %20, %21, %22, %23, %24, %25, %26, %27, %28, %29, %30, %31, %32, %33, %34, %35, %36, %37, %38, %39, %40, %41, %42, %43, %44, %45, %46, %47, %48, %49, %50, %51, %52, %53, %54, %55, %56, %57, %58, %59, %60, %61, %62, %63}, {b0, b1, b2, b3}, d, 1, 1, 1, 0;\nwgmma.commit_group.sync.aligned;\nwgmma.wait_group.sync.aligned 1;\nmov.b32 a2, b1;\nmov.b32 a0, t0;\nmov.b32 a3, t0;\nmov.b32 a1, t1;\n"
        "ld.shared.b32 t0, [%64+1280];\nld.shared.b32 t1, [%64+1408];\nadd.s64 d, %65, 32;\nwgmma.fence.sync.aligned;\nwgmma.mma_async.sync.aligned.m64n128k16.f32.bf16.bf16 {%0, %1, %2, %3, %4, %5, %6, %7, %8, %9, %10, %11, %12, %13, %14, %15, %16, %17, %18, %19, %20, %21, %22, %23, %24, %25, %26, %27, %28, %29, %30, %31, %32, %33, %34, %35, %36, %37, %38, %39, %40, %41, %42, %43, %44, %45, %46, %47, %48, %49, %50, %51, %52, %53, %54, %55, %56, %57, %58, %59, %60, %61, %62, %63}, {a0, a1, a2, a3}, d, 1, 1, 1, 0;\nwgmma.commit_group.sync.aligned;\nwgmma.wait_group.sync.aligned 1;\nmov.b32 b2, a1;\nmov.b32 b0, t0;\nmov.b32 b3, t0;\nmov.b32 b1, t1;\n"
        "ld.shared.b32 t0, [%64+1536];\nld.shared.b32 t1, [%64+1664];\nadd.s64 d, %65, 40;\nwgmma.fence.sync.aligned;\nwgmma.mma_async.sync.aligned.m64n128k16.f32.bf16.bf16 {%0, %1, %2, %3, %4, %5, %6, %7, %8, %9, %10, %11, %12, %13, %14, %15, %16, %17, %18, %19, %20, %21, %22, %23, %24, %25, %26, %27, %28, %29, %30, %31, %32, %33, %34, %35, %36, %37, %38, %39, %40, %41, %42, %43, %44, %45, %46, %47, %48, %49, %50, %51, %52, %53, %54, %55, %56, %57, %58, %59, %60, %61, %62, %63}, {b0, b1, b2, b3}, d, 1, 1, 1, 0;\nwgmma.commit_group.sync.aligned;\nwgmma.wait_group.sync.aligned 1;\nmov.b32 a2, b1;\nmov.b32 a0, t0;\nmov.b32 a3, t0;\nmov.b32 a1, t1;\n"
        "ld.shared.b32 t0, [%64+1792];\nld.shared.b32 t1, [%64+1920];\nadd.s64 d, %65, 48;\nwgmma.fence.sync.aligned;\nwgmma.mma_async.sync.aligned.m64n128k16.f32.bf16.bf16 {%0, %1, %2, %3, %4, %5, %6, %7, %8, %9, %10, %11, %12, %13, %14, %15, %16, %17, %18, %19, %20, %21, %22, %23, %24, %25, %26, %27, %28, %29, %30, %31, %32, %33, %34, %35, %36, %37, %38, %39, %40, %41, %42, %43, %44, %45, %46, %47, %48, %49, %50, %51, %52, %53, %54, %55, %56, %57, %58, %59, %60, %61, %62, %63}, {a0, a1, a2, a3}, d, 1, 1, 1, 0;\nwgmma.commit_group.sync.aligned;\nwgmma.wait_group.sync.aligned 1;\nmov.b32 b2, a1;\nmov.b32 b0, t0;\nmov.b32 b3, t0;\nmov.b32 b1, t1;\n"
        "ld.shared.b32 t0, [%64+2048];\nld.shared.b32 t1, [%64+2176];\nadd.s64 d, %65, 56;\nwgmma.fence.sync.aligned;\nwgmma.mma_async.sync.aligned.m64n128k16.f32.bf16.bf16 {%0, %1, %2, %3, %4, %5, %6, %7, %8, %9, %10, %11, %12, %13, %14, %15, %16, %17, %18, %19, %20, %21, %22, %23, %24, %25, %26, %27, %28, %29, %30, %31, %32, %33, %34, %35, %36, %37, %38, %39, %40, %41, %42, %43, %44, %45, %46, %47, %48, %49, %50, %51, %52, %53, %54, %55, %56, %57, %58, %59, %60, %61, %62, %63}, {b0, b1, b2, b3}, d, 1, 1, 1, 0;\nwgmma.commit_group.sync.aligned;\nwgmma.wait_group.sync.aligned 1;\nmov.b32 a2, b1;\nmov.b32 a0, t0;\nmov.b32 a3, t0;\nmov.b32 a1, t1;\n"
        "ld.shared.b32 t0, [%64+2304];\nld.shared.b32 t1, [%64+2432];\nadd.s64 d, %65, 64;\nwgmma.fence.sync.aligned;\nwgmma.mma_async.sync.aligned.m64n96k16.f32.bf16.bf16 {%0, %1, %2, %3, %4, %5, %6, %7, %8, %9, %10, %11, %12, %13, %14, %15, %16, %17, %18, %19, %20, %21, %22, %23, %24, %25, %26, %27, %28, %29, %30, %31, %32, %33, %34, %35, %36, %37, %38, %39, %40, %41, %42, %43, %44, %45, %46, %47}, {a0, a1, a2, a3}, d, 1, 1, 1, 0;\nwgmma.commit_group.sync.aligned;\nwgmma.wait_group.sync.aligned 1;\nmov.b32 b2, a1;\nmov.b32 b0, t0;\nmov.b32 b3, t0;\nmov.b32 b1, t1;\n"
        "ld.shared.b32 t0, [%64+2560];\nld.shared.b32 t1, [%64+2688];\nadd.s64 d, %65, 72;\nwgmma.fence.sync.aligned;\nwgmma.mma_async.sync.aligned.m64n96k16.f32.bf16.bf16 {%0, %1, %2, %3, %4, %5, %6, %7, %8, %9, %10, %11, %12, %13, %14, %15, %16, %17, %18, %19, %20, %21, %22, %23, %24, %25, %26, %27, %28, %29, %30, %31, %32, %33, %34, %35, %36, %37, %38, %39, %40, %41, %42, %43, %44, %45, %46, %47}, {b0, b1, b2, b3}, d, 1, 1, 1, 0;\nwgmma.commit_group.sync.aligned;\nwgmma.wait_group.sync.aligned 1;\nmov.b32 a2, b1;\nmov.b32 a0, t0;\nmov.b32 a3, t0;\nmov.b32 a1, t1;\n"
        "ld.shared.b32 t0, [%64+2816];\nld.shared.b32 t1, [%64+2944];\nadd.s64 d, %65, 80;\nwgmma.fence.sync.aligned;\nwgmma.mma_async.sync.aligned.m64n88k16.f32.bf16.bf16 {%0, %1, %2, %3, %4, %5, %6, %7, %8, %9, %10, %11, %12, %13, %14, %15, %16, %17, %18, %19, %20, %21, %22, %23, %24, %25, %26, %27, %28, %29, %30, %31, %32, %33, %34, %35, %36, %37, %38, %39, %40, %41, %42, %43}, {a0, a1, a2, a3}, d, 1, 1, 1, 0;\nwgmma.commit_group.sync.aligned;\nwgmma.wait_group.sync.aligned 1;\nmov.b32 b2, a1;\nmov.b32 b0, t0;\nmov.b32 b3, t0;\nmov.b32 b1, t1;\n"
        "ld.shared.b32 t0, [%64+3072];\nld.shared.b32 t1, [%64+3200];\nadd.s64 d, %65, 88;\nwgmma.fence.sync.aligned;\nwgmma.mma_async.sync.aligned.m64n88k16.f32.bf16.bf16 {%0, %1, %2, %3, %4, %5, %6, %7, %8, %9, %10, %11, %12, %13, %14, %15, %16, %17, %18, %19, %20, %21, %22, %23, %24, %25, %26, %27, %28, %29, %30, %31, %32, %33, %34, %35, %36, %37, %38, %39, %40, %41, %42, %43}, {b0, b1, b2, b3}, d, 1, 1, 1, 0;\nwgmma.commit_group.sync.aligned;\nwgmma.wait_group.sync.aligned 1;\nmov.b32 a2, b1;\nmov.b32 a0, t0;\nmov.b32 a3, t0;\nmov.b32 a1, t1;\n"
        "ld.shared.b32 t0, [%64+3328];\nld.shared.b32 t1, [%64+3456];\nadd.s64 d, %65, 96;\nwgmma.fence.sync.aligned;\nwgmma.mma_async.sync.aligned.m64n80k16.f32.bf16.bf16 {%0, %1, %2, %3, %4, %5, %6, %7, %8, %9, %10, %11, %12, %13, %14, %15, %16, %17, %18, %19, %20, %21, %22, %23, %24, %25, %26, %27, %28, %29, %30, %31, %32, %33, %34, %35, %36, %37, %38, %39}, {a0, a1, a2, a3}, d, 1, 1, 1, 0;\nwgmma.commit_group.sync.aligned;\nwgmma.wait_group.sync.aligned 1;\nmov.b32 b2, a1;\nmov.b32 b0, t0;\nmov.b32 b3, t0;\nmov.b32 b1, t1;\n"
        "ld.shared.b32 t0, [%64+3584];\nld.shared.b32 t1, [%64+3712];\nadd.s64 d, %65, 104;\nwgmma.fence.sync.aligned;\nwgmma.mma_async.sync.aligned.m64n80k16.f32.bf16.bf16 {%0, %1, %2, %3, %4, %5, %6, %7, %8, %9, %10, %11, %12, %13, %14, %15, %16, %17, %18, %19, %20, %21, %22, %23, %24, %25, %26, %27, %28, %29, %30, %31, %32, %33, %34, %35, %36, %37, %38, %39}, {b0, b1, b2, b3}, d, 1, 1, 1, 0;\nwgmma.commit_group.sync.aligned;\nwgmma.wait_group.sync.aligned 1;\nmov.b32 a2, b1;\nmov.b32 a0, t0;\nmov.b32 a3, t0;\nmov.b32 a1, t1;\n"
        "ld.shared.b32 t0, [%64+3840];\nld.shared.b32 t1, [%64+3968];\nadd.s64 d, %65, 112;\nwgmma.fence.sync.aligned;\nwgmma.mma_async.sync.aligned.m64n72k16.f32.bf16.bf16 {%0, %1, %2, %3, %4, %5, %6, %7, %8, %9, %10, %11, %12, %13, %14, %15, %16, %17, %18, %19, %20, %21, %22, %23, %24, %25, %26, %27, %28, %29, %30, %31, %32, %33, %34, %35}, {a0, a1, a2, a3}, d, 1, 1, 1, 0;\nwgmma.commit_group.sync.aligned;\nwgmma.wait_group.sync.aligned 1;\nmov.b32 b2, a1;\nmov.b32 b0, t0;\nmov.b32 b3, t0;\nmov.b32 b1, t1;\n"
        "ld.shared.b32 t0, [%64+4096];\nld.shared.b32 t1, [%64+4224];\nadd.s64 d, %65, 120;\nwgmma.fence.sync.aligned;\nwgmma.mma_async.sync.aligned.m64n72k16.f32.bf16.bf16 {%0, %1, %2, %3, %4, %5, %6, %7, %8, %9, %10, %11, %12, %13, %14, %15, %16, %17, %18, %19, %20, %21, %22, %23, %24, %25, %26, %27, %28, %29, %30, %31, %32, %33, %34, %35}, {b0, b1, b2, b3}, d, 1, 1, 1, 0;\nwgmma.commit_group.sync.aligned;\nwgmma.wait_group.sync.aligned 1;\nmov.b32 a2, b1;\nmov.b32 a0, t0;\nmov.b32 a3, t0;\nmov.b32 a1, t1;\n"
        "ld.shared.b32 t0, [%64+4352];\nld.shared.b32 t1, [%64+4480];\nadd.s64 d, %65, 128;\nwgmma.fence.sync.aligned;\nwgmma.mma_async.sync.aligned.m64n64k16.f32.bf16.bf16 {%0, %1, %2, %3, %4, %5, %6, %7, %8, %9, %10, %11, %12, %13, %14, %15, %16, %17, %18, %19, %20, %21, %22, %23, %24, %25, %26, %27, %28, %29, %30, %31}, {a0, a1, a2, a3}, d, 1, 1, 1, 0;\nwgmma.commit_group.sync.aligned;\nwgmma.wait_group.sync.aligned 1;\nmov.b32 b2, a1;\nmov.b32 b0, t0;\nmov.b32 b3, t0;\nmov.b32 b1, t1;\n"
        "ld.shared.b32 t0, [%64+4608];\nld.shared.b32 t1, [%64+4736];\nadd.s64 d, %65, 136;\nwgmma.fence.sync.aligned;\nwgmma.mma_async.sync.aligned.m64n64k16.f32.bf16.bf16 {%0, %1, %2, %3, %4, %5, %6, %7, %8, %9, %10, %11, %12, %13, %14, %15, %16, %17, %18, %19, %20, %21, %22, %23, %24, %25, %26, %27, %28, %29, %30, %31}, {b0, b1, b2, b3}, d, 1, 1, 1, 0;\nwgmma.commit_group.sync.aligned;\nwgmma.wait_group.sync.aligned 1;\nmov.b32 a2, b1;\nmov.b32 a0, t0;\nmov.b32 a3, t0;\nmov.b32 a1, t1;\n"
        "ld.shared.b32 t0, [%64+4864];\nld.shared.b32 t1, [%64+4992];\nadd.s64 d, %65, 144;\nwgmma.fence.sync.aligned;\nwgmma.mma_async.sync.aligned.m64n56k16.f32.bf16.bf16 {%0, %1, %2, %3, %4, %5, %6, %7, %8, %9, %10, %11, %12, %13, %14, %15, %16, %17, %18, %19, %20, %21, %22, %23, %24, %25, %26, %27}, {a0, a1, a2, a3}, d, 1, 1, 1, 0;\nwgmma.commit_group.sync.aligned;\nwgmma.wait_group.sync.aligned 1;\nmov.b32 b2, a1;\nmov.b32 b0, t0;\nmov.b32 b3, t0;\nmov.b32 b1, t1;\n"
        "ld.shared.b32 t0, [%64+5120];\nld.shared.b32 t1, [%64+5248];\nadd.s64 d, %65, 152;\nwgmma.fence.sync.aligned;\nwgmma.mma_async.sync.aligned.m64n56k16.f32.bf16.bf16 {%0, %1, %2, %3, %4, %5, %6, %7, %8, %9, %10, %11, %12, %13, %14, %15, %16, %17, %18, %19, %20, %21, %22, %23, %24, %25, %26, %27}, {b0, b1, b2, b3}, d, 1, 1, 1, 0;\nwgmma.commit_group.sync.aligned;\nwgmma.wait_group.sync.aligned 1;\nmov.b32 a2, b1;\nmov.b32 a0, t0;\nmov.b32 a3, t0;\nmov.b32 a1, t1;\n"
        "ld.shared.b32 t0, [%64+5376];\nld.shared.b32 t1, [%64+5504];\nadd.s64 d, %65, 160;\nwgmma.fence.sync.aligned;\nwgmma.mma_async.sync.aligned.m64n48k16.f32.bf16.bf16 {%0, %1, %2, %3, %4, %5, %6, %7, %8, %9, %10, %11, %12, %13, %14, %15, %16, %17, %18, %19, %20, %21, %22, %23}, {a0, a1, a2, a3}, d, 1, 1, 1, 0;\nwgmma.commit_group.sync.aligned;\nwgmma.wait_group.sync.aligned 1;\nmov.b32 b2, a1;\nmov.b32 b0, t0;\nmov.b32 b3, t0;\nmov.b32 b1, t1;\n"
        "ld.shared.b32 t0, [%64+5632];\nld.shared.b32 t1, [%64+5760];\nadd.s64 d, %65, 168;\nwgmma.fence.sync.aligned;\nwgmma.mma_async.sync.aligned.m64n48k16.f32.bf16.bf16 {%0, %1, %2, %3, %4, %5, %6, %7, %8, %9, %10, %11, %12, %13, %14, %15, %16, %17, %18, %19, %20, %21, %22, %23}, {b0, b1, b2, b3}, d, 1, 1, 1, 0;\nwgmma.commit_group.sync.aligned;\nwgmma.wait_group.sync.aligned 1;\nmov.b32 a2, b1;\nmov.b32 a0, t0;\nmov.b32 a3, t0;\nmov.b32 a1, t1;\n"
        "ld.shared.b32 t0, [%64+5888];\nld.shared.b32 t1, [%64+6016];\nadd.s64 d, %65, 176;\nwgmma.fence.sync.aligned;\nwgmma.mma_async.sync.aligned.m64n40k16.f32.bf16.bf16 {%0, %1, %2, %3, %4, %5, %6, %7, %8, %9, %10, %11, %12, %13, %14, %15, %16, %17, %18, %19}, {a0, a1, a2, a3}, d, 1, 1, 1, 0;\nwgmma.commit_group.sync.aligned;\nwgmma.wait_group.sync.aligned 1;\nmov.b32 b2, a1;\nmov.b32 b0, t0;\nmov.b32 b3, t0;\nmov.b32 b1, t1;\n"
        "ld.shared.b32 t0, [%64+6144];\nld.shared.b32 t1, [%64+6272];\nadd.s64 d, %65, 184;\nwgmma.fence.sync.aligned;\nwgmma.mma_async.sync.aligned.m64n40k16.f32.bf16.bf16 {%0, %1, %2, %3, %4, %5, %6, %7, %8, %9, %10, %11, %12, %13, %14, %15, %16, %17, %18, %19}, {b0, b1, b2, b3}, d, 1, 1, 1, 0;\nwgmma.commit_group.sync.aligned;\nwgmma.wait_group.sync.aligned 1;\nmov.b32 a2, b1;\nmov.b32 a0, t0;\nmov.b32 a3, t0;\nmov.b32 a1, t1;\n"
        "ld.shared.b32 t0, [%64+6400];\nld.shared.b32 t1, [%64+6528];\nadd.s64 d, %65, 192;\nwgmma.fence.sync.aligned;\nwgmma.mma_async.sync.aligned.m64n32k16.f32.bf16.bf16 {%0, %1, %2, %3, %4, %5, %6, %7, %8, %9, %10, %11, %12, %13, %14, %15}, {a0, a1, a2, a3}, d, 1, 1, 1, 0;\nwgmma.commit_group.sync.aligned;\nwgmma.wait_group.sync.aligned 1;\nmov.b32 b2, a1;\nmov.b32 b0, t0;\nmov.b32 b3, t0;\nmov.b32 b1, t1;\n"
        "ld.shared.b32 t0, [%64+6656];\nld.shared.b32 t1, [%64+6784];\nadd.s64 d, %65, 200;\nwgmma.fence.sync.aligned;\nwgmma.mma_async.sync.aligned.m64n32k16.f32.bf16.bf16 {%0, %1, %2, %3, %4, %5, %6, %7, %8, %9, %10, %11, %12, %13, %14, %15}, {b0, b1, b2, b3}, d, 1, 1, 1, 0;\nwgmma.commit_group.sync.aligned;\nwgmma.wait_group.sync.aligned 1;\nmov.b32 a2, b1;\nmov.b32 a0, t0;\nmov.b32 a3, t0;\nmov.b32 a1, t1;\n"
        "ld.shared.b32 t0, [%64+6912];\nld.shared.b32 t1, [%64+7040];\nadd.s64 d, %65, 208;\nwgmma.fence.sync.aligned;\nwgmma.mma_async.sync.aligned.m64n24k16.f32.bf16.bf16 {%0, %1, %2, %3, %4, %5, %6, %7, %8, %9, %10, %11}, {a0, a1, a2, a3}, d, 1, 1, 1, 0;\nwgmma.commit_group.sync.aligned;\nwgmma.wait_group.sync.aligned 1;\nmov.b32 b2, a1;\nmov.b32 b0, t0;\nmov.b32 b3, t0;\nmov.b32 b1, t1;\n"
        "ld.shared.b32 t0, [%64+7168];\nld.shared.b32 t1, [%64+7296];\nadd.s64 d, %65, 216;\nwgmma.fence.sync.aligned;\nwgmma.mma_async.sync.aligned.m64n24k16.f32.bf16.bf16 {%0, %1, %2, %3, %4, %5, %6, %7, %8, %9, %10, %11}, {b0, b1, b2, b3}, d, 1, 1, 1, 0;\nwgmma.commit_group.sync.aligned;\nwgmma.wait_group.sync.aligned 1;\nmov.b32 a2, b1;\nmov.b32 a0, t0;\nmov.b32 a3, t0;\nmov.b32 a1, t1;\n"
        "ld.shared.b32 t0, [%64+7424];\nld.shared.b32 t1, [%64+7552];\nadd.s64 d, %65, 224;\nwgmma.fence.sync.aligned;\nwgmma.mma_async.sync.aligned.m64n16k16.f32.bf16.bf16 {%0, %1, %2, %3, %4, %5, %6, %7}, {a0, a1, a2, a3}, d, 1, 1, 1, 0;\nwgmma.commit_group.sync.aligned;\nwgmma.wait_group.sync.aligned 1;\nmov.b32 b2, a1;\nmov.b32 b0, t0;\nmov.b32 b3, t0;\nmov.b32 b1, t1;\n"
        "ld.shared.b32 t0, [%64+7680];\nld.shared.b32 t1, [%64+7808];\nadd.s64 d, %65, 232;\nwgmma.fence.sync.aligned;\nwgmma.mma_async.sync.aligned.m64n16k16.f32.bf16.bf16 {%0, %1, %2, %3, %4, %5, %6, %7}, {b0, b1, b2, b3}, d, 1, 1, 1, 0;\nwgmma.commit_group.sync.aligned;\nwgmma.wait_group.sync.aligned 1;\nmov.b32 a2, b1;\nmov.b32 a0, t0;\nmov.b32 a3, t0;\nmov.b32 a1, t1;\n"
        "ld.shared.b32 t0, [%64+7936];\nld.shared.b32 t1, [%64+8064];\nadd.s64 d, %65, 240;\nwgmma.fence.sync.aligned;\nwgmma.mma_async.sync.aligned.m64n8k16.f32.bf16.bf16 {%0, %1, %2, %3}, {a0, a1, a2, a3}, d, 1, 1, 1, 0;\nwgmma.commit_group.sync.aligned;\nwgmma.wait_group.sync.aligned 1;\nmov.b32 b2, a1;\nmov.b32 b0, t0;\nmov.b32 b3, t0;\nmov.b32 b1, t1;\n"
        "add.s64 d, %65, 248;\nwgmma.fence.sync.aligned;\nwgmma.mma_async.sync.aligned.m64n8k16.f32.bf16.bf16 {%0, %1, %2, %3}, {b0, b1, b2, b3}, d, 1, 1, 1, 0;\nwgmma.commit_group.sync.aligned;\nwgmma.wait_group.sync.aligned 0;\n"
        "}" : "+f"(d[0]), "+f"(d[1]), "+f"(d[2]), "+f"(d[3]), "+f"(d[4]), "+f"(d[5]), "+f"(d[6]), "+f"(d[7]), "+f"(d[8]), "+f"(d[9]), "+f"(d[10]), "+f"(d[11]), "+f"(d[12]), "+f"(d[13]), "+f"(d[14]), "+f"(d[15]), "+f"(d[16]), "+f"(d[17]), "+f"(d[18]), "+f"(d[19]), "+f"(d[20]), "+f"(d[21]), "+f"(d[22]), "+f"(d[23]), "+f"(d[24]), "+f"(d[25]), "+f"(d[26]), "+f"(d[27]), "+f"(d[28]), "+f"(d[29]), "+f"(d[30]), "+f"(d[31]), "+f"(d[32]), "+f"(d[33]), "+f"(d[34]), "+f"(d[35]), "+f"(d[36]), "+f"(d[37]), "+f"(d[38]), "+f"(d[39]), "+f"(d[40]), "+f"(d[41]), "+f"(d[42]), "+f"(d[43]), "+f"(d[44]), "+f"(d[45]), "+f"(d[46]), "+f"(d[47]), "+f"(d[48]), "+f"(d[49]), "+f"(d[50]), "+f"(d[51]), "+f"(d[52]), "+f"(d[53]), "+f"(d[54]), "+f"(d[55]), "+f"(d[56]), "+f"(d[57]), "+f"(d[58]), "+f"(d[59]), "+f"(d[60]), "+f"(d[61]), "+f"(d[62]), "+f"(d[63]) : "r"(pa), "l"(db) : "memory");
}
__device__ __forceinline__ void wgmma_rs80(float (&d)[40], uint32_t a0, uint32_t a1, uint32_t a2, uint32_t a3, uint64_t db, int sc) {
    asm volatile("{\n.reg .pred p;\nsetp.ne.b32 p, %45, 0;\n"
        "wgmma.mma_async.sync.aligned.m64n80k16.f32.bf16.bf16 {%0, %1, %2, %3, %4, %5, %6, %7, %8, %9, %10, %11, %12, %13, %14, %15, %16, %17, %18, %19, %20, %21, %22, %23, %24, %25, %26, %27, %28, %29, %30, %31, %32, %33, %34, %35, %36, %37, %38, %39}, {%40, %41, %42, %43}, %44, p, 1, 1, 1;\n}\n"
        : "+f"(d[0]), "+f"(d[1]), "+f"(d[2]), "+f"(d[3]), "+f"(d[4]), "+f"(d[5]), "+f"(d[6]), "+f"(d[7]), "+f"(d[8]), "+f"(d[9]), "+f"(d[10]), "+f"(d[11]), "+f"(d[12]), "+f"(d[13]), "+f"(d[14]), "+f"(d[15]), "+f"(d[16]), "+f"(d[17]), "+f"(d[18]), "+f"(d[19]), "+f"(d[20]), "+f"(d[21]), "+f"(d[22]), "+f"(d[23]), "+f"(d[24]), "+f"(d[25]), "+f"(d[26]), "+f"(d[27]), "+f"(d[28]), "+f"(d[29]), "+f"(d[30]), "+f"(d[31]), "+f"(d[32]), "+f"(d[33]), "+f"(d[34]), "+f"(d[35]), "+f"(d[36]), "+f"(d[37]), "+f"(d[38]), "+f"(d[39]) : "r"(a0), "r"(a1), "r"(a2), "r"(a3), "l"(db), "r"(sc));
}
__device__ __forceinline__ void wgmma_ss80(float (&d)[40], uint64_t da, uint64_t db, int sc) {
    asm volatile("{\n.reg .pred p;\nsetp.ne.b32 p, %42, 0;\n"
        "wgmma.mma_async.sync.aligned.m64n80k16.f32.bf16.bf16 {%0, %1, %2, %3, %4, %5, %6, %7, %8, %9, %10, %11, %12, %13, %14, %15, %16, %17, %18, %19, %20, %21, %22, %23, %24, %25, %26, %27, %28, %29, %30, %31, %32, %33, %34, %35, %36, %37, %38, %39}, %40, %41, p, 1, 1, 0, 1;\n}\n"
        : "+f"(d[0]), "+f"(d[1]), "+f"(d[2]), "+f"(d[3]), "+f"(d[4]), "+f"(d[5]), "+f"(d[6]), "+f"(d[7]), "+f"(d[8]), "+f"(d[9]), "+f"(d[10]), "+f"(d[11]), "+f"(d[12]), "+f"(d[13]), "+f"(d[14]), "+f"(d[15]), "+f"(d[16]), "+f"(d[17]), "+f"(d[18]), "+f"(d[19]), "+f"(d[20]), "+f"(d[21]), "+f"(d[22]), "+f"(d[23]), "+f"(d[24]), "+f"(d[25]), "+f"(d[26]), "+f"(d[27]), "+f"(d[28]), "+f"(d[29]), "+f"(d[30]), "+f"(d[31]), "+f"(d[32]), "+f"(d[33]), "+f"(d[34]), "+f"(d[35]), "+f"(d[36]), "+f"(d[37]), "+f"(d[38]), "+f"(d[39]) : "l"(da), "l"(db), "r"(sc));
}
__device__ __forceinline__ void wgmma_ss80t(float (&d)[40], uint64_t da, uint64_t db, int sc) {
    asm volatile("{\n.reg .pred p;\nsetp.ne.b32 p, %42, 0;\n"
        "wgmma.mma_async.sync.aligned.m64n80k16.f32.bf16.bf16 {%0, %1, %2, %3, %4, %5, %6, %7, %8, %9, %10, %11, %12, %13, %14, %15, %16, %17, %18, %19, %20, %21, %22, %23, %24, %25, %26, %27, %28, %29, %30, %31, %32, %33, %34, %35, %36, %37, %38, %39}, %40, %41, p, 1, 1, 1, 1;\n}\n"
        : "+f"(d[0]), "+f"(d[1]), "+f"(d[2]), "+f"(d[3]), "+f"(d[4]), "+f"(d[5]), "+f"(d[6]), "+f"(d[7]), "+f"(d[8]), "+f"(d[9]), "+f"(d[10]), "+f"(d[11]), "+f"(d[12]), "+f"(d[13]), "+f"(d[14]), "+f"(d[15]), "+f"(d[16]), "+f"(d[17]), "+f"(d[18]), "+f"(d[19]), "+f"(d[20]), "+f"(d[21]), "+f"(d[22]), "+f"(d[23]), "+f"(d[24]), "+f"(d[25]), "+f"(d[26]), "+f"(d[27]), "+f"(d[28]), "+f"(d[29]), "+f"(d[30]), "+f"(d[31]), "+f"(d[32]), "+f"(d[33]), "+f"(d[34]), "+f"(d[35]), "+f"(d[36]), "+f"(d[37]), "+f"(d[38]), "+f"(d[39]) : "l"(da), "l"(db), "r"(sc));
}
__device__ __forceinline__ void wgmma_ss8_ta(float (&d)[4], uint64_t da, uint64_t db, int sc) {
    asm volatile("{\n.reg .pred p;\nsetp.ne.b32 p, %6, 0;\n"
        "wgmma.mma_async.sync.aligned.m64n8k16.f32.bf16.bf16 {%0, %1, %2, %3}, %4, %5, p, 1, 1, 1, 0;\n}\n"
        : "+f"(d[0]), "+f"(d[1]), "+f"(d[2]), "+f"(d[3]) : "l"(da), "l"(db), "r"(sc));
}
__device__ __forceinline__ void wgmma_rs8(float (&d)[4], uint32_t a0, uint32_t a1, uint32_t a2, uint32_t a3, uint64_t db, int sc) {
    asm volatile("{\n.reg .pred p;\nsetp.ne.b32 p, %9, 0;\n"
        "wgmma.mma_async.sync.aligned.m64n8k16.f32.bf16.bf16 {%0, %1, %2, %3}, {%4, %5, %6, %7}, %8, p, 1, 1, 0;\n}\n"
        : "+f"(d[0]), "+f"(d[1]), "+f"(d[2]), "+f"(d[3]) : "r"(a0), "r"(a1), "r"(a2), "r"(a3), "l"(db), "r"(sc));
}
__device__ __forceinline__ void wgmma_rs128(float (&d)[64], uint32_t a0, uint32_t a1, uint32_t a2, uint32_t a3, uint64_t db, int sc) {
    asm volatile("{\n.reg .pred p;\nsetp.ne.b32 p, %69, 0;\n"
        "wgmma.mma_async.sync.aligned.m64n128k16.f32.bf16.bf16 {%0, %1, %2, %3, %4, %5, %6, %7, %8, %9, %10, %11, %12, %13, %14, %15, %16, %17, %18, %19, %20, %21, %22, %23, %24, %25, %26, %27, %28, %29, %30, %31, %32, %33, %34, %35, %36, %37, %38, %39, %40, %41, %42, %43, %44, %45, %46, %47, %48, %49, %50, %51, %52, %53, %54, %55, %56, %57, %58, %59, %60, %61, %62, %63}, {%64, %65, %66, %67}, %68, p, 1, 1, 1;\n}\n"
        : "+f"(d[0]), "+f"(d[1]), "+f"(d[2]), "+f"(d[3]), "+f"(d[4]), "+f"(d[5]), "+f"(d[6]), "+f"(d[7]), "+f"(d[8]), "+f"(d[9]), "+f"(d[10]), "+f"(d[11]), "+f"(d[12]), "+f"(d[13]), "+f"(d[14]), "+f"(d[15]), "+f"(d[16]), "+f"(d[17]), "+f"(d[18]), "+f"(d[19]), "+f"(d[20]), "+f"(d[21]), "+f"(d[22]), "+f"(d[23]), "+f"(d[24]), "+f"(d[25]), "+f"(d[26]), "+f"(d[27]), "+f"(d[28]), "+f"(d[29]), "+f"(d[30]), "+f"(d[31]), "+f"(d[32]), "+f"(d[33]), "+f"(d[34]), "+f"(d[35]), "+f"(d[36]), "+f"(d[37]), "+f"(d[38]), "+f"(d[39]), "+f"(d[40]), "+f"(d[41]), "+f"(d[42]), "+f"(d[43]), "+f"(d[44]), "+f"(d[45]), "+f"(d[46]), "+f"(d[47]), "+f"(d[48]), "+f"(d[49]), "+f"(d[50]), "+f"(d[51]), "+f"(d[52]), "+f"(d[53]), "+f"(d[54]), "+f"(d[55]), "+f"(d[56]), "+f"(d[57]), "+f"(d[58]), "+f"(d[59]), "+f"(d[60]), "+f"(d[61]), "+f"(d[62]), "+f"(d[63]) : "r"(a0), "r"(a1), "r"(a2), "r"(a3), "l"(db), "r"(sc));
}
__device__ __forceinline__ void wgmma_rs88(float (&d)[44], uint32_t a0, uint32_t a1, uint32_t a2, uint32_t a3, uint64_t db, int sc) {
    asm volatile("{\n.reg .pred p;\nsetp.ne.b32 p, %49, 0;\n"
        "wgmma.mma_async.sync.aligned.m64n88k16.f32.bf16.bf16 {%0, %1, %2, %3, %4, %5, %6, %7, %8, %9, %10, %11, %12, %13, %14, %15, %16, %17, %18, %19, %20, %21, %22, %23, %24, %25, %26, %27, %28, %29, %30, %31, %32, %33, %34, %35, %36, %37, %38, %39, %40, %41, %42, %43}, {%44, %45, %46, %47}, %48, p, 1, 1, 1;\n}\n"
        : "+f"(d[0]), "+f"(d[1]), "+f"(d[2]), "+f"(d[3]), "+f"(d[4]), "+f"(d[5]), "+f"(d[6]), "+f"(d[7]), "+f"(d[8]), "+f"(d[9]), "+f"(d[10]), "+f"(d[11]), "+f"(d[12]), "+f"(d[13]), "+f"(d[14]), "+f"(d[15]), "+f"(d[16]), "+f"(d[17]), "+f"(d[18]), "+f"(d[19]), "+f"(d[20]), "+f"(d[21]), "+f"(d[22]), "+f"(d[23]), "+f"(d[24]), "+f"(d[25]), "+f"(d[26]), "+f"(d[27]), "+f"(d[28]), "+f"(d[29]), "+f"(d[30]), "+f"(d[31]), "+f"(d[32]), "+f"(d[33]), "+f"(d[34]), "+f"(d[35]), "+f"(d[36]), "+f"(d[37]), "+f"(d[38]), "+f"(d[39]), "+f"(d[40]), "+f"(d[41]), "+f"(d[42]), "+f"(d[43]) : "r"(a0), "r"(a1), "r"(a2), "r"(a3), "l"(db), "r"(sc));
}
__device__ __forceinline__ void wgmma_rs128k(float (&d)[64], uint32_t a0, uint32_t a1, uint32_t a2, uint32_t a3, uint64_t db, int sc) {
    asm volatile("{\n.reg .pred p;\nsetp.ne.b32 p, %69, 0;\n"
        "wgmma.mma_async.sync.aligned.m64n128k16.f32.bf16.bf16 {%0, %1, %2, %3, %4, %5, %6, %7, %8, %9, %10, %11, %12, %13, %14, %15, %16, %17, %18, %19, %20, %21, %22, %23, %24, %25, %26, %27, %28, %29, %30, %31, %32, %33, %34, %35, %36, %37, %38, %39, %40, %41, %42, %43, %44, %45, %46, %47, %48, %49, %50, %51, %52, %53, %54, %55, %56, %57, %58, %59, %60, %61, %62, %63}, {%64, %65, %66, %67}, %68, p, 1, 1, 0;\n}\n"
        : "+f"(d[0]), "+f"(d[1]), "+f"(d[2]), "+f"(d[3]), "+f"(d[4]), "+f"(d[5]), "+f"(d[6]), "+f"(d[7]), "+f"(d[8]), "+f"(d[9]), "+f"(d[10]), "+f"(d[11]), "+f"(d[12]), "+f"(d[13]), "+f"(d[14]), "+f"(d[15]), "+f"(d[16]), "+f"(d[17]), "+f"(d[18]), "+f"(d[19]), "+f"(d[20]), "+f"(d[21]), "+f"(d[22]), "+f"(d[23]), "+f"(d[24]), "+f"(d[25]), "+f"(d[26]), "+f"(d[27]), "+f"(d[28]), "+f"(d[29]), "+f"(d[30]), "+f"(d[31]), "+f"(d[32]), "+f"(d[33]), "+f"(d[34]), "+f"(d[35]), "+f"(d[36]), "+f"(d[37]), "+f"(d[38]), "+f"(d[39]), "+f"(d[40]), "+f"(d[41]), "+f"(d[42]), "+f"(d[43]), "+f"(d[44]), "+f"(d[45]), "+f"(d[46]), "+f"(d[47]), "+f"(d[48]), "+f"(d[49]), "+f"(d[50]), "+f"(d[51]), "+f"(d[52]), "+f"(d[53]), "+f"(d[54]), "+f"(d[55]), "+f"(d[56]), "+f"(d[57]), "+f"(d[58]), "+f"(d[59]), "+f"(d[60]), "+f"(d[61]), "+f"(d[62]), "+f"(d[63]) : "r"(a0), "r"(a1), "r"(a2), "r"(a3), "l"(db), "r"(sc));
}
__device__ __forceinline__ void wgmma_rs88k(float (&d)[44], uint32_t a0, uint32_t a1, uint32_t a2, uint32_t a3, uint64_t db, int sc) {
    asm volatile("{\n.reg .pred p;\nsetp.ne.b32 p, %49, 0;\n"
        "wgmma.mma_async.sync.aligned.m64n88k16.f32.bf16.bf16 {%0, %1, %2, %3, %4, %5, %6, %7, %8, %9, %10, %11, %12, %13, %14, %15, %16, %17, %18, %19, %20, %21, %22, %23, %24, %25, %26, %27, %28, %29, %30, %31, %32, %33, %34, %35, %36, %37, %38, %39, %40, %41, %42, %43}, {%44, %45, %46, %47}, %48, p, 1, 1, 0;\n}\n"
        : "+f"(d[0]), "+f"(d[1]), "+f"(d[2]), "+f"(d[3]), "+f"(d[4]), "+f"(d[5]), "+f"(d[6]), "+f"(d[7]), "+f"(d[8]), "+f"(d[9]), "+f"(d[10]), "+f"(d[11]), "+f"(d[12]), "+f"(d[13]), "+f"(d[14]), "+f"(d[15]), "+f"(d[16]), "+f"(d[17]), "+f"(d[18]), "+f"(d[19]), "+f"(d[20]), "+f"(d[21]), "+f"(d[22]), "+f"(d[23]), "+f"(d[24]), "+f"(d[25]), "+f"(d[26]), "+f"(d[27]), "+f"(d[28]), "+f"(d[29]), "+f"(d[30]), "+f"(d[31]), "+f"(d[32]), "+f"(d[33]), "+f"(d[34]), "+f"(d[35]), "+f"(d[36]), "+f"(d[37]), "+f"(d[38]), "+f"(d[39]), "+f"(d[40]), "+f"(d[41]), "+f"(d[42]), "+f"(d[43]) : "r"(a0), "r"(a1), "r"(a2), "r"(a3), "l"(db), "r"(sc));
}
__device__ __forceinline__ void wgmma_rs80k(float (&d)[40], uint32_t a0, uint32_t a1, uint32_t a2, uint32_t a3, uint64_t db, int sc) {
    asm volatile("{\n.reg .pred p;\nsetp.ne.b32 p, %45, 0;\n"
        "wgmma.mma_async.sync.aligned.m64n80k16.f32.bf16.bf16 {%0, %1, %2, %3, %4, %5, %6, %7, %8, %9, %10, %11, %12, %13, %14, %15, %16, %17, %18, %19, %20, %21, %22, %23, %24, %25, %26, %27, %28, %29, %30, %31, %32, %33, %34, %35, %36, %37, %38, %39}, {%40, %41, %42, %43}, %44, p, 1, 1, 0;\n}\n"
        : "+f"(d[0]), "+f"(d[1]), "+f"(d[2]), "+f"(d[3]), "+f"(d[4]), "+f"(d[5]), "+f"(d[6]), "+f"(d[7]), "+f"(d[8]), "+f"(d[9]), "+f"(d[10]), "+f"(d[11]), "+f"(d[12]), "+f"(d[13]), "+f"(d[14]), "+f"(d[15]), "+f"(d[16]), "+f"(d[17]), "+f"(d[18]), "+f"(d[19]), "+f"(d[20]), "+f"(d[21]), "+f"(d[22]), "+f"(d[23]), "+f"(d[24]), "+f"(d[25]), "+f"(d[26]), "+f"(d[27]), "+f"(d[28]), "+f"(d[29]), "+f"(d[30]), "+f"(d[31]), "+f"(d[32]), "+f"(d[33]), "+f"(d[34]), "+f"(d[35]), "+f"(d[36]), "+f"(d[37]), "+f"(d[38]), "+f"(d[39]) : "r"(a0), "r"(a1), "r"(a2), "r"(a3), "l"(db), "r"(sc));
}
__device__ __forceinline__ void wgmma_rs64(float (&d)[32], uint32_t a0, uint32_t a1, uint32_t a2, uint32_t a3, uint64_t db, int sc) {
    asm volatile("{\n.reg .pred p;\nsetp.ne.b32 p, %37, 0;\n"
        "wgmma.mma_async.sync.aligned.m64n64k16.f32.bf16.bf16 {%0, %1, %2, %3, %4, %5, %6, %7, %8, %9, %10, %11, %12, %13, %14, %15, %16, %17, %18, %19, %20, %21, %22, %23, %24, %25, %26, %27, %28, %29, %30, %31}, {%32, %33, %34, %35}, %36, p, 1, 1, 1;\n}\n"
        : "+f"(d[0]), "+f"(d[1]), "+f"(d[2]), "+f"(d[3]), "+f"(d[4]), "+f"(d[5]), "+f"(d[6]), "+f"(d[7]), "+f"(d[8]), "+f"(d[9]), "+f"(d[10]), "+f"(d[11]), "+f"(d[12]), "+f"(d[13]), "+f"(d[14]), "+f"(d[15]), "+f"(d[16]), "+f"(d[17]), "+f"(d[18]), "+f"(d[19]), "+f"(d[20]), "+f"(d[21]), "+f"(d[22]), "+f"(d[23]), "+f"(d[24]), "+f"(d[25]), "+f"(d[26]), "+f"(d[27]), "+f"(d[28]), "+f"(d[29]), "+f"(d[30]), "+f"(d[31]) : "r"(a0), "r"(a1), "r"(a2), "r"(a3), "l"(db), "r"(sc));
}

__device__ __forceinline__ uint64_t mkdesc(uint32_t lo) { return ((uint64_t)0x40000040u << 32) | lo; }
template <int F> __device__ __forceinline__ uint32_t lop3(uint32_t a, uint32_t b, uint32_t c) { uint32_t r; asm("lop3.b32 %0, %1, %2, %3, %4;" : "=r"(r) : "r"(a), "r"(b), "r"(c), "n"(F)); return r; }
__device__ __forceinline__ void stg128_tag(void* p, uint32_t x, uint32_t y, uint32_t z, uint32_t u, uint32_t ep, int w) {
    stg128(p, lop3<0xB8>(x, w == 0, ep), lop3<0xB8>(y, w == 1, ep), lop3<0xB8>(z, w == 2, ep), lop3<0xB8>(u, w == 3, ep));
}
__device__ __forceinline__ uint32_t tag(uint32_t w, uint32_t ep) { asm("lop3.b32 %0, %0, 1, %1, 0xB8;" : "+r"(w) : "r"(ep)); return w; }
template <int N> __device__ __forceinline__ void pack_part(uint32_t (&p)[32], const float (&v)[N], uint32_t ep) {
#pragma unroll
    for (int i = 0; i < N / 2; i++) p[i] = (i & 3) ? pack2(v[2 * i], v[2 * i + 1]) : tag(pack2(v[2 * i], v[2 * i + 1]), ep);
#pragma unroll
    for (int i = 0; i < N / 2; i++) asm volatile("" : "+r"(p[i]));
}
__device__ __forceinline__ void st_part(uint4* p, const uint32_t* v) {
    asm volatile("{\n.reg .b64 l, h;\n.reg .b128 q;\nmov.b64 l, {%1, %2};\nmov.b64 h, {%3, %4};\nmov.b128 q, {l, h};\nst.relaxed.gpu.global.b128 [%0], q;\n}"
                 ::"l"(p), "r"(v[0]), "r"(v[1]), "r"(v[2]), "r"(v[3]) : "memory");
}
__device__ __forceinline__ void st_peer(uint32_t a, uint32_t x, uint32_t y, uint32_t z, uint32_t w, uint32_t bar) {
    asm volatile("st.async.shared::cluster.mbarrier::complete_tx::bytes.v4.b32 [%0], {%1, %2, %3, %4}, [%5];" ::"r"(a), "r"(x), "r"(y), "r"(z), "r"(w), "r"(bar) : "memory");
}
__device__ __forceinline__ int g4_block(int c, int j) { return c ? j ^ (8 - 2 * c) : 8 + (j & 1); }
__device__ __forceinline__ uint32_t recv_off(int w) { return w ? OFF_XR : OFF_REM; }
__device__ __forceinline__ uint4 ld_part(const void* p) {
    uint4 v;
    asm volatile("{\n.reg .b64 l, h;\n.reg .b128 q;\nld.relaxed.gpu.global.b128 q, [%4];\nmov.b128 {l, h}, q;\nmov.b64 {%0, %1}, l;\nmov.b64 {%2, %3}, h;\n}"
                 : "=r"(v.x), "=r"(v.y), "=r"(v.z), "=r"(v.w) : "l"(p) : "memory");
    return v;
}
__device__ __forceinline__ void ld_part4(uint4 (&u)[4], const uint4* p, int st) {
#pragma unroll
    for (int i = 0; i < 4; i++) u[i] = ld_part(p + i * st);
}
__device__ __forceinline__ uint32_t stale4(const uint4 (&u)[4], uint32_t ep) { return lop3<0x7E>(u[0].x, ep, u[1].x) | lop3<0x7E>(u[2].x, ep, u[3].x); }
__device__ __forceinline__ uint4 add2(uint4 a, uint4 b) { return make_uint4(add2(a.x, b.x), add2(a.y, b.y), add2(a.z, b.z), add2(a.w, b.w)); }
__device__ __forceinline__ uint4 fin16(uint4 v, uint4 b, uint32_t c, uint32_t d) { return make_uint4(fma2(c, v.x, b.x), fma2(c, v.y, b.y), fma2(d, v.z, b.z), fma2(d, v.w, b.w)); }
__device__ __forceinline__ uint32_t ld_gb(uint32_t sb, int i, int t) { const float2 c = lds64f(sb + M_GB + (8 * i + 2 * t) * 4); return pack2(c.x, c.y); }
__device__ __forceinline__ uint32_t split2(float x) { const float h = rbf(x); return pack2(h, x - h); }
__device__ __forceinline__ uint32_t b80_desc(uint32_t dsb, uint32_t wn, uint32_t rn, uint32_t h) {
    const uint32_t wb = dsb + OFF_W + (wn & 7) * 16384 + h * 8192, rm = dsb + OFF_REM + rn * 4096 + h * 2048;
    return (wb >> 4) | ((rm - wb) << 12);
}
constexpr int64_t B80_STEP = 128 - (126 << 16), B80_HALF = 512 - (384 << 16);
constexpr uint32_t ring_mask(int L) {
    uint32_t m = 0;
    for (int i = L; i < 20; i++) m |= (uint32_t)(i >= 20 - L || !((i - L) & 1)) << i;
    return m;
}
constexpr uint32_t M0 = ring_mask(LEAD1), M1 = ring_mask(10), M2 = ring_mask(XLEAD);
__device__ __forceinline__ uint32_t ring_pos(int w, int n, int L) { return w ? (n < 10 - L ? L + 2 * n : 10 + n) : (n < L ? n : 2 * n - L + 1); }
__device__ __forceinline__ int g1_block(int n, int j) { return n < 5 ? 2 * n + (j & 1) : 2 * n - 9 - (j & 1); }

__device__ __forceinline__ void load_tile(const Maps& mp, uint32_t dst, int e, int tile, int kb, int j, uint32_t bar) {
    mbar_expect(bar, 8192);
    tma_ld2(dst, &mp.x[e], 64 * (e == 0 ? tile : e == 1 ? kb : 0), 64 * (e == 0 ? g1_block(kb, j) : e == 1 ? tile : 10 * tile + kb), bar);
}

template <int OCT>
__device__ __forceinline__ void gemv_tile(float (&d)[4], uint32_t a, uint32_t b, int kb0) {
    uint32_t alo = ((a & 0x3FFFF) >> 4) | 0x10000u, blo_ = ((b & 0x3FFFF) >> 4) | (OCT << 16);
#pragma unroll 1
    for (int s = 0; s < 20; s += 4) {
        const int kb = kb0 + (s >> 2);
        const uint32_t bk = blo_ + (OCT == 7 ? (kb & 1) * 288 + (kb >> 1) * 56 : kb * 64);
        wg_fence();
#pragma unroll
        for (int q = 0; q < 4; q++) wgmma_ss8_ta(d, mkdesc(alo + (s + q) * 128), ((uint64_t)8 << 32) | (bk + q * 2 * OCT), s + q);
        wg_commit();
    }
    wg_wait<0>();
    reg_fence(d);
}

__device__ __forceinline__ void flush_tile(uint32_t st, bf16* dst, int u) {
#pragma unroll
    for (int i = 0; i < 2; i++) {
        const int idx = u + 320 * i, row = idx >> 3, c = idx & 7;
        stg128(dst + (size_t)row * S_ + 8 * c, lds128(st + row * 128 + ((c ^ ((row >> 1) & 7)) << 4)));
    }
}

__device__ __forceinline__ int tid_now() { int t; asm volatile("mov.u32 %0, %%tid.x;" : "=r"(t)); return t; }
__device__ __forceinline__ float zscale(float c) { return c == 0.f ? 0x1p-30f : c; }
__device__ __forceinline__ bool bar_any(int id, bool p) {
    uint32_t r;
    asm volatile("{\n.reg .pred a, b;\nsetp.ne.u32 a, %2, 0;\nbarrier.red.or.pred.aligned b, %1, 128, a;\nselp.u32 %0, 1, 0, b;\n}" : "=r"(r) : "r"(id), "r"((uint32_t)p) : "memory");
    return r != 0;
}

__global__ void __cluster_dims__(2, 1, 1) __launch_bounds__(NTHR, 1) fused_kernel(const __grid_constant__ Ptrs pp, bf16* __restrict__ out, const __grid_constant__ Maps mp) {
    extern __shared__ __align__(1024) uint8_t smem_raw[];
    const uint32_t sb = s2u(smem_raw), bars = sb + M_BAR, dsb = sb & 0x3FFFF;
    const int id = blockIdx.x, warp = __shfl_sync(0xffffffffu, (int)threadIdx.x >> 5, 0), wg = warp >> 2;
    const uint32_t c0 = clock_lo();
#define TIDS const int tid = tid_now(), lane = tid & 31, wt = tid & 127, g = lane >> 2, t = lane & 3; (void)wt; (void)g; (void)t;
    TS(threadIdx.x == 0, 0) TG(threadIdx.x == 0, 62)

    if (id >= 128) {
        TIDS
        if (sb & 1023) __trap();
        const int hs = id - 128;
        constexpr int H_B = 204800;
        static_assert(H_B + TAB_BYTES + 8 * VEC_BYTES <= OFF_M, "helper map");
        if (warp < 10 && elect()) { mbar_init(bars + warp * 8, 1); mbar_init(bars + 80 + warp * 8, 1); asm volatile("fence.mbarrier_init.release.cluster;" ::: "memory"); }
        __syncthreads();
        const uint32_t e0 = ld_cold(&g_epoch);
        wait_clock(c0, HELP_T);
        uint4 wr[10];
#pragma unroll
        for (int u = 0; u < 10; u++) wr[u] = ldg128(((hs >> 1) ? pp.w2 : pp.w1) + (size_t)(320 * (hs & 1) + (tid >> 4) + 32 * u) * D_ + 512 + 8 * (tid & 15));
        {
            const int r = tid >> 4, c = tid & 15;
            uint4* dst[2];
#pragma unroll
            for (int e = 0; e < 2; e++) {
                const int p = !(hs >> 1) ? r : e && (hs & 1) ? (r & ~14) | ((r & 6) << 1) | ((r & 8) >> 2) : (r & ~30) | ((r & 6) << 2) | ((r & 24) >> 2);
                dst[e] = &g_wr[(((hs >> 1) * 8 + (c >> 1)) * 10 + 5 * (hs & 1)) * 128 + (p & 15) * 8 + ((2 * (p >> 4) + (c & 1)) ^ (p & 7))];
            }
#pragma unroll
            for (int u = 0; u < 10; u++) stg128(reinterpret_cast<uint4*>(reinterpret_cast<uintptr_t>(dst[u >= 6]) ^ (64 * (u & 1))) + (u >> 1) * 128, wr[u]);
        }
        __syncthreads();
        if (warp == 0) signal_cnt(&g_cnt.wr[0], lane, 1);
        __syncthreads();
        if (warp < 5 && elect()) {
            const int un = 5 * hs + warp;
            mbar_expect(bars + warp * 8, 40960);
            tma_ld2(sb + warp * 40960, &mp.w1h, 64 * (un >> 1), 320 * (un & 1), bars + warp * 8);
            tma_ld2(sb + warp * 40960 + 20480, &mp.w1h, 64 * (un >> 1), 320 * (un & 1) + 160, bars + warp * 8);
        }
        if (tid < 320) {
            const uint4* gm = reinterpret_cast<const uint4*>(g_mod + 3 * D_) + tid;
            const unsigned epoch = e0 + 1;
            uint4 r[6];
            unsigned it = 0;
            for (;;) {
                uint32_t bad = 0;
#pragma unroll
                for (int i = 0; i < 6; i++) { r[i] = ld_part(gm + (i >> 1) * (D_ / 2) + (i & 1) * 3 * D_); bad |= (r[i].y ^ epoch) | (r[i].w ^ epoch); }
                if (__all_sync(~0u, !bad)) break;
                if (++it > SPIN_LIMIT) SPIN_FAIL(54)
            }
            uint32_t mv[3];
#pragma unroll
            for (int i = 0; i < 3; i++) mv[i] = pack2(__uint_as_float(r[2 * i].x) + __uint_as_float(r[2 * i + 1].x), __uint_as_float(r[2 * i].z) + __uint_as_float(r[2 * i + 1].z));
            const uint32_t sw2 = mv[0], cw = add2(mv[1], 0x3f803f80u), gw = mv[2];
            const float c0 = blo(cw), c1 = bhi(cw), s0 = blo(sw2), s1 = bhi(sw2);
            const float i0 = __frcp_rn(zscale(c0)), i1 = __frcp_rn(zscale(c1));
            const uint32_t ci = pack2(i0, i1), cq = pack2(i0 * i0, i1 * i1);
            const uint32_t a = sb + H_B + ((tid >> 5) & 1) * 4608 + (tid >> 6) * 896 + ((tid >> 2) & 7) * 112 + (tid & 3) * 4;
            sts32(a, ci); sts32(a + 16, pack2(i0 - blo(ci), i1 - bhi(ci)));
            sts32(a + 32, cq); sts32(a + 48, pack2(fmaf(i0, i0, -blo(cq)), fmaf(i1, i1, -bhi(cq))));
            sts32(a + 64, cw); sts32(a + 80, sw2); sts32(a + 96, 0x3f803f80u);
            if ((tid & ~35) == 284) sts32(a + 112, 0);
            const uint32_t v = sb + H_B + TAB_BYTES + (tid < 256 ? (tid >> 5) * VEC_BYTES + (tid & 31) * 8 : ((tid - 256) >> 3) * VEC_BYTES + 256 + (tid & 7) * 8);
            sts64f(v, blo(gw), bhi(gw)); sts64f(v + 320, c0, c1); sts64f(v + 640, s0, s1); sts64f(v + 960, i0, i1);
            float k[5] = {c0 + c1, s0 + s1, fmaf(c0, c0, c1 * c1), fmaf(c0, s0, c1 * s1), fmaf(s0, s0, s1 * s1)};
#pragma unroll 1
            for (int o = 16; o; o >>= 1) {
#pragma unroll
                for (int e = 0; e < 5; e++) k[e] += __shfl_xor_sync(~0u, k[e], o);
            }
            const uint32_t ks = sb + H_B + TAB_BYTES + (lane & 7) * VEC_BYTES + 1280 + (warp >> 1) * 32;
            if ((warp & 1) && lane < 8) { sts128f(ks, k[0], k[1], k[2], k[3]); sts128f(ks + 16, k[4], 0.f, 0.f, 0.f); }
            bar_sync(3, 320);
            if (!(warp & 1) && lane < 8) {
                const float4 o = lds128f(ks);
                sts128f(ks, k[0] + o.x, k[1] + o.y, k[2] + o.z, k[3] + o.w); sts32(ks + 16, __float_as_uint(k[4] + __uint_as_float(lds32(ks + 16))));
            }
            fence_async_smem();
        }
        __syncthreads();
        if (hs == 0 && warp == 15 && elect()) {
            asm volatile("cp.async.bulk.global.shared::cta.bulk_group [%0], [%1], %2;\ncp.async.bulk.commit_group;\ncp.async.bulk.wait_group 0;"
                         ::"l"(g_tab), "r"(sb + H_B), "n"(TAB_BYTES + 8 * VEC_BYTES) : "memory");
            asm volatile("red.release.gpu.global.add.u32 [%0], 1;" ::"l"(&g_cnt.tab[0]) : "memory");
        }
        __syncwarp();
#pragma unroll 1
        for (int i = wg; i < 20; i += 4) {
            const int r = i / 5, b = i - 5 * r, un = 5 * hs + b, u3 = 20 * r + un;
            auto refill = [&](int e, int u, uint32_t fb) {
                mbar_expect(fb, 40960);
                tma_ld2(sb + e * 40960, &mp.w3h, 64 * (u >> 1), 320 * (u & 1), fb);
                tma_ld2(sb + e * 40960 + 20480, &mp.w3h, 64 * (u >> 1), 320 * (u & 1) + 160, fb);
            };
            if (i > 4 && i < 9) {
                bar_sync(1, 512);
                if (warp == 0) {
                    signal_cnt(&g_cnt.uv[0], lane, 1);
                    if (elect()) {
#pragma unroll 1
                        for (int e = 0; e < 5; e++) refill(e, 5 * hs + e, bars + (5 + e) * 8);
                        l2_prefetch(pp.w2 + (size_t)160 * hs * D_, 160 * D_ * 2);
                    }
                    __syncwarp();
                }
            }
            mbar_wait(bars + i * 8, 0);
            float d[4];
            gemv_tile<7>(d, sb + b * 40960, sb + H_B, 5 * (un & 1));
            const int col = 16 * (warp & 3) + g;
            float* dst = r ? g_cs3 + (un & 1) * 1920 + 64 * ((u3 >> 1) - 10) + col : g_uv + (un & 1) * 3 * D_ + 2 * D_ + 64 * (un >> 1) + col;
            if (t == 3) { dst[0] = d[0]; dst[8] = d[2]; }
            if (r == 0 && t == 2) { dst[-2 * D_] = d[0]; dst[8 - 2 * D_] = d[2]; dst[-D_] = d[1]; dst[8 - D_] = d[3]; }
            if (r == 1 || r == 2) {
                bar_sync(4 + wg, 128);
                if (wt == 0) refill(b, u3, bars + (i + 5) * 8);
            }
        }
        __syncthreads();
        if (warp == 0) signal_cnt(&g_cnt.cs[0], lane, 1);
        if (tid == 511) l2_prefetch(pp.w4 + (size_t)432 * hs * D_, 432 * D_ * 2);
        for (uint32_t it = 0; ld_cold(&g_cnt.cs[0]) < 4;) { if (++it > SPIN_LIMIT) SPIN_FAIL(47) }
        asm volatile("fence.acquire.gpu;" ::: "memory");
        if (tid < 432) {
            const int jj = 2 * hs + (tid >= 216), c = tid % 216;
            const float* src = g_cs3 + (c < 192 ? 192 * jj + c : 1344 + 24 * jj + c);
            const uint32_t s = split2(ldcg32f(src) + ldcg32f(src + 1920));
            stg128(&g_cs3b[432 * hs + tid], s, s & 0xffffu, 0, 0);
        }
        __syncthreads();
        if (warp == 0) signal_cnt(&g_cnt.cs2[0], lane, 1);
        if (tid == 0 && hs == 3) {
            uint32_t it = 0;
            while (ld_cold(&g_epoch) == e0) { __nanosleep(256); if (++it > (1u << 20)) SPIN_FAIL(48) }
        }
        return;
    }

    if (elect()) {
        if (warp == 15) {
            mbar_init(bars + B_IN * 8, 1); mbar_init(bars + B_IN * 8 + 8, 1);
            asm volatile("fence.mbarrier_init.release.cluster;" ::: "memory");
            mbar_expect(bars + B_IN * 8, 131 * 160);
            tma_ld2(sb + OFF_KIN, &mp.k, 80 * (id & 7), 64 * (id >> 3) - 3, bars + B_IN * 8);
            tma_ld2(sb + OFF_VIN, &mp.v, 80 * (id & 7), 64 * (id >> 3), bars + B_IN * 8);
        } else if (warp < 13) {
            const uint32_t n = (0x1C14111111881ull >> (4 * warp)) & 15;
#pragma unroll
            for (int i = 0; i < 4; i++) mbar_init(bars + warp * 64 + i * 8, n);
            if (warp == 11) { mbar_init(bars + B_XFREE * 8, 16); mbar_init(bars + B_OWN * 8, 8); }
            else if (warp < 11) {
#pragma unroll
                for (int i = 4; i < 8; i++) mbar_init(bars + warp * 64 + i * 8, n);
            }
            asm volatile("fence.mbarrier_init.release.cluster;" ::: "memory");
        }
    }
    asm volatile("" ::"l"(pp.s), "l"(pp.c), "l"(out));
    TR4((threadIdx.x & 31) == 0, warp)
    const int pr = id >> 1;
    const int grp = pr < 4 ? 15 : pr < 36 ? (pr - 4) & 7 : 8 + (pr - 36) % 7;
    const int j = 2 * (pr < 4 ? pr : pr < 36 ? (pr - 4) >> 3 : (pr - 36) / 7) + (id & 1);

    if (wg == 3) {
        TIDS
        const int sw = warp - 12;
        uint32_t ep = ld_cold(&g_epoch);
        TR4(lane == 0, 20 + sw)
        __syncthreads();
        TR4(lane == 0, 30 + sw)
        asm volatile("barrier.cluster.arrive.relaxed.aligned;" ::: "memory");
        if (sw == 0) {
#pragma unroll 1
            for (int n = 0; n < 12; n++) {
                wait_clock(c0, PF_T0 + PF_DT * n);
                if (elect()) l2_prefetch(n < 4 ? (const char*)pp.q + id * 20480 + n * 5120 : (const char*)pp.w_mod + id * 38400 + (n - 4) * 4800, n < 4 ? 5120 : 4800);
            }
        } else if (sw == 1) {
            wait_clock(c0, T_SSM);
            if (elect()) {
                mbar_expect(bars + B_SSM * 8, 20480);
                bulk_ld(sb + OFF_SSM, pp.ssm_k + (size_t)5 * id * S_, 20480, bars + B_SSM * 8);
            }
            mbar_spin(bars + B_KVS * 8, 0);
            signal_cnt(&g_cnt.kv[(id & 7) * 32], lane, 1, true);
            TS(lane == 0, 2)
            mbar_spin(bars + B_RAW * 8, 0);
            if (elect()) {
                mbar_expect(bars + B_QIN * 8, 20480);
                tma_ld3(sb + OFF_QIN, &mp.q, 0, 16 * id, 0, bars + B_QIN * 8);
            }
        } else if (sw == 2) {
            if (elect()) {
#pragma unroll 1
                for (int i = 2; i < (int)(sizeof(Maps) / sizeof(CUtensorMap)); i++) asm volatile("prefetch.tensormap [%0];" ::"l"(&mp.k + i) : "memory");
#pragma unroll 1
                for (int i = B_SUMS; i < B_SIG; i++) mbar_expect(bars + i * 8, i < B_RECV ? 2048 : (i & 3) < 3 ? 8192 : 3072);
            }
            wait_cnt(&g_cnt.kv[(id >> 4) * 32], 16, true);
            TS(lane == 0, 4)
            if (elect()) {
                mbar_expect(bars + B_RAW * 8, 12288);
                mbar_expect(bars + B_RAW2 * 8, 8192);
#pragma unroll
                for (int c = 0; c < 5; c++) bulk_ld(sb + OFF_CH + c * CH_BYTES, g_kvT + (size_t)(5 * id + c) * S_, 4096, bars + (c < 3 ? B_RAW : B_RAW2) * 8);
            }
            mbar_spin(bars + B_BK * 8, 0);
            mbar_spin(bars + B_QIN * 8, 0);
            if (id < 120 && elect()) {
                mbar_expect(bars + B_WM * 8, 40960);
                tma_ld2(sb + OFF_WM, &mp.wmod, 64 * pr, 320 * (id & 1), bars + B_WM * 8);
                tma_ld2(sb + OFF_WM + 20480, &mp.wmod, 64 * pr, 320 * (id & 1) + 160, bars + B_WM * 8);
            }
            TS(lane == 0, 57)
        } else {
            wait_clock(c0, T_KVB);
            if (elect()) {
                mbar_expect(bars + (B_IN + 1) * 8, 131 * 160);
                tma_ld2(sb + OFF_KIN + 10752, &mp.k, 80 * (id & 7), 64 * (id >> 3) + 1021, bars + (B_IN + 1) * 8);
                tma_ld2(sb + OFF_VIN + 10240, &mp.v, 80 * (id & 7), 64 * (id >> 3) + 1024, bars + (B_IN + 1) * 8);
            }
            TS(lane == 0, 53)
            if (lane == 0) sts32(sb + M_EP, ep + 1);
            sts32(sb + M_NUL + lane * 4, 0);
#pragma unroll 1
            for (int i = 0; i < 10; i++) sts128(sb + OFF_Z + i * 512 + lane * 16, 0, 0, 0, 0);
            __syncwarp();
#pragma unroll 1
            for (int i = lane; i < 160; i += 32) {
                const uint32_t c = ldg32(pp.c + 320 * (id & 1) + 2 * i);
                sts32(sb + OFF_Z + (i >> 2) * 128 + (i & 3) * 4, pack2(silu(blo(c)), silu(bhi(c))));
            }
            fence_async_smem();
            for (uint32_t ph = 0, again = 1; again; ph ^= 1) {
                mbar_spin(bars + B_RAW2 * 8, ph);
                uint32_t bad = 0;
#pragma unroll
                for (int i = 0; i < 8; i++) bad |= lop3<0x7E>(lds32(sb + OFF_CH + 3 * CH_BYTES + i * 512 + lane * 16), ~ep, lds32(sb + OFF_CH + 4 * CH_BYTES + i * 512 + lane * 16));
                again = __any_sync(~0u, bad & 1);
                if (again && elect()) {
                    mbar_expect(bars + B_RAW2 * 8, 8192);
#pragma unroll
                    for (int c = 3; c < 5; c++) bulk_ld(sb + OFF_CH + c * CH_BYTES, g_kvT + (size_t)(5 * id + c) * S_, 4096, bars + B_RAW2 * 8);
                }
            }
            if (elect()) mbar_arrive(bars + B_RAW3 * 8);
        }
        {
            mbar_spin(bars + B_QIN * 8, 0);
            asm volatile("add.u32 %0, %0, 1;" : "+r"(ep));
            TS(wt == 0, 54)
            const int tk = 8 * ((lane >> 1) & 1) + 2 * (lane >> 3) + (lane & 1), ck = 4 * (sw & 1) + ((lane >> 1) & 2);
            const uint32_t src = sb + OFF_QIN + (sw >> 1) * 2048 + tk * 128;
            bf16* dst = g_qT + (size_t)id * 16 * D_ + (32 * sw + 8 * (t & 2) + g) * 16 + 8 * (t & 1);
constexpr int QU = Q_UNROLL;
#pragma unroll QU
            for (int i = 0; i < 5; i++) {
                uint32_t r[8];
                ldsm4t(src + i * 4096 + ((ck ^ (tk & 7)) << 4), r[0], r[1], r[2], r[3]);
                ldsm4t(src + i * 4096 + (((ck + 1) ^ (tk & 7)) << 4), r[4], r[5], r[6], r[7]);
                stg128(dst + i * 2048, tag(r[0], ep), r[1], r[2], r[3]);
                stg128(dst + i * 2048 + 128, tag(r[4], ep), r[5], r[6], r[7]);
            }
            float s1 = 0.f, s2 = 0.f;
#pragma unroll 2
            for (int i = 0; i < 10; i++) {
                const uint4 w4 = lds128(sb + OFF_QIN + i * 2048 + wt * 16);
                const uint32_t w[4] = {w4.x, w4.y, w4.z, w4.w};
#pragma unroll
                for (int e = 0; e < 4; e++) { const float a = blo(w[e]), b = bhi(w[e]); s1 += a + b; s2 = fmaf(a, a, fmaf(b, b, s2)); }
            }
#pragma unroll
            for (int o = 1; o < 8; o *= 2) { s1 += __shfl_xor_sync(~0u, s1, o); s2 += __shfl_xor_sync(~0u, s2, o); }
            s1 *= 1.f / D_;
            uint32_t rs = pack2(rsqrtf(fmaxf(s2 * (1.f / D_) - s1 * s1, 0.f) + 1e-5f), 0.f);
            if (lane < 8) rs = tag(rs, ep);
            rs = pack2(blo(rs), -s1 * blo(rs));
            const uint32_t sel = lane ? 0x7632 : 0x5410;
            const uint32_t a0 = __shfl_sync(~0u, rs, 0), a1 = __shfl_sync(~0u, rs, 8), a2 = __shfl_sync(~0u, rs, 16), a3 = __shfl_sync(~0u, rs, 24);
            if (lane < 2) stg64(g_qst + lane * S_ + 16 * id + 4 * sw, tag(__byte_perm(a0, a1, sel), ep), __byte_perm(a2, a3, sel));
            TS(wt == 0, 55)
        }
        bar_sync(6, 128);
        if (sw == 3) {
            signal_cnt(&g_cnt.q[(lane & 3) * 32], lane, 4, true);
            TS(lane == 0, 3)
        }
        asm volatile("setmaxnreg.dec.sync.aligned.u32 32;");
        asm volatile("barrier.cluster.wait.aligned;" ::: "memory");
        if (sw == 1) {
            mbar_spin(bars + B_XS * 8, 0);
            signal_cnt(&g_cnt.x[(lane & 3) * 32], lane, 4, true);
            TS(lane == 0, 20)
#pragma unroll 1
            for (int e = 1; e < 3; e++) {
                wait_cnt(e == 1 ? &g_cnt.g1[min(grp + 15 + min(lane, 2), 31) * 32] : &g_cnt.g2[(grp + 16) * 32], 32, true);
                if (elect()) mbar_arrive(bars + (B_GATE + 2 + e) * 8);
                TS(lane == 0, 27 + 2 * e)
            }
            return;
        }
        if (sw == 2) {
            mbar_spin(bars + B_XS * 8, 0);
            fence_async_smem();
            const unsigned* flag = &g_cnt.x[(id & 3) * 32];
            uint32_t m = 0;
            int n = 0, a0 = 0, a1 = 0;
            uint32_t k = 0;
#pragma unroll 1
            for (int s = 0; s < 6; s++) {
                const int e = s >> 1, end = 20 * e + ((s & 1) ? 20 : e == 0 ? LEAD1 : e == 1 ? 10 : XLEAD);
                if (s & 1) mbar_spin(bars + (B_GATE + 2 + e) * 8, !e);
                else {
                    wait_cnt(flag, e ? 32 : 128, true);
                    flag = e ? &g_cnt.g2[grp * 32] : &g_cnt.g1[max(grp - 1 + min(lane, 2), 0) * 32];
                    m = e == 0 ? M0 : e == 1 ? M1 : M2;
                    k = e ? 0 : (j & 1) * 0x400040;
                    a0 = e ? 0 : 64 * grp; a1 = e == 0 ? 0 : e == 1 ? 64 * grp : 640 * grp;
                    TS(lane == 0, 26 + 2 * e)
                }
                const int b0 = e ? 0 : 1024, b1 = e == 0 ? 0 : e == 1 ? 1024 : 10240, step = e ? 64 : 128;
                const uint32_t turn = e ? 1 : 512 + 64 * (j & 1), back = -448 - 128 * (j & 1);
#pragma unroll 1
                for (; n < end; n++, m >>= 1) {
                    const uint32_t w = m & 1, sh = 16 * w, kc = (k >> sh) & 0xffff;
                    k += (kc == turn ? back : step) << sh;
                    const uint32_t fb = bars + (B_LAND + (n & 7)) * 8;
                    mbar_spin(fb - (B_LAND - B_XEMPTY) * 8, ((n >> 3) & 1) ^ 1);
                    TR2(lane == 0 && n < 40, 20 + n)
                    if (elect()) {
                        mbar_expect(fb, 8192);
                        tma_ld2(sb + OFF_XR + (n & 7) * 8192, &mp.x[e], a0 + w * b0 + (e == 1 ? kc : 0), a1 + w * b1 + (e == 1 ? 0 : kc), fb);
                    }
                }
            }
            mbar_spin(bars + B_VEC3 * 8, 0);
            unsigned old = 0;
            asm volatile("{\n.reg .pred P;\nsetp.eq.s32 P, %2, 0;\n@P atom.relaxed.gpu.global.add.u32 %0, [%1], %3;\n}" : "+r"(old) : "l"(&g_cnt.done[0]), "r"(lane), "r"(1) : "memory");
            if (__any_sync(~0u, old == 127)) {
#pragma unroll 1
                for (int i = lane; i < (int)(sizeof(Counters) / 128); i += 32) reinterpret_cast<unsigned*>(&g_cnt)[i * 32] = 0;
                signal_cnt(&g_epoch, lane, 1, true);
            }
        } else if (sw == 0) {
            wait_cnt(&g_cnt.wr[0], 4);
            mbar_spin(bars + B_QRDY * 8, 0);
            const uint32_t wf = bars + B_WFULL * 8, we = bars + B_WEMPTY * 8;
#pragma unroll 1
            for (int n = 0; n < 5; n++) {
                if (n == 3) { mbar_spin(bars + B_XS * 8, 0); fence_async_smem(); }
                TR2(lane == 0, 70 + n)
                if (elect()) {
                    const uint32_t fb = wf + n * 8, dst = sb + OFF_W + n * 16384;
                    mbar_expect(fb, 20480);
#pragma unroll 1
                    for (int h = 0; h < 2; h++) {
                        const int kb = g1_block(2 * n + h, j);
                        tma_ld2(dst + h * 8192, &mp.w1, 64 * j, 64 * kb, fb);
                        bulk_ld(sb + OFF_REM + n * 4096 + h * 2048, &g_wr[(j * 10 + kb) * 128], 2048, fb);
                    }
                }
            }
            mbar_spin(bars + B_GATE * 8, 0);
#pragma unroll 1
            for (int i = -3; i < 5; i++) {
                const int n = i < 0 ? 8 + i : 5 + i;
                const uint32_t fb = wf + (n & 7) * 8;
                if (i >= 0) mbar_spin(we + i * 8, 0);
                TR2(lane == 0 && i >= 0, 70 + n)
                if (elect()) {
                    if (i < 0 || i >= 3) { mbar_expect(fb, 20480); tma_ld5(sb + OFF_W + (n & 7) * 16384, n < 9 ? &mp.w2a : &mp.w2b, 64 * j, n < 9 ? 4 * (n - 5) : 0, fb); }
                    if (i >= 0) bulk_ld(sb + OFF_REM + i * 4096, &g_wr[((8 + j) * 10 + 2 * i) * 128], 4096, fb);
                }
            }
            mbar_spin(bars + (B_GATE + 1) * 8, 0);
#pragma unroll 1
            for (int n = 10; n < 30; n++) {
                if (n == W3_N2) mbar_spin(bars + (B_GATE + 2) * 8, 0);
                mbar_spin(we + (n & 7) * 8, ((n >> 3) & 1) ^ 1);
                TR2(lane == 0, 70 + n)
                if (elect()) {
                    const uint32_t dst = sb + OFF_W + (n & 7) * 16384, fb = wf + (n & 7) * 8;
                    mbar_expect(fb, 13824);
                    tma_ld3(dst, &mp.w3a, 0, 32 * (n - 10), 3 * j, fb);
                    tma_ld2(dst + 12288, &mp.w3b, 1536 + 24 * j, 32 * (n - 10), fb);
                }
            }
            mbar_spin(we + 6 * 8, 0);
            mbar_spin(bars + B_VEC3 * 8, 0);
            if (elect()) { mbar_expect(wf + 6 * 8, 3456); bulk_ld(sb + OFF_W + 6 * 16384, &g_cs3b[216 * j], 3456, wf + 6 * 8); }
#pragma unroll 1
            for (int n = 31; n < 50; n++) {
                const int e = n < 38 ? 4 : (n - 38) & 3, m0 = n == 35, m1 = e == 3 ? -1 : m0 | (e == 1), rem = 96 + 3 * (j >> 1);
                const int c1_ = j ^ (n < 38 ? 6 : 4 >> ((n - 38) >> 2) & 6), c0_ = n < 38 ? 8 + (j & 1) : c1_;
                const int f = (0xC840A80C204ull >> (4 * min(n - 31, e + 7))) & 15;
                const int r0 = m0 ? rem : 6 * (j ^ (f >> 3)) + (f & 6), r1 = m1 ? rem : r0 + (n < 38 ? 0 : 2);
                mbar_spin(we + (n & 7) * 8, ((n >> 3) & 1) ^ 1);
                if (elect()) {
                    const uint32_t dst = sb + OFF_W + (n & 7) * 16384, fb = wf + (n & 7) * 8;
                    mbar_expect(fb, m1 < 0 ? 8192 : 16384 - 2048 * (m0 + m1));
                    tma_ld2(dst, &mp.w4[m0], 64 * c0_, r0 * (32 >> m0), fb);
                    if (m1 >= 0) tma_ld2(dst + 8192, &mp.w4[m1], 64 * c1_, r1 * (32 >> m1), fb);
                }
            }
        } else {
            {
                wait_cnt(&g_cnt.tab[0], 1);
                mbar_spin(bars + B_QRDY * 8, 0);
                if (elect()) {
                    mbar_expect(bars + B_TAB * 8, TAB_BYTES / 2 + VEC_BYTES);
                    bulk_ld(sb + OFF_TAB, g_tab + (j & 1) * (TAB_BYTES / 32), TAB_BYTES / 2, bars + B_TAB * 8);
                    bulk_ld(sb + M_GB, g_tab + (TAB_BYTES + j * VEC_BYTES) / 16, VEC_BYTES, bars + B_TAB * 8);
                }
                TS(lane == 0, 5)
            }
            wait_cnt(&g_cnt.uv[0], 4);
#pragma unroll 1
            for (int c = lane; c < 80; c += 32) {
                const float* src = g_uv + (c < 64 ? 64 * j + c : 448 + 16 * j + c);
                const uint32_t u = split2(ldcg32f(src) + ldcg32f(src + 3 * D_)), v = split2(ldcg32f(src + D_) + ldcg32f(src + 4 * D_));
                const uint32_t s = split2(ldcg32f(src + 2 * D_) + ldcg32f(src + 5 * D_));
                sts128(sb + OFF_F1 + c * 16, u, __byte_perm(u, v, 0x5410), __byte_perm(v, 0, 0x1032), s);
                sts128(sb + M_F1 + c * 16, s & 0xffffu, 0, 0, 0);
            }
            fence_async_smem();
            warp_arrive(bars + B_VEC * 8);
            TS(lane == 0, 9)
            wait_cnt(&g_cnt.cs2[0], 4);
            if (elect()) mbar_arrive(bars + B_VEC3 * 8);
            TS(lane == 0, 19)
        }
        return;
    }

    {
        uint32_t ep;
        {
            TIDS
            ep = ld_cold(&g_epoch);
            const int cp = (tid + 16) % 40, cp1 = tid % 40;
            const uint4 sh0 = ldg128(pp.shift_k + (80 * (id & 7) + 2 * cp1) * 4), sh1 = ldg128(pp.shift_k + (80 * (id & 7) + 2 * cp) * 4);
            uint32_t dd;
            asm volatile("ld.global.nc.u16 %0, [%1];" : "=r"(dd) : "l"(pp.ssm_D + 5 * id + min(wg + 3 * lane, 4)));
            TR4(lane == 0, 40 + warp)
            __syncthreads();
            asm volatile("barrier.cluster.arrive.relaxed.aligned;" ::: "memory");
            asm volatile("add.u32 %0, %0, 1;" : "+r"(ep));
#pragma unroll 1
            for (int hw = 0; hw < 2; hw++) {
                if ((unsigned)(warp - 2 * hw) >= 10) continue;
                const int u = tid - 64 * hw;
                const int c = hw ? cp : cp1, oc = u / 40, line = 31 - 16 * hw - (id >> 3);
                const uint4 sh = hw ? sh1 : sh0;
                const uint32_t st = sb + OFF_ST + hw * 10240, sta = st + c * 256 + ((((6 - 2 * (oc & 3)) ^ (oc >> 2) ^ (line & 1)) ^ (c & 7)) << 4), in = oc * 1280 + c * 4;
                const uint32_t f0 = __byte_perm(sh.x, sh.z, 0x5410), f1 = __byte_perm(sh.x, sh.z, 0x7632), f2 = __byte_perm(sh.y, sh.w, 0x5410), f3 = __byte_perm(sh.y, sh.w, 0x7632);
                uint32_t kk[11], vv[8];
                mbar_spin(bars + (B_IN + hw) * 8, 0);
                TS(tid == 64, 18 + 42 * hw)
#pragma unroll
                for (int i = 0; i < 11; i++) kk[i] = lds32(sb + OFF_KIN + hw * 10752 + in + i * 160);
#pragma unroll
                for (int i = 0; i < 8; i++) vv[i] = lds32(sb + OFF_VIN + hw * 10240 + in + i * 160);
#pragma unroll
                for (int i = 0; i < 8; i++) vv[i] = mul2(fma2(kk[i + 3], f0, fma2(kk[i + 2], f1, fma2(kk[i + 1], f2, mul2(kk[i], f3)))), vv[i]);
                sts128(sta, tag(__byte_perm(vv[0], vv[1], 0x5410), ep), __byte_perm(vv[2], vv[3], 0x5410), __byte_perm(vv[4], vv[5], 0x5410), __byte_perm(vv[6], vv[7], 0x5410));
                sts128(sta + 128, tag(__byte_perm(vv[0], vv[1], 0x7632), ep), __byte_perm(vv[2], vv[3], 0x7632), __byte_perm(vv[4], vv[5], 0x7632), __byte_perm(vv[6], vv[7], 0x7632));
                bar_sync(7 + hw, 320);
                flush_tile(st, g_kvT + (size_t)(80 * (id & 7)) * S_ + 64 * line, u);
                TS(tid == 64 && hw, 1)
            }
            warp_arrive(bars + B_KVS * 8);
            if (tid < 320) sts128(sb + OFF_CH + (tid >> 6) * CH_BYTES + 4096 + (tid & 63) * 16, 0, 0, 0, 0);
            mbar_spin(bars + B_SSM * 8, 0);
            TS(tid == 0, 14)
#pragma unroll 1
            for (int u0 = wg; u0 < 20; u0 += 12) {
                uint2 w[4];
                uint32_t pv[4];
#pragma unroll
                for (int i = 0; i < 4; i++) {
                    const uint32_t a = sb + OFF_SSM + min(u0 + 3 * i, 19) * 1024 + wt * 8;
                    w[i] = lds64(a); pv[i] = lds32(a - 4);
                }
#pragma unroll
                for (int i = 0; i < 4; i++) {
                    const int un = min(u0 + 3 * i, 19);
                    sts128(sb + OFF_CH + (un >> 2) * CH_BYTES + OFF_P + (un & 3) * 2048 + wt * 16, __byte_perm(w[i].x, pv[i], 0x7610), __byte_perm(w[i].x, 0, 0x1032), __byte_perm(w[i].y, w[i].x, 0x7610), __byte_perm(w[i].y, 0, 0x1032));
                }
            }
            __syncwarp();
            if (wt < 2 - (wg >> 1)) {
                const uint32_t h = lds32(sb + OFF_SSM + (wg + 3 * wt) * 4096), h0 = pack2(blo(h) + blo(dd), 0.f);
                sts64f(sb + OFF_CH + (wg + 3 * wt) * CH_BYTES + OFF_P, __uint_as_float(h0), __uint_as_float(__byte_perm(h, h0, 0x5432)));
            }
            fence_async_smem();
            warp_arrive(bars + B_BK * 8);
            asm volatile("barrier.cluster.wait.aligned;" ::: "memory");
            mbar_spin(bars + B_BK * 8, 0);
            TS(tid == 0, 15)
        }

#pragma unroll 1
        for (int c = wg; c < 5; c += 3) {
            const uint32_t kvb = sb + OFF_CH + c * CH_BYTES;
            mbar_spin(bars + (c < 3 ? B_RAW : B_RAW3) * 8, 0);
            for (uint32_t ph = 0; c < 3; ph ^= 1) {
                const int wt = tid_now() & 127;
                if (!RARE(bar_any(1 + wg, lop3<0x7E>(lds32(kvb + wt * 16), ep, lds32(kvb + 2048 + wt * 16)) & 1))) break;
                if (wt == 0) { mbar_expect(bars + (B_RETRY + wg) * 8, 4096); bulk_ld(kvb, g_kvT + (size_t)(5 * id + c) * S_, 4096, bars + (B_RETRY + wg) * 8); }
                mbar_spin(bars + (B_RETRY + wg) * 8, ph);
                STALE1(3)
            }
            TS(threadIdx.x == 0, c ? 13 : 11)
            float acc[64];
            {
                const int l = tid_now() & 31;
                conv_channel(acc, kvb + OFF_P + (8 * (warp & 3) + (l >> 2) - 2 * (l & 3)) * 4, (((uint64_t)0xC0000010u << 32) | ((kvb & 0x3FFFF) >> 4) | 0x10000u) + pp.nil);
            }
            TS(threadIdx.x == 0, c ? 16 : 12)
            if (c < 3) warp_arrive(bars + B_R1 * 8);
            else mbar_spin(bars + B_R1 * 8, 0);
            if (wg == 2 && id < 120) {
                TIDS
                mbar_spin(bars + B_RAW3 * 8, 0);
                mbar_spin(bars + B_WM * 8, 0);
                TS(wt == 0, 56)
                float d[4];
                gemv_tile<8>(d, sb + OFF_WM, sb + OFF_Z, 0);
                const float d2 = __shfl_up_sync(~0u, d[2], 1);
                TS(wt == 0, 7)
                if (t < 2) asm volatile("{\n.reg .b64 v;\nmov.b64 v, {%1, %2};\nst.relaxed.gpu.global.b64 [%0], v;\n}" ::"l"(g_mod + (id & 1) * 6 * D_ + 64 * pr + 16 * (warp & 3) + g + 8 * t),
                                        "r"(__float_as_uint(t ? d2 : d[0])), "r"(lds32(sb + M_EP)) : "memory");
            }
            TR4(threadIdx.x == 0, 60 + (c >= 3) * 10)
            TIDS
            const int e = 127 - 8 * (lane >> 4) - (lane & 7), u0 = (warp & 3) + 8 * (e >> 2) + (e & 3) + 4 * ((lane >> 3) & 1);
            const uint32_t ring = sb + OFF_RING + c * 16384 + (warp & 3) * 4096, wa = ring + (u0 ^ ((u0 >> 1) & 4)) * 16;
            if (lane < (warp & 3)) sts128(ring + lane * 16, 0, 0, 0, 0);
#pragma unroll
            for (int i = 0; i < 8; i++)
                stsm4t(i == 0 && u0 >= 256 ? sb + M_SINK : wa - 512 * i, pack2(acc[8 * i], acc[8 * i + 1]), pack2(acc[8 * i + 2], acc[8 * i + 3]),
                       pack2(acc[8 * i + 4], acc[8 * i + 5]), pack2(acc[8 * i + 6], acc[8 * i + 7]));
            warp_arrive(bars + (B_RING + c) * 8);
            TR4(threadIdx.x == 0, 61 + (c >= 3) * 10)
        }
        TIDS
        if (wg == 2) bar_sync(3, 128);
        if (warp == 8) {
            wait_cnt(&g_cnt.q[(id & 3) * 32], 128, true);
            if (elect()) {
                mbar_expect(bars + B_QRDY * 8, 28672);
                tma_ld2(sb + OFF_QT, &mp.qT, 80 * id, 0, bars + B_QRDY * 8);
                bulk_ld(sb + OFF_QT + 20480, g_qst, 8192, bars + B_QRDY * 8);
            }
            TS(lane == 0, 8)
        } else if (warp == 9) {
            const int v = min(lane / 5, 3);
            const uint2* gm = g_mod + (v + (v == 3)) * D_ + 5 * id + lane % 5;
            const unsigned epoch = lds32(sb + M_EP);
            uint2 r0, r1;
            unsigned it = 0;
            do {
                r0 = ld_mod(gm); r1 = ld_mod(gm + 6 * D_);
                SPIN_CHECK(55)
            } while (!__all_sync(~0u, r0.y == epoch && r1.y == epoch));
            const float m0 = __uint_as_float(r0.x), m1 = __uint_as_float(r1.x);
            const float m = rbf(m0 + m1), p = rbf(1.f + m);
            const float cz = zscale(__shfl_sync(~0u, p, 15 + lane % 5)), ga = __shfl_sync(~0u, m, 10 + lane % 5);
            if (lane < 15) sts32(sb + M_AB + lane % 5 * 16 + v * 4, lane < 10 ? __float_as_uint(cz * ga * (lane < 5 ? m : p)) : pack2(cz, cz));
            warp_arrive(bars + B_MODR * 8);
            TS(lane == 0, 6)
        }
        mbar_spin(bars + B_QRDY * 8, 0);
        uint4 rs[2], nm[2];
#pragma unroll
        for (int h = 0; h < 2; h++) { rs[h] = lds128(sb + OFF_QT + 20480 + h * 2048 + wt * 16); nm[h] = lds128(sb + OFF_QT + 24576 + h * 2048 + wt * 16); }
        mbar_spin(bars + B_MODR * 8, 0);
        TR4(threadIdx.x == 0, 72)
        uint32_t it = 0;
        while (RARE(__any_sync(~0u, (lop3<0x7E>(rs[0].x, ep, rs[0].z) | lop3<0x7E>(nm[0].x, ep, nm[0].z) | lop3<0x7E>(rs[1].x, ep, rs[1].z) | lop3<0x7E>(nm[1].x, ep, nm[1].z)) & 1))) {
#pragma unroll
            for (int h = 0; h < 2; h++) { rs[h] = ld_part(g_qst + 1024 * h + 8 * wt); nm[h] = ld_part(g_qst + S_ + 1024 * h + 8 * wt); }
            STALE(1)
            SPIN_CHECK(53)
        }
        TR4(threadIdx.x == 0, 73)
#pragma unroll 1
        for (int c = wg == 2 ? 0 : 3 + wg; c < (wg == 2 ? 3 : 4 + wg); c++) {
            uint4 q[2], p[2][4];
#pragma unroll
            for (int h = 0; h < 2; h++) q[h] = lds128(sb + OFF_QT + h * 10240 + (wt >> 1) * 160 + c * 32 + (wt & 1) * 16);
            const float4 ab = lds128f(sb + M_AB + c * 16);
            mbar_spin(bars + (B_RING + c) * 8, 0);
            TR4(wt == 0, wg == 2 ? 80 + 2 * c : 74)
#pragma unroll
            for (int i = 0; i < 8; i++) p[i >> 2][i & 3] = lds128(sb + OFF_RING + c * 16384 + (i & 3) * 4096 + (i >> 2) * 2048 + (wt ^ ((wt >> 1) & 4)) * 16);
            while (RARE(__any_sync(~0u, lop3<0x7E>(q[0].x, ep, q[1].x) & 1))) {
#pragma unroll
                for (int h = 0; h < 2; h++) q[h] = ld_part(g_qT + ((64 * h + (wt >> 1)) * D_ + 5 * id + c) * 16 + 8 * (wt & 1));
                STALE(2)
                SPIN_CHECK(52)
            }
            TR4(wt == 0, wg == 2 ? 81 + 2 * c : 75)
#pragma unroll
            for (int h = 0; h < 2; h++) {
                const uint32_t qq[4] = {q[h].x, q[h].y, q[h].z, q[h].w}, r4[4] = {rs[h].x, rs[h].y, rs[h].z, rs[h].w}, n4[4] = {nm[h].x, nm[h].y, nm[h].z, nm[h].w};
                const uint4 y = add2(add2(p[h][0], p[h][1]), add2(p[h][2], p[h][3]));
                const uint32_t yy[4] = {y.x, y.y, y.z, y.w};
                uint32_t o[4];
#pragma unroll
                for (int i = 0; i < 4; i++) {
                    const uint32_t n = fma2(qq[i], r4[i], n4[i]);
                    o[i] = fma2(pack2(fmaf(blo(n), ab.y, ab.x), fmaf(bhi(n), ab.y, ab.x)), yy[i], mul2(qq[i], __float_as_uint(ab.z)));
                }
                stg128_tag(g_x1T + (size_t)(5 * id + c) * S_ + 1024 * h + 8 * wt, o[0], o[1], o[2], o[3], ep, ((5 * id + c) >> 3) & 3);
            }
        }
        warp_arrive(bars + B_XS * 8);
        TS(tid == 0, 17)
        TS(tid == 256, 52)
    }

    const uint32_t nil = pp.nil;
    const int wq = warp & 3;
    if (wg == 2) {
        TIDS
        asm volatile("setmaxnreg.dec.sync.aligned.u32 32;");
        {
            const uint32_t ep = lds32(sb + M_EP);
            uint32_t ph = 0;
#pragma unroll 1
            for (int m = wq - 4; m < 60; m += 4) {
                const int n = max(m, 0);
                const int e = (n >= 20) + (n >= 40), i = n - 20 * e;
                const uint32_t M = e == 0 ? M0 : e == 1 ? M1 : M2;
                const int w = (M >> i) & 1, c = __popc(M & ((1u << i) - 1)), kb = w ? c : i - c;
                const uint32_t a = sb + OFF_XR + (n & 7) * 8192;
                uint32_t ta = a + (e == 0 ? lane * 128 + ((lane & 7) << 4) + (lane >> 3) * 4
                                 : e == 1 ? (lane & 15) * 128 + (((lane >> 4 << 1) ^ (lane & 7)) << 4) + (lane & 8) + (lane >> 4) * 4
                                          : lane * 32 + (lane >> 2) * 4);
                uint32_t tb = e == 0 ? ta ^ 32 : ta + 2048, tc = e == 2 ? ta + 1024 : ta ^ 64, td = e == 2 ? tb + 1024 : tb ^ 64;
                uint32_t live = m >= 0,
                    f0 = bars + (B_XFULL + 8 * w + ((10 * e + kb) & 7)) * 8;
                uint32_t f1 = m == GATE_W2 || m == GATE_W3 || m == GATE_W3B ? bars + (B_GATE + (m >= GATE_W3) + (m >= GATE_W3B)) * 8 : 0;
                if (lane) f0 = f1;
                if (lane > 1 || m < 0) f0 = 0;
                asm volatile("" : "+r"(ta), "+r"(tb), "+r"(tc), "+r"(td), "+r"(live), "+r"(f0));
                mbar_spin(bars + (m < 0 ? B_BK : B_LAND + (n & 7)) * 8, (n >> 3) & 1);
                TR5(lane == 0, n)
                while (true) {
                    uint32_t v[8];
#pragma unroll
                    for (int i = 0; i < 8; i++) v[i] = lds32(((i & 2) ? ((i & 1) ? td : tc) : (i & 1) ? tb : ta) + (i >> 2) * 4096);
                    const uint32_t bad = lop3<0xFE>(lop3<0x7E>(v[0], ep, v[1]), lop3<0x7E>(v[2], ep, v[3]), lop3<0x7E>(v[4], ep, v[5]));
                    if (!RARE(__any_sync(~0u, lop3<0xA8>(bad, lop3<0x7E>(v[6], ep, v[7]), live)))) break;
                    if (elect()) load_tile(mp, a, e, grp + 16 * w, kb, j, bars + (B_AGAIN + wq) * 8);
                    mbar_spin(bars + (B_AGAIN + wq) * 8, ph);
                    ph ^= 1;
                    STALE1(e)
                }
                TR5(lane == 0, 60 + n)
                if (f0) mbar_arrive(f0);
            }
        }
        if (wq == 0) {
#pragma unroll 1
            for (int w = 0; w < 2; w++) {
                const uint4* src = g_part + (size_t)(grp + 16 * w) * 40960;
                mbar_wait(bars + (B_RING + w) * 8, 1);
                if (elect()) {
                    const uint32_t fb = bars + (B_IN + w) * 8, rem = sb + OFF_OUT + w * 10240;
                    mbar_expect(fb, 10240);
                    bulk_ld(rem + 8192, &g_x1f[((grp + 16 * w) * 8 + j) * 640 + 512], 2048, fb);
#pragma unroll 1
                    for (int i = 0; i < 4; i++) bulk_ld(rem + i * 2048, src + ((j >> 2) + 2 * i) * 5120 + 4096 + j * 128, 2048, fb);
                }
            }
        }
#pragma unroll 1
        for (int uw = 0; uw < 2; uw++) {
            const int tile = grp + 16 * uw;
            const uint32_t ep = lds32(sb + M_EP), in = sb + OFF_OUT + uw * 10240 + wt * 16, sr = in - lane * 16;
            mbar_wait(bars + (B_IN + uw) * 8, 1);
            uint4 r = make_uint4(0, 0, 0, 0);
#pragma unroll 1
            for (int h = 0; h < 2; h++) {
                uint4 a = lds128(in + h * 4096), b = lds128(in + h * 4096 + 2048);
                uint32_t it = 0;
                while (RARE(__any_sync(~0u, lop3<0x7E>(a.x, ep, b.x) & 1))) {
                    const uint4* p = g_part + (size_t)tile * 40960 + ((j >> 2) + 4 * h) * 5120 + 4096 + j * 128 + wt;
                    a = ld_part(p); b = ld_part(p + 10240);
                    STALE(3)
                    if (++it > SPIN_LIMIT) SPIN_FAIL(58)
                }
                r = add2(r, add2(a, b));
            }
            r = fin16(r, lds128(in + 8192), ld_gb(sb, 8, t), ld_gb(sb, 9, t));
            __syncwarp();
            stsm4(sr + (lane & 15) * 32 + (((lane >> 4) ^ ((lane >> 2) & 1)) << 4), r.x, r.y, r.z, r.w);
            __syncwarp();
            stg128(out + (size_t)(64 * tile + 16 * wq + (lane >> 1)) * D_ + 512 + 16 * j + 8 * (lane & 1), lds128(sr + (lane >> 1) * 32 + (((lane & 1) ^ ((lane >> 3) & 1)) << 4)));
            __syncwarp();
        }
        TS(wt == 0, 21)
        if (wq == 0) {
            uint32_t it = 0;
            while (!mbar_try(bars + B_OWN * 8, 0)) { if (++it > SPIN_LIMIT) SPIN_FAIL(56) }
        }
        return;
    }

    TIDS
    const int uw = wg, tile = grp + 16 * uw, row0 = 64 * tile + 16 * wq;
    const bool leader = wt == 0; (void)leader;
    const uint32_t xfull = bars + (B_XFULL + 8 * uw) * 8, xempty = bars + B_XEMPTY * 8, wfull = bars + B_WFULL * 8, wempty = bars + B_WEMPTY * 8;
    const uint64_t dz = mkdesc(0) + pp.nil;
    auto xwait = [&](uint32_t n) { mbar_spin(xfull + (n & 7) * 8, (n >> 3) & 1); };
    asm volatile("setmaxnreg.inc.sync.aligned.u32 224;");
    const uint32_t ep = lds32(sb + M_EP);
    uint32_t res[20] = {};
    {
        float acc[40];
        const uint32_t la = ((lane & 7) + 8 * (lane >> 4)) * 128 + (((2 * wq + ((lane >> 3) & 1)) ^ (lane & 7)) << 4);
        auto pos = [&](int n) { return ring_pos(uw, n, LEAD1) & 7; };
        auto slot = [&](int n) { return sb + OFF_XR + pos(n) * 8192; };
        float al[2], r1[2], n1[2];
        {
            float sl[4], sq[4], v[4];
            uint32_t z0[16], z1[16], zz[16];
            uint64_t bd = dz + b80_desc(dsb, 0, 0, 0), tb = (((uint64_t)8 << 32) | ((dsb + OFF_TAB) >> 4) | (7u << 16)) + pp.nil;
            auto ldfrag = [&](uint32_t (&z)[16], int n) {
#pragma unroll
                for (int q = 0; q < 4; q++) ldsm4t(slot(n) + la + q * 2048, z[4 * q], z[4 * q + 1], z[4 * q + 2], z[4 * q + 3]);
            };
            auto tile1 = [&](const uint32_t (&zc)[16], uint32_t (&zn)[16], int n, int h) {
                const bool last = h && n == 5, ok = mbar_test(xfull + (n + 1) * 8, 0), okw = !h || mbar_test(wfull + ((n + 1) >> 1) * 8, 0);
                const int kb = g1_block(n, j);
                wg_fence();
#pragma unroll
                for (int q = 0; q < 2; q++) wgmma_rs80(acc, zc[4 * q], zc[4 * q + 1], zc[4 * q + 2], zc[4 * q + 3], bd + q * B80_STEP, 1);
                wg_commit();
                wg_wait<1>();
                if (!ok) xwait(n + 1);
                if (!last) ldfrag(zn, n + 1);
#pragma unroll
                for (int e = 0; e < 16; e++) zz[e] = mul2(zc[e], zc[e]);
                const uint64_t t0 = last ? ((uint64_t)8 << 32) | ((dsb + M_NUL) >> 4) : tb;
                const uint32_t ts = last ? 0 : 14;
                wg_fence();
#pragma unroll
                for (int q = 0; q < 4; q++) wgmma_rs8(sl, zc[4 * q], zc[4 * q + 1], zc[4 * q + 2], zc[4 * q + 3], t0 + q * ts, 1);
#pragma unroll
                for (int q = 0; q < 4; q++) wgmma_rs8(sq, zz[4 * q], zz[4 * q + 1], zz[4 * q + 2], zz[4 * q + 3], t0 + q * ts, 1);
#pragma unroll
                for (int q = 2; q < 4; q++) wgmma_rs80(acc, zc[4 * q], zc[4 * q + 1], zc[4 * q + 2], zc[4 * q + 3], bd + q * B80_STEP, 1);
                wg_commit();
#pragma unroll
                for (int q = 0; q < 4; q++) ldsm4t_if(kb == j, slot(n) + la + q * 2048, &res[4 * q]);
                if (!h) ldsm4t_if(kb == 8 + (j >> 2), slot(n) + la + (j & 3) * 2048, &res[16]);
                if (lane < 2) mbar_arrive_after(xempty + pos(n) * 8, res[12], res[16], nil);
                if (!h && n && lane == 0) mbar_arrive(wempty + ((n >> 1) - 1) * 8);
                tb += 56;
                bd = bd + (uint64_t)B80_HALF;
                if (!okw) mbar_spin(wfull + ((n + 1) >> 1) * 8, 0);
                TR(leader, 100 + 10 * uw + n)
            };
            zero(acc); zero(sl); zero(sq);
            mbar_spin(bars + B_TAB * 8, 0);
            mbar_spin(wfull, 0);
            xwait(0);
            TS(leader, 32 + uw)
            ldfrag(z0, 0);
#pragma unroll 1
            for (int n = 0; n < 6; n += 2) { tile1(z0, z1, n, 0); tile1(z1, z0, n + 1, 1); }
#pragma unroll
            for (int n = 6; n < 10; n++) {
                const uint64_t ad = dz + (((dsb + OFF_XR + pos(n) * 8192) >> 4) | 0x10000u);
                const bool ok = n == 9 || mbar_test(xfull + ((n + 1) & 7) * 8, (n + 1) >> 3), okw = n != 7 || mbar_test(wfull + 4 * 8, 0);
                wg_fence();
#pragma unroll
                for (int q = 0; q < 4; q++) wgmma_ss80t(acc, ad + q * 128, bd + q * B80_STEP, 1);
                wg_commit();
                bd = bd + (uint64_t)B80_HALF;
                if (n == 9) ldsm4t_if(9 - (j & 1) == 8 + (j >> 2), slot(9) + la + (j & 3) * 2048, &res[16]);
                wg_wait<1>();
                if (n > 6 && lane < 2) mbar_arrive(xempty + pos(n - 1) * 8);
                if (!(n & 1) && lane == 0) mbar_arrive(wempty + ((n >> 1) - 1) * 8);
                if (n == 6) {
                    reg_fence(sl); reg_fence(sq);
#pragma unroll
                    for (int e = 0; e < 2; e++) {
                        v[2 * e] = t == 0 ? sl[2 * e] + sl[2 * e + 1] : t == 1 ? sq[2 * e] + sq[2 * e + 1] : sl[2 * e];
                        v[2 * e + 1] = t == 2 ? sl[2 * e + 1] : sq[2 * e];
                    }
                    st_peer(peer_addr(sb + OFF_ROW + uw * 2048 + wt * 16), __float_as_uint(v[0]), __float_as_uint(v[1]), __float_as_uint(v[2]), __float_as_uint(v[3]), peer_addr(bars + (B_SUMS + uw) * 8));
                    TS(leader && !uw, 59)
                }
                if (!ok) xwait(n + 1);
                if (!okw) mbar_spin(wfull + 4 * 8, 0);
                TR(leader, 100 + 10 * uw + n)
            }
            float4 k = lds128f(sb + M_KS);
            float k4 = __uint_as_float(lds32(sb + M_KS + 16));
#pragma unroll
            for (int w = 1; w < 5; w++) {
                const float4 o = lds128f(sb + M_KS + w * 32);
                k.x += o.x; k.y += o.y; k.z += o.z; k.w += o.w; k4 += __uint_as_float(lds32(sb + M_KS + w * 32 + 16));
            }
            mbar_spin(bars + (B_SUMS + uw) * 8, 0);
            TS(leader && !uw, 10)
            const float4 o = lds128f(sb + OFF_ROW + uw * 2048 + wt * 16);
            v[0] += o.x; v[1] += o.y; v[2] += o.z; v[3] += o.w;
            uint32_t fa[4];
#pragma unroll
            for (int h = 0; h < 2; h++) {
                const int l0 = lane & ~3;
                const float s1 = __shfl_sync(~0u, v[2 * h], l0), s2 = __shfl_sync(~0u, v[2 * h], l0 + 1), scc = __shfl_sync(~0u, v[2 * h], l0 + 2);
                const float scs = __shfl_sync(~0u, v[2 * h + 1], l0 + 2), sc = __shfl_sync(~0u, v[2 * h], l0 + 3), sqq = __shfl_sync(~0u, v[2 * h + 1], l0 + 3);
                const float m1 = s1 * (1.f / D_), va = fmaxf(s2 * (1.f / D_) - m1 * m1, 0.f) + 1e-5f, r = rsqrtf(va);
                const float m2 = (r * (sc - m1 * k.x) + k.y) * (1.f / D_);
                const float e2 = (r * (r * (sqq + m1 * (m1 * k.z - 2.f * scc)) + 2.f * (scs - m1 * k.w)) + k4) * (1.f / D_);
                al[h] = r * 0.5f * rsqrtf(fmaxf(e2 - m2 * m2, 0.f) + 1e-5f); r1[h] = r; n1[h] = -m1 * r;
                const uint32_t fb = split2(va * r), fx = split2(t == 3 ? -m2 * va * r : -m1), fc = __shfl_sync(~0u, fx, lane | 3);
                fa[h] = __byte_perm(fx, fb, t == 1 ? 0x5432 : t == 2 ? 0x7654 : 0x1010);
                fa[2 + h] = t ? 0 : fc >> 16;
            }
            mbar_spin(bars + B_VEC * 8, 0);
            wg_fence();
            wgmma_rs80k(acc, fa[0], fa[1], fa[2], fa[3], ((uint64_t)8 << 32) | ((dsb + OFF_F1) >> 4) | (((M_F1 - OFF_F1) >> 4) << 16), 1);
            wg_commit();
        }
        wg_wait<0>();
        reg_fence(acc);
        if (lane < 2) mbar_arrive_after(xempty + pos(9) * 8, res[16], 0, nil);
        if (lane == 0) mbar_arrive(wempty + 4 * 8);
        TS(leader, 34 + uw)
        {
            bf16* const trow = g_t + (size_t)(row0 + g + 2) * D_;
#pragma unroll
            for (int b = 0; b < 3; b++) {
                uint32_t p[8];
#pragma unroll
                for (int ii = 0; ii < 4; ii++) {
                    const int i = 4 * b + ii;
                    if (i >= 10) continue;
#pragma unroll
                    for (int h = 0; h < 2; h++) p[(i & 3) + 4 * h] = pack2(gelu2(acc[4 * i + 2 * h] * al[h]), gelu2(acc[4 * i + 2 * h + 1] * al[h]));
                }
                if (b < 2) {
                    const int gr = (2 * j + b) / 5, sh = (gr & 1) ? -1 - (gr >> 1) : 1 + (gr >> 1);
                    bf16* dst = trow + 64 * j + 32 * b + 8 * t;
                    const int w = (((g + sh) >> 2) & 2) + (t >> 1);
                    stg128_tag(dst + sh * D_, p[0], p[1], p[2], p[3], ep, w);
                    stg128_tag(dst + (sh + 8) * D_, p[4], p[5], p[6], p[7], ep, w ^ 2);
                    if (row0 + g < sh || row0 + g + 8 >= S_ + sh) stg128_tag(dst + (sh > 0 ? 0 : 8) * D_, 0, 0, 0, 0, ep, (sh > 0 ? 0 : 2) + (t >> 1));
                } else {
                    bf16* dst = trow + 512 + 16 * j + 4 * t;
                    const uint32_t lo = t == (g < 2), hi = t == (g >= 2), o = j & 1;
                    stg64(dst - 2 * D_, lop3<0xB8>(p[0], lo & ~o, ep), lop3<0xB8>(p[1], lo & o, ep));
                    stg64(dst + 6 * D_, lop3<0xB8>(p[4], hi & ~o, ep), lop3<0xB8>(p[5], hi & o, ep));
                    if (row0 + g + 8 >= S_ - 2) stg64(dst + 8 * D_, ep & (t == 1) & ~o, ep & (t == 1) & o);
                }
            }
        }
        signal_cnt(&g_cnt.g1[tile * 32], lane, 1, true);
        TS(leader, 36 + uw)
#pragma unroll
        for (int i = 0; i < 10; i++) {
            const float2 c = lds64f(sb + M_C + (8 * i + 2 * t) * 4), s = lds64f(sb + M_SB + (8 * i + 2 * t) * 4);
#pragma unroll
            for (int h = 0; h < 2; h++) {
                acc[4 * i + 2 * h] = fmaf(blo(res[2 * i + h]), r1[h], fmaf(n1[h], c.x, s.x));
                acc[4 * i + 2 * h + 1] = fmaf(bhi(res[2 * i + h]), r1[h], fmaf(n1[h], c.y, s.y));
            }
        }
        mbar_spin(wfull + 5 * 8, 0);
        xwait(10);
        TS(leader, 22 + uw)
        uint32_t xo = (4 + 2 * uw) * 8, xp = 0;
        uint64_t ad = dz + (((dsb + OFF_XR) >> 4) | 0x10000u) + xo * 64, bd = dz + b80_desc(dsb, 5, 0, 0);
#pragma unroll 1
        for (int i = 0; i < 5; i++) {
            const uint32_t x1 = xfull + ((3 + 2 * i) & 7) * 8, p1 = i < 3, x2 = xfull + (min(4 + 2 * i, 11) & 7) * 8, p2 = i < 2;
            const uint32_t w2 = wfull + (min(6 + i, 9) & 7) * 8, pw = i >= 2;
            const bool ok1 = mbar_test(x1, p1);
            wg_fence();
#pragma unroll
            for (int q = 0; q < 4; q++) wgmma_ss80(acc, ad + q * 2, bd + q * B80_STEP, 1);
            wg_commit();
            wg_wait<1>();
            if (lane < 2 && i) mbar_arrive(xempty + xp);
            if (lane == 0 && i) mbar_arrive(wempty + ((4 + i) & 7) * 8);
            if (!ok1) mbar_spin(x1, p1);
            const bool ok2 = mbar_test(x2, p2), okw = mbar_test(w2, pw);
            wg_fence();
#pragma unroll
            for (int q = 0; q < 4; q++) wgmma_ss80(acc, ad + 512 + q * 2, bd + B80_HALF + q * B80_STEP, 1);
            wg_commit();
            const uint32_t xc = xo;
            xp = xo + 8; xo = (xo + 16) & 56;
            ad += xo ? 1024 : 1024 - 4096;
            bd += i == 2 ? 2 * B80_HALF - 8192 + (8192ll << 16) : 2 * B80_HALF;
            asm volatile("" : "+l"(ad), "+l"(bd));
            wg_wait<1>();
            if (lane < 2) mbar_arrive(xempty + xc);
            if (!ok2) mbar_spin(x2, p2);
            if (!okw) mbar_spin(w2, pw);
            TR(leader, (uw ? 86 : 20) + 2 * i)
        }
        wg_wait<0>();
        reg_fence(acc);
        if (lane < 2) mbar_arrive(xempty + xp);
        if (lane == 0) mbar_arrive(wempty + (9 & 7) * 8);
        TS(leader, 38 + uw)
        float a0 = 0.f, b0 = 0.f, a1 = 0.f, b1 = 0.f;
        uint32_t x2[20];
#pragma unroll
        for (int i = 0; i < 5; i++) {
            uint32_t* p = &x2[4 * i];
#pragma unroll
            for (int e = 0; e < 4; e++) p[e] = pack2(acc[8 * i + 2 * e], acc[8 * i + 2 * e + 1]);
#pragma unroll
            for (int e = 0; e < 4; e++) p[e] = lop3<0xB8>(p[e], (((wt >> 3) ^ (wt << 2)) & 7) == e, ep);
            stg128(&g_x2f[(tile * 40 + (i < 4 ? 4 * j + i : 32 + j)) * 128 + wt], p[0], p[1], p[2], p[3]);
#pragma unroll
            for (int e = 0; e < 8; e += 4) {
                const float* u = &acc[8 * i + e];
                a0 += u[0] + u[1]; b0 = fmaf(u[0], u[0], fmaf(u[1], u[1], b0));
                a1 += u[2] + u[3]; b1 = fmaf(u[2], u[2], fmaf(u[3], u[3], b1));
            }
        }
#pragma unroll
        for (int o = 1; o < 4; o *= 2) {
            a0 += __shfl_xor_sync(~0u, a0, o); b0 += __shfl_xor_sync(~0u, b0, o);
            a1 += __shfl_xor_sync(~0u, a1, o); b1 += __shfl_xor_sync(~0u, b1, o);
        }
        if (t < 2) stg64(&g_stats[(tile * 8 + j) * 64 + 16 * wq + g + 8 * t], tag(__float_as_uint(t ? a1 : a0), ep), __float_as_uint(t ? b1 : b0));
        signal_cnt(&g_cnt.g2[tile * 32], lane, 1, true);
        TS(leader, 40 + uw)
#pragma unroll
        for (int i = 0; i < 10; i++) {
            const float2 c = lds64f(sb + M_GB + (8 * i + 2 * t) * 4), e = lds64f(sb + M_CI + (8 * i + 2 * t) * 4);
#pragma unroll
            for (int h = 0; h < 2; h++)
                res[2 * i + h] = fma2(pack2(c.x, c.y), x2[2 * i + h], pack2(e.x * blo(res[2 * i + h]), e.y * bhi(res[2 * i + h])));
        }
#pragma unroll
        for (int i = 0; i < 20; i++) asm volatile("" : "+r"(res[i]));
    }
    float acc0[64], acc1[44];
    float2 q[4];
    {
        uint4 f0, f1, f2, f3;
        auto xseq = [&](int kb) { return ring_pos(uw, kb, XLEAD) & 7; };
        auto step = [&](const uint4& f, uint64_t bd) {
            wg_fence();
            wgmma_rs128(acc0, f.x, f.y, f.z, f.w, bd, 1);
            wgmma_rs88(acc1, f.x, f.y, f.z, f.w, bd + 512, 1);
            wg_commit();
        };
        const uint32_t xa = sb + OFF_XR + wt * 16;
        const float2* const gs = &g_stats[(tile * 8 + 2 * t) * 64 + 16 * wq + g];
        zero(acc0); zero(acc1);
        uint32_t xs = xseq(0);
        xwait(20);
        TS(leader, 42 + uw)
        f0 = lds128(xa + xs * 8192); f1 = lds128(xa + xs * 8192 + 2048);
#pragma unroll
        for (int i = 0; i < 4; i++) q[i] = ld_stat(gs + (i & 1) * 64 + 8 * (i >> 1));
        mbar_spin(wfull + (10 & 7) * 8, (10 >> 3) & 1);
#pragma unroll 1
        for (int kb = 0; kb < 10; kb++) {
            const uint32_t wn = 10 + 2 * kb;
            const uint64_t bd = dz + (((dsb + OFF_W + (wn & 7) * 16384) >> 4) | (256u << 16));
            step(f0, bd);
            wg_wait<1>();
            if (kb && lane == 0) mbar_arrive(wempty + ((wn - 1) & 7) * 8);
            f2 = lds128(xa + xs * 8192 + 4096); f3 = lds128(xa + xs * 8192 + 6144);
            const bool w1 = mbar_test(wfull + ((wn + 1) & 7) * 8, (wn >> 3) & 1), x1 = mbar_test(xfull + ((21 + kb) & 7) * 8, ((21 + kb) >> 3) & 1);
            step(f1, bd + 128);
            if (!w1) mbar_spin(wfull + ((wn + 1) & 7) * 8, (wn >> 3) & 1);
            step(f2, bd + 1024);
            if (lane < 2) mbar_arrive_after(xempty + xs * 8, f2.x, f3.x, nil);
            wg_wait<1>();
            if (lane == 0) mbar_arrive(wempty + (wn & 7) * 8);
            xs = xseq(kb + 1);
            if (x1) { f0 = lds128(xa + xs * 8192); f1 = lds128(xa + xs * 8192 + 2048); }
            const bool w2 = mbar_test(wfull + ((wn + 2) & 7) * 8, ((wn + 2) >> 3) & 1);
            step(f3, bd + 1152);
            if (kb < 9 && !x1) { xwait(21 + kb); f0 = lds128(xa + xs * 8192); f1 = lds128(xa + xs * 8192 + 2048); }
            if (!w2) mbar_spin(wfull + ((wn + 2) & 7) * 8, ((wn + 2) >> 3) & 1);
            if (kb == 4) {
                uint32_t it = 0;
                while (RARE(__any_sync(~0u, ((__float_as_uint(q[0].x) ^ ep) | (__float_as_uint(q[1].x) ^ ep) | (__float_as_uint(q[2].x) ^ ep) | (__float_as_uint(q[3].x) ^ ep)) & 1))) {
#pragma unroll
                    for (int i = 0; i < 4; i++) q[i] = ld_stat(gs + (i & 1) * 64 + 8 * (i >> 1));
                    SPIN_CHECK(49)
                }
                float a0 = q[0].x + q[1].x, b0 = q[0].y + q[1].y, a1 = q[2].x + q[3].x, b1 = q[2].y + q[3].y;
#pragma unroll
                for (int o = 1; o < 4; o *= 2) {
                    a0 += __shfl_xor_sync(~0u, a0, o); b0 += __shfl_xor_sync(~0u, b0, o);
                    a1 += __shfl_xor_sync(~0u, a1, o); b1 += __shfl_xor_sync(~0u, b1, o);
                }
                a0 *= 1.f / D_; a1 *= 1.f / D_;
                const float r0 = 0.5f * rsqrtf(fmaxf(b0 * (1.f / D_) - a0 * a0, 0.f) + 1e-5f), r1 = 0.5f * rsqrtf(fmaxf(b1 * (1.f / D_) - a1 * a1, 0.f) + 1e-5f);
                const uint32_t sel = t == 0 ? 0x1010 : t == 1 ? 0x4432 : 0x4444;
                q[0] = make_float2(r0, r1);
                q[1] = make_float2(__uint_as_float(__byte_perm(split2(-a0), 0, sel)), __uint_as_float(__byte_perm(split2(-a1), 0, sel)));
            }
            if (kb == 6) {
#pragma unroll
                for (int i = 0; i < 5; i++) stg128(&g_x1f[(tile * 8 + j) * 640 + i * 128 + wt], res[4 * i], res[4 * i + 1], res[4 * i + 2], res[4 * i + 3]);
            }
            if (kb == 8) asm volatile("fence.proxy.async.global;" ::: "memory");
            TR(leader, 10 * uw + kb)
        }
        const uint64_t fd = ((uint64_t)8 << 32) | ((dsb + OFF_W + 6 * 16384) >> 4);
        wg_fence();
        wgmma_rs128k(acc0, __float_as_uint(q[1].x), __float_as_uint(q[1].y), 0, 0, fd, 1);
        wgmma_rs88k(acc1, __float_as_uint(q[1].x), __float_as_uint(q[1].y), 0, 0, fd + 128, 1);
        wg_commit();
        if (lane == 0) {
            mbar_arrive(bars + B_XFREE * 8);
            asm volatile("mbarrier.arrive.shared::cluster.b64 _, [%0];" ::"r"(peer_addr(bars + B_XFREE * 8)) : "memory");
        }
    }
    const uint32_t recv = sb + recv_off(uw) + wt * 16;
    uint32_t ha[48] = {}, hb[48], hx[12];
    uint64_t wb = dz + (((dsb + OFF_W) >> 4) | (512u << 16));
    auto wdesc = [&](int n) { return wb + (n & 7) * 1024; };
    auto wwait = [&](int n) { mbar_spin(wfull + (n & 7) * 8, (n >> 3) & 1); };
    auto wfree = [&](int n) { if (lane == 0) mbar_arrive(wempty + (n & 7) * 8); };
    auto fresh = [&]() { wb += pp.nil; asm volatile("" : "+l"(wb)); };
    uint32_t pk[32];
    {
        float P0[64];
        const float r0 = q[0].x, r1 = q[0].y;
        const uint32_t ra = peer_addr(recv), rb = peer_addr(bars + (B_RECV + 4 * uw) * 8);
        auto conv32 = [&](const float* v, int b) {
#pragma unroll
            for (int i = 0; i < 4; i++) {
                ha[8 * b + 2 * i] = pack2(gelu2(v[4 * i] * r0), gelu2(v[4 * i + 1] * r0));
                ha[8 * b + 2 * i + 1] = pack2(gelu2(v[4 * i + 2] * r1), gelu2(v[4 * i + 3] * r1));
            }
#pragma unroll
            for (int s = 2 * b; s < 2 * b + 2; s++) st_peer(ra + s * 2048, ha[4 * s], ha[4 * s + 1], ha[4 * s + 2], ha[4 * s + 3], rb + (b >> 1) * 8);
        };
        auto fetch = [&](int k) {
            mbar_spin(bars + (B_RECV + 4 * uw + k) * 8, 0);
#pragma unroll
            for (int s = 4 * k; s < 4 * k + 4; s++) { const uint4 x = lds128(recv + s * 2048); hb[4 * s] = x.x; hb[4 * s + 1] = x.y; hb[4 * s + 2] = x.z; hb[4 * s + 3] = x.w; }
        };
        auto stage = [&](int n, const uint32_t* a, int steps, int sc) {
            wwait(n);
            wg_fence();
#pragma unroll
            for (int s = 0; s < steps; s++) wgmma_rs128(P0, a[4 * s], a[4 * s + 1], a[4 * s + 2], a[4 * s + 3], wdesc(n) + s * 128, sc || s);
            wg_commit();
        };
        wg_wait<0>();
        reg_fence(acc0); reg_fence(acc1);
        wfree(29); wfree(30);
        TS(leader, 44 + uw)
        uint32_t hr[6];
#pragma unroll
        for (int i = 0; i < 6; i++) {
            const float r = (i & 1) ? r1 : r0;
            hr[i] = pack2(gelu2(acc1[32 + 2 * i] * r), gelu2(acc1[33 + 2 * i] * r));
        }
        if (uw) mbar_spin(bars + B_XFREE * 8, 0);
        st_peer(ra + 24576, hr[0], hr[1], hr[2], hr[3], rb + 24);
        asm volatile("st.async.shared::cluster.mbarrier::complete_tx::bytes.v2.b32 [%0], {%1, %2}, [%3];" ::"r"(ra + 26624 - wt * 8), "r"(hr[4]), "r"(hr[5]), "r"(rb + 24) : "memory");
        conv32(&acc1[0], 4);
        conv32(&acc1[16], 5);
        TS(leader, 46 + uw)
        stage(31, &ha[32], 4, 0);
#pragma unroll
        for (int b = 0; b < 4; b++) {
            conv32(&acc0[16 * b], b);
            if (b == 3) {
                fetch(2);
                mbar_spin(bars + (B_RECV + 4 * uw + 3) * 8, 0);
                const uint4 x = lds128(recv + 24576);
                const uint2 y = lds64(recv + 26624 - wt * 8);
                const uint32_t hp[6] = {x.x, x.y, x.z, x.w, y.x, y.y};
#pragma unroll
                for (int i = 0; i < 6; i++) { hx[i] = (j & 1) ? hp[i] : hr[i]; hx[6 + i] = (j & 1) ? hr[i] : hp[i]; }
            }
            if (!(b & 1)) wwait(32 + (b >> 1));
            wg_fence();
#pragma unroll
            for (int s = 0; s < 2; s++) wgmma_rs128(P0, ha[8 * b + 4 * s], ha[8 * b + 4 * s + 1], ha[8 * b + 4 * s + 2], ha[8 * b + 4 * s + 3], wdesc(32 + (b >> 1)) + (2 * (b & 1) + s) * 128, 1);
            wg_commit();
            if (!(b & 1)) { wg_wait<1>(); wfree(31 + (b >> 1)); }
        }
        TR(leader, 64 + 10 * uw)
        fresh();
        stage(34, &hb[32], 4, 1); wg_wait<1>(); wfree(33);
        fetch(0);
        stage(35, hx, 3, 1); wg_wait<1>(); wfree(34);
        fetch(1);
        stage(36, &hb[0], 4, 1); wg_wait<1>(); wfree(35);
        stage(37, &hb[16], 4, 1); wg_wait<1>(); wfree(36);
        wg_wait<0>();
        reg_fence(P0);
        pack_part<64>(pk, P0, ep);
        uint32_t all = 0;
#pragma unroll
        for (int i = 0; i < 32; i++) all |= pk[i];
        if (lane == 0) mbar_arrive_after(wempty + (37 & 7) * 8, all, 0, nil);
        TR(leader, 65 + 10 * uw)
    }
    {
        uint4* const dst = g_part + (size_t)(tile * 8 + j) * 5120 + wt;
        const uint4* const src = g_part + (size_t)tile * 40960 + j * 512 + wt;
        float F[2][32];
        uint32_t gb[8];
        float2 gf[8];
        uint4 base[4], u1[4], u2[4], u3[4];
#pragma unroll
        for (int c = 2; c < 5; c++) {
            float (&P)[32] = F[c & 1];
            fresh();
#pragma unroll
            for (int s = 0; s < 27; s++) {
                const int e = s < 8 ? 0 : s < 15 ? 1 : s < 23 ? 2 : 3, o = s - (e == 0 ? 0 : e == 1 ? 8 : e == 2 ? 15 : 23), n = 30 + 4 * c + e;
                const uint32_t* a = s < 12 ? &ha[4 * s] : s < 15 ? &hx[4 * (s - 12)] : &hb[4 * (s - 15)];
                if (o == 0) wwait(n);
                if (o == 0 || s == 1) wg_fence();
                wgmma_rs64(P, a[0], a[1], a[2], a[3], wdesc(n) + o * 128, s);
                if (o == 0) { wg_commit(); wg_wait<1>(); if (c > 2 || s) wfree(n - 1); }
                if (s == 0 && c > 2) { reg_fence(F[~c & 1]); pack_part<32>(pk, F[~c & 1], ep); }
                if (c == 2 && s % 3 == 0 && s < 24) st_part(dst + g4_block(s / 12, j) * 512 + (s / 3 & 3) * 128, &pk[4 * (s / 3)]);
                if (c == 3 && s % 4 == 1 && s < 16) st_part(dst + g4_block(2, j) * 512 + s / 4 * 128, &pk[4 * (s / 4)]);
                if (c == 4 && s % ST3 == 0 && s < 4 * ST3) st_part(dst + g4_block(3, j) * 512 + s / ST3 * 128, &pk[4 * (s / ST3)]);
                if (c == 4 && s >= 4 && s < 8) base[s - 4] = ldcg128(&g_x1f[(tile * 8 + j) * 640 + (s - 4) * 128 + wt]);
                if (c == 4 && s >= 19 && s < 23) { gf[2 * s - 38] = lds64f(sb + M_GB + (16 * (s - 19) + 2 * t) * 4); gf[2 * s - 37] = lds64f(sb + M_GB + (16 * (s - 19) + 8 + 2 * t) * 4); }
                if (c == 4 && s >= 8 && s < 12) u1[s - 8] = ld_part(src + (j ^ 6) * 5120 + (s - 8) * 128);
                if (c == 4 && s >= 15 && s < 19) u2[s - 15] = ld_part(src + (j ^ 4) * 5120 + (s - 15) * 128);
                if (c == 4 && s >= LD3 && s < LD3 + 4) u3[s - LD3] = ld_part(src + (j ^ 2) * 5120 + (s - LD3) * 128);
                if (s == 7 || s == 14 || s == 22 || s == 26) wg_commit();
                if (c == 4) { TR(leader && s == 7, 68 + 10 * uw) TR(leader && s == 14, 69 + 10 * uw) TR(leader && s == 22, 70 + 10 * uw) }
            }
            if (c == 2 && lane == 0) mbar_arrive(bars + (B_RING + uw) * 8);
            TR(leader, 64 + c + (c == 4 ? 3 : 0) + 10 * uw)
        }
        float (&O)[32] = F[0];
#pragma unroll
        for (int i = 0; i < 8; i++) gb[i] = pack2(gf[i].x, gf[i].y);
        uint32_t it = 0;
        while (__any_sync(~0u, (stale4(u1, ep) | stale4(u2, ep) | stale4(u3, ep)) & 1)) {
            ld_part4(u1, src + (j ^ 6) * 5120, 128); ld_part4(u2, src + (j ^ 4) * 5120, 128); ld_part4(u3, src + (j ^ 2) * 5120, 128);
            STALE(6)
            SPIN_CHECK(58)
        }
        TR(leader, 73 + 10 * uw)
#pragma unroll
        for (int i = 0; i < 4; i++) u1[i] = add2(add2(u1[i], u2[i]), u3[i]);
        TS(leader, 50 + uw)
        wg_wait<0>();
        reg_fence(O);
        TS(leader, 48 + uw)
        const uint32_t so = sb + recv_off(uw) + wq * 2048;
#pragma unroll
        for (int i = 0; i < 4; i++) {
            const float* o = &O[8 * i];
            const uint4 r = fin16(add2(u1[i], make_uint4(pack2(o[0], o[1]), pack2(o[2], o[3]), pack2(o[4], o[5]), pack2(o[6], o[7]))), base[i], gb[2 * i], gb[2 * i + 1]);
            stsm4(so + (lane & 15) * 128 + (((2 * i + (lane >> 4)) ^ (lane & 7)) << 4), r.x, r.y, r.z, r.w);
        }
        __syncwarp();
#pragma unroll
        for (int i = 0; i < 4; i++) {
            const int row = (lane >> 3) + 4 * i;
            stg128(out + (size_t)(row0 + row) * D_ + 64 * j + 8 * (lane & 7), lds128(so + row * 128 + (((lane & 7) ^ (row & 7)) << 4)));
        }
        TS(leader, 24 + uw)
        warp_arrive(bars + B_OWN * 8);
    }
}

typedef CUresult (*EncFn)(CUtensorMap*, CUtensorMapDataType, cuuint32_t, void*, const cuuint64_t*, const cuuint64_t*, const cuuint32_t*,
                          const cuuint32_t*, CUtensorMapInterleave, CUtensorMapSwizzle, CUtensorMapL2promotion, CUtensorMapFloatOOBfill);

static void enc(EncFn fn, CUtensorMap* m, void* p, int rank, const cuuint64_t* dims, const cuuint64_t* strides, const cuuint32_t* box, bool plain = false) {
    const CUtensorMapSwizzle sw = box[0] > 64 || plain ? CU_TENSOR_MAP_SWIZZLE_NONE : CU_TENSOR_MAP_SWIZZLE_128B;
    cuuint32_t es[5] = {1, 1, 1, 1, 1};
    CUresult r = fn(m, CU_TENSOR_MAP_DATA_TYPE_BFLOAT16, rank, p, dims, strides, box, es, CU_TENSOR_MAP_INTERLEAVE_NONE, sw,
                    CU_TENSOR_MAP_L2_PROMOTION_L2_128B, CU_TENSOR_MAP_FLOAT_OOB_FILL_NONE);
    (void)r;
}
static void enc2(EncFn fn, CUtensorMap* m, void* p, uint64_t cols, uint64_t rows, uint32_t bc, uint32_t br, bool plain = false) {
    cuuint64_t dims[2] = {cols, rows}, st[1] = {cols * 2};
    cuuint32_t box[2] = {bc, br};
    enc(fn, m, p, 2, dims, st, box, plain);
}

extern "C" void kernel_launch(void* const* d_in, const int* in_sizes, int n_in, void* d_out, int out_size) {
    static Maps mp;
    static Ptrs pp;
    static void* cached[13];
    bool same = true;
    for (int i = 0; i < 13; i++) same = same && (cached[i] == d_in[i]);
    if (!same) {
        void* fnp = nullptr;
        cudaDriverEntryPointQueryResult qr;
        cudaGetDriverEntryPoint("cuTensorMapEncodeTiled", &fnp, cudaEnableDefault, &qr);
        EncFn fn = (EncFn)fnp;
        cudaGetSymbolAddress((void**)&pp.s, g_scratch);
        void *x1T = g_x1T, *t = g_t;
        cuuint64_t dq[3] = {64, S_, 10}, sq[2] = {D_ * 2, 128};
        cuuint32_t bq[3] = {64, 16, 10};
        enc(fn, &mp.q, d_in[0], 3, dq, sq, bq);
        enc2(fn, &mp.k, d_in[1], D_, S_, 80, 67); enc2(fn, &mp.v, d_in[2], D_, S_, 80, 64);
        enc2(fn, &mp.qT, g_qT, 16 * D_, 128, 80, 128);
        enc2(fn, &mp.x[0], x1T, S_, D_, 64, 64); enc2(fn, &mp.x[1], (bf16*)t + 2 * D_, D_, S_, 64, 64);
        enc2(fn, &mp.x[2], g_x2f, 64, 320 * 64, 64, 64, true);
        enc2(fn, &mp.w1, d_in[7], D_, D_, 64, 64); enc2(fn, &mp.w1h, d_in[7], D_, D_, 64, 160); enc2(fn, &mp.w3h, d_in[9], F_, D_, 64, 160);
        enc2(fn, &mp.wmod, d_in[12], 6 * D_, D_, 64, 160);
        const cuuint64_t R = D_ * 2;
        cuuint64_t da[5] = {D_, 2, 4, 4, 16}, sa[4] = {R, 8 * R, 2 * R, 32 * R}, db[5] = {D_, 2, 2, 4, 8}, sb[4] = {R, 8 * R, 2 * R, 16 * R};
        cuuint32_t ba[5] = {64, 2, 4, 4, 4}, bb[5] = {64, 2, 2, 4, 8};
        enc(fn, &mp.w2a, d_in[8], 5, da, sa, ba); enc(fn, &mp.w2b, (bf16*)d_in[8] + 512 * D_, 5, db, sb, bb);
        cuuint64_t dw[3] = {64, D_, 27}, sw[2] = {F_ * 2, 128};
        cuuint32_t bw[3] = {64, 32, 3};
        enc(fn, &mp.w3a, d_in[9], 3, dw, sw, bw);
        enc2(fn, &mp.w3b, d_in[9], F_, D_, 24, 32);
        enc2(fn, &mp.w4[0], d_in[10], D_, F_, 64, 64); enc2(fn, &mp.w4[1], d_in[10], D_, F_, 64, 48);
        pp.q = (const bf16*)d_in[0]; pp.w_mod = (const bf16*)d_in[12]; pp.shift_k = (const bf16*)d_in[3];
        pp.ssm_k = (const bf16*)d_in[4]; pp.ssm_D = (const bf16*)d_in[5]; pp.w1 = (const bf16*)d_in[7]; pp.w2 = (const bf16*)d_in[8];
        pp.w4 = (const bf16*)d_in[10]; pp.c = (const bf16*)d_in[11];
        cudaFuncSetAttribute(fused_kernel, cudaFuncAttributeMaxDynamicSharedMemorySize, SMEM_BYTES);
        for (int i = 0; i < 13; i++) cached[i] = d_in[i];
    }
    fused_kernel<<<NCTA, NTHR, SMEM_BYTES, cudaStreamPerThread>>>(pp, (bf16*)d_out, mp);
}
```

```cpp
#include <cuda_runtime.h>
#include <cuda_bf16.h>
#include <cuda.h>
#include <stdint.h>
#include <stdio.h>

typedef __nv_bfloat16 bf16;

constexpr int S_ = 2048, D_ = 640, F_ = 1728;
constexpr int NCTA = 132, NTHR = 512;

constexpr int TAB_BYTES = 9216, VEC_BYTES = 1440;
struct Counters {
    unsigned kv[8 * 32];
    unsigned q[4 * 32], x[4 * 32];
    unsigned wr[32], tab[32], uv[32], cs[32], cs2[32], done[32];
    unsigned g1[32 * 32];
    unsigned g2[32 * 32];
};
struct Scratch {
    Counters cnt;
    unsigned epoch;
    alignas(1024) bf16 qst[2 * S_];
    alignas(1024) uint4 wr[2 * 8 * 10 * 128];
    alignas(1024) uint2 mod[2 * 6 * D_];
    alignas(1024) uint4 tab[(TAB_BYTES + 8 * VEC_BYTES) / 16];
    alignas(1024) float uv[2 * 3 * D_];
    alignas(1024) float cs3[2 * 1920];
    alignas(1024) uint4 cs3b[8 * 216];
    alignas(1024) float2 stats[32 * 8 * 64];
    alignas(1024) bf16 kvT[D_ * S_];
    alignas(1024) bf16 qT[D_ * S_];
    alignas(1024) bf16 x1T[D_ * S_];
    alignas(1024) bf16 t[(S_ + 4) * D_];
    alignas(1024) uint4 x2f[32 * 40 * 128];
    alignas(1024) uint4 x1f[32 * 8 * 5 * 128];
    alignas(1024) uint4 part[32 * 8 * 10 * 4 * 128];
};
__device__ Scratch g_scratch;
#define g_kvT (pp.s->kvT)
#define g_qT (pp.s->qT)
#define g_x1T (pp.s->x1T)
#define g_qst (pp.s->qst)
#define g_t (pp.s->t)
#define g_x2f (pp.s->x2f)
#define g_x1f (pp.s->x1f)
#define g_part (pp.s->part)
#define g_wr (pp.s->wr)
#define g_mod (pp.s->mod)
#define g_tab (pp.s->tab)
#define g_uv (pp.s->uv)
#define g_cs3 (pp.s->cs3)
#define g_cs3b (pp.s->cs3b)
#define g_stats (pp.s->stats)
#define g_cnt (pp.s->cnt)
#define g_epoch (pp.s->epoch)

struct Maps {
    CUtensorMap k, v, q;
    CUtensorMap qT;
    CUtensorMap x[3];
    CUtensorMap w1, w1h, w3h, wmod;
    CUtensorMap w2a, w2b;
    CUtensorMap w3a, w3b;
    CUtensorMap w4[2];
};

struct Ptrs {
    Scratch* s;
    uint64_t nil;
    const bf16 *q, *w_mod, *shift_k, *ssm_k, *ssm_D, *w1, *w2, *w4, *c;
};

constexpr int OFF_W = 0;
constexpr int OFF_XR = 131072;
constexpr int OFF_REM = 196608;
constexpr int OFF_TAB = OFF_REM + 5 * 4096;
constexpr int OFF_ROW = OFF_TAB + 4608;
constexpr int OFF_F1 = OFF_ROW + 4096;
constexpr int RECV_BYTES = 30720;
constexpr int OFF_M = OFF_REM + RECV_BYTES;
constexpr int OFF_OUT = OFF_XR + 32768;
static_assert(OFF_F1 + 1280 <= OFF_M, "G1 map");
constexpr int OFF_ST = 0;
constexpr int OFF_SSM = 20480;
constexpr int OFF_WM = 0;
constexpr int OFF_QIN = 49152;
constexpr int OFF_QT = 49152;
constexpr int OFF_Z = OFF_TAB;
constexpr int OFF_RING = 80896;
constexpr int OFF_KIN = OFF_RING, OFF_VIN = OFF_KIN + 2 * 10752;
constexpr int OFF_CH = OFF_RING + 3 * 16384, CH_BYTES = 13312, OFF_P = 5120;
static_assert(OFF_RING + 5 * 16384 <= OFF_CH + 3 * CH_BYTES && OFF_CH + 5 * CH_BYTES <= OFF_REM, "the last two rings replace channels 0..2");
constexpr int M_BAR = OFF_M;
constexpr int M_F1 = OFF_M + 800;
constexpr int M_GB = M_F1 + 1280, M_C = M_GB + 320, M_SB = M_C + 320, M_CI = M_SB + 320;
constexpr int M_KS = M_CI + 320;
constexpr int M_AB = M_KS + 160;
constexpr int M_EP = M_AB + 80;
constexpr int M_SINK = M_EP + 16;
constexpr int M_NUL = M_SINK + 16;
constexpr int M_TS = M_NUL + 128;
constexpr int SMEM_BYTES = M_TS;
static_assert(SMEM_BYTES <= 232448, "smem");

enum { B_WFULL = 0, B_WEMPTY = 8, B_XEMPTY = 16, B_XFULL = 24  ,
       B_RAW = 40, B_QIN = 41, B_SSM = 42, B_VEC = 43, B_VEC3 = 44, B_WM = 45, B_TAB = 46, B_QRDY = 47,
       B_MODR = 48, B_GATE = 49, B_RETRY = 55, B_RAW2 = 59, B_RAW3 = 60, B_SUMS = 62, B_RECV = 64  ,
       B_SIG = 72, B_RING = 74  ,
       B_LAND = 80,
       B_XS = 88, B_R1 = 89, B_BK = 90, B_KVS = 91,
       B_XFREE = 92, B_OWN = 93,
       B_IN = 94, B_AGAIN = 96 };
#define T_KVB 1800
#define T_SSM 3300
#define PF_T0 4800
#define PF_DT 420
#define Q_UNROLL 1
#define HELP_T 1000
#define R_GATE 34
#define REG_AUX 40
#define REG_SVC 40
#define REG_MMA 216
#define STR2(x) #x
#define STR(x) STR2(x)
#define ST3 1
#define LD3 23
#define GATE_W2 7
#define GATE_W3 27
#define GATE_W3B 37
#define W3_N2 13
#define LEAD1 4
#define XLEAD 3

#define SPIN_FAIL(code) __trap();
#define SPIN_LIMIT (1u << 22)
#define STALE(c)
#define STALE1(c)
#define TS(c, i)
#define TG(c, i)
#define TR(c, i)
#define TR2(c, i)
#define TR4(c, i)
#define TR5(c, i)
#define SPIN_CHECK(code) asm volatile("" ::"r"(it));
#define RARE(x) __builtin_expect((x) != 0, 0)
__device__ __forceinline__ uint32_t s2u(const void* p) { return (uint32_t)__cvta_generic_to_shared(p); }
__device__ __forceinline__ bool elect() {
    uint32_t p;
    asm volatile("{.reg .pred P; elect.sync _|P, 0xffffffff; selp.u32 %0,1,0,P;}" : "=r"(p));
    return p != 0;
}
__device__ __forceinline__ void mbar_init(uint32_t b, uint32_t n) { asm volatile("mbarrier.init.shared.b64 [%0], %1;" ::"r"(b), "r"(n)); }
__device__ __forceinline__ void mbar_expect(uint32_t b, uint32_t bytes) {
    asm volatile("mbarrier.arrive.expect_tx.shared.b64 _, [%0], %1;" ::"r"(b), "r"(bytes) : "memory");
}
__device__ __forceinline__ void mbar_arrive(uint32_t b) { asm volatile("mbarrier.arrive.shared.b64 _, [%0];" ::"r"(b) : "memory"); }
__device__ __forceinline__ void mbar_arrive_after(uint32_t b, uint32_t v0, uint32_t v1, uint32_t nil) { mbar_arrive(b + ((v0 | v1) & nil)); }
__device__ __forceinline__ void warp_arrive(uint32_t b) { __syncwarp(); if (elect()) mbar_arrive(b); }
__device__ __forceinline__ uint32_t peer_addr(uint32_t a) {
    uint32_t r;
    asm("{\n.reg .b32 q;\nmov.u32 q, %%cluster_ctarank;\nxor.b32 q, q, 1;\nmapa.shared::cluster.u32 %0, %1, q;\n}" : "=r"(r) : "r"(a));
    return r;
}
__device__ __forceinline__ bool mbar_test(uint32_t b, uint32_t parity) {
    uint32_t ok;
    asm volatile("{.reg .pred P; mbarrier.test_wait.parity.shared.b64 P, [%1], %2; selp.u32 %0,1,0,P;}" : "=r"(ok) : "r"(b), "r"(parity) : "memory");
    return ok != 0;
}
__device__ __forceinline__ bool mbar_try(uint32_t b, uint32_t parity) {
    uint32_t ok;
    asm volatile("{.reg .pred P; mbarrier.try_wait.parity.shared.b64 P, [%1], %2; selp.u32 %0,1,0,P;}" : "=r"(ok) : "r"(b), "r"(parity) : "memory");
    return ok != 0;
}
__device__ __forceinline__ void mbar_wait(uint32_t b, uint32_t parity) {
    if (__all_sync(0xffffffffu, mbar_try(b, parity))) return;
    uint32_t it = 0;
    while (!__all_sync(0xffffffffu, mbar_try(b, parity))) { if (++it > SPIN_LIMIT) SPIN_FAIL((b >> 3) & 63) }
}
__device__ __forceinline__ void mbar_spin(uint32_t b, uint32_t parity) {
    asm volatile("{\n.reg .pred P;\nSPIN:\nmbarrier.try_wait.parity.shared.b64 P, [%0], %1;\n@!P bra.uni SPIN;\n}" ::"r"(b), "r"(parity) : "memory");
}
__device__ __forceinline__ void bar_sync(int id, int n) { asm volatile("bar.sync %0, %1;" ::"r"(id), "r"(n) : "memory"); }
__device__ __forceinline__ void fence_async_smem() { asm volatile("fence.proxy.async.shared::cta;" ::: "memory"); }
__device__ __forceinline__ void wait_cnt(const unsigned* p, unsigned target, bool tagged = false) {
    unsigned v, it = 0;
    do {
        asm volatile("ld.relaxed.gpu.global.u32 %0, [%1];" : "=r"(v) : "l"(p) : "memory");
        SPIN_CHECK(60 + (target & 3))
    } while (!__all_sync(0xffffffffu, v >= target));
    if (!tagged) asm volatile("fence.acquire.gpu;" ::: "memory");
}
__device__ __forceinline__ void signal_cnt(unsigned* p, int lane, int n, bool tagged = false) {
    if (tagged) asm volatile("{\n.reg .pred P;\nsetp.lt.s32 P, %1, %2;\n@P red.relaxed.gpu.global.add.u32 [%0], %3;\n}" ::"l"(p), "r"(lane), "r"(n), "r"(1) : "memory");
    else if (lane < n) asm volatile("red.release.gpu.global.add.u32 [%0], 1;" ::"l"(p) : "memory");
    __syncwarp();
}
__device__ __forceinline__ uint32_t clock_lo() { uint32_t c; asm volatile("mov.u32 %0, %%clock;" : "=r"(c)); return c; }
__device__ __forceinline__ void wait_clock(uint32_t c0, uint32_t t) {
    asm volatile("{\n.reg .pred P;\n.reg .b32 c;\nWAIT:\nnanosleep.u32 20;\nmov.u32 c, %%clock;\nsub.u32 c, c, %0;\nsetp.lt.u32 P, c, %1;\n@P bra.uni WAIT;\n}" ::"r"(c0), "r"(t) : "memory");
}
__device__ __forceinline__ void tma_ld2(uint32_t dst, const CUtensorMap* m, int c0, int c1, uint32_t bar) {
    asm volatile("cp.async.bulk.tensor.2d.shared::cluster.global.mbarrier::complete_tx::bytes [%0], [%1, {%3, %4}], [%2];"
                 ::"r"(dst), "l"(m), "r"(bar), "r"(c0), "r"(c1) : "memory");
}
__device__ __forceinline__ void tma_ld3(uint32_t dst, const CUtensorMap* m, int c0, int c1, int c2, uint32_t bar) {
    asm volatile("cp.async.bulk.tensor.3d.shared::cluster.global.mbarrier::complete_tx::bytes [%0], [%1, {%3, %4, %5}], [%2];"
                 ::"r"(dst), "l"(m), "r"(bar), "r"(c0), "r"(c1), "r"(c2) : "memory");
}
__device__ __forceinline__ void tma_ld5(uint32_t dst, const CUtensorMap* m, int col, int blk, uint32_t bar) {
    asm volatile("cp.async.bulk.tensor.5d.shared::cluster.global.mbarrier::complete_tx::bytes [%0], [%1, {%3, %4, %4, %4, %5}], [%2];"
                 ::"r"(dst), "l"(m), "r"(bar), "r"(col), "r"(0), "r"(blk) : "memory");
}
__device__ __forceinline__ void bulk_ld(uint32_t dst, const void* src, uint32_t bytes, uint32_t bar) {
    asm volatile("cp.async.bulk.shared::cluster.global.mbarrier::complete_tx::bytes [%0], [%1], %2, [%3];" ::"r"(dst), "l"(src), "r"(bytes), "r"(bar) : "memory");
}
__device__ __forceinline__ void l2_prefetch(const void* p, uint32_t bytes) {
    asm volatile("cp.async.bulk.prefetch.L2.global [%0], %1;" ::"l"(p), "r"(bytes) : "memory");
}
__device__ __forceinline__ void wg_fence() { asm volatile("wgmma.fence.sync.aligned;" ::: "memory"); }
__device__ __forceinline__ void wg_commit() { asm volatile("wgmma.commit_group.sync.aligned;" ::: "memory"); }
template <int N> __device__ __forceinline__ void wg_wait() { asm volatile("wgmma.wait_group.sync.aligned %0;" ::"n"(N) : "memory"); }
template <int N> __device__ __forceinline__ void reg_fence(float (&d)[N]) {
#pragma unroll
    for (int i = 0; i < N; i++) asm volatile("" : "+f"(d[i])::"memory");
}
template <int N> __device__ __forceinline__ void zero(float (&d)[N]) {
#pragma unroll
    for (int i = 0; i < N; i++) asm volatile("mov.b32 %0, 0;" : "=f"(d[i]));
}
__device__ __forceinline__ uint32_t lds32(uint32_t a) { uint32_t v; asm volatile("ld.shared.b32 %0, [%1];" : "=r"(v) : "r"(a)); return v; }
__device__ __forceinline__ uint2 lds64(uint32_t a) { uint2 v; asm volatile("ld.shared.v2.b32 {%0,%1}, [%2];" : "=r"(v.x), "=r"(v.y) : "r"(a)); return v; }
__device__ __forceinline__ float2 lds64f(uint32_t a) { float2 v; asm volatile("ld.shared.v2.f32 {%0,%1}, [%2];" : "=f"(v.x), "=f"(v.y) : "r"(a)); return v; }
__device__ __forceinline__ void sts32(uint32_t a, uint32_t v) { asm volatile("st.shared.b32 [%0], %1;" ::"r"(a), "r"(v) : "memory"); }
__device__ __forceinline__ void sts64f(uint32_t a, float x, float y) { asm volatile("st.shared.v2.f32 [%0], {%1,%2};" ::"r"(a), "f"(x), "f"(y) : "memory"); }
__device__ __forceinline__ void sts128(uint32_t a, uint32_t x, uint32_t y, uint32_t z, uint32_t w) {
    asm volatile("st.shared.v4.b32 [%0], {%1,%2,%3,%4};" ::"r"(a), "r"(x), "r"(y), "r"(z), "r"(w) : "memory");
}
__device__ __forceinline__ void sts128f(uint32_t a, float x, float y, float z, float w) {
    asm volatile("st.shared.v4.f32 [%0], {%1,%2,%3,%4};" ::"r"(a), "f"(x), "f"(y), "f"(z), "f"(w) : "memory");
}
__device__ __forceinline__ uint4 lds128(uint32_t a) {
    uint4 v;
    asm volatile("ld.shared.v4.b32 {%0,%1,%2,%3}, [%4];" : "=r"(v.x), "=r"(v.y), "=r"(v.z), "=r"(v.w) : "r"(a) : "memory");
    return v;
}
__device__ __forceinline__ float4 lds128f(uint32_t a) {
    float4 v;
    asm volatile("ld.shared.v4.f32 {%0,%1,%2,%3}, [%4];" : "=f"(v.x), "=f"(v.y), "=f"(v.z), "=f"(v.w) : "r"(a) : "memory");
    return v;
}
__device__ __forceinline__ void stg128(void* p, uint32_t x, uint32_t y, uint32_t z, uint32_t w) {
    asm volatile("st.global.v4.b32 [%0], {%1,%2,%3,%4};" ::"l"(p), "r"(x), "r"(y), "r"(z), "r"(w) : "memory");
}
__device__ __forceinline__ void stg128(void* p, uint4 v) { stg128(p, v.x, v.y, v.z, v.w); }
__device__ __forceinline__ void stg128_if(void* p, uint4 v, int on) {
    asm volatile("{\n.reg .pred p;\nsetp.ne.s32 p, %5, 0;\n@p st.global.v4.b32 [%0], {%1,%2,%3,%4};\n}" ::"l"(p), "r"(v.x), "r"(v.y), "r"(v.z), "r"(v.w), "r"(on) : "memory");
}
__device__ __forceinline__ void stg64(void* p, uint32_t x, uint32_t y) { asm volatile("st.global.v2.b32 [%0], {%1,%2};" ::"l"(p), "r"(x), "r"(y) : "memory"); }
__device__ __forceinline__ void stsm4(uint32_t a, uint32_t r0, uint32_t r1, uint32_t r2, uint32_t r3) {
    asm volatile("stmatrix.sync.aligned.m8n8.x4.shared.b16 [%0], {%1,%2,%3,%4};" ::"r"(a), "r"(r0), "r"(r1), "r"(r2), "r"(r3) : "memory");
}
__device__ __forceinline__ void stsm4t(uint32_t a, uint32_t r0, uint32_t r1, uint32_t r2, uint32_t r3) {
    asm volatile("stmatrix.sync.aligned.m8n8.x4.trans.shared.b16 [%0], {%1,%2,%3,%4};" ::"r"(a), "r"(r0), "r"(r1), "r"(r2), "r"(r3) : "memory");
}
__device__ __forceinline__ void ldsm4t_if(bool p, uint32_t a, uint32_t* r) {
    asm volatile("{\n.reg .pred p;\nsetp.ne.u32 p, %5, 0;\n@p ldmatrix.sync.aligned.m8n8.x4.trans.shared.b16 {%0,%1,%2,%3}, [%4];\n}"
                 : "+r"(r[0]), "+r"(r[1]), "+r"(r[2]), "+r"(r[3]) : "r"(a), "r"((uint32_t)p) : "memory");
}
__device__ __forceinline__ void ldsm4t(uint32_t a, uint32_t& r0, uint32_t& r1, uint32_t& r2, uint32_t& r3) {
    asm volatile("ldmatrix.sync.aligned.m8n8.x4.trans.shared.b16 {%0,%1,%2,%3}, [%4];" : "=r"(r0), "=r"(r1), "=r"(r2), "=r"(r3) : "r"(a) : "memory");
}
__device__ __forceinline__ uint32_t pack2(float lo, float hi) {
    uint32_t r;
    asm("cvt.rn.bf16x2.f32 %0, %1, %2;" : "=r"(r) : "f"(hi), "f"(lo));
    return r;
}
__device__ __forceinline__ uint32_t mul2(uint32_t a, uint32_t b) { uint32_t r; asm("mul.rn.bf16x2 %0, %1, %2;" : "=r"(r) : "r"(a), "r"(b)); return r; }
__device__ __forceinline__ uint32_t fma2(uint32_t a, uint32_t b, uint32_t c) { uint32_t r; asm("fma.rn.bf16x2 %0, %1, %2, %3;" : "=r"(r) : "r"(a), "r"(b), "r"(c)); return r; }
__device__ __forceinline__ uint32_t add2(uint32_t a, uint32_t b) { uint32_t r; asm("add.rn.bf16x2 %0, %1, %2;" : "=r"(r) : "r"(a), "r"(b)); return r; }
__device__ __forceinline__ void hmma(float (&d)[4], uint32_t a0, uint32_t a1, uint32_t a2, uint32_t a3, uint32_t b0, uint32_t b1) {
    asm volatile("mma.sync.aligned.m16n8k16.row.col.f32.bf16.bf16.f32 {%0,%1,%2,%3}, {%4,%5,%6,%7}, {%8,%9}, {%0,%1,%2,%3};"
        : "+f"(d[0]), "+f"(d[1]), "+f"(d[2]), "+f"(d[3]) : "r"(a0), "r"(a1), "r"(a2), "r"(a3), "r"(b0), "r"(b1));
}
__device__ __forceinline__ float blo(uint32_t w) { return __uint_as_float(w << 16); }
__device__ __forceinline__ float bhi(uint32_t w) { return __uint_as_float(w & 0xffff0000u); }
__device__ __forceinline__ float rbf(float x) { return __bfloat162float(__float2bfloat16_rn(x)); }
__device__ __forceinline__ uint32_t ldg32(const void* p) { uint32_t v; asm volatile("ld.global.nc.b32 %0, [%1];" : "=r"(v) : "l"(p)); return v; }
__device__ __forceinline__ uint2 ldg64(const void* p) { uint2 v; asm volatile("ld.global.nc.v2.b32 {%0,%1}, [%2];" : "=r"(v.x), "=r"(v.y) : "l"(p)); return v; }
__device__ __forceinline__ uint4 ldg128(const void* p) {
    uint4 v;
    asm volatile("ld.global.nc.v4.b32 {%0,%1,%2,%3}, [%4];" : "=r"(v.x), "=r"(v.y), "=r"(v.z), "=r"(v.w) : "l"(p));
    return v;
}
__device__ __forceinline__ uint4 ldcg128(const void* p) {
    uint4 v;
    asm volatile("ld.global.cg.v4.u32 {%0,%1,%2,%3}, [%4];" : "=r"(v.x), "=r"(v.y), "=r"(v.z), "=r"(v.w) : "l"(p) : "memory");
    return v;
}
__device__ __forceinline__ float4 ldcg128f(const void* p) {
    float4 v;
    asm volatile("ld.global.cg.v4.f32 {%0,%1,%2,%3}, [%4];" : "=f"(v.x), "=f"(v.y), "=f"(v.z), "=f"(v.w) : "l"(p) : "memory");
    return v;
}
__device__ __forceinline__ float2 ldcg64f(const void* p) { float2 v; asm volatile("ld.global.cg.v2.f32 {%0,%1}, [%2];" : "=f"(v.x), "=f"(v.y) : "l"(p) : "memory"); return v; }
__device__ __forceinline__ float ldcg32f(const void* p) { float v; asm volatile("ld.global.cg.f32 %0, [%1];" : "=f"(v) : "l"(p) : "memory"); return v; }
__device__ __forceinline__ float2 ld_stat(const float2* p) {
    float2 v;
    asm volatile("{\n.reg .b64 q;\nld.relaxed.gpu.global.b64 q, [%2];\nmov.b64 {%0, %1}, q;\n}" : "=f"(v.x), "=f"(v.y) : "l"(p) : "memory");
    return v;
}
__device__ __forceinline__ uint32_t ld_cold(const unsigned* p) { uint32_t v; asm volatile("ld.relaxed.gpu.global.u32 %0, [%1];" : "=r"(v) : "l"(p) : "memory"); return v; }
__device__ __forceinline__ uint2 ld_mod(const uint2* p) {
    uint64_t v;
    asm volatile("ld.relaxed.gpu.global.b64 %0, [%1];" : "=l"(v) : "l"(p) : "memory");
    return make_uint2((uint32_t)v, (uint32_t)(v >> 32));
}
__device__ __forceinline__ float silu(float x) {
    float e, r;
    asm("ex2.approx.ftz.f32 %0, %1;" : "=f"(e) : "f"(x * -1.4426950408889634f));
    asm("rcp.approx.ftz.f32 %0, %1;" : "=f"(r) : "f"(1.f + e));
    return x * r;
}
__device__ __forceinline__ float gelu2(float h) {
    float u = h * fmaf(h * h, 8.f * 0.0356774081f, 2.f * 0.7978845608f);
    float th;
    asm("tanh.approx.f32 %0, %1;" : "=f"(th) : "f"(u));
    return fmaf(h, th, h);
}
__device__ __forceinline__ float gelu2r(float a, float2 k) {
    float th;
    asm("tanh.approx.f32 %0, %1;" : "=f"(th) : "f"(a * fmaf(a * a, k.x, k.y)));
    return fmaf(a, th, a);
}

__device__ __forceinline__ void conv_channel(float (&d)[64], uint32_t pa, uint64_t db) {
    asm volatile("{\n.reg .b32 a0, a1, a2, a3, b0, b1, b2, b3, t0, t1;\n.reg .b64 d;\nld.shared.b32 a0, [%64];\nld.shared.b32 a1, [%64+128];\nld.shared.b32 a2, [%64+-128];\nmov.b32 a3, a0;\n"
        "ld.shared.b32 t0, [%64+256];\nld.shared.b32 t1, [%64+384];\nadd.s64 d, %65, 0;\nwgmma.fence.sync.aligned;\nwgmma.mma_async.sync.aligned.m64n128k16.f32.bf16.bf16 {%0, %1, %2, %3, %4, %5, %6, %7, %8, %9, %10, %11, %12, %13, %14, %15, %16, %17, %18, %19, %20, %21, %22, %23, %24, %25, %26, %27, %28, %29, %30, %31, %32, %33, %34, %35, %36, %37, %38, %39, %40, %41, %42, %43, %44, %45, %46, %47, %48, %49, %50, %51, %52, %53, %54, %55, %56, %57, %58, %59, %60, %61, %62, %63}, {a0, a1, a2, a3}, d, 0, 1, 1, 0;\nwgmma.commit_group.sync.aligned;\nwgmma.wait_group.sync.aligned 1;\nmov.b32 b2, a1;\nmov.b32 b0, t0;\nmov.b32 b3, t0;\nmov.b32 b1, t1;\n"
        "ld.shared.b32 t0, [%64+512];\nld.shared.b32 t1, [%64+640];\nadd.s64 d, %65, 8;\nwgmma.fence.sync.aligned;\nwgmma.mma_async.sync.aligned.m64n128k16.f32.bf16.bf16 {%0, %1, %2, %3, %4, %5, %6, %7, %8, %9, %10, %11, %12, %13, %14, %15, %16, %17, %18, %19, %20, %21, %22, %23, %24, %25, %26, %27, %28, %29, %30, %31, %32, %33, %34, %35, %36, %37, %38, %39, %40, %41, %42, %43, %44, %45, %46, %47, %48, %49, %50, %51, %52, %53, %54, %55, %56, %57, %58, %59, %60, %61, %62, %63}, {b0, b1, b2, b3}, d, 1, 1, 1, 0;\nwgmma.commit_group.sync.aligned;\nwgmma.wait_group.sync.aligned 1;\nmov.b32 a2, b1;\nmov.b32 a0, t0;\nmov.b32 a3, t0;\nmov.b32 a1, t1;\n"
        "ld.shared.b32 t0, [%64+768];\nld.shared.b32 t1, [%64+896];\nadd.s64 d, %65, 16;\nwgmma.fence.sync.aligned;\nwgmma.mma_async.sync.aligned.m64n128k16.f32.bf16.bf16 {%0, %1, %2, %3, %4, %5, %6, %7, %8, %9, %10, %11, %12, %13, %14, %15, %16, %17, %18, %19, %20, %21, %22, %23, %24, %25, %26, %27, %28, %29, %30, %31, %32, %33, %34, %35, %36, %37, %38, %39, %40, %41, %42, %43, %44, %45, %46, %47, %48, %49, %50, %51, %52, %53, %54, %55, %56, %57, %58, %59, %60, %61, %62, %63}, {a0, a1, a2, a3}, d, 1, 1, 1, 0;\nwgmma.commit_group.sync.aligned;\nwgmma.wait_group.sync.aligned 1;\nmov.b32 b2, a1;\nmov.b32 b0, t0;\nmov.b32 b3, t0;\nmov.b32 b1, t1;\n"
        "ld.shared.b32 t0, [%64+1024];\nld.shared.b32 t1, [%64+1152];\nadd.s64 d, %65, 24;\nwgmma.fence.sync.aligned;\nwgmma.mma_async.sync.aligned.m64n128k16.f32.bf16.bf16 {%0, %1, %2, %3, %4, %5, %6, %7, %8, %9, %10, %11, %12, %13, %14, %15, %16, %17, %18, %19, %20, %21, %22, %23, %24, %25, %26, %27, %28, %29, %30, %31, %32, %33, %34, %35, %36, %37, %38, %39, %40, %41, %42, %43, %44, %45, %46, %47, %48, %49, %50, %51, %52, %53, %54, %55, %56, %57, %58, %59, %60, %61, %62, %63}, {b0, b1, b2, b3}, d, 1, 1, 1, 0;\nwgmma.commit_group.sync.aligned;\nwgmma.wait_group.sync.aligned 1;\nmov.b32 a2, b1;\nmov.b32 a0, t0;\nmov.b32 a3, t0;\nmov.b32 a1, t1;\n"
        "ld.shared.b32 t0, [%64+1280];\nld.shared.b32 t1, [%64+1408];\nadd.s64 d, %65, 32;\nwgmma.fence.sync.aligned;\nwgmma.mma_async.sync.aligned.m64n128k16.f32.bf16.bf16 {%0, %1, %2, %3, %4, %5, %6, %7, %8, %9, %10, %11, %12, %13, %14, %15, %16, %17, %18, %19, %20, %21, %22, %23, %24, %25, %26, %27, %28, %29, %30, %31, %32, %33, %34, %35, %36, %37, %38, %39, %40, %41, %42, %43, %44, %45, %46, %47, %48, %49, %50, %51, %52, %53, %54, %55, %56, %57, %58, %59, %60, %61, %62, %63}, {a0, a1, a2, a3}, d, 1, 1, 1, 0;\nwgmma.commit_group.sync.aligned;\nwgmma.wait_group.sync.aligned 1;\nmov.b32 b2, a1;\nmov.b32 b0, t0;\nmov.b32 b3, t0;\nmov.b32 b1, t1;\n"
        "ld.shared.b32 t0, [%64+1536];\nld.shared.b32 t1, [%64+1664];\nadd.s64 d, %65, 40;\nwgmma.fence.sync.aligned;\nwgmma.mma_async.sync.aligned.m64n128k16.f32.bf16.bf16 {%0, %1, %2, %3, %4, %5, %6, %7, %8, %9, %10, %11, %12, %13, %14, %15, %16, %17, %18, %19, %20, %21, %22, %23, %24, %25, %26, %27, %28, %29, %30, %31, %32, %33, %34, %35, %36, %37, %38, %39, %40, %41, %42, %43, %44, %45, %46, %47, %48, %49, %50, %51, %52, %53, %54, %55, %56, %57, %58, %59, %60, %61, %62, %63}, {b0, b1, b2, b3}, d, 1, 1, 1, 0;\nwgmma.commit_group.sync.aligned;\nwgmma.wait_group.sync.aligned 1;\nmov.b32 a2, b1;\nmov.b32 a0, t0;\nmov.b32 a3, t0;\nmov.b32 a1, t1;\n"
        "ld.shared.b32 t0, [%64+1792];\nld.shared.b32 t1, [%64+1920];\nadd.s64 d, %65, 48;\nwgmma.fence.sync.aligned;\nwgmma.mma_async.sync.aligned.m64n128k16.f32.bf16.bf16 {%0, %1, %2, %3, %4, %5, %6, %7, %8, %9, %10, %11, %12, %13, %14, %15, %16, %17, %18, %19, %20, %21, %22, %23, %24, %25, %26, %27, %28, %29, %30, %31, %32, %33, %34, %35, %36, %37, %38, %39, %40, %41, %42, %43, %44, %45, %46, %47, %48, %49, %50, %51, %52, %53, %54, %55, %56, %57, %58, %59, %60, %61, %62, %63}, {a0, a1, a2, a3}, d, 1, 1, 1, 0;\nwgmma.commit_group.sync.aligned;\nwgmma.wait_group.sync.aligned 1;\nmov.b32 b2, a1;\nmov.b32 b0, t0;\nmov.b32 b3, t0;\nmov.b32 b1, t1;\n"
        "ld.shared.b32 t0, [%64+2048];\nld.shared.b32 t1, [%64+2176];\nadd.s64 d, %65, 56;\nwgmma.fence.sync.aligned;\nwgmma.mma_async.sync.aligned.m64n128k16.f32.bf16.bf16 {%0, %1, %2, %3, %4, %5, %6, %7, %8, %9, %10, %11, %12, %13, %14, %15, %16, %17, %18, %19, %20, %21, %22, %23, %24, %25, %26, %27, %28, %29, %30, %31, %32, %33, %34, %35, %36, %37, %38, %39, %40, %41, %42, %43, %44, %45, %46, %47, %48, %49, %50, %51, %52, %53, %54, %55, %56, %57, %58, %59, %60, %61, %62, %63}, {b0, b1, b2, b3}, d, 1, 1, 1, 0;\nwgmma.commit_group.sync.aligned;\nwgmma.wait_group.sync.aligned 1;\nmov.b32 a2, b1;\nmov.b32 a0, t0;\nmov.b32 a3, t0;\nmov.b32 a1, t1;\n"
        "ld.shared.b32 t0, [%64+2304];\nld.shared.b32 t1, [%64+2432];\nadd.s64 d, %65, 64;\nwgmma.fence.sync.aligned;\nwgmma.mma_async.sync.aligned.m64n96k16.f32.bf16.bf16 {%0, %1, %2, %3, %4, %5, %6, %7, %8, %9, %10, %11, %12, %13, %14, %15, %16, %17, %18, %19, %20, %21, %22, %23, %24, %25, %26, %27, %28, %29, %30, %31, %32, %33, %34, %35, %36, %37, %38, %39, %40, %41, %42, %43, %44, %45, %46, %47}, {a0, a1, a2, a3}, d, 1, 1, 1, 0;\nwgmma.commit_group.sync.aligned;\nwgmma.wait_group.sync.aligned 1;\nmov.b32 b2, a1;\nmov.b32 b0, t0;\nmov.b32 b3, t0;\nmov.b32 b1, t1;\n"
        "ld.shared.b32 t0, [%64+2560];\nld.shared.b32 t1, [%64+2688];\nadd.s64 d, %65, 72;\nwgmma.fence.sync.aligned;\nwgmma.mma_async.sync.aligned.m64n96k16.f32.bf16.bf16 {%0, %1, %2, %3, %4, %5, %6, %7, %8, %9, %10, %11, %12, %13, %14, %15, %16, %17, %18, %19, %20, %21, %22, %23, %24, %25, %26, %27, %28, %29, %30, %31, %32, %33, %34, %35, %36, %37, %38, %39, %40, %41, %42, %43, %44, %45, %46, %47}, {b0, b1, b2, b3}, d, 1, 1, 1, 0;\nwgmma.commit_group.sync.aligned;\nwgmma.wait_group.sync.aligned 1;\nmov.b32 a2, b1;\nmov.b32 a0, t0;\nmov.b32 a3, t0;\nmov.b32 a1, t1;\n"
        "ld.shared.b32 t0, [%64+2816];\nld.shared.b32 t1, [%64+2944];\nadd.s64 d, %65, 80;\nwgmma.fence.sync.aligned;\nwgmma.mma_async.sync.aligned.m64n88k16.f32.bf16.bf16 {%0, %1, %2, %3, %4, %5, %6, %7, %8, %9, %10, %11, %12, %13, %14, %15, %16, %17, %18, %19, %20, %21, %22, %23, %24, %25, %26, %27, %28, %29, %30, %31, %32, %33, %34, %35, %36, %37, %38, %39, %40, %41, %42, %43}, {a0, a1, a2, a3}, d, 1, 1, 1, 0;\nwgmma.commit_group.sync.aligned;\nwgmma.wait_group.sync.aligned 1;\nmov.b32 b2, a1;\nmov.b32 b0, t0;\nmov.b32 b3, t0;\nmov.b32 b1, t1;\n"
        "ld.shared.b32 t0, [%64+3072];\nld.shared.b32 t1, [%64+3200];\nadd.s64 d, %65, 88;\nwgmma.fence.sync.aligned;\nwgmma.mma_async.sync.aligned.m64n88k16.f32.bf16.bf16 {%0, %1, %2, %3, %4, %5, %6, %7, %8, %9, %10, %11, %12, %13, %14, %15, %16, %17, %18, %19, %20, %21, %22, %23, %24, %25, %26, %27, %28, %29, %30, %31, %32, %33, %34, %35, %36, %37, %38, %39, %40, %41, %42, %43}, {b0, b1, b2, b3}, d, 1, 1, 1, 0;\nwgmma.commit_group.sync.aligned;\nwgmma.wait_group.sync.aligned 1;\nmov.b32 a2, b1;\nmov.b32 a0, t0;\nmov.b32 a3, t0;\nmov.b32 a1, t1;\n"
        "ld.shared.b32 t0, [%64+3328];\nld.shared.b32 t1, [%64+3456];\nadd.s64 d, %65, 96;\nwgmma.fence.sync.aligned;\nwgmma.mma_async.sync.aligned.m64n80k16.f32.bf16.bf16 {%0, %1, %2, %3, %4, %5, %6, %7, %8, %9, %10, %11, %12, %13, %14, %15, %16, %17, %18, %19, %20, %21, %22, %23, %24, %25, %26, %27, %28, %29, %30, %31, %32, %33, %34, %35, %36, %37, %38, %39}, {a0, a1, a2, a3}, d, 1, 1, 1, 0;\nwgmma.commit_group.sync.aligned;\nwgmma.wait_group.sync.aligned 1;\nmov.b32 b2, a1;\nmov.b32 b0, t0;\nmov.b32 b3, t0;\nmov.b32 b1, t1;\n"
        "ld.shared.b32 t0, [%64+3584];\nld.shared.b32 t1, [%64+3712];\nadd.s64 d, %65, 104;\nwgmma.fence.sync.aligned;\nwgmma.mma_async.sync.aligned.m64n80k16.f32.bf16.bf16 {%0, %1, %2, %3, %4, %5, %6, %7, %8, %9, %10, %11, %12, %13, %14, %15, %16, %17, %18, %19, %20, %21, %22, %23, %24, %25, %26, %27, %28, %29, %30, %31, %32, %33, %34, %35, %36, %37, %38, %39}, {b0, b1, b2, b3}, d, 1, 1, 1, 0;\nwgmma.commit_group.sync.aligned;\nwgmma.wait_group.sync.aligned 1;\nmov.b32 a2, b1;\nmov.b32 a0, t0;\nmov.b32 a3, t0;\nmov.b32 a1, t1;\n"
        "ld.shared.b32 t0, [%64+3840];\nld.shared.b32 t1, [%64+3968];\nadd.s64 d, %65, 112;\nwgmma.fence.sync.aligned;\nwgmma.mma_async.sync.aligned.m64n72k16.f32.bf16.bf16 {%0, %1, %2, %3, %4, %5, %6, %7, %8, %9, %10, %11, %12, %13, %14, %15, %16, %17, %18, %19, %20, %21, %22, %23, %24, %25, %26, %27, %28, %29, %30, %31, %32, %33, %34, %35}, {a0, a1, a2, a3}, d, 1, 1, 1, 0;\nwgmma.commit_group.sync.aligned;\nwgmma.wait_group.sync.aligned 1;\nmov.b32 b2, a1;\nmov.b32 b0, t0;\nmov.b32 b3, t0;\nmov.b32 b1, t1;\n"
        "ld.shared.b32 t0, [%64+4096];\nld.shared.b32 t1, [%64+4224];\nadd.s64 d, %65, 120;\nwgmma.fence.sync.aligned;\nwgmma.mma_async.sync.aligned.m64n72k16.f32.bf16.bf16 {%0, %1, %2, %3, %4, %5, %6, %7, %8, %9, %10, %11, %12, %13, %14, %15, %16, %17, %18, %19, %20, %21, %22, %23, %24, %25, %26, %27, %28, %29, %30, %31, %32, %33, %34, %35}, {b0, b1, b2, b3}, d, 1, 1, 1, 0;\nwgmma.commit_group.sync.aligned;\nwgmma.wait_group.sync.aligned 1;\nmov.b32 a2, b1;\nmov.b32 a0, t0;\nmov.b32 a3, t0;\nmov.b32 a1, t1;\n"
        "ld.shared.b32 t0, [%64+4352];\nld.shared.b32 t1, [%64+4480];\nadd.s64 d, %65, 128;\nwgmma.fence.sync.aligned;\nwgmma.mma_async.sync.aligned.m64n64k16.f32.bf16.bf16 {%0, %1, %2, %3, %4, %5, %6, %7, %8, %9, %10, %11, %12, %13, %14, %15, %16, %17, %18, %19, %20, %21, %22, %23, %24, %25, %26, %27, %28, %29, %30, %31}, {a0, a1, a2, a3}, d, 1, 1, 1, 0;\nwgmma.commit_group.sync.aligned;\nwgmma.wait_group.sync.aligned 1;\nmov.b32 b2, a1;\nmov.b32 b0, t0;\nmov.b32 b3, t0;\nmov.b32 b1, t1;\n"
        "ld.shared.b32 t0, [%64+4608];\nld.shared.b32 t1, [%64+4736];\nadd.s64 d, %65, 136;\nwgmma.fence.sync.aligned;\nwgmma.mma_async.sync.aligned.m64n64k16.f32.bf16.bf16 {%0, %1, %2, %3, %4, %5, %6, %7, %8, %9, %10, %11, %12, %13, %14, %15, %16, %17, %18, %19, %20, %21, %22, %23, %24, %25, %26, %27, %28, %29, %30, %31}, {b0, b1, b2, b3}, d, 1, 1, 1, 0;\nwgmma.commit_group.sync.aligned;\nwgmma.wait_group.sync.aligned 1;\nmov.b32 a2, b1;\nmov.b32 a0, t0;\nmov.b32 a3, t0;\nmov.b32 a1, t1;\n"
        "ld.shared.b32 t0, [%64+4864];\nld.shared.b32 t1, [%64+4992];\nadd.s64 d, %65, 144;\nwgmma.fence.sync.aligned;\nwgmma.mma_async.sync.aligned.m64n56k16.f32.bf16.bf16 {%0, %1, %2, %3, %4, %5, %6, %7, %8, %9, %10, %11, %12, %13, %14, %15, %16, %17, %18, %19, %20, %21, %22, %23, %24, %25, %26, %27}, {a0, a1, a2, a3}, d, 1, 1, 1, 0;\nwgmma.commit_group.sync.aligned;\nwgmma.wait_group.sync.aligned 1;\nmov.b32 b2, a1;\nmov.b32 b0, t0;\nmov.b32 b3, t0;\nmov.b32 b1, t1;\n"
        "ld.shared.b32 t0, [%64+5120];\nld.shared.b32 t1, [%64+5248];\nadd.s64 d, %65, 152;\nwgmma.fence.sync.aligned;\nwgmma.mma_async.sync.aligned.m64n56k16.f32.bf16.bf16 {%0, %1, %2, %3, %4, %5, %6, %7, %8, %9, %10, %11, %12, %13, %14, %15, %16, %17, %18, %19, %20, %21, %22, %23, %24, %25, %26, %27}, {b0, b1, b2, b3}, d, 1, 1, 1, 0;\nwgmma.commit_group.sync.aligned;\nwgmma.wait_group.sync.aligned 1;\nmov.b32 a2, b1;\nmov.b32 a0, t0;\nmov.b32 a3, t0;\nmov.b32 a1, t1;\n"
        "ld.shared.b32 t0, [%64+5376];\nld.shared.b32 t1, [%64+5504];\nadd.s64 d, %65, 160;\nwgmma.fence.sync.aligned;\nwgmma.mma_async.sync.aligned.m64n48k16.f32.bf16.bf16 {%0, %1, %2, %3, %4, %5, %6, %7, %8, %9, %10, %11, %12, %13, %14, %15, %16, %17, %18, %19, %20, %21, %22, %23}, {a0, a1, a2, a3}, d, 1, 1, 1, 0;\nwgmma.commit_group.sync.aligned;\nwgmma.wait_group.sync.aligned 1;\nmov.b32 b2, a1;\nmov.b32 b0, t0;\nmov.b32 b3, t0;\nmov.b32 b1, t1;\n"
        "ld.shared.b32 t0, [%64+5632];\nld.shared.b32 t1, [%64+5760];\nadd.s64 d, %65, 168;\nwgmma.fence.sync.aligned;\nwgmma.mma_async.sync.aligned.m64n48k16.f32.bf16.bf16 {%0, %1, %2, %3, %4, %5, %6, %7, %8, %9, %10, %11, %12, %13, %14, %15, %16, %17, %18, %19, %20, %21, %22, %23}, {b0, b1, b2, b3}, d, 1, 1, 1, 0;\nwgmma.commit_group.sync.aligned;\nwgmma.wait_group.sync.aligned 1;\nmov.b32 a2, b1;\nmov.b32 a0, t0;\nmov.b32 a3, t0;\nmov.b32 a1, t1;\n"
        "ld.shared.b32 t0, [%64+5888];\nld.shared.b32 t1, [%64+6016];\nadd.s64 d, %65, 176;\nwgmma.fence.sync.aligned;\nwgmma.mma_async.sync.aligned.m64n40k16.f32.bf16.bf16 {%0, %1, %2, %3, %4, %5, %6, %7, %8, %9, %10, %11, %12, %13, %14, %15, %16, %17, %18, %19}, {a0, a1, a2, a3}, d, 1, 1, 1, 0;\nwgmma.commit_group.sync.aligned;\nwgmma.wait_group.sync.aligned 1;\nmov.b32 b2, a1;\nmov.b32 b0, t0;\nmov.b32 b3, t0;\nmov.b32 b1, t1;\n"
        "ld.shared.b32 t0, [%64+6144];\nld.shared.b32 t1, [%64+6272];\nadd.s64 d, %65, 184;\nwgmma.fence.sync.aligned;\nwgmma.mma_async.sync.aligned.m64n40k16.f32.bf16.bf16 {%0, %1, %2, %3, %4, %5, %6, %7, %8, %9, %10, %11, %12, %13, %14, %15, %16, %17, %18, %19}, {b0, b1, b2, b3}, d, 1, 1, 1, 0;\nwgmma.commit_group.sync.aligned;\nwgmma.wait_group.sync.aligned 1;\nmov.b32 a2, b1;\nmov.b32 a0, t0;\nmov.b32 a3, t0;\nmov.b32 a1, t1;\n"
        "ld.shared.b32 t0, [%64+6400];\nld.shared.b32 t1, [%64+6528];\nadd.s64 d, %65, 192;\nwgmma.fence.sync.aligned;\nwgmma.mma_async.sync.aligned.m64n32k16.f32.bf16.bf16 {%0, %1, %2, %3, %4, %5, %6, %7, %8, %9, %10, %11, %12, %13, %14, %15}, {a0, a1, a2, a3}, d, 1, 1, 1, 0;\nwgmma.commit_group.sync.aligned;\nwgmma.wait_group.sync.aligned 1;\nmov.b32 b2, a1;\nmov.b32 b0, t0;\nmov.b32 b3, t0;\nmov.b32 b1, t1;\n"
        "ld.shared.b32 t0, [%64+6656];\nld.shared.b32 t1, [%64+6784];\nadd.s64 d, %65, 200;\nwgmma.fence.sync.aligned;\nwgmma.mma_async.sync.aligned.m64n32k16.f32.bf16.bf16 {%0, %1, %2, %3, %4, %5, %6, %7, %8, %9, %10, %11, %12, %13, %14, %15}, {b0, b1, b2, b3}, d, 1, 1, 1, 0;\nwgmma.commit_group.sync.aligned;\nwgmma.wait_group.sync.aligned 1;\nmov.b32 a2, b1;\nmov.b32 a0, t0;\nmov.b32 a3, t0;\nmov.b32 a1, t1;\n"
        "ld.shared.b32 t0, [%64+6912];\nld.shared.b32 t1, [%64+7040];\nadd.s64 d, %65, 208;\nwgmma.fence.sync.aligned;\nwgmma.mma_async.sync.aligned.m64n24k16.f32.bf16.bf16 {%0, %1, %2, %3, %4, %5, %6, %7, %8, %9, %10, %11}, {a0, a1, a2, a3}, d, 1, 1, 1, 0;\nwgmma.commit_group.sync.aligned;\nwgmma.wait_group.sync.aligned 1;\nmov.b32 b2, a1;\nmov.b32 b0, t0;\nmov.b32 b3, t0;\nmov.b32 b1, t1;\n"
        "ld.shared.b32 t0, [%64+7168];\nld.shared.b32 t1, [%64+7296];\nadd.s64 d, %65, 216;\nwgmma.fence.sync.aligned;\nwgmma.mma_async.sync.aligned.m64n24k16.f32.bf16.bf16 {%0, %1, %2, %3, %4, %5, %6, %7, %8, %9, %10, %11}, {b0, b1, b2, b3}, d, 1, 1, 1, 0;\nwgmma.commit_group.sync.aligned;\nwgmma.wait_group.sync.aligned 1;\nmov.b32 a2, b1;\nmov.b32 a0, t0;\nmov.b32 a3, t0;\nmov.b32 a1, t1;\n"
        "ld.shared.b32 t0, [%64+7424];\nld.shared.b32 t1, [%64+7552];\nadd.s64 d, %65, 224;\nwgmma.fence.sync.aligned;\nwgmma.mma_async.sync.aligned.m64n16k16.f32.bf16.bf16 {%0, %1, %2, %3, %4, %5, %6, %7}, {a0, a1, a2, a3}, d, 1, 1, 1, 0;\nwgmma.commit_group.sync.aligned;\nwgmma.wait_group.sync.aligned 1;\nmov.b32 b2, a1;\nmov.b32 b0, t0;\nmov.b32 b3, t0;\nmov.b32 b1, t1;\n"
        "ld.shared.b32 t0, [%64+7680];\nld.shared.b32 t1, [%64+7808];\nadd.s64 d, %65, 232;\nwgmma.fence.sync.aligned;\nwgmma.mma_async.sync.aligned.m64n16k16.f32.bf16.bf16 {%0, %1, %2, %3, %4, %5, %6, %7}, {b0, b1, b2, b3}, d, 1, 1, 1, 0;\nwgmma.commit_group.sync.aligned;\nwgmma.wait_group.sync.aligned 1;\nmov.b32 a2, b1;\nmov.b32 a0, t0;\nmov.b32 a3, t0;\nmov.b32 a1, t1;\n"
        "ld.shared.b32 t0, [%64+7936];\nld.shared.b32 t1, [%64+8064];\nadd.s64 d, %65, 240;\nwgmma.fence.sync.aligned;\nwgmma.mma_async.sync.aligned.m64n8k16.f32.bf16.bf16 {%0, %1, %2, %3}, {a0, a1, a2, a3}, d, 1, 1, 1, 0;\nwgmma.commit_group.sync.aligned;\nwgmma.wait_group.sync.aligned 1;\nmov.b32 b2, a1;\nmov.b32 b0, t0;\nmov.b32 b3, t0;\nmov.b32 b1, t1;\n"
        "add.s64 d, %65, 248;\nwgmma.fence.sync.aligned;\nwgmma.mma_async.sync.aligned.m64n8k16.f32.bf16.bf16 {%0, %1, %2, %3}, {b0, b1, b2, b3}, d, 1, 1, 1, 0;\nwgmma.commit_group.sync.aligned;\nwgmma.wait_group.sync.aligned 0;\n"
        "}" : "+f"(d[0]), "+f"(d[1]), "+f"(d[2]), "+f"(d[3]), "+f"(d[4]), "+f"(d[5]), "+f"(d[6]), "+f"(d[7]), "+f"(d[8]), "+f"(d[9]), "+f"(d[10]), "+f"(d[11]), "+f"(d[12]), "+f"(d[13]), "+f"(d[14]), "+f"(d[15]), "+f"(d[16]), "+f"(d[17]), "+f"(d[18]), "+f"(d[19]), "+f"(d[20]), "+f"(d[21]), "+f"(d[22]), "+f"(d[23]), "+f"(d[24]), "+f"(d[25]), "+f"(d[26]), "+f"(d[27]), "+f"(d[28]), "+f"(d[29]), "+f"(d[30]), "+f"(d[31]), "+f"(d[32]), "+f"(d[33]), "+f"(d[34]), "+f"(d[35]), "+f"(d[36]), "+f"(d[37]), "+f"(d[38]), "+f"(d[39]), "+f"(d[40]), "+f"(d[41]), "+f"(d[42]), "+f"(d[43]), "+f"(d[44]), "+f"(d[45]), "+f"(d[46]), "+f"(d[47]), "+f"(d[48]), "+f"(d[49]), "+f"(d[50]), "+f"(d[51]), "+f"(d[52]), "+f"(d[53]), "+f"(d[54]), "+f"(d[55]), "+f"(d[56]), "+f"(d[57]), "+f"(d[58]), "+f"(d[59]), "+f"(d[60]), "+f"(d[61]), "+f"(d[62]), "+f"(d[63]) : "r"(pa), "l"(db) : "memory");
}
__device__ __forceinline__ void wgmma_rs80(float (&d)[40], uint32_t a0, uint32_t a1, uint32_t a2, uint32_t a3, uint64_t db, int sc) {
    asm volatile("{\n.reg .pred p;\nsetp.ne.b32 p, %45, 0;\n"
        "wgmma.mma_async.sync.aligned.m64n80k16.f32.bf16.bf16 {%0, %1, %2, %3, %4, %5, %6, %7, %8, %9, %10, %11, %12, %13, %14, %15, %16, %17, %18, %19, %20, %21, %22, %23, %24, %25, %26, %27, %28, %29, %30, %31, %32, %33, %34, %35, %36, %37, %38, %39}, {%40, %41, %42, %43}, %44, p, 1, 1, 1;\n}\n"
        : "+f"(d[0]), "+f"(d[1]), "+f"(d[2]), "+f"(d[3]), "+f"(d[4]), "+f"(d[5]), "+f"(d[6]), "+f"(d[7]), "+f"(d[8]), "+f"(d[9]), "+f"(d[10]), "+f"(d[11]), "+f"(d[12]), "+f"(d[13]), "+f"(d[14]), "+f"(d[15]), "+f"(d[16]), "+f"(d[17]), "+f"(d[18]), "+f"(d[19]), "+f"(d[20]), "+f"(d[21]), "+f"(d[22]), "+f"(d[23]), "+f"(d[24]), "+f"(d[25]), "+f"(d[26]), "+f"(d[27]), "+f"(d[28]), "+f"(d[29]), "+f"(d[30]), "+f"(d[31]), "+f"(d[32]), "+f"(d[33]), "+f"(d[34]), "+f"(d[35]), "+f"(d[36]), "+f"(d[37]), "+f"(d[38]), "+f"(d[39]) : "r"(a0), "r"(a1), "r"(a2), "r"(a3), "l"(db), "r"(sc));
}
__device__ __forceinline__ void wgmma_ss80(float (&d)[40], uint64_t da, uint64_t db, int sc) {
    asm volatile("{\n.reg .pred p;\nsetp.ne.b32 p, %42, 0;\n"
        "wgmma.mma_async.sync.aligned.m64n80k16.f32.bf16.bf16 {%0, %1, %2, %3, %4, %5, %6, %7, %8, %9, %10, %11, %12, %13, %14, %15, %16, %17, %18, %19, %20, %21, %22, %23, %24, %25, %26, %27, %28, %29, %30, %31, %32, %33, %34, %35, %36, %37, %38, %39}, %40, %41, p, 1, 1, 0, 1;\n}\n"
        : "+f"(d[0]), "+f"(d[1]), "+f"(d[2]), "+f"(d[3]), "+f"(d[4]), "+f"(d[5]), "+f"(d[6]), "+f"(d[7]), "+f"(d[8]), "+f"(d[9]), "+f"(d[10]), "+f"(d[11]), "+f"(d[12]), "+f"(d[13]), "+f"(d[14]), "+f"(d[15]), "+f"(d[16]), "+f"(d[17]), "+f"(d[18]), "+f"(d[19]), "+f"(d[20]), "+f"(d[21]), "+f"(d[22]), "+f"(d[23]), "+f"(d[24]), "+f"(d[25]), "+f"(d[26]), "+f"(d[27]), "+f"(d[28]), "+f"(d[29]), "+f"(d[30]), "+f"(d[31]), "+f"(d[32]), "+f"(d[33]), "+f"(d[34]), "+f"(d[35]), "+f"(d[36]), "+f"(d[37]), "+f"(d[38]), "+f"(d[39]) : "l"(da), "l"(db), "r"(sc));
}
__device__ __forceinline__ void wgmma_ss80t(float (&d)[40], uint64_t da, uint64_t db, int sc) {
    asm volatile("{\n.reg .pred p;\nsetp.ne.b32 p, %42, 0;\n"
        "wgmma.mma_async.sync.aligned.m64n80k16.f32.bf16.bf16 {%0, %1, %2, %3, %4, %5, %6, %7, %8, %9, %10, %11, %12, %13, %14, %15, %16, %17, %18, %19, %20, %21, %22, %23, %24, %25, %26, %27, %28, %29, %30, %31, %32, %33, %34, %35, %36, %37, %38, %39}, %40, %41, p, 1, 1, 1, 1;\n}\n"
        : "+f"(d[0]), "+f"(d[1]), "+f"(d[2]), "+f"(d[3]), "+f"(d[4]), "+f"(d[5]), "+f"(d[6]), "+f"(d[7]), "+f"(d[8]), "+f"(d[9]), "+f"(d[10]), "+f"(d[11]), "+f"(d[12]), "+f"(d[13]), "+f"(d[14]), "+f"(d[15]), "+f"(d[16]), "+f"(d[17]), "+f"(d[18]), "+f"(d[19]), "+f"(d[20]), "+f"(d[21]), "+f"(d[22]), "+f"(d[23]), "+f"(d[24]), "+f"(d[25]), "+f"(d[26]), "+f"(d[27]), "+f"(d[28]), "+f"(d[29]), "+f"(d[30]), "+f"(d[31]), "+f"(d[32]), "+f"(d[33]), "+f"(d[34]), "+f"(d[35]), "+f"(d[36]), "+f"(d[37]), "+f"(d[38]), "+f"(d[39]) : "l"(da), "l"(db), "r"(sc));
}
__device__ __forceinline__ void wgmma_ss8_ta(float (&d)[4], uint64_t da, uint64_t db, int sc) {
    asm volatile("{\n.reg .pred p;\nsetp.ne.b32 p, %6, 0;\n"
        "wgmma.mma_async.sync.aligned.m64n8k16.f32.bf16.bf16 {%0, %1, %2, %3}, %4, %5, p, 1, 1, 1, 0;\n}\n"
        : "+f"(d[0]), "+f"(d[1]), "+f"(d[2]), "+f"(d[3]) : "l"(da), "l"(db), "r"(sc));
}
__device__ __forceinline__ void wgmma_rs8(float (&d)[4], uint32_t a0, uint32_t a1, uint32_t a2, uint32_t a3, uint64_t db, int sc) {
    asm volatile("{\n.reg .pred p;\nsetp.ne.b32 p, %9, 0;\n"
        "wgmma.mma_async.sync.aligned.m64n8k16.f32.bf16.bf16 {%0, %1, %2, %3}, {%4, %5, %6, %7}, %8, p, 1, 1, 0;\n}\n"
        : "+f"(d[0]), "+f"(d[1]), "+f"(d[2]), "+f"(d[3]) : "r"(a0), "r"(a1), "r"(a2), "r"(a3), "l"(db), "r"(sc));
}
__device__ __forceinline__ void wgmma_rs128(float (&d)[64], uint32_t a0, uint32_t a1, uint32_t a2, uint32_t a3, uint64_t db, int sc) {
    asm volatile("{\n.reg .pred p;\nsetp.ne.b32 p, %69, 0;\n"
        "wgmma.mma_async.sync.aligned.m64n128k16.f32.bf16.bf16 {%0, %1, %2, %3, %4, %5, %6, %7, %8, %9, %10, %11, %12, %13, %14, %15, %16, %17, %18, %19, %20, %21, %22, %23, %24, %25, %26, %27, %28, %29, %30, %31, %32, %33, %34, %35, %36, %37, %38, %39, %40, %41, %42, %43, %44, %45, %46, %47, %48, %49, %50, %51, %52, %53, %54, %55, %56, %57, %58, %59, %60, %61, %62, %63}, {%64, %65, %66, %67}, %68, p, 1, 1, 1;\n}\n"
        : "+f"(d[0]), "+f"(d[1]), "+f"(d[2]), "+f"(d[3]), "+f"(d[4]), "+f"(d[5]), "+f"(d[6]), "+f"(d[7]), "+f"(d[8]), "+f"(d[9]), "+f"(d[10]), "+f"(d[11]), "+f"(d[12]), "+f"(d[13]), "+f"(d[14]), "+f"(d[15]), "+f"(d[16]), "+f"(d[17]), "+f"(d[18]), "+f"(d[19]), "+f"(d[20]), "+f"(d[21]), "+f"(d[22]), "+f"(d[23]), "+f"(d[24]), "+f"(d[25]), "+f"(d[26]), "+f"(d[27]), "+f"(d[28]), "+f"(d[29]), "+f"(d[30]), "+f"(d[31]), "+f"(d[32]), "+f"(d[33]), "+f"(d[34]), "+f"(d[35]), "+f"(d[36]), "+f"(d[37]), "+f"(d[38]), "+f"(d[39]), "+f"(d[40]), "+f"(d[41]), "+f"(d[42]), "+f"(d[43]), "+f"(d[44]), "+f"(d[45]), "+f"(d[46]), "+f"(d[47]), "+f"(d[48]), "+f"(d[49]), "+f"(d[50]), "+f"(d[51]), "+f"(d[52]), "+f"(d[53]), "+f"(d[54]), "+f"(d[55]), "+f"(d[56]), "+f"(d[57]), "+f"(d[58]), "+f"(d[59]), "+f"(d[60]), "+f"(d[61]), "+f"(d[62]), "+f"(d[63]) : "r"(a0), "r"(a1), "r"(a2), "r"(a3), "l"(db), "r"(sc));
}
__device__ __forceinline__ void wgmma_rs88(float (&d)[44], uint32_t a0, uint32_t a1, uint32_t a2, uint32_t a3, uint64_t db, int sc) {
    asm volatile("{\n.reg .pred p;\nsetp.ne.b32 p, %49, 0;\n"
        "wgmma.mma_async.sync.aligned.m64n88k16.f32.bf16.bf16 {%0, %1, %2, %3, %4, %5, %6, %7, %8, %9, %10, %11, %12, %13, %14, %15, %16, %17, %18, %19, %20, %21, %22, %23, %24, %25, %26, %27, %28, %29, %30, %31, %32, %33, %34, %35, %36, %37, %38, %39, %40, %41, %42, %43}, {%44, %45, %46, %47}, %48, p, 1, 1, 1;\n}\n"
        : "+f"(d[0]), "+f"(d[1]), "+f"(d[2]), "+f"(d[3]), "+f"(d[4]), "+f"(d[5]), "+f"(d[6]), "+f"(d[7]), "+f"(d[8]), "+f"(d[9]), "+f"(d[10]), "+f"(d[11]), "+f"(d[12]), "+f"(d[13]), "+f"(d[14]), "+f"(d[15]), "+f"(d[16]), "+f"(d[17]), "+f"(d[18]), "+f"(d[19]), "+f"(d[20]), "+f"(d[21]), "+f"(d[22]), "+f"(d[23]), "+f"(d[24]), "+f"(d[25]), "+f"(d[26]), "+f"(d[27]), "+f"(d[28]), "+f"(d[29]), "+f"(d[30]), "+f"(d[31]), "+f"(d[32]), "+f"(d[33]), "+f"(d[34]), "+f"(d[35]), "+f"(d[36]), "+f"(d[37]), "+f"(d[38]), "+f"(d[39]), "+f"(d[40]), "+f"(d[41]), "+f"(d[42]), "+f"(d[43]) : "r"(a0), "r"(a1), "r"(a2), "r"(a3), "l"(db), "r"(sc));
}
__device__ __forceinline__ void wgmma_rs128k(float (&d)[64], uint32_t a0, uint32_t a1, uint32_t a2, uint32_t a3, uint64_t db, int sc) {
    asm volatile("{\n.reg .pred p;\nsetp.ne.b32 p, %69, 0;\n"
        "wgmma.mma_async.sync.aligned.m64n128k16.f32.bf16.bf16 {%0, %1, %2, %3, %4, %5, %6, %7, %8, %9, %10, %11, %12, %13, %14, %15, %16, %17, %18, %19, %20, %21, %22, %23, %24, %25, %26, %27, %28, %29, %30, %31, %32, %33, %34, %35, %36, %37, %38, %39, %40, %41, %42, %43, %44, %45, %46, %47, %48, %49, %50, %51, %52, %53, %54, %55, %56, %57, %58, %59, %60, %61, %62, %63}, {%64, %65, %66, %67}, %68, p, 1, 1, 0;\n}\n"
        : "+f"(d[0]), "+f"(d[1]), "+f"(d[2]), "+f"(d[3]), "+f"(d[4]), "+f"(d[5]), "+f"(d[6]), "+f"(d[7]), "+f"(d[8]), "+f"(d[9]), "+f"(d[10]), "+f"(d[11]), "+f"(d[12]), "+f"(d[13]), "+f"(d[14]), "+f"(d[15]), "+f"(d[16]), "+f"(d[17]), "+f"(d[18]), "+f"(d[19]), "+f"(d[20]), "+f"(d[21]), "+f"(d[22]), "+f"(d[23]), "+f"(d[24]), "+f"(d[25]), "+f"(d[26]), "+f"(d[27]), "+f"(d[28]), "+f"(d[29]), "+f"(d[30]), "+f"(d[31]), "+f"(d[32]), "+f"(d[33]), "+f"(d[34]), "+f"(d[35]), "+f"(d[36]), "+f"(d[37]), "+f"(d[38]), "+f"(d[39]), "+f"(d[40]), "+f"(d[41]), "+f"(d[42]), "+f"(d[43]), "+f"(d[44]), "+f"(d[45]), "+f"(d[46]), "+f"(d[47]), "+f"(d[48]), "+f"(d[49]), "+f"(d[50]), "+f"(d[51]), "+f"(d[52]), "+f"(d[53]), "+f"(d[54]), "+f"(d[55]), "+f"(d[56]), "+f"(d[57]), "+f"(d[58]), "+f"(d[59]), "+f"(d[60]), "+f"(d[61]), "+f"(d[62]), "+f"(d[63]) : "r"(a0), "r"(a1), "r"(a2), "r"(a3), "l"(db), "r"(sc));
}
__device__ __forceinline__ void wgmma_rs88k(float (&d)[44], uint32_t a0, uint32_t a1, uint32_t a2, uint32_t a3, uint64_t db, int sc) {
    asm volatile("{\n.reg .pred p;\nsetp.ne.b32 p, %49, 0;\n"
        "wgmma.mma_async.sync.aligned.m64n88k16.f32.bf16.bf16 {%0, %1, %2, %3, %4, %5, %6, %7, %8, %9, %10, %11, %12, %13, %14, %15, %16, %17, %18, %19, %20, %21, %22, %23, %24, %25, %26, %27, %28, %29, %30, %31, %32, %33, %34, %35, %36, %37, %38, %39, %40, %41, %42, %43}, {%44, %45, %46, %47}, %48, p, 1, 1, 0;\n}\n"
        : "+f"(d[0]), "+f"(d[1]), "+f"(d[2]), "+f"(d[3]), "+f"(d[4]), "+f"(d[5]), "+f"(d[6]), "+f"(d[7]), "+f"(d[8]), "+f"(d[9]), "+f"(d[10]), "+f"(d[11]), "+f"(d[12]), "+f"(d[13]), "+f"(d[14]), "+f"(d[15]), "+f"(d[16]), "+f"(d[17]), "+f"(d[18]), "+f"(d[19]), "+f"(d[20]), "+f"(d[21]), "+f"(d[22]), "+f"(d[23]), "+f"(d[24]), "+f"(d[25]), "+f"(d[26]), "+f"(d[27]), "+f"(d[28]), "+f"(d[29]), "+f"(d[30]), "+f"(d[31]), "+f"(d[32]), "+f"(d[33]), "+f"(d[34]), "+f"(d[35]), "+f"(d[36]), "+f"(d[37]), "+f"(d[38]), "+f"(d[39]), "+f"(d[40]), "+f"(d[41]), "+f"(d[42]), "+f"(d[43]) : "r"(a0), "r"(a1), "r"(a2), "r"(a3), "l"(db), "r"(sc));
}
__device__ __forceinline__ void wgmma_rs80k(float (&d)[40], uint32_t a0, uint32_t a1, uint32_t a2, uint32_t a3, uint64_t db, int sc) {
    asm volatile("{\n.reg .pred p;\nsetp.ne.b32 p, %45, 0;\n"
        "wgmma.mma_async.sync.aligned.m64n80k16.f32.bf16.bf16 {%0, %1, %2, %3, %4, %5, %6, %7, %8, %9, %10, %11, %12, %13, %14, %15, %16, %17, %18, %19, %20, %21, %22, %23, %24, %25, %26, %27, %28, %29, %30, %31, %32, %33, %34, %35, %36, %37, %38, %39}, {%40, %41, %42, %43}, %44, p, 1, 1, 0;\n}\n"
        : "+f"(d[0]), "+f"(d[1]), "+f"(d[2]), "+f"(d[3]), "+f"(d[4]), "+f"(d[5]), "+f"(d[6]), "+f"(d[7]), "+f"(d[8]), "+f"(d[9]), "+f"(d[10]), "+f"(d[11]), "+f"(d[12]), "+f"(d[13]), "+f"(d[14]), "+f"(d[15]), "+f"(d[16]), "+f"(d[17]), "+f"(d[18]), "+f"(d[19]), "+f"(d[20]), "+f"(d[21]), "+f"(d[22]), "+f"(d[23]), "+f"(d[24]), "+f"(d[25]), "+f"(d[26]), "+f"(d[27]), "+f"(d[28]), "+f"(d[29]), "+f"(d[30]), "+f"(d[31]), "+f"(d[32]), "+f"(d[33]), "+f"(d[34]), "+f"(d[35]), "+f"(d[36]), "+f"(d[37]), "+f"(d[38]), "+f"(d[39]) : "r"(a0), "r"(a1), "r"(a2), "r"(a3), "l"(db), "r"(sc));
}
__device__ __forceinline__ void wgmma_rs64(float (&d)[32], uint32_t a0, uint32_t a1, uint32_t a2, uint32_t a3, uint64_t db, int sc) {
    asm volatile("{\n.reg .pred p;\nsetp.ne.b32 p, %37, 0;\n"
        "wgmma.mma_async.sync.aligned.m64n64k16.f32.bf16.bf16 {%0, %1, %2, %3, %4, %5, %6, %7, %8, %9, %10, %11, %12, %13, %14, %15, %16, %17, %18, %19, %20, %21, %22, %23, %24, %25, %26, %27, %28, %29, %30, %31}, {%32, %33, %34, %35}, %36, p, 1, 1, 1;\n}\n"
        : "+f"(d[0]), "+f"(d[1]), "+f"(d[2]), "+f"(d[3]), "+f"(d[4]), "+f"(d[5]), "+f"(d[6]), "+f"(d[7]), "+f"(d[8]), "+f"(d[9]), "+f"(d[10]), "+f"(d[11]), "+f"(d[12]), "+f"(d[13]), "+f"(d[14]), "+f"(d[15]), "+f"(d[16]), "+f"(d[17]), "+f"(d[18]), "+f"(d[19]), "+f"(d[20]), "+f"(d[21]), "+f"(d[22]), "+f"(d[23]), "+f"(d[24]), "+f"(d[25]), "+f"(d[26]), "+f"(d[27]), "+f"(d[28]), "+f"(d[29]), "+f"(d[30]), "+f"(d[31]) : "r"(a0), "r"(a1), "r"(a2), "r"(a3), "l"(db), "r"(sc));
}

__device__ __forceinline__ uint64_t mkdesc(uint32_t lo) { return ((uint64_t)0x40000040u << 32) | lo; }
template <int F> __device__ __forceinline__ uint32_t lop3(uint32_t a, uint32_t b, uint32_t c) { uint32_t r; asm("lop3.b32 %0, %1, %2, %3, %4;" : "=r"(r) : "r"(a), "r"(b), "r"(c), "n"(F)); return r; }
__device__ __forceinline__ void stg128_tag(void* p, uint32_t x, uint32_t y, uint32_t z, uint32_t u, uint32_t ep, int w) {
    stg128(p, lop3<0xB8>(x, w == 0, ep), lop3<0xB8>(y, w == 1, ep), lop3<0xB8>(z, w == 2, ep), lop3<0xB8>(u, w == 3, ep));
}
__device__ __forceinline__ uint32_t tag(uint32_t w, uint32_t ep) { asm("lop3.b32 %0, %0, 1, %1, 0xB8;" : "+r"(w) : "r"(ep)); return w; }
template <int N> __device__ __forceinline__ void pack_part(uint32_t (&p)[32], const float (&v)[N], uint32_t ep) {
#pragma unroll
    for (int i = 0; i < N / 2; i++) p[i] = (i & 3) ? pack2(v[2 * i], v[2 * i + 1]) : tag(pack2(v[2 * i], v[2 * i + 1]), ep);
#pragma unroll
    for (int i = 0; i < N / 2; i++) asm volatile("" : "+r"(p[i]));
}
__device__ __forceinline__ void st_part(uint4* p, const uint32_t* v) {
    asm volatile("{\n.reg .b64 l, h;\n.reg .b128 q;\nmov.b64 l, {%1, %2};\nmov.b64 h, {%3, %4};\nmov.b128 q, {l, h};\nst.relaxed.gpu.global.b128 [%0], q;\n}"
                 ::"l"(p), "r"(v[0]), "r"(v[1]), "r"(v[2]), "r"(v[3]) : "memory");
}
__device__ __forceinline__ void st_peer(uint32_t a, uint32_t x, uint32_t y, uint32_t z, uint32_t w, uint32_t bar) {
    asm volatile("st.async.shared::cluster.mbarrier::complete_tx::bytes.v4.b32 [%0], {%1, %2, %3, %4}, [%5];" ::"r"(a), "r"(x), "r"(y), "r"(z), "r"(w), "r"(bar) : "memory");
}
__device__ __forceinline__ int g4_block(int c, int j) { return c ? j ^ (8 - 2 * c) : 8 + (j & 1); }
__device__ __forceinline__ uint32_t recv_off(int w) { return w ? OFF_XR : OFF_REM; }
__device__ __forceinline__ uint4 ld_part(const void* p) {
    uint4 v;
    asm volatile("{\n.reg .b64 l, h;\n.reg .b128 q;\nld.relaxed.gpu.global.b128 q, [%4];\nmov.b128 {l, h}, q;\nmov.b64 {%0, %1}, l;\nmov.b64 {%2, %3}, h;\n}"
                 : "=r"(v.x), "=r"(v.y), "=r"(v.z), "=r"(v.w) : "l"(p) : "memory");
    return v;
}
__device__ __forceinline__ void ld_part4(uint4 (&u)[4], const uint4* p, int st) {
#pragma unroll
    for (int i = 0; i < 4; i++) u[i] = ld_part(p + i * st);
}
__device__ __forceinline__ uint32_t stale4(const uint4 (&u)[4], uint32_t ep) { return lop3<0x7E>(u[0].x, ep, u[1].x) | lop3<0x7E>(u[2].x, ep, u[3].x); }
__device__ __forceinline__ uint4 add2(uint4 a, uint4 b) { return make_uint4(add2(a.x, b.x), add2(a.y, b.y), add2(a.z, b.z), add2(a.w, b.w)); }
__device__ __forceinline__ uint4 fin16(uint4 v, uint4 b, uint4 c) { return make_uint4(fma2(c.x, v.x, b.x), fma2(c.y, v.y, b.y), fma2(c.z, v.z, b.z), fma2(c.w, v.w, b.w)); }
__device__ __forceinline__ uint4 scale16(float2 c, float2 d, float r0, float r1) {
    return make_uint4(pack2(c.x * r0, c.y * r0), pack2(c.x * r1, c.y * r1), pack2(d.x * r0, d.y * r0), pack2(d.x * r1, d.y * r1));
}
__device__ __forceinline__ uint32_t split2(float x) { const float h = rbf(x); return pack2(h, x - h); }
__device__ __forceinline__ uint32_t b80_desc(uint32_t dsb, uint32_t wn, uint32_t rn, uint32_t h) {
    const uint32_t wb = dsb + OFF_W + (wn & 7) * 16384 + h * 8192, rm = dsb + OFF_REM + rn * 4096 + h * 2048;
    return (wb >> 4) | ((rm - wb) << 12);
}
constexpr int64_t B80_STEP = 128 - (126 << 16), B80_HALF = 512 - (384 << 16);
constexpr uint32_t ring_mask(int L) {
    uint32_t m = 0;
    for (int i = L; i < 20; i++) m |= (uint32_t)(i >= 20 - L || !((i - L) & 1)) << i;
    return m;
}
constexpr uint32_t M0 = ring_mask(LEAD1), M1 = ring_mask(10), M2 = ring_mask(XLEAD);
__device__ __forceinline__ uint32_t ring_pos(int w, int n, int L) { return w ? (n < 10 - L ? L + 2 * n : 10 + n) : (n < L ? n : 2 * n - L + 1); }
__device__ __forceinline__ int g1_block(int n, int j) { return n < 5 ? 2 * n + (j & 1) : 2 * n - 9 - (j & 1); }

__device__ __forceinline__ void load_tile(const Maps& mp, uint32_t dst, int e, int tile, int kb, int j, uint32_t bar) {
    mbar_expect(bar, 8192);
    tma_ld2(dst, &mp.x[e], 64 * (e == 0 ? tile : e == 1 ? kb : 0), 64 * (e == 0 ? g1_block(kb, j) : e == 1 ? tile : 10 * tile + kb), bar);
}

template <int OCT>
__device__ __forceinline__ void gemv_tile(float (&d)[4], uint32_t a, uint32_t b, int kb0) {
    uint32_t alo = ((a & 0x3FFFF) >> 4) | 0x10000u, blo_ = ((b & 0x3FFFF) >> 4) | (OCT << 16);
#pragma unroll 1
    for (int s = 0; s < 20; s += 4) {
        const int kb = kb0 + (s >> 2);
        const uint32_t bk = blo_ + (OCT == 7 ? (kb & 1) * 288 + (kb >> 1) * 56 : kb * 64);
        wg_fence();
#pragma unroll
        for (int q = 0; q < 4; q++) wgmma_ss8_ta(d, mkdesc(alo + (s + q) * 128), ((uint64_t)8 << 32) | (bk + q * 2 * OCT), s + q);
        wg_commit();
    }
    wg_wait<0>();
    reg_fence(d);
}

__device__ __forceinline__ void flush_tile(uint32_t st, bf16* dst, int u) {
#pragma unroll
    for (int i = 0; i < 2; i++) {
        const int idx = u + 320 * i, row = idx >> 3, c = idx & 7;
        stg128(dst + (size_t)row * S_ + 8 * c, lds128(st + row * 128 + ((c ^ ((row >> 1) & 7)) << 4)));
    }
}

__device__ __forceinline__ int tid_now() { int t; asm volatile("mov.u32 %0, %%tid.x;" : "=r"(t)); return t; }
__device__ __forceinline__ float zscale(float c) { return c == 0.f ? 0x1p-30f : c; }
__device__ __forceinline__ bool bar_any(int id, bool p) {
    uint32_t r;
    asm volatile("{\n.reg .pred a, b;\nsetp.ne.u32 a, %2, 0;\nbarrier.red.or.pred.aligned b, %1, 128, a;\nselp.u32 %0, 1, 0, b;\n}" : "=r"(r) : "r"(id), "r"((uint32_t)p) : "memory");
    return r != 0;
}

__global__ void __cluster_dims__(2, 1, 1) __launch_bounds__(NTHR, 1) fused_kernel(const __grid_constant__ Ptrs pp, bf16* __restrict__ out, const __grid_constant__ Maps mp) {
    extern __shared__ __align__(1024) uint8_t smem_raw[];
    const uint32_t sb = s2u(smem_raw), bars = sb + M_BAR, dsb = sb & 0x3FFFF;
    const int id = blockIdx.x, warp = __shfl_sync(0xffffffffu, (int)threadIdx.x >> 5, 0), wg = warp >> 2;
    const uint32_t c0 = clock_lo();
#define TIDS const int tid = tid_now(), lane = tid & 31, wt = tid & 127, g = lane >> 2, t = lane & 3; (void)wt; (void)g; (void)t;
    TS(threadIdx.x == 0, 0) TG(threadIdx.x == 0, 62)

    if (id >= 128) {
        TIDS
        if (sb & 1023) __trap();
        const int hs = id - 128;
        constexpr int H_B = 204800;
        static_assert(H_B + TAB_BYTES + 8 * VEC_BYTES <= OFF_M, "helper map");
        if (warp < 10 && elect()) { mbar_init(bars + warp * 8, 1); mbar_init(bars + 80 + warp * 8, 1); asm volatile("fence.mbarrier_init.release.cluster;" ::: "memory"); }
        __syncthreads();
        const uint32_t e0 = ld_cold(&g_epoch);
        wait_clock(c0, HELP_T);
        uint4 wr[10];
#pragma unroll
        for (int u = 0; u < 10; u++) wr[u] = ldg128(((hs >> 1) ? pp.w2 : pp.w1) + (size_t)(320 * (hs & 1) + (tid >> 4) + 32 * u) * D_ + 512 + 8 * (tid & 15));
        {
            const int r = tid >> 4, c = tid & 15;
            uint4* dst[2];
#pragma unroll
            for (int e = 0; e < 2; e++) {
                const int p = !(hs >> 1) ? r : e && (hs & 1) ? (r & ~14) | ((r & 6) << 1) | ((r & 8) >> 2) : (r & ~30) | ((r & 6) << 2) | ((r & 24) >> 2);
                dst[e] = &g_wr[(((hs >> 1) * 8 + (c >> 1)) * 10 + 5 * (hs & 1)) * 128 + (p & 15) * 8 + ((2 * (p >> 4) + (c & 1)) ^ (p & 7))];
            }
#pragma unroll
            for (int u = 0; u < 10; u++) stg128(reinterpret_cast<uint4*>(reinterpret_cast<uintptr_t>(dst[u >= 6]) ^ (64 * (u & 1))) + (u >> 1) * 128, wr[u]);
        }
        __syncthreads();
        if (warp == 0) signal_cnt(&g_cnt.wr[0], lane, 1);
        __syncthreads();
        if (warp < 5 && elect()) {
            const int un = 5 * hs + warp;
            mbar_expect(bars + warp * 8, 40960);
            tma_ld2(sb + warp * 40960, &mp.w1h, 64 * (un >> 1), 320 * (un & 1), bars + warp * 8);
            tma_ld2(sb + warp * 40960 + 20480, &mp.w1h, 64 * (un >> 1), 320 * (un & 1) + 160, bars + warp * 8);
        }
        if (tid < 320) {
            const uint4* gm = reinterpret_cast<const uint4*>(g_mod + 3 * D_) + tid;
            const unsigned epoch = e0 + 1;
            uint4 r[6];
            unsigned it = 0;
            for (;;) {
                uint32_t bad = 0;
#pragma unroll
                for (int i = 0; i < 6; i++) { r[i] = ld_part(gm + (i >> 1) * (D_ / 2) + (i & 1) * 3 * D_); bad |= (r[i].y ^ epoch) | (r[i].w ^ epoch); }
                if (__all_sync(~0u, !bad)) break;
                if (++it > SPIN_LIMIT) SPIN_FAIL(54)
            }
            uint32_t mv[3];
#pragma unroll
            for (int i = 0; i < 3; i++) mv[i] = pack2(__uint_as_float(r[2 * i].x) + __uint_as_float(r[2 * i + 1].x), __uint_as_float(r[2 * i].z) + __uint_as_float(r[2 * i + 1].z));
            const uint32_t sw2 = mv[0], cw = add2(mv[1], 0x3f803f80u), gw = mv[2];
            const float c0 = blo(cw), c1 = bhi(cw), s0 = blo(sw2), s1 = bhi(sw2);
            const float i0 = __frcp_rn(zscale(c0)), i1 = __frcp_rn(zscale(c1));
            const uint32_t ci = pack2(i0, i1), cq = pack2(i0 * i0, i1 * i1);
            const uint32_t a = sb + H_B + ((tid >> 5) & 1) * 4608 + (tid >> 6) * 896 + ((tid >> 2) & 7) * 112 + (tid & 3) * 4;
            sts32(a, ci); sts32(a + 16, pack2(i0 - blo(ci), i1 - bhi(ci)));
            sts32(a + 32, cq); sts32(a + 48, pack2(fmaf(i0, i0, -blo(cq)), fmaf(i1, i1, -bhi(cq))));
            sts32(a + 64, cw); sts32(a + 80, sw2); sts32(a + 96, 0x3f803f80u);
            if ((tid & ~35) == 284) sts32(a + 112, 0);
            const uint32_t v = sb + H_B + TAB_BYTES + (tid < 256 ? (tid >> 5) * VEC_BYTES + (tid & 31) * 8 : ((tid - 256) >> 3) * VEC_BYTES + 256 + (tid & 7) * 8);
            sts64f(v, blo(gw), bhi(gw)); sts64f(v + 320, c0, c1); sts64f(v + 640, s0, s1); sts64f(v + 960, i0, i1);
            float k[5] = {c0 + c1, s0 + s1, fmaf(c0, c0, c1 * c1), fmaf(c0, s0, c1 * s1), fmaf(s0, s0, s1 * s1)};
#pragma unroll 1
            for (int o = 16; o; o >>= 1) {
#pragma unroll
                for (int e = 0; e < 5; e++) k[e] += __shfl_xor_sync(~0u, k[e], o);
            }
            const uint32_t ks = sb + H_B + TAB_BYTES + (lane & 7) * VEC_BYTES + 1280 + (warp >> 1) * 32;
            if ((warp & 1) && lane < 8) { sts128f(ks, k[0], k[1], k[2], k[3]); sts128f(ks + 16, k[4], 0.f, 0.f, 0.f); }
            bar_sync(3, 320);
            if (!(warp & 1) && lane < 8) {
                const float4 o = lds128f(ks);
                sts128f(ks, k[0] + o.x, k[1] + o.y, k[2] + o.z, k[3] + o.w); sts32(ks + 16, __float_as_uint(k[4] + __uint_as_float(lds32(ks + 16))));
            }
            fence_async_smem();
        }
        __syncthreads();
        if (hs == 0 && warp == 15 && elect()) {
            asm volatile("cp.async.bulk.global.shared::cta.bulk_group [%0], [%1], %2;\ncp.async.bulk.commit_group;\ncp.async.bulk.wait_group 0;"
                         ::"l"(g_tab), "r"(sb + H_B), "n"(TAB_BYTES + 8 * VEC_BYTES) : "memory");
            asm volatile("red.release.gpu.global.add.u32 [%0], 1;" ::"l"(&g_cnt.tab[0]) : "memory");
        }
        __syncwarp();
#pragma unroll 1
        for (int i = wg; i < 20; i += 4) {
            const int r = i / 5, b = i - 5 * r, un = 5 * hs + b, u3 = 20 * r + un;
            auto refill = [&](int e, int u, uint32_t fb) {
                mbar_expect(fb, 40960);
                tma_ld2(sb + e * 40960, &mp.w3h, 64 * (u >> 1), 320 * (u & 1), fb);
                tma_ld2(sb + e * 40960 + 20480, &mp.w3h, 64 * (u >> 1), 320 * (u & 1) + 160, fb);
            };
            if (i > 4 && i < 9) {
                bar_sync(1, 512);
                if (warp == 0) {
                    signal_cnt(&g_cnt.uv[0], lane, 1);
                    if (elect()) {
#pragma unroll 1
                        for (int e = 0; e < 5; e++) refill(e, 5 * hs + e, bars + (5 + e) * 8);
                        l2_prefetch(pp.w2 + (size_t)160 * hs * D_, 160 * D_ * 2);
                    }
                    __syncwarp();
                }
            }
            mbar_wait(bars + i * 8, 0);
            float d[4];
            gemv_tile<7>(d, sb + b * 40960, sb + H_B, 5 * (un & 1));
            const int col = 16 * (warp & 3) + g;
            float* dst = r ? g_cs3 + (un & 1) * 1920 + 64 * ((u3 >> 1) - 10) + col : g_uv + (un & 1) * 3 * D_ + 2 * D_ + 64 * (un >> 1) + col;
            if (t == 3) { dst[0] = d[0]; dst[8] = d[2]; }
            if (r == 0 && t == 2) { dst[-2 * D_] = d[0]; dst[8 - 2 * D_] = d[2]; dst[-D_] = d[1]; dst[8 - D_] = d[3]; }
            if (r == 1 || r == 2) {
                bar_sync(4 + wg, 128);
                if (wt == 0) refill(b, u3, bars + (i + 5) * 8);
            }
        }
        __syncthreads();
        if (warp == 0) signal_cnt(&g_cnt.cs[0], lane, 1);
        if (tid == 511) l2_prefetch(pp.w4 + (size_t)432 * hs * D_, 432 * D_ * 2);
        for (uint32_t it = 0; ld_cold(&g_cnt.cs[0]) < 4;) { if (++it > SPIN_LIMIT) SPIN_FAIL(47) }
        asm volatile("fence.acquire.gpu;" ::: "memory");
        if (tid < 432) {
            const int jj = 2 * hs + (tid >= 216), c = tid % 216;
            const float* src = g_cs3 + (c < 192 ? 192 * jj + c : 1344 + 24 * jj + c);
            const uint32_t s = split2(ldcg32f(src) + ldcg32f(src + 1920));
            stg128(&g_cs3b[432 * hs + tid], s, s & 0xffffu, 0, 0);
        }
        __syncthreads();
        if (warp == 0) signal_cnt(&g_cnt.cs2[0], lane, 1);
        if (tid == 0 && hs == 3) {
            uint32_t it = 0;
            while (ld_cold(&g_epoch) == e0) { __nanosleep(256); if (++it > (1u << 20)) SPIN_FAIL(48) }
        }
        return;
    }

    if (elect()) {
        if (warp == 15) {
            mbar_init(bars + B_IN * 8, 1); mbar_init(bars + B_IN * 8 + 8, 1);
            asm volatile("fence.mbarrier_init.release.cluster;" ::: "memory");
            mbar_expect(bars + B_IN * 8, 131 * 160);
            tma_ld2(sb + OFF_KIN, &mp.k, 80 * (id & 7), 64 * (id >> 3) - 3, bars + B_IN * 8);
            tma_ld2(sb + OFF_VIN, &mp.v, 80 * (id & 7), 64 * (id >> 3), bars + B_IN * 8);
        } else if (warp < 13) {
            const uint32_t n = (0x1C14111111881ull >> (4 * warp)) & 15;
#pragma unroll
            for (int i = 0; i < 4; i++) mbar_init(bars + warp * 64 + i * 8, n);
            if (warp == 11) { mbar_init(bars + B_XFREE * 8, 16); mbar_init(bars + B_OWN * 8, 8); }
            else if (warp < 11) {
#pragma unroll
                for (int i = 4; i < 8; i++) mbar_init(bars + warp * 64 + i * 8, n);
            }
            asm volatile("fence.mbarrier_init.release.cluster;" ::: "memory");
        }
    }
    asm volatile("" ::"l"(pp.s), "l"(pp.c), "l"(out));
    TR4((threadIdx.x & 31) == 0, warp)
    const int pr = id >> 1;
    const int grp = pr < 4 ? 15 : pr < 36 ? (pr - 4) & 7 : 8 + (pr - 36) % 7;
    const int j = 2 * (pr < 4 ? pr : pr < 36 ? (pr - 4) >> 3 : (pr - 36) / 7) + (id & 1);

    if (wg == 3) {
        TIDS
        const int sw = warp - 12;
        uint32_t ep = ld_cold(&g_epoch);
        TR4(lane == 0, 20 + sw)
        __syncthreads();
        TR4(lane == 0, 30 + sw)
        asm volatile("barrier.cluster.arrive.relaxed.aligned;" ::: "memory");
        if (sw == 0) {
#pragma unroll 1
            for (int n = 0; n < 12; n++) {
                wait_clock(c0, PF_T0 + PF_DT * n);
                if (elect()) l2_prefetch(n < 4 ? (const char*)pp.q + id * 20480 + n * 5120 : (const char*)pp.w_mod + id * 38400 + (n - 4) * 4800, n < 4 ? 5120 : 4800);
            }
        } else if (sw == 1) {
            wait_clock(c0, T_SSM);
            if (elect()) {
                mbar_expect(bars + B_SSM * 8, 20480);
                bulk_ld(sb + OFF_SSM, pp.ssm_k + (size_t)5 * id * S_, 20480, bars + B_SSM * 8);
            }
            mbar_spin(bars + B_KVS * 8, 0);
            signal_cnt(&g_cnt.kv[(id & 7) * 32], lane, 1, true);
            TS(lane == 0, 2)
            mbar_spin(bars + B_RAW * 8, 0);
            if (elect()) {
                mbar_expect(bars + B_QIN * 8, 20480);
                tma_ld3(sb + OFF_QIN, &mp.q, 0, 16 * id, 0, bars + B_QIN * 8);
            }
        } else if (sw == 2) {
            if (elect()) {
#pragma unroll 1
                for (int i = 2; i < (int)(sizeof(Maps) / sizeof(CUtensorMap)); i++) asm volatile("prefetch.tensormap [%0];" ::"l"(&mp.k + i) : "memory");
#pragma unroll 1
                for (int i = B_SUMS; i < B_SIG; i++) mbar_expect(bars + i * 8, i < B_RECV ? 2048 : (i & 3) < 3 ? 8192 : 3072);
            }
            wait_cnt(&g_cnt.kv[(id >> 4) * 32], 16, true);
            TS(lane == 0, 4)
            if (elect()) {
                mbar_expect(bars + B_RAW * 8, 12288);
                mbar_expect(bars + B_RAW2 * 8, 8192);
#pragma unroll
                for (int c = 0; c < 5; c++) bulk_ld(sb + OFF_CH + c * CH_BYTES, g_kvT + (size_t)(5 * id + c) * S_, 4096, bars + (c < 3 ? B_RAW : B_RAW2) * 8);
            }
            mbar_spin(bars + B_BK * 8, 0);
            mbar_spin(bars + B_QIN * 8, 0);
            if (id < 120 && elect()) {
                mbar_expect(bars + B_WM * 8, 40960);
                tma_ld2(sb + OFF_WM, &mp.wmod, 64 * pr, 320 * (id & 1), bars + B_WM * 8);
                tma_ld2(sb + OFF_WM + 20480, &mp.wmod, 64 * pr, 320 * (id & 1) + 160, bars + B_WM * 8);
            }
            TS(lane == 0, 57)
        } else {
            wait_clock(c0, T_KVB);
            if (elect()) {
                mbar_expect(bars + (B_IN + 1) * 8, 131 * 160);
                tma_ld2(sb + OFF_KIN + 10752, &mp.k, 80 * (id & 7), 64 * (id >> 3) + 1021, bars + (B_IN + 1) * 8);
                tma_ld2(sb + OFF_VIN + 10240, &mp.v, 80 * (id & 7), 64 * (id >> 3) + 1024, bars + (B_IN + 1) * 8);
            }
            TS(lane == 0, 53)
            if (lane == 0) sts32(sb + M_EP, ep + 1);
            sts32(sb + M_NUL + lane * 4, 0);
#pragma unroll 1
            for (int i = 0; i < 10; i++) sts128(sb + OFF_Z + i * 512 + lane * 16, 0, 0, 0, 0);
            __syncwarp();
#pragma unroll 1
            for (int i = lane; i < 160; i += 32) {
                const uint32_t c = ldg32(pp.c + 320 * (id & 1) + 2 * i);
                sts32(sb + OFF_Z + (i >> 2) * 128 + (i & 3) * 4, pack2(silu(blo(c)), silu(bhi(c))));
            }
            fence_async_smem();
            for (uint32_t ph = 0, again = 1; again; ph ^= 1) {
                mbar_spin(bars + B_RAW2 * 8, ph);
                uint32_t bad = 0;
#pragma unroll
                for (int i = 0; i < 8; i++) bad |= lop3<0x7E>(lds32(sb + OFF_CH + 3 * CH_BYTES + i * 512 + lane * 16), ~ep, lds32(sb + OFF_CH + 4 * CH_BYTES + i * 512 + lane * 16));
                again = __any_sync(~0u, bad & 1);
                if (again && elect()) {
                    mbar_expect(bars + B_RAW2 * 8, 8192);
#pragma unroll
                    for (int c = 3; c < 5; c++) bulk_ld(sb + OFF_CH + c * CH_BYTES, g_kvT + (size_t)(5 * id + c) * S_, 4096, bars + B_RAW2 * 8);
                }
            }
            if (elect()) mbar_arrive(bars + B_RAW3 * 8);
        }
        {
            mbar_spin(bars + B_QIN * 8, 0);
            asm volatile("add.u32 %0, %0, 1;" : "+r"(ep));
            TS(wt == 0, 54)
            const int tk = 8 * ((lane >> 1) & 1) + 2 * (lane >> 3) + (lane & 1), ck = 4 * (sw & 1) + ((lane >> 1) & 2);
            const uint32_t src = sb + OFF_QIN + (sw >> 1) * 2048 + tk * 128;
            bf16* dst = g_qT + (size_t)id * 16 * D_ + (32 * sw + 8 * (t & 2) + g) * 16 + 8 * (t & 1);
constexpr int QU = Q_UNROLL;
#pragma unroll QU
            for (int i = 0; i < 5; i++) {
                uint32_t r[8];
                ldsm4t(src + i * 4096 + ((ck ^ (tk & 7)) << 4), r[0], r[1], r[2], r[3]);
                ldsm4t(src + i * 4096 + (((ck + 1) ^ (tk & 7)) << 4), r[4], r[5], r[6], r[7]);
                stg128(dst + i * 2048, tag(r[0], ep), r[1], r[2], r[3]);
                stg128(dst + i * 2048 + 128, tag(r[4], ep), r[5], r[6], r[7]);
            }
            float s1 = 0.f, s2 = 0.f;
#pragma unroll 2
            for (int i = 0; i < 10; i++) {
                const uint4 w4 = lds128(sb + OFF_QIN + i * 2048 + wt * 16);
                const uint32_t w[4] = {w4.x, w4.y, w4.z, w4.w};
#pragma unroll
                for (int e = 0; e < 4; e++) { const float a = blo(w[e]), b = bhi(w[e]); s1 += a + b; s2 = fmaf(a, a, fmaf(b, b, s2)); }
            }
#pragma unroll
            for (int o = 1; o < 8; o *= 2) { s1 += __shfl_xor_sync(~0u, s1, o); s2 += __shfl_xor_sync(~0u, s2, o); }
            s1 *= 1.f / D_;
            uint32_t rs = pack2(rsqrtf(fmaxf(s2 * (1.f / D_) - s1 * s1, 0.f) + 1e-5f), 0.f);
            if (lane < 8) rs = tag(rs, ep);
            rs = pack2(blo(rs), -s1 * blo(rs));
            const uint32_t sel = lane ? 0x7632 : 0x5410;
            const uint32_t a0 = __shfl_sync(~0u, rs, 0), a1 = __shfl_sync(~0u, rs, 8), a2 = __shfl_sync(~0u, rs, 16), a3 = __shfl_sync(~0u, rs, 24);
            if (lane < 2) stg64(g_qst + lane * S_ + 16 * id + 4 * sw, tag(__byte_perm(a0, a1, sel), ep), __byte_perm(a2, a3, sel));
            TS(wt == 0, 55)
        }
        bar_sync(6, 128);
        if (sw == 3) {
            signal_cnt(&g_cnt.q[(lane & 3) * 32], lane, 4, true);
            TS(lane == 0, 3)
        }
        asm volatile("setmaxnreg.dec.sync.aligned.u32 " STR(REG_SVC) ";");
        asm volatile("barrier.cluster.wait.aligned;" ::: "memory");
        if (sw == 1) {
            mbar_spin(bars + B_XS * 8, 0);
            signal_cnt(&g_cnt.x[(lane & 3) * 32], lane, 4, true);
            TS(lane == 0, 20)
#pragma unroll 1
            for (int e = 1; e < 3; e++) {
                wait_cnt(e == 1 ? &g_cnt.g1[min(grp + 15 + min(lane, 2), 31) * 32] : &g_cnt.g2[(grp + 16) * 32], 32, true);
                if (elect()) mbar_arrive(bars + (B_GATE + 2 + e) * 8);
                TS(lane == 0, 27 + 2 * e)
            }
            return;
        }
        if (sw == 2) {
            mbar_spin(bars + B_XS * 8, 0);
            fence_async_smem();
            const unsigned* flag = &g_cnt.x[(id & 3) * 32];
            uint32_t m = 0;
            int n = 0, a0 = 0, a1 = 0;
            uint32_t k = 0;
#pragma unroll 1
            for (int s = 0; s < 6; s++) {
                const int e = s >> 1, end = 20 * e + ((s & 1) ? 20 : e == 0 ? LEAD1 : e == 1 ? 10 : XLEAD);
                if (s & 1) mbar_spin(bars + (B_GATE + 2 + e) * 8, !e);
                else {
                    wait_cnt(flag, e ? 32 : 128, true);
                    flag = e ? &g_cnt.g2[grp * 32] : &g_cnt.g1[max(grp - 1 + min(lane, 2), 0) * 32];
                    m = e == 0 ? M0 : e == 1 ? M1 : M2;
                    k = e ? 0 : (j & 1) * 0x400040;
                    a0 = e ? 0 : 64 * grp; a1 = e == 0 ? 0 : e == 1 ? 64 * grp : 640 * grp;
                    TS(lane == 0, 26 + 2 * e)
                }
                const int b0 = e ? 0 : 1024, b1 = e == 0 ? 0 : e == 1 ? 1024 : 10240, step = e ? 64 : 128;
                const uint32_t turn = e ? 1 : 512 + 64 * (j & 1), back = -448 - 128 * (j & 1);
#pragma unroll 1
                for (; n < end; n++, m >>= 1) {
                    const uint32_t w = m & 1, sh = 16 * w, kc = (k >> sh) & 0xffff;
                    k += (kc == turn ? back : step) << sh;
                    const uint32_t fb = bars + (B_LAND + (n & 7)) * 8;
                    mbar_spin(fb - (B_LAND - B_XEMPTY) * 8, ((n >> 3) & 1) ^ 1);
                    TR2(lane == 0 && n < 40, 20 + n)
                    if (elect()) {
                        mbar_expect(fb, 8192);
                        tma_ld2(sb + OFF_XR + (n & 7) * 8192, &mp.x[e], a0 + w * b0 + (e == 1 ? kc : 0), a1 + w * b1 + (e == 1 ? 0 : kc), fb);
                    }
                }
            }
            mbar_spin(bars + B_VEC3 * 8, 0);
            unsigned old = 0;
            asm volatile("{\n.reg .pred P;\nsetp.eq.s32 P, %2, 0;\n@P atom.relaxed.gpu.global.add.u32 %0, [%1], %3;\n}" : "+r"(old) : "l"(&g_cnt.done[0]), "r"(lane), "r"(1) : "memory");
            if (__any_sync(~0u, old == 127)) {
#pragma unroll 1
                for (int i = lane; i < (int)(sizeof(Counters) / 128); i += 32) reinterpret_cast<unsigned*>(&g_cnt)[i * 32] = 0;
                signal_cnt(&g_epoch, lane, 1, true);
            }
        } else if (sw == 0) {
            wait_cnt(&g_cnt.wr[0], 4);
            mbar_spin(bars + B_QRDY * 8, 0);
            const uint32_t wf = bars + B_WFULL * 8, we = bars + B_WEMPTY * 8;
#pragma unroll 1
            for (int n = 0; n < 5; n++) {
                if (n == 3) { mbar_spin(bars + B_XS * 8, 0); fence_async_smem(); }
                TR2(lane == 0, 70 + n)
                if (elect()) {
                    const uint32_t fb = wf + n * 8, dst = sb + OFF_W + n * 16384;
                    mbar_expect(fb, 20480);
#pragma unroll 1
                    for (int h = 0; h < 2; h++) {
                        const int kb = g1_block(2 * n + h, j);
                        tma_ld2(dst + h * 8192, &mp.w1, 64 * j, 64 * kb, fb);
                        bulk_ld(sb + OFF_REM + n * 4096 + h * 2048, &g_wr[(j * 10 + kb) * 128], 2048, fb);
                    }
                }
            }
            mbar_spin(bars + B_GATE * 8, 0);
#pragma unroll 1
            for (int i = -3; i < 5; i++) {
                const int n = i < 0 ? 8 + i : 5 + i;
                const uint32_t fb = wf + (n & 7) * 8;
                if (i >= 0) mbar_spin(we + i * 8, 0);
                TR2(lane == 0 && i >= 0, 70 + n)
                if (elect()) {
                    if (i < 0 || i >= 3) { mbar_expect(fb, 20480); tma_ld5(sb + OFF_W + (n & 7) * 16384, n < 9 ? &mp.w2a : &mp.w2b, 64 * j, n < 9 ? 4 * (n - 5) : 0, fb); }
                    if (i >= 0) bulk_ld(sb + OFF_REM + i * 4096, &g_wr[((8 + j) * 10 + 2 * i) * 128], 4096, fb);
                }
            }
            mbar_spin(bars + (B_GATE + 1) * 8, 0);
#pragma unroll 1
            for (int n = 10; n < 30; n++) {
                if (n == W3_N2) mbar_spin(bars + (B_GATE + 2) * 8, 0);
                mbar_spin(we + (n & 7) * 8, ((n >> 3) & 1) ^ 1);
                TR2(lane == 0, 70 + n)
                if (elect()) {
                    const uint32_t dst = sb + OFF_W + (n & 7) * 16384, fb = wf + (n & 7) * 8;
                    mbar_expect(fb, 13824);
                    tma_ld3(dst, &mp.w3a, 0, 32 * (n - 10), 3 * j, fb);
                    tma_ld2(dst + 12288, &mp.w3b, 1536 + 24 * j, 32 * (n - 10), fb);
                }
            }
            mbar_spin(we + 6 * 8, 0);
            mbar_spin(bars + B_VEC3 * 8, 0);
            if (elect()) { mbar_expect(wf + 6 * 8, 3456); bulk_ld(sb + OFF_W + 6 * 16384, &g_cs3b[216 * j], 3456, wf + 6 * 8); }
#pragma unroll 1
            for (int n = 31; n < 50; n++) {
                const int e = n < 38 ? 4 : (n - 38) & 3, m0 = n == 35, m1 = e == 3 ? -1 : m0 | (e == 1), rem = 96 + 3 * (j >> 1);
                const int c1_ = j ^ (n < 38 ? 6 : 4 >> ((n - 38) >> 2) & 6), c0_ = n < 38 ? 8 + (j & 1) : c1_;
                const int f = (0xC840A80C204ull >> (4 * min(n - 31, e + 7))) & 15;
                const int r0 = m0 ? rem : 6 * (j ^ (f >> 3)) + (f & 6), r1 = m1 ? rem : r0 + (n < 38 ? 0 : 2);
                mbar_spin(we + (n & 7) * 8, ((n >> 3) & 1) ^ 1);
                if (elect()) {
                    const uint32_t dst = sb + OFF_W + (n & 7) * 16384, fb = wf + (n & 7) * 8;
                    mbar_expect(fb, m1 < 0 ? 8192 : 16384 - 2048 * (m0 + m1));
                    tma_ld2(dst, &mp.w4[m0], 64 * c0_, r0 * (32 >> m0), fb);
                    if (m1 >= 0) tma_ld2(dst + 8192, &mp.w4[m1], 64 * c1_, r1 * (32 >> m1), fb);
                }
            }
        } else {
            {
                wait_cnt(&g_cnt.tab[0], 1);
                mbar_spin(bars + B_QRDY * 8, 0);
                if (elect()) {
                    mbar_expect(bars + B_TAB * 8, TAB_BYTES / 2 + VEC_BYTES);
                    bulk_ld(sb + OFF_TAB, g_tab + (j & 1) * (TAB_BYTES / 32), TAB_BYTES / 2, bars + B_TAB * 8);
                    bulk_ld(sb + M_GB, g_tab + (TAB_BYTES + j * VEC_BYTES) / 16, VEC_BYTES, bars + B_TAB * 8);
                }
                TS(lane == 0, 5)
            }
            wait_cnt(&g_cnt.uv[0], 4);
#pragma unroll 1
            for (int c = lane; c < 80; c += 32) {
                const float* src = g_uv + (c < 64 ? 64 * j + c : 448 + 16 * j + c);
                const uint32_t u = split2(ldcg32f(src) + ldcg32f(src + 3 * D_)), v = split2(ldcg32f(src + D_) + ldcg32f(src + 4 * D_));
                const uint32_t s = split2(ldcg32f(src + 2 * D_) + ldcg32f(src + 5 * D_));
                sts128(sb + OFF_F1 + c * 16, u, __byte_perm(u, v, 0x5410), __byte_perm(v, 0, 0x1032), s);
                sts128(sb + M_F1 + c * 16, s & 0xffffu, 0, 0, 0);
            }
            fence_async_smem();
            warp_arrive(bars + B_VEC * 8);
            TS(lane == 0, 9)
            wait_cnt(&g_cnt.cs2[0], 4);
            if (elect()) mbar_arrive(bars + B_VEC3 * 8);
            TS(lane == 0, 19)
        }
        return;
    }

    {
        uint32_t ep;
        {
            TIDS
            ep = ld_cold(&g_epoch);
            const int cp = (tid + 16) % 40, cp1 = tid % 40;
            const uint4 sh0 = ldg128(pp.shift_k + (80 * (id & 7) + 2 * cp1) * 4), sh1 = ldg128(pp.shift_k + (80 * (id & 7) + 2 * cp) * 4);
            uint32_t dd;
            asm volatile("ld.global.nc.u16 %0, [%1];" : "=r"(dd) : "l"(pp.ssm_D + 5 * id + min(wg + 3 * lane, 4)));
            TR4(lane == 0, 40 + warp)
            __syncthreads();
            asm volatile("barrier.cluster.arrive.relaxed.aligned;" ::: "memory");
            asm volatile("add.u32 %0, %0, 1;" : "+r"(ep));
#pragma unroll 1
            for (int hw = 0; hw < 2; hw++) {
                if ((unsigned)(warp - 2 * hw) >= 10) continue;
                const int u = tid - 64 * hw;
                const int c = hw ? cp : cp1, oc = u / 40, line = 31 - 16 * hw - (id >> 3);
                const uint4 sh = hw ? sh1 : sh0;
                const uint32_t st = sb + OFF_ST + hw * 10240, sta = st + c * 256 + ((((6 - 2 * (oc & 3)) ^ (oc >> 2) ^ (line & 1)) ^ (c & 7)) << 4), in = oc * 1280 + c * 4;
                const uint32_t f0 = __byte_perm(sh.x, sh.z, 0x5410), f1 = __byte_perm(sh.x, sh.z, 0x7632), f2 = __byte_perm(sh.y, sh.w, 0x5410), f3 = __byte_perm(sh.y, sh.w, 0x7632);
                uint32_t kk[11], vv[8];
                mbar_spin(bars + (B_IN + hw) * 8, 0);
                TS(tid == 64, 18 + 42 * hw)
#pragma unroll
                for (int i = 0; i < 11; i++) kk[i] = lds32(sb + OFF_KIN + hw * 10752 + in + i * 160);
#pragma unroll
                for (int i = 0; i < 8; i++) vv[i] = lds32(sb + OFF_VIN + hw * 10240 + in + i * 160);
#pragma unroll
                for (int i = 0; i < 8; i++) vv[i] = mul2(fma2(kk[i + 3], f0, fma2(kk[i + 2], f1, fma2(kk[i + 1], f2, mul2(kk[i], f3)))), vv[i]);
                sts128(sta, tag(__byte_perm(vv[0], vv[1], 0x5410), ep), __byte_perm(vv[2], vv[3], 0x5410), __byte_perm(vv[4], vv[5], 0x5410), __byte_perm(vv[6], vv[7], 0x5410));
                sts128(sta + 128, tag(__byte_perm(vv[0], vv[1], 0x7632), ep), __byte_perm(vv[2], vv[3], 0x7632), __byte_perm(vv[4], vv[5], 0x7632), __byte_perm(vv[6], vv[7], 0x7632));
                bar_sync(7 + hw, 320);
                flush_tile(st, g_kvT + (size_t)(80 * (id & 7)) * S_ + 64 * line, u);
                TS(tid == 64 && hw, 1)
            }
            warp_arrive(bars + B_KVS * 8);
            if (tid < 320) sts128(sb + OFF_CH + (tid >> 6) * CH_BYTES + 4096 + (tid & 63) * 16, 0, 0, 0, 0);
            mbar_spin(bars + B_SSM * 8, 0);
            TS(tid == 0, 14)
#pragma unroll 1
            for (int u0 = wg; u0 < 20; u0 += 12) {
                uint2 w[4];
                uint32_t pv[4];
#pragma unroll
                for (int i = 0; i < 4; i++) {
                    const uint32_t a = sb + OFF_SSM + min(u0 + 3 * i, 19) * 1024 + wt * 8;
                    w[i] = lds64(a); pv[i] = lds32(a - 4);
                }
#pragma unroll
                for (int i = 0; i < 4; i++) {
                    const int un = min(u0 + 3 * i, 19);
                    sts128(sb + OFF_CH + (un >> 2) * CH_BYTES + OFF_P + (un & 3) * 2048 + wt * 16, __byte_perm(w[i].x, pv[i], 0x7610), __byte_perm(w[i].x, 0, 0x1032), __byte_perm(w[i].y, w[i].x, 0x7610), __byte_perm(w[i].y, 0, 0x1032));
                }
            }
            __syncwarp();
            if (wt < 2 - (wg >> 1)) {
                const uint32_t h = lds32(sb + OFF_SSM + (wg + 3 * wt) * 4096), h0 = pack2(blo(h) + blo(dd), 0.f);
                sts64f(sb + OFF_CH + (wg + 3 * wt) * CH_BYTES + OFF_P, __uint_as_float(h0), __uint_as_float(__byte_perm(h, h0, 0x5432)));
            }
            fence_async_smem();
            warp_arrive(bars + B_BK * 8);
            asm volatile("barrier.cluster.wait.aligned;" ::: "memory");
            mbar_spin(bars + B_BK * 8, 0);
            TS(tid == 0, 15)
        }

#pragma unroll 1
        for (int c = wg; c < 5; c += 3) {
            const uint32_t kvb = sb + OFF_CH + c * CH_BYTES;
            mbar_spin(bars + (c < 3 ? B_RAW : B_RAW3) * 8, 0);
            for (uint32_t ph = 0; c < 3; ph ^= 1) {
                const int wt = tid_now() & 127;
                if (!RARE(bar_any(1 + wg, lop3<0x7E>(lds32(kvb + wt * 16), ep, lds32(kvb + 2048 + wt * 16)) & 1))) break;
                if (wt == 0) { mbar_expect(bars + (B_RETRY + wg) * 8, 4096); bulk_ld(kvb, g_kvT + (size_t)(5 * id + c) * S_, 4096, bars + (B_RETRY + wg) * 8); }
                mbar_spin(bars + (B_RETRY + wg) * 8, ph);
                STALE1(3)
            }
            TS(threadIdx.x == 0, c ? 13 : 11)
            float acc[64];
            {
                const int l = tid_now() & 31;
                conv_channel(acc, kvb + OFF_P + (8 * (warp & 3) + (l >> 2) - 2 * (l & 3)) * 4, (((uint64_t)0xC0000010u << 32) | ((kvb & 0x3FFFF) >> 4) | 0x10000u) + pp.nil);
            }
            TS(threadIdx.x == 0, c ? 16 : 12)
            if (c < 3) warp_arrive(bars + B_R1 * 8);
            else mbar_spin(bars + B_R1 * 8, 0);
            if (wg == 2 && id < 120) {
                TIDS
                mbar_spin(bars + B_RAW3 * 8, 0);
                mbar_spin(bars + B_WM * 8, 0);
                TS(wt == 0, 56)
                float d[4];
                gemv_tile<8>(d, sb + OFF_WM, sb + OFF_Z, 0);
                const float d2 = __shfl_up_sync(~0u, d[2], 1);
                TS(wt == 0, 7)
                if (t < 2) asm volatile("{\n.reg .b64 v;\nmov.b64 v, {%1, %2};\nst.relaxed.gpu.global.b64 [%0], v;\n}" ::"l"(g_mod + (id & 1) * 6 * D_ + 64 * pr + 16 * (warp & 3) + g + 8 * t),
                                        "r"(__float_as_uint(t ? d2 : d[0])), "r"(lds32(sb + M_EP)) : "memory");
            }
            TR4(threadIdx.x == 0, 60 + (c >= 3) * 10)
            TIDS
            const int e = 127 - 8 * (lane >> 4) - (lane & 7), u0 = (warp & 3) + 8 * (e >> 2) + (e & 3) + 4 * ((lane >> 3) & 1);
            const uint32_t ring = sb + OFF_RING + c * 16384 + (warp & 3) * 4096, wa = ring + (u0 ^ ((u0 >> 1) & 4)) * 16;
            if (lane < (warp & 3)) sts128(ring + lane * 16, 0, 0, 0, 0);
#pragma unroll
            for (int i = 0; i < 8; i++)
                stsm4t(i == 0 && u0 >= 256 ? sb + M_SINK : wa - 512 * i, pack2(acc[8 * i], acc[8 * i + 1]), pack2(acc[8 * i + 2], acc[8 * i + 3]),
                       pack2(acc[8 * i + 4], acc[8 * i + 5]), pack2(acc[8 * i + 6], acc[8 * i + 7]));
            warp_arrive(bars + (B_RING + c) * 8);
            TR4(threadIdx.x == 0, 61 + (c >= 3) * 10)
        }
        TIDS
        if (wg == 2) bar_sync(3, 128);
        if (warp == 8) {
            wait_cnt(&g_cnt.q[(id & 3) * 32], 128, true);
            if (elect()) {
                mbar_expect(bars + B_QRDY * 8, 28672);
                tma_ld2(sb + OFF_QT, &mp.qT, 80 * id, 0, bars + B_QRDY * 8);
                bulk_ld(sb + OFF_QT + 20480, g_qst, 8192, bars + B_QRDY * 8);
            }
            TS(lane == 0, 8)
        } else if (warp == 9) {
            const int v = min(lane / 5, 3);
            const uint2* gm = g_mod + (v + (v == 3)) * D_ + 5 * id + lane % 5;
            const unsigned epoch = lds32(sb + M_EP);
            uint2 r0, r1;
            unsigned it = 0;
            do {
                r0 = ld_mod(gm); r1 = ld_mod(gm + 6 * D_);
                SPIN_CHECK(55)
            } while (!__all_sync(~0u, r0.y == epoch && r1.y == epoch));
            const float m0 = __uint_as_float(r0.x), m1 = __uint_as_float(r1.x);
            const float m = rbf(m0 + m1), p = rbf(1.f + m);
            const float cz = zscale(__shfl_sync(~0u, p, 15 + lane % 5)), ga = __shfl_sync(~0u, m, 10 + lane % 5);
            if (lane < 15) sts32(sb + M_AB + lane % 5 * 16 + v * 4, lane < 10 ? __float_as_uint(cz * ga * (lane < 5 ? m : p)) : pack2(cz, cz));
            warp_arrive(bars + B_MODR * 8);
            TS(lane == 0, 6)
        }
        mbar_spin(bars + B_QRDY * 8, 0);
        uint4 rs[2], nm[2];
#pragma unroll
        for (int h = 0; h < 2; h++) { rs[h] = lds128(sb + OFF_QT + 20480 + h * 2048 + wt * 16); nm[h] = lds128(sb + OFF_QT + 24576 + h * 2048 + wt * 16); }
        mbar_spin(bars + B_MODR * 8, 0);
        TR4(threadIdx.x == 0, 72)
        uint32_t it = 0;
        while (RARE(__any_sync(~0u, (lop3<0x7E>(rs[0].x, ep, rs[0].z) | lop3<0x7E>(nm[0].x, ep, nm[0].z) | lop3<0x7E>(rs[1].x, ep, rs[1].z) | lop3<0x7E>(nm[1].x, ep, nm[1].z)) & 1))) {
#pragma unroll
            for (int h = 0; h < 2; h++) { rs[h] = ld_part(g_qst + 1024 * h + 8 * wt); nm[h] = ld_part(g_qst + S_ + 1024 * h + 8 * wt); }
            STALE(1)
            SPIN_CHECK(53)
        }
        TR4(threadIdx.x == 0, 73)
#pragma unroll 1
        for (int c = wg == 2 ? 0 : 3 + wg; c < (wg == 2 ? 3 : 4 + wg); c++) {
            uint4 q[2], p[2][4];
#pragma unroll
            for (int h = 0; h < 2; h++) q[h] = lds128(sb + OFF_QT + h * 10240 + (wt >> 1) * 160 + c * 32 + (wt & 1) * 16);
            const float4 ab = lds128f(sb + M_AB + c * 16);
            mbar_spin(bars + (B_RING + c) * 8, 0);
            TR4(wt == 0, wg == 2 ? 80 + 2 * c : 74)
#pragma unroll
            for (int i = 0; i < 8; i++) p[i >> 2][i & 3] = lds128(sb + OFF_RING + c * 16384 + (i & 3) * 4096 + (i >> 2) * 2048 + (wt ^ ((wt >> 1) & 4)) * 16);
            while (RARE(__any_sync(~0u, lop3<0x7E>(q[0].x, ep, q[1].x) & 1))) {
#pragma unroll
                for (int h = 0; h < 2; h++) q[h] = ld_part(g_qT + ((64 * h + (wt >> 1)) * D_ + 5 * id + c) * 16 + 8 * (wt & 1));
                STALE(2)
                SPIN_CHECK(52)
            }
            TR4(wt == 0, wg == 2 ? 81 + 2 * c : 75)
#pragma unroll
            for (int h = 0; h < 2; h++) {
                const uint32_t qq[4] = {q[h].x, q[h].y, q[h].z, q[h].w}, r4[4] = {rs[h].x, rs[h].y, rs[h].z, rs[h].w}, n4[4] = {nm[h].x, nm[h].y, nm[h].z, nm[h].w};
                const uint4 y = add2(add2(p[h][0], p[h][1]), add2(p[h][2], p[h][3]));
                const uint32_t yy[4] = {y.x, y.y, y.z, y.w};
                uint32_t o[4];
#pragma unroll
                for (int i = 0; i < 4; i++) {
                    const uint32_t n = fma2(qq[i], r4[i], n4[i]);
                    o[i] = fma2(pack2(fmaf(blo(n), ab.y, ab.x), fmaf(bhi(n), ab.y, ab.x)), yy[i], mul2(qq[i], __float_as_uint(ab.z)));
                }
                stg128_tag(g_x1T + (size_t)(5 * id + c) * S_ + 1024 * h + 8 * wt, o[0], o[1], o[2], o[3], ep, ((5 * id + c) >> 3) & 3);
            }
        }
        warp_arrive(bars + B_XS * 8);
        TS(tid == 0, 17)
        TS(tid == 256, 52)
    }

    const uint32_t nil = pp.nil;
    const int wq = warp & 3;
    if (wg == 2) {
        TIDS
        asm volatile("setmaxnreg.dec.sync.aligned.u32 " STR(REG_AUX) ";");
        {
            const uint32_t ep = lds32(sb + M_EP);
            uint32_t ph = 0;
#pragma unroll 1
            for (int m = wq - 4; m < 60; m += 4) {
                const int n = max(m, 0);
                const int e = (n >= 20) + (n >= 40), i = n - 20 * e;
                const uint32_t M = e == 0 ? M0 : e == 1 ? M1 : M2;
                const int w = (M >> i) & 1, c = __popc(M & ((1u << i) - 1)), kb = w ? c : i - c;
                const uint32_t a = sb + OFF_XR + (n & 7) * 8192;
                uint32_t ta = a + (e == 0 ? lane * 128 + ((lane & 7) << 4) + (lane >> 3) * 4
                                 : e == 1 ? (lane & 15) * 128 + (((lane >> 4 << 1) ^ (lane & 7)) << 4) + (lane & 8) + (lane >> 4) * 4
                                          : lane * 32 + (lane >> 2) * 4);
                uint32_t tb = e == 0 ? ta ^ 32 : ta + 2048, tc = e == 2 ? ta + 1024 : ta ^ 64, td = e == 2 ? tb + 1024 : tb ^ 64;
                uint32_t live = m >= 0,
                    f0 = bars + (B_XFULL + 8 * w + ((10 * e + kb) & 7)) * 8;
                uint32_t f1 = m == GATE_W2 || m == GATE_W3 || m == GATE_W3B ? bars + (B_GATE + (m >= GATE_W3) + (m >= GATE_W3B)) * 8 : 0;
                if (lane) f0 = f1;
                if (lane > 1 || m < 0) f0 = 0;
                asm volatile("" : "+r"(ta), "+r"(tb), "+r"(tc), "+r"(td), "+r"(live), "+r"(f0));
                mbar_spin(bars + (m < 0 ? B_BK : B_LAND + (n & 7)) * 8, (n >> 3) & 1);
                TR5(lane == 0, n)
                while (true) {
                    uint32_t v[8];
#pragma unroll
                    for (int i = 0; i < 8; i++) v[i] = lds32(((i & 2) ? ((i & 1) ? td : tc) : (i & 1) ? tb : ta) + (i >> 2) * 4096);
                    const uint32_t bad = lop3<0xFE>(lop3<0x7E>(v[0], ep, v[1]), lop3<0x7E>(v[2], ep, v[3]), lop3<0x7E>(v[4], ep, v[5]));
                    if (!RARE(__any_sync(~0u, lop3<0xA8>(bad, lop3<0x7E>(v[6], ep, v[7]), live)))) break;
                    if (elect()) load_tile(mp, a, e, grp + 16 * w, kb, j, bars + (B_AGAIN + wq) * 8);
                    mbar_spin(bars + (B_AGAIN + wq) * 8, ph);
                    ph ^= 1;
                    STALE1(e)
                }
                TR5(lane == 0, 60 + n)
                if (f0) mbar_arrive(f0);
            }
        }
        if (wq == 0) {
#pragma unroll 1
            for (int w = 0; w < 2; w++) {
                const uint4* src = g_part + (size_t)(grp + 16 * w) * 40960;
                TR4(lane == 0, 90 + 2 * w)
                mbar_wait(bars + (B_RING + w) * 8, 1);
                TR4(lane == 0, 91 + 2 * w)
                if (elect()) {
                    const uint32_t fb = bars + (B_IN + w) * 8, rem = sb + OFF_OUT + w * 10240;
                    mbar_expect(fb, 10240);
                    bulk_ld(rem + 8192, &g_x1f[((grp + 16 * w) * 8 + j) * 640 + 512], 2048, fb);
#pragma unroll 1
                    for (int i = 0; i < 4; i++) bulk_ld(rem + i * 2048, src + ((j >> 2) + 2 * i) * 5120 + 4096 + j * 128, 2048, fb);
                }
            }
        }
#pragma unroll 1
        for (int uw = 0; uw < 2; uw++) {
            const int tile = grp + 16 * uw;
            const uint32_t ep = lds32(sb + M_EP), in = sb + OFF_OUT + uw * 10240 + wt * 16, sr = in - lane * 16;
            mbar_wait(bars + (B_IN + uw) * 8, 1);
            TR4(wt == 0, 94 + 3 * uw)
            uint4 u[4];
#pragma unroll
            for (int i = 0; i < 4; i++) u[i] = lds128(in + i * 2048);
            const uint4 base = lds128(in + 8192);
            const uint32_t ra = sb + M_F1 + (64 * uw + 16 * wq + g) * 4;
            const uint4 gr = scale16(lds64f(sb + M_GB + (64 + 2 * t) * 4), lds64f(sb + M_GB + (72 + 2 * t) * 4), __uint_as_float(lds32(ra)), __uint_as_float(lds32(ra + 32)));
            uint32_t it = 0;
            while (RARE(__any_sync(~0u, stale4(u, ep) & 1))) {
                ld_part4(u, g_part + (size_t)tile * 40960 + (j >> 2) * 5120 + 4096 + j * 128 + wt, 10240);
                STALE(3)
                if (++it > SPIN_LIMIT) SPIN_FAIL(58)
            }
            TR4(wt == 0, 95 + 3 * uw)
            const uint4 r = fin16(add2(add2(u[0], u[1]), add2(u[2], u[3])), base, gr);
            __syncwarp();
            stsm4(sr + (lane & 15) * 32 + (((lane >> 4) ^ ((lane >> 2) & 1)) << 4), r.x, r.y, r.z, r.w);
            __syncwarp();
            stg128(out + (size_t)(64 * tile + 16 * wq + (lane >> 1)) * D_ + 512 + 16 * j + 8 * (lane & 1), lds128(sr + (lane >> 1) * 32 + (((lane & 1) ^ ((lane >> 3) & 1)) << 4)));
            TR4(wt == 0, 96 + 3 * uw)
            __syncwarp();
        }
        TS(wt == 0, 21)
        if (wq == 0) {
            uint32_t it = 0;
            while (!mbar_try(bars + B_OWN * 8, 0)) { if (++it > SPIN_LIMIT) SPIN_FAIL(56) }
        }
        return;
    }

    TIDS
    const int uw = wg, tile = grp + 16 * uw, row0 = 64 * tile + 16 * wq;
    const bool leader = wt == 0; (void)leader;
    const uint32_t xfull = bars + (B_XFULL + 8 * uw) * 8, xempty = bars + B_XEMPTY * 8, wfull = bars + B_WFULL * 8, wempty = bars + B_WEMPTY * 8;
    const uint64_t dz = mkdesc(0) + pp.nil;
    auto xwait = [&](uint32_t n) { mbar_spin(xfull + (n & 7) * 8, (n >> 3) & 1); };
    asm volatile("setmaxnreg.inc.sync.aligned.u32 " STR(REG_MMA) ";");
    const uint32_t ep = lds32(sb + M_EP);
    uint32_t res[20] = {};
    {
        float acc[40];
        const uint32_t la = ((lane & 7) + 8 * (lane >> 4)) * 128 + (((2 * wq + ((lane >> 3) & 1)) ^ (lane & 7)) << 4);
        auto pos = [&](int n) { return ring_pos(uw, n, LEAD1) & 7; };
        auto slot = [&](int n) { return sb + OFF_XR + pos(n) * 8192; };
        float al[2], r1[2], n1[2];
        {
            float sl[4], sq[4], v[4];
            uint32_t z0[16], z1[16], zz[16];
            uint64_t bd = dz + b80_desc(dsb, 0, 0, 0), tb = (((uint64_t)8 << 32) | ((dsb + OFF_TAB) >> 4) | (7u << 16)) + pp.nil;
            auto ldfrag = [&](uint32_t (&z)[16], int n) {
#pragma unroll
                for (int q = 0; q < 4; q++) ldsm4t(slot(n) + la + q * 2048, z[4 * q], z[4 * q + 1], z[4 * q + 2], z[4 * q + 3]);
            };
            auto tile1 = [&](const uint32_t (&zc)[16], uint32_t (&zn)[16], int n, int h) {
                const bool last = h && n == 5, ok = mbar_test(xfull + (n + 1) * 8, 0), okw = !h || mbar_test(wfull + ((n + 1) >> 1) * 8, 0);
                const int kb = g1_block(n, j);
                wg_fence();
#pragma unroll
                for (int q = 0; q < 2; q++) wgmma_rs80(acc, zc[4 * q], zc[4 * q + 1], zc[4 * q + 2], zc[4 * q + 3], bd + q * B80_STEP, 1);
                wg_commit();
                wg_wait<1>();
                if (!ok) xwait(n + 1);
                if (!last) ldfrag(zn, n + 1);
#pragma unroll
                for (int e = 0; e < 16; e++) zz[e] = mul2(zc[e], zc[e]);
                const uint64_t t0 = last ? ((uint64_t)8 << 32) | ((dsb + M_NUL) >> 4) : tb;
                const uint32_t ts = last ? 0 : 14;
                wg_fence();
#pragma unroll
                for (int q = 0; q < 4; q++) wgmma_rs8(sl, zc[4 * q], zc[4 * q + 1], zc[4 * q + 2], zc[4 * q + 3], t0 + q * ts, 1);
#pragma unroll
                for (int q = 0; q < 4; q++) wgmma_rs8(sq, zz[4 * q], zz[4 * q + 1], zz[4 * q + 2], zz[4 * q + 3], t0 + q * ts, 1);
#pragma unroll
                for (int q = 2; q < 4; q++) wgmma_rs80(acc, zc[4 * q], zc[4 * q + 1], zc[4 * q + 2], zc[4 * q + 3], bd + q * B80_STEP, 1);
                wg_commit();
#pragma unroll
                for (int q = 0; q < 4; q++) ldsm4t_if(kb == j, slot(n) + la + q * 2048, &res[4 * q]);
                if (!h) ldsm4t_if(kb == 8 + (j >> 2), slot(n) + la + (j & 3) * 2048, &res[16]);
                if (lane < 2) mbar_arrive_after(xempty + pos(n) * 8, res[12], res[16], nil);
                if (!h && n && lane == 0) mbar_arrive(wempty + ((n >> 1) - 1) * 8);
                tb += 56;
                bd = bd + (uint64_t)B80_HALF;
                if (!okw) mbar_spin(wfull + ((n + 1) >> 1) * 8, 0);
                TR(leader, 100 + 10 * uw + n)
            };
            zero(acc); zero(sl); zero(sq);
            mbar_spin(bars + B_TAB * 8, 0);
            mbar_spin(wfull, 0);
            xwait(0);
            TS(leader, 32 + uw)
            ldfrag(z0, 0);
#pragma unroll 1
            for (int n = 0; n < 6; n += 2) { tile1(z0, z1, n, 0); tile1(z1, z0, n + 1, 1); }
#pragma unroll
            for (int n = 6; n < 10; n++) {
                const uint64_t ad = dz + (((dsb + OFF_XR + pos(n) * 8192) >> 4) | 0x10000u);
                const bool ok = n == 9 || mbar_test(xfull + ((n + 1) & 7) * 8, (n + 1) >> 3), okw = n != 7 || mbar_test(wfull + 4 * 8, 0);
                wg_fence();
#pragma unroll
                for (int q = 0; q < 4; q++) wgmma_ss80t(acc, ad + q * 128, bd + q * B80_STEP, 1);
                wg_commit();
                bd = bd + (uint64_t)B80_HALF;
                if (n == 9) ldsm4t_if(9 - (j & 1) == 8 + (j >> 2), slot(9) + la + (j & 3) * 2048, &res[16]);
                wg_wait<1>();
                if (n > 6 && lane < 2) mbar_arrive(xempty + pos(n - 1) * 8);
                if (!(n & 1) && lane == 0) mbar_arrive(wempty + ((n >> 1) - 1) * 8);
                if (n == 6) {
                    reg_fence(sl); reg_fence(sq);
#pragma unroll
                    for (int e = 0; e < 2; e++) {
                        v[2 * e] = t == 0 ? sl[2 * e] + sl[2 * e + 1] : t == 1 ? sq[2 * e] + sq[2 * e + 1] : sl[2 * e];
                        v[2 * e + 1] = t == 2 ? sl[2 * e + 1] : sq[2 * e];
                    }
                    st_peer(peer_addr(sb + OFF_ROW + uw * 2048 + wt * 16), __float_as_uint(v[0]), __float_as_uint(v[1]), __float_as_uint(v[2]), __float_as_uint(v[3]), peer_addr(bars + (B_SUMS + uw) * 8));
                    TS(leader && !uw, 59)
                }
                if (!ok) xwait(n + 1);
                if (!okw) mbar_spin(wfull + 4 * 8, 0);
                TR(leader, 100 + 10 * uw + n)
            }
            float4 k = lds128f(sb + M_KS);
            float k4 = __uint_as_float(lds32(sb + M_KS + 16));
#pragma unroll
            for (int w = 1; w < 5; w++) {
                const float4 o = lds128f(sb + M_KS + w * 32);
                k.x += o.x; k.y += o.y; k.z += o.z; k.w += o.w; k4 += __uint_as_float(lds32(sb + M_KS + w * 32 + 16));
            }
            mbar_spin(bars + (B_SUMS + uw) * 8, 0);
            TS(leader && !uw, 10)
            const float4 o = lds128f(sb + OFF_ROW + uw * 2048 + wt * 16);
            v[0] += o.x; v[1] += o.y; v[2] += o.z; v[3] += o.w;
            uint32_t fa[4];
#pragma unroll
            for (int h = 0; h < 2; h++) {
                const int l0 = lane & ~3;
                const float s1 = __shfl_sync(~0u, v[2 * h], l0), s2 = __shfl_sync(~0u, v[2 * h], l0 + 1), scc = __shfl_sync(~0u, v[2 * h], l0 + 2);
                const float scs = __shfl_sync(~0u, v[2 * h + 1], l0 + 2), sc = __shfl_sync(~0u, v[2 * h], l0 + 3), sqq = __shfl_sync(~0u, v[2 * h + 1], l0 + 3);
                const float m1 = s1 * (1.f / D_), va = fmaxf(s2 * (1.f / D_) - m1 * m1, 0.f) + 1e-5f, r = rsqrtf(va);
                const float m2 = (r * (sc - m1 * k.x) + k.y) * (1.f / D_);
                const float e2 = (r * (r * (sqq + m1 * (m1 * k.z - 2.f * scc)) + 2.f * (scs - m1 * k.w)) + k4) * (1.f / D_);
                al[h] = r * 0.5f * rsqrtf(fmaxf(e2 - m2 * m2, 0.f) + 1e-5f); r1[h] = r; n1[h] = -m1 * r;
                const uint32_t fb = split2(va * r), fx = split2(t == 3 ? -m2 * va * r : -m1), fc = __shfl_sync(~0u, fx, lane | 3);
                fa[h] = __byte_perm(fx, fb, t == 1 ? 0x5432 : t == 2 ? 0x7654 : 0x1010);
                fa[2 + h] = t ? 0 : fc >> 16;
            }
            mbar_spin(bars + B_VEC * 8, 0);
            wg_fence();
            wgmma_rs80k(acc, fa[0], fa[1], fa[2], fa[3], ((uint64_t)8 << 32) | ((dsb + OFF_F1) >> 4) | (((M_F1 - OFF_F1) >> 4) << 16), 1);
            wg_commit();
        }
        wg_wait<0>();
        reg_fence(acc);
        if (lane < 2) mbar_arrive_after(xempty + pos(9) * 8, res[16], 0, nil);
        if (lane == 0) mbar_arrive(wempty + 4 * 8);
        TS(leader, 34 + uw)
        {
            bf16* const trow = g_t + (size_t)(row0 + g + 2) * D_;
#pragma unroll
            for (int b = 0; b < 3; b++) {
                uint32_t p[8];
#pragma unroll
                for (int ii = 0; ii < 4; ii++) {
                    const int i = 4 * b + ii;
                    if (i >= 10) continue;
#pragma unroll
                    for (int h = 0; h < 2; h++) p[(i & 3) + 4 * h] = pack2(gelu2(acc[4 * i + 2 * h] * al[h]), gelu2(acc[4 * i + 2 * h + 1] * al[h]));
                }
                if (b < 2) {
                    const int gr = (2 * j + b) / 5, sh = (gr & 1) ? -1 - (gr >> 1) : 1 + (gr >> 1);
                    bf16* dst = trow + 64 * j + 32 * b + 8 * t;
                    const int w = (((g + sh) >> 2) & 2) + (t >> 1);
                    stg128_tag(dst + sh * D_, p[0], p[1], p[2], p[3], ep, w);
                    stg128_tag(dst + (sh + 8) * D_, p[4], p[5], p[6], p[7], ep, w ^ 2);
                    if (row0 + g < sh || row0 + g + 8 >= S_ + sh) stg128_tag(dst + (sh > 0 ? 0 : 8) * D_, 0, 0, 0, 0, ep, (sh > 0 ? 0 : 2) + (t >> 1));
                } else {
                    bf16* dst = trow + 512 + 16 * j + 4 * t;
                    const uint32_t lo = t == (g < 2), hi = t == (g >= 2), o = j & 1;
                    stg64(dst - 2 * D_, lop3<0xB8>(p[0], lo & ~o, ep), lop3<0xB8>(p[1], lo & o, ep));
                    stg64(dst + 6 * D_, lop3<0xB8>(p[4], hi & ~o, ep), lop3<0xB8>(p[5], hi & o, ep));
                    if (row0 + g + 8 >= S_ - 2) stg64(dst + 8 * D_, ep & (t == 1) & ~o, ep & (t == 1) & o);
                }
            }
        }
        signal_cnt(&g_cnt.g1[tile * 32], lane, 1, true);
        TS(leader, 36 + uw)
#pragma unroll
        for (int i = 0; i < 10; i++) {
            const float2 c = lds64f(sb + M_C + (8 * i + 2 * t) * 4), s = lds64f(sb + M_SB + (8 * i + 2 * t) * 4);
#pragma unroll
            for (int h = 0; h < 2; h++) {
                acc[4 * i + 2 * h] = fmaf(blo(res[2 * i + h]), r1[h], fmaf(n1[h], c.x, s.x));
                acc[4 * i + 2 * h + 1] = fmaf(bhi(res[2 * i + h]), r1[h], fmaf(n1[h], c.y, s.y));
            }
        }
        mbar_spin(wfull + 5 * 8, 0);
        xwait(10);
        TS(leader, 22 + uw)
        uint32_t xo = (4 + 2 * uw) * 8, xp = 0;
        uint64_t ad = dz + (((dsb + OFF_XR) >> 4) | 0x10000u) + xo * 64, bd = dz + b80_desc(dsb, 5, 0, 0);
#pragma unroll 1
        for (int i = 0; i < 5; i++) {
            const uint32_t x1 = xfull + ((3 + 2 * i) & 7) * 8, p1 = i < 3, x2 = xfull + (min(4 + 2 * i, 11) & 7) * 8, p2 = i < 2;
            const uint32_t w2 = wfull + (min(6 + i, 9) & 7) * 8, pw = i >= 2;
            const bool ok1 = mbar_test(x1, p1);
            wg_fence();
#pragma unroll
            for (int q = 0; q < 4; q++) wgmma_ss80(acc, ad + q * 2, bd + q * B80_STEP, 1);
            wg_commit();
            wg_wait<1>();
            if (lane < 2 && i) mbar_arrive(xempty + xp);
            if (lane == 0 && i) mbar_arrive(wempty + ((4 + i) & 7) * 8);
            if (!ok1) mbar_spin(x1, p1);
            const bool ok2 = mbar_test(x2, p2), okw = mbar_test(w2, pw);
            wg_fence();
#pragma unroll
            for (int q = 0; q < 4; q++) wgmma_ss80(acc, ad + 512 + q * 2, bd + B80_HALF + q * B80_STEP, 1);
            wg_commit();
            const uint32_t xc = xo;
            xp = xo + 8; xo = (xo + 16) & 56;
            ad += xo ? 1024 : 1024 - 4096;
            bd += i == 2 ? 2 * B80_HALF - 8192 + (8192ll << 16) : 2 * B80_HALF;
            asm volatile("" : "+l"(ad), "+l"(bd));
            wg_wait<1>();
            if (lane < 2) mbar_arrive(xempty + xc);
            if (!ok2) mbar_spin(x2, p2);
            if (!okw) mbar_spin(w2, pw);
            TR(leader, (uw ? 86 : 20) + 2 * i)
        }
        wg_wait<0>();
        reg_fence(acc);
        if (lane < 2) mbar_arrive(xempty + xp);
        if (lane == 0) mbar_arrive(wempty + (9 & 7) * 8);
        TS(leader, 38 + uw)
        float a0 = 0.f, b0 = 0.f, a1 = 0.f, b1 = 0.f;
        uint32_t x2[20];
#pragma unroll
        for (int i = 0; i < 5; i++) {
            uint32_t* p = &x2[4 * i];
#pragma unroll
            for (int e = 0; e < 4; e++) p[e] = pack2(acc[8 * i + 2 * e], acc[8 * i + 2 * e + 1]);
#pragma unroll
            for (int e = 0; e < 4; e++) p[e] = lop3<0xB8>(p[e], (((wt >> 3) ^ (wt << 2)) & 7) == e, ep);
            stg128(&g_x2f[(tile * 40 + (i < 4 ? 4 * j + i : 32 + j)) * 128 + wt], p[0], p[1], p[2], p[3]);
#pragma unroll
            for (int e = 0; e < 8; e += 4) {
                const float* u = &acc[8 * i + e];
                a0 += u[0] + u[1]; b0 = fmaf(u[0], u[0], fmaf(u[1], u[1], b0));
                a1 += u[2] + u[3]; b1 = fmaf(u[2], u[2], fmaf(u[3], u[3], b1));
            }
        }
#pragma unroll
        for (int o = 1; o < 4; o *= 2) {
            a0 += __shfl_xor_sync(~0u, a0, o); b0 += __shfl_xor_sync(~0u, b0, o);
            a1 += __shfl_xor_sync(~0u, a1, o); b1 += __shfl_xor_sync(~0u, b1, o);
        }
        if (t < 2) stg64(&g_stats[(tile * 8 + j) * 64 + 16 * wq + g + 8 * t], tag(__float_as_uint(t ? a1 : a0), ep), __float_as_uint(t ? b1 : b0));
        signal_cnt(&g_cnt.g2[tile * 32], lane, 1, true);
        TS(leader, 40 + uw)
#pragma unroll
        for (int i = 0; i < 10; i++) {
            const float2 c = lds64f(sb + M_GB + (8 * i + 2 * t) * 4), e = lds64f(sb + M_CI + (8 * i + 2 * t) * 4);
#pragma unroll
            for (int h = 0; h < 2; h++)
                res[2 * i + h] = fma2(pack2(c.x, c.y), x2[2 * i + h], pack2(e.x * blo(res[2 * i + h]), e.y * bhi(res[2 * i + h])));
        }
#pragma unroll
        for (int i = 0; i < 20; i++) asm volatile("" : "+r"(res[i]));
    }
    float acc0[64], acc1[44];
    float2 q[4];
    {
        uint4 f0, f1, f2, f3;
        auto xseq = [&](int kb) { return ring_pos(uw, kb, XLEAD) & 7; };
        auto step = [&](const uint4& f, uint64_t bd) {
            wg_fence();
            wgmma_rs128(acc0, f.x, f.y, f.z, f.w, bd, 1);
            wgmma_rs88(acc1, f.x, f.y, f.z, f.w, bd + 512, 1);
            wg_commit();
        };
        const uint32_t xa = sb + OFF_XR + wt * 16;
        const float2* const gs = &g_stats[(tile * 8 + 2 * t) * 64 + 16 * wq + g];
        zero(acc0); zero(acc1);
        uint32_t xs = xseq(0);
        xwait(20);
        TS(leader, 42 + uw)
        f0 = lds128(xa + xs * 8192); f1 = lds128(xa + xs * 8192 + 2048);
#pragma unroll
        for (int i = 0; i < 4; i++) q[i] = ld_stat(gs + (i & 1) * 64 + 8 * (i >> 1));
        mbar_spin(wfull + (10 & 7) * 8, (10 >> 3) & 1);
#pragma unroll 1
        for (int kb = 0; kb < 10; kb++) {
            const uint32_t wn = 10 + 2 * kb;
            const uint64_t bd = dz + (((dsb + OFF_W + (wn & 7) * 16384) >> 4) | (256u << 16));
            step(f0, bd);
            wg_wait<1>();
            if (kb && lane == 0) mbar_arrive(wempty + ((wn - 1) & 7) * 8);
            f2 = lds128(xa + xs * 8192 + 4096); f3 = lds128(xa + xs * 8192 + 6144);
            const bool w1 = mbar_test(wfull + ((wn + 1) & 7) * 8, (wn >> 3) & 1), x1 = mbar_test(xfull + ((21 + kb) & 7) * 8, ((21 + kb) >> 3) & 1);
            step(f1, bd + 128);
            if (!w1) mbar_spin(wfull + ((wn + 1) & 7) * 8, (wn >> 3) & 1);
            step(f2, bd + 1024);
            if (lane < 2) mbar_arrive_after(xempty + xs * 8, f2.x, f3.x, nil);
            wg_wait<1>();
            if (lane == 0) mbar_arrive(wempty + (wn & 7) * 8);
            xs = xseq(kb + 1);
            if (x1) { f0 = lds128(xa + xs * 8192); f1 = lds128(xa + xs * 8192 + 2048); }
            const bool w2 = mbar_test(wfull + ((wn + 2) & 7) * 8, ((wn + 2) >> 3) & 1);
            step(f3, bd + 1152);
            if (kb < 9 && !x1) { xwait(21 + kb); f0 = lds128(xa + xs * 8192); f1 = lds128(xa + xs * 8192 + 2048); }
            if (!w2) mbar_spin(wfull + ((wn + 2) & 7) * 8, ((wn + 2) >> 3) & 1);
            if (kb == 4) {
                uint32_t it = 0;
                while (RARE(__any_sync(~0u, ((__float_as_uint(q[0].x) ^ ep) | (__float_as_uint(q[1].x) ^ ep) | (__float_as_uint(q[2].x) ^ ep) | (__float_as_uint(q[3].x) ^ ep)) & 1))) {
#pragma unroll
                    for (int i = 0; i < 4; i++) q[i] = ld_stat(gs + (i & 1) * 64 + 8 * (i >> 1));
                    SPIN_CHECK(49)
                }
                float a0 = q[0].x + q[1].x, b0 = q[0].y + q[1].y, a1 = q[2].x + q[3].x, b1 = q[2].y + q[3].y;
#pragma unroll
                for (int o = 1; o < 4; o *= 2) {
                    a0 += __shfl_xor_sync(~0u, a0, o); b0 += __shfl_xor_sync(~0u, b0, o);
                    a1 += __shfl_xor_sync(~0u, a1, o); b1 += __shfl_xor_sync(~0u, b1, o);
                }
                a0 *= 1.f / D_; a1 *= 1.f / D_;
                const float r0 = 0.5f * rsqrtf(fmaxf(b0 * (1.f / D_) - a0 * a0, 0.f) + 1e-5f), r1 = 0.5f * rsqrtf(fmaxf(b1 * (1.f / D_) - a1 * a1, 0.f) + 1e-5f);
                const uint32_t sel = t == 0 ? 0x1010 : t == 1 ? 0x4432 : 0x4444;
                if (t == 0) { sts32(sb + M_F1 + (64 * uw + 16 * wq + g) * 4, __float_as_uint(r0)); sts32(sb + M_F1 + (64 * uw + 16 * wq + g + 8) * 4, __float_as_uint(r1)); }
                q[2] = make_float2(8.f * 0.0356774081f * r0 * r0 * r0, 2.f * 0.7978845608f * r0);
                q[3] = make_float2(8.f * 0.0356774081f * r1 * r1 * r1, 2.f * 0.7978845608f * r1);
                q[1] = make_float2(__uint_as_float(__byte_perm(split2(-a0), 0, sel)), __uint_as_float(__byte_perm(split2(-a1), 0, sel)));
            }
            if (kb == 6) {
#pragma unroll
                for (int i = 0; i < 5; i++) stg128(&g_x1f[(tile * 8 + j) * 640 + i * 128 + wt], res[4 * i], res[4 * i + 1], res[4 * i + 2], res[4 * i + 3]);
            }
            if (kb == 8) asm volatile("fence.proxy.async.global;" ::: "memory");
            TR(leader, 10 * uw + kb)
        }
        const uint64_t fd = ((uint64_t)8 << 32) | ((dsb + OFF_W + 6 * 16384) >> 4);
        wg_fence();
        wgmma_rs128k(acc0, __float_as_uint(q[1].x), __float_as_uint(q[1].y), 0, 0, fd, 1);
        wgmma_rs88k(acc1, __float_as_uint(q[1].x), __float_as_uint(q[1].y), 0, 0, fd + 128, 1);
        wg_commit();
        if (lane == 0) {
            mbar_arrive(bars + B_XFREE * 8);
            asm volatile("mbarrier.arrive.shared::cluster.b64 _, [%0];" ::"r"(peer_addr(bars + B_XFREE * 8)) : "memory");
        }
    }
    const uint32_t recv = sb + recv_off(uw) + wt * 16;
    uint32_t ha[48] = {}, hb[48], hx[12];
    uint64_t wb = dz + (((dsb + OFF_W) >> 4) | (512u << 16));
    auto wdesc = [&](int n) { return wb + (n & 7) * 1024; };
    auto wwait = [&](int n) { mbar_spin(wfull + (n & 7) * 8, (n >> 3) & 1); };
    auto wfree = [&](int n) { if (lane == 0) mbar_arrive(wempty + (n & 7) * 8); };
    auto fresh = [&]() { wb += pp.nil; asm volatile("" : "+l"(wb)); };
    uint32_t pk[32];
    {
        float P0[64];
        const float2 r0 = q[2], r1 = q[3];
        const uint32_t ra = peer_addr(recv), rb = peer_addr(bars + (B_RECV + 4 * uw) * 8);
        auto conv32 = [&](const float* v, int b) {
#pragma unroll
            for (int i = 0; i < 4; i++) {
                ha[8 * b + 2 * i] = pack2(gelu2r(v[4 * i], r0), gelu2r(v[4 * i + 1], r0));
                ha[8 * b + 2 * i + 1] = pack2(gelu2r(v[4 * i + 2], r1), gelu2r(v[4 * i + 3], r1));
            }
#pragma unroll
            for (int s = 2 * b; s < 2 * b + 2; s++) st_peer(ra + s * 2048, ha[4 * s], ha[4 * s + 1], ha[4 * s + 2], ha[4 * s + 3], rb + (b >> 1) * 8);
        };
        auto fetch = [&](int k) {
            mbar_spin(bars + (B_RECV + 4 * uw + k) * 8, 0);
#pragma unroll
            for (int s = 4 * k; s < 4 * k + 4; s++) { const uint4 x = lds128(recv + s * 2048); hb[4 * s] = x.x; hb[4 * s + 1] = x.y; hb[4 * s + 2] = x.z; hb[4 * s + 3] = x.w; }
        };
        auto stage = [&](int n, const uint32_t* a, int steps, int sc) {
            wwait(n);
            wg_fence();
#pragma unroll
            for (int s = 0; s < steps; s++) wgmma_rs128(P0, a[4 * s], a[4 * s + 1], a[4 * s + 2], a[4 * s + 3], wdesc(n) + s * 128, sc || s);
            wg_commit();
        };
        wg_wait<0>();
        reg_fence(acc0); reg_fence(acc1);
        wfree(29); wfree(30);
        TS(leader, 44 + uw)
        uint32_t hr[6];
#pragma unroll
        for (int i = 0; i < 6; i++) {
            const float2 r = (i & 1) ? r1 : r0;
            hr[i] = pack2(gelu2r(acc1[32 + 2 * i], r), gelu2r(acc1[33 + 2 * i], r));
        }
        if (uw) mbar_spin(bars + B_XFREE * 8, 0);
        st_peer(ra + 24576, hr[0], hr[1], hr[2], hr[3], rb + 24);
        asm volatile("st.async.shared::cluster.mbarrier::complete_tx::bytes.v2.b32 [%0], {%1, %2}, [%3];" ::"r"(ra + 26624 - wt * 8), "r"(hr[4]), "r"(hr[5]), "r"(rb + 24) : "memory");
        conv32(&acc1[0], 4);
        conv32(&acc1[16], 5);
        TS(leader, 46 + uw)
        stage(31, &ha[32], 4, 0);
#pragma unroll
        for (int b = 0; b < 4; b++) {
            conv32(&acc0[16 * b], b);
            if (b == 3) {
                fetch(2);
                mbar_spin(bars + (B_RECV + 4 * uw + 3) * 8, 0);
                const uint4 x = lds128(recv + 24576);
                const uint2 y = lds64(recv + 26624 - wt * 8);
                const uint32_t hp[6] = {x.x, x.y, x.z, x.w, y.x, y.y};
#pragma unroll
                for (int i = 0; i < 6; i++) { hx[i] = (j & 1) ? hp[i] : hr[i]; hx[6 + i] = (j & 1) ? hr[i] : hp[i]; }
            }
            if (!(b & 1)) wwait(32 + (b >> 1));
            wg_fence();
#pragma unroll
            for (int s = 0; s < 2; s++) wgmma_rs128(P0, ha[8 * b + 4 * s], ha[8 * b + 4 * s + 1], ha[8 * b + 4 * s + 2], ha[8 * b + 4 * s + 3], wdesc(32 + (b >> 1)) + (2 * (b & 1) + s) * 128, 1);
            wg_commit();
            if (!(b & 1)) { wg_wait<1>(); wfree(31 + (b >> 1)); }
        }
        TR(leader, 64 + 10 * uw)
        fresh();
        stage(34, &hb[32], 4, 1); wg_wait<1>(); wfree(33);
        fetch(0);
        stage(35, hx, 3, 1); wg_wait<1>(); wfree(34);
        fetch(1);
        stage(36, &hb[0], 4, 1); wg_wait<1>(); wfree(35);
        stage(37, &hb[16], 4, 1); wg_wait<1>(); wfree(36);
        wg_wait<0>();
        reg_fence(P0);
        pack_part<64>(pk, P0, ep);
        uint32_t all = 0;
#pragma unroll
        for (int i = 0; i < 32; i++) all |= pk[i];
        if (lane == 0) mbar_arrive_after(wempty + (37 & 7) * 8, all, 0, nil);
        TR(leader, 65 + 10 * uw)
    }
    {
        uint4* const dst = g_part + (size_t)(tile * 8 + j) * 5120 + wt;
        const uint4* const src = g_part + (size_t)tile * 40960 + j * 512 + wt;
        float F[2][32];
        uint4 gb[4];
        float rr[2];
        float2 gf[8];
        uint4 base[4], u1[4], u2[4], u3[4];
#pragma unroll
        for (int c = 2; c < 5; c++) {
            float (&P)[32] = F[c & 1];
            fresh();
#pragma unroll
            for (int s = 0; s < 27; s++) {
                const int e = s < 8 ? 0 : s < 15 ? 1 : s < 23 ? 2 : 3, o = s - (e == 0 ? 0 : e == 1 ? 8 : e == 2 ? 15 : 23), n = 30 + 4 * c + e;
                const uint32_t* a = s < 12 ? &ha[4 * s] : s < 15 ? &hx[4 * (s - 12)] : &hb[4 * (s - 15)];
                if (o == 0) wwait(n);
                if (o == 0 || s == 1) wg_fence();
                wgmma_rs64(P, a[0], a[1], a[2], a[3], wdesc(n) + o * 128, s);
                if (o == 0) { wg_commit(); wg_wait<1>(); if (c > 2 || s) wfree(n - 1); }
                if (s == 0 && c > 2) { reg_fence(F[~c & 1]); pack_part<32>(pk, F[~c & 1], ep); }
                if (c == 2 && s % 3 == 0 && s < 24) st_part(dst + g4_block(s / 12, j) * 512 + (s / 3 & 3) * 128, &pk[4 * (s / 3)]);
                if (c == 3 && s % 4 == 1 && s < 16) st_part(dst + g4_block(2, j) * 512 + s / 4 * 128, &pk[4 * (s / 4)]);
                if (c == 4 && s % ST3 == 0 && s < 4 * ST3) st_part(dst + g4_block(3, j) * 512 + s / ST3 * 128, &pk[4 * (s / ST3)]);
                if (c == 4 && s >= 4 && s < 8) base[s - 4] = ldcg128(&g_x1f[(tile * 8 + j) * 640 + (s - 4) * 128 + wt]);
                if (c == 4 && s >= 19 && s < 23) { gf[2 * s - 38] = lds64f(sb + M_GB + (16 * (s - 19) + 2 * t) * 4); gf[2 * s - 37] = lds64f(sb + M_GB + (16 * (s - 19) + 8 + 2 * t) * 4); }
                if (c == 4 && s >= 12 && s < 14) rr[s - 12] = __uint_as_float(lds32(sb + M_F1 + (64 * uw + 16 * wq + g + 8 * (s - 12)) * 4));
                if (c == 4 && s >= 8 && s < 12) u1[s - 8] = ld_part(src + (j ^ 6) * 5120 + (s - 8) * 128);
                if (c == 4 && s >= 15 && s < 19) u2[s - 15] = ld_part(src + (j ^ 4) * 5120 + (s - 15) * 128);
                if (c == 4 && s >= LD3 && s < LD3 + 4) u3[s - LD3] = ld_part(src + (j ^ 2) * 5120 + (s - LD3) * 128);
                if (27 * (c - 2) + s == R_GATE && lane == 0) mbar_arrive(bars + (B_RING + uw) * 8);
                if (s == 7 || s == 14 || s == 22 || s == 26) wg_commit();
                if (c == 4) { TR(leader && s == 7, 68 + 10 * uw) TR(leader && s == 14, 69 + 10 * uw) TR(leader && s == 22, 70 + 10 * uw) }
            }
            TR(leader, 64 + c + (c == 4 ? 3 : 0) + 10 * uw)
        }
        float (&O)[32] = F[0];
#pragma unroll
        for (int i = 0; i < 4; i++) gb[i] = scale16(gf[2 * i], gf[2 * i + 1], rr[0], rr[1]);
        uint32_t it = 0;
        while (__any_sync(~0u, (stale4(u1, ep) | stale4(u2, ep) | stale4(u3, ep)) & 1)) {
            ld_part4(u1, src + (j ^ 6) * 5120, 128); ld_part4(u2, src + (j ^ 4) * 5120, 128); ld_part4(u3, src + (j ^ 2) * 5120, 128);
            STALE(6)
            SPIN_CHECK(58)
        }
        TR(leader, 73 + 10 * uw)
#pragma unroll
        for (int i = 0; i < 4; i++) u1[i] = add2(add2(u1[i], u2[i]), u3[i]);
        TS(leader, 50 + uw)
        wg_wait<0>();
        reg_fence(O);
        TS(leader, 48 + uw)
        const uint32_t so = sb + recv_off(uw) + wq * 2048;
#pragma unroll
        for (int i = 0; i < 4; i++) {
            const float* o = &O[8 * i];
            const uint4 r = fin16(add2(u1[i], make_uint4(pack2(o[0], o[1]), pack2(o[2], o[3]), pack2(o[4], o[5]), pack2(o[6], o[7]))), base[i], gb[i]);
            stsm4(so + (lane & 15) * 128 + (((2 * i + (lane >> 4)) ^ (lane & 7)) << 4), r.x, r.y, r.z, r.w);
        }
        TR4(leader, 100 + uw)
        __syncwarp();
#pragma unroll
        for (int i = 0; i < 4; i++) {
            const int row = (lane >> 3) + 4 * i;
            stg128(out + (size_t)(row0 + row) * D_ + 64 * j + 8 * (lane & 7), lds128(so + row * 128 + (((lane & 7) ^ (row & 7)) << 4)));
        }
        TS(leader, 24 + uw)
        warp_arrive(bars + B_OWN * 8);
    }
}

typedef CUresult (*EncFn)(CUtensorMap*, CUtensorMapDataType, cuuint32_t, void*, const cuuint64_t*, const cuuint64_t*, const cuuint32_t*,
                          const cuuint32_t*, CUtensorMapInterleave, CUtensorMapSwizzle, CUtensorMapL2promotion, CUtensorMapFloatOOBfill);

static void enc(EncFn fn, CUtensorMap* m, void* p, int rank, const cuuint64_t* dims, const cuuint64_t* strides, const cuuint32_t* box, bool plain = false) {
    const CUtensorMapSwizzle sw = box[0] > 64 || plain ? CU_TENSOR_MAP_SWIZZLE_NONE : CU_TENSOR_MAP_SWIZZLE_128B;
    cuuint32_t es[5] = {1, 1, 1, 1, 1};
    CUresult r = fn(m, CU_TENSOR_MAP_DATA_TYPE_BFLOAT16, rank, p, dims, strides, box, es, CU_TENSOR_MAP_INTERLEAVE_NONE, sw,
                    CU_TENSOR_MAP_L2_PROMOTION_L2_128B, CU_TENSOR_MAP_FLOAT_OOB_FILL_NONE);
    (void)r;
}
static void enc2(EncFn fn, CUtensorMap* m, void* p, uint64_t cols, uint64_t rows, uint32_t bc, uint32_t br, bool plain = false) {
    cuuint64_t dims[2] = {cols, rows}, st[1] = {cols * 2};
    cuuint32_t box[2] = {bc, br};
    enc(fn, m, p, 2, dims, st, box, plain);
}

extern "C" void kernel_launch(void* const* d_in, const int* in_sizes, int n_in, void* d_out, int out_size) {
    static Maps mp;
    static Ptrs pp;
    static void* cached[13];
    bool same = true;
    for (int i = 0; i < 13; i++) same = same && (cached[i] == d_in[i]);
    if (!same) {
        void* fnp = nullptr;
        cudaDriverEntryPointQueryResult qr;
        cudaGetDriverEntryPoint("cuTensorMapEncodeTiled", &fnp, cudaEnableDefault, &qr);
        EncFn fn = (EncFn)fnp;
        cudaGetSymbolAddress((void**)&pp.s, g_scratch);
        void *x1T = g_x1T, *t = g_t;
        cuuint64_t dq[3] = {64, S_, 10}, sq[2] = {D_ * 2, 128};
        cuuint32_t bq[3] = {64, 16, 10};
        enc(fn, &mp.q, d_in[0], 3, dq, sq, bq);
        enc2(fn, &mp.k, d_in[1], D_, S_, 80, 67); enc2(fn, &mp.v, d_in[2], D_, S_, 80, 64);
        enc2(fn, &mp.qT, g_qT, 16 * D_, 128, 80, 128);
        enc2(fn, &mp.x[0], x1T, S_, D_, 64, 64); enc2(fn, &mp.x[1], (bf16*)t + 2 * D_, D_, S_, 64, 64);
        enc2(fn, &mp.x[2], g_x2f, 64, 320 * 64, 64, 64, true);
        enc2(fn, &mp.w1, d_in[7], D_, D_, 64, 64); enc2(fn, &mp.w1h, d_in[7], D_, D_, 64, 160); enc2(fn, &mp.w3h, d_in[9], F_, D_, 64, 160);
        enc2(fn, &mp.wmod, d_in[12], 6 * D_, D_, 64, 160);
        const cuuint64_t R = D_ * 2;
        cuuint64_t da[5] = {D_, 2, 4, 4, 16}, sa[4] = {R, 8 * R, 2 * R, 32 * R}, db[5] = {D_, 2, 2, 4, 8}, sb[4] = {R, 8 * R, 2 * R, 16 * R};
        cuuint32_t ba[5] = {64, 2, 4, 4, 4}, bb[5] = {64, 2, 2, 4, 8};
        enc(fn, &mp.w2a, d_in[8], 5, da, sa, ba); enc(fn, &mp.w2b, (bf16*)d_in[8] + 512 * D_, 5, db, sb, bb);
        cuuint64_t dw[3] = {64, D_, 27}, sw[2] = {F_ * 2, 128};
        cuuint32_t bw[3] = {64, 32, 3};
        enc(fn, &mp.w3a, d_in[9], 3, dw, sw, bw);
        enc2(fn, &mp.w3b, d_in[9], F_, D_, 24, 32);
        enc2(fn, &mp.w4[0], d_in[10], D_, F_, 64, 64); enc2(fn, &mp.w4[1], d_in[10], D_, F_, 64, 48);
        pp.q = (const bf16*)d_in[0]; pp.w_mod = (const bf16*)d_in[12]; pp.shift_k = (const bf16*)d_in[3];
        pp.ssm_k = (const bf16*)d_in[4]; pp.ssm_D = (const bf16*)d_in[5]; pp.w1 = (const bf16*)d_in[7]; pp.w2 = (const bf16*)d_in[8];
        pp.w4 = (const bf16*)d_in[10]; pp.c = (const bf16*)d_in[11];
        cudaFuncSetAttribute(fused_kernel, cudaFuncAttributeMaxDynamicSharedMemorySize, SMEM_BYTES);
        for (int i = 0; i < 13; i++) cached[i] = d_in[i];
    }
    fused_kernel<<<NCTA, NTHR, SMEM_BYTES, cudaStreamPerThread>>>(pp, (bf16*)d_out, mp);
}
```

```cpp
#include <cuda_runtime.h>
#include <cuda_bf16.h>
#include <cuda.h>
#include <stdint.h>
#include <stdio.h>

typedef __nv_bfloat16 bf16;

constexpr int S_ = 2048, D_ = 640, F_ = 1728;
constexpr int NCTA = 132, NTHR = 512;

constexpr int TAB_BYTES = 9216, VEC_BYTES = 1440;
struct Counters {
    unsigned kv[8 * 32];
    unsigned q[4 * 32], x[4 * 32];
    unsigned wr[32], tab[32], uv[32], cs[32], cs2[32], done[32];
    unsigned g1[32 * 32];
    unsigned g2[32 * 32];
};
struct Scratch {
    Counters cnt;
    unsigned epoch;
    alignas(1024) bf16 qst[2 * S_];
    alignas(1024) uint4 wr[2 * 8 * 10 * 128];
    alignas(1024) uint2 mod[2 * 6 * D_];
    alignas(1024) uint4 tab[(TAB_BYTES + 8 * VEC_BYTES) / 16];
    alignas(1024) float uv[2 * 3 * D_];
    alignas(1024) float cs3[2 * 1920];
    alignas(1024) uint4 cs3b[8 * 216];
    alignas(1024) float2 stats[32 * 8 * 64];
    alignas(1024) bf16 kvT[D_ * S_];
    alignas(1024) bf16 qT[D_ * S_];
    alignas(1024) bf16 x1T[D_ * S_];
    alignas(1024) bf16 t[(S_ + 4) * D_];
    alignas(1024) uint4 x2f[32 * 40 * 128];
    alignas(1024) uint4 x1f[32 * 8 * 5 * 128];
    alignas(1024) uint4 part[32 * 8 * 10 * 4 * 128];
};
__device__ Scratch g_scratch;
#define g_kvT (pp.s->kvT)
#define g_qT (pp.s->qT)
#define g_x1T (pp.s->x1T)
#define g_qst (pp.s->qst)
#define g_t (pp.s->t)
#define g_x2f (pp.s->x2f)
#define g_x1f (pp.s->x1f)
#define g_part (pp.s->part)
#define g_wr (pp.s->wr)
#define g_mod (pp.s->mod)
#define g_tab (pp.s->tab)
#define g_uv (pp.s->uv)
#define g_cs3 (pp.s->cs3)
#define g_cs3b (pp.s->cs3b)
#define g_stats (pp.s->stats)
#define g_cnt (pp.s->cnt)
#define g_epoch (pp.s->epoch)

struct Maps {
    CUtensorMap k, v, q;
    CUtensorMap qT;
    CUtensorMap x[3];
    CUtensorMap w1, w1h, w3h, wmod;
    CUtensorMap w2a, w2b;
    CUtensorMap w3a, w3b;
    CUtensorMap w4[2];
};

struct Ptrs {
    Scratch* s;
    uint64_t nil;
    const bf16 *q, *w_mod, *shift_k, *ssm_k, *ssm_D, *w1, *w2, *w4, *c;
};

constexpr int OFF_W = 0;
constexpr int OFF_XR = 131072;
constexpr int OFF_REM = 196608;
constexpr int OFF_TAB = OFF_REM + 5 * 4096;
constexpr int OFF_ROW = OFF_TAB + 4608;
constexpr int OFF_F1 = OFF_ROW + 4096;
constexpr int RECV_BYTES = 30720;
constexpr int OFF_M = OFF_REM + RECV_BYTES;
constexpr int OFF_OUT = OFF_XR + 32768;
static_assert(OFF_F1 + 1280 <= OFF_M, "G1 map");
constexpr int OFF_ST = 0;
constexpr int OFF_SSM = 20480;
constexpr int OFF_WM = 0;
constexpr int OFF_QIN = 49152;
constexpr int OFF_QT = 49152;
constexpr int OFF_Z = OFF_TAB;
constexpr int OFF_RING = 80896;
constexpr int OFF_KIN = OFF_RING, OFF_VIN = OFF_KIN + 2 * 10752;
constexpr int OFF_CH = OFF_RING + 3 * 16384, CH_BYTES = 13312, OFF_P = 5120;
static_assert(OFF_RING + 5 * 16384 <= OFF_CH + 3 * CH_BYTES && OFF_CH + 5 * CH_BYTES <= OFF_REM, "the last two rings replace channels 0..2");
constexpr int M_BAR = OFF_M;
constexpr int M_F1 = OFF_M + 832;
constexpr int M_GB = M_F1 + 1280, M_C = M_GB + 320, M_SB = M_C + 320, M_CI = M_SB + 320;
constexpr int M_KS = M_CI + 320;
constexpr int M_AB = M_KS + 160;
constexpr int M_EP = M_AB + 80;
constexpr int M_SINK = M_EP + 16;
constexpr int M_NUL = M_SINK + 16;
constexpr int M_TS = M_NUL + 128;
constexpr int SMEM_BYTES = M_TS;
static_assert(SMEM_BYTES <= 232448, "smem");

enum { B_WFULL = 0, B_WEMPTY = 8, B_XEMPTY = 16, B_XFULL = 24  ,
       B_RAW = 44, B_QIN = 45, B_SSM = 46, B_VEC = 47, B_VEC3 = 48, B_WM = 49, B_TAB = 50, B_QRDY = 51,
       B_MODR = 52, B_RAW2 = 53, B_RAW3 = 54, B_GATE = 56, B_SUMS = 62, B_RECV = 64  ,
       B_LAND = 72, B_AGAIN = 80, B_RETRY = 84,
       B_XS = 88, B_R1 = 89, B_BK = 90, B_KVS = 91,
       B_XFREE = 92, B_OWN = 93, B_IN = 94,
       B_RING = 96   };
#define T_KVB 1800
#define T_SSM 3300
#define PF_T0 4800
#define PF_DT 420
#define Q_UNROLL 1
#define HELP_T 1000
#define R_GATE 34
#define REG_AUX 40
#define REG_SVC 40
#define REG_MMA 216
#define STR2(x) #x
#define STR(x) STR2(x)
#define ST3 1
#define LD3 23
#define GATE_W2 7
#define GATE_W3 27
#define GATE_W3B 37
#define W3_N2 13
#define LEAD2 2
#define LEAD1 4
#define XLEAD 3

#define SPIN_FAIL(code) __trap();
#define SPIN_LIMIT (1u << 22)
#define STALE(c)
#define STALE1(c)
#define TS(c, i)
#define TG(c, i)
#define TR(c, i)
#define TR2(c, i)
#define TR4(c, i)
#define TR5(c, i)
#define SPIN_CHECK(code) asm volatile("" ::"r"(it));
#define RARE(x) __builtin_expect((x) != 0, 0)
__device__ __forceinline__ uint32_t s2u(const void* p) { return (uint32_t)__cvta_generic_to_shared(p); }
__device__ __forceinline__ bool elect() {
    uint32_t p;
    asm volatile("{.reg .pred P; elect.sync _|P, 0xffffffff; selp.u32 %0,1,0,P;}" : "=r"(p));
    return p != 0;
}
__device__ __forceinline__ void mbar_init(uint32_t b, uint32_t n) { asm volatile("mbarrier.init.shared.b64 [%0], %1;" ::"r"(b), "r"(n)); }
__device__ __forceinline__ void mbar_expect(uint32_t b, uint32_t bytes) {
    asm volatile("mbarrier.arrive.expect_tx.shared.b64 _, [%0], %1;" ::"r"(b), "r"(bytes) : "memory");
}
__device__ __forceinline__ void mbar_arrive(uint32_t b) { asm volatile("mbarrier.arrive.shared.b64 _, [%0];" ::"r"(b) : "memory"); }
__device__ __forceinline__ void mbar_arrive_after(uint32_t b, uint32_t v0, uint32_t v1, uint32_t nil) { mbar_arrive(b + ((v0 | v1) & nil)); }
__device__ __forceinline__ void warp_arrive(uint32_t b) { __syncwarp(); if (elect()) mbar_arrive(b); }
__device__ __forceinline__ uint32_t peer_addr(uint32_t a) {
    uint32_t r;
    asm("{\n.reg .b32 q;\nmov.u32 q, %%cluster_ctarank;\nxor.b32 q, q, 1;\nmapa.shared::cluster.u32 %0, %1, q;\n}" : "=r"(r) : "r"(a));
    return r;
}
__device__ __forceinline__ bool mbar_test(uint32_t b, uint32_t parity) {
    uint32_t ok;
    asm volatile("{.reg .pred P; mbarrier.test_wait.parity.shared.b64 P, [%1], %2; selp.u32 %0,1,0,P;}" : "=r"(ok) : "r"(b), "r"(parity) : "memory");
    return ok != 0;
}
__device__ __forceinline__ bool mbar_try(uint32_t b, uint32_t parity) {
    uint32_t ok;
    asm volatile("{.reg .pred P; mbarrier.try_wait.parity.shared.b64 P, [%1], %2; selp.u32 %0,1,0,P;}" : "=r"(ok) : "r"(b), "r"(parity) : "memory");
    return ok != 0;
}
__device__ __forceinline__ void mbar_wait(uint32_t b, uint32_t parity) {
    if (__all_sync(0xffffffffu, mbar_try(b, parity))) return;
    uint32_t it = 0;
    while (!__all_sync(0xffffffffu, mbar_try(b, parity))) { if (++it > SPIN_LIMIT) SPIN_FAIL((b >> 3) & 63) }
}
__device__ __forceinline__ void mbar_spin(uint32_t b, uint32_t parity) {
    asm volatile("{\n.reg .pred P;\nSPIN:\nmbarrier.try_wait.parity.shared.b64 P, [%0], %1;\n@!P bra.uni SPIN;\n}" ::"r"(b), "r"(parity) : "memory");
}
__device__ __forceinline__ void bar_sync(int id, int n) { asm volatile("bar.sync %0, %1;" ::"r"(id), "r"(n) : "memory"); }
__device__ __forceinline__ void fence_async_smem() { asm volatile("fence.proxy.async.shared::cta;" ::: "memory"); }
__device__ __forceinline__ void wait_cnt(const unsigned* p, unsigned target, bool tagged = false) {
    unsigned v, it = 0;
    do {
        asm volatile("ld.relaxed.gpu.global.u32 %0, [%1];" : "=r"(v) : "l"(p) : "memory");
        SPIN_CHECK(60 + (target & 3))
    } while (!__all_sync(0xffffffffu, v >= target));
    if (!tagged) asm volatile("fence.acquire.gpu;" ::: "memory");
}
__device__ __forceinline__ void signal_cnt(unsigned* p, int lane, int n, bool tagged = false) {
    if (tagged) asm volatile("{\n.reg .pred P;\nsetp.lt.s32 P, %1, %2;\n@P red.relaxed.gpu.global.add.u32 [%0], %3;\n}" ::"l"(p), "r"(lane), "r"(n), "r"(1) : "memory");
    else if (lane < n) asm volatile("red.release.gpu.global.add.u32 [%0], 1;" ::"l"(p) : "memory");
    __syncwarp();
}
__device__ __forceinline__ uint32_t clock_lo() { uint32_t c; asm volatile("mov.u32 %0, %%clock;" : "=r"(c)); return c; }
__device__ __forceinline__ void wait_clock(uint32_t c0, uint32_t t) {
    asm volatile("{\n.reg .pred P;\n.reg .b32 c;\nWAIT:\nnanosleep.u32 20;\nmov.u32 c, %%clock;\nsub.u32 c, c, %0;\nsetp.lt.u32 P, c, %1;\n@P bra.uni WAIT;\n}" ::"r"(c0), "r"(t) : "memory");
}
__device__ __forceinline__ void tma_ld2(uint32_t dst, const CUtensorMap* m, int c0, int c1, uint32_t bar) {
    asm volatile("cp.async.bulk.tensor.2d.shared::cluster.global.mbarrier::complete_tx::bytes [%0], [%1, {%3, %4}], [%2];"
                 ::"r"(dst), "l"(m), "r"(bar), "r"(c0), "r"(c1) : "memory");
}
__device__ __forceinline__ void tma_ld3(uint32_t dst, const CUtensorMap* m, int c0, int c1, int c2, uint32_t bar) {
    asm volatile("cp.async.bulk.tensor.3d.shared::cluster.global.mbarrier::complete_tx::bytes [%0], [%1, {%3, %4, %5}], [%2];"
                 ::"r"(dst), "l"(m), "r"(bar), "r"(c0), "r"(c1), "r"(c2) : "memory");
}
__device__ __forceinline__ void tma_ld5(uint32_t dst, const CUtensorMap* m, int col, int blk, uint32_t bar) {
    asm volatile("cp.async.bulk.tensor.5d.shared::cluster.global.mbarrier::complete_tx::bytes [%0], [%1, {%3, %4, %4, %4, %5}], [%2];"
                 ::"r"(dst), "l"(m), "r"(bar), "r"(col), "r"(0), "r"(blk) : "memory");
}
__device__ __forceinline__ void bulk_ld(uint32_t dst, const void* src, uint32_t bytes, uint32_t bar) {
    asm volatile("cp.async.bulk.shared::cluster.global.mbarrier::complete_tx::bytes [%0], [%1], %2, [%3];" ::"r"(dst), "l"(src), "r"(bytes), "r"(bar) : "memory");
}
__device__ __forceinline__ void l2_prefetch(const void* p, uint32_t bytes) {
    asm volatile("cp.async.bulk.prefetch.L2.global [%0], %1;" ::"l"(p), "r"(bytes) : "memory");
}
__device__ __forceinline__ void wg_fence() { asm volatile("wgmma.fence.sync.aligned;" ::: "memory"); }
__device__ __forceinline__ void wg_commit() { asm volatile("wgmma.commit_group.sync.aligned;" ::: "memory"); }
template <int N> __device__ __forceinline__ void wg_wait() { asm volatile("wgmma.wait_group.sync.aligned %0;" ::"n"(N) : "memory"); }
template <int N> __device__ __forceinline__ void reg_fence(float (&d)[N]) {
#pragma unroll
    for (int i = 0; i < N; i++) asm volatile("" : "+f"(d[i])::"memory");
}
template <int N> __device__ __forceinline__ void zero(float (&d)[N]) {
#pragma unroll
    for (int i = 0; i < N; i++) asm volatile("mov.b32 %0, 0;" : "=f"(d[i]));
}
__device__ __forceinline__ uint32_t lds32(uint32_t a) { uint32_t v; asm volatile("ld.shared.b32 %0, [%1];" : "=r"(v) : "r"(a)); return v; }
__device__ __forceinline__ uint2 lds64(uint32_t a) { uint2 v; asm volatile("ld.shared.v2.b32 {%0,%1}, [%2];" : "=r"(v.x), "=r"(v.y) : "r"(a)); return v; }
__device__ __forceinline__ float2 lds64f(uint32_t a) { float2 v; asm volatile("ld.shared.v2.f32 {%0,%1}, [%2];" : "=f"(v.x), "=f"(v.y) : "r"(a)); return v; }
__device__ __forceinline__ void sts32(uint32_t a, uint32_t v) { asm volatile("st.shared.b32 [%0], %1;" ::"r"(a), "r"(v) : "memory"); }
__device__ __forceinline__ void sts64f(uint32_t a, float x, float y) { asm volatile("st.shared.v2.f32 [%0], {%1,%2};" ::"r"(a), "f"(x), "f"(y) : "memory"); }
__device__ __forceinline__ void sts128(uint32_t a, uint32_t x, uint32_t y, uint32_t z, uint32_t w) {
    asm volatile("st.shared.v4.b32 [%0], {%1,%2,%3,%4};" ::"r"(a), "r"(x), "r"(y), "r"(z), "r"(w) : "memory");
}
__device__ __forceinline__ void sts128f(uint32_t a, float x, float y, float z, float w) {
    asm volatile("st.shared.v4.f32 [%0], {%1,%2,%3,%4};" ::"r"(a), "f"(x), "f"(y), "f"(z), "f"(w) : "memory");
}
__device__ __forceinline__ uint4 lds128(uint32_t a) {
    uint4 v;
    asm volatile("ld.shared.v4.b32 {%0,%1,%2,%3}, [%4];" : "=r"(v.x), "=r"(v.y), "=r"(v.z), "=r"(v.w) : "r"(a) : "memory");
    return v;
}
__device__ __forceinline__ float4 lds128f(uint32_t a) {
    float4 v;
    asm volatile("ld.shared.v4.f32 {%0,%1,%2,%3}, [%4];" : "=f"(v.x), "=f"(v.y), "=f"(v.z), "=f"(v.w) : "r"(a) : "memory");
    return v;
}
__device__ __forceinline__ void stg128(void* p, uint32_t x, uint32_t y, uint32_t z, uint32_t w) {
    asm volatile("st.global.v4.b32 [%0], {%1,%2,%3,%4};" ::"l"(p), "r"(x), "r"(y), "r"(z), "r"(w) : "memory");
}
__device__ __forceinline__ void stg128(void* p, uint4 v) { stg128(p, v.x, v.y, v.z, v.w); }
__device__ __forceinline__ void stg128_if(void* p, uint4 v, int on) {
    asm volatile("{\n.reg .pred p;\nsetp.ne.s32 p, %5, 0;\n@p st.global.v4.b32 [%0], {%1,%2,%3,%4};\n}" ::"l"(p), "r"(v.x), "r"(v.y), "r"(v.z), "r"(v.w), "r"(on) : "memory");
}
__device__ __forceinline__ void stg64(void* p, uint32_t x, uint32_t y) { asm volatile("st.global.v2.b32 [%0], {%1,%2};" ::"l"(p), "r"(x), "r"(y) : "memory"); }
__device__ __forceinline__ void stsm4(uint32_t a, uint32_t r0, uint32_t r1, uint32_t r2, uint32_t r3) {
    asm volatile("stmatrix.sync.aligned.m8n8.x4.shared.b16 [%0], {%1,%2,%3,%4};" ::"r"(a), "r"(r0), "r"(r1), "r"(r2), "r"(r3) : "memory");
}
__device__ __forceinline__ void stsm4t(uint32_t a, uint32_t r0, uint32_t r1, uint32_t r2, uint32_t r3) {
    asm volatile("stmatrix.sync.aligned.m8n8.x4.trans.shared.b16 [%0], {%1,%2,%3,%4};" ::"r"(a), "r"(r0), "r"(r1), "r"(r2), "r"(r3) : "memory");
}
__device__ __forceinline__ void ldsm4t_if(bool p, uint32_t a, uint32_t* r) {
    asm volatile("{\n.reg .pred p;\nsetp.ne.u32 p, %5, 0;\n@p ldmatrix.sync.aligned.m8n8.x4.trans.shared.b16 {%0,%1,%2,%3}, [%4];\n}"
                 : "+r"(r[0]), "+r"(r[1]), "+r"(r[2]), "+r"(r[3]) : "r"(a), "r"((uint32_t)p) : "memory");
}
__device__ __forceinline__ void ldsm4t(uint32_t a, uint32_t& r0, uint32_t& r1, uint32_t& r2, uint32_t& r3) {
    asm volatile("ldmatrix.sync.aligned.m8n8.x4.trans.shared.b16 {%0,%1,%2,%3}, [%4];" : "=r"(r0), "=r"(r1), "=r"(r2), "=r"(r3) : "r"(a) : "memory");
}
__device__ __forceinline__ uint32_t pack2(float lo, float hi) {
    uint32_t r;
    asm("cvt.rn.bf16x2.f32 %0, %1, %2;" : "=r"(r) : "f"(hi), "f"(lo));
    return r;
}
__device__ __forceinline__ uint32_t mul2(uint32_t a, uint32_t b) { uint32_t r; asm("mul.rn.bf16x2 %0, %1, %2;" : "=r"(r) : "r"(a), "r"(b)); return r; }
__device__ __forceinline__ uint32_t fma2(uint32_t a, uint32_t b, uint32_t c) { uint32_t r; asm("fma.rn.bf16x2 %0, %1, %2, %3;" : "=r"(r) : "r"(a), "r"(b), "r"(c)); return r; }
__device__ __forceinline__ uint32_t add2(uint32_t a, uint32_t b) { uint32_t r; asm("add.rn.bf16x2 %0, %1, %2;" : "=r"(r) : "r"(a), "r"(b)); return r; }
__device__ __forceinline__ void hmma(float (&d)[4], uint32_t a0, uint32_t a1, uint32_t a2, uint32_t a3, uint32_t b0, uint32_t b1) {
    asm volatile("mma.sync.aligned.m16n8k16.row.col.f32.bf16.bf16.f32 {%0,%1,%2,%3}, {%4,%5,%6,%7}, {%8,%9}, {%0,%1,%2,%3};"
        : "+f"(d[0]), "+f"(d[1]), "+f"(d[2]), "+f"(d[3]) : "r"(a0), "r"(a1), "r"(a2), "r"(a3), "r"(b0), "r"(b1));
}
__device__ __forceinline__ float blo(uint32_t w) { return __uint_as_float(w << 16); }
__device__ __forceinline__ float bhi(uint32_t w) { return __uint_as_float(w & 0xffff0000u); }
__device__ __forceinline__ float rbf(float x) { return __bfloat162float(__float2bfloat16_rn(x)); }
__device__ __forceinline__ uint32_t ldg32(const void* p) { uint32_t v; asm volatile("ld.global.nc.b32 %0, [%1];" : "=r"(v) : "l"(p)); return v; }
__device__ __forceinline__ uint2 ldg64(const void* p) { uint2 v; asm volatile("ld.global.nc.v2.b32 {%0,%1}, [%2];" : "=r"(v.x), "=r"(v.y) : "l"(p)); return v; }
__device__ __forceinline__ uint4 ldg128(const void* p) {
    uint4 v;
    asm volatile("ld.global.nc.v4.b32 {%0,%1,%2,%3}, [%4];" : "=r"(v.x), "=r"(v.y), "=r"(v.z), "=r"(v.w) : "l"(p));
    return v;
}
__device__ __forceinline__ uint4 ldcg128(const void* p) {
    uint4 v;
    asm volatile("ld.global.cg.v4.u32 {%0,%1,%2,%3}, [%4];" : "=r"(v.x), "=r"(v.y), "=r"(v.z), "=r"(v.w) : "l"(p) : "memory");
    return v;
}
__device__ __forceinline__ float4 ldcg128f(const void* p) {
    float4 v;
    asm volatile("ld.global.cg.v4.f32 {%0,%1,%2,%3}, [%4];" : "=f"(v.x), "=f"(v.y), "=f"(v.z), "=f"(v.w) : "l"(p) : "memory");
    return v;
}
__device__ __forceinline__ float2 ldcg64f(const void* p) { float2 v; asm volatile("ld.global.cg.v2.f32 {%0,%1}, [%2];" : "=f"(v.x), "=f"(v.y) : "l"(p) : "memory"); return v; }
__device__ __forceinline__ float ldcg32f(const void* p) { float v; asm volatile("ld.global.cg.f32 %0, [%1];" : "=f"(v) : "l"(p) : "memory"); return v; }
__device__ __forceinline__ float2 ld_stat(const float2* p) {
    float2 v;
    asm volatile("{\n.reg .b64 q;\nld.relaxed.gpu.global.b64 q, [%2];\nmov.b64 {%0, %1}, q;\n}" : "=f"(v.x), "=f"(v.y) : "l"(p) : "memory");
    return v;
}
__device__ __forceinline__ uint32_t ld_cold(const unsigned* p) { uint32_t v; asm volatile("ld.relaxed.gpu.global.u32 %0, [%1];" : "=r"(v) : "l"(p) : "memory"); return v; }
__device__ __forceinline__ uint2 ld_mod(const uint2* p) {
    uint64_t v;
    asm volatile("ld.relaxed.gpu.global.b64 %0, [%1];" : "=l"(v) : "l"(p) : "memory");
    return make_uint2((uint32_t)v, (uint32_t)(v >> 32));
}
__device__ __forceinline__ float silu(float x) {
    float e, r;
    asm("ex2.approx.ftz.f32 %0, %1;" : "=f"(e) : "f"(x * -1.4426950408889634f));
    asm("rcp.approx.ftz.f32 %0, %1;" : "=f"(r) : "f"(1.f + e));
    return x * r;
}
__device__ __forceinline__ float gelu2(float h) {
    float u = h * fmaf(h * h, 8.f * 0.0356774081f, 2.f * 0.7978845608f);
    float th;
    asm("tanh.approx.f32 %0, %1;" : "=f"(th) : "f"(u));
    return fmaf(h, th, h);
}
__device__ __forceinline__ float gelu2r(float a, float2 k) {
    float th;
    asm("tanh.approx.f32 %0, %1;" : "=f"(th) : "f"(a * fmaf(a * a, k.x, k.y)));
    return fmaf(a, th, a);
}

__device__ __forceinline__ void conv_channel(float (&d)[64], uint32_t pa, uint64_t db) {
    asm volatile("{\n.reg .b32 a0, a1, a2, a3, b0, b1, b2, b3, t0, t1;\n.reg .b64 d;\nld.shared.b32 a0, [%64];\nld.shared.b32 a1, [%64+128];\nld.shared.b32 a2, [%64+-128];\nmov.b32 a3, a0;\n"
        "ld.shared.b32 t0, [%64+256];\nld.shared.b32 t1, [%64+384];\nadd.s64 d, %65, 0;\nwgmma.fence.sync.aligned;\nwgmma.mma_async.sync.aligned.m64n128k16.f32.bf16.bf16 {%0, %1, %2, %3, %4, %5, %6, %7, %8, %9, %10, %11, %12, %13, %14, %15, %16, %17, %18, %19, %20, %21, %22, %23, %24, %25, %26, %27, %28, %29, %30, %31, %32, %33, %34, %35, %36, %37, %38, %39, %40, %41, %42, %43, %44, %45, %46, %47, %48, %49, %50, %51, %52, %53, %54, %55, %56, %57, %58, %59, %60, %61, %62, %63}, {a0, a1, a2, a3}, d, 0, 1, 1, 0;\nwgmma.commit_group.sync.aligned;\nwgmma.wait_group.sync.aligned 1;\nmov.b32 b2, a1;\nmov.b32 b0, t0;\nmov.b32 b3, t0;\nmov.b32 b1, t1;\n"
        "ld.shared.b32 t0, [%64+512];\nld.shared.b32 t1, [%64+640];\nadd.s64 d, %65, 8;\nwgmma.fence.sync.aligned;\nwgmma.mma_async.sync.aligned.m64n128k16.f32.bf16.bf16 {%0, %1, %2, %3, %4, %5, %6, %7, %8, %9, %10, %11, %12, %13, %14, %15, %16, %17, %18, %19, %20, %21, %22, %23, %24, %25, %26, %27, %28, %29, %30, %31, %32, %33, %34, %35, %36, %37, %38, %39, %40, %41, %42, %43, %44, %45, %46, %47, %48, %49, %50, %51, %52, %53, %54, %55, %56, %57, %58, %59, %60, %61, %62, %63}, {b0, b1, b2, b3}, d, 1, 1, 1, 0;\nwgmma.commit_group.sync.aligned;\nwgmma.wait_group.sync.aligned 1;\nmov.b32 a2, b1;\nmov.b32 a0, t0;\nmov.b32 a3, t0;\nmov.b32 a1, t1;\n"
        "ld.shared.b32 t0, [%64+768];\nld.shared.b32 t1, [%64+896];\nadd.s64 d, %65, 16;\nwgmma.fence.sync.aligned;\nwgmma.mma_async.sync.aligned.m64n128k16.f32.bf16.bf16 {%0, %1, %2, %3, %4, %5, %6, %7, %8, %9, %10, %11, %12, %13, %14, %15, %16, %17, %18, %19, %20, %21, %22, %23, %24, %25, %26, %27, %28, %29, %30, %31, %32, %33, %34, %35, %36, %37, %38, %39, %40, %41, %42, %43, %44, %45, %46, %47, %48, %49, %50, %51, %52, %53, %54, %55, %56, %57, %58, %59, %60, %61, %62, %63}, {a0, a1, a2, a3}, d, 1, 1, 1, 0;\nwgmma.commit_group.sync.aligned;\nwgmma.wait_group.sync.aligned 1;\nmov.b32 b2, a1;\nmov.b32 b0, t0;\nmov.b32 b3, t0;\nmov.b32 b1, t1;\n"
        "ld.shared.b32 t0, [%64+1024];\nld.shared.b32 t1, [%64+1152];\nadd.s64 d, %65, 24;\nwgmma.fence.sync.aligned;\nwgmma.mma_async.sync.aligned.m64n128k16.f32.bf16.bf16 {%0, %1, %2, %3, %4, %5, %6, %7, %8, %9, %10, %11, %12, %13, %14, %15, %16, %17, %18, %19, %20, %21, %22, %23, %24, %25, %26, %27, %28, %29, %30, %31, %32, %33, %34, %35, %36, %37, %38, %39, %40, %41, %42, %43, %44, %45, %46, %47, %48, %49, %50, %51, %52, %53, %54, %55, %56, %57, %58, %59, %60, %61, %62, %63}, {b0, b1, b2, b3}, d, 1, 1, 1, 0;\nwgmma.commit_group.sync.aligned;\nwgmma.wait_group.sync.aligned 1;\nmov.b32 a2, b1;\nmov.b32 a0, t0;\nmov.b32 a3, t0;\nmov.b32 a1, t1;\n"
        "ld.shared.b32 t0, [%64+1280];\nld.shared.b32 t1, [%64+1408];\nadd.s64 d, %65, 32;\nwgmma.fence.sync.aligned;\nwgmma.mma_async.sync.aligned.m64n128k16.f32.bf16.bf16 {%0, %1, %2, %3, %4, %5, %6, %7, %8, %9, %10, %11, %12, %13, %14, %15, %16, %17, %18, %19, %20, %21, %22, %23, %24, %25, %26, %27, %28, %29, %30, %31, %32, %33, %34, %35, %36, %37, %38, %39, %40, %41, %42, %43, %44, %45, %46, %47, %48, %49, %50, %51, %52, %53, %54, %55, %56, %57, %58, %59, %60, %61, %62, %63}, {a0, a1, a2, a3}, d, 1, 1, 1, 0;\nwgmma.commit_group.sync.aligned;\nwgmma.wait_group.sync.aligned 1;\nmov.b32 b2, a1;\nmov.b32 b0, t0;\nmov.b32 b3, t0;\nmov.b32 b1, t1;\n"
        "ld.shared.b32 t0, [%64+1536];\nld.shared.b32 t1, [%64+1664];\nadd.s64 d, %65, 40;\nwgmma.fence.sync.aligned;\nwgmma.mma_async.sync.aligned.m64n128k16.f32.bf16.bf16 {%0, %1, %2, %3, %4, %5, %6, %7, %8, %9, %10, %11, %12, %13, %14, %15, %16, %17, %18, %19, %20, %21, %22, %23, %24, %25, %26, %27, %28, %29, %30, %31, %32, %33, %34, %35, %36, %37, %38, %39, %40, %41, %42, %43, %44, %45, %46, %47, %48, %49, %50, %51, %52, %53, %54, %55, %56, %57, %58, %59, %60, %61, %62, %63}, {b0, b1, b2, b3}, d, 1, 1, 1, 0;\nwgmma.commit_group.sync.aligned;\nwgmma.wait_group.sync.aligned 1;\nmov.b32 a2, b1;\nmov.b32 a0, t0;\nmov.b32 a3, t0;\nmov.b32 a1, t1;\n"
        "ld.shared.b32 t0, [%64+1792];\nld.shared.b32 t1, [%64+1920];\nadd.s64 d, %65, 48;\nwgmma.fence.sync.aligned;\nwgmma.mma_async.sync.aligned.m64n128k16.f32.bf16.bf16 {%0, %1, %2, %3, %4, %5, %6, %7, %8, %9, %10, %11, %12, %13, %14, %15, %16, %17, %18, %19, %20, %21, %22, %23, %24, %25, %26, %27, %28, %29, %30, %31, %32, %33, %34, %35, %36, %37, %38, %39, %40, %41, %42, %43, %44, %45, %46, %47, %48, %49, %50, %51, %52, %53, %54, %55, %56, %57, %58, %59, %60, %61, %62, %63}, {a0, a1, a2, a3}, d, 1, 1, 1, 0;\nwgmma.commit_group.sync.aligned;\nwgmma.wait_group.sync.aligned 1;\nmov.b32 b2, a1;\nmov.b32 b0, t0;\nmov.b32 b3, t0;\nmov.b32 b1, t1;\n"
        "ld.shared.b32 t0, [%64+2048];\nld.shared.b32 t1, [%64+2176];\nadd.s64 d, %65, 56;\nwgmma.fence.sync.aligned;\nwgmma.mma_async.sync.aligned.m64n128k16.f32.bf16.bf16 {%0, %1, %2, %3, %4, %5, %6, %7, %8, %9, %10, %11, %12, %13, %14, %15, %16, %17, %18, %19, %20, %21, %22, %23, %24, %25, %26, %27, %28, %29, %30, %31, %32, %33, %34, %35, %36, %37, %38, %39, %40, %41, %42, %43, %44, %45, %46, %47, %48, %49, %50, %51, %52, %53, %54, %55, %56, %57, %58, %59, %60, %61, %62, %63}, {b0, b1, b2, b3}, d, 1, 1, 1, 0;\nwgmma.commit_group.sync.aligned;\nwgmma.wait_group.sync.aligned 1;\nmov.b32 a2, b1;\nmov.b32 a0, t0;\nmov.b32 a3, t0;\nmov.b32 a1, t1;\n"
        "ld.shared.b32 t0, [%64+2304];\nld.shared.b32 t1, [%64+2432];\nadd.s64 d, %65, 64;\nwgmma.fence.sync.aligned;\nwgmma.mma_async.sync.aligned.m64n96k16.f32.bf16.bf16 {%0, %1, %2, %3, %4, %5, %6, %7, %8, %9, %10, %11, %12, %13, %14, %15, %16, %17, %18, %19, %20, %21, %22, %23, %24, %25, %26, %27, %28, %29, %30, %31, %32, %33, %34, %35, %36, %37, %38, %39, %40, %41, %42, %43, %44, %45, %46, %47}, {a0, a1, a2, a3}, d, 1, 1, 1, 0;\nwgmma.commit_group.sync.aligned;\nwgmma.wait_group.sync.aligned 1;\nmov.b32 b2, a1;\nmov.b32 b0, t0;\nmov.b32 b3, t0;\nmov.b32 b1, t1;\n"
        "ld.shared.b32 t0, [%64+2560];\nld.shared.b32 t1, [%64+2688];\nadd.s64 d, %65, 72;\nwgmma.fence.sync.aligned;\nwgmma.mma_async.sync.aligned.m64n96k16.f32.bf16.bf16 {%0, %1, %2, %3, %4, %5, %6, %7, %8, %9, %10, %11, %12, %13, %14, %15, %16, %17, %18, %19, %20, %21, %22, %23, %24, %25, %26, %27, %28, %29, %30, %31, %32, %33, %34, %35, %36, %37, %38, %39, %40, %41, %42, %43, %44, %45, %46, %47}, {b0, b1, b2, b3}, d, 1, 1, 1, 0;\nwgmma.commit_group.sync.aligned;\nwgmma.wait_group.sync.aligned 1;\nmov.b32 a2, b1;\nmov.b32 a0, t0;\nmov.b32 a3, t0;\nmov.b32 a1, t1;\n"
        "ld.shared.b32 t0, [%64+2816];\nld.shared.b32 t1, [%64+2944];\nadd.s64 d, %65, 80;\nwgmma.fence.sync.aligned;\nwgmma.mma_async.sync.aligned.m64n88k16.f32.bf16.bf16 {%0, %1, %2, %3, %4, %5, %6, %7, %8, %9, %10, %11, %12, %13, %14, %15, %16, %17, %18, %19, %20, %21, %22, %23, %24, %25, %26, %27, %28, %29, %30, %31, %32, %33, %34, %35, %36, %37, %38, %39, %40, %41, %42, %43}, {a0, a1, a2, a3}, d, 1, 1, 1, 0;\nwgmma.commit_group.sync.aligned;\nwgmma.wait_group.sync.aligned 1;\nmov.b32 b2, a1;\nmov.b32 b0, t0;\nmov.b32 b3, t0;\nmov.b32 b1, t1;\n"
        "ld.shared.b32 t0, [%64+3072];\nld.shared.b32 t1, [%64+3200];\nadd.s64 d, %65, 88;\nwgmma.fence.sync.aligned;\nwgmma.mma_async.sync.aligned.m64n88k16.f32.bf16.bf16 {%0, %1, %2, %3, %4, %5, %6, %7, %8, %9, %10, %11, %12, %13, %14, %15, %16, %17, %18, %19, %20, %21, %22, %23, %24, %25, %26, %27, %28, %29, %30, %31, %32, %33, %34, %35, %36, %37, %38, %39, %40, %41, %42, %43}, {b0, b1, b2, b3}, d, 1, 1, 1, 0;\nwgmma.commit_group.sync.aligned;\nwgmma.wait_group.sync.aligned 1;\nmov.b32 a2, b1;\nmov.b32 a0, t0;\nmov.b32 a3, t0;\nmov.b32 a1, t1;\n"
        "ld.shared.b32 t0, [%64+3328];\nld.shared.b32 t1, [%64+3456];\nadd.s64 d, %65, 96;\nwgmma.fence.sync.aligned;\nwgmma.mma_async.sync.aligned.m64n80k16.f32.bf16.bf16 {%0, %1, %2, %3, %4, %5, %6, %7, %8, %9, %10, %11, %12, %13, %14, %15, %16, %17, %18, %19, %20, %21, %22, %23, %24, %25, %26, %27, %28, %29, %30, %31, %32, %33, %34, %35, %36, %37, %38, %39}, {a0, a1, a2, a3}, d, 1, 1, 1, 0;\nwgmma.commit_group.sync.aligned;\nwgmma.wait_group.sync.aligned 1;\nmov.b32 b2, a1;\nmov.b32 b0, t0;\nmov.b32 b3, t0;\nmov.b32 b1, t1;\n"
        "ld.shared.b32 t0, [%64+3584];\nld.shared.b32 t1, [%64+3712];\nadd.s64 d, %65, 104;\nwgmma.fence.sync.aligned;\nwgmma.mma_async.sync.aligned.m64n80k16.f32.bf16.bf16 {%0, %1, %2, %3, %4, %5, %6, %7, %8, %9, %10, %11, %12, %13, %14, %15, %16, %17, %18, %19, %20, %21, %22, %23, %24, %25, %26, %27, %28, %29, %30, %31, %32, %33, %34, %35, %36, %37, %38, %39}, {b0, b1, b2, b3}, d, 1, 1, 1, 0;\nwgmma.commit_group.sync.aligned;\nwgmma.wait_group.sync.aligned 1;\nmov.b32 a2, b1;\nmov.b32 a0, t0;\nmov.b32 a3, t0;\nmov.b32 a1, t1;\n"
        "ld.shared.b32 t0, [%64+3840];\nld.shared.b32 t1, [%64+3968];\nadd.s64 d, %65, 112;\nwgmma.fence.sync.aligned;\nwgmma.mma_async.sync.aligned.m64n72k16.f32.bf16.bf16 {%0, %1, %2, %3, %4, %5, %6, %7, %8, %9, %10, %11, %12, %13, %14, %15, %16, %17, %18, %19, %20, %21, %22, %23, %24, %25, %26, %27, %28, %29, %30, %31, %32, %33, %34, %35}, {a0, a1, a2, a3}, d, 1, 1, 1, 0;\nwgmma.commit_group.sync.aligned;\nwgmma.wait_group.sync.aligned 1;\nmov.b32 b2, a1;\nmov.b32 b0, t0;\nmov.b32 b3, t0;\nmov.b32 b1, t1;\n"
        "ld.shared.b32 t0, [%64+4096];\nld.shared.b32 t1, [%64+4224];\nadd.s64 d, %65, 120;\nwgmma.fence.sync.aligned;\nwgmma.mma_async.sync.aligned.m64n72k16.f32.bf16.bf16 {%0, %1, %2, %3, %4, %5, %6, %7, %8, %9, %10, %11, %12, %13, %14, %15, %16, %17, %18, %19, %20, %21, %22, %23, %24, %25, %26, %27, %28, %29, %30, %31, %32, %33, %34, %35}, {b0, b1, b2, b3}, d, 1, 1, 1, 0;\nwgmma.commit_group.sync.aligned;\nwgmma.wait_group.sync.aligned 1;\nmov.b32 a2, b1;\nmov.b32 a0, t0;\nmov.b32 a3, t0;\nmov.b32 a1, t1;\n"
        "ld.shared.b32 t0, [%64+4352];\nld.shared.b32 t1, [%64+4480];\nadd.s64 d, %65, 128;\nwgmma.fence.sync.aligned;\nwgmma.mma_async.sync.aligned.m64n64k16.f32.bf16.bf16 {%0, %1, %2, %3, %4, %5, %6, %7, %8, %9, %10, %11, %12, %13, %14, %15, %16, %17, %18, %19, %20, %21, %22, %23, %24, %25, %26, %27, %28, %29, %30, %31}, {a0, a1, a2, a3}, d, 1, 1, 1, 0;\nwgmma.commit_group.sync.aligned;\nwgmma.wait_group.sync.aligned 1;\nmov.b32 b2, a1;\nmov.b32 b0, t0;\nmov.b32 b3, t0;\nmov.b32 b1, t1;\n"
        "ld.shared.b32 t0, [%64+4608];\nld.shared.b32 t1, [%64+4736];\nadd.s64 d, %65, 136;\nwgmma.fence.sync.aligned;\nwgmma.mma_async.sync.aligned.m64n64k16.f32.bf16.bf16 {%0, %1, %2, %3, %4, %5, %6, %7, %8, %9, %10, %11, %12, %13, %14, %15, %16, %17, %18, %19, %20, %21, %22, %23, %24, %25, %26, %27, %28, %29, %30, %31}, {b0, b1, b2, b3}, d, 1, 1, 1, 0;\nwgmma.commit_group.sync.aligned;\nwgmma.wait_group.sync.aligned 1;\nmov.b32 a2, b1;\nmov.b32 a0, t0;\nmov.b32 a3, t0;\nmov.b32 a1, t1;\n"
        "ld.shared.b32 t0, [%64+4864];\nld.shared.b32 t1, [%64+4992];\nadd.s64 d, %65, 144;\nwgmma.fence.sync.aligned;\nwgmma.mma_async.sync.aligned.m64n56k16.f32.bf16.bf16 {%0, %1, %2, %3, %4, %5, %6, %7, %8, %9, %10, %11, %12, %13, %14, %15, %16, %17, %18, %19, %20, %21, %22, %23, %24, %25, %26, %27}, {a0, a1, a2, a3}, d, 1, 1, 1, 0;\nwgmma.commit_group.sync.aligned;\nwgmma.wait_group.sync.aligned 1;\nmov.b32 b2, a1;\nmov.b32 b0, t0;\nmov.b32 b3, t0;\nmov.b32 b1, t1;\n"
        "ld.shared.b32 t0, [%64+5120];\nld.shared.b32 t1, [%64+5248];\nadd.s64 d, %65, 152;\nwgmma.fence.sync.aligned;\nwgmma.mma_async.sync.aligned.m64n56k16.f32.bf16.bf16 {%0, %1, %2, %3, %4, %5, %6, %7, %8, %9, %10, %11, %12, %13, %14, %15, %16, %17, %18, %19, %20, %21, %22, %23, %24, %25, %26, %27}, {b0, b1, b2, b3}, d, 1, 1, 1, 0;\nwgmma.commit_group.sync.aligned;\nwgmma.wait_group.sync.aligned 1;\nmov.b32 a2, b1;\nmov.b32 a0, t0;\nmov.b32 a3, t0;\nmov.b32 a1, t1;\n"
        "ld.shared.b32 t0, [%64+5376];\nld.shared.b32 t1, [%64+5504];\nadd.s64 d, %65, 160;\nwgmma.fence.sync.aligned;\nwgmma.mma_async.sync.aligned.m64n48k16.f32.bf16.bf16 {%0, %1, %2, %3, %4, %5, %6, %7, %8, %9, %10, %11, %12, %13, %14, %15, %16, %17, %18, %19, %20, %21, %22, %23}, {a0, a1, a2, a3}, d, 1, 1, 1, 0;\nwgmma.commit_group.sync.aligned;\nwgmma.wait_group.sync.aligned 1;\nmov.b32 b2, a1;\nmov.b32 b0, t0;\nmov.b32 b3, t0;\nmov.b32 b1, t1;\n"
        "ld.shared.b32 t0, [%64+5632];\nld.shared.b32 t1, [%64+5760];\nadd.s64 d, %65, 168;\nwgmma.fence.sync.aligned;\nwgmma.mma_async.sync.aligned.m64n48k16.f32.bf16.bf16 {%0, %1, %2, %3, %4, %5, %6, %7, %8, %9, %10, %11, %12, %13, %14, %15, %16, %17, %18, %19, %20, %21, %22, %23}, {b0, b1, b2, b3}, d, 1, 1, 1, 0;\nwgmma.commit_group.sync.aligned;\nwgmma.wait_group.sync.aligned 1;\nmov.b32 a2, b1;\nmov.b32 a0, t0;\nmov.b32 a3, t0;\nmov.b32 a1, t1;\n"
        "ld.shared.b32 t0, [%64+5888];\nld.shared.b32 t1, [%64+6016];\nadd.s64 d, %65, 176;\nwgmma.fence.sync.aligned;\nwgmma.mma_async.sync.aligned.m64n40k16.f32.bf16.bf16 {%0, %1, %2, %3, %4, %5, %6, %7, %8, %9, %10, %11, %12, %13, %14, %15, %16, %17, %18, %19}, {a0, a1, a2, a3}, d, 1, 1, 1, 0;\nwgmma.commit_group.sync.aligned;\nwgmma.wait_group.sync.aligned 1;\nmov.b32 b2, a1;\nmov.b32 b0, t0;\nmov.b32 b3, t0;\nmov.b32 b1, t1;\n"
        "ld.shared.b32 t0, [%64+6144];\nld.shared.b32 t1, [%64+6272];\nadd.s64 d, %65, 184;\nwgmma.fence.sync.aligned;\nwgmma.mma_async.sync.aligned.m64n40k16.f32.bf16.bf16 {%0, %1, %2, %3, %4, %5, %6, %7, %8, %9, %10, %11, %12, %13, %14, %15, %16, %17, %18, %19}, {b0, b1, b2, b3}, d, 1, 1, 1, 0;\nwgmma.commit_group.sync.aligned;\nwgmma.wait_group.sync.aligned 1;\nmov.b32 a2, b1;\nmov.b32 a0, t0;\nmov.b32 a3, t0;\nmov.b32 a1, t1;\n"
        "ld.shared.b32 t0, [%64+6400];\nld.shared.b32 t1, [%64+6528];\nadd.s64 d, %65, 192;\nwgmma.fence.sync.aligned;\nwgmma.mma_async.sync.aligned.m64n32k16.f32.bf16.bf16 {%0, %1, %2, %3, %4, %5, %6, %7, %8, %9, %10, %11, %12, %13, %14, %15}, {a0, a1, a2, a3}, d, 1, 1, 1, 0;\nwgmma.commit_group.sync.aligned;\nwgmma.wait_group.sync.aligned 1;\nmov.b32 b2, a1;\nmov.b32 b0, t0;\nmov.b32 b3, t0;\nmov.b32 b1, t1;\n"
        "ld.shared.b32 t0, [%64+6656];\nld.shared.b32 t1, [%64+6784];\nadd.s64 d, %65, 200;\nwgmma.fence.sync.aligned;\nwgmma.mma_async.sync.aligned.m64n32k16.f32.bf16.bf16 {%0, %1, %2, %3, %4, %5, %6, %7, %8, %9, %10, %11, %12, %13, %14, %15}, {b0, b1, b2, b3}, d, 1, 1, 1, 0;\nwgmma.commit_group.sync.aligned;\nwgmma.wait_group.sync.aligned 1;\nmov.b32 a2, b1;\nmov.b32 a0, t0;\nmov.b32 a3, t0;\nmov.b32 a1, t1;\n"
        "ld.shared.b32 t0, [%64+6912];\nld.shared.b32 t1, [%64+7040];\nadd.s64 d, %65, 208;\nwgmma.fence.sync.aligned;\nwgmma.mma_async.sync.aligned.m64n24k16.f32.bf16.bf16 {%0, %1, %2, %3, %4, %5, %6, %7, %8, %9, %10, %11}, {a0, a1, a2, a3}, d, 1, 1, 1, 0;\nwgmma.commit_group.sync.aligned;\nwgmma.wait_group.sync.aligned 1;\nmov.b32 b2, a1;\nmov.b32 b0, t0;\nmov.b32 b3, t0;\nmov.b32 b1, t1;\n"
        "ld.shared.b32 t0, [%64+7168];\nld.shared.b32 t1, [%64+7296];\nadd.s64 d, %65, 216;\nwgmma.fence.sync.aligned;\nwgmma.mma_async.sync.aligned.m64n24k16.f32.bf16.bf16 {%0, %1, %2, %3, %4, %5, %6, %7, %8, %9, %10, %11}, {b0, b1, b2, b3}, d, 1, 1, 1, 0;\nwgmma.commit_group.sync.aligned;\nwgmma.wait_group.sync.aligned 1;\nmov.b32 a2, b1;\nmov.b32 a0, t0;\nmov.b32 a3, t0;\nmov.b32 a1, t1;\n"
        "ld.shared.b32 t0, [%64+7424];\nld.shared.b32 t1, [%64+7552];\nadd.s64 d, %65, 224;\nwgmma.fence.sync.aligned;\nwgmma.mma_async.sync.aligned.m64n16k16.f32.bf16.bf16 {%0, %1, %2, %3, %4, %5, %6, %7}, {a0, a1, a2, a3}, d, 1, 1, 1, 0;\nwgmma.commit_group.sync.aligned;\nwgmma.wait_group.sync.aligned 1;\nmov.b32 b2, a1;\nmov.b32 b0, t0;\nmov.b32 b3, t0;\nmov.b32 b1, t1;\n"
        "ld.shared.b32 t0, [%64+7680];\nld.shared.b32 t1, [%64+7808];\nadd.s64 d, %65, 232;\nwgmma.fence.sync.aligned;\nwgmma.mma_async.sync.aligned.m64n16k16.f32.bf16.bf16 {%0, %1, %2, %3, %4, %5, %6, %7}, {b0, b1, b2, b3}, d, 1, 1, 1, 0;\nwgmma.commit_group.sync.aligned;\nwgmma.wait_group.sync.aligned 1;\nmov.b32 a2, b1;\nmov.b32 a0, t0;\nmov.b32 a3, t0;\nmov.b32 a1, t1;\n"
        "ld.shared.b32 t0, [%64+7936];\nld.shared.b32 t1, [%64+8064];\nadd.s64 d, %65, 240;\nwgmma.fence.sync.aligned;\nwgmma.mma_async.sync.aligned.m64n8k16.f32.bf16.bf16 {%0, %1, %2, %3}, {a0, a1, a2, a3}, d, 1, 1, 1, 0;\nwgmma.commit_group.sync.aligned;\nwgmma.wait_group.sync.aligned 1;\nmov.b32 b2, a1;\nmov.b32 b0, t0;\nmov.b32 b3, t0;\nmov.b32 b1, t1;\n"
        "add.s64 d, %65, 248;\nwgmma.fence.sync.aligned;\nwgmma.mma_async.sync.aligned.m64n8k16.f32.bf16.bf16 {%0, %1, %2, %3}, {b0, b1, b2, b3}, d, 1, 1, 1, 0;\nwgmma.commit_group.sync.aligned;\nwgmma.wait_group.sync.aligned 0;\n"
        "}" : "+f"(d[0]), "+f"(d[1]), "+f"(d[2]), "+f"(d[3]), "+f"(d[4]), "+f"(d[5]), "+f"(d[6]), "+f"(d[7]), "+f"(d[8]), "+f"(d[9]), "+f"(d[10]), "+f"(d[11]), "+f"(d[12]), "+f"(d[13]), "+f"(d[14]), "+f"(d[15]), "+f"(d[16]), "+f"(d[17]), "+f"(d[18]), "+f"(d[19]), "+f"(d[20]), "+f"(d[21]), "+f"(d[22]), "+f"(d[23]), "+f"(d[24]), "+f"(d[25]), "+f"(d[26]), "+f"(d[27]), "+f"(d[28]), "+f"(d[29]), "+f"(d[30]), "+f"(d[31]), "+f"(d[32]), "+f"(d[33]), "+f"(d[34]), "+f"(d[35]), "+f"(d[36]), "+f"(d[37]), "+f"(d[38]), "+f"(d[39]), "+f"(d[40]), "+f"(d[41]), "+f"(d[42]), "+f"(d[43]), "+f"(d[44]), "+f"(d[45]), "+f"(d[46]), "+f"(d[47]), "+f"(d[48]), "+f"(d[49]), "+f"(d[50]), "+f"(d[51]), "+f"(d[52]), "+f"(d[53]), "+f"(d[54]), "+f"(d[55]), "+f"(d[56]), "+f"(d[57]), "+f"(d[58]), "+f"(d[59]), "+f"(d[60]), "+f"(d[61]), "+f"(d[62]), "+f"(d[63]) : "r"(pa), "l"(db) : "memory");
}
__device__ __forceinline__ void wgmma_rs80(float (&d)[40], uint32_t a0, uint32_t a1, uint32_t a2, uint32_t a3, uint64_t db, int sc) {
    asm volatile("{\n.reg .pred p;\nsetp.ne.b32 p, %45, 0;\n"
        "wgmma.mma_async.sync.aligned.m64n80k16.f32.bf16.bf16 {%0, %1, %2, %3, %4, %5, %6, %7, %8, %9, %10, %11, %12, %13, %14, %15, %16, %17, %18, %19, %20, %21, %22, %23, %24, %25, %26, %27, %28, %29, %30, %31, %32, %33, %34, %35, %36, %37, %38, %39}, {%40, %41, %42, %43}, %44, p, 1, 1, 1;\n}\n"
        : "+f"(d[0]), "+f"(d[1]), "+f"(d[2]), "+f"(d[3]), "+f"(d[4]), "+f"(d[5]), "+f"(d[6]), "+f"(d[7]), "+f"(d[8]), "+f"(d[9]), "+f"(d[10]), "+f"(d[11]), "+f"(d[12]), "+f"(d[13]), "+f"(d[14]), "+f"(d[15]), "+f"(d[16]), "+f"(d[17]), "+f"(d[18]), "+f"(d[19]), "+f"(d[20]), "+f"(d[21]), "+f"(d[22]), "+f"(d[23]), "+f"(d[24]), "+f"(d[25]), "+f"(d[26]), "+f"(d[27]), "+f"(d[28]), "+f"(d[29]), "+f"(d[30]), "+f"(d[31]), "+f"(d[32]), "+f"(d[33]), "+f"(d[34]), "+f"(d[35]), "+f"(d[36]), "+f"(d[37]), "+f"(d[38]), "+f"(d[39]) : "r"(a0), "r"(a1), "r"(a2), "r"(a3), "l"(db), "r"(sc));
}
__device__ __forceinline__ void wgmma_ss80(float (&d)[40], uint64_t da, uint64_t db, int sc) {
    asm volatile("{\n.reg .pred p;\nsetp.ne.b32 p, %42, 0;\n"
        "wgmma.mma_async.sync.aligned.m64n80k16.f32.bf16.bf16 {%0, %1, %2, %3, %4, %5, %6, %7, %8, %9, %10, %11, %12, %13, %14, %15, %16, %17, %18, %19, %20, %21, %22, %23, %24, %25, %26, %27, %28, %29, %30, %31, %32, %33, %34, %35, %36, %37, %38, %39}, %40, %41, p, 1, 1, 0, 1;\n}\n"
        : "+f"(d[0]), "+f"(d[1]), "+f"(d[2]), "+f"(d[3]), "+f"(d[4]), "+f"(d[5]), "+f"(d[6]), "+f"(d[7]), "+f"(d[8]), "+f"(d[9]), "+f"(d[10]), "+f"(d[11]), "+f"(d[12]), "+f"(d[13]), "+f"(d[14]), "+f"(d[15]), "+f"(d[16]), "+f"(d[17]), "+f"(d[18]), "+f"(d[19]), "+f"(d[20]), "+f"(d[21]), "+f"(d[22]), "+f"(d[23]), "+f"(d[24]), "+f"(d[25]), "+f"(d[26]), "+f"(d[27]), "+f"(d[28]), "+f"(d[29]), "+f"(d[30]), "+f"(d[31]), "+f"(d[32]), "+f"(d[33]), "+f"(d[34]), "+f"(d[35]), "+f"(d[36]), "+f"(d[37]), "+f"(d[38]), "+f"(d[39]) : "l"(da), "l"(db), "r"(sc));
}
__device__ __forceinline__ void wgmma_ss80t(float (&d)[40], uint64_t da, uint64_t db, int sc) {
    asm volatile("{\n.reg .pred p;\nsetp.ne.b32 p, %42, 0;\n"
        "wgmma.mma_async.sync.aligned.m64n80k16.f32.bf16.bf16 {%0, %1, %2, %3, %4, %5, %6, %7, %8, %9, %10, %11, %12, %13, %14, %15, %16, %17, %18, %19, %20, %21, %22, %23, %24, %25, %26, %27, %28, %29, %30, %31, %32, %33, %34, %35, %36, %37, %38, %39}, %40, %41, p, 1, 1, 1, 1;\n}\n"
        : "+f"(d[0]), "+f"(d[1]), "+f"(d[2]), "+f"(d[3]), "+f"(d[4]), "+f"(d[5]), "+f"(d[6]), "+f"(d[7]), "+f"(d[8]), "+f"(d[9]), "+f"(d[10]), "+f"(d[11]), "+f"(d[12]), "+f"(d[13]), "+f"(d[14]), "+f"(d[15]), "+f"(d[16]), "+f"(d[17]), "+f"(d[18]), "+f"(d[19]), "+f"(d[20]), "+f"(d[21]), "+f"(d[22]), "+f"(d[23]), "+f"(d[24]), "+f"(d[25]), "+f"(d[26]), "+f"(d[27]), "+f"(d[28]), "+f"(d[29]), "+f"(d[30]), "+f"(d[31]), "+f"(d[32]), "+f"(d[33]), "+f"(d[34]), "+f"(d[35]), "+f"(d[36]), "+f"(d[37]), "+f"(d[38]), "+f"(d[39]) : "l"(da), "l"(db), "r"(sc));
}
__device__ __forceinline__ void wgmma_ss8_ta(float (&d)[4], uint64_t da, uint64_t db, int sc) {
    asm volatile("{\n.reg .pred p;\nsetp.ne.b32 p, %6, 0;\n"
        "wgmma.mma_async.sync.aligned.m64n8k16.f32.bf16.bf16 {%0, %1, %2, %3}, %4, %5, p, 1, 1, 1, 0;\n}\n"
        : "+f"(d[0]), "+f"(d[1]), "+f"(d[2]), "+f"(d[3]) : "l"(da), "l"(db), "r"(sc));
}
__device__ __forceinline__ void wgmma_rs8(float (&d)[4], uint32_t a0, uint32_t a1, uint32_t a2, uint32_t a3, uint64_t db, int sc) {
    asm volatile("{\n.reg .pred p;\nsetp.ne.b32 p, %9, 0;\n"
        "wgmma.mma_async.sync.aligned.m64n8k16.f32.bf16.bf16 {%0, %1, %2, %3}, {%4, %5, %6, %7}, %8, p, 1, 1, 0;\n}\n"
        : "+f"(d[0]), "+f"(d[1]), "+f"(d[2]), "+f"(d[3]) : "r"(a0), "r"(a1), "r"(a2), "r"(a3), "l"(db), "r"(sc));
}
__device__ __forceinline__ void wgmma_rs128(float (&d)[64], uint32_t a0, uint32_t a1, uint32_t a2, uint32_t a3, uint64_t db, int sc) {
    asm volatile("{\n.reg .pred p;\nsetp.ne.b32 p, %69, 0;\n"
        "wgmma.mma_async.sync.aligned.m64n128k16.f32.bf16.bf16 {%0, %1, %2, %3, %4, %5, %6, %7, %8, %9, %10, %11, %12, %13, %14, %15, %16, %17, %18, %19, %20, %21, %22, %23, %24, %25, %26, %27, %28, %29, %30, %31, %32, %33, %34, %35, %36, %37, %38, %39, %40, %41, %42, %43, %44, %45, %46, %47, %48, %49, %50, %51, %52, %53, %54, %55, %56, %57, %58, %59, %60, %61, %62, %63}, {%64, %65, %66, %67}, %68, p, 1, 1, 1;\n}\n"
        : "+f"(d[0]), "+f"(d[1]), "+f"(d[2]), "+f"(d[3]), "+f"(d[4]), "+f"(d[5]), "+f"(d[6]), "+f"(d[7]), "+f"(d[8]), "+f"(d[9]), "+f"(d[10]), "+f"(d[11]), "+f"(d[12]), "+f"(d[13]), "+f"(d[14]), "+f"(d[15]), "+f"(d[16]), "+f"(d[17]), "+f"(d[18]), "+f"(d[19]), "+f"(d[20]), "+f"(d[21]), "+f"(d[22]), "+f"(d[23]), "+f"(d[24]), "+f"(d[25]), "+f"(d[26]), "+f"(d[27]), "+f"(d[28]), "+f"(d[29]), "+f"(d[30]), "+f"(d[31]), "+f"(d[32]), "+f"(d[33]), "+f"(d[34]), "+f"(d[35]), "+f"(d[36]), "+f"(d[37]), "+f"(d[38]), "+f"(d[39]), "+f"(d[40]), "+f"(d[41]), "+f"(d[42]), "+f"(d[43]), "+f"(d[44]), "+f"(d[45]), "+f"(d[46]), "+f"(d[47]), "+f"(d[48]), "+f"(d[49]), "+f"(d[50]), "+f"(d[51]), "+f"(d[52]), "+f"(d[53]), "+f"(d[54]), "+f"(d[55]), "+f"(d[56]), "+f"(d[57]), "+f"(d[58]), "+f"(d[59]), "+f"(d[60]), "+f"(d[61]), "+f"(d[62]), "+f"(d[63]) : "r"(a0), "r"(a1), "r"(a2), "r"(a3), "l"(db), "r"(sc));
}
__device__ __forceinline__ void wgmma_rs88(float (&d)[44], uint32_t a0, uint32_t a1, uint32_t a2, uint32_t a3, uint64_t db, int sc) {
    asm volatile("{\n.reg .pred p;\nsetp.ne.b32 p, %49, 0;\n"
        "wgmma.mma_async.sync.aligned.m64n88k16.f32.bf16.bf16 {%0, %1, %2, %3, %4, %5, %6, %7, %8, %9, %10, %11, %12, %13, %14, %15, %16, %17, %18, %19, %20, %21, %22, %23, %24, %25, %26, %27, %28, %29, %30, %31, %32, %33, %34, %35, %36, %37, %38, %39, %40, %41, %42, %43}, {%44, %45, %46, %47}, %48, p, 1, 1, 1;\n}\n"
        : "+f"(d[0]), "+f"(d[1]), "+f"(d[2]), "+f"(d[3]), "+f"(d[4]), "+f"(d[5]), "+f"(d[6]), "+f"(d[7]), "+f"(d[8]), "+f"(d[9]), "+f"(d[10]), "+f"(d[11]), "+f"(d[12]), "+f"(d[13]), "+f"(d[14]), "+f"(d[15]), "+f"(d[16]), "+f"(d[17]), "+f"(d[18]), "+f"(d[19]), "+f"(d[20]), "+f"(d[21]), "+f"(d[22]), "+f"(d[23]), "+f"(d[24]), "+f"(d[25]), "+f"(d[26]), "+f"(d[27]), "+f"(d[28]), "+f"(d[29]), "+f"(d[30]), "+f"(d[31]), "+f"(d[32]), "+f"(d[33]), "+f"(d[34]), "+f"(d[35]), "+f"(d[36]), "+f"(d[37]), "+f"(d[38]), "+f"(d[39]), "+f"(d[40]), "+f"(d[41]), "+f"(d[42]), "+f"(d[43]) : "r"(a0), "r"(a1), "r"(a2), "r"(a3), "l"(db), "r"(sc));
}
__device__ __forceinline__ void wgmma_rs128k(float (&d)[64], uint32_t a0, uint32_t a1, uint32_t a2, uint32_t a3, uint64_t db, int sc) {
    asm volatile("{\n.reg .pred p;\nsetp.ne.b32 p, %69, 0;\n"
        "wgmma.mma_async.sync.aligned.m64n128k16.f32.bf16.bf16 {%0, %1, %2, %3, %4, %5, %6, %7, %8, %9, %10, %11, %12, %13, %14, %15, %16, %17, %18, %19, %20, %21, %22, %23, %24, %25, %26, %27, %28, %29, %30, %31, %32, %33, %34, %35, %36, %37, %38, %39, %40, %41, %42, %43, %44, %45, %46, %47, %48, %49, %50, %51, %52, %53, %54, %55, %56, %57, %58, %59, %60, %61, %62, %63}, {%64, %65, %66, %67}, %68, p, 1, 1, 0;\n}\n"
        : "+f"(d[0]), "+f"(d[1]), "+f"(d[2]), "+f"(d[3]), "+f"(d[4]), "+f"(d[5]), "+f"(d[6]), "+f"(d[7]), "+f"(d[8]), "+f"(d[9]), "+f"(d[10]), "+f"(d[11]), "+f"(d[12]), "+f"(d[13]), "+f"(d[14]), "+f"(d[15]), "+f"(d[16]), "+f"(d[17]), "+f"(d[18]), "+f"(d[19]), "+f"(d[20]), "+f"(d[21]), "+f"(d[22]), "+f"(d[23]), "+f"(d[24]), "+f"(d[25]), "+f"(d[26]), "+f"(d[27]), "+f"(d[28]), "+f"(d[29]), "+f"(d[30]), "+f"(d[31]), "+f"(d[32]), "+f"(d[33]), "+f"(d[34]), "+f"(d[35]), "+f"(d[36]), "+f"(d[37]), "+f"(d[38]), "+f"(d[39]), "+f"(d[40]), "+f"(d[41]), "+f"(d[42]), "+f"(d[43]), "+f"(d[44]), "+f"(d[45]), "+f"(d[46]), "+f"(d[47]), "+f"(d[48]), "+f"(d[49]), "+f"(d[50]), "+f"(d[51]), "+f"(d[52]), "+f"(d[53]), "+f"(d[54]), "+f"(d[55]), "+f"(d[56]), "+f"(d[57]), "+f"(d[58]), "+f"(d[59]), "+f"(d[60]), "+f"(d[61]), "+f"(d[62]), "+f"(d[63]) : "r"(a0), "r"(a1), "r"(a2), "r"(a3), "l"(db), "r"(sc));
}
__device__ __forceinline__ void wgmma_rs88k(float (&d)[44], uint32_t a0, uint32_t a1, uint32_t a2, uint32_t a3, uint64_t db, int sc) {
    asm volatile("{\n.reg .pred p;\nsetp.ne.b32 p, %49, 0;\n"
        "wgmma.mma_async.sync.aligned.m64n88k16.f32.bf16.bf16 {%0, %1, %2, %3, %4, %5, %6, %7, %8, %9, %10, %11, %12, %13, %14, %15, %16, %17, %18, %19, %20, %21, %22, %23, %24, %25, %26, %27, %28, %29, %30, %31, %32, %33, %34, %35, %36, %37, %38, %39, %40, %41, %42, %43}, {%44, %45, %46, %47}, %48, p, 1, 1, 0;\n}\n"
        : "+f"(d[0]), "+f"(d[1]), "+f"(d[2]), "+f"(d[3]), "+f"(d[4]), "+f"(d[5]), "+f"(d[6]), "+f"(d[7]), "+f"(d[8]), "+f"(d[9]), "+f"(d[10]), "+f"(d[11]), "+f"(d[12]), "+f"(d[13]), "+f"(d[14]), "+f"(d[15]), "+f"(d[16]), "+f"(d[17]), "+f"(d[18]), "+f"(d[19]), "+f"(d[20]), "+f"(d[21]), "+f"(d[22]), "+f"(d[23]), "+f"(d[24]), "+f"(d[25]), "+f"(d[26]), "+f"(d[27]), "+f"(d[28]), "+f"(d[29]), "+f"(d[30]), "+f"(d[31]), "+f"(d[32]), "+f"(d[33]), "+f"(d[34]), "+f"(d[35]), "+f"(d[36]), "+f"(d[37]), "+f"(d[38]), "+f"(d[39]), "+f"(d[40]), "+f"(d[41]), "+f"(d[42]), "+f"(d[43]) : "r"(a0), "r"(a1), "r"(a2), "r"(a3), "l"(db), "r"(sc));
}
__device__ __forceinline__ void wgmma_rs80k(float (&d)[40], uint32_t a0, uint32_t a1, uint32_t a2, uint32_t a3, uint64_t db, int sc) {
    asm volatile("{\n.reg .pred p;\nsetp.ne.b32 p, %45, 0;\n"
        "wgmma.mma_async.sync.aligned.m64n80k16.f32.bf16.bf16 {%0, %1, %2, %3, %4, %5, %6, %7, %8, %9, %10, %11, %12, %13, %14, %15, %16, %17, %18, %19, %20, %21, %22, %23, %24, %25, %26, %27, %28, %29, %30, %31, %32, %33, %34, %35, %36, %37, %38, %39}, {%40, %41, %42, %43}, %44, p, 1, 1, 0;\n}\n"
        : "+f"(d[0]), "+f"(d[1]), "+f"(d[2]), "+f"(d[3]), "+f"(d[4]), "+f"(d[5]), "+f"(d[6]), "+f"(d[7]), "+f"(d[8]), "+f"(d[9]), "+f"(d[10]), "+f"(d[11]), "+f"(d[12]), "+f"(d[13]), "+f"(d[14]), "+f"(d[15]), "+f"(d[16]), "+f"(d[17]), "+f"(d[18]), "+f"(d[19]), "+f"(d[20]), "+f"(d[21]), "+f"(d[22]), "+f"(d[23]), "+f"(d[24]), "+f"(d[25]), "+f"(d[26]), "+f"(d[27]), "+f"(d[28]), "+f"(d[29]), "+f"(d[30]), "+f"(d[31]), "+f"(d[32]), "+f"(d[33]), "+f"(d[34]), "+f"(d[35]), "+f"(d[36]), "+f"(d[37]), "+f"(d[38]), "+f"(d[39]) : "r"(a0), "r"(a1), "r"(a2), "r"(a3), "l"(db), "r"(sc));
}
__device__ __forceinline__ void wgmma_rs64(float (&d)[32], uint32_t a0, uint32_t a1, uint32_t a2, uint32_t a3, uint64_t db, int sc) {
    asm volatile("{\n.reg .pred p;\nsetp.ne.b32 p, %37, 0;\n"
        "wgmma.mma_async.sync.aligned.m64n64k16.f32.bf16.bf16 {%0, %1, %2, %3, %4, %5, %6, %7, %8, %9, %10, %11, %12, %13, %14, %15, %16, %17, %18, %19, %20, %21, %22, %23, %24, %25, %26, %27, %28, %29, %30, %31}, {%32, %33, %34, %35}, %36, p, 1, 1, 1;\n}\n"
        : "+f"(d[0]), "+f"(d[1]), "+f"(d[2]), "+f"(d[3]), "+f"(d[4]), "+f"(d[5]), "+f"(d[6]), "+f"(d[7]), "+f"(d[8]), "+f"(d[9]), "+f"(d[10]), "+f"(d[11]), "+f"(d[12]), "+f"(d[13]), "+f"(d[14]), "+f"(d[15]), "+f"(d[16]), "+f"(d[17]), "+f"(d[18]), "+f"(d[19]), "+f"(d[20]), "+f"(d[21]), "+f"(d[22]), "+f"(d[23]), "+f"(d[24]), "+f"(d[25]), "+f"(d[26]), "+f"(d[27]), "+f"(d[28]), "+f"(d[29]), "+f"(d[30]), "+f"(d[31]) : "r"(a0), "r"(a1), "r"(a2), "r"(a3), "l"(db), "r"(sc));
}

__device__ __forceinline__ uint64_t mkdesc(uint32_t lo) { return ((uint64_t)0x40000040u << 32) | lo; }
template <int F> __device__ __forceinline__ uint32_t lop3(uint32_t a, uint32_t b, uint32_t c) { uint32_t r; asm("lop3.b32 %0, %1, %2, %3, %4;" : "=r"(r) : "r"(a), "r"(b), "r"(c), "n"(F)); return r; }
__device__ __forceinline__ void stg128_tag(void* p, uint32_t x, uint32_t y, uint32_t z, uint32_t u, uint32_t ep, int w) {
    stg128(p, lop3<0xB8>(x, w == 0, ep), lop3<0xB8>(y, w == 1, ep), lop3<0xB8>(z, w == 2, ep), lop3<0xB8>(u, w == 3, ep));
}
__device__ __forceinline__ uint32_t tag(uint32_t w, uint32_t ep) { asm("lop3.b32 %0, %0, 1, %1, 0xB8;" : "+r"(w) : "r"(ep)); return w; }
template <int N> __device__ __forceinline__ void pack_part(uint32_t (&p)[32], const float (&v)[N], uint32_t ep) {
#pragma unroll
    for (int i = 0; i < N / 2; i++) p[i] = (i & 3) ? pack2(v[2 * i], v[2 * i + 1]) : tag(pack2(v[2 * i], v[2 * i + 1]), ep);
#pragma unroll
    for (int i = 0; i < N / 2; i++) asm volatile("" : "+r"(p[i]));
}
__device__ __forceinline__ void st_part(uint4* p, const uint32_t* v) {
    asm volatile("{\n.reg .b64 l, h;\n.reg .b128 q;\nmov.b64 l, {%1, %2};\nmov.b64 h, {%3, %4};\nmov.b128 q, {l, h};\nst.relaxed.gpu.global.b128 [%0], q;\n}"
                 ::"l"(p), "r"(v[0]), "r"(v[1]), "r"(v[2]), "r"(v[3]) : "memory");
}
__device__ __forceinline__ void st_peer(uint32_t a, uint32_t x, uint32_t y, uint32_t z, uint32_t w, uint32_t bar) {
    asm volatile("st.async.shared::cluster.mbarrier::complete_tx::bytes.v4.b32 [%0], {%1, %2, %3, %4}, [%5];" ::"r"(a), "r"(x), "r"(y), "r"(z), "r"(w), "r"(bar) : "memory");
}
__device__ __forceinline__ int g4_block(int c, int j) { return c ? j ^ (8 - 2 * c) : 8 + (j & 1); }
__device__ __forceinline__ uint32_t recv_off(int w) { return w ? OFF_XR : OFF_REM; }
__device__ __forceinline__ uint4 ld_part(const void* p) {
    uint4 v;
    asm volatile("{\n.reg .b64 l, h;\n.reg .b128 q;\nld.relaxed.gpu.global.b128 q, [%4];\nmov.b128 {l, h}, q;\nmov.b64 {%0, %1}, l;\nmov.b64 {%2, %3}, h;\n}"
                 : "=r"(v.x), "=r"(v.y), "=r"(v.z), "=r"(v.w) : "l"(p) : "memory");
    return v;
}
__device__ __forceinline__ void ld_part4(uint4 (&u)[4], const uint4* p, int st) {
#pragma unroll
    for (int i = 0; i < 4; i++) u[i] = ld_part(p + i * st);
}
__device__ __forceinline__ uint32_t stale4(const uint4 (&u)[4], uint32_t ep) { return lop3<0x7E>(u[0].x, ep, u[1].x) | lop3<0x7E>(u[2].x, ep, u[3].x); }
__device__ __forceinline__ uint4 add2(uint4 a, uint4 b) { return make_uint4(add2(a.x, b.x), add2(a.y, b.y), add2(a.z, b.z), add2(a.w, b.w)); }
__device__ __forceinline__ uint4 fin16(uint4 v, uint4 b, uint4 c) { return make_uint4(fma2(c.x, v.x, b.x), fma2(c.y, v.y, b.y), fma2(c.z, v.z, b.z), fma2(c.w, v.w, b.w)); }
__device__ __forceinline__ uint4 scale16(float2 c, float2 d, float r0, float r1) {
    return make_uint4(pack2(c.x * r0, c.y * r0), pack2(c.x * r1, c.y * r1), pack2(d.x * r0, d.y * r0), pack2(d.x * r1, d.y * r1));
}
__device__ __forceinline__ uint32_t split2(float x) { const float h = rbf(x); return pack2(h, x - h); }
__device__ __forceinline__ uint32_t b80_desc(uint32_t dsb, uint32_t wn, uint32_t rn, uint32_t h) {
    const uint32_t wb = dsb + OFF_W + (wn & 7) * 16384 + h * 8192, rm = dsb + OFF_REM + rn * 4096 + h * 2048;
    return (wb >> 4) | ((rm - wb) << 12);
}
constexpr int64_t B80_STEP = 128 - (126 << 16), B80_HALF = 512 - (384 << 16);
constexpr uint32_t ring_mask(int L) {
    uint32_t m = 0;
    for (int i = L; i < 20; i++) m |= (uint32_t)(i >= 20 - L || !((i - L) & 1)) << i;
    return m;
}
constexpr int pair_pos(int w, int i) { return w ? (i < 5 - LEAD2 ? LEAD2 + 2 * i : 5 + i) : (i < LEAD2 ? i : 2 * i - LEAD2 + 1); }
constexpr uint32_t pair_mask() { uint32_t m = 0; for (int i = 0; i < 5; i++) m |= 3u << (2 * pair_pos(1, i)); return m; }
constexpr uint32_t pair_slots(int w) { uint32_t m = 0; for (int i = 0; i < 5; i++) m |= (uint32_t)((2 + pair_pos(w, i)) & 3) << (2 * i); return m; }
constexpr uint32_t M0 = ring_mask(LEAD1), M1 = pair_mask(), M2 = ring_mask(XLEAD), P0S = pair_slots(0), P1S = pair_slots(1);
__device__ __forceinline__ uint32_t ring_pos(int w, int n, int L) { return w ? (n < 10 - L ? L + 2 * n : 10 + n) : (n < L ? n : 2 * n - L + 1); }
__device__ __forceinline__ int g1_block(int n, int j) { return n < 5 ? 2 * n + (j & 1) : 2 * n - 9 - (j & 1); }

__device__ __forceinline__ void load_tile(const Maps& mp, uint32_t dst, int e, int tile, int kb, int j, uint32_t bar) {
    mbar_expect(bar, 8192);
    tma_ld2(dst, &mp.x[e], 64 * (e == 0 ? tile : e == 1 ? kb : 0), 64 * (e == 0 ? g1_block(kb, j) : e == 1 ? tile : 10 * tile + kb), bar);
}

template <int OCT>
__device__ __forceinline__ void gemv_tile(float (&d)[4], uint32_t a, uint32_t b, int kb0) {
    uint32_t alo = ((a & 0x3FFFF) >> 4) | 0x10000u, blo_ = ((b & 0x3FFFF) >> 4) | (OCT << 16);
#pragma unroll 1
    for (int s = 0; s < 20; s += 4) {
        const int kb = kb0 + (s >> 2);
        const uint32_t bk = blo_ + (OCT == 7 ? (kb & 1) * 288 + (kb >> 1) * 56 : kb * 64);
        wg_fence();
#pragma unroll
        for (int q = 0; q < 4; q++) wgmma_ss8_ta(d, mkdesc(alo + (s + q) * 128), ((uint64_t)8 << 32) | (bk + q * 2 * OCT), s + q);
        wg_commit();
    }
    wg_wait<0>();
    reg_fence(d);
}

__device__ __forceinline__ void flush_tile(uint32_t st, bf16* dst, int u) {
#pragma unroll
    for (int i = 0; i < 2; i++) {
        const int idx = u + 320 * i, row = idx >> 3, c = idx & 7;
        stg128(dst + (size_t)row * S_ + 8 * c, lds128(st + row * 128 + ((c ^ ((row >> 1) & 7)) << 4)));
    }
}

__device__ __forceinline__ int tid_now() { int t; asm volatile("mov.u32 %0, %%tid.x;" : "=r"(t)); return t; }
__device__ __forceinline__ float zscale(float c) { return c == 0.f ? 0x1p-30f : c; }
__device__ __forceinline__ bool bar_any(int id, bool p) {
    uint32_t r;
    asm volatile("{\n.reg .pred a, b;\nsetp.ne.u32 a, %2, 0;\nbarrier.red.or.pred.aligned b, %1, 128, a;\nselp.u32 %0, 1, 0, b;\n}" : "=r"(r) : "r"(id), "r"((uint32_t)p) : "memory");
    return r != 0;
}

__global__ void __cluster_dims__(2, 1, 1) __launch_bounds__(NTHR, 1) fused_kernel(const __grid_constant__ Ptrs pp, bf16* __restrict__ out, const __grid_constant__ Maps mp) {
    extern __shared__ __align__(1024) uint8_t smem_raw[];
    const uint32_t sb = s2u(smem_raw), bars = sb + M_BAR, dsb = sb & 0x3FFFF;
    const int id = blockIdx.x, warp = __shfl_sync(0xffffffffu, (int)threadIdx.x >> 5, 0), wg = warp >> 2;
    const uint32_t c0 = clock_lo();
#define TIDS const int tid = tid_now(), lane = tid & 31, wt = tid & 127, g = lane >> 2, t = lane & 3; (void)wt; (void)g; (void)t;
    TS(threadIdx.x == 0, 0) TG(threadIdx.x == 0, 62)

    if (id >= 128) {
        TIDS
        if (sb & 1023) __trap();
        const int hs = id - 128;
        constexpr int H_B = 204800;
        static_assert(H_B + TAB_BYTES + 8 * VEC_BYTES <= OFF_M, "helper map");
        if (warp < 10 && elect()) { mbar_init(bars + warp * 8, 1); mbar_init(bars + 80 + warp * 8, 1); asm volatile("fence.mbarrier_init.release.cluster;" ::: "memory"); }
        __syncthreads();
        const uint32_t e0 = ld_cold(&g_epoch);
        wait_clock(c0, HELP_T);
        uint4 wr[10];
#pragma unroll
        for (int u = 0; u < 10; u++) wr[u] = ldg128(((hs >> 1) ? pp.w2 : pp.w1) + (size_t)(320 * (hs & 1) + (tid >> 4) + 32 * u) * D_ + 512 + 8 * (tid & 15));
        {
            const int r = tid >> 4, c = tid & 15;
            uint4* dst[2];
#pragma unroll
            for (int e = 0; e < 2; e++) {
                const int p = !(hs >> 1) ? r : e && (hs & 1) ? (r & ~14) | ((r & 6) << 1) | ((r & 8) >> 2) : (r & ~30) | ((r & 6) << 2) | ((r & 24) >> 2);
                dst[e] = &g_wr[(((hs >> 1) * 8 + (c >> 1)) * 10 + 5 * (hs & 1)) * 128 + (p & 15) * 8 + ((2 * (p >> 4) + (c & 1)) ^ (p & 7))];
            }
#pragma unroll
            for (int u = 0; u < 10; u++) stg128(reinterpret_cast<uint4*>(reinterpret_cast<uintptr_t>(dst[u >= 6]) ^ (64 * (u & 1))) + (u >> 1) * 128, wr[u]);
        }
        __syncthreads();
        if (warp == 0) signal_cnt(&g_cnt.wr[0], lane, 1);
        __syncthreads();
        if (warp < 5 && elect()) {
            const int un = 5 * hs + warp;
            mbar_expect(bars + warp * 8, 40960);
            tma_ld2(sb + warp * 40960, &mp.w1h, 64 * (un >> 1), 320 * (un & 1), bars + warp * 8);
            tma_ld2(sb + warp * 40960 + 20480, &mp.w1h, 64 * (un >> 1), 320 * (un & 1) + 160, bars + warp * 8);
        }
        if (tid < 320) {
            const uint4* gm = reinterpret_cast<const uint4*>(g_mod + 3 * D_) + tid;
            const unsigned epoch = e0 + 1;
            uint4 r[6];
            unsigned it = 0;
            for (;;) {
                uint32_t bad = 0;
#pragma unroll
                for (int i = 0; i < 6; i++) { r[i] = ld_part(gm + (i >> 1) * (D_ / 2) + (i & 1) * 3 * D_); bad |= (r[i].y ^ epoch) | (r[i].w ^ epoch); }
                if (__all_sync(~0u, !bad)) break;
                if (++it > SPIN_LIMIT) SPIN_FAIL(54)
            }
            uint32_t mv[3];
#pragma unroll
            for (int i = 0; i < 3; i++) mv[i] = pack2(__uint_as_float(r[2 * i].x) + __uint_as_float(r[2 * i + 1].x), __uint_as_float(r[2 * i].z) + __uint_as_float(r[2 * i + 1].z));
            const uint32_t sw2 = mv[0], cw = add2(mv[1], 0x3f803f80u), gw = mv[2];
            const float c0 = blo(cw), c1 = bhi(cw), s0 = blo(sw2), s1 = bhi(sw2);
            const float i0 = __frcp_rn(zscale(c0)), i1 = __frcp_rn(zscale(c1));
            const uint32_t ci = pack2(i0, i1), cq = pack2(i0 * i0, i1 * i1);
            const uint32_t a = sb + H_B + ((tid >> 5) & 1) * 4608 + (tid >> 6) * 896 + ((tid >> 2) & 7) * 112 + (tid & 3) * 4;
            sts32(a, ci); sts32(a + 16, pack2(i0 - blo(ci), i1 - bhi(ci)));
            sts32(a + 32, cq); sts32(a + 48, pack2(fmaf(i0, i0, -blo(cq)), fmaf(i1, i1, -bhi(cq))));
            sts32(a + 64, cw); sts32(a + 80, sw2); sts32(a + 96, 0x3f803f80u);
            if ((tid & ~35) == 284) sts32(a + 112, 0);
            const uint32_t v = sb + H_B + TAB_BYTES + (tid < 256 ? (tid >> 5) * VEC_BYTES + (tid & 31) * 8 : ((tid - 256) >> 3) * VEC_BYTES + 256 + (tid & 7) * 8);
            sts64f(v, blo(gw), bhi(gw)); sts64f(v + 320, c0, c1); sts64f(v + 640, s0, s1); sts64f(v + 960, i0, i1);
            float k[5] = {c0 + c1, s0 + s1, fmaf(c0, c0, c1 * c1), fmaf(c0, s0, c1 * s1), fmaf(s0, s0, s1 * s1)};
#pragma unroll 1
            for (int o = 16; o; o >>= 1) {
#pragma unroll
                for (int e = 0; e < 5; e++) k[e] += __shfl_xor_sync(~0u, k[e], o);
            }
            const uint32_t ks = sb + H_B + TAB_BYTES + (lane & 7) * VEC_BYTES + 1280 + (warp >> 1) * 32;
            if ((warp & 1) && lane < 8) { sts128f(ks, k[0], k[1], k[2], k[3]); sts128f(ks + 16, k[4], 0.f, 0.f, 0.f); }
            bar_sync(3, 320);
            if (!(warp & 1) && lane < 8) {
                const float4 o = lds128f(ks);
                sts128f(ks, k[0] + o.x, k[1] + o.y, k[2] + o.z, k[3] + o.w); sts32(ks + 16, __float_as_uint(k[4] + __uint_as_float(lds32(ks + 16))));
            }
            fence_async_smem();
        }
        __syncthreads();
        if (hs == 0 && warp == 15 && elect()) {
            asm volatile("cp.async.bulk.global.shared::cta.bulk_group [%0], [%1], %2;\ncp.async.bulk.commit_group;\ncp.async.bulk.wait_group 0;"
                         ::"l"(g_tab), "r"(sb + H_B), "n"(TAB_BYTES + 8 * VEC_BYTES) : "memory");
            asm volatile("red.release.gpu.global.add.u32 [%0], 1;" ::"l"(&g_cnt.tab[0]) : "memory");
        }
        __syncwarp();
#pragma unroll 1
        for (int i = wg; i < 20; i += 4) {
            const int r = i / 5, b = i - 5 * r, un = 5 * hs + b, u3 = 20 * r + un;
            auto refill = [&](int e, int u, uint32_t fb) {
                mbar_expect(fb, 40960);
                tma_ld2(sb + e * 40960, &mp.w3h, 64 * (u >> 1), 320 * (u & 1), fb);
                tma_ld2(sb + e * 40960 + 20480, &mp.w3h, 64 * (u >> 1), 320 * (u & 1) + 160, fb);
            };
            if (i > 4 && i < 9) {
                bar_sync(1, 512);
                if (warp == 0) {
                    signal_cnt(&g_cnt.uv[0], lane, 1);
                    if (elect()) {
#pragma unroll 1
                        for (int e = 0; e < 5; e++) refill(e, 5 * hs + e, bars + (5 + e) * 8);
                        l2_prefetch(pp.w2 + (size_t)160 * hs * D_, 160 * D_ * 2);
                    }
                    __syncwarp();
                }
            }
            mbar_wait(bars + i * 8, 0);
            float d[4];
            gemv_tile<7>(d, sb + b * 40960, sb + H_B, 5 * (un & 1));
            const int col = 16 * (warp & 3) + g;
            float* dst = r ? g_cs3 + (un & 1) * 1920 + 64 * ((u3 >> 1) - 10) + col : g_uv + (un & 1) * 3 * D_ + 2 * D_ + 64 * (un >> 1) + col;
            if (t == 3) { dst[0] = d[0]; dst[8] = d[2]; }
            if (r == 0 && t == 2) { dst[-2 * D_] = d[0]; dst[8 - 2 * D_] = d[2]; dst[-D_] = d[1]; dst[8 - D_] = d[3]; }
            if (r == 1 || r == 2) {
                bar_sync(4 + wg, 128);
                if (wt == 0) refill(b, u3, bars + (i + 5) * 8);
            }
        }
        __syncthreads();
        if (warp == 0) signal_cnt(&g_cnt.cs[0], lane, 1);
        if (tid == 511) l2_prefetch(pp.w4 + (size_t)432 * hs * D_, 432 * D_ * 2);
        for (uint32_t it = 0; ld_cold(&g_cnt.cs[0]) < 4;) { if (++it > SPIN_LIMIT) SPIN_FAIL(47) }
        asm volatile("fence.acquire.gpu;" ::: "memory");
        if (tid < 432) {
            const int jj = 2 * hs + (tid >= 216), c = tid % 216;
            const float* src = g_cs3 + (c < 192 ? 192 * jj + c : 1344 + 24 * jj + c);
            const uint32_t s = split2(ldcg32f(src) + ldcg32f(src + 1920));
            stg128(&g_cs3b[432 * hs + tid], s, s & 0xffffu, 0, 0);
        }
        __syncthreads();
        if (warp == 0) signal_cnt(&g_cnt.cs2[0], lane, 1);
        if (tid == 0 && hs == 3) {
            uint32_t it = 0;
            while (ld_cold(&g_epoch) == e0) { __nanosleep(256); if (++it > (1u << 20)) SPIN_FAIL(48) }
        }
        return;
    }

    if (elect()) {
        if (warp == 15) {
            mbar_init(bars + B_IN * 8, 1); mbar_init(bars + B_IN * 8 + 8, 1);
            asm volatile("fence.mbarrier_init.release.cluster;" ::: "memory");
            mbar_expect(bars + B_IN * 8, 131 * 160);
            tma_ld2(sb + OFF_KIN, &mp.k, 80 * (id & 7), 64 * (id >> 3) - 3, bars + B_IN * 8);
            tma_ld2(sb + OFF_VIN, &mp.v, 80 * (id & 7), 64 * (id >> 3), bars + B_IN * 8);
        } else if (warp < 13) {
            const uint32_t n = (0x4C11111111881ull >> (4 * warp)) & 15;
#pragma unroll
            for (int i = 0; i < 4; i++) mbar_init(bars + warp * 64 + i * 8, n);
            if (warp == 11) { mbar_init(bars + B_XFREE * 8, 16); mbar_init(bars + B_OWN * 8, 8); }
            else {
#pragma unroll
                for (int i = 4; i < 8; i++) mbar_init(bars + warp * 64 + i * 8, n);
            }
            asm volatile("fence.mbarrier_init.release.cluster;" ::: "memory");
        }
    }
    asm volatile("" ::"l"(pp.s), "l"(pp.c), "l"(out));
    TR4((threadIdx.x & 31) == 0, warp)
    const int pr = id >> 1;
    const int grp = pr < 4 ? 15 : pr < 36 ? (pr - 4) & 7 : 8 + (pr - 36) % 7;
    const int j = 2 * (pr < 4 ? pr : pr < 36 ? (pr - 4) >> 3 : (pr - 36) / 7) + (id & 1);

    if (wg == 3) {
        TIDS
        const int sw = warp - 12;
        uint32_t ep = ld_cold(&g_epoch);
        TR4(lane == 0, 20 + sw)
        __syncthreads();
        TR4(lane == 0, 30 + sw)
        asm volatile("barrier.cluster.arrive.relaxed.aligned;" ::: "memory");
        if (sw == 0) {
#pragma unroll 1
            for (int n = 0; n < 12; n++) {
                wait_clock(c0, PF_T0 + PF_DT * n);
                if (elect()) l2_prefetch(n < 4 ? (const char*)pp.q + id * 20480 + n * 5120 : (const char*)pp.w_mod + id * 38400 + (n - 4) * 4800, n < 4 ? 5120 : 4800);
            }
        } else if (sw == 1) {
            wait_clock(c0, T_SSM);
            if (elect()) {
                mbar_expect(bars + B_SSM * 8, 20480);
                bulk_ld(sb + OFF_SSM, pp.ssm_k + (size_t)5 * id * S_, 20480, bars + B_SSM * 8);
            }
            mbar_spin(bars + B_KVS * 8, 0);
            signal_cnt(&g_cnt.kv[(id & 7) * 32], lane, 1, true);
            TS(lane == 0, 2)
            mbar_spin(bars + B_RAW * 8, 0);
            if (elect()) {
                mbar_expect(bars + B_QIN * 8, 20480);
                tma_ld3(sb + OFF_QIN, &mp.q, 0, 16 * id, 0, bars + B_QIN * 8);
            }
        } else if (sw == 2) {
            if (elect()) {
#pragma unroll 1
                for (int i = 2; i < (int)(sizeof(Maps) / sizeof(CUtensorMap)); i++) asm volatile("prefetch.tensormap [%0];" ::"l"(&mp.k + i) : "memory");
#pragma unroll 1
                for (int i = B_SUMS; i < B_LAND; i++) mbar_expect(bars + i * 8, i < B_RECV ? 2048 : (i & 3) < 3 ? 8192 : 3072);
            }
            wait_cnt(&g_cnt.kv[(id >> 4) * 32], 16, true);
            TS(lane == 0, 4)
            if (elect()) {
                mbar_expect(bars + B_RAW * 8, 12288);
                mbar_expect(bars + B_RAW2 * 8, 8192);
#pragma unroll
                for (int c = 0; c < 5; c++) bulk_ld(sb + OFF_CH + c * CH_BYTES, g_kvT + (size_t)(5 * id + c) * S_, 4096, bars + (c < 3 ? B_RAW : B_RAW2) * 8);
            }
            mbar_spin(bars + B_BK * 8, 0);
            mbar_spin(bars + B_QIN * 8, 0);
            if (id < 120 && elect()) {
                mbar_expect(bars + B_WM * 8, 40960);
                tma_ld2(sb + OFF_WM, &mp.wmod, 64 * pr, 320 * (id & 1), bars + B_WM * 8);
                tma_ld2(sb + OFF_WM + 20480, &mp.wmod, 64 * pr, 320 * (id & 1) + 160, bars + B_WM * 8);
            }
            TS(lane == 0, 57)
        } else {
            wait_clock(c0, T_KVB);
            if (elect()) {
                mbar_expect(bars + (B_IN + 1) * 8, 131 * 160);
                tma_ld2(sb + OFF_KIN + 10752, &mp.k, 80 * (id & 7), 64 * (id >> 3) + 1021, bars + (B_IN + 1) * 8);
                tma_ld2(sb + OFF_VIN + 10240, &mp.v, 80 * (id & 7), 64 * (id >> 3) + 1024, bars + (B_IN + 1) * 8);
            }
            TS(lane == 0, 53)
            if (lane == 0) sts32(sb + M_EP, ep + 1);
            sts32(sb + M_NUL + lane * 4, 0);
#pragma unroll 1
            for (int i = 0; i < 10; i++) sts128(sb + OFF_Z + i * 512 + lane * 16, 0, 0, 0, 0);
            __syncwarp();
#pragma unroll 1
            for (int i = lane; i < 160; i += 32) {
                const uint32_t c = ldg32(pp.c + 320 * (id & 1) + 2 * i);
                sts32(sb + OFF_Z + (i >> 2) * 128 + (i & 3) * 4, pack2(silu(blo(c)), silu(bhi(c))));
            }
            fence_async_smem();
            for (uint32_t ph = 0, again = 1; again; ph ^= 1) {
                mbar_spin(bars + B_RAW2 * 8, ph);
                uint32_t bad = 0;
#pragma unroll
                for (int i = 0; i < 8; i++) bad |= lop3<0x7E>(lds32(sb + OFF_CH + 3 * CH_BYTES + i * 512 + lane * 16), ~ep, lds32(sb + OFF_CH + 4 * CH_BYTES + i * 512 + lane * 16));
                again = __any_sync(~0u, bad & 1);
                if (again && elect()) {
                    mbar_expect(bars + B_RAW2 * 8, 8192);
#pragma unroll
                    for (int c = 3; c < 5; c++) bulk_ld(sb + OFF_CH + c * CH_BYTES, g_kvT + (size_t)(5 * id + c) * S_, 4096, bars + B_RAW2 * 8);
                }
            }
            if (elect()) mbar_arrive(bars + B_RAW3 * 8);
        }
        {
            mbar_spin(bars + B_QIN * 8, 0);
            asm volatile("add.u32 %0, %0, 1;" : "+r"(ep));
            TS(wt == 0, 54)
            const int tk = 8 * ((lane >> 1) & 1) + 2 * (lane >> 3) + (lane & 1), ck = 4 * (sw & 1) + ((lane >> 1) & 2);
            const uint32_t src = sb + OFF_QIN + (sw >> 1) * 2048 + tk * 128;
            bf16* dst = g_qT + (size_t)id * 16 * D_ + (32 * sw + 8 * (t & 2) + g) * 16 + 8 * (t & 1);
constexpr int QU = Q_UNROLL;
#pragma unroll QU
            for (int i = 0; i < 5; i++) {
                uint32_t r[8];
                ldsm4t(src + i * 4096 + ((ck ^ (tk & 7)) << 4), r[0], r[1], r[2], r[3]);
                ldsm4t(src + i * 4096 + (((ck + 1) ^ (tk & 7)) << 4), r[4], r[5], r[6], r[7]);
                stg128(dst + i * 2048, tag(r[0], ep), r[1], r[2], r[3]);
                stg128(dst + i * 2048 + 128, tag(r[4], ep), r[5], r[6], r[7]);
            }
            float s1 = 0.f, s2 = 0.f;
#pragma unroll 2
            for (int i = 0; i < 10; i++) {
                const uint4 w4 = lds128(sb + OFF_QIN + i * 2048 + wt * 16);
                const uint32_t w[4] = {w4.x, w4.y, w4.z, w4.w};
#pragma unroll
                for (int e = 0; e < 4; e++) { const float a = blo(w[e]), b = bhi(w[e]); s1 += a + b; s2 = fmaf(a, a, fmaf(b, b, s2)); }
            }
#pragma unroll
            for (int o = 1; o < 8; o *= 2) { s1 += __shfl_xor_sync(~0u, s1, o); s2 += __shfl_xor_sync(~0u, s2, o); }
            s1 *= 1.f / D_;
            uint32_t rs = pack2(rsqrtf(fmaxf(s2 * (1.f / D_) - s1 * s1, 0.f) + 1e-5f), 0.f);
            if (lane < 8) rs = tag(rs, ep);
            rs = pack2(blo(rs), -s1 * blo(rs));
            const uint32_t sel = lane ? 0x7632 : 0x5410;
            const uint32_t a0 = __shfl_sync(~0u, rs, 0), a1 = __shfl_sync(~0u, rs, 8), a2 = __shfl_sync(~0u, rs, 16), a3 = __shfl_sync(~0u, rs, 24);
            if (lane < 2) stg64(g_qst + lane * S_ + 16 * id + 4 * sw, tag(__byte_perm(a0, a1, sel), ep), __byte_perm(a2, a3, sel));
            TS(wt == 0, 55)
        }
        bar_sync(6, 128);
        if (sw == 3) {
            signal_cnt(&g_cnt.q[(lane & 3) * 32], lane, 4, true);
            TS(lane == 0, 3)
        }
        asm volatile("setmaxnreg.dec.sync.aligned.u32 " STR(REG_SVC) ";");
        asm volatile("barrier.cluster.wait.aligned;" ::: "memory");
        if (sw == 1) {
            mbar_spin(bars + B_XS * 8, 0);
            signal_cnt(&g_cnt.x[(lane & 3) * 32], lane, 4, true);
            TS(lane == 0, 20)
        }
        if (sw == 1 || sw == 2) {
            mbar_spin(bars + B_XS * 8, 0);
            fence_async_smem();
            const unsigned* flag = &g_cnt.x[(id & 3) * 32];
            int n = sw & 1;
#pragma unroll 1
            for (int s = 0; s < 6; s++) {
                const int e = s >> 1, end = 20 * e + ((s & 1) ? 20 : e == 0 ? LEAD1 : e == 1 ? 2 * LEAD2 : XLEAD);
                const uint32_t M = e == 0 ? M0 : e == 1 ? M1 : M2;
                if (s & 1) mbar_spin(bars + (B_GATE + 2 + e) * 8, !e);
                else {
                    wait_cnt(flag, e ? 32 : 128, true);
                    flag = e ? &g_cnt.g2[grp * 32] : &g_cnt.g1[max(grp - 1 + min(lane, 2), 0) * 32];
                    TS(lane == 0 && sw == 2, 26 + 2 * e)
                }
#pragma unroll 1
                for (; n < end; n += 2) {
                    const int i = n - 20 * e, w = (M >> i) & 1, c = __popc(M & ((1u << i) - 1));
                    mbar_spin(bars + (B_XEMPTY + (n & 7)) * 8, ((n >> 3) & 1) ^ 1);
                    TR2(lane == 0 && n < 40, 20 + n)
                    if (elect()) load_tile(mp, sb + OFF_XR + (n & 7) * 8192, e, grp + 16 * w, w ? c : i - c, j, bars + (B_LAND + (n & 7)) * 8);
                }
            }
            if (sw == 1) { if (elect()) mbar_arrive(bars + (B_GATE + 5) * 8); return; }
            mbar_spin(bars + (B_GATE + 5) * 8, 0);
            mbar_spin(bars + B_VEC3 * 8, 0);
            unsigned old = 0;
            asm volatile("{\n.reg .pred P;\nsetp.eq.s32 P, %2, 0;\n@P atom.relaxed.gpu.global.add.u32 %0, [%1], %3;\n}" : "+r"(old) : "l"(&g_cnt.done[0]), "r"(lane), "r"(1) : "memory");
            if (__any_sync(~0u, old == 127)) {
#pragma unroll 1
                for (int i = lane; i < (int)(sizeof(Counters) / 128); i += 32) reinterpret_cast<unsigned*>(&g_cnt)[i * 32] = 0;
                signal_cnt(&g_epoch, lane, 1, true);
            }
        } else if (sw == 0) {
            wait_cnt(&g_cnt.wr[0], 4);
            mbar_spin(bars + B_QRDY * 8, 0);
            const uint32_t wf = bars + B_WFULL * 8, we = bars + B_WEMPTY * 8;
#pragma unroll 1
            for (int n = 0; n < 5; n++) {
                if (n == 3) { mbar_spin(bars + B_XS * 8, 0); fence_async_smem(); }
                TR2(lane == 0, 70 + n)
                if (elect()) {
                    const uint32_t fb = wf + n * 8, dst = sb + OFF_W + n * 16384;
                    mbar_expect(fb, 20480);
#pragma unroll 1
                    for (int h = 0; h < 2; h++) {
                        const int kb = g1_block(2 * n + h, j);
                        tma_ld2(dst + h * 8192, &mp.w1, 64 * j, 64 * kb, fb);
                        bulk_ld(sb + OFF_REM + n * 4096 + h * 2048, &g_wr[(j * 10 + kb) * 128], 2048, fb);
                    }
                }
            }
            mbar_spin(bars + B_GATE * 8, 0);
#pragma unroll 1
            for (int i = -3; i < 5; i++) {
                const int n = i < 0 ? 8 + i : 5 + i;
                const uint32_t fb = wf + (n & 7) * 8;
                if (i >= 0) mbar_spin(we + i * 8, 0);
                TR2(lane == 0 && i >= 0, 70 + n)
                if (elect()) {
                    if (i < 0 || i >= 3) { mbar_expect(fb, 20480); tma_ld5(sb + OFF_W + (n & 7) * 16384, n < 9 ? &mp.w2a : &mp.w2b, 64 * j, n < 9 ? 4 * (n - 5) : 0, fb); }
                    if (i >= 0) bulk_ld(sb + OFF_REM + i * 4096, &g_wr[((8 + j) * 10 + 2 * i) * 128], 4096, fb);
                }
            }
            mbar_spin(bars + (B_GATE + 1) * 8, 0);
#pragma unroll 1
            for (int n = 10; n < 30; n++) {
                if (n == W3_N2) mbar_spin(bars + (B_GATE + 2) * 8, 0);
                mbar_spin(we + (n & 7) * 8, ((n >> 3) & 1) ^ 1);
                TR2(lane == 0, 70 + n)
                if (elect()) {
                    const uint32_t dst = sb + OFF_W + (n & 7) * 16384, fb = wf + (n & 7) * 8;
                    mbar_expect(fb, 13824);
                    tma_ld3(dst, &mp.w3a, 0, 32 * (n - 10), 3 * j, fb);
                    tma_ld2(dst + 12288, &mp.w3b, 1536 + 24 * j, 32 * (n - 10), fb);
                }
            }
            mbar_spin(we + 6 * 8, 0);
            mbar_spin(bars + B_VEC3 * 8, 0);
            if (elect()) { mbar_expect(wf + 6 * 8, 3456); bulk_ld(sb + OFF_W + 6 * 16384, &g_cs3b[216 * j], 3456, wf + 6 * 8); }
#pragma unroll 1
            for (int n = 31; n < 50; n++) {
                const int e = n < 38 ? 4 : (n - 38) & 3, m0 = n == 35, m1 = e == 3 ? -1 : m0 | (e == 1), rem = 96 + 3 * (j >> 1);
                const int c1_ = j ^ (n < 38 ? 6 : 4 >> ((n - 38) >> 2) & 6), c0_ = n < 38 ? 8 + (j & 1) : c1_;
                const int f = (0xC840A80C204ull >> (4 * min(n - 31, e + 7))) & 15;
                const int r0 = m0 ? rem : 6 * (j ^ (f >> 3)) + (f & 6), r1 = m1 ? rem : r0 + (n < 38 ? 0 : 2);
                mbar_spin(we + (n & 7) * 8, ((n >> 3) & 1) ^ 1);
                if (elect()) {
                    const uint32_t dst = sb + OFF_W + (n & 7) * 16384, fb = wf + (n & 7) * 8;
                    mbar_expect(fb, m1 < 0 ? 8192 : 16384 - 2048 * (m0 + m1));
                    tma_ld2(dst, &mp.w4[m0], 64 * c0_, r0 * (32 >> m0), fb);
                    if (m1 >= 0) tma_ld2(dst + 8192, &mp.w4[m1], 64 * c1_, r1 * (32 >> m1), fb);
                }
            }
        } else {
            {
                wait_cnt(&g_cnt.tab[0], 1);
                mbar_spin(bars + B_QRDY * 8, 0);
                if (elect()) {
                    mbar_expect(bars + B_TAB * 8, TAB_BYTES / 2 + VEC_BYTES);
                    bulk_ld(sb + OFF_TAB, g_tab + (j & 1) * (TAB_BYTES / 32), TAB_BYTES / 2, bars + B_TAB * 8);
                    bulk_ld(sb + M_GB, g_tab + (TAB_BYTES + j * VEC_BYTES) / 16, VEC_BYTES, bars + B_TAB * 8);
                }
                TS(lane == 0, 5)
            }
            wait_cnt(&g_cnt.uv[0], 4);
#pragma unroll 1
            for (int c = lane; c < 80; c += 32) {
                const float* src = g_uv + (c < 64 ? 64 * j + c : 448 + 16 * j + c);
                const uint32_t u = split2(ldcg32f(src) + ldcg32f(src + 3 * D_)), v = split2(ldcg32f(src + D_) + ldcg32f(src + 4 * D_));
                const uint32_t s = split2(ldcg32f(src + 2 * D_) + ldcg32f(src + 5 * D_));
                sts128(sb + OFF_F1 + c * 16, u, __byte_perm(u, v, 0x5410), __byte_perm(v, 0, 0x1032), s);
                sts128(sb + M_F1 + c * 16, s & 0xffffu, 0, 0, 0);
            }
            fence_async_smem();
            warp_arrive(bars + B_VEC * 8);
            TS(lane == 0, 9)
#pragma unroll 1
            for (int e = 1; e < 3; e++) {
                wait_cnt(e == 1 ? &g_cnt.g1[min(grp + 15 + min(lane, 2), 31) * 32] : &g_cnt.g2[(grp + 16) * 32], 32, true);
                if (elect()) mbar_arrive(bars + (B_GATE + 2 + e) * 8);
                TS(lane == 0, 27 + 2 * e)
            }
            wait_cnt(&g_cnt.cs2[0], 4);
            if (elect()) mbar_arrive(bars + B_VEC3 * 8);
            TS(lane == 0, 19)
        }
        return;
    }

    {
        uint32_t ep;
        {
            TIDS
            ep = ld_cold(&g_epoch);
            const int cp = (tid + 16) % 40, cp1 = tid % 40;
            const uint4 sh0 = ldg128(pp.shift_k + (80 * (id & 7) + 2 * cp1) * 4), sh1 = ldg128(pp.shift_k + (80 * (id & 7) + 2 * cp) * 4);
            uint32_t dd;
            asm volatile("ld.global.nc.u16 %0, [%1];" : "=r"(dd) : "l"(pp.ssm_D + 5 * id + min(wg + 3 * lane, 4)));
            TR4(lane == 0, 40 + warp)
            __syncthreads();
            asm volatile("barrier.cluster.arrive.relaxed.aligned;" ::: "memory");
            asm volatile("add.u32 %0, %0, 1;" : "+r"(ep));
#pragma unroll 1
            for (int hw = 0; hw < 2; hw++) {
                if ((unsigned)(warp - 2 * hw) >= 10) continue;
                const int u = tid - 64 * hw;
                const int c = hw ? cp : cp1, oc = u / 40, line = 31 - 16 * hw - (id >> 3);
                const uint4 sh = hw ? sh1 : sh0;
                const uint32_t st = sb + OFF_ST + hw * 10240, sta = st + c * 256 + ((((6 - 2 * (oc & 3)) ^ (oc >> 2) ^ (line & 1)) ^ (c & 7)) << 4), in = oc * 1280 + c * 4;
                const uint32_t f0 = __byte_perm(sh.x, sh.z, 0x5410), f1 = __byte_perm(sh.x, sh.z, 0x7632), f2 = __byte_perm(sh.y, sh.w, 0x5410), f3 = __byte_perm(sh.y, sh.w, 0x7632);
                uint32_t kk[11], vv[8];
                mbar_spin(bars + (B_IN + hw) * 8, 0);
                TS(tid == 64, 18 + 42 * hw)
#pragma unroll
                for (int i = 0; i < 11; i++) kk[i] = lds32(sb + OFF_KIN + hw * 10752 + in + i * 160);
#pragma unroll
                for (int i = 0; i < 8; i++) vv[i] = lds32(sb + OFF_VIN + hw * 10240 + in + i * 160);
#pragma unroll
                for (int i = 0; i < 8; i++) vv[i] = mul2(fma2(kk[i + 3], f0, fma2(kk[i + 2], f1, fma2(kk[i + 1], f2, mul2(kk[i], f3)))), vv[i]);
                sts128(sta, tag(__byte_perm(vv[0], vv[1], 0x5410), ep), __byte_perm(vv[2], vv[3], 0x5410), __byte_perm(vv[4], vv[5], 0x5410), __byte_perm(vv[6], vv[7], 0x5410));
                sts128(sta + 128, tag(__byte_perm(vv[0], vv[1], 0x7632), ep), __byte_perm(vv[2], vv[3], 0x7632), __byte_perm(vv[4], vv[5], 0x7632), __byte_perm(vv[6], vv[7], 0x7632));
                bar_sync(7 + hw, 320);
                flush_tile(st, g_kvT + (size_t)(80 * (id & 7)) * S_ + 64 * line, u);
                TS(tid == 64 && hw, 1)
            }
            warp_arrive(bars + B_KVS * 8);
            if (tid < 320) sts128(sb + OFF_CH + (tid >> 6) * CH_BYTES + 4096 + (tid & 63) * 16, 0, 0, 0, 0);
            mbar_spin(bars + B_SSM * 8, 0);
            TS(tid == 0, 14)
#pragma unroll 1
            for (int u0 = wg; u0 < 20; u0 += 12) {
                uint2 w[4];
                uint32_t pv[4];
#pragma unroll
                for (int i = 0; i < 4; i++) {
                    const uint32_t a = sb + OFF_SSM + min(u0 + 3 * i, 19) * 1024 + wt * 8;
                    w[i] = lds64(a); pv[i] = lds32(a - 4);
                }
#pragma unroll
                for (int i = 0; i < 4; i++) {
                    const int un = min(u0 + 3 * i, 19);
                    sts128(sb + OFF_CH + (un >> 2) * CH_BYTES + OFF_P + (un & 3) * 2048 + wt * 16, __byte_perm(w[i].x, pv[i], 0x7610), __byte_perm(w[i].x, 0, 0x1032), __byte_perm(w[i].y, w[i].x, 0x7610), __byte_perm(w[i].y, 0, 0x1032));
                }
            }
            __syncwarp();
            if (wt < 2 - (wg >> 1)) {
                const uint32_t h = lds32(sb + OFF_SSM + (wg + 3 * wt) * 4096), h0 = pack2(blo(h) + blo(dd), 0.f);
                sts64f(sb + OFF_CH + (wg + 3 * wt) * CH_BYTES + OFF_P, __uint_as_float(h0), __uint_as_float(__byte_perm(h, h0, 0x5432)));
            }
            fence_async_smem();
            warp_arrive(bars + B_BK * 8);
            asm volatile("barrier.cluster.wait.aligned;" ::: "memory");
            mbar_spin(bars + B_BK * 8, 0);
            TS(tid == 0, 15)
        }

#pragma unroll 1
        for (int c = wg; c < 5; c += 3) {
            const uint32_t kvb = sb + OFF_CH + c * CH_BYTES;
            mbar_spin(bars + (c < 3 ? B_RAW : B_RAW3) * 8, 0);
            for (uint32_t ph = 0; c < 3; ph ^= 1) {
                const int wt = tid_now() & 127;
                if (!RARE(bar_any(1 + wg, lop3<0x7E>(lds32(kvb + wt * 16), ep, lds32(kvb + 2048 + wt * 16)) & 1))) break;
                if (wt == 0) { mbar_expect(bars + (B_RETRY + wg) * 8, 4096); bulk_ld(kvb, g_kvT + (size_t)(5 * id + c) * S_, 4096, bars + (B_RETRY + wg) * 8); }
                mbar_spin(bars + (B_RETRY + wg) * 8, ph);
                STALE1(-8)
            }
            TS(threadIdx.x == 0, c ? 13 : 11)
            float acc[64];
            {
                const int l = tid_now() & 31;
                conv_channel(acc, kvb + OFF_P + (8 * (warp & 3) + (l >> 2) - 2 * (l & 3)) * 4, (((uint64_t)0xC0000010u << 32) | ((kvb & 0x3FFFF) >> 4) | 0x10000u) + pp.nil);
            }
            TS(threadIdx.x == 0, c ? 16 : 12)
            if (c < 3) warp_arrive(bars + B_R1 * 8);
            else mbar_spin(bars + B_R1 * 8, 0);
            if (wg == 2 && id < 120) {
                TIDS
                mbar_spin(bars + B_RAW3 * 8, 0);
                mbar_spin(bars + B_WM * 8, 0);
                TS(wt == 0, 56)
                float d[4];
                gemv_tile<8>(d, sb + OFF_WM, sb + OFF_Z, 0);
                const float d2 = __shfl_up_sync(~0u, d[2], 1);
                TS(wt == 0, 7)
                if (t < 2) asm volatile("{\n.reg .b64 v;\nmov.b64 v, {%1, %2};\nst.relaxed.gpu.global.b64 [%0], v;\n}" ::"l"(g_mod + (id & 1) * 6 * D_ + 64 * pr + 16 * (warp & 3) + g + 8 * t),
                                        "r"(__float_as_uint(t ? d2 : d[0])), "r"(lds32(sb + M_EP)) : "memory");
            }
            TR4(threadIdx.x == 0, 60 + (c >= 3) * 10)
            TIDS
            const int e = 127 - 8 * (lane >> 4) - (lane & 7), u0 = (warp & 3) + 8 * (e >> 2) + (e & 3) + 4 * ((lane >> 3) & 1);
            const uint32_t ring = sb + OFF_RING + c * 16384 + (warp & 3) * 4096, wa = ring + (u0 ^ ((u0 >> 1) & 4)) * 16;
            if (lane < (warp & 3)) sts128(ring + lane * 16, 0, 0, 0, 0);
#pragma unroll
            for (int i = 0; i < 8; i++)
                stsm4t(i == 0 && u0 >= 256 ? sb + M_SINK : wa - 512 * i, pack2(acc[8 * i], acc[8 * i + 1]), pack2(acc[8 * i + 2], acc[8 * i + 3]),
                       pack2(acc[8 * i + 4], acc[8 * i + 5]), pack2(acc[8 * i + 6], acc[8 * i + 7]));
            warp_arrive(bars + (B_RING + c) * 8);
            TR4(threadIdx.x == 0, 61 + (c >= 3) * 10)
        }
        TIDS
        if (wg == 2) bar_sync(3, 128);
        if (warp == 8) {
            wait_cnt(&g_cnt.q[(id & 3) * 32], 128, true);
            if (elect()) {
                mbar_expect(bars + B_QRDY * 8, 28672);
                tma_ld2(sb + OFF_QT, &mp.qT, 80 * id, 0, bars + B_QRDY * 8);
                bulk_ld(sb + OFF_QT + 20480, g_qst, 8192, bars + B_QRDY * 8);
            }
            TS(lane == 0, 8)
        } else if (warp == 9) {
            const int v = min(lane / 5, 3);
            const uint2* gm = g_mod + (v + (v == 3)) * D_ + 5 * id + lane % 5;
            const unsigned epoch = lds32(sb + M_EP);
            uint2 r0, r1;
            unsigned it = 0;
            do {
                r0 = ld_mod(gm); r1 = ld_mod(gm + 6 * D_);
                SPIN_CHECK(55)
            } while (!__all_sync(~0u, r0.y == epoch && r1.y == epoch));
            const float m0 = __uint_as_float(r0.x), m1 = __uint_as_float(r1.x);
            const float m = rbf(m0 + m1), p = rbf(1.f + m);
            const float cz = zscale(__shfl_sync(~0u, p, 15 + lane % 5)), ga = __shfl_sync(~0u, m, 10 + lane % 5);
            if (lane < 15) sts32(sb + M_AB + lane % 5 * 16 + v * 4, lane < 10 ? __float_as_uint(cz * ga * (lane < 5 ? m : p)) : pack2(cz, cz));
            warp_arrive(bars + B_MODR * 8);
            TS(lane == 0, 6)
        }
        mbar_spin(bars + B_QRDY * 8, 0);
        uint4 rs[2], nm[2];
#pragma unroll
        for (int h = 0; h < 2; h++) { rs[h] = lds128(sb + OFF_QT + 20480 + h * 2048 + wt * 16); nm[h] = lds128(sb + OFF_QT + 24576 + h * 2048 + wt * 16); }
        mbar_spin(bars + B_MODR * 8, 0);
        TR4(threadIdx.x == 0, 72)
        uint32_t it = 0;
        while (RARE(__any_sync(~0u, (lop3<0x7E>(rs[0].x, ep, rs[0].z) | lop3<0x7E>(nm[0].x, ep, nm[0].z) | lop3<0x7E>(rs[1].x, ep, rs[1].z) | lop3<0x7E>(nm[1].x, ep, nm[1].z)) & 1))) {
#pragma unroll
            for (int h = 0; h < 2; h++) { rs[h] = ld_part(g_qst + 1024 * h + 8 * wt); nm[h] = ld_part(g_qst + S_ + 1024 * h + 8 * wt); }
            STALE(1)
            SPIN_CHECK(53)
        }
        TR4(threadIdx.x == 0, 73)
#pragma unroll 1
        for (int c = wg == 2 ? 0 : 3 + wg; c < (wg == 2 ? 3 : 4 + wg); c++) {
            uint4 q[2], p[2][4];
#pragma unroll
            for (int h = 0; h < 2; h++) q[h] = lds128(sb + OFF_QT + h * 10240 + (wt >> 1) * 160 + c * 32 + (wt & 1) * 16);
            const float4 ab = lds128f(sb + M_AB + c * 16);
            mbar_spin(bars + (B_RING + c) * 8, 0);
            TR4(wt == 0, wg == 2 ? 80 + 2 * c : 74)
#pragma unroll
            for (int i = 0; i < 8; i++) p[i >> 2][i & 3] = lds128(sb + OFF_RING + c * 16384 + (i & 3) * 4096 + (i >> 2) * 2048 + (wt ^ ((wt >> 1) & 4)) * 16);
            while (RARE(__any_sync(~0u, lop3<0x7E>(q[0].x, ep, q[1].x) & 1))) {
#pragma unroll
                for (int h = 0; h < 2; h++) q[h] = ld_part(g_qT + ((64 * h + (wt >> 1)) * D_ + 5 * id + c) * 16 + 8 * (wt & 1));
                STALE(2)
                SPIN_CHECK(52)
            }
            TR4(wt == 0, wg == 2 ? 81 + 2 * c : 75)
#pragma unroll
            for (int h = 0; h < 2; h++) {
                const uint32_t qq[4] = {q[h].x, q[h].y, q[h].z, q[h].w}, r4[4] = {rs[h].x, rs[h].y, rs[h].z, rs[h].w}, n4[4] = {nm[h].x, nm[h].y, nm[h].z, nm[h].w};
                const uint4 y = add2(add2(p[h][0], p[h][1]), add2(p[h][2], p[h][3]));
                const uint32_t yy[4] = {y.x, y.y, y.z, y.w};
                uint32_t o[4];
#pragma unroll
                for (int i = 0; i < 4; i++) {
                    const uint32_t n = fma2(qq[i], r4[i], n4[i]);
                    o[i] = fma2(pack2(fmaf(blo(n), ab.y, ab.x), fmaf(bhi(n), ab.y, ab.x)), yy[i], mul2(qq[i], __float_as_uint(ab.z)));
                }
                stg128_tag(g_x1T + (size_t)(5 * id + c) * S_ + 1024 * h + 8 * wt, o[0], o[1], o[2], o[3], ep, ((5 * id + c) >> 3) & 3);
            }
        }
        warp_arrive(bars + B_XS * 8);
        TS(tid == 0, 17)
        TS(tid == 256, 52)
    }

    const uint32_t nil = pp.nil;
    const int wq = warp & 3;
    if (wg == 2) {
        TIDS
        asm volatile("setmaxnreg.dec.sync.aligned.u32 " STR(REG_AUX) ";");
        {
            const uint32_t ep = lds32(sb + M_EP);
            uint32_t ph = 0;
#pragma unroll 1
            for (int m = wq - 4; m < 60; m += 4) {
                const int n = max(m, 0);
                const int e = (n >= 20) + (n >= 40), i = n - 20 * e;
                const uint32_t M = e == 0 ? M0 : e == 1 ? M1 : M2;
                const int w = (M >> i) & 1, c = __popc(M & ((1u << i) - 1)), kb = w ? c : i - c;
                const uint32_t a = sb + OFF_XR + (n & 7) * 8192;
                uint32_t ta = a + (e == 0 ? lane * 128 + ((lane & 7) << 4) + (lane >> 3) * 4
                                 : e == 1 ? (lane & 15) * 128 + (((lane >> 4 << 1) ^ (lane & 7)) << 4) + (lane & 8) + (lane >> 4) * 4
                                          : lane * 32 + (lane >> 2) * 4);
                uint32_t tb = e == 0 ? ta ^ 32 : ta + 2048, tc = e == 2 ? ta + 1024 : ta ^ 64, td = e == 2 ? tb + 1024 : tb ^ 64;
                uint32_t live = m >= 0,
                    f0 = bars + (B_XFULL + 10 * w + kb) * 8;
                uint32_t f1 = m == GATE_W2 || m == GATE_W3 || m == GATE_W3B ? bars + (B_GATE + (m >= GATE_W3) + (m >= GATE_W3B)) * 8 : 0;
                if (lane) f0 = f1;
                if (lane > 1 || m < 0) f0 = 0;
                asm volatile("" : "+r"(ta), "+r"(tb), "+r"(tc), "+r"(td), "+r"(live), "+r"(f0));
                mbar_spin(bars + (m < 0 ? B_BK : B_LAND + (n & 7)) * 8, (n >> 3) & 1);
                TR5(lane == 0, n)
                while (true) {
                    uint32_t v[8];
#pragma unroll
                    for (int i = 0; i < 8; i++) v[i] = lds32(((i & 2) ? ((i & 1) ? td : tc) : (i & 1) ? tb : ta) + (i >> 2) * 4096);
                    const uint32_t bad = lop3<0xFE>(lop3<0x7E>(v[0], ep, v[1]), lop3<0x7E>(v[2], ep, v[3]), lop3<0x7E>(v[4], ep, v[5]));
                    if (!RARE(__any_sync(~0u, lop3<0xA8>(bad, lop3<0x7E>(v[6], ep, v[7]), live)))) break;
                    if (elect()) load_tile(mp, a, e, grp + 16 * w, kb, j, bars + (B_AGAIN + wq) * 8);
                    mbar_spin(bars + (B_AGAIN + wq) * 8, ph);
                    ph ^= 1;
                    STALE1(e)
                }
                TR5(lane == 0, 60 + n)
                if (f0) mbar_arrive(f0);
            }
        }
        if (wq == 0) {
#pragma unroll 1
            for (int w = 0; w < 2; w++) {
                const uint4* src = g_part + (size_t)(grp + 16 * w) * 40960;
                TR4(lane == 0, 90 + 2 * w)
                mbar_wait(bars + (B_RING + w) * 8, 1);
                TR4(lane == 0, 91 + 2 * w)
                if (elect()) {
                    const uint32_t fb = bars + (B_IN + w) * 8, rem = sb + OFF_OUT + w * 10240;
                    mbar_expect(fb, 10240);
                    bulk_ld(rem + 8192, &g_x1f[((grp + 16 * w) * 8 + j) * 640 + 512], 2048, fb);
#pragma unroll 1
                    for (int i = 0; i < 4; i++) bulk_ld(rem + i * 2048, src + ((j >> 2) + 2 * i) * 5120 + 4096 + j * 128, 2048, fb);
                }
            }
        }
#pragma unroll 1
        for (int uw = 0; uw < 2; uw++) {
            const int tile = grp + 16 * uw;
            const uint32_t ep = lds32(sb + M_EP), in = sb + OFF_OUT + uw * 10240 + wt * 16, sr = in - lane * 16;
            mbar_wait(bars + (B_IN + uw) * 8, 1);
            TR4(wt == 0, 94 + 3 * uw)
            uint4 u[4];
#pragma unroll
            for (int i = 0; i < 4; i++) u[i] = lds128(in + i * 2048);
            const uint4 base = lds128(in + 8192);
            const uint32_t ra = sb + M_F1 + (64 * uw + 16 * wq + g) * 4;
            const uint4 gr = scale16(lds64f(sb + M_GB + (64 + 2 * t) * 4), lds64f(sb + M_GB + (72 + 2 * t) * 4), __uint_as_float(lds32(ra)), __uint_as_float(lds32(ra + 32)));
            uint32_t it = 0;
            while (RARE(__any_sync(~0u, stale4(u, ep) & 1))) {
                ld_part4(u, g_part + (size_t)tile * 40960 + (j >> 2) * 5120 + 4096 + j * 128 + wt, 10240);
                STALE(3)
                if (++it > SPIN_LIMIT) SPIN_FAIL(58)
            }
            TR4(wt == 0, 95 + 3 * uw)
            const uint4 r = fin16(add2(add2(u[0], u[1]), add2(u[2], u[3])), base, gr);
            __syncwarp();
            stsm4(sr + (lane & 15) * 32 + (((lane >> 4) ^ ((lane >> 2) & 1)) << 4), r.x, r.y, r.z, r.w);
            __syncwarp();
            stg128(out + (size_t)(64 * tile + 16 * wq + (lane >> 1)) * D_ + 512 + 16 * j + 8 * (lane & 1), lds128(sr + (lane >> 1) * 32 + (((lane & 1) ^ ((lane >> 3) & 1)) << 4)));
            TR4(wt == 0, 96 + 3 * uw)
            __syncwarp();
        }
        TS(wt == 0, 21)
        if (wq == 0) {
            uint32_t it = 0;
            while (!mbar_try(bars + B_OWN * 8, 0)) { if (++it > SPIN_LIMIT) SPIN_FAIL(56) }
        }
        return;
    }

    TIDS
    const int uw = wg, tile = grp + 16 * uw, row0 = 64 * tile + 16 * wq;
    const bool leader = wt == 0; (void)leader;
    const uint32_t xfull = bars + (B_XFULL + 10 * uw) * 8, xempty = bars + B_XEMPTY * 8, wfull = bars + B_WFULL * 8, wempty = bars + B_WEMPTY * 8;
    const uint64_t dz = mkdesc(0) + pp.nil;
    auto xwait = [&](uint32_t kb, uint32_t e) { mbar_spin(xfull + kb * 8, e & 1); };
    asm volatile("setmaxnreg.inc.sync.aligned.u32 " STR(REG_MMA) ";");
    const uint32_t ep = lds32(sb + M_EP);
    uint32_t res[20] = {};
    {
        float acc[40];
        const uint32_t la = ((lane & 7) + 8 * (lane >> 4)) * 128 + (((2 * wq + ((lane >> 3) & 1)) ^ (lane & 7)) << 4);
        auto pos = [&](int n) { return ring_pos(uw, n, LEAD1) & 7; };
        auto slot = [&](int n) { return sb + OFF_XR + pos(n) * 8192; };
        float al[2], r1[2], n1[2];
        {
            float sl[4], sq[4], v[4];
            uint32_t z0[16], z1[16], zz[16];
            uint64_t bd = dz + b80_desc(dsb, 0, 0, 0), tb = (((uint64_t)8 << 32) | ((dsb + OFF_TAB) >> 4) | (7u << 16)) + pp.nil;
            auto ldfrag = [&](uint32_t (&z)[16], int n) {
#pragma unroll
                for (int q = 0; q < 4; q++) ldsm4t(slot(n) + la + q * 2048, z[4 * q], z[4 * q + 1], z[4 * q + 2], z[4 * q + 3]);
            };
            auto tile1 = [&](const uint32_t (&zc)[16], uint32_t (&zn)[16], int n, int h) {
                const bool last = h && n == 5, ok = mbar_test(xfull + (n + 1) * 8, 0), okw = !h || mbar_test(wfull + ((n + 1) >> 1) * 8, 0);
                const int kb = g1_block(n, j);
                wg_fence();
#pragma unroll
                for (int q = 0; q < 2; q++) wgmma_rs80(acc, zc[4 * q], zc[4 * q + 1], zc[4 * q + 2], zc[4 * q + 3], bd + q * B80_STEP, 1);
                wg_commit();
                wg_wait<1>();
                if (!ok) xwait(n + 1, 0);
                if (!last) ldfrag(zn, n + 1);
#pragma unroll
                for (int e = 0; e < 16; e++) zz[e] = mul2(zc[e], zc[e]);
                const uint64_t t0 = last ? ((uint64_t)8 << 32) | ((dsb + M_NUL) >> 4) : tb;
                const uint32_t ts = last ? 0 : 14;
                wg_fence();
#pragma unroll
                for (int q = 0; q < 4; q++) wgmma_rs8(sl, zc[4 * q], zc[4 * q + 1], zc[4 * q + 2], zc[4 * q + 3], t0 + q * ts, 1);
#pragma unroll
                for (int q = 0; q < 4; q++) wgmma_rs8(sq, zz[4 * q], zz[4 * q + 1], zz[4 * q + 2], zz[4 * q + 3], t0 + q * ts, 1);
#pragma unroll
                for (int q = 2; q < 4; q++) wgmma_rs80(acc, zc[4 * q], zc[4 * q + 1], zc[4 * q + 2], zc[4 * q + 3], bd + q * B80_STEP, 1);
                wg_commit();
#pragma unroll
                for (int q = 0; q < 4; q++) ldsm4t_if(kb == j, slot(n) + la + q * 2048, &res[4 * q]);
                if (!h) ldsm4t_if(kb == 8 + (j >> 2), slot(n) + la + (j & 3) * 2048, &res[16]);
                if (lane < 2) mbar_arrive_after(xempty + pos(n) * 8, res[12], res[16], nil);
                if (!h && n && lane == 0) mbar_arrive(wempty + ((n >> 1) - 1) * 8);
                tb += 56;
                bd = bd + (uint64_t)B80_HALF;
                if (!okw) mbar_spin(wfull + ((n + 1) >> 1) * 8, 0);
                TR(leader, 100 + 10 * uw + n)
            };
            zero(acc); zero(sl); zero(sq);
            mbar_spin(bars + B_TAB * 8, 0);
            mbar_spin(wfull, 0);
            xwait(0, 0);
            TS(leader, 32 + uw)
            ldfrag(z0, 0);
#pragma unroll 1
            for (int n = 0; n < 6; n += 2) { tile1(z0, z1, n, 0); tile1(z1, z0, n + 1, 1); }
#pragma unroll
            for (int n = 6; n < 10; n++) {
                const uint64_t ad = dz + (((dsb + OFF_XR + pos(n) * 8192) >> 4) | 0x10000u);
                const bool ok = n == 9 || mbar_test(xfull + (n + 1) * 8, 0), okw = n != 7 || mbar_test(wfull + 4 * 8, 0);
                wg_fence();
#pragma unroll
                for (int q = 0; q < 4; q++) wgmma_ss80t(acc, ad + q * 128, bd + q * B80_STEP, 1);
                wg_commit();
                bd = bd + (uint64_t)B80_HALF;
                if (n == 9) ldsm4t_if(9 - (j & 1) == 8 + (j >> 2), slot(9) + la + (j & 3) * 2048, &res[16]);
                wg_wait<1>();
                if (n > 6 && lane < 2) mbar_arrive(xempty + pos(n - 1) * 8);
                if (!(n & 1) && lane == 0) mbar_arrive(wempty + ((n >> 1) - 1) * 8);
                if (n == 6) {
                    reg_fence(sl); reg_fence(sq);
#pragma unroll
                    for (int e = 0; e < 2; e++) {
                        v[2 * e] = t == 0 ? sl[2 * e] + sl[2 * e + 1] : t == 1 ? sq[2 * e] + sq[2 * e + 1] : sl[2 * e];
                        v[2 * e + 1] = t == 2 ? sl[2 * e + 1] : sq[2 * e];
                    }
                    st_peer(peer_addr(sb + OFF_ROW + uw * 2048 + wt * 16), __float_as_uint(v[0]), __float_as_uint(v[1]), __float_as_uint(v[2]), __float_as_uint(v[3]), peer_addr(bars + (B_SUMS + uw) * 8));
                    TS(leader && !uw, 59)
                }
                if (!ok) xwait(n + 1, 0);
                if (!okw) mbar_spin(wfull + 4 * 8, 0);
                TR(leader, 100 + 10 * uw + n)
            }
            float4 k = lds128f(sb + M_KS);
            float k4 = __uint_as_float(lds32(sb + M_KS + 16));
#pragma unroll
            for (int w = 1; w < 5; w++) {
                const float4 o = lds128f(sb + M_KS + w * 32);
                k.x += o.x; k.y += o.y; k.z += o.z; k.w += o.w; k4 += __uint_as_float(lds32(sb + M_KS + w * 32 + 16));
            }
            mbar_spin(bars + (B_SUMS + uw) * 8, 0);
            TS(leader && !uw, 10)
            const float4 o = lds128f(sb + OFF_ROW + uw * 2048 + wt * 16);
            v[0] += o.x; v[1] += o.y; v[2] += o.z; v[3] += o.w;
            uint32_t fa[4];
#pragma unroll
            for (int h = 0; h < 2; h++) {
                const int l0 = lane & ~3;
                const float s1 = __shfl_sync(~0u, v[2 * h], l0), s2 = __shfl_sync(~0u, v[2 * h], l0 + 1), scc = __shfl_sync(~0u, v[2 * h], l0 + 2);
                const float scs = __shfl_sync(~0u, v[2 * h + 1], l0 + 2), sc = __shfl_sync(~0u, v[2 * h], l0 + 3), sqq = __shfl_sync(~0u, v[2 * h + 1], l0 + 3);
                const float m1 = s1 * (1.f / D_), va = fmaxf(s2 * (1.f / D_) - m1 * m1, 0.f) + 1e-5f, r = rsqrtf(va);
                const float m2 = (r * (sc - m1 * k.x) + k.y) * (1.f / D_);
                const float e2 = (r * (r * (sqq + m1 * (m1 * k.z - 2.f * scc)) + 2.f * (scs - m1 * k.w)) + k4) * (1.f / D_);
                al[h] = r * 0.5f * rsqrtf(fmaxf(e2 - m2 * m2, 0.f) + 1e-5f); r1[h] = r; n1[h] = -m1 * r;
                const uint32_t fb = split2(va * r), fx = split2(t == 3 ? -m2 * va * r : -m1), fc = __shfl_sync(~0u, fx, lane | 3);
                fa[h] = __byte_perm(fx, fb, t == 1 ? 0x5432 : t == 2 ? 0x7654 : 0x1010);
                fa[2 + h] = t ? 0 : fc >> 16;
            }
            mbar_spin(bars + B_VEC * 8, 0);
            wg_fence();
            wgmma_rs80k(acc, fa[0], fa[1], fa[2], fa[3], ((uint64_t)8 << 32) | ((dsb + OFF_F1) >> 4) | (((M_F1 - OFF_F1) >> 4) << 16), 1);
            wg_commit();
        }
        wg_wait<0>();
        reg_fence(acc);
        if (lane < 2) mbar_arrive_after(xempty + pos(9) * 8, res[16], 0, nil);
        if (lane == 0) mbar_arrive(wempty + 4 * 8);
        TS(leader, 34 + uw)
        {
            bf16* const trow = g_t + (size_t)(row0 + g + 2) * D_;
#pragma unroll
            for (int b = 0; b < 3; b++) {
                uint32_t p[8];
#pragma unroll
                for (int ii = 0; ii < 4; ii++) {
                    const int i = 4 * b + ii;
                    if (i >= 10) continue;
#pragma unroll
                    for (int h = 0; h < 2; h++) p[(i & 3) + 4 * h] = pack2(gelu2(acc[4 * i + 2 * h] * al[h]), gelu2(acc[4 * i + 2 * h + 1] * al[h]));
                }
                if (b < 2) {
                    const int gr = (2 * j + b) / 5, sh = (gr & 1) ? -1 - (gr >> 1) : 1 + (gr >> 1);
                    bf16* dst = trow + 64 * j + 32 * b + 8 * t;
                    const int w = (((g + sh) >> 2) & 2) + (t >> 1);
                    stg128_tag(dst + sh * D_, p[0], p[1], p[2], p[3], ep, w);
                    stg128_tag(dst + (sh + 8) * D_, p[4], p[5], p[6], p[7], ep, w ^ 2);
                    if (row0 + g < sh || row0 + g + 8 >= S_ + sh) stg128_tag(dst + (sh > 0 ? 0 : 8) * D_, 0, 0, 0, 0, ep, (sh > 0 ? 0 : 2) + (t >> 1));
                } else {
                    bf16* dst = trow + 512 + 16 * j + 4 * t;
                    const uint32_t lo = t == (g < 2), hi = t == (g >= 2), o = j & 1;
                    stg64(dst - 2 * D_, lop3<0xB8>(p[0], lo & ~o, ep), lop3<0xB8>(p[1], lo & o, ep));
                    stg64(dst + 6 * D_, lop3<0xB8>(p[4], hi & ~o, ep), lop3<0xB8>(p[5], hi & o, ep));
                    if (row0 + g + 8 >= S_ - 2) stg64(dst + 8 * D_, ep & (t == 1) & ~o, ep & (t == 1) & o);
                }
            }
        }
        signal_cnt(&g_cnt.g1[tile * 32], lane, 1, true);
        TS(leader, 36 + uw)
#pragma unroll
        for (int i = 0; i < 10; i++) {
            const float2 c = lds64f(sb + M_C + (8 * i + 2 * t) * 4), s = lds64f(sb + M_SB + (8 * i + 2 * t) * 4);
#pragma unroll
            for (int h = 0; h < 2; h++) {
                acc[4 * i + 2 * h] = fmaf(blo(res[2 * i + h]), r1[h], fmaf(n1[h], c.x, s.x));
                acc[4 * i + 2 * h + 1] = fmaf(bhi(res[2 * i + h]), r1[h], fmaf(n1[h], c.y, s.y));
            }
        }
        mbar_spin(wfull + 5 * 8, 0);
        xwait(0, 1);
        TS(leader, 22 + uw)
        uint32_t ps = uw ? P1S : P0S, xo = (ps & 3) * 16, xp = 0;
        const uint64_t ax = dz + (((dsb + OFF_XR) >> 4) | 0x10000u);
        uint64_t ad = ax + xo * 64, bd = dz + b80_desc(dsb, 5, 0, 0);
#pragma unroll 1
        for (int i = 0; i < 5; i++) {
            const uint32_t x1 = xfull + (1 + 2 * i) * 8, p1 = 1, x2 = xfull + min(2 + 2 * i, 9) * 8, p2 = 1;
            const uint32_t w2 = wfull + (min(6 + i, 9) & 7) * 8, pw = i >= 2;
            const bool ok1 = mbar_test(x1, p1);
            wg_fence();
#pragma unroll
            for (int q = 0; q < 4; q++) wgmma_ss80(acc, ad + q * 2, bd + q * B80_STEP, 1);
            wg_commit();
            wg_wait<1>();
            if (lane < 2 && i) mbar_arrive(xempty + xp);
            if (lane == 0 && i) mbar_arrive(wempty + ((4 + i) & 7) * 8);
            if (!ok1) mbar_spin(x1, p1);
            const bool ok2 = mbar_test(x2, p2), okw = mbar_test(w2, pw);
            wg_fence();
#pragma unroll
            for (int q = 0; q < 4; q++) wgmma_ss80(acc, ad + 512 + q * 2, bd + B80_HALF + q * B80_STEP, 1);
            wg_commit();
            const uint32_t xc = xo;
            ps >>= 2;
            xp = xo + 8; xo = (ps & 3) * 16;
            ad = ax + xo * 64;
            bd += i == 2 ? 2 * B80_HALF - 8192 + (8192ll << 16) : 2 * B80_HALF;
            asm volatile("" : "+l"(ad), "+l"(bd));
            wg_wait<1>();
            if (lane < 2) mbar_arrive(xempty + xc);
            if (!ok2) mbar_spin(x2, p2);
            if (!okw) mbar_spin(w2, pw);
            TR(leader, (uw ? 86 : 20) + 2 * i)
        }
        wg_wait<0>();
        reg_fence(acc);
        if (lane < 2) mbar_arrive(xempty + xp);
        if (lane == 0) mbar_arrive(wempty + (9 & 7) * 8);
        TS(leader, 38 + uw)
        float a0 = 0.f, b0 = 0.f, a1 = 0.f, b1 = 0.f;
        uint32_t x2[20];
#pragma unroll
        for (int i = 0; i < 5; i++) {
            uint32_t* p = &x2[4 * i];
#pragma unroll
            for (int e = 0; e < 4; e++) p[e] = pack2(acc[8 * i + 2 * e], acc[8 * i + 2 * e + 1]);
#pragma unroll
            for (int e = 0; e < 4; e++) p[e] = lop3<0xB8>(p[e], (((wt >> 3) ^ (wt << 2)) & 7) == e, ep);
            stg128(&g_x2f[(tile * 40 + (i < 4 ? 4 * j + i : 32 + j)) * 128 + wt], p[0], p[1], p[2], p[3]);
#pragma unroll
            for (int e = 0; e < 8; e += 4) {
                const float* u = &acc[8 * i + e];
                a0 += u[0] + u[1]; b0 = fmaf(u[0], u[0], fmaf(u[1], u[1], b0));
                a1 += u[2] + u[3]; b1 = fmaf(u[2], u[2], fmaf(u[3], u[3], b1));
            }
        }
#pragma unroll
        for (int o = 1; o < 4; o *= 2) {
            a0 += __shfl_xor_sync(~0u, a0, o); b0 += __shfl_xor_sync(~0u, b0, o);
            a1 += __shfl_xor_sync(~0u, a1, o); b1 += __shfl_xor_sync(~0u, b1, o);
        }
        if (t < 2) stg64(&g_stats[(tile * 8 + j) * 64 + 16 * wq + g + 8 * t], tag(__float_as_uint(t ? a1 : a0), ep), __float_as_uint(t ? b1 : b0));
        signal_cnt(&g_cnt.g2[tile * 32], lane, 1, true);
        TS(leader, 40 + uw)
#pragma unroll
        for (int i = 0; i < 10; i++) {
            const float2 c = lds64f(sb + M_GB + (8 * i + 2 * t) * 4), e = lds64f(sb + M_CI + (8 * i + 2 * t) * 4);
#pragma unroll
            for (int h = 0; h < 2; h++)
                res[2 * i + h] = fma2(pack2(c.x, c.y), x2[2 * i + h], pack2(e.x * blo(res[2 * i + h]), e.y * bhi(res[2 * i + h])));
        }
#pragma unroll
        for (int i = 0; i < 20; i++) asm volatile("" : "+r"(res[i]));
    }
    float acc0[64], acc1[44];
    float2 q[4];
    {
        uint4 f0, f1, f2, f3;
        auto xseq = [&](int kb) { return ring_pos(uw, kb, XLEAD) & 7; };
        auto step = [&](const uint4& f, uint64_t bd) {
            wg_fence();
            wgmma_rs128(acc0, f.x, f.y, f.z, f.w, bd, 1);
            wgmma_rs88(acc1, f.x, f.y, f.z, f.w, bd + 512, 1);
            wg_commit();
        };
        const uint32_t xa = sb + OFF_XR + wt * 16;
        const float2* const gs = &g_stats[(tile * 8 + 2 * t) * 64 + 16 * wq + g];
        zero(acc0); zero(acc1);
        uint32_t xs = xseq(0);
        xwait(0, 2);
        TS(leader, 42 + uw)
        f0 = lds128(xa + xs * 8192); f1 = lds128(xa + xs * 8192 + 2048);
#pragma unroll
        for (int i = 0; i < 4; i++) q[i] = ld_stat(gs + (i & 1) * 64 + 8 * (i >> 1));
        mbar_spin(wfull + (10 & 7) * 8, (10 >> 3) & 1);
#pragma unroll 1
        for (int kb = 0; kb < 10; kb++) {
            const uint32_t wn = 10 + 2 * kb;
            const uint64_t bd = dz + (((dsb + OFF_W + (wn & 7) * 16384) >> 4) | (256u << 16));
            step(f0, bd);
            wg_wait<1>();
            if (kb && lane == 0) mbar_arrive(wempty + ((wn - 1) & 7) * 8);
            f2 = lds128(xa + xs * 8192 + 4096); f3 = lds128(xa + xs * 8192 + 6144);
            const bool w1 = mbar_test(wfull + ((wn + 1) & 7) * 8, (wn >> 3) & 1), x1 = kb < 9 && mbar_test(xfull + (kb + 1) * 8, 0);
            step(f1, bd + 128);
            if (!w1) mbar_spin(wfull + ((wn + 1) & 7) * 8, (wn >> 3) & 1);
            step(f2, bd + 1024);
            if (lane < 2) mbar_arrive_after(xempty + xs * 8, f2.x, f3.x, nil);
            wg_wait<1>();
            if (lane == 0) mbar_arrive(wempty + (wn & 7) * 8);
            xs = xseq(kb + 1);
            if (x1) { f0 = lds128(xa + xs * 8192); f1 = lds128(xa + xs * 8192 + 2048); }
            const bool w2 = mbar_test(wfull + ((wn + 2) & 7) * 8, ((wn + 2) >> 3) & 1);
            step(f3, bd + 1152);
            if (kb < 9 && !x1) { xwait(kb + 1, 2); f0 = lds128(xa + xs * 8192); f1 = lds128(xa + xs * 8192 + 2048); }
            if (!w2) mbar_spin(wfull + ((wn + 2) & 7) * 8, ((wn + 2) >> 3) & 1);
            if (kb == 4) {
                uint32_t it = 0;
                while (RARE(__any_sync(~0u, ((__float_as_uint(q[0].x) ^ ep) | (__float_as_uint(q[1].x) ^ ep) | (__float_as_uint(q[2].x) ^ ep) | (__float_as_uint(q[3].x) ^ ep)) & 1))) {
#pragma unroll
                    for (int i = 0; i < 4; i++) q[i] = ld_stat(gs + (i & 1) * 64 + 8 * (i >> 1));
                    SPIN_CHECK(49)
                }
                float a0 = q[0].x + q[1].x, b0 = q[0].y + q[1].y, a1 = q[2].x + q[3].x, b1 = q[2].y + q[3].y;
#pragma unroll
                for (int o = 1; o < 4; o *= 2) {
                    a0 += __shfl_xor_sync(~0u, a0, o); b0 += __shfl_xor_sync(~0u, b0, o);
                    a1 += __shfl_xor_sync(~0u, a1, o); b1 += __shfl_xor_sync(~0u, b1, o);
                }
                a0 *= 1.f / D_; a1 *= 1.f / D_;
                const float r0 = 0.5f * rsqrtf(fmaxf(b0 * (1.f / D_) - a0 * a0, 0.f) + 1e-5f), r1 = 0.5f * rsqrtf(fmaxf(b1 * (1.f / D_) - a1 * a1, 0.f) + 1e-5f);
                const uint32_t sel = t == 0 ? 0x1010 : t == 1 ? 0x4432 : 0x4444;
                if (t == 0) { sts32(sb + M_F1 + (64 * uw + 16 * wq + g) * 4, __float_as_uint(r0)); sts32(sb + M_F1 + (64 * uw + 16 * wq + g + 8) * 4, __float_as_uint(r1)); }
                q[2] = make_float2(8.f * 0.0356774081f * r0 * r0 * r0, 2.f * 0.7978845608f * r0);
                q[3] = make_float2(8.f * 0.0356774081f * r1 * r1 * r1, 2.f * 0.7978845608f * r1);
                q[1] = make_float2(__uint_as_float(__byte_perm(split2(-a0), 0, sel)), __uint_as_float(__byte_perm(split2(-a1), 0, sel)));
            }
            if (kb == 6) {
#pragma unroll
                for (int i = 0; i < 5; i++) stg128(&g_x1f[(tile * 8 + j) * 640 + i * 128 + wt], res[4 * i], res[4 * i + 1], res[4 * i + 2], res[4 * i + 3]);
            }
            if (kb == 8) asm volatile("fence.proxy.async.global;" ::: "memory");
            TR(leader, 10 * uw + kb)
        }
        const uint64_t fd = ((uint64_t)8 << 32) | ((dsb + OFF_W + 6 * 16384) >> 4);
        wg_fence();
        wgmma_rs128k(acc0, __float_as_uint(q[1].x), __float_as_uint(q[1].y), 0, 0, fd, 1);
        wgmma_rs88k(acc1, __float_as_uint(q[1].x), __float_as_uint(q[1].y), 0, 0, fd + 128, 1);
        wg_commit();
        if (lane == 0) {
            mbar_arrive(bars + B_XFREE * 8);
            asm volatile("mbarrier.arrive.shared::cluster.b64 _, [%0];" ::"r"(peer_addr(bars + B_XFREE * 8)) : "memory");
        }
    }
    const uint32_t recv = sb + recv_off(uw) + wt * 16;
    uint32_t ha[48] = {}, hb[48], hx[12];
    uint64_t wb = dz + (((dsb + OFF_W) >> 4) | (512u << 16));
    auto wdesc = [&](int n) { return wb + (n & 7) * 1024; };
    auto wwait = [&](int n) { mbar_spin(wfull + (n & 7) * 8, (n >> 3) & 1); };
    auto wfree = [&](int n) { if (lane == 0) mbar_arrive(wempty + (n & 7) * 8); };
    auto fresh = [&]() { wb += pp.nil; asm volatile("" : "+l"(wb)); };
    uint32_t pk[32];
    {
        float P0[64];
        const float2 r0 = q[2], r1 = q[3];
        const uint32_t ra = peer_addr(recv), rb = peer_addr(bars + (B_RECV + 4 * uw) * 8);
        auto conv32 = [&](const float* v, int b) {
#pragma unroll
            for (int i = 0; i < 4; i++) {
                ha[8 * b + 2 * i] = pack2(gelu2r(v[4 * i], r0), gelu2r(v[4 * i + 1], r0));
                ha[8 * b + 2 * i + 1] = pack2(gelu2r(v[4 * i + 2], r1), gelu2r(v[4 * i + 3], r1));
            }
#pragma unroll
            for (int s = 2 * b; s < 2 * b + 2; s++) st_peer(ra + s * 2048, ha[4 * s], ha[4 * s + 1], ha[4 * s + 2], ha[4 * s + 3], rb + (b >> 1) * 8);
        };
        auto fetch = [&](int k) {
            mbar_spin(bars + (B_RECV + 4 * uw + k) * 8, 0);
#pragma unroll
            for (int s = 4 * k; s < 4 * k + 4; s++) { const uint4 x = lds128(recv + s * 2048); hb[4 * s] = x.x; hb[4 * s + 1] = x.y; hb[4 * s + 2] = x.z; hb[4 * s + 3] = x.w; }
        };
        auto stage = [&](int n, const uint32_t* a, int steps, int sc) {
            wwait(n);
            wg_fence();
#pragma unroll
            for (int s = 0; s < steps; s++) wgmma_rs128(P0, a[4 * s], a[4 * s + 1], a[4 * s + 2], a[4 * s + 3], wdesc(n) + s * 128, sc || s);
            wg_commit();
        };
        wg_wait<0>();
        reg_fence(acc0); reg_fence(acc1);
        wfree(29); wfree(30);
        TS(leader, 44 + uw)
        uint32_t hr[6];
#pragma unroll
        for (int i = 0; i < 6; i++) {
            const float2 r = (i & 1) ? r1 : r0;
            hr[i] = pack2(gelu2r(acc1[32 + 2 * i], r), gelu2r(acc1[33 + 2 * i], r));
        }
        if (uw) mbar_spin(bars + B_XFREE * 8, 0);
        st_peer(ra + 24576, hr[0], hr[1], hr[2], hr[3], rb + 24);
        asm volatile("st.async.shared::cluster.mbarrier::complete_tx::bytes.v2.b32 [%0], {%1, %2}, [%3];" ::"r"(ra + 26624 - wt * 8), "r"(hr[4]), "r"(hr[5]), "r"(rb + 24) : "memory");
        conv32(&acc1[0], 4);
        conv32(&acc1[16], 5);
        TS(leader, 46 + uw)
        stage(31, &ha[32], 4, 0);
#pragma unroll
        for (int b = 0; b < 4; b++) {
            conv32(&acc0[16 * b], b);
            if (b == 3) {
                fetch(2);
                mbar_spin(bars + (B_RECV + 4 * uw + 3) * 8, 0);
                const uint4 x = lds128(recv + 24576);
                const uint2 y = lds64(recv + 26624 - wt * 8);
                const uint32_t hp[6] = {x.x, x.y, x.z, x.w, y.x, y.y};
#pragma unroll
                for (int i = 0; i < 6; i++) { hx[i] = (j & 1) ? hp[i] : hr[i]; hx[6 + i] = (j & 1) ? hr[i] : hp[i]; }
            }
            if (!(b & 1)) wwait(32 + (b >> 1));
            wg_fence();
#pragma unroll
            for (int s = 0; s < 2; s++) wgmma_rs128(P0, ha[8 * b + 4 * s], ha[8 * b + 4 * s + 1], ha[8 * b + 4 * s + 2], ha[8 * b + 4 * s + 3], wdesc(32 + (b >> 1)) + (2 * (b & 1) + s) * 128, 1);
            wg_commit();
            if (!(b & 1)) { wg_wait<1>(); wfree(31 + (b >> 1)); }
        }
        TR(leader, 64 + 10 * uw)
        fresh();
        stage(34, &hb[32], 4, 1); wg_wait<1>(); wfree(33);
        fetch(0);
        stage(35, hx, 3, 1); wg_wait<1>(); wfree(34);
        fetch(1);
        stage(36, &hb[0], 4, 1); wg_wait<1>(); wfree(35);
        stage(37, &hb[16], 4, 1); wg_wait<1>(); wfree(36);
        wg_wait<0>();
        reg_fence(P0);
        pack_part<64>(pk, P0, ep);
        uint32_t all = 0;
#pragma unroll
        for (int i = 0; i < 32; i++) all |= pk[i];
        if (lane == 0) mbar_arrive_after(wempty + (37 & 7) * 8, all, 0, nil);
        TR(leader, 65 + 10 * uw)
    }
    {
        uint4* const dst = g_part + (size_t)(tile * 8 + j) * 5120 + wt;
        const uint4* const src = g_part + (size_t)tile * 40960 + j * 512 + wt;
        float F[2][32];
        uint4 gb[4];
        float rr[2];
        float2 gf[8];
        uint4 base[4], u1[4], u2[4], u3[4];
#pragma unroll
        for (int c = 2; c < 5; c++) {
            float (&P)[32] = F[c & 1];
            fresh();
#pragma unroll
            for (int s = 0; s < 27; s++) {
                const int e = s < 8 ? 0 : s < 15 ? 1 : s < 23 ? 2 : 3, o = s - (e == 0 ? 0 : e == 1 ? 8 : e == 2 ? 15 : 23), n = 30 + 4 * c + e;
                const uint32_t* a = s < 12 ? &ha[4 * s] : s < 15 ? &hx[4 * (s - 12)] : &hb[4 * (s - 15)];
                if (o == 0) wwait(n);
                if (o == 0 || s == 1) wg_fence();
                wgmma_rs64(P, a[0], a[1], a[2], a[3], wdesc(n) + o * 128, s);
                if (o == 0) { wg_commit(); wg_wait<1>(); if (c > 2 || s) wfree(n - 1); }
                if (s == 0 && c > 2) { reg_fence(F[~c & 1]); pack_part<32>(pk, F[~c & 1], ep); }
                if (c == 2 && s % 3 == 0 && s < 24) st_part(dst + g4_block(s / 12, j) * 512 + (s / 3 & 3) * 128, &pk[4 * (s / 3)]);
                if (c == 3 && s % 4 == 1 && s < 16) st_part(dst + g4_block(2, j) * 512 + s / 4 * 128, &pk[4 * (s / 4)]);
                if (c == 4 && s % ST3 == 0 && s < 4 * ST3) st_part(dst + g4_block(3, j) * 512 + s / ST3 * 128, &pk[4 * (s / ST3)]);
                if (c == 4 && s >= 4 && s < 8) base[s - 4] = ldcg128(&g_x1f[(tile * 8 + j) * 640 + (s - 4) * 128 + wt]);
                if (c == 4 && s >= 19 && s < 23) { gf[2 * s - 38] = lds64f(sb + M_GB + (16 * (s - 19) + 2 * t) * 4); gf[2 * s - 37] = lds64f(sb + M_GB + (16 * (s - 19) + 8 + 2 * t) * 4); }
                if (c == 4 && s >= 12 && s < 14) rr[s - 12] = __uint_as_float(lds32(sb + M_F1 + (64 * uw + 16 * wq + g + 8 * (s - 12)) * 4));
                if (c == 4 && s >= 8 && s < 12) u1[s - 8] = ld_part(src + (j ^ 6) * 5120 + (s - 8) * 128);
                if (c == 4 && s >= 15 && s < 19) u2[s - 15] = ld_part(src + (j ^ 4) * 5120 + (s - 15) * 128);
                if (c == 4 && s >= LD3 && s < LD3 + 4) u3[s - LD3] = ld_part(src + (j ^ 2) * 5120 + (s - LD3) * 128);
                if (27 * (c - 2) + s == R_GATE && lane == 0) mbar_arrive(bars + (B_RING + uw) * 8);
                if (s == 7 || s == 14 || s == 22 || s == 26) wg_commit();
                if (c == 4) { TR(leader && s == 7, 68 + 10 * uw) TR(leader && s == 14, 69 + 10 * uw) TR(leader && s == 22, 70 + 10 * uw) }
            }
            TR(leader, 64 + c + (c == 4 ? 3 : 0) + 10 * uw)
        }
        float (&O)[32] = F[0];
#pragma unroll
        for (int i = 0; i < 4; i++) gb[i] = scale16(gf[2 * i], gf[2 * i + 1], rr[0], rr[1]);
        uint32_t it = 0;
        while (__any_sync(~0u, (stale4(u1, ep) | stale4(u2, ep) | stale4(u3, ep)) & 1)) {
            ld_part4(u1, src + (j ^ 6) * 5120, 128); ld_part4(u2, src + (j ^ 4) * 5120, 128); ld_part4(u3, src + (j ^ 2) * 5120, 128);
            STALE(6)
            SPIN_CHECK(58)
        }
        TR(leader, 73 + 10 * uw)
#pragma unroll
        for (int i = 0; i < 4; i++) u1[i] = add2(add2(u1[i], u2[i]), u3[i]);
        TS(leader, 50 + uw)
        wg_wait<0>();
        reg_fence(O);
        TS(leader, 48 + uw)
        const uint32_t so = sb + recv_off(uw) + wq * 2048;
#pragma unroll
        for (int i = 0; i < 4; i++) {
            const float* o = &O[8 * i];
            const uint4 r = fin16(add2(u1[i], make_uint4(pack2(o[0], o[1]), pack2(o[2], o[3]), pack2(o[4], o[5]), pack2(o[6], o[7]))), base[i], gb[i]);
            stsm4(so + (lane & 15) * 128 + (((2 * i + (lane >> 4)) ^ (lane & 7)) << 4), r.x, r.y, r.z, r.w);
        }
        TR4(leader, 100 + uw)
        __syncwarp();
#pragma unroll
        for (int i = 0; i < 4; i++) {
            const int row = (lane >> 3) + 4 * i;
            stg128(out + (size_t)(row0 + row) * D_ + 64 * j + 8 * (lane & 7), lds128(so + row * 128 + (((lane & 7) ^ (row & 7)) << 4)));
        }
        TS(leader, 24 + uw)
        warp_arrive(bars + B_OWN * 8);
    }
}

typedef CUresult (*EncFn)(CUtensorMap*, CUtensorMapDataType, cuuint32_t, void*, const cuuint64_t*, const cuuint64_t*, const cuuint32_t*,
                          const cuuint32_t*, CUtensorMapInterleave, CUtensorMapSwizzle, CUtensorMapL2promotion, CUtensorMapFloatOOBfill);

static void enc(EncFn fn, CUtensorMap* m, void* p, int rank, const cuuint64_t* dims, const cuuint64_t* strides, const cuuint32_t* box, bool plain = false) {
    const CUtensorMapSwizzle sw = box[0] > 64 || plain ? CU_TENSOR_MAP_SWIZZLE_NONE : CU_TENSOR_MAP_SWIZZLE_128B;
    cuuint32_t es[5] = {1, 1, 1, 1, 1};
    CUresult r = fn(m, CU_TENSOR_MAP_DATA_TYPE_BFLOAT16, rank, p, dims, strides, box, es, CU_TENSOR_MAP_INTERLEAVE_NONE, sw,
                    CU_TENSOR_MAP_L2_PROMOTION_L2_128B, CU_TENSOR_MAP_FLOAT_OOB_FILL_NONE);
    (void)r;
}
static void enc2(EncFn fn, CUtensorMap* m, void* p, uint64_t cols, uint64_t rows, uint32_t bc, uint32_t br, bool plain = false) {
    cuuint64_t dims[2] = {cols, rows}, st[1] = {cols * 2};
    cuuint32_t box[2] = {bc, br};
    enc(fn, m, p, 2, dims, st, box, plain);
}

extern "C" void kernel_launch(void* const* d_in, const int* in_sizes, int n_in, void* d_out, int out_size) {
    static Maps mp;
    static Ptrs pp;
    static void* cached[13];
    bool same = true;
    for (int i = 0; i < 13; i++) same = same && (cached[i] == d_in[i]);
    if (!same) {
        void* fnp = nullptr;
        cudaDriverEntryPointQueryResult qr;
        cudaGetDriverEntryPoint("cuTensorMapEncodeTiled", &fnp, cudaEnableDefault, &qr);
        EncFn fn = (EncFn)fnp;
        cudaGetSymbolAddress((void**)&pp.s, g_scratch);
        void *x1T = g_x1T, *t = g_t;
        cuuint64_t dq[3] = {64, S_, 10}, sq[2] = {D_ * 2, 128};
        cuuint32_t bq[3] = {64, 16, 10};
        enc(fn, &mp.q, d_in[0], 3, dq, sq, bq);
        enc2(fn, &mp.k, d_in[1], D_, S_, 80, 67); enc2(fn, &mp.v, d_in[2], D_, S_, 80, 64);
        enc2(fn, &mp.qT, g_qT, 16 * D_, 128, 80, 128);
        enc2(fn, &mp.x[0], x1T, S_, D_, 64, 64); enc2(fn, &mp.x[1], (bf16*)t + 2 * D_, D_, S_, 64, 64);
        enc2(fn, &mp.x[2], g_x2f, 64, 320 * 64, 64, 64, true);
        enc2(fn, &mp.w1, d_in[7], D_, D_, 64, 64); enc2(fn, &mp.w1h, d_in[7], D_, D_, 64, 160); enc2(fn, &mp.w3h, d_in[9], F_, D_, 64, 160);
        enc2(fn, &mp.wmod, d_in[12], 6 * D_, D_, 64, 160);
        const cuuint64_t R = D_ * 2;
        cuuint64_t da[5] = {D_, 2, 4, 4, 16}, sa[4] = {R, 8 * R, 2 * R, 32 * R}, db[5] = {D_, 2, 2, 4, 8}, sb[4] = {R, 8 * R, 2 * R, 16 * R};
        cuuint32_t ba[5] = {64, 2, 4, 4, 4}, bb[5] = {64, 2, 2, 4, 8};
        enc(fn, &mp.w2a, d_in[8], 5, da, sa, ba); enc(fn, &mp.w2b, (bf16*)d_in[8] + 512 * D_, 5, db, sb, bb);
        cuuint64_t dw[3] = {64, D_, 27}, sw[2] = {F_ * 2, 128};
        cuuint32_t bw[3] = {64, 32, 3};
        enc(fn, &mp.w3a, d_in[9], 3, dw, sw, bw);
        enc2(fn, &mp.w3b, d_in[9], F_, D_, 24, 32);
        enc2(fn, &mp.w4[0], d_in[10], D_, F_, 64, 64); enc2(fn, &mp.w4[1], d_in[10], D_, F_, 64, 48);
        pp.q = (const bf16*)d_in[0]; pp.w_mod = (const bf16*)d_in[12]; pp.shift_k = (const bf16*)d_in[3];
        pp.ssm_k = (const bf16*)d_in[4]; pp.ssm_D = (const bf16*)d_in[5]; pp.w1 = (const bf16*)d_in[7]; pp.w2 = (const bf16*)d_in[8];
        pp.w4 = (const bf16*)d_in[10]; pp.c = (const bf16*)d_in[11];
        cudaFuncSetAttribute(fused_kernel, cudaFuncAttributeMaxDynamicSharedMemorySize, SMEM_BYTES);
        for (int i = 0; i < 13; i++) cached[i] = d_in[i];
    }
    fused_kernel<<<NCTA, NTHR, SMEM_BYTES, cudaStreamPerThread>>>(pp, (bf16*)d_out, mp);
}
```

```cpp
#include <cuda_runtime.h>
#include <cuda_bf16.h>
#include <cuda.h>
#include <stdint.h>
#include <stdio.h>

typedef __nv_bfloat16 bf16;

constexpr int S_ = 2048, D_ = 640, F_ = 1728;
constexpr int NCTA = 132, NTHR = 512;

constexpr int TAB_BYTES = 9216, VEC_BYTES = 1440;
struct Counters {
    unsigned kv[8 * 32];
    unsigned q[4 * 32], x[4 * 32];
    unsigned wr[32], tab[32], uv[32], cs[32], cs2[32], done[32];
    unsigned g1[32 * 32];
    unsigned g2[32 * 32];
};
struct Scratch {
    Counters cnt;
    unsigned epoch;
    alignas(1024) bf16 qst[2 * S_];
    alignas(1024) uint4 wr[2 * 8 * 10 * 128];
    alignas(1024) uint2 mod[2 * 6 * D_];
    alignas(1024) uint4 tab[(TAB_BYTES + 8 * VEC_BYTES) / 16];
    alignas(1024) float uv[2 * 3 * D_];
    alignas(1024) float cs3[2 * 1920];
    alignas(1024) uint4 cs3b[8 * 216];
    alignas(1024) float2 stats[32 * 8 * 64];
    alignas(1024) bf16 kvT[D_ * S_];
    alignas(1024) bf16 qT[D_ * S_];
    alignas(1024) bf16 x1T[D_ * S_];
    alignas(1024) bf16 t[(S_ + 4) * D_];
    alignas(1024) uint4 x2f[32 * 40 * 128];
    alignas(1024) uint4 x1f[32 * 8 * 5 * 128];
    alignas(1024) uint4 part[32 * 8 * 10 * 4 * 128];
};
__device__ Scratch g_scratch;
#define g_kvT (pp.s->kvT)
#define g_qT (pp.s->qT)
#define g_x1T (pp.s->x1T)
#define g_qst (pp.s->qst)
#define g_t (pp.s->t)
#define g_x2f (pp.s->x2f)
#define g_x1f (pp.s->x1f)
#define g_part (pp.s->part)
#define g_wr (pp.s->wr)
#define g_mod (pp.s->mod)
#define g_tab (pp.s->tab)
#define g_uv (pp.s->uv)
#define g_cs3 (pp.s->cs3)
#define g_cs3b (pp.s->cs3b)
#define g_stats (pp.s->stats)
#define g_cnt (pp.s->cnt)
#define g_epoch (pp.s->epoch)

struct Maps {
    CUtensorMap k, v, q;
    CUtensorMap qT;
    CUtensorMap x[3];
    CUtensorMap w1, w1h, w3h, wmod;
    CUtensorMap w2a, w2b;
    CUtensorMap w3a, w3b;
    CUtensorMap w4[2];
};

struct Ptrs {
    Scratch* s;
    uint64_t nil;
    const bf16 *q, *w_mod, *shift_k, *ssm_k, *ssm_D, *w1, *w2, *w4, *c;
};

constexpr int OFF_W = 0;
constexpr int OFF_XR = 131072;
constexpr int OFF_REM = 196608;
constexpr int OFF_TAB = OFF_REM + 5 * 4096;
constexpr int OFF_ROW = OFF_TAB + 4608;
constexpr int OFF_F1 = OFF_ROW + 4096;
constexpr int RECV_BYTES = 30720;
constexpr int OFF_M = OFF_REM + RECV_BYTES;
constexpr int OFF_OUT = OFF_XR + 32768;
static_assert(OFF_F1 + 1280 <= OFF_M, "G1 map");
constexpr int OFF_ST = 0;
constexpr int OFF_SSM = 20480;
constexpr int OFF_WM = 0;
constexpr int OFF_QIN = 49152;
constexpr int OFF_QT = 49152;
constexpr int OFF_Z = OFF_TAB;
constexpr int OFF_RING = 80896;
constexpr int OFF_KIN = OFF_RING, OFF_VIN = OFF_KIN + 2 * 10752;
constexpr int OFF_CH = OFF_RING + 3 * 16384, CH_BYTES = 13312, OFF_P = 5120;
static_assert(OFF_RING + 5 * 16384 <= OFF_CH + 3 * CH_BYTES && OFF_CH + 5 * CH_BYTES <= OFF_REM, "the last two rings replace channels 0..2");
constexpr int M_BAR = OFF_M;
constexpr int M_F1 = OFF_M + 832;
constexpr int M_GB = M_F1 + 1280, M_C = M_GB + 320, M_SB = M_C + 320, M_CI = M_SB + 320;
constexpr int M_KS = M_CI + 320;
constexpr int M_AB = M_KS + 160;
constexpr int M_EP = M_AB + 80;
constexpr int M_SINK = M_EP + 16;
constexpr int M_NUL = M_SINK + 16;
constexpr int M_TS = M_NUL + 128;
constexpr int SMEM_BYTES = M_TS;
static_assert(SMEM_BYTES <= 232448, "smem");

enum { B_WFULL = 0, B_WEMPTY = 8, B_XEMPTY = 16, B_XFULL = 24  ,
       B_RAW = 44, B_QIN = 45, B_SSM = 46, B_VEC = 47, B_VEC3 = 48, B_WM = 49, B_TAB = 50, B_QRDY = 51,
       B_MODR = 52, B_RAW2 = 53, B_RAW3 = 54, B_GATE = 56, B_SUMS = 62, B_RECV = 64  ,
       B_LAND = 72, B_AGAIN = 80, B_RETRY = 84,
       B_XS = 88, B_R1 = 89, B_BK = 90, B_KVS = 91,
       B_XFREE = 92, B_OWN = 93, B_IN = 94,
       B_RING = 96   };
#define T_KVB 1800
#define T_SSM 3300
#define PF_T0 4800
#define PF_DT 420
#define Q_UNROLL 1
#define HELP_T 1000
#define R_GATE 34
#define REG_AUX 40
#define REG_SVC 40
#define REG_MMA 216
#define STR2(x) #x
#define STR(x) STR2(x)
#define ST3 1
#define LD3 23
#define GATE_W2 7
#define GATE_W3 27
#define GATE_W3B 37
#define W3_N2 13
#define LEAD2 5
#define LEAD1 4
#define XLEAD 3

#define SPIN_FAIL(code) __trap();
#define SPIN_LIMIT (1u << 22)
#define STALE(c)
#define STALE1(c)
#define TS(c, i)
#define TG(c, i)
#define TR(c, i)
#define TR2(c, i)
#define TR4(c, i)
#define TR5(c, i)
#define SPIN_CHECK(code) asm volatile("" ::"r"(it));
#define RARE(x) __builtin_expect((x) != 0, 0)
__device__ __forceinline__ uint32_t s2u(const void* p) { return (uint32_t)__cvta_generic_to_shared(p); }
__device__ __forceinline__ bool elect() {
    uint32_t p;
    asm volatile("{.reg .pred P; elect.sync _|P, 0xffffffff; selp.u32 %0,1,0,P;}" : "=r"(p));
    return p != 0;
}
__device__ __forceinline__ void mbar_init(uint32_t b, uint32_t n) { asm volatile("mbarrier.init.shared.b64 [%0], %1;" ::"r"(b), "r"(n)); }
__device__ __forceinline__ void mbar_expect(uint32_t b, uint32_t bytes) {
    asm volatile("mbarrier.arrive.expect_tx.shared.b64 _, [%0], %1;" ::"r"(b), "r"(bytes) : "memory");
}
__device__ __forceinline__ void mbar_arrive(uint32_t b) { asm volatile("mbarrier.arrive.shared.b64 _, [%0];" ::"r"(b) : "memory"); }
__device__ __forceinline__ void mbar_arrive_after(uint32_t b, uint32_t v0, uint32_t v1, uint32_t nil) { mbar_arrive(b + ((v0 | v1) & nil)); }
__device__ __forceinline__ void warp_arrive(uint32_t b) { __syncwarp(); if (elect()) mbar_arrive(b); }
__device__ __forceinline__ uint32_t peer_addr(uint32_t a) {
    uint32_t r;
    asm("{\n.reg .b32 q;\nmov.u32 q, %%cluster_ctarank;\nxor.b32 q, q, 1;\nmapa.shared::cluster.u32 %0, %1, q;\n}" : "=r"(r) : "r"(a));
    return r;
}
__device__ __forceinline__ bool mbar_test(uint32_t b, uint32_t parity) {
    uint32_t ok;
    asm volatile("{.reg .pred P; mbarrier.test_wait.parity.shared.b64 P, [%1], %2; selp.u32 %0,1,0,P;}" : "=r"(ok) : "r"(b), "r"(parity) : "memory");
    return ok != 0;
}
__device__ __forceinline__ bool mbar_try(uint32_t b, uint32_t parity) {
    uint32_t ok;
    asm volatile("{.reg .pred P; mbarrier.try_wait.parity.shared.b64 P, [%1], %2; selp.u32 %0,1,0,P;}" : "=r"(ok) : "r"(b), "r"(parity) : "memory");
    return ok != 0;
}
__device__ __forceinline__ void mbar_wait(uint32_t b, uint32_t parity) {
    if (__all_sync(0xffffffffu, mbar_try(b, parity))) return;
    uint32_t it = 0;
    while (!__all_sync(0xffffffffu, mbar_try(b, parity))) { if (++it > SPIN_LIMIT) SPIN_FAIL((b >> 3) & 63) }
}
__device__ __forceinline__ void mbar_spin(uint32_t b, uint32_t parity) {
    asm volatile("{\n.reg .pred P;\nSPIN:\nmbarrier.try_wait.parity.shared.b64 P, [%0], %1;\n@!P bra.uni SPIN;\n}" ::"r"(b), "r"(parity) : "memory");
}
__device__ __forceinline__ void bar_sync(int id, int n) { asm volatile("bar.sync %0, %1;" ::"r"(id), "r"(n) : "memory"); }
__device__ __forceinline__ void fence_async_smem() { asm volatile("fence.proxy.async.shared::cta;" ::: "memory"); }
__device__ __forceinline__ void wait_cnt(const unsigned* p, unsigned target, bool tagged = false) {
    unsigned v, it = 0;
    do {
        asm volatile("ld.relaxed.gpu.global.u32 %0, [%1];" : "=r"(v) : "l"(p) : "memory");
        SPIN_CHECK(60 + (target & 3))
    } while (!__all_sync(0xffffffffu, v >= target));
    if (!tagged) asm volatile("fence.acquire.gpu;" ::: "memory");
}
__device__ __forceinline__ void signal_cnt(unsigned* p, int lane, int n, bool tagged = false) {
    if (tagged) asm volatile("{\n.reg .pred P;\nsetp.lt.s32 P, %1, %2;\n@P red.relaxed.gpu.global.add.u32 [%0], %3;\n}" ::"l"(p), "r"(lane), "r"(n), "r"(1) : "memory");
    else if (lane < n) asm volatile("red.release.gpu.global.add.u32 [%0], 1;" ::"l"(p) : "memory");
    __syncwarp();
}
__device__ __forceinline__ uint32_t clock_lo() { uint32_t c; asm volatile("mov.u32 %0, %%clock;" : "=r"(c)); return c; }
__device__ __forceinline__ void wait_clock(uint32_t c0, uint32_t t) {
    asm volatile("{\n.reg .pred P;\n.reg .b32 c;\nWAIT:\nnanosleep.u32 20;\nmov.u32 c, %%clock;\nsub.u32 c, c, %0;\nsetp.lt.u32 P, c, %1;\n@P bra.uni WAIT;\n}" ::"r"(c0), "r"(t) : "memory");
}
__device__ __forceinline__ void tma_ld2(uint32_t dst, const CUtensorMap* m, int c0, int c1, uint32_t bar) {
    asm volatile("cp.async.bulk.tensor.2d.shared::cluster.global.mbarrier::complete_tx::bytes [%0], [%1, {%3, %4}], [%2];"
                 ::"r"(dst), "l"(m), "r"(bar), "r"(c0), "r"(c1) : "memory");
}
__device__ __forceinline__ void tma_ld3(uint32_t dst, const CUtensorMap* m, int c0, int c1, int c2, uint32_t bar) {
    asm volatile("cp.async.bulk.tensor.3d.shared::cluster.global.mbarrier::complete_tx::bytes [%0], [%1, {%3, %4, %5}], [%2];"
                 ::"r"(dst), "l"(m), "r"(bar), "r"(c0), "r"(c1), "r"(c2) : "memory");
}
__device__ __forceinline__ void tma_ld5(uint32_t dst, const CUtensorMap* m, int col, int blk, uint32_t bar) {
    asm volatile("cp.async.bulk.tensor.5d.shared::cluster.global.mbarrier::complete_tx::bytes [%0], [%1, {%3, %4, %4, %4, %5}], [%2];"
                 ::"r"(dst), "l"(m), "r"(bar), "r"(col), "r"(0), "r"(blk) : "memory");
}
__device__ __forceinline__ void bulk_ld(uint32_t dst, const void* src, uint32_t bytes, uint32_t bar) {
    asm volatile("cp.async.bulk.shared::cluster.global.mbarrier::complete_tx::bytes [%0], [%1], %2, [%3];" ::"r"(dst), "l"(src), "r"(bytes), "r"(bar) : "memory");
}
__device__ __forceinline__ void l2_prefetch(const void* p, uint32_t bytes) {
    asm volatile("cp.async.bulk.prefetch.L2.global [%0], %1;" ::"l"(p), "r"(bytes) : "memory");
}
__device__ __forceinline__ void wg_fence() { asm volatile("wgmma.fence.sync.aligned;" ::: "memory"); }
__device__ __forceinline__ void wg_commit() { asm volatile("wgmma.commit_group.sync.aligned;" ::: "memory"); }
template <int N> __device__ __forceinline__ void wg_wait() { asm volatile("wgmma.wait_group.sync.aligned %0;" ::"n"(N) : "memory"); }
template <int N> __device__ __forceinline__ void reg_fence(float (&d)[N]) {
#pragma unroll
    for (int i = 0; i < N; i++) asm volatile("" : "+f"(d[i])::"memory");
}
template <int N> __device__ __forceinline__ void zero(float (&d)[N]) {
#pragma unroll
    for (int i = 0; i < N; i++) asm volatile("mov.b32 %0, 0;" : "=f"(d[i]));
}
__device__ __forceinline__ uint32_t lds32(uint32_t a) { uint32_t v; asm volatile("ld.shared.b32 %0, [%1];" : "=r"(v) : "r"(a)); return v; }
__device__ __forceinline__ uint2 lds64(uint32_t a) { uint2 v; asm volatile("ld.shared.v2.b32 {%0,%1}, [%2];" : "=r"(v.x), "=r"(v.y) : "r"(a)); return v; }
__device__ __forceinline__ float2 lds64f(uint32_t a) { float2 v; asm volatile("ld.shared.v2.f32 {%0,%1}, [%2];" : "=f"(v.x), "=f"(v.y) : "r"(a)); return v; }
__device__ __forceinline__ void sts32(uint32_t a, uint32_t v) { asm volatile("st.shared.b32 [%0], %1;" ::"r"(a), "r"(v) : "memory"); }
__device__ __forceinline__ void sts64f(uint32_t a, float x, float y) { asm volatile("st.shared.v2.f32 [%0], {%1,%2};" ::"r"(a), "f"(x), "f"(y) : "memory"); }
__device__ __forceinline__ void sts128(uint32_t a, uint32_t x, uint32_t y, uint32_t z, uint32_t w) {
    asm volatile("st.shared.v4.b32 [%0], {%1,%2,%3,%4};" ::"r"(a), "r"(x), "r"(y), "r"(z), "r"(w) : "memory");
}
__device__ __forceinline__ void sts128f(uint32_t a, float x, float y, float z, float w) {
    asm volatile("st.shared.v4.f32 [%0], {%1,%2,%3,%4};" ::"r"(a), "f"(x), "f"(y), "f"(z), "f"(w) : "memory");
}
__device__ __forceinline__ uint4 lds128(uint32_t a) {
    uint4 v;
    asm volatile("ld.shared.v4.b32 {%0,%1,%2,%3}, [%4];" : "=r"(v.x), "=r"(v.y), "=r"(v.z), "=r"(v.w) : "r"(a) : "memory");
    return v;
}
__device__ __forceinline__ void lds128_if(int p, uint4& v, uint32_t a) {
    asm volatile("{\n.reg .pred p;\nsetp.ne.s32 p, %5, 0;\n@p ld.shared.v4.b32 {%0,%1,%2,%3}, [%4];\n}" : "+r"(v.x), "+r"(v.y), "+r"(v.z), "+r"(v.w) : "r"(a), "r"(p) : "memory");
}
__device__ __forceinline__ float4 lds128f(uint32_t a) {
    float4 v;
    asm volatile("ld.shared.v4.f32 {%0,%1,%2,%3}, [%4];" : "=f"(v.x), "=f"(v.y), "=f"(v.z), "=f"(v.w) : "r"(a) : "memory");
    return v;
}
__device__ __forceinline__ void stg128(void* p, uint32_t x, uint32_t y, uint32_t z, uint32_t w) {
    asm volatile("st.global.v4.b32 [%0], {%1,%2,%3,%4};" ::"l"(p), "r"(x), "r"(y), "r"(z), "r"(w) : "memory");
}
__device__ __forceinline__ void stg128(void* p, uint4 v) { stg128(p, v.x, v.y, v.z, v.w); }
__device__ __forceinline__ void stg128_if(void* p, uint4 v, int on) {
    asm volatile("{\n.reg .pred p;\nsetp.ne.s32 p, %5, 0;\n@p st.global.v4.b32 [%0], {%1,%2,%3,%4};\n}" ::"l"(p), "r"(v.x), "r"(v.y), "r"(v.z), "r"(v.w), "r"(on) : "memory");
}
__device__ __forceinline__ void stg64(void* p, uint32_t x, uint32_t y) { asm volatile("st.global.v2.b32 [%0], {%1,%2};" ::"l"(p), "r"(x), "r"(y) : "memory"); }
__device__ __forceinline__ void stsm4(uint32_t a, uint32_t r0, uint32_t r1, uint32_t r2, uint32_t r3) {
    asm volatile("stmatrix.sync.aligned.m8n8.x4.shared.b16 [%0], {%1,%2,%3,%4};" ::"r"(a), "r"(r0), "r"(r1), "r"(r2), "r"(r3) : "memory");
}
__device__ __forceinline__ void stsm4t(uint32_t a, uint32_t r0, uint32_t r1, uint32_t r2, uint32_t r3) {
    asm volatile("stmatrix.sync.aligned.m8n8.x4.trans.shared.b16 [%0], {%1,%2,%3,%4};" ::"r"(a), "r"(r0), "r"(r1), "r"(r2), "r"(r3) : "memory");
}
__device__ __forceinline__ void ldsm4t_if(bool p, uint32_t a, uint32_t* r) {
    asm volatile("{\n.reg .pred p;\nsetp.ne.u32 p, %5, 0;\n@p ldmatrix.sync.aligned.m8n8.x4.trans.shared.b16 {%0,%1,%2,%3}, [%4];\n}"
                 : "+r"(r[0]), "+r"(r[1]), "+r"(r[2]), "+r"(r[3]) : "r"(a), "r"((uint32_t)p) : "memory");
}
__device__ __forceinline__ void ldsm4t(uint32_t a, uint32_t& r0, uint32_t& r1, uint32_t& r2, uint32_t& r3) {
    asm volatile("ldmatrix.sync.aligned.m8n8.x4.trans.shared.b16 {%0,%1,%2,%3}, [%4];" : "=r"(r0), "=r"(r1), "=r"(r2), "=r"(r3) : "r"(a) : "memory");
}
__device__ __forceinline__ uint32_t pack2(float lo, float hi) {
    uint32_t r;
    asm("cvt.rn.bf16x2.f32 %0, %1, %2;" : "=r"(r) : "f"(hi), "f"(lo));
    return r;
}
__device__ __forceinline__ uint32_t mul2(uint32_t a, uint32_t b) { uint32_t r; asm("mul.rn.bf16x2 %0, %1, %2;" : "=r"(r) : "r"(a), "r"(b)); return r; }
__device__ __forceinline__ uint32_t fma2(uint32_t a, uint32_t b, uint32_t c) { uint32_t r; asm("fma.rn.bf16x2 %0, %1, %2, %3;" : "=r"(r) : "r"(a), "r"(b), "r"(c)); return r; }
__device__ __forceinline__ uint32_t add2(uint32_t a, uint32_t b) { uint32_t r; asm("add.rn.bf16x2 %0, %1, %2;" : "=r"(r) : "r"(a), "r"(b)); return r; }
__device__ __forceinline__ void hmma(float (&d)[4], uint32_t a0, uint32_t a1, uint32_t a2, uint32_t a3, uint32_t b0, uint32_t b1) {
    asm volatile("mma.sync.aligned.m16n8k16.row.col.f32.bf16.bf16.f32 {%0,%1,%2,%3}, {%4,%5,%6,%7}, {%8,%9}, {%0,%1,%2,%3};"
        : "+f"(d[0]), "+f"(d[1]), "+f"(d[2]), "+f"(d[3]) : "r"(a0), "r"(a1), "r"(a2), "r"(a3), "r"(b0), "r"(b1));
}
__device__ __forceinline__ float blo(uint32_t w) { return __uint_as_float(w << 16); }
__device__ __forceinline__ float bhi(uint32_t w) { return __uint_as_float(w & 0xffff0000u); }
__device__ __forceinline__ float rbf(float x) { return __bfloat162float(__float2bfloat16_rn(x)); }
__device__ __forceinline__ uint32_t ldg32(const void* p) { uint32_t v; asm volatile("ld.global.nc.b32 %0, [%1];" : "=r"(v) : "l"(p)); return v; }
__device__ __forceinline__ uint2 ldg64(const void* p) { uint2 v; asm volatile("ld.global.nc.v2.b32 {%0,%1}, [%2];" : "=r"(v.x), "=r"(v.y) : "l"(p)); return v; }
__device__ __forceinline__ uint4 ldg128(const void* p) {
    uint4 v;
    asm volatile("ld.global.nc.v4.b32 {%0,%1,%2,%3}, [%4];" : "=r"(v.x), "=r"(v.y), "=r"(v.z), "=r"(v.w) : "l"(p));
    return v;
}
__device__ __forceinline__ uint4 ldcg128(const void* p) {
    uint4 v;
    asm volatile("ld.global.cg.v4.u32 {%0,%1,%2,%3}, [%4];" : "=r"(v.x), "=r"(v.y), "=r"(v.z), "=r"(v.w) : "l"(p) : "memory");
    return v;
}
__device__ __forceinline__ float4 ldcg128f(const void* p) {
    float4 v;
    asm volatile("ld.global.cg.v4.f32 {%0,%1,%2,%3}, [%4];" : "=f"(v.x), "=f"(v.y), "=f"(v.z), "=f"(v.w) : "l"(p) : "memory");
    return v;
}
__device__ __forceinline__ float2 ldcg64f(const void* p) { float2 v; asm volatile("ld.global.cg.v2.f32 {%0,%1}, [%2];" : "=f"(v.x), "=f"(v.y) : "l"(p) : "memory"); return v; }
__device__ __forceinline__ float ldcg32f(const void* p) { float v; asm volatile("ld.global.cg.f32 %0, [%1];" : "=f"(v) : "l"(p) : "memory"); return v; }
__device__ __forceinline__ float2 ld_stat(const float2* p) {
    float2 v;
    asm volatile("{\n.reg .b64 q;\nld.relaxed.gpu.global.b64 q, [%2];\nmov.b64 {%0, %1}, q;\n}" : "=f"(v.x), "=f"(v.y) : "l"(p) : "memory");
    return v;
}
__device__ __forceinline__ uint32_t ld_cold(const unsigned* p) { uint32_t v; asm volatile("ld.relaxed.gpu.global.u32 %0, [%1];" : "=r"(v) : "l"(p) : "memory"); return v; }
__device__ __forceinline__ uint2 ld_mod(const uint2* p) {
    uint64_t v;
    asm volatile("ld.relaxed.gpu.global.b64 %0, [%1];" : "=l"(v) : "l"(p) : "memory");
    return make_uint2((uint32_t)v, (uint32_t)(v >> 32));
}
__device__ __forceinline__ float silu(float x) {
    float e, r;
    asm("ex2.approx.ftz.f32 %0, %1;" : "=f"(e) : "f"(x * -1.4426950408889634f));
    asm("rcp.approx.ftz.f32 %0, %1;" : "=f"(r) : "f"(1.f + e));
    return x * r;
}
__device__ __forceinline__ float gelu2(float h) {
    float u = h * fmaf(h * h, 8.f * 0.0356774081f, 2.f * 0.7978845608f);
    float th;
    asm("tanh.approx.f32 %0, %1;" : "=f"(th) : "f"(u));
    return fmaf(h, th, h);
}
__device__ __forceinline__ float gelu2r(float a, float2 k) {
    float th;
    asm("tanh.approx.f32 %0, %1;" : "=f"(th) : "f"(a * fmaf(a * a, k.x, k.y)));
    return fmaf(a, th, a);
}

__device__ __forceinline__ void conv_channel(float (&d)[64], uint32_t pa, uint64_t db) {
    asm volatile("{\n.reg .b32 a0, a1, a2, a3, b0, b1, b2, b3, t0, t1;\n.reg .b64 d;\nld.shared.b32 a0, [%64];\nld.shared.b32 a1, [%64+128];\nld.shared.b32 a2, [%64+-128];\nmov.b32 a3, a0;\n"
        "ld.shared.b32 t0, [%64+256];\nld.shared.b32 t1, [%64+384];\nadd.s64 d, %65, 0;\nwgmma.fence.sync.aligned;\nwgmma.mma_async.sync.aligned.m64n128k16.f32.bf16.bf16 {%0, %1, %2, %3, %4, %5, %6, %7, %8, %9, %10, %11, %12, %13, %14, %15, %16, %17, %18, %19, %20, %21, %22, %23, %24, %25, %26, %27, %28, %29, %30, %31, %32, %33, %34, %35, %36, %37, %38, %39, %40, %41, %42, %43, %44, %45, %46, %47, %48, %49, %50, %51, %52, %53, %54, %55, %56, %57, %58, %59, %60, %61, %62, %63}, {a0, a1, a2, a3}, d, 0, 1, 1, 0;\nwgmma.commit_group.sync.aligned;\nwgmma.wait_group.sync.aligned 1;\nmov.b32 b2, a1;\nmov.b32 b0, t0;\nmov.b32 b3, t0;\nmov.b32 b1, t1;\n"
        "ld.shared.b32 t0, [%64+512];\nld.shared.b32 t1, [%64+640];\nadd.s64 d, %65, 8;\nwgmma.fence.sync.aligned;\nwgmma.mma_async.sync.aligned.m64n128k16.f32.bf16.bf16 {%0, %1, %2, %3, %4, %5, %6, %7, %8, %9, %10, %11, %12, %13, %14, %15, %16, %17, %18, %19, %20, %21, %22, %23, %24, %25, %26, %27, %28, %29, %30, %31, %32, %33, %34, %35, %36, %37, %38, %39, %40, %41, %42, %43, %44, %45, %46, %47, %48, %49, %50, %51, %52, %53, %54, %55, %56, %57, %58, %59, %60, %61, %62, %63}, {b0, b1, b2, b3}, d, 1, 1, 1, 0;\nwgmma.commit_group.sync.aligned;\nwgmma.wait_group.sync.aligned 1;\nmov.b32 a2, b1;\nmov.b32 a0, t0;\nmov.b32 a3, t0;\nmov.b32 a1, t1;\n"
        "ld.shared.b32 t0, [%64+768];\nld.shared.b32 t1, [%64+896];\nadd.s64 d, %65, 16;\nwgmma.fence.sync.aligned;\nwgmma.mma_async.sync.aligned.m64n128k16.f32.bf16.bf16 {%0, %1, %2, %3, %4, %5, %6, %7, %8, %9, %10, %11, %12, %13, %14, %15, %16, %17, %18, %19, %20, %21, %22, %23, %24, %25, %26, %27, %28, %29, %30, %31, %32, %33, %34, %35, %36, %37, %38, %39, %40, %41, %42, %43, %44, %45, %46, %47, %48, %49, %50, %51, %52, %53, %54, %55, %56, %57, %58, %59, %60, %61, %62, %63}, {a0, a1, a2, a3}, d, 1, 1, 1, 0;\nwgmma.commit_group.sync.aligned;\nwgmma.wait_group.sync.aligned 1;\nmov.b32 b2, a1;\nmov.b32 b0, t0;\nmov.b32 b3, t0;\nmov.b32 b1, t1;\n"
        "ld.shared.b32 t0, [%64+1024];\nld.shared.b32 t1, [%64+1152];\nadd.s64 d, %65, 24;\nwgmma.fence.sync.aligned;\nwgmma.mma_async.sync.aligned.m64n128k16.f32.bf16.bf16 {%0, %1, %2, %3, %4, %5, %6, %7, %8, %9, %10, %11, %12, %13, %14, %15, %16, %17, %18, %19, %20, %21, %22, %23, %24, %25, %26, %27, %28, %29, %30, %31, %32, %33, %34, %35, %36, %37, %38, %39, %40, %41, %42, %43, %44, %45, %46, %47, %48, %49, %50, %51, %52, %53, %54, %55, %56, %57, %58, %59, %60, %61, %62, %63}, {b0, b1, b2, b3}, d, 1, 1, 1, 0;\nwgmma.commit_group.sync.aligned;\nwgmma.wait_group.sync.aligned 1;\nmov.b32 a2, b1;\nmov.b32 a0, t0;\nmov.b32 a3, t0;\nmov.b32 a1, t1;\n"
        "ld.shared.b32 t0, [%64+1280];\nld.shared.b32 t1, [%64+1408];\nadd.s64 d, %65, 32;\nwgmma.fence.sync.aligned;\nwgmma.mma_async.sync.aligned.m64n128k16.f32.bf16.bf16 {%0, %1, %2, %3, %4, %5, %6, %7, %8, %9, %10, %11, %12, %13, %14, %15, %16, %17, %18, %19, %20, %21, %22, %23, %24, %25, %26, %27, %28, %29, %30, %31, %32, %33, %34, %35, %36, %37, %38, %39, %40, %41, %42, %43, %44, %45, %46, %47, %48, %49, %50, %51, %52, %53, %54, %55, %56, %57, %58, %59, %60, %61, %62, %63}, {a0, a1, a2, a3}, d, 1, 1, 1, 0;\nwgmma.commit_group.sync.aligned;\nwgmma.wait_group.sync.aligned 1;\nmov.b32 b2, a1;\nmov.b32 b0, t0;\nmov.b32 b3, t0;\nmov.b32 b1, t1;\n"
        "ld.shared.b32 t0, [%64+1536];\nld.shared.b32 t1, [%64+1664];\nadd.s64 d, %65, 40;\nwgmma.fence.sync.aligned;\nwgmma.mma_async.sync.aligned.m64n128k16.f32.bf16.bf16 {%0, %1, %2, %3, %4, %5, %6, %7, %8, %9, %10, %11, %12, %13, %14, %15, %16, %17, %18, %19, %20, %21, %22, %23, %24, %25, %26, %27, %28, %29, %30, %31, %32, %33, %34, %35, %36, %37, %38, %39, %40, %41, %42, %43, %44, %45, %46, %47, %48, %49, %50, %51, %52, %53, %54, %55, %56, %57, %58, %59, %60, %61, %62, %63}, {b0, b1, b2, b3}, d, 1, 1, 1, 0;\nwgmma.commit_group.sync.aligned;\nwgmma.wait_group.sync.aligned 1;\nmov.b32 a2, b1;\nmov.b32 a0, t0;\nmov.b32 a3, t0;\nmov.b32 a1, t1;\n"
        "ld.shared.b32 t0, [%64+1792];\nld.shared.b32 t1, [%64+1920];\nadd.s64 d, %65, 48;\nwgmma.fence.sync.aligned;\nwgmma.mma_async.sync.aligned.m64n128k16.f32.bf16.bf16 {%0, %1, %2, %3, %4, %5, %6, %7, %8, %9, %10, %11, %12, %13, %14, %15, %16, %17, %18, %19, %20, %21, %22, %23, %24, %25, %26, %27, %28, %29, %30, %31, %32, %33, %34, %35, %36, %37, %38, %39, %40, %41, %42, %43, %44, %45, %46, %47, %48, %49, %50, %51, %52, %53, %54, %55, %56, %57, %58, %59, %60, %61, %62, %63}, {a0, a1, a2, a3}, d, 1, 1, 1, 0;\nwgmma.commit_group.sync.aligned;\nwgmma.wait_group.sync.aligned 1;\nmov.b32 b2, a1;\nmov.b32 b0, t0;\nmov.b32 b3, t0;\nmov.b32 b1, t1;\n"
        "ld.shared.b32 t0, [%64+2048];\nld.shared.b32 t1, [%64+2176];\nadd.s64 d, %65, 56;\nwgmma.fence.sync.aligned;\nwgmma.mma_async.sync.aligned.m64n128k16.f32.bf16.bf16 {%0, %1, %2, %3, %4, %5, %6, %7, %8, %9, %10, %11, %12, %13, %14, %15, %16, %17, %18, %19, %20, %21, %22, %23, %24, %25, %26, %27, %28, %29, %30, %31, %32, %33, %34, %35, %36, %37, %38, %39, %40, %41, %42, %43, %44, %45, %46, %47, %48, %49, %50, %51, %52, %53, %54, %55, %56, %57, %58, %59, %60, %61, %62, %63}, {b0, b1, b2, b3}, d, 1, 1, 1, 0;\nwgmma.commit_group.sync.aligned;\nwgmma.wait_group.sync.aligned 1;\nmov.b32 a2, b1;\nmov.b32 a0, t0;\nmov.b32 a3, t0;\nmov.b32 a1, t1;\n"
        "ld.shared.b32 t0, [%64+2304];\nld.shared.b32 t1, [%64+2432];\nadd.s64 d, %65, 64;\nwgmma.fence.sync.aligned;\nwgmma.mma_async.sync.aligned.m64n96k16.f32.bf16.bf16 {%0, %1, %2, %3, %4, %5, %6, %7, %8, %9, %10, %11, %12, %13, %14, %15, %16, %17, %18, %19, %20, %21, %22, %23, %24, %25, %26, %27, %28, %29, %30, %31, %32, %33, %34, %35, %36, %37, %38, %39, %40, %41, %42, %43, %44, %45, %46, %47}, {a0, a1, a2, a3}, d, 1, 1, 1, 0;\nwgmma.commit_group.sync.aligned;\nwgmma.wait_group.sync.aligned 1;\nmov.b32 b2, a1;\nmov.b32 b0, t0;\nmov.b32 b3, t0;\nmov.b32 b1, t1;\n"
        "ld.shared.b32 t0, [%64+2560];\nld.shared.b32 t1, [%64+2688];\nadd.s64 d, %65, 72;\nwgmma.fence.sync.aligned;\nwgmma.mma_async.sync.aligned.m64n96k16.f32.bf16.bf16 {%0, %1, %2, %3, %4, %5, %6, %7, %8, %9, %10, %11, %12, %13, %14, %15, %16, %17, %18, %19, %20, %21, %22, %23, %24, %25, %26, %27, %28, %29, %30, %31, %32, %33, %34, %35, %36, %37, %38, %39, %40, %41, %42, %43, %44, %45, %46, %47}, {b0, b1, b2, b3}, d, 1, 1, 1, 0;\nwgmma.commit_group.sync.aligned;\nwgmma.wait_group.sync.aligned 1;\nmov.b32 a2, b1;\nmov.b32 a0, t0;\nmov.b32 a3, t0;\nmov.b32 a1, t1;\n"
        "ld.shared.b32 t0, [%64+2816];\nld.shared.b32 t1, [%64+2944];\nadd.s64 d, %65, 80;\nwgmma.fence.sync.aligned;\nwgmma.mma_async.sync.aligned.m64n88k16.f32.bf16.bf16 {%0, %1, %2, %3, %4, %5, %6, %7, %8, %9, %10, %11, %12, %13, %14, %15, %16, %17, %18, %19, %20, %21, %22, %23, %24, %25, %26, %27, %28, %29, %30, %31, %32, %33, %34, %35, %36, %37, %38, %39, %40, %41, %42, %43}, {a0, a1, a2, a3}, d, 1, 1, 1, 0;\nwgmma.commit_group.sync.aligned;\nwgmma.wait_group.sync.aligned 1;\nmov.b32 b2, a1;\nmov.b32 b0, t0;\nmov.b32 b3, t0;\nmov.b32 b1, t1;\n"
        "ld.shared.b32 t0, [%64+3072];\nld.shared.b32 t1, [%64+3200];\nadd.s64 d, %65, 88;\nwgmma.fence.sync.aligned;\nwgmma.mma_async.sync.aligned.m64n88k16.f32.bf16.bf16 {%0, %1, %2, %3, %4, %5, %6, %7, %8, %9, %10, %11, %12, %13, %14, %15, %16, %17, %18, %19, %20, %21, %22, %23, %24, %25, %26, %27, %28, %29, %30, %31, %32, %33, %34, %35, %36, %37, %38, %39, %40, %41, %42, %43}, {b0, b1, b2, b3}, d, 1, 1, 1, 0;\nwgmma.commit_group.sync.aligned;\nwgmma.wait_group.sync.aligned 1;\nmov.b32 a2, b1;\nmov.b32 a0, t0;\nmov.b32 a3, t0;\nmov.b32 a1, t1;\n"
        "ld.shared.b32 t0, [%64+3328];\nld.shared.b32 t1, [%64+3456];\nadd.s64 d, %65, 96;\nwgmma.fence.sync.aligned;\nwgmma.mma_async.sync.aligned.m64n80k16.f32.bf16.bf16 {%0, %1, %2, %3, %4, %5, %6, %7, %8, %9, %10, %11, %12, %13, %14, %15, %16, %17, %18, %19, %20, %21, %22, %23, %24, %25, %26, %27, %28, %29, %30, %31, %32, %33, %34, %35, %36, %37, %38, %39}, {a0, a1, a2, a3}, d, 1, 1, 1, 0;\nwgmma.commit_group.sync.aligned;\nwgmma.wait_group.sync.aligned 1;\nmov.b32 b2, a1;\nmov.b32 b0, t0;\nmov.b32 b3, t0;\nmov.b32 b1, t1;\n"
        "ld.shared.b32 t0, [%64+3584];\nld.shared.b32 t1, [%64+3712];\nadd.s64 d, %65, 104;\nwgmma.fence.sync.aligned;\nwgmma.mma_async.sync.aligned.m64n80k16.f32.bf16.bf16 {%0, %1, %2, %3, %4, %5, %6, %7, %8, %9, %10, %11, %12, %13, %14, %15, %16, %17, %18, %19, %20, %21, %22, %23, %24, %25, %26, %27, %28, %29, %30, %31, %32, %33, %34, %35, %36, %37, %38, %39}, {b0, b1, b2, b3}, d, 1, 1, 1, 0;\nwgmma.commit_group.sync.aligned;\nwgmma.wait_group.sync.aligned 1;\nmov.b32 a2, b1;\nmov.b32 a0, t0;\nmov.b32 a3, t0;\nmov.b32 a1, t1;\n"
        "ld.shared.b32 t0, [%64+3840];\nld.shared.b32 t1, [%64+3968];\nadd.s64 d, %65, 112;\nwgmma.fence.sync.aligned;\nwgmma.mma_async.sync.aligned.m64n72k16.f32.bf16.bf16 {%0, %1, %2, %3, %4, %5, %6, %7, %8, %9, %10, %11, %12, %13, %14, %15, %16, %17, %18, %19, %20, %21, %22, %23, %24, %25, %26, %27, %28, %29, %30, %31, %32, %33, %34, %35}, {a0, a1, a2, a3}, d, 1, 1, 1, 0;\nwgmma.commit_group.sync.aligned;\nwgmma.wait_group.sync.aligned 1;\nmov.b32 b2, a1;\nmov.b32 b0, t0;\nmov.b32 b3, t0;\nmov.b32 b1, t1;\n"
        "ld.shared.b32 t0, [%64+4096];\nld.shared.b32 t1, [%64+4224];\nadd.s64 d, %65, 120;\nwgmma.fence.sync.aligned;\nwgmma.mma_async.sync.aligned.m64n72k16.f32.bf16.bf16 {%0, %1, %2, %3, %4, %5, %6, %7, %8, %9, %10, %11, %12, %13, %14, %15, %16, %17, %18, %19, %20, %21, %22, %23, %24, %25, %26, %27, %28, %29, %30, %31, %32, %33, %34, %35}, {b0, b1, b2, b3}, d, 1, 1, 1, 0;\nwgmma.commit_group.sync.aligned;\nwgmma.wait_group.sync.aligned 1;\nmov.b32 a2, b1;\nmov.b32 a0, t0;\nmov.b32 a3, t0;\nmov.b32 a1, t1;\n"
        "ld.shared.b32 t0, [%64+4352];\nld.shared.b32 t1, [%64+4480];\nadd.s64 d, %65, 128;\nwgmma.fence.sync.aligned;\nwgmma.mma_async.sync.aligned.m64n64k16.f32.bf16.bf16 {%0, %1, %2, %3, %4, %5, %6, %7, %8, %9, %10, %11, %12, %13, %14, %15, %16, %17, %18, %19, %20, %21, %22, %23, %24, %25, %26, %27, %28, %29, %30, %31}, {a0, a1, a2, a3}, d, 1, 1, 1, 0;\nwgmma.commit_group.sync.aligned;\nwgmma.wait_group.sync.aligned 1;\nmov.b32 b2, a1;\nmov.b32 b0, t0;\nmov.b32 b3, t0;\nmov.b32 b1, t1;\n"
        "ld.shared.b32 t0, [%64+4608];\nld.shared.b32 t1, [%64+4736];\nadd.s64 d, %65, 136;\nwgmma.fence.sync.aligned;\nwgmma.mma_async.sync.aligned.m64n64k16.f32.bf16.bf16 {%0, %1, %2, %3, %4, %5, %6, %7, %8, %9, %10, %11, %12, %13, %14, %15, %16, %17, %18, %19, %20, %21, %22, %23, %24, %25, %26, %27, %28, %29, %30, %31}, {b0, b1, b2, b3}, d, 1, 1, 1, 0;\nwgmma.commit_group.sync.aligned;\nwgmma.wait_group.sync.aligned 1;\nmov.b32 a2, b1;\nmov.b32 a0, t0;\nmov.b32 a3, t0;\nmov.b32 a1, t1;\n"
        "ld.shared.b32 t0, [%64+4864];\nld.shared.b32 t1, [%64+4992];\nadd.s64 d, %65, 144;\nwgmma.fence.sync.aligned;\nwgmma.mma_async.sync.aligned.m64n56k16.f32.bf16.bf16 {%0, %1, %2, %3, %4, %5, %6, %7, %8, %9, %10, %11, %12, %13, %14, %15, %16, %17, %18, %19, %20, %21, %22, %23, %24, %25, %26, %27}, {a0, a1, a2, a3}, d, 1, 1, 1, 0;\nwgmma.commit_group.sync.aligned;\nwgmma.wait_group.sync.aligned 1;\nmov.b32 b2, a1;\nmov.b32 b0, t0;\nmov.b32 b3, t0;\nmov.b32 b1, t1;\n"
        "ld.shared.b32 t0, [%64+5120];\nld.shared.b32 t1, [%64+5248];\nadd.s64 d, %65, 152;\nwgmma.fence.sync.aligned;\nwgmma.mma_async.sync.aligned.m64n56k16.f32.bf16.bf16 {%0, %1, %2, %3, %4, %5, %6, %7, %8, %9, %10, %11, %12, %13, %14, %15, %16, %17, %18, %19, %20, %21, %22, %23, %24, %25, %26, %27}, {b0, b1, b2, b3}, d, 1, 1, 1, 0;\nwgmma.commit_group.sync.aligned;\nwgmma.wait_group.sync.aligned 1;\nmov.b32 a2, b1;\nmov.b32 a0, t0;\nmov.b32 a3, t0;\nmov.b32 a1, t1;\n"
        "ld.shared.b32 t0, [%64+5376];\nld.shared.b32 t1, [%64+5504];\nadd.s64 d, %65, 160;\nwgmma.fence.sync.aligned;\nwgmma.mma_async.sync.aligned.m64n48k16.f32.bf16.bf16 {%0, %1, %2, %3, %4, %5, %6, %7, %8, %9, %10, %11, %12, %13, %14, %15, %16, %17, %18, %19, %20, %21, %22, %23}, {a0, a1, a2, a3}, d, 1, 1, 1, 0;\nwgmma.commit_group.sync.aligned;\nwgmma.wait_group.sync.aligned 1;\nmov.b32 b2, a1;\nmov.b32 b0, t0;\nmov.b32 b3, t0;\nmov.b32 b1, t1;\n"
        "ld.shared.b32 t0, [%64+5632];\nld.shared.b32 t1, [%64+5760];\nadd.s64 d, %65, 168;\nwgmma.fence.sync.aligned;\nwgmma.mma_async.sync.aligned.m64n48k16.f32.bf16.bf16 {%0, %1, %2, %3, %4, %5, %6, %7, %8, %9, %10, %11, %12, %13, %14, %15, %16, %17, %18, %19, %20, %21, %22, %23}, {b0, b1, b2, b3}, d, 1, 1, 1, 0;\nwgmma.commit_group.sync.aligned;\nwgmma.wait_group.sync.aligned 1;\nmov.b32 a2, b1;\nmov.b32 a0, t0;\nmov.b32 a3, t0;\nmov.b32 a1, t1;\n"
        "ld.shared.b32 t0, [%64+5888];\nld.shared.b32 t1, [%64+6016];\nadd.s64 d, %65, 176;\nwgmma.fence.sync.aligned;\nwgmma.mma_async.sync.aligned.m64n40k16.f32.bf16.bf16 {%0, %1, %2, %3, %4, %5, %6, %7, %8, %9, %10, %11, %12, %13, %14, %15, %16, %17, %18, %19}, {a0, a1, a2, a3}, d, 1, 1, 1, 0;\nwgmma.commit_group.sync.aligned;\nwgmma.wait_group.sync.aligned 1;\nmov.b32 b2, a1;\nmov.b32 b0, t0;\nmov.b32 b3, t0;\nmov.b32 b1, t1;\n"
        "ld.shared.b32 t0, [%64+6144];\nld.shared.b32 t1, [%64+6272];\nadd.s64 d, %65, 184;\nwgmma.fence.sync.aligned;\nwgmma.mma_async.sync.aligned.m64n40k16.f32.bf16.bf16 {%0, %1, %2, %3, %4, %5, %6, %7, %8, %9, %10, %11, %12, %13, %14, %15, %16, %17, %18, %19}, {b0, b1, b2, b3}, d, 1, 1, 1, 0;\nwgmma.commit_group.sync.aligned;\nwgmma.wait_group.sync.aligned 1;\nmov.b32 a2, b1;\nmov.b32 a0, t0;\nmov.b32 a3, t0;\nmov.b32 a1, t1;\n"
        "ld.shared.b32 t0, [%64+6400];\nld.shared.b32 t1, [%64+6528];\nadd.s64 d, %65, 192;\nwgmma.fence.sync.aligned;\nwgmma.mma_async.sync.aligned.m64n32k16.f32.bf16.bf16 {%0, %1, %2, %3, %4, %5, %6, %7, %8, %9, %10, %11, %12, %13, %14, %15}, {a0, a1, a2, a3}, d, 1, 1, 1, 0;\nwgmma.commit_group.sync.aligned;\nwgmma.wait_group.sync.aligned 1;\nmov.b32 b2, a1;\nmov.b32 b0, t0;\nmov.b32 b3, t0;\nmov.b32 b1, t1;\n"
        "ld.shared.b32 t0, [%64+6656];\nld.shared.b32 t1, [%64+6784];\nadd.s64 d, %65, 200;\nwgmma.fence.sync.aligned;\nwgmma.mma_async.sync.aligned.m64n32k16.f32.bf16.bf16 {%0, %1, %2, %3, %4, %5, %6, %7, %8, %9, %10, %11, %12, %13, %14, %15}, {b0, b1, b2, b3}, d, 1, 1, 1, 0;\nwgmma.commit_group.sync.aligned;\nwgmma.wait_group.sync.aligned 1;\nmov.b32 a2, b1;\nmov.b32 a0, t0;\nmov.b32 a3, t0;\nmov.b32 a1, t1;\n"
        "ld.shared.b32 t0, [%64+6912];\nld.shared.b32 t1, [%64+7040];\nadd.s64 d, %65, 208;\nwgmma.fence.sync.aligned;\nwgmma.mma_async.sync.aligned.m64n24k16.f32.bf16.bf16 {%0, %1, %2, %3, %4, %5, %6, %7, %8, %9, %10, %11}, {a0, a1, a2, a3}, d, 1, 1, 1, 0;\nwgmma.commit_group.sync.aligned;\nwgmma.wait_group.sync.aligned 1;\nmov.b32 b2, a1;\nmov.b32 b0, t0;\nmov.b32 b3, t0;\nmov.b32 b1, t1;\n"
        "ld.shared.b32 t0, [%64+7168];\nld.shared.b32 t1, [%64+7296];\nadd.s64 d, %65, 216;\nwgmma.fence.sync.aligned;\nwgmma.mma_async.sync.aligned.m64n24k16.f32.bf16.bf16 {%0, %1, %2, %3, %4, %5, %6, %7, %8, %9, %10, %11}, {b0, b1, b2, b3}, d, 1, 1, 1, 0;\nwgmma.commit_group.sync.aligned;\nwgmma.wait_group.sync.aligned 1;\nmov.b32 a2, b1;\nmov.b32 a0, t0;\nmov.b32 a3, t0;\nmov.b32 a1, t1;\n"
        "ld.shared.b32 t0, [%64+7424];\nld.shared.b32 t1, [%64+7552];\nadd.s64 d, %65, 224;\nwgmma.fence.sync.aligned;\nwgmma.mma_async.sync.aligned.m64n16k16.f32.bf16.bf16 {%0, %1, %2, %3, %4, %5, %6, %7}, {a0, a1, a2, a3}, d, 1, 1, 1, 0;\nwgmma.commit_group.sync.aligned;\nwgmma.wait_group.sync.aligned 1;\nmov.b32 b2, a1;\nmov.b32 b0, t0;\nmov.b32 b3, t0;\nmov.b32 b1, t1;\n"
        "ld.shared.b32 t0, [%64+7680];\nld.shared.b32 t1, [%64+7808];\nadd.s64 d, %65, 232;\nwgmma.fence.sync.aligned;\nwgmma.mma_async.sync.aligned.m64n16k16.f32.bf16.bf16 {%0, %1, %2, %3, %4, %5, %6, %7}, {b0, b1, b2, b3}, d, 1, 1, 1, 0;\nwgmma.commit_group.sync.aligned;\nwgmma.wait_group.sync.aligned 1;\nmov.b32 a2, b1;\nmov.b32 a0, t0;\nmov.b32 a3, t0;\nmov.b32 a1, t1;\n"
        "ld.shared.b32 t0, [%64+7936];\nld.shared.b32 t1, [%64+8064];\nadd.s64 d, %65, 240;\nwgmma.fence.sync.aligned;\nwgmma.mma_async.sync.aligned.m64n8k16.f32.bf16.bf16 {%0, %1, %2, %3}, {a0, a1, a2, a3}, d, 1, 1, 1, 0;\nwgmma.commit_group.sync.aligned;\nwgmma.wait_group.sync.aligned 1;\nmov.b32 b2, a1;\nmov.b32 b0, t0;\nmov.b32 b3, t0;\nmov.b32 b1, t1;\n"
        "add.s64 d, %65, 248;\nwgmma.fence.sync.aligned;\nwgmma.mma_async.sync.aligned.m64n8k16.f32.bf16.bf16 {%0, %1, %2, %3}, {b0, b1, b2, b3}, d, 1, 1, 1, 0;\nwgmma.commit_group.sync.aligned;\nwgmma.wait_group.sync.aligned 0;\n"
        "}" : "+f"(d[0]), "+f"(d[1]), "+f"(d[2]), "+f"(d[3]), "+f"(d[4]), "+f"(d[5]), "+f"(d[6]), "+f"(d[7]), "+f"(d[8]), "+f"(d[9]), "+f"(d[10]), "+f"(d[11]), "+f"(d[12]), "+f"(d[13]), "+f"(d[14]), "+f"(d[15]), "+f"(d[16]), "+f"(d[17]), "+f"(d[18]), "+f"(d[19]), "+f"(d[20]), "+f"(d[21]), "+f"(d[22]), "+f"(d[23]), "+f"(d[24]), "+f"(d[25]), "+f"(d[26]), "+f"(d[27]), "+f"(d[28]), "+f"(d[29]), "+f"(d[30]), "+f"(d[31]), "+f"(d[32]), "+f"(d[33]), "+f"(d[34]), "+f"(d[35]), "+f"(d[36]), "+f"(d[37]), "+f"(d[38]), "+f"(d[39]), "+f"(d[40]), "+f"(d[41]), "+f"(d[42]), "+f"(d[43]), "+f"(d[44]), "+f"(d[45]), "+f"(d[46]), "+f"(d[47]), "+f"(d[48]), "+f"(d[49]), "+f"(d[50]), "+f"(d[51]), "+f"(d[52]), "+f"(d[53]), "+f"(d[54]), "+f"(d[55]), "+f"(d[56]), "+f"(d[57]), "+f"(d[58]), "+f"(d[59]), "+f"(d[60]), "+f"(d[61]), "+f"(d[62]), "+f"(d[63]) : "r"(pa), "l"(db) : "memory");
}
__device__ __forceinline__ void wgmma_rs80(float (&d)[40], uint32_t a0, uint32_t a1, uint32_t a2, uint32_t a3, uint64_t db, int sc) {
    asm volatile("{\n.reg .pred p;\nsetp.ne.b32 p, %45, 0;\n"
        "wgmma.mma_async.sync.aligned.m64n80k16.f32.bf16.bf16 {%0, %1, %2, %3, %4, %5, %6, %7, %8, %9, %10, %11, %12, %13, %14, %15, %16, %17, %18, %19, %20, %21, %22, %23, %24, %25, %26, %27, %28, %29, %30, %31, %32, %33, %34, %35, %36, %37, %38, %39}, {%40, %41, %42, %43}, %44, p, 1, 1, 1;\n}\n"
        : "+f"(d[0]), "+f"(d[1]), "+f"(d[2]), "+f"(d[3]), "+f"(d[4]), "+f"(d[5]), "+f"(d[6]), "+f"(d[7]), "+f"(d[8]), "+f"(d[9]), "+f"(d[10]), "+f"(d[11]), "+f"(d[12]), "+f"(d[13]), "+f"(d[14]), "+f"(d[15]), "+f"(d[16]), "+f"(d[17]), "+f"(d[18]), "+f"(d[19]), "+f"(d[20]), "+f"(d[21]), "+f"(d[22]), "+f"(d[23]), "+f"(d[24]), "+f"(d[25]), "+f"(d[26]), "+f"(d[27]), "+f"(d[28]), "+f"(d[29]), "+f"(d[30]), "+f"(d[31]), "+f"(d[32]), "+f"(d[33]), "+f"(d[34]), "+f"(d[35]), "+f"(d[36]), "+f"(d[37]), "+f"(d[38]), "+f"(d[39]) : "r"(a0), "r"(a1), "r"(a2), "r"(a3), "l"(db), "r"(sc));
}
__device__ __forceinline__ void wgmma_ss80(float (&d)[40], uint64_t da, uint64_t db, int sc) {
    asm volatile("{\n.reg .pred p;\nsetp.ne.b32 p, %42, 0;\n"
        "wgmma.mma_async.sync.aligned.m64n80k16.f32.bf16.bf16 {%0, %1, %2, %3, %4, %5, %6, %7, %8, %9, %10, %11, %12, %13, %14, %15, %16, %17, %18, %19, %20, %21, %22, %23, %24, %25, %26, %27, %28, %29, %30, %31, %32, %33, %34, %35, %36, %37, %38, %39}, %40, %41, p, 1, 1, 0, 1;\n}\n"
        : "+f"(d[0]), "+f"(d[1]), "+f"(d[2]), "+f"(d[3]), "+f"(d[4]), "+f"(d[5]), "+f"(d[6]), "+f"(d[7]), "+f"(d[8]), "+f"(d[9]), "+f"(d[10]), "+f"(d[11]), "+f"(d[12]), "+f"(d[13]), "+f"(d[14]), "+f"(d[15]), "+f"(d[16]), "+f"(d[17]), "+f"(d[18]), "+f"(d[19]), "+f"(d[20]), "+f"(d[21]), "+f"(d[22]), "+f"(d[23]), "+f"(d[24]), "+f"(d[25]), "+f"(d[26]), "+f"(d[27]), "+f"(d[28]), "+f"(d[29]), "+f"(d[30]), "+f"(d[31]), "+f"(d[32]), "+f"(d[33]), "+f"(d[34]), "+f"(d[35]), "+f"(d[36]), "+f"(d[37]), "+f"(d[38]), "+f"(d[39]) : "l"(da), "l"(db), "r"(sc));
}
__device__ __forceinline__ void wgmma_ss80t(float (&d)[40], uint64_t da, uint64_t db, int sc) {
    asm volatile("{\n.reg .pred p;\nsetp.ne.b32 p, %42, 0;\n"
        "wgmma.mma_async.sync.aligned.m64n80k16.f32.bf16.bf16 {%0, %1, %2, %3, %4, %5, %6, %7, %8, %9, %10, %11, %12, %13, %14, %15, %16, %17, %18, %19, %20, %21, %22, %23, %24, %25, %26, %27, %28, %29, %30, %31, %32, %33, %34, %35, %36, %37, %38, %39}, %40, %41, p, 1, 1, 1, 1;\n}\n"
        : "+f"(d[0]), "+f"(d[1]), "+f"(d[2]), "+f"(d[3]), "+f"(d[4]), "+f"(d[5]), "+f"(d[6]), "+f"(d[7]), "+f"(d[8]), "+f"(d[9]), "+f"(d[10]), "+f"(d[11]), "+f"(d[12]), "+f"(d[13]), "+f"(d[14]), "+f"(d[15]), "+f"(d[16]), "+f"(d[17]), "+f"(d[18]), "+f"(d[19]), "+f"(d[20]), "+f"(d[21]), "+f"(d[22]), "+f"(d[23]), "+f"(d[24]), "+f"(d[25]), "+f"(d[26]), "+f"(d[27]), "+f"(d[28]), "+f"(d[29]), "+f"(d[30]), "+f"(d[31]), "+f"(d[32]), "+f"(d[33]), "+f"(d[34]), "+f"(d[35]), "+f"(d[36]), "+f"(d[37]), "+f"(d[38]), "+f"(d[39]) : "l"(da), "l"(db), "r"(sc));
}
__device__ __forceinline__ void wgmma_ss8_ta(float (&d)[4], uint64_t da, uint64_t db, int sc) {
    asm volatile("{\n.reg .pred p;\nsetp.ne.b32 p, %6, 0;\n"
        "wgmma.mma_async.sync.aligned.m64n8k16.f32.bf16.bf16 {%0, %1, %2, %3}, %4, %5, p, 1, 1, 1, 0;\n}\n"
        : "+f"(d[0]), "+f"(d[1]), "+f"(d[2]), "+f"(d[3]) : "l"(da), "l"(db), "r"(sc));
}
__device__ __forceinline__ void wgmma_rs8(float (&d)[4], uint32_t a0, uint32_t a1, uint32_t a2, uint32_t a3, uint64_t db, int sc) {
    asm volatile("{\n.reg .pred p;\nsetp.ne.b32 p, %9, 0;\n"
        "wgmma.mma_async.sync.aligned.m64n8k16.f32.bf16.bf16 {%0, %1, %2, %3}, {%4, %5, %6, %7}, %8, p, 1, 1, 0;\n}\n"
        : "+f"(d[0]), "+f"(d[1]), "+f"(d[2]), "+f"(d[3]) : "r"(a0), "r"(a1), "r"(a2), "r"(a3), "l"(db), "r"(sc));
}
__device__ __forceinline__ void wgmma_rs128(float (&d)[64], uint32_t a0, uint32_t a1, uint32_t a2, uint32_t a3, uint64_t db, int sc) {
    asm volatile("{\n.reg .pred p;\nsetp.ne.b32 p, %69, 0;\n"
        "wgmma.mma_async.sync.aligned.m64n128k16.f32.bf16.bf16 {%0, %1, %2, %3, %4, %5, %6, %7, %8, %9, %10, %11, %12, %13, %14, %15, %16, %17, %18, %19, %20, %21, %22, %23, %24, %25, %26, %27, %28, %29, %30, %31, %32, %33, %34, %35, %36, %37, %38, %39, %40, %41, %42, %43, %44, %45, %46, %47, %48, %49, %50, %51, %52, %53, %54, %55, %56, %57, %58, %59, %60, %61, %62, %63}, {%64, %65, %66, %67}, %68, p, 1, 1, 1;\n}\n"
        : "+f"(d[0]), "+f"(d[1]), "+f"(d[2]), "+f"(d[3]), "+f"(d[4]), "+f"(d[5]), "+f"(d[6]), "+f"(d[7]), "+f"(d[8]), "+f"(d[9]), "+f"(d[10]), "+f"(d[11]), "+f"(d[12]), "+f"(d[13]), "+f"(d[14]), "+f"(d[15]), "+f"(d[16]), "+f"(d[17]), "+f"(d[18]), "+f"(d[19]), "+f"(d[20]), "+f"(d[21]), "+f"(d[22]), "+f"(d[23]), "+f"(d[24]), "+f"(d[25]), "+f"(d[26]), "+f"(d[27]), "+f"(d[28]), "+f"(d[29]), "+f"(d[30]), "+f"(d[31]), "+f"(d[32]), "+f"(d[33]), "+f"(d[34]), "+f"(d[35]), "+f"(d[36]), "+f"(d[37]), "+f"(d[38]), "+f"(d[39]), "+f"(d[40]), "+f"(d[41]), "+f"(d[42]), "+f"(d[43]), "+f"(d[44]), "+f"(d[45]), "+f"(d[46]), "+f"(d[47]), "+f"(d[48]), "+f"(d[49]), "+f"(d[50]), "+f"(d[51]), "+f"(d[52]), "+f"(d[53]), "+f"(d[54]), "+f"(d[55]), "+f"(d[56]), "+f"(d[57]), "+f"(d[58]), "+f"(d[59]), "+f"(d[60]), "+f"(d[61]), "+f"(d[62]), "+f"(d[63]) : "r"(a0), "r"(a1), "r"(a2), "r"(a3), "l"(db), "r"(sc));
}
__device__ __forceinline__ void wgmma_rs88(float (&d)[44], uint32_t a0, uint32_t a1, uint32_t a2, uint32_t a3, uint64_t db, int sc) {
    asm volatile("{\n.reg .pred p;\nsetp.ne.b32 p, %49, 0;\n"
        "wgmma.mma_async.sync.aligned.m64n88k16.f32.bf16.bf16 {%0, %1, %2, %3, %4, %5, %6, %7, %8, %9, %10, %11, %12, %13, %14, %15, %16, %17, %18, %19, %20, %21, %22, %23, %24, %25, %26, %27, %28, %29, %30, %31, %32, %33, %34, %35, %36, %37, %38, %39, %40, %41, %42, %43}, {%44, %45, %46, %47}, %48, p, 1, 1, 1;\n}\n"
        : "+f"(d[0]), "+f"(d[1]), "+f"(d[2]), "+f"(d[3]), "+f"(d[4]), "+f"(d[5]), "+f"(d[6]), "+f"(d[7]), "+f"(d[8]), "+f"(d[9]), "+f"(d[10]), "+f"(d[11]), "+f"(d[12]), "+f"(d[13]), "+f"(d[14]), "+f"(d[15]), "+f"(d[16]), "+f"(d[17]), "+f"(d[18]), "+f"(d[19]), "+f"(d[20]), "+f"(d[21]), "+f"(d[22]), "+f"(d[23]), "+f"(d[24]), "+f"(d[25]), "+f"(d[26]), "+f"(d[27]), "+f"(d[28]), "+f"(d[29]), "+f"(d[30]), "+f"(d[31]), "+f"(d[32]), "+f"(d[33]), "+f"(d[34]), "+f"(d[35]), "+f"(d[36]), "+f"(d[37]), "+f"(d[38]), "+f"(d[39]), "+f"(d[40]), "+f"(d[41]), "+f"(d[42]), "+f"(d[43]) : "r"(a0), "r"(a1), "r"(a2), "r"(a3), "l"(db), "r"(sc));
}
__device__ __forceinline__ void wgmma_rs128k(float (&d)[64], uint32_t a0, uint32_t a1, uint32_t a2, uint32_t a3, uint64_t db, int sc) {
    asm volatile("{\n.reg .pred p;\nsetp.ne.b32 p, %69, 0;\n"
        "wgmma.mma_async.sync.aligned.m64n128k16.f32.bf16.bf16 {%0, %1, %2, %3, %4, %5, %6, %7, %8, %9, %10, %11, %12, %13, %14, %15, %16, %17, %18, %19, %20, %21, %22, %23, %24, %25, %26, %27, %28, %29, %30, %31, %32, %33, %34, %35, %36, %37, %38, %39, %40, %41, %42, %43, %44, %45, %46, %47, %48, %49, %50, %51, %52, %53, %54, %55, %56, %57, %58, %59, %60, %61, %62, %63}, {%64, %65, %66, %67}, %68, p, 1, 1, 0;\n}\n"
        : "+f"(d[0]), "+f"(d[1]), "+f"(d[2]), "+f"(d[3]), "+f"(d[4]), "+f"(d[5]), "+f"(d[6]), "+f"(d[7]), "+f"(d[8]), "+f"(d[9]), "+f"(d[10]), "+f"(d[11]), "+f"(d[12]), "+f"(d[13]), "+f"(d[14]), "+f"(d[15]), "+f"(d[16]), "+f"(d[17]), "+f"(d[18]), "+f"(d[19]), "+f"(d[20]), "+f"(d[21]), "+f"(d[22]), "+f"(d[23]), "+f"(d[24]), "+f"(d[25]), "+f"(d[26]), "+f"(d[27]), "+f"(d[28]), "+f"(d[29]), "+f"(d[30]), "+f"(d[31]), "+f"(d[32]), "+f"(d[33]), "+f"(d[34]), "+f"(d[35]), "+f"(d[36]), "+f"(d[37]), "+f"(d[38]), "+f"(d[39]), "+f"(d[40]), "+f"(d[41]), "+f"(d[42]), "+f"(d[43]), "+f"(d[44]), "+f"(d[45]), "+f"(d[46]), "+f"(d[47]), "+f"(d[48]), "+f"(d[49]), "+f"(d[50]), "+f"(d[51]), "+f"(d[52]), "+f"(d[53]), "+f"(d[54]), "+f"(d[55]), "+f"(d[56]), "+f"(d[57]), "+f"(d[58]), "+f"(d[59]), "+f"(d[60]), "+f"(d[61]), "+f"(d[62]), "+f"(d[63]) : "r"(a0), "r"(a1), "r"(a2), "r"(a3), "l"(db), "r"(sc));
}
__device__ __forceinline__ void wgmma_rs88k(float (&d)[44], uint32_t a0, uint32_t a1, uint32_t a2, uint32_t a3, uint64_t db, int sc) {
    asm volatile("{\n.reg .pred p;\nsetp.ne.b32 p, %49, 0;\n"
        "wgmma.mma_async.sync.aligned.m64n88k16.f32.bf16.bf16 {%0, %1, %2, %3, %4, %5, %6, %7, %8, %9, %10, %11, %12, %13, %14, %15, %16, %17, %18, %19, %20, %21, %22, %23, %24, %25, %26, %27, %28, %29, %30, %31, %32, %33, %34, %35, %36, %37, %38, %39, %40, %41, %42, %43}, {%44, %45, %46, %47}, %48, p, 1, 1, 0;\n}\n"
        : "+f"(d[0]), "+f"(d[1]), "+f"(d[2]), "+f"(d[3]), "+f"(d[4]), "+f"(d[5]), "+f"(d[6]), "+f"(d[7]), "+f"(d[8]), "+f"(d[9]), "+f"(d[10]), "+f"(d[11]), "+f"(d[12]), "+f"(d[13]), "+f"(d[14]), "+f"(d[15]), "+f"(d[16]), "+f"(d[17]), "+f"(d[18]), "+f"(d[19]), "+f"(d[20]), "+f"(d[21]), "+f"(d[22]), "+f"(d[23]), "+f"(d[24]), "+f"(d[25]), "+f"(d[26]), "+f"(d[27]), "+f"(d[28]), "+f"(d[29]), "+f"(d[30]), "+f"(d[31]), "+f"(d[32]), "+f"(d[33]), "+f"(d[34]), "+f"(d[35]), "+f"(d[36]), "+f"(d[37]), "+f"(d[38]), "+f"(d[39]), "+f"(d[40]), "+f"(d[41]), "+f"(d[42]), "+f"(d[43]) : "r"(a0), "r"(a1), "r"(a2), "r"(a3), "l"(db), "r"(sc));
}
__device__ __forceinline__ void wgmma_rs80k(float (&d)[40], uint32_t a0, uint32_t a1, uint32_t a2, uint32_t a3, uint64_t db, int sc) {
    asm volatile("{\n.reg .pred p;\nsetp.ne.b32 p, %45, 0;\n"
        "wgmma.mma_async.sync.aligned.m64n80k16.f32.bf16.bf16 {%0, %1, %2, %3, %4, %5, %6, %7, %8, %9, %10, %11, %12, %13, %14, %15, %16, %17, %18, %19, %20, %21, %22, %23, %24, %25, %26, %27, %28, %29, %30, %31, %32, %33, %34, %35, %36, %37, %38, %39}, {%40, %41, %42, %43}, %44, p, 1, 1, 0;\n}\n"
        : "+f"(d[0]), "+f"(d[1]), "+f"(d[2]), "+f"(d[3]), "+f"(d[4]), "+f"(d[5]), "+f"(d[6]), "+f"(d[7]), "+f"(d[8]), "+f"(d[9]), "+f"(d[10]), "+f"(d[11]), "+f"(d[12]), "+f"(d[13]), "+f"(d[14]), "+f"(d[15]), "+f"(d[16]), "+f"(d[17]), "+f"(d[18]), "+f"(d[19]), "+f"(d[20]), "+f"(d[21]), "+f"(d[22]), "+f"(d[23]), "+f"(d[24]), "+f"(d[25]), "+f"(d[26]), "+f"(d[27]), "+f"(d[28]), "+f"(d[29]), "+f"(d[30]), "+f"(d[31]), "+f"(d[32]), "+f"(d[33]), "+f"(d[34]), "+f"(d[35]), "+f"(d[36]), "+f"(d[37]), "+f"(d[38]), "+f"(d[39]) : "r"(a0), "r"(a1), "r"(a2), "r"(a3), "l"(db), "r"(sc));
}
__device__ __forceinline__ void wgmma_rs64(float (&d)[32], uint32_t a0, uint32_t a1, uint32_t a2, uint32_t a3, uint64_t db, int sc) {
    asm volatile("{\n.reg .pred p;\nsetp.ne.b32 p, %37, 0;\n"
        "wgmma.mma_async.sync.aligned.m64n64k16.f32.bf16.bf16 {%0, %1, %2, %3, %4, %5, %6, %7, %8, %9, %10, %11, %12, %13, %14, %15, %16, %17, %18, %19, %20, %21, %22, %23, %24, %25, %26, %27, %28, %29, %30, %31}, {%32, %33, %34, %35}, %36, p, 1, 1, 1;\n}\n"
        : "+f"(d[0]), "+f"(d[1]), "+f"(d[2]), "+f"(d[3]), "+f"(d[4]), "+f"(d[5]), "+f"(d[6]), "+f"(d[7]), "+f"(d[8]), "+f"(d[9]), "+f"(d[10]), "+f"(d[11]), "+f"(d[12]), "+f"(d[13]), "+f"(d[14]), "+f"(d[15]), "+f"(d[16]), "+f"(d[17]), "+f"(d[18]), "+f"(d[19]), "+f"(d[20]), "+f"(d[21]), "+f"(d[22]), "+f"(d[23]), "+f"(d[24]), "+f"(d[25]), "+f"(d[26]), "+f"(d[27]), "+f"(d[28]), "+f"(d[29]), "+f"(d[30]), "+f"(d[31]) : "r"(a0), "r"(a1), "r"(a2), "r"(a3), "l"(db), "r"(sc));
}

__device__ __forceinline__ uint64_t mkdesc(uint32_t lo) { return ((uint64_t)0x40000040u << 32) | lo; }
template <int F> __device__ __forceinline__ uint32_t lop3(uint32_t a, uint32_t b, uint32_t c) { uint32_t r; asm("lop3.b32 %0, %1, %2, %3, %4;" : "=r"(r) : "r"(a), "r"(b), "r"(c), "n"(F)); return r; }
__device__ __forceinline__ void stg128_tag(void* p, uint32_t x, uint32_t y, uint32_t z, uint32_t u, uint32_t ep, int w) {
    stg128(p, lop3<0xB8>(x, w == 0, ep), lop3<0xB8>(y, w == 1, ep), lop3<0xB8>(z, w == 2, ep), lop3<0xB8>(u, w == 3, ep));
}
__device__ __forceinline__ uint32_t tag(uint32_t w, uint32_t ep) { asm("lop3.b32 %0, %0, 1, %1, 0xB8;" : "+r"(w) : "r"(ep)); return w; }
template <int N> __device__ __forceinline__ void pack_part(uint32_t (&p)[32], const float (&v)[N], uint32_t ep) {
#pragma unroll
    for (int i = 0; i < N / 2; i++) p[i] = (i & 3) ? pack2(v[2 * i], v[2 * i + 1]) : tag(pack2(v[2 * i], v[2 * i + 1]), ep);
#pragma unroll
    for (int i = 0; i < N / 2; i++) asm volatile("" : "+r"(p[i]));
}
__device__ __forceinline__ void st_part(uint4* p, const uint32_t* v) {
    asm volatile("{\n.reg .b64 l, h;\n.reg .b128 q;\nmov.b64 l, {%1, %2};\nmov.b64 h, {%3, %4};\nmov.b128 q, {l, h};\nst.relaxed.gpu.global.b128 [%0], q;\n}"
                 ::"l"(p), "r"(v[0]), "r"(v[1]), "r"(v[2]), "r"(v[3]) : "memory");
}
__device__ __forceinline__ void st_peer(uint32_t a, uint32_t x, uint32_t y, uint32_t z, uint32_t w, uint32_t bar) {
    asm volatile("st.async.shared::cluster.mbarrier::complete_tx::bytes.v4.b32 [%0], {%1, %2, %3, %4}, [%5];" ::"r"(a), "r"(x), "r"(y), "r"(z), "r"(w), "r"(bar) : "memory");
}
__device__ __forceinline__ int g4_block(int c, int j) { return c ? j ^ (8 - 2 * c) : 8 + (j & 1); }
__device__ __forceinline__ uint32_t recv_off(int w) { return w ? OFF_XR : OFF_REM; }
__device__ __forceinline__ uint4 ld_part(const void* p) {
    uint4 v;
    asm volatile("{\n.reg .b64 l, h;\n.reg .b128 q;\nld.relaxed.gpu.global.b128 q, [%4];\nmov.b128 {l, h}, q;\nmov.b64 {%0, %1}, l;\nmov.b64 {%2, %3}, h;\n}"
                 : "=r"(v.x), "=r"(v.y), "=r"(v.z), "=r"(v.w) : "l"(p) : "memory");
    return v;
}
__device__ __forceinline__ void ld_part4(uint4 (&u)[4], const uint4* p, int st) {
#pragma unroll
    for (int i = 0; i < 4; i++) u[i] = ld_part(p + i * st);
}
__device__ __forceinline__ uint32_t stale4(const uint4 (&u)[4], uint32_t ep) { return lop3<0x7E>(u[0].x, ep, u[1].x) | lop3<0x7E>(u[2].x, ep, u[3].x); }
__device__ __forceinline__ uint4 add2(uint4 a, uint4 b) { return make_uint4(add2(a.x, b.x), add2(a.y, b.y), add2(a.z, b.z), add2(a.w, b.w)); }
__device__ __forceinline__ uint4 fin16(uint4 v, uint4 b, uint4 c) { return make_uint4(fma2(c.x, v.x, b.x), fma2(c.y, v.y, b.y), fma2(c.z, v.z, b.z), fma2(c.w, v.w, b.w)); }
__device__ __forceinline__ uint4 scale16(float2 c, float2 d, float r0, float r1) {
    return make_uint4(pack2(c.x * r0, c.y * r0), pack2(c.x * r1, c.y * r1), pack2(d.x * r0, d.y * r0), pack2(d.x * r1, d.y * r1));
}
__device__ __forceinline__ uint32_t split2(float x) { const float h = rbf(x); return pack2(h, x - h); }
__device__ __forceinline__ uint32_t b80_desc(uint32_t dsb, uint32_t wn, uint32_t rn, uint32_t h) {
    const uint32_t wb = dsb + OFF_W + (wn & 7) * 16384 + h * 8192, rm = dsb + OFF_REM + rn * 4096 + h * 2048;
    return (wb >> 4) | ((rm - wb) << 12);
}
constexpr int64_t B80_STEP = 128 - (126 << 16), B80_HALF = 512 - (384 << 16);
constexpr uint32_t ring_mask(int L) {
    uint32_t m = 0;
    for (int i = L; i < 20; i++) m |= (uint32_t)(i >= 20 - L || !((i - L) & 1)) << i;
    return m;
}
constexpr int pair_pos(int w, int i) { return w ? (i < 5 - LEAD2 ? LEAD2 + 2 * i : 5 + i) : (i < LEAD2 ? i : 2 * i - LEAD2 + 1); }
constexpr uint32_t pair_mask() { uint32_t m = 0; for (int i = 0; i < 5; i++) m |= 3u << (2 * pair_pos(1, i)); return m; }
constexpr uint32_t pair_slots(int w) { uint32_t m = 0; for (int i = 0; i < 5; i++) m |= (uint32_t)((2 + pair_pos(w, i)) & 3) << (2 * i); return m; }
constexpr uint32_t M0 = ring_mask(LEAD1), M1 = pair_mask(), M2 = ring_mask(XLEAD), P0S = pair_slots(0), P1S = pair_slots(1);
__device__ __forceinline__ uint32_t ring_pos(int w, int n, int L) { return w ? (n < 10 - L ? L + 2 * n : 10 + n) : (n < L ? n : 2 * n - L + 1); }
__device__ __forceinline__ int g1_block(int n, int j) { return n < 5 ? 2 * n + (j & 1) : 2 * n - 9 - (j & 1); }

__device__ __forceinline__ int g3_block(int n, int j) { return n ? n - (n <= j) : j; }
__device__ __forceinline__ void load_tile(const Maps& mp, uint32_t dst, int e, int tile, int kb, int j, uint32_t bar) {
    mbar_expect(bar, 8192);
    tma_ld2(dst, &mp.x[e], 64 * (e == 0 ? tile : e == 1 ? kb : 0), 64 * (e == 0 ? g1_block(kb, j) : e == 1 ? tile : 10 * tile + g3_block(kb, j)), bar);
}

template <int OCT>
__device__ __forceinline__ void gemv_tile(float (&d)[4], uint32_t a, uint32_t b, int kb0) {
    uint32_t alo = ((a & 0x3FFFF) >> 4) | 0x10000u, blo_ = ((b & 0x3FFFF) >> 4) | (OCT << 16);
#pragma unroll 1
    for (int s = 0; s < 20; s += 4) {
        const int kb = kb0 + (s >> 2);
        const uint32_t bk = blo_ + (OCT == 7 ? (kb & 1) * 288 + (kb >> 1) * 56 : kb * 64);
        wg_fence();
#pragma unroll
        for (int q = 0; q < 4; q++) wgmma_ss8_ta(d, mkdesc(alo + (s + q) * 128), ((uint64_t)8 << 32) | (bk + q * 2 * OCT), s + q);
        wg_commit();
    }
    wg_wait<0>();
    reg_fence(d);
}

__device__ __forceinline__ void flush_tile(uint32_t st, bf16* dst, int u) {
#pragma unroll
    for (int i = 0; i < 2; i++) {
        const int idx = u + 320 * i, row = idx >> 3, c = idx & 7;
        stg128(dst + (size_t)row * S_ + 8 * c, lds128(st + row * 128 + ((c ^ ((row >> 1) & 7)) << 4)));
    }
}

__device__ __forceinline__ int tid_now() { int t; asm volatile("mov.u32 %0, %%tid.x;" : "=r"(t)); return t; }
__device__ __forceinline__ float zscale(float c) { return c == 0.f ? 0x1p-30f : c; }
__device__ __forceinline__ bool bar_any(int id, bool p) {
    uint32_t r;
    asm volatile("{\n.reg .pred a, b;\nsetp.ne.u32 a, %2, 0;\nbarrier.red.or.pred.aligned b, %1, 128, a;\nselp.u32 %0, 1, 0, b;\n}" : "=r"(r) : "r"(id), "r"((uint32_t)p) : "memory");
    return r != 0;
}

__global__ void __cluster_dims__(2, 1, 1) __launch_bounds__(NTHR, 1) fused_kernel(const __grid_constant__ Ptrs pp, bf16* __restrict__ out, const __grid_constant__ Maps mp) {
    extern __shared__ __align__(1024) uint8_t smem_raw[];
    const uint32_t sb = s2u(smem_raw), bars = sb + M_BAR, dsb = sb & 0x3FFFF;
    const int id = blockIdx.x, warp = __shfl_sync(0xffffffffu, (int)threadIdx.x >> 5, 0), wg = warp >> 2;
    const uint32_t c0 = clock_lo();
#define TIDS const int tid = tid_now(), lane = tid & 31, wt = tid & 127, g = lane >> 2, t = lane & 3; (void)wt; (void)g; (void)t;
    TS(threadIdx.x == 0, 0) TG(threadIdx.x == 0, 62)

    if (id >= 128) {
        TIDS
        if (sb & 1023) __trap();
        const int hs = id - 128;
        constexpr int H_B = 204800;
        static_assert(H_B + TAB_BYTES + 8 * VEC_BYTES <= OFF_M, "helper map");
        if (warp < 10 && elect()) { mbar_init(bars + warp * 8, 1); mbar_init(bars + 80 + warp * 8, 1); asm volatile("fence.mbarrier_init.release.cluster;" ::: "memory"); }
        __syncthreads();
        const uint32_t e0 = ld_cold(&g_epoch);
        wait_clock(c0, HELP_T);
        uint4 wr[10];
#pragma unroll
        for (int u = 0; u < 10; u++) wr[u] = ldg128(((hs >> 1) ? pp.w2 : pp.w1) + (size_t)(320 * (hs & 1) + (tid >> 4) + 32 * u) * D_ + 512 + 8 * (tid & 15));
        {
            const int r = tid >> 4, c = tid & 15;
            uint4* dst[2];
#pragma unroll
            for (int e = 0; e < 2; e++) {
                const int p = !(hs >> 1) ? r : e && (hs & 1) ? (r & ~14) | ((r & 6) << 1) | ((r & 8) >> 2) : (r & ~30) | ((r & 6) << 2) | ((r & 24) >> 2);
                dst[e] = &g_wr[(((hs >> 1) * 8 + (c >> 1)) * 10 + 5 * (hs & 1)) * 128 + (p & 15) * 8 + ((2 * (p >> 4) + (c & 1)) ^ (p & 7))];
            }
#pragma unroll
            for (int u = 0; u < 10; u++) stg128(reinterpret_cast<uint4*>(reinterpret_cast<uintptr_t>(dst[u >= 6]) ^ (64 * (u & 1))) + (u >> 1) * 128, wr[u]);
        }
        __syncthreads();
        if (warp == 0) signal_cnt(&g_cnt.wr[0], lane, 1);
        __syncthreads();
        if (warp < 5 && elect()) {
            const int un = 5 * hs + warp;
            mbar_expect(bars + warp * 8, 40960);
            tma_ld2(sb + warp * 40960, &mp.w1h, 64 * (un >> 1), 320 * (un & 1), bars + warp * 8);
            tma_ld2(sb + warp * 40960 + 20480, &mp.w1h, 64 * (un >> 1), 320 * (un & 1) + 160, bars + warp * 8);
        }
        if (tid < 320) {
            const uint4* gm = reinterpret_cast<const uint4*>(g_mod + 3 * D_) + tid;
            const unsigned epoch = e0 + 1;
            uint4 r[6];
            unsigned it = 0;
            for (;;) {
                uint32_t bad = 0;
#pragma unroll
                for (int i = 0; i < 6; i++) { r[i] = ld_part(gm + (i >> 1) * (D_ / 2) + (i & 1) * 3 * D_); bad |= (r[i].y ^ epoch) | (r[i].w ^ epoch); }
                if (__all_sync(~0u, !bad)) break;
                if (++it > SPIN_LIMIT) SPIN_FAIL(54)
            }
            uint32_t mv[3];
#pragma unroll
            for (int i = 0; i < 3; i++) mv[i] = pack2(__uint_as_float(r[2 * i].x) + __uint_as_float(r[2 * i + 1].x), __uint_as_float(r[2 * i].z) + __uint_as_float(r[2 * i + 1].z));
            const uint32_t sw2 = mv[0], cw = add2(mv[1], 0x3f803f80u), gw = mv[2];
            const float c0 = blo(cw), c1 = bhi(cw), s0 = blo(sw2), s1 = bhi(sw2);
            const float i0 = __frcp_rn(zscale(c0)), i1 = __frcp_rn(zscale(c1));
            const uint32_t ci = pack2(i0, i1), cq = pack2(i0 * i0, i1 * i1);
            const uint32_t a = sb + H_B + ((tid >> 5) & 1) * 4608 + (tid >> 6) * 896 + ((tid >> 2) & 7) * 112 + (tid & 3) * 4;
            sts32(a, ci); sts32(a + 16, pack2(i0 - blo(ci), i1 - bhi(ci)));
            sts32(a + 32, cq); sts32(a + 48, pack2(fmaf(i0, i0, -blo(cq)), fmaf(i1, i1, -bhi(cq))));
            sts32(a + 64, cw); sts32(a + 80, sw2); sts32(a + 96, 0x3f803f80u);
            if ((tid & ~35) == 284) sts32(a + 112, 0);
            const uint32_t v = sb + H_B + TAB_BYTES + (tid < 256 ? (tid >> 5) * VEC_BYTES + (tid & 31) * 8 : ((tid - 256) >> 3) * VEC_BYTES + 256 + (tid & 7) * 8);
            sts64f(v, blo(gw), bhi(gw)); sts64f(v + 320, c0, c1); sts64f(v + 640, s0, s1); sts64f(v + 960, i0, i1);
            float k[5] = {c0 + c1, s0 + s1, fmaf(c0, c0, c1 * c1), fmaf(c0, s0, c1 * s1), fmaf(s0, s0, s1 * s1)};
#pragma unroll 1
            for (int o = 16; o; o >>= 1) {
#pragma unroll
                for (int e = 0; e < 5; e++) k[e] += __shfl_xor_sync(~0u, k[e], o);
            }
            const uint32_t ks = sb + H_B + TAB_BYTES + (lane & 7) * VEC_BYTES + 1280 + (warp >> 1) * 32;
            if ((warp & 1) && lane < 8) { sts128f(ks, k[0], k[1], k[2], k[3]); sts128f(ks + 16, k[4], 0.f, 0.f, 0.f); }
            bar_sync(3, 320);
            if (!(warp & 1) && lane < 8) {
                const float4 o = lds128f(ks);
                sts128f(ks, k[0] + o.x, k[1] + o.y, k[2] + o.z, k[3] + o.w); sts32(ks + 16, __float_as_uint(k[4] + __uint_as_float(lds32(ks + 16))));
            }
            fence_async_smem();
        }
        __syncthreads();
        if (hs == 0 && warp == 15 && elect()) {
            asm volatile("cp.async.bulk.global.shared::cta.bulk_group [%0], [%1], %2;\ncp.async.bulk.commit_group;\ncp.async.bulk.wait_group 0;"
                         ::"l"(g_tab), "r"(sb + H_B), "n"(TAB_BYTES + 8 * VEC_BYTES) : "memory");
            asm volatile("red.release.gpu.global.add.u32 [%0], 1;" ::"l"(&g_cnt.tab[0]) : "memory");
        }
        __syncwarp();
#pragma unroll 1
        for (int i = wg; i < 20; i += 4) {
            const int r = i / 5, b = i - 5 * r, un = 5 * hs + b, u3 = 20 * r + un;
            auto refill = [&](int e, int u, uint32_t fb) {
                mbar_expect(fb, 40960);
                tma_ld2(sb + e * 40960, &mp.w3h, 64 * (u >> 1), 320 * (u & 1), fb);
                tma_ld2(sb + e * 40960 + 20480, &mp.w3h, 64 * (u >> 1), 320 * (u & 1) + 160, fb);
            };
            if (i > 4 && i < 9) {
                bar_sync(1, 512);
                if (warp == 0) {
                    signal_cnt(&g_cnt.uv[0], lane, 1);
                    if (elect()) {
#pragma unroll 1
                        for (int e = 0; e < 5; e++) refill(e, 5 * hs + e, bars + (5 + e) * 8);
                        l2_prefetch(pp.w2 + (size_t)160 * hs * D_, 160 * D_ * 2);
                    }
                    __syncwarp();
                }
            }
            mbar_wait(bars + i * 8, 0);
            float d[4];
            gemv_tile<7>(d, sb + b * 40960, sb + H_B, 5 * (un & 1));
            const int col = 16 * (warp & 3) + g;
            float* dst = r ? g_cs3 + (un & 1) * 1920 + 64 * ((u3 >> 1) - 10) + col : g_uv + (un & 1) * 3 * D_ + 2 * D_ + 64 * (un >> 1) + col;
            if (t == 3) { dst[0] = d[0]; dst[8] = d[2]; }
            if (r == 0 && t == 2) { dst[-2 * D_] = d[0]; dst[8 - 2 * D_] = d[2]; dst[-D_] = d[1]; dst[8 - D_] = d[3]; }
            if (r == 1 || r == 2) {
                bar_sync(4 + wg, 128);
                if (wt == 0) refill(b, u3, bars + (i + 5) * 8);
            }
        }
        __syncthreads();
        if (warp == 0) signal_cnt(&g_cnt.cs[0], lane, 1);
        if (tid == 511) l2_prefetch(pp.w4 + (size_t)432 * hs * D_, 432 * D_ * 2);
        for (uint32_t it = 0; ld_cold(&g_cnt.cs[0]) < 4;) { if (++it > SPIN_LIMIT) SPIN_FAIL(47) }
        asm volatile("fence.acquire.gpu;" ::: "memory");
        if (tid < 432) {
            const int jj = 2 * hs + (tid >= 216), c = tid % 216;
            const float* src = g_cs3 + (c < 192 ? 192 * jj + c : 1344 + 24 * jj + c);
            const uint32_t s = split2(ldcg32f(src) + ldcg32f(src + 1920));
            stg128(&g_cs3b[432 * hs + tid], s, s & 0xffffu, 0, 0);
        }
        __syncthreads();
        if (warp == 0) signal_cnt(&g_cnt.cs2[0], lane, 1);
        if (tid == 0 && hs == 3) {
            uint32_t it = 0;
            while (ld_cold(&g_epoch) == e0) { __nanosleep(256); if (++it > (1u << 20)) SPIN_FAIL(48) }
        }
        return;
    }

    if (elect()) {
        if (warp == 15) {
            mbar_init(bars + B_IN * 8, 1); mbar_init(bars + B_IN * 8 + 8, 1);
            asm volatile("fence.mbarrier_init.release.cluster;" ::: "memory");
            mbar_expect(bars + B_IN * 8, 131 * 160);
            tma_ld2(sb + OFF_KIN, &mp.k, 80 * (id & 7), 64 * (id >> 3) - 3, bars + B_IN * 8);
            tma_ld2(sb + OFF_VIN, &mp.v, 80 * (id & 7), 64 * (id >> 3), bars + B_IN * 8);
        } else if (warp < 13) {
            const uint32_t n = (0x4C11111111881ull >> (4 * warp)) & 15;
#pragma unroll
            for (int i = 0; i < 4; i++) mbar_init(bars + warp * 64 + i * 8, n);
            if (warp == 11) { mbar_init(bars + B_XFREE * 8, 16); mbar_init(bars + B_OWN * 8, 8); }
            else {
#pragma unroll
                for (int i = 4; i < 8; i++) mbar_init(bars + warp * 64 + i * 8, n);
            }
            asm volatile("fence.mbarrier_init.release.cluster;" ::: "memory");
        }
    }
    asm volatile("" ::"l"(pp.s), "l"(pp.c), "l"(out));
    TR4((threadIdx.x & 31) == 0, warp)
    const int pr = id >> 1;
    const int grp = pr < 4 ? 15 : pr < 36 ? (pr - 4) & 7 : 8 + (pr - 36) % 7;
    const int j = 2 * (pr < 4 ? pr : pr < 36 ? (pr - 4) >> 3 : (pr - 36) / 7) + (id & 1);

    if (wg == 3) {
        TIDS
        const int sw = warp - 12;
        uint32_t ep = ld_cold(&g_epoch);
        TR4(lane == 0, 20 + sw)
        __syncthreads();
        TR4(lane == 0, 30 + sw)
        asm volatile("barrier.cluster.arrive.relaxed.aligned;" ::: "memory");
        if (sw == 0) {
#pragma unroll 1
            for (int n = 0; n < 12; n++) {
                wait_clock(c0, PF_T0 + PF_DT * n);
                if (elect()) l2_prefetch(n < 4 ? (const char*)pp.q + id * 20480 + n * 5120 : (const char*)pp.w_mod + id * 38400 + (n - 4) * 4800, n < 4 ? 5120 : 4800);
            }
        } else if (sw == 1) {
            wait_clock(c0, T_SSM);
            if (elect()) {
                mbar_expect(bars + B_SSM * 8, 20480);
                bulk_ld(sb + OFF_SSM, pp.ssm_k + (size_t)5 * id * S_, 20480, bars + B_SSM * 8);
            }
            mbar_spin(bars + B_KVS * 8, 0);
            signal_cnt(&g_cnt.kv[(id & 7) * 32], lane, 1, true);
            TS(lane == 0, 2)
            mbar_spin(bars + B_RAW * 8, 0);
            if (elect()) {
                mbar_expect(bars + B_QIN * 8, 20480);
                tma_ld3(sb + OFF_QIN, &mp.q, 0, 16 * id, 0, bars + B_QIN * 8);
            }
        } else if (sw == 2) {
            if (elect()) {
#pragma unroll 1
                for (int i = 2; i < (int)(sizeof(Maps) / sizeof(CUtensorMap)); i++) asm volatile("prefetch.tensormap [%0];" ::"l"(&mp.k + i) : "memory");
#pragma unroll 1
                for (int i = B_SUMS; i < B_LAND; i++) mbar_expect(bars + i * 8, i < B_RECV ? 2048 : (i & 3) < 3 ? 8192 : 3072);
            }
            wait_cnt(&g_cnt.kv[(id >> 4) * 32], 16, true);
            TS(lane == 0, 4)
            if (elect()) {
                mbar_expect(bars + B_RAW * 8, 12288);
                mbar_expect(bars + B_RAW2 * 8, 8192);
#pragma unroll
                for (int c = 0; c < 5; c++) bulk_ld(sb + OFF_CH + c * CH_BYTES, g_kvT + (size_t)(5 * id + c) * S_, 4096, bars + (c < 3 ? B_RAW : B_RAW2) * 8);
            }
            mbar_spin(bars + B_BK * 8, 0);
            mbar_spin(bars + B_QIN * 8, 0);
            if (id < 120 && elect()) {
                mbar_expect(bars + B_WM * 8, 40960);
                tma_ld2(sb + OFF_WM, &mp.wmod, 64 * pr, 320 * (id & 1), bars + B_WM * 8);
                tma_ld2(sb + OFF_WM + 20480, &mp.wmod, 64 * pr, 320 * (id & 1) + 160, bars + B_WM * 8);
            }
            TS(lane == 0, 57)
        } else {
            wait_clock(c0, T_KVB);
            if (elect()) {
                mbar_expect(bars + (B_IN + 1) * 8, 131 * 160);
                tma_ld2(sb + OFF_KIN + 10752, &mp.k, 80 * (id & 7), 64 * (id >> 3) + 1021, bars + (B_IN + 1) * 8);
                tma_ld2(sb + OFF_VIN + 10240, &mp.v, 80 * (id & 7), 64 * (id >> 3) + 1024, bars + (B_IN + 1) * 8);
            }
            TS(lane == 0, 53)
            if (lane == 0) sts32(sb + M_EP, ep + 1);
            sts32(sb + M_NUL + lane * 4, 0);
#pragma unroll 1
            for (int i = 0; i < 10; i++) sts128(sb + OFF_Z + i * 512 + lane * 16, 0, 0, 0, 0);
            __syncwarp();
#pragma unroll 1
            for (int i = lane; i < 160; i += 32) {
                const uint32_t c = ldg32(pp.c + 320 * (id & 1) + 2 * i);
                sts32(sb + OFF_Z + (i >> 2) * 128 + (i & 3) * 4, pack2(silu(blo(c)), silu(bhi(c))));
            }
            fence_async_smem();
            for (uint32_t ph = 0, again = 1; again; ph ^= 1) {
                mbar_spin(bars + B_RAW2 * 8, ph);
                uint32_t bad = 0;
#pragma unroll
                for (int i = 0; i < 8; i++) bad |= lop3<0x7E>(lds32(sb + OFF_CH + 3 * CH_BYTES + i * 512 + lane * 16), ~ep, lds32(sb + OFF_CH + 4 * CH_BYTES + i * 512 + lane * 16));
                again = __any_sync(~0u, bad & 1);
                if (again && elect()) {
                    mbar_expect(bars + B_RAW2 * 8, 8192);
#pragma unroll
                    for (int c = 3; c < 5; c++) bulk_ld(sb + OFF_CH + c * CH_BYTES, g_kvT + (size_t)(5 * id + c) * S_, 4096, bars + B_RAW2 * 8);
                }
            }
            if (elect()) mbar_arrive(bars + B_RAW3 * 8);
        }
        {
            mbar_spin(bars + B_QIN * 8, 0);
            asm volatile("add.u32 %0, %0, 1;" : "+r"(ep));
            TS(wt == 0, 54)
            const int tk = 8 * ((lane >> 1) & 1) + 2 * (lane >> 3) + (lane & 1), ck = 4 * (sw & 1) + ((lane >> 1) & 2);
            const uint32_t src = sb + OFF_QIN + (sw >> 1) * 2048 + tk * 128;
            bf16* dst = g_qT + (size_t)id * 16 * D_ + (32 * sw + 8 * (t & 2) + g) * 16 + 8 * (t & 1);
constexpr int QU = Q_UNROLL;
#pragma unroll QU
            for (int i = 0; i < 5; i++) {
                uint32_t r[8];
                ldsm4t(src + i * 4096 + ((ck ^ (tk & 7)) << 4), r[0], r[1], r[2], r[3]);
                ldsm4t(src + i * 4096 + (((ck + 1) ^ (tk & 7)) << 4), r[4], r[5], r[6], r[7]);
                stg128(dst + i * 2048, tag(r[0], ep), r[1], r[2], r[3]);
                stg128(dst + i * 2048 + 128, tag(r[4], ep), r[5], r[6], r[7]);
            }
            float s1 = 0.f, s2 = 0.f;
#pragma unroll 2
            for (int i = 0; i < 10; i++) {
                const uint4 w4 = lds128(sb + OFF_QIN + i * 2048 + wt * 16);
                const uint32_t w[4] = {w4.x, w4.y, w4.z, w4.w};
#pragma unroll
                for (int e = 0; e < 4; e++) { const float a = blo(w[e]), b = bhi(w[e]); s1 += a + b; s2 = fmaf(a, a, fmaf(b, b, s2)); }
            }
#pragma unroll
            for (int o = 1; o < 8; o *= 2) { s1 += __shfl_xor_sync(~0u, s1, o); s2 += __shfl_xor_sync(~0u, s2, o); }
            s1 *= 1.f / D_;
            uint32_t rs = pack2(rsqrtf(fmaxf(s2 * (1.f / D_) - s1 * s1, 0.f) + 1e-5f), 0.f);
            if (lane < 8) rs = tag(rs, ep);
            rs = pack2(blo(rs), -s1 * blo(rs));
            const uint32_t sel = lane ? 0x7632 : 0x5410;
            const uint32_t a0 = __shfl_sync(~0u, rs, 0), a1 = __shfl_sync(~0u, rs, 8), a2 = __shfl_sync(~0u, rs, 16), a3 = __shfl_sync(~0u, rs, 24);
            if (lane < 2) stg64(g_qst + lane * S_ + 16 * id + 4 * sw, tag(__byte_perm(a0, a1, sel), ep), __byte_perm(a2, a3, sel));
            TS(wt == 0, 55)
        }
        bar_sync(6, 128);
        if (sw == 3) {
            signal_cnt(&g_cnt.q[(lane & 3) * 32], lane, 4, true);
            TS(lane == 0, 3)
        }
        asm volatile("setmaxnreg.dec.sync.aligned.u32 " STR(REG_SVC) ";");
        asm volatile("barrier.cluster.wait.aligned;" ::: "memory");
        if (sw == 1) {
            mbar_spin(bars + B_XS * 8, 0);
            signal_cnt(&g_cnt.x[(lane & 3) * 32], lane, 4, true);
            TS(lane == 0, 20)
        }
        if (sw == 1 || sw == 2) {
            mbar_spin(bars + B_XS * 8, 0);
            fence_async_smem();
            const unsigned* flag = &g_cnt.x[(id & 3) * 32];
            int n = sw & 1;
#pragma unroll 1
            for (int s = 0; s < 6; s++) {
                const int e = s >> 1, end = 20 * e + ((s & 1) ? 20 : e == 0 ? LEAD1 : e == 1 ? 2 * LEAD2 : XLEAD);
                const uint32_t M = e == 0 ? M0 : e == 1 ? M1 : M2;
                if (s & 1) mbar_spin(bars + (B_GATE + 2 + e) * 8, !e);
                else {
                    wait_cnt(flag, e ? 32 : 128, true);
                    flag = e ? &g_cnt.g2[grp * 32] : &g_cnt.g1[max(grp - 1 + min(lane, 2), 0) * 32];
                    TS(lane == 0 && sw == 2, 26 + 2 * e)
                }
#pragma unroll 1
                for (; n < end; n += 2) {
                    const int i = n - 20 * e, w = (M >> i) & 1, c = __popc(M & ((1u << i) - 1));
                    mbar_spin(bars + (B_XEMPTY + (n & 7)) * 8, ((n >> 3) & 1) ^ 1);
                    TR2(lane == 0 && n < 40, 20 + n)
                    if (elect()) {
                        if (n == 40 || n == 40 + XLEAD) {
                            mbar_arrive(bars + (B_LAND + (n & 7)) * 8);
                            asm volatile("mbarrier.arrive.shared.b64 _, [%0], 8;" ::"r"(bars + (B_XEMPTY + (n & 7)) * 8) : "memory");
                        } else load_tile(mp, sb + OFF_XR + (n & 7) * 8192, e, grp + 16 * w, w ? c : i - c, j, bars + (B_LAND + (n & 7)) * 8);
                    }
                }
            }
            if (sw == 1) { if (elect()) mbar_arrive(bars + (B_GATE + 5) * 8); return; }
            mbar_spin(bars + (B_GATE + 5) * 8, 0);
            mbar_spin(bars + B_VEC3 * 8, 0);
            unsigned old = 0;
            asm volatile("{\n.reg .pred P;\nsetp.eq.s32 P, %2, 0;\n@P atom.relaxed.gpu.global.add.u32 %0, [%1], %3;\n}" : "+r"(old) : "l"(&g_cnt.done[0]), "r"(lane), "r"(1) : "memory");
            if (__any_sync(~0u, old == 127)) {
#pragma unroll 1
                for (int i = lane; i < (int)(sizeof(Counters) / 128); i += 32) reinterpret_cast<unsigned*>(&g_cnt)[i * 32] = 0;
                signal_cnt(&g_epoch, lane, 1, true);
            }
        } else if (sw == 0) {
            wait_cnt(&g_cnt.wr[0], 4);
            mbar_spin(bars + B_QRDY * 8, 0);
            const uint32_t wf = bars + B_WFULL * 8, we = bars + B_WEMPTY * 8;
#pragma unroll 1
            for (int n = 0; n < 5; n++) {
                if (n == 3) { mbar_spin(bars + B_XS * 8, 0); fence_async_smem(); }
                TR2(lane == 0, 70 + n)
                if (elect()) {
                    const uint32_t fb = wf + n * 8, dst = sb + OFF_W + n * 16384;
                    mbar_expect(fb, 20480);
#pragma unroll 1
                    for (int h = 0; h < 2; h++) {
                        const int kb = g1_block(2 * n + h, j);
                        tma_ld2(dst + h * 8192, &mp.w1, 64 * j, 64 * kb, fb);
                        bulk_ld(sb + OFF_REM + n * 4096 + h * 2048, &g_wr[(j * 10 + kb) * 128], 2048, fb);
                    }
                }
            }
            mbar_spin(bars + B_GATE * 8, 0);
#pragma unroll 1
            for (int i = -3; i < 5; i++) {
                const int n = i < 0 ? 8 + i : 5 + i;
                const uint32_t fb = wf + (n & 7) * 8;
                if (i >= 0) mbar_spin(we + i * 8, 0);
                TR2(lane == 0 && i >= 0, 70 + n)
                if (elect()) {
                    if (i < 0 || i >= 3) { mbar_expect(fb, 20480); tma_ld5(sb + OFF_W + (n & 7) * 16384, n < 9 ? &mp.w2a : &mp.w2b, 64 * j, n < 9 ? 4 * (n - 5) : 0, fb); }
                    if (i >= 0) bulk_ld(sb + OFF_REM + i * 4096, &g_wr[((8 + j) * 10 + 2 * i) * 128], 4096, fb);
                }
            }
            mbar_spin(bars + (B_GATE + 1) * 8, 0);
#pragma unroll 1
            for (int n = 10; n < 30; n++) {
                if (n == W3_N2) mbar_spin(bars + (B_GATE + 2) * 8, 0);
                mbar_spin(we + (n & 7) * 8, ((n >> 3) & 1) ^ 1);
                TR2(lane == 0, 70 + n)
                if (elect()) {
                    const uint32_t dst = sb + OFF_W + (n & 7) * 16384, fb = wf + (n & 7) * 8;
                    mbar_expect(fb, 13824);
                    const int row = 64 * g3_block((n - 10) >> 1, j) + 32 * (n & 1);
                    tma_ld3(dst, &mp.w3a, 0, row, 3 * j, fb);
                    tma_ld2(dst + 12288, &mp.w3b, 1536 + 24 * j, row, fb);
                }
            }
            mbar_spin(we + 6 * 8, 0);
            mbar_spin(bars + B_VEC3 * 8, 0);
            if (elect()) { mbar_expect(wf + 6 * 8, 3456); bulk_ld(sb + OFF_W + 6 * 16384, &g_cs3b[216 * j], 3456, wf + 6 * 8); }
#pragma unroll 1
            for (int n = 31; n < 50; n++) {
                const int e = n < 38 ? 4 : (n - 38) & 3, m0 = n == 35, m1 = e == 3 ? -1 : m0 | (e == 1), rem = 96 + 3 * (j >> 1);
                const int c1_ = j ^ (n < 38 ? 6 : 4 >> ((n - 38) >> 2) & 6), c0_ = n < 38 ? 8 + (j & 1) : c1_;
                const int f = (0xC840A80C204ull >> (4 * min(n - 31, e + 7))) & 15;
                const int r0 = m0 ? rem : 6 * (j ^ (f >> 3)) + (f & 6), r1 = m1 ? rem : r0 + (n < 38 ? 0 : 2);
                mbar_spin(we + (n & 7) * 8, ((n >> 3) & 1) ^ 1);
                if (elect()) {
                    const uint32_t dst = sb + OFF_W + (n & 7) * 16384, fb = wf + (n & 7) * 8;
                    mbar_expect(fb, m1 < 0 ? 8192 : 16384 - 2048 * (m0 + m1));
                    tma_ld2(dst, &mp.w4[m0], 64 * c0_, r0 * (32 >> m0), fb);
                    if (m1 >= 0) tma_ld2(dst + 8192, &mp.w4[m1], 64 * c1_, r1 * (32 >> m1), fb);
                }
            }
        } else {
            {
                wait_cnt(&g_cnt.tab[0], 1);
                mbar_spin(bars + B_QRDY * 8, 0);
                if (elect()) {
                    mbar_expect(bars + B_TAB * 8, TAB_BYTES / 2 + VEC_BYTES);
                    bulk_ld(sb + OFF_TAB, g_tab + (j & 1) * (TAB_BYTES / 32), TAB_BYTES / 2, bars + B_TAB * 8);
                    bulk_ld(sb + M_GB, g_tab + (TAB_BYTES + j * VEC_BYTES) / 16, VEC_BYTES, bars + B_TAB * 8);
                }
                TS(lane == 0, 5)
            }
            wait_cnt(&g_cnt.uv[0], 4);
#pragma unroll 1
            for (int c = lane; c < 80; c += 32) {
                const float* src = g_uv + (c < 64 ? 64 * j + c : 448 + 16 * j + c);
                const uint32_t u = split2(ldcg32f(src) + ldcg32f(src + 3 * D_)), v = split2(ldcg32f(src + D_) + ldcg32f(src + 4 * D_));
                const uint32_t s = split2(ldcg32f(src + 2 * D_) + ldcg32f(src + 5 * D_));
                sts128(sb + OFF_F1 + c * 16, u, __byte_perm(u, v, 0x5410), __byte_perm(v, 0, 0x1032), s);
                sts128(sb + M_F1 + c * 16, s & 0xffffu, 0, 0, 0);
            }
            fence_async_smem();
            warp_arrive(bars + B_VEC * 8);
            TS(lane == 0, 9)
#pragma unroll 1
            for (int e = 1; e < 3; e++) {
                wait_cnt(e == 1 ? &g_cnt.g1[min(grp + 15 + min(lane, 2), 31) * 32] : &g_cnt.g2[(grp + 16) * 32], 32, true);
                if (elect()) mbar_arrive(bars + (B_GATE + 2 + e) * 8);
                TS(lane == 0, 27 + 2 * e)
            }
            wait_cnt(&g_cnt.cs2[0], 4);
            if (elect()) mbar_arrive(bars + B_VEC3 * 8);
            TS(lane == 0, 19)
        }
        return;
    }

    {
        uint32_t ep;
        {
            TIDS
            ep = ld_cold(&g_epoch);
            const int cp = (tid + 16) % 40, cp1 = tid % 40;
            const uint4 sh0 = ldg128(pp.shift_k + (80 * (id & 7) + 2 * cp1) * 4), sh1 = ldg128(pp.shift_k + (80 * (id & 7) + 2 * cp) * 4);
            uint32_t dd;
            asm volatile("ld.global.nc.u16 %0, [%1];" : "=r"(dd) : "l"(pp.ssm_D + 5 * id + min(wg + 3 * lane, 4)));
            TR4(lane == 0, 40 + warp)
            __syncthreads();
            asm volatile("barrier.cluster.arrive.relaxed.aligned;" ::: "memory");
            asm volatile("add.u32 %0, %0, 1;" : "+r"(ep));
#pragma unroll 1
            for (int hw = 0; hw < 2; hw++) {
                if ((unsigned)(warp - 2 * hw) >= 10) continue;
                const int u = tid - 64 * hw;
                const int c = hw ? cp : cp1, oc = u / 40, line = 31 - 16 * hw - (id >> 3);
                const uint4 sh = hw ? sh1 : sh0;
                const uint32_t st = sb + OFF_ST + hw * 10240, sta = st + c * 256 + ((((6 - 2 * (oc & 3)) ^ (oc >> 2) ^ (line & 1)) ^ (c & 7)) << 4), in = oc * 1280 + c * 4;
                const uint32_t f0 = __byte_perm(sh.x, sh.z, 0x5410), f1 = __byte_perm(sh.x, sh.z, 0x7632), f2 = __byte_perm(sh.y, sh.w, 0x5410), f3 = __byte_perm(sh.y, sh.w, 0x7632);
                uint32_t kk[11], vv[8];
                mbar_spin(bars + (B_IN + hw) * 8, 0);
                TS(tid == 64, 18 + 42 * hw)
#pragma unroll
                for (int i = 0; i < 11; i++) kk[i] = lds32(sb + OFF_KIN + hw * 10752 + in + i * 160);
#pragma unroll
                for (int i = 0; i < 8; i++) vv[i] = lds32(sb + OFF_VIN + hw * 10240 + in + i * 160);
#pragma unroll
                for (int i = 0; i < 8; i++) vv[i] = mul2(fma2(kk[i + 3], f0, fma2(kk[i + 2], f1, fma2(kk[i + 1], f2, mul2(kk[i], f3)))), vv[i]);
                sts128(sta, tag(__byte_perm(vv[0], vv[1], 0x5410), ep), __byte_perm(vv[2], vv[3], 0x5410), __byte_perm(vv[4], vv[5], 0x5410), __byte_perm(vv[6], vv[7], 0x5410));
                sts128(sta + 128, tag(__byte_perm(vv[0], vv[1], 0x7632), ep), __byte_perm(vv[2], vv[3], 0x7632), __byte_perm(vv[4], vv[5], 0x7632), __byte_perm(vv[6], vv[7], 0x7632));
                bar_sync(7 + hw, 320);
                flush_tile(st, g_kvT + (size_t)(80 * (id & 7)) * S_ + 64 * line, u);
                TS(tid == 64 && hw, 1)
            }
            warp_arrive(bars + B_KVS * 8);
            if (tid < 320) sts128(sb + OFF_CH + (tid >> 6) * CH_BYTES + 4096 + (tid & 63) * 16, 0, 0, 0, 0);
            mbar_spin(bars + B_SSM * 8, 0);
            TS(tid == 0, 14)
#pragma unroll 1
            for (int u0 = wg; u0 < 20; u0 += 12) {
                uint2 w[4];
                uint32_t pv[4];
#pragma unroll
                for (int i = 0; i < 4; i++) {
                    const uint32_t a = sb + OFF_SSM + min(u0 + 3 * i, 19) * 1024 + wt * 8;
                    w[i] = lds64(a); pv[i] = lds32(a - 4);
                }
#pragma unroll
                for (int i = 0; i < 4; i++) {
                    const int un = min(u0 + 3 * i, 19);
                    sts128(sb + OFF_CH + (un >> 2) * CH_BYTES + OFF_P + (un & 3) * 2048 + wt * 16, __byte_perm(w[i].x, pv[i], 0x7610), __byte_perm(w[i].x, 0, 0x1032), __byte_perm(w[i].y, w[i].x, 0x7610), __byte_perm(w[i].y, 0, 0x1032));
                }
            }
            __syncwarp();
            if (wt < 2 - (wg >> 1)) {
                const uint32_t h = lds32(sb + OFF_SSM + (wg + 3 * wt) * 4096), h0 = pack2(blo(h) + blo(dd), 0.f);
                sts64f(sb + OFF_CH + (wg + 3 * wt) * CH_BYTES + OFF_P, __uint_as_float(h0), __uint_as_float(__byte_perm(h, h0, 0x5432)));
            }
            fence_async_smem();
            warp_arrive(bars + B_BK * 8);
            asm volatile("barrier.cluster.wait.aligned;" ::: "memory");
            mbar_spin(bars + B_BK * 8, 0);
            TS(tid == 0, 15)
        }

#pragma unroll 1
        for (int c = wg; c < 5; c += 3) {
            const uint32_t kvb = sb + OFF_CH + c * CH_BYTES;
            mbar_spin(bars + (c < 3 ? B_RAW : B_RAW3) * 8, 0);
            for (uint32_t ph = 0; c < 3; ph ^= 1) {
                const int wt = tid_now() & 127;
                if (!RARE(bar_any(1 + wg, lop3<0x7E>(lds32(kvb + wt * 16), ep, lds32(kvb + 2048 + wt * 16)) & 1))) break;
                if (wt == 0) { mbar_expect(bars + (B_RETRY + wg) * 8, 4096); bulk_ld(kvb, g_kvT + (size_t)(5 * id + c) * S_, 4096, bars + (B_RETRY + wg) * 8); }
                mbar_spin(bars + (B_RETRY + wg) * 8, ph);
                STALE1(-8)
            }
            TS(threadIdx.x == 0, c ? 13 : 11)
            float acc[64];
            {
                const int l = tid_now() & 31;
                conv_channel(acc, kvb + OFF_P + (8 * (warp & 3) + (l >> 2) - 2 * (l & 3)) * 4, (((uint64_t)0xC0000010u << 32) | ((kvb & 0x3FFFF) >> 4) | 0x10000u) + pp.nil);
            }
            TS(threadIdx.x == 0, c ? 16 : 12)
            if (c < 3) warp_arrive(bars + B_R1 * 8);
            else mbar_spin(bars + B_R1 * 8, 0);
            if (wg == 2 && id < 120) {
                TIDS
                mbar_spin(bars + B_RAW3 * 8, 0);
                mbar_spin(bars + B_WM * 8, 0);
                TS(wt == 0, 56)
                float d[4];
                gemv_tile<8>(d, sb + OFF_WM, sb + OFF_Z, 0);
                const float d2 = __shfl_up_sync(~0u, d[2], 1);
                TS(wt == 0, 7)
                if (t < 2) asm volatile("{\n.reg .b64 v;\nmov.b64 v, {%1, %2};\nst.relaxed.gpu.global.b64 [%0], v;\n}" ::"l"(g_mod + (id & 1) * 6 * D_ + 64 * pr + 16 * (warp & 3) + g + 8 * t),
                                        "r"(__float_as_uint(t ? d2 : d[0])), "r"(lds32(sb + M_EP)) : "memory");
            }
            TR4(threadIdx.x == 0, 60 + (c >= 3) * 10)
            TIDS
            const int e = 127 - 8 * (lane >> 4) - (lane & 7), u0 = (warp & 3) + 8 * (e >> 2) + (e & 3) + 4 * ((lane >> 3) & 1);
            const uint32_t ring = sb + OFF_RING + c * 16384 + (warp & 3) * 4096, wa = ring + (u0 ^ ((u0 >> 1) & 4)) * 16;
            if (lane < (warp & 3)) sts128(ring + lane * 16, 0, 0, 0, 0);
#pragma unroll
            for (int i = 0; i < 8; i++)
                stsm4t(i == 0 && u0 >= 256 ? sb + M_SINK : wa - 512 * i, pack2(acc[8 * i], acc[8 * i + 1]), pack2(acc[8 * i + 2], acc[8 * i + 3]),
                       pack2(acc[8 * i + 4], acc[8 * i + 5]), pack2(acc[8 * i + 6], acc[8 * i + 7]));
            warp_arrive(bars + (B_RING + c) * 8);
            TR4(threadIdx.x == 0, 61 + (c >= 3) * 10)
        }
        TIDS
        if (wg == 2) bar_sync(3, 128);
        if (warp == 8) {
            wait_cnt(&g_cnt.q[(id & 3) * 32], 128, true);
            if (elect()) {
                mbar_expect(bars + B_QRDY * 8, 28672);
                tma_ld2(sb + OFF_QT, &mp.qT, 80 * id, 0, bars + B_QRDY * 8);
                bulk_ld(sb + OFF_QT + 20480, g_qst, 8192, bars + B_QRDY * 8);
            }
            TS(lane == 0, 8)
        } else if (warp == 9) {
            const int v = min(lane / 5, 3);
            const uint2* gm = g_mod + (v + (v == 3)) * D_ + 5 * id + lane % 5;
            const unsigned epoch = lds32(sb + M_EP);
            uint2 r0, r1;
            unsigned it = 0;
            do {
                r0 = ld_mod(gm); r1 = ld_mod(gm + 6 * D_);
                SPIN_CHECK(55)
            } while (!__all_sync(~0u, r0.y == epoch && r1.y == epoch));
            const float m0 = __uint_as_float(r0.x), m1 = __uint_as_float(r1.x);
            const float m = rbf(m0 + m1), p = rbf(1.f + m);
            const float cz = zscale(__shfl_sync(~0u, p, 15 + lane % 5)), ga = __shfl_sync(~0u, m, 10 + lane % 5);
            if (lane < 15) sts32(sb + M_AB + lane % 5 * 16 + v * 4, lane < 10 ? __float_as_uint(cz * ga * (lane < 5 ? m : p)) : pack2(cz, cz));
            warp_arrive(bars + B_MODR * 8);
            TS(lane == 0, 6)
        }
        mbar_spin(bars + B_QRDY * 8, 0);
        uint4 rs[2], nm[2];
#pragma unroll
        for (int h = 0; h < 2; h++) { rs[h] = lds128(sb + OFF_QT + 20480 + h * 2048 + wt * 16); nm[h] = lds128(sb + OFF_QT + 24576 + h * 2048 + wt * 16); }
        mbar_spin(bars + B_MODR * 8, 0);
        TR4(threadIdx.x == 0, 72)
        uint32_t it = 0;
        while (RARE(__any_sync(~0u, (lop3<0x7E>(rs[0].x, ep, rs[0].z) | lop3<0x7E>(nm[0].x, ep, nm[0].z) | lop3<0x7E>(rs[1].x, ep, rs[1].z) | lop3<0x7E>(nm[1].x, ep, nm[1].z)) & 1))) {
#pragma unroll
            for (int h = 0; h < 2; h++) { rs[h] = ld_part(g_qst + 1024 * h + 8 * wt); nm[h] = ld_part(g_qst + S_ + 1024 * h + 8 * wt); }
            STALE(1)
            SPIN_CHECK(53)
        }
        TR4(threadIdx.x == 0, 73)
#pragma unroll 1
        for (int c = wg == 2 ? 0 : 3 + wg; c < (wg == 2 ? 3 : 4 + wg); c++) {
            uint4 q[2], p[2][4];
#pragma unroll
            for (int h = 0; h < 2; h++) q[h] = lds128(sb + OFF_QT + h * 10240 + (wt >> 1) * 160 + c * 32 + (wt & 1) * 16);
            const float4 ab = lds128f(sb + M_AB + c * 16);
            mbar_spin(bars + (B_RING + c) * 8, 0);
            TR4(wt == 0, wg == 2 ? 80 + 2 * c : 74)
#pragma unroll
            for (int i = 0; i < 8; i++) p[i >> 2][i & 3] = lds128(sb + OFF_RING + c * 16384 + (i & 3) * 4096 + (i >> 2) * 2048 + (wt ^ ((wt >> 1) & 4)) * 16);
            while (RARE(__any_sync(~0u, lop3<0x7E>(q[0].x, ep, q[1].x) & 1))) {
#pragma unroll
                for (int h = 0; h < 2; h++) q[h] = ld_part(g_qT + ((64 * h + (wt >> 1)) * D_ + 5 * id + c) * 16 + 8 * (wt & 1));
                STALE(2)
                SPIN_CHECK(52)
            }
            TR4(wt == 0, wg == 2 ? 81 + 2 * c : 75)
#pragma unroll
            for (int h = 0; h < 2; h++) {
                const uint32_t qq[4] = {q[h].x, q[h].y, q[h].z, q[h].w}, r4[4] = {rs[h].x, rs[h].y, rs[h].z, rs[h].w}, n4[4] = {nm[h].x, nm[h].y, nm[h].z, nm[h].w};
                const uint4 y = add2(add2(p[h][0], p[h][1]), add2(p[h][2], p[h][3]));
                const uint32_t yy[4] = {y.x, y.y, y.z, y.w};
                uint32_t o[4];
#pragma unroll
                for (int i = 0; i < 4; i++) {
                    const uint32_t n = fma2(qq[i], r4[i], n4[i]);
                    o[i] = fma2(pack2(fmaf(blo(n), ab.y, ab.x), fmaf(bhi(n), ab.y, ab.x)), yy[i], mul2(qq[i], __float_as_uint(ab.z)));
                }
                stg128_tag(g_x1T + (size_t)(5 * id + c) * S_ + 1024 * h + 8 * wt, o[0], o[1], o[2], o[3], ep, ((5 * id + c) >> 3) & 3);
            }
        }
        warp_arrive(bars + B_XS * 8);
        TS(tid == 0, 17)
        TS(tid == 256, 52)
    }

    const uint32_t nil = pp.nil;
    const int wq = warp & 3;
    if (wg == 2) {
        TIDS
        asm volatile("setmaxnreg.dec.sync.aligned.u32 " STR(REG_AUX) ";");
        {
            const uint32_t ep = lds32(sb + M_EP);
            uint32_t ph = 0;
#pragma unroll 1
            for (int m = wq - 4; m < 60; m += 4) {
                const int n = max(m, 0);
                const int e = (n >= 20) + (n >= 40), i = n - 20 * e;
                const uint32_t M = e == 0 ? M0 : e == 1 ? M1 : M2;
                const int w = (M >> i) & 1, c = __popc(M & ((1u << i) - 1)), kb = w ? c : i - c;
                const uint32_t a = sb + OFF_XR + (n & 7) * 8192;
                uint32_t ta = a + (e == 0 ? lane * 128 + ((lane & 7) << 4) + (lane >> 3) * 4
                                 : e == 1 ? (lane & 15) * 128 + (((lane >> 4 << 1) ^ (lane & 7)) << 4) + (lane & 8) + (lane >> 4) * 4
                                          : lane * 32 + (lane >> 2) * 4);
                uint32_t tb = e == 0 ? ta ^ 32 : ta + 2048, tc = e == 2 ? ta + 1024 : ta ^ 64, td = e == 2 ? tb + 1024 : tb ^ 64;
                uint32_t live = m >= 0 && m != 40 && m != 40 + XLEAD,
                    f0 = bars + (B_XFULL + 10 * w + kb) * 8;
                uint32_t f1 = m == GATE_W2 || m == GATE_W3 || m == GATE_W3B ? bars + (B_GATE + (m >= GATE_W3) + (m >= GATE_W3B)) * 8 : 0;
                if (lane) f0 = f1;
                if (lane > 1 || m < 0) f0 = 0;
                asm volatile("" : "+r"(ta), "+r"(tb), "+r"(tc), "+r"(td), "+r"(live), "+r"(f0));
                mbar_spin(bars + (m < 0 ? B_BK : B_LAND + (n & 7)) * 8, (n >> 3) & 1);
                TR5(lane == 0, n)
                while (true) {
                    uint32_t v[8];
#pragma unroll
                    for (int i = 0; i < 8; i++) v[i] = lds32(((i & 2) ? ((i & 1) ? td : tc) : (i & 1) ? tb : ta) + (i >> 2) * 4096);
                    const uint32_t bad = lop3<0xFE>(lop3<0x7E>(v[0], ep, v[1]), lop3<0x7E>(v[2], ep, v[3]), lop3<0x7E>(v[4], ep, v[5]));
                    if (!RARE(__any_sync(~0u, lop3<0xA8>(bad, lop3<0x7E>(v[6], ep, v[7]), live)))) break;
                    if (elect()) load_tile(mp, a, e, grp + 16 * w, kb, j, bars + (B_AGAIN + wq) * 8);
                    mbar_spin(bars + (B_AGAIN + wq) * 8, ph);
                    ph ^= 1;
                    STALE1(e)
                }
                TR5(lane == 0, 60 + n)
                if (f0) mbar_arrive(f0);
            }
        }
        if (wq == 0) {
#pragma unroll 1
            for (int w = 0; w < 2; w++) {
                const uint4* src = g_part + (size_t)(grp + 16 * w) * 40960;
                TR4(lane == 0, 90 + 2 * w)
                mbar_wait(bars + (B_RING + w) * 8, 1);
                TR4(lane == 0, 91 + 2 * w)
                if (elect()) {
                    const uint32_t fb = bars + (B_IN + w) * 8, rem = sb + OFF_OUT + w * 10240;
                    mbar_expect(fb, 10240);
                    bulk_ld(rem + 8192, &g_x1f[((grp + 16 * w) * 8 + j) * 640 + 512], 2048, fb);
#pragma unroll 1
                    for (int i = 0; i < 4; i++) bulk_ld(rem + i * 2048, src + ((j >> 2) + 2 * i) * 5120 + 4096 + j * 128, 2048, fb);
                }
            }
        }
#pragma unroll 1
        for (int uw = 0; uw < 2; uw++) {
            const int tile = grp + 16 * uw;
            const uint32_t ep = lds32(sb + M_EP), in = sb + OFF_OUT + uw * 10240 + wt * 16, sr = in - lane * 16;
            mbar_wait(bars + (B_IN + uw) * 8, 1);
            TR4(wt == 0, 94 + 3 * uw)
            uint4 u[4];
#pragma unroll
            for (int i = 0; i < 4; i++) u[i] = lds128(in + i * 2048);
            const uint4 base = lds128(in + 8192);
            const uint32_t ra = sb + M_F1 + (64 * uw + 16 * wq + g) * 4;
            const uint4 gr = scale16(lds64f(sb + M_GB + (64 + 2 * t) * 4), lds64f(sb + M_GB + (72 + 2 * t) * 4), __uint_as_float(lds32(ra)), __uint_as_float(lds32(ra + 32)));
            uint32_t it = 0;
            while (RARE(__any_sync(~0u, stale4(u, ep) & 1))) {
                ld_part4(u, g_part + (size_t)tile * 40960 + (j >> 2) * 5120 + 4096 + j * 128 + wt, 10240);
                STALE(3)
                if (++it > SPIN_LIMIT) SPIN_FAIL(58)
            }
            TR4(wt == 0, 95 + 3 * uw)
            const uint4 r = fin16(add2(add2(u[0], u[1]), add2(u[2], u[3])), base, gr);
            __syncwarp();
            stsm4(sr + (lane & 15) * 32 + (((lane >> 4) ^ ((lane >> 2) & 1)) << 4), r.x, r.y, r.z, r.w);
            __syncwarp();
            stg128(out + (size_t)(64 * tile + 16 * wq + (lane >> 1)) * D_ + 512 + 16 * j + 8 * (lane & 1), lds128(sr + (lane >> 1) * 32 + (((lane & 1) ^ ((lane >> 3) & 1)) << 4)));
            TR4(wt == 0, 96 + 3 * uw)
            __syncwarp();
        }
        TS(wt == 0, 21)
        if (wq == 0) {
            uint32_t it = 0;
            while (!mbar_try(bars + B_OWN * 8, 0)) { if (++it > SPIN_LIMIT) SPIN_FAIL(56) }
        }
        return;
    }

    TIDS
    const int uw = wg, tile = grp + 16 * uw, row0 = 64 * tile + 16 * wq;
    const bool leader = wt == 0; (void)leader;
    const uint32_t xfull = bars + (B_XFULL + 10 * uw) * 8, xempty = bars + B_XEMPTY * 8, wfull = bars + B_WFULL * 8, wempty = bars + B_WEMPTY * 8;
    const uint64_t dz = mkdesc(0) + pp.nil;
    auto xwait = [&](uint32_t kb, uint32_t e) { mbar_spin(xfull + kb * 8, e & 1); };
    asm volatile("setmaxnreg.inc.sync.aligned.u32 " STR(REG_MMA) ";");
    const uint32_t ep = lds32(sb + M_EP);
    uint32_t x2[20];
    uint32_t res[20] = {};
    {
        float acc[40];
        const uint32_t la = ((lane & 7) + 8 * (lane >> 4)) * 128 + (((2 * wq + ((lane >> 3) & 1)) ^ (lane & 7)) << 4);
        auto pos = [&](int n) { return ring_pos(uw, n, LEAD1) & 7; };
        auto slot = [&](int n) { return sb + OFF_XR + pos(n) * 8192; };
        float al[2], r1[2], n1[2];
        {
            float sl[4], sq[4], v[4];
            uint32_t z0[16], z1[16], zz[16];
            uint64_t bd = dz + b80_desc(dsb, 0, 0, 0), tb = (((uint64_t)8 << 32) | ((dsb + OFF_TAB) >> 4) | (7u << 16)) + pp.nil;
            auto ldfrag = [&](uint32_t (&z)[16], int n) {
#pragma unroll
                for (int q = 0; q < 4; q++) ldsm4t(slot(n) + la + q * 2048, z[4 * q], z[4 * q + 1], z[4 * q + 2], z[4 * q + 3]);
            };
            auto tile1 = [&](const uint32_t (&zc)[16], uint32_t (&zn)[16], int n, int h) {
                const bool last = h && n == 5, ok = mbar_test(xfull + (n + 1) * 8, 0), okw = !h || mbar_test(wfull + ((n + 1) >> 1) * 8, 0);
                const int kb = g1_block(n, j);
                wg_fence();
#pragma unroll
                for (int q = 0; q < 2; q++) wgmma_rs80(acc, zc[4 * q], zc[4 * q + 1], zc[4 * q + 2], zc[4 * q + 3], bd + q * B80_STEP, 1);
                wg_commit();
                wg_wait<1>();
                if (!ok) xwait(n + 1, 0);
                if (!last) ldfrag(zn, n + 1);
#pragma unroll
                for (int e = 0; e < 16; e++) zz[e] = mul2(zc[e], zc[e]);
                const uint64_t t0 = last ? ((uint64_t)8 << 32) | ((dsb + M_NUL) >> 4) : tb;
                const uint32_t ts = last ? 0 : 14;
                wg_fence();
#pragma unroll
                for (int q = 0; q < 4; q++) wgmma_rs8(sl, zc[4 * q], zc[4 * q + 1], zc[4 * q + 2], zc[4 * q + 3], t0 + q * ts, 1);
#pragma unroll
                for (int q = 0; q < 4; q++) wgmma_rs8(sq, zz[4 * q], zz[4 * q + 1], zz[4 * q + 2], zz[4 * q + 3], t0 + q * ts, 1);
#pragma unroll
                for (int q = 2; q < 4; q++) wgmma_rs80(acc, zc[4 * q], zc[4 * q + 1], zc[4 * q + 2], zc[4 * q + 3], bd + q * B80_STEP, 1);
                wg_commit();
#pragma unroll
                for (int q = 0; q < 4; q++) ldsm4t_if(kb == j, slot(n) + la + q * 2048, &res[4 * q]);
                if (!h) ldsm4t_if(kb == 8 + (j >> 2), slot(n) + la + (j & 3) * 2048, &res[16]);
                if (lane < 2) mbar_arrive_after(xempty + pos(n) * 8, res[12], res[16], nil);
                if (!h && n && lane == 0) mbar_arrive(wempty + ((n >> 1) - 1) * 8);
                tb += 56;
                bd = bd + (uint64_t)B80_HALF;
                if (!okw) mbar_spin(wfull + ((n + 1) >> 1) * 8, 0);
                TR(leader, 100 + 10 * uw + n)
            };
            zero(acc); zero(sl); zero(sq);
            mbar_spin(bars + B_TAB * 8, 0);
            mbar_spin(wfull, 0);
            xwait(0, 0);
            TS(leader, 32 + uw)
            ldfrag(z0, 0);
#pragma unroll 1
            for (int n = 0; n < 6; n += 2) { tile1(z0, z1, n, 0); tile1(z1, z0, n + 1, 1); }
#pragma unroll
            for (int n = 6; n < 10; n++) {
                const uint64_t ad = dz + (((dsb + OFF_XR + pos(n) * 8192) >> 4) | 0x10000u);
                const bool ok = n == 9 || mbar_test(xfull + (n + 1) * 8, 0), okw = n != 7 || mbar_test(wfull + 4 * 8, 0);
                wg_fence();
#pragma unroll
                for (int q = 0; q < 4; q++) wgmma_ss80t(acc, ad + q * 128, bd + q * B80_STEP, 1);
                wg_commit();
                bd = bd + (uint64_t)B80_HALF;
                if (n == 9) ldsm4t_if(9 - (j & 1) == 8 + (j >> 2), slot(9) + la + (j & 3) * 2048, &res[16]);
                wg_wait<1>();
                if (n > 6 && lane < 2) mbar_arrive(xempty + pos(n - 1) * 8);
                if (!(n & 1) && lane == 0) mbar_arrive(wempty + ((n >> 1) - 1) * 8);
                if (n == 6) {
                    reg_fence(sl); reg_fence(sq);
#pragma unroll
                    for (int e = 0; e < 2; e++) {
                        v[2 * e] = t == 0 ? sl[2 * e] + sl[2 * e + 1] : t == 1 ? sq[2 * e] + sq[2 * e + 1] : sl[2 * e];
                        v[2 * e + 1] = t == 2 ? sl[2 * e + 1] : sq[2 * e];
                    }
                    st_peer(peer_addr(sb + OFF_ROW + uw * 2048 + wt * 16), __float_as_uint(v[0]), __float_as_uint(v[1]), __float_as_uint(v[2]), __float_as_uint(v[3]), peer_addr(bars + (B_SUMS + uw) * 8));
                    TS(leader && !uw, 59)
                }
                if (!ok) xwait(n + 1, 0);
                if (!okw) mbar_spin(wfull + 4 * 8, 0);
                TR(leader, 100 + 10 * uw + n)
            }
            float4 k = lds128f(sb + M_KS);
            float k4 = __uint_as_float(lds32(sb + M_KS + 16));
#pragma unroll
            for (int w = 1; w < 5; w++) {
                const float4 o = lds128f(sb + M_KS + w * 32);
                k.x += o.x; k.y += o.y; k.z += o.z; k.w += o.w; k4 += __uint_as_float(lds32(sb + M_KS + w * 32 + 16));
            }
            mbar_spin(bars + (B_SUMS + uw) * 8, 0);
            TS(leader && !uw, 10)
            const float4 o = lds128f(sb + OFF_ROW + uw * 2048 + wt * 16);
            v[0] += o.x; v[1] += o.y; v[2] += o.z; v[3] += o.w;
            uint32_t fa[4];
#pragma unroll
            for (int h = 0; h < 2; h++) {
                const int l0 = lane & ~3;
                const float s1 = __shfl_sync(~0u, v[2 * h], l0), s2 = __shfl_sync(~0u, v[2 * h], l0 + 1), scc = __shfl_sync(~0u, v[2 * h], l0 + 2);
                const float scs = __shfl_sync(~0u, v[2 * h + 1], l0 + 2), sc = __shfl_sync(~0u, v[2 * h], l0 + 3), sqq = __shfl_sync(~0u, v[2 * h + 1], l0 + 3);
                const float m1 = s1 * (1.f / D_), va = fmaxf(s2 * (1.f / D_) - m1 * m1, 0.f) + 1e-5f, r = rsqrtf(va);
                const float m2 = (r * (sc - m1 * k.x) + k.y) * (1.f / D_);
                const float e2 = (r * (r * (sqq + m1 * (m1 * k.z - 2.f * scc)) + 2.f * (scs - m1 * k.w)) + k4) * (1.f / D_);
                al[h] = r * 0.5f * rsqrtf(fmaxf(e2 - m2 * m2, 0.f) + 1e-5f); r1[h] = r; n1[h] = -m1 * r;
                const uint32_t fb = split2(va * r), fx = split2(t == 3 ? -m2 * va * r : -m1), fc = __shfl_sync(~0u, fx, lane | 3);
                fa[h] = __byte_perm(fx, fb, t == 1 ? 0x5432 : t == 2 ? 0x7654 : 0x1010);
                fa[2 + h] = t ? 0 : fc >> 16;
            }
            mbar_spin(bars + B_VEC * 8, 0);
            wg_fence();
            wgmma_rs80k(acc, fa[0], fa[1], fa[2], fa[3], ((uint64_t)8 << 32) | ((dsb + OFF_F1) >> 4) | (((M_F1 - OFF_F1) >> 4) << 16), 1);
            wg_commit();
        }
        wg_wait<0>();
        reg_fence(acc);
        if (lane < 2) mbar_arrive_after(xempty + pos(9) * 8, res[16], 0, nil);
        if (lane == 0) mbar_arrive(wempty + 4 * 8);
        TS(leader, 34 + uw)
        {
            bf16* const trow = g_t + (size_t)(row0 + g + 2) * D_;
#pragma unroll
            for (int b = 0; b < 3; b++) {
                uint32_t p[8];
#pragma unroll
                for (int ii = 0; ii < 4; ii++) {
                    const int i = 4 * b + ii;
                    if (i >= 10) continue;
#pragma unroll
                    for (int h = 0; h < 2; h++) p[(i & 3) + 4 * h] = pack2(gelu2(acc[4 * i + 2 * h] * al[h]), gelu2(acc[4 * i + 2 * h + 1] * al[h]));
                }
                if (b < 2) {
                    const int gr = (2 * j + b) / 5, sh = (gr & 1) ? -1 - (gr >> 1) : 1 + (gr >> 1);
                    bf16* dst = trow + 64 * j + 32 * b + 8 * t;
                    const int w = (((g + sh) >> 2) & 2) + (t >> 1);
                    stg128_tag(dst + sh * D_, p[0], p[1], p[2], p[3], ep, w);
                    stg128_tag(dst + (sh + 8) * D_, p[4], p[5], p[6], p[7], ep, w ^ 2);
                    if (row0 + g < sh || row0 + g + 8 >= S_ + sh) stg128_tag(dst + (sh > 0 ? 0 : 8) * D_, 0, 0, 0, 0, ep, (sh > 0 ? 0 : 2) + (t >> 1));
                } else {
                    bf16* dst = trow + 512 + 16 * j + 4 * t;
                    const uint32_t lo = t == (g < 2), hi = t == (g >= 2), o = j & 1;
                    stg64(dst - 2 * D_, lop3<0xB8>(p[0], lo & ~o, ep), lop3<0xB8>(p[1], lo & o, ep));
                    stg64(dst + 6 * D_, lop3<0xB8>(p[4], hi & ~o, ep), lop3<0xB8>(p[5], hi & o, ep));
                    if (row0 + g + 8 >= S_ - 2) stg64(dst + 8 * D_, ep & (t == 1) & ~o, ep & (t == 1) & o);
                }
            }
        }
        signal_cnt(&g_cnt.g1[tile * 32], lane, 1, true);
        TS(leader, 36 + uw)
#pragma unroll
        for (int i = 0; i < 10; i++) {
            const float2 c = lds64f(sb + M_C + (8 * i + 2 * t) * 4), s = lds64f(sb + M_SB + (8 * i + 2 * t) * 4);
#pragma unroll
            for (int h = 0; h < 2; h++) {
                acc[4 * i + 2 * h] = fmaf(blo(res[2 * i + h]), r1[h], fmaf(n1[h], c.x, s.x));
                acc[4 * i + 2 * h + 1] = fmaf(bhi(res[2 * i + h]), r1[h], fmaf(n1[h], c.y, s.y));
            }
        }
        mbar_spin(wfull + 5 * 8, 0);
        xwait(0, 1);
        TS(leader, 22 + uw)
        uint32_t ps = uw ? P1S : P0S, xo = (ps & 3) * 16, xp = 0;
        const uint64_t ax = dz + (((dsb + OFF_XR) >> 4) | 0x10000u);
        uint64_t ad = ax + xo * 64, bd = dz + b80_desc(dsb, 5, 0, 0);
#pragma unroll 1
        for (int i = 0; i < 5; i++) {
            const uint32_t x1 = xfull + (1 + 2 * i) * 8, p1 = 1, x2 = xfull + min(2 + 2 * i, 9) * 8, p2 = 1;
            const uint32_t w2 = wfull + (min(6 + i, 9) & 7) * 8, pw = i >= 2;
            const bool ok1 = mbar_test(x1, p1);
            wg_fence();
#pragma unroll
            for (int q = 0; q < 4; q++) wgmma_ss80(acc, ad + q * 2, bd + q * B80_STEP, 1);
            wg_commit();
            wg_wait<1>();
            if (lane < 2 && i) mbar_arrive(xempty + xp);
            if (lane == 0 && i) mbar_arrive(wempty + ((4 + i) & 7) * 8);
            if (!ok1) mbar_spin(x1, p1);
            const bool ok2 = mbar_test(x2, p2), okw = mbar_test(w2, pw);
            wg_fence();
#pragma unroll
            for (int q = 0; q < 4; q++) wgmma_ss80(acc, ad + 512 + q * 2, bd + B80_HALF + q * B80_STEP, 1);
            wg_commit();
            const uint32_t xc = xo;
            ps >>= 2;
            xp = xo + 8; xo = (ps & 3) * 16;
            ad = ax + xo * 64;
            bd += i == 2 ? 2 * B80_HALF - 8192 + (8192ll << 16) : 2 * B80_HALF;
            asm volatile("" : "+l"(ad), "+l"(bd));
            wg_wait<1>();
            if (lane < 2) mbar_arrive(xempty + xc);
            if (!ok2) mbar_spin(x2, p2);
            if (!okw) mbar_spin(w2, pw);
            TR(leader, (uw ? 86 : 20) + 2 * i)
        }
        wg_wait<0>();
        reg_fence(acc);
        if (lane < 2) mbar_arrive(xempty + xp);
        if (lane == 0) mbar_arrive(wempty + (9 & 7) * 8);
        TS(leader, 38 + uw)
        float a0 = 0.f, b0 = 0.f, a1 = 0.f, b1 = 0.f;
#pragma unroll
        for (int i = 0; i < 5; i++) {
            uint32_t* p = &x2[4 * i];
#pragma unroll
            for (int e = 0; e < 4; e++) p[e] = pack2(acc[8 * i + 2 * e], acc[8 * i + 2 * e + 1]);
#pragma unroll
            for (int e = 0; e < 4; e++) p[e] = lop3<0xB8>(p[e], (((wt >> 3) ^ (wt << 2)) & 7) == e, ep);
            stg128(&g_x2f[(tile * 40 + (i < 4 ? 4 * j + i : 32 + j)) * 128 + wt], p[0], p[1], p[2], p[3]);
#pragma unroll
            for (int e = 0; e < 8; e += 4) {
                const float* u = &acc[8 * i + e];
                a0 += u[0] + u[1]; b0 = fmaf(u[0], u[0], fmaf(u[1], u[1], b0));
                a1 += u[2] + u[3]; b1 = fmaf(u[2], u[2], fmaf(u[3], u[3], b1));
            }
        }
#pragma unroll
        for (int o = 1; o < 4; o *= 2) {
            a0 += __shfl_xor_sync(~0u, a0, o); b0 += __shfl_xor_sync(~0u, b0, o);
            a1 += __shfl_xor_sync(~0u, a1, o); b1 += __shfl_xor_sync(~0u, b1, o);
        }
        if (t < 2) stg64(&g_stats[(tile * 8 + j) * 64 + 16 * wq + g + 8 * t], tag(__float_as_uint(t ? a1 : a0), ep), __float_as_uint(t ? b1 : b0));
        signal_cnt(&g_cnt.g2[tile * 32], lane, 1, true);
        TS(leader, 40 + uw)
#pragma unroll
        for (int i = 0; i < 10; i++) {
            const float2 c = lds64f(sb + M_GB + (8 * i + 2 * t) * 4), e = lds64f(sb + M_CI + (8 * i + 2 * t) * 4);
#pragma unroll
            for (int h = 0; h < 2; h++)
                res[2 * i + h] = fma2(pack2(c.x, c.y), x2[2 * i + h], pack2(e.x * blo(res[2 * i + h]), e.y * bhi(res[2 * i + h])));
        }
#pragma unroll
        for (int i = 0; i < 20; i++) asm volatile("" : "+r"(res[i]));
    }
    float acc0[64], acc1[44];
    float2 q[4];
    {
        uint4 f0, f1, f2, f3;
        auto xseq = [&](int kb) { return ring_pos(uw, kb, XLEAD) & 7; };
        auto step = [&](const uint4& f, uint64_t bd) {
            wg_fence();
            wgmma_rs128(acc0, f.x, f.y, f.z, f.w, bd, 1);
            wgmma_rs88(acc1, f.x, f.y, f.z, f.w, bd + 512, 1);
            wg_commit();
        };
        const uint32_t xa = sb + OFF_XR + wt * 16;
        const float2* const gs = &g_stats[(tile * 8 + 2 * t) * 64 + 16 * wq + g];
        zero(acc0); zero(acc1);
        uint32_t xs = 0;
        f0 = make_uint4(x2[0], x2[1], x2[2], x2[3]); f1 = make_uint4(x2[4], x2[5], x2[6], x2[7]);
        f2 = make_uint4(x2[8], x2[9], x2[10], x2[11]); f3 = make_uint4(x2[12], x2[13], x2[14], x2[15]);
#pragma unroll
        for (int i = 0; i < 4; i++) q[i] = make_float2(0.f, 0.f);
        mbar_spin(wempty + (9 & 7) * 8, 1);
        mbar_spin(wfull + (10 & 7) * 8, (10 >> 3) & 1);
#pragma unroll 1
        for (int kb = 0; kb < 10; kb++) {
            const uint32_t wn = 10 + 2 * kb;
            const uint64_t bd = dz + (((dsb + OFF_W + (wn & 7) * 16384) >> 4) | (256u << 16));
            step(f0, bd);
            wg_wait<1>();
            if (kb && lane == 0) mbar_arrive(wempty + ((wn - 1) & 7) * 8);
            lds128_if(kb, f2, xa + xs * 8192 + 4096); lds128_if(kb, f3, xa + xs * 8192 + 6144);
            const bool w1 = mbar_test(wfull + ((wn + 1) & 7) * 8, (wn >> 3) & 1), x1 = kb < 9 && mbar_test(xfull + (kb + 1) * 8, 0);
            step(f1, bd + 128);
            if (!w1) mbar_spin(wfull + ((wn + 1) & 7) * 8, (wn >> 3) & 1);
            step(f2, bd + 1024);
            if (lane < 2 && kb) mbar_arrive_after(xempty + xs * 8, f2.x, f3.x, nil);
            wg_wait<1>();
            if (lane == 0) mbar_arrive(wempty + (wn & 7) * 8);
            xs = xseq(kb + 1);
            if (x1) { f0 = lds128(xa + xs * 8192); f1 = lds128(xa + xs * 8192 + 2048); }
            const bool w2 = mbar_test(wfull + ((wn + 2) & 7) * 8, ((wn + 2) >> 3) & 1);
            step(f3, bd + 1152);
            if (kb < 9 && !x1) { xwait(kb + 1, 2); f0 = lds128(xa + xs * 8192); f1 = lds128(xa + xs * 8192 + 2048); }
            if (!w2) mbar_spin(wfull + ((wn + 2) & 7) * 8, ((wn + 2) >> 3) & 1);
            if (kb == 0) {
                TS(leader, 42 + uw)
#pragma unroll
                for (int i = 0; i < 4; i++) q[i] = ld_stat(gs + (i & 1) * 64 + 8 * (i >> 1));
            }
            if (kb == 4) {
                uint32_t it = 0;
                while (RARE(__any_sync(~0u, ((__float_as_uint(q[0].x) ^ ep) | (__float_as_uint(q[1].x) ^ ep) | (__float_as_uint(q[2].x) ^ ep) | (__float_as_uint(q[3].x) ^ ep)) & 1))) {
#pragma unroll
                    for (int i = 0; i < 4; i++) q[i] = ld_stat(gs + (i & 1) * 64 + 8 * (i >> 1));
                    SPIN_CHECK(49)
                }
                float a0 = q[0].x + q[1].x, b0 = q[0].y + q[1].y, a1 = q[2].x + q[3].x, b1 = q[2].y + q[3].y;
#pragma unroll
                for (int o = 1; o < 4; o *= 2) {
                    a0 += __shfl_xor_sync(~0u, a0, o); b0 += __shfl_xor_sync(~0u, b0, o);
                    a1 += __shfl_xor_sync(~0u, a1, o); b1 += __shfl_xor_sync(~0u, b1, o);
                }
                a0 *= 1.f / D_; a1 *= 1.f / D_;
                const float r0 = 0.5f * rsqrtf(fmaxf(b0 * (1.f / D_) - a0 * a0, 0.f) + 1e-5f), r1 = 0.5f * rsqrtf(fmaxf(b1 * (1.f / D_) - a1 * a1, 0.f) + 1e-5f);
                const uint32_t sel = t == 0 ? 0x1010 : t == 1 ? 0x4432 : 0x4444;
                if (t == 0) { sts32(sb + M_F1 + (64 * uw + 16 * wq + g) * 4, __float_as_uint(r0)); sts32(sb + M_F1 + (64 * uw + 16 * wq + g + 8) * 4, __float_as_uint(r1)); }
                q[2] = make_float2(8.f * 0.0356774081f * r0 * r0 * r0, 2.f * 0.7978845608f * r0);
                q[3] = make_float2(8.f * 0.0356774081f * r1 * r1 * r1, 2.f * 0.7978845608f * r1);
                q[1] = make_float2(__uint_as_float(__byte_perm(split2(-a0), 0, sel)), __uint_as_float(__byte_perm(split2(-a1), 0, sel)));
            }
            if (kb == 6) {
#pragma unroll
                for (int i = 0; i < 5; i++) stg128(&g_x1f[(tile * 8 + j) * 640 + i * 128 + wt], res[4 * i], res[4 * i + 1], res[4 * i + 2], res[4 * i + 3]);
            }
            if (kb == 8) asm volatile("fence.proxy.async.global;" ::: "memory");
            TR(leader, 10 * uw + kb)
        }
        const uint64_t fd = ((uint64_t)8 << 32) | ((dsb + OFF_W + 6 * 16384) >> 4);
        wg_fence();
        wgmma_rs128k(acc0, __float_as_uint(q[1].x), __float_as_uint(q[1].y), 0, 0, fd, 1);
        wgmma_rs88k(acc1, __float_as_uint(q[1].x), __float_as_uint(q[1].y), 0, 0, fd + 128, 1);
        wg_commit();
        if (lane == 0) {
            mbar_arrive(bars + B_XFREE * 8);
            asm volatile("mbarrier.arrive.shared::cluster.b64 _, [%0];" ::"r"(peer_addr(bars + B_XFREE * 8)) : "memory");
        }
    }
    const uint32_t recv = sb + recv_off(uw) + wt * 16;
    uint32_t ha[48] = {}, hb[48], hx[12];
    uint64_t wb = dz + (((dsb + OFF_W) >> 4) | (512u << 16));
    auto wdesc = [&](int n) { return wb + (n & 7) * 1024; };
    auto wwait = [&](int n) { mbar_spin(wfull + (n & 7) * 8, (n >> 3) & 1); };
    auto wfree = [&](int n) { if (lane == 0) mbar_arrive(wempty + (n & 7) * 8); };
    auto fresh = [&]() { wb += pp.nil; asm volatile("" : "+l"(wb)); };
    uint32_t pk[32];
    {
        float P0[64];
        const float2 r0 = q[2], r1 = q[3];
        const uint32_t ra = peer_addr(recv), rb = peer_addr(bars + (B_RECV + 4 * uw) * 8);
        auto conv32 = [&](const float* v, int b) {
#pragma unroll
            for (int i = 0; i < 4; i++) {
                ha[8 * b + 2 * i] = pack2(gelu2r(v[4 * i], r0), gelu2r(v[4 * i + 1], r0));
                ha[8 * b + 2 * i + 1] = pack2(gelu2r(v[4 * i + 2], r1), gelu2r(v[4 * i + 3], r1));
            }
#pragma unroll
            for (int s = 2 * b; s < 2 * b + 2; s++) st_peer(ra + s * 2048, ha[4 * s], ha[4 * s + 1], ha[4 * s + 2], ha[4 * s + 3], rb + (b >> 1) * 8);
        };
        auto fetch = [&](int k) {
            mbar_spin(bars + (B_RECV + 4 * uw + k) * 8, 0);
#pragma unroll
            for (int s = 4 * k; s < 4 * k + 4; s++) { const uint4 x = lds128(recv + s * 2048); hb[4 * s] = x.x; hb[4 * s + 1] = x.y; hb[4 * s + 2] = x.z; hb[4 * s + 3] = x.w; }
        };
        auto stage = [&](int n, const uint32_t* a, int steps, int sc) {
            wwait(n);
            wg_fence();
#pragma unroll
            for (int s = 0; s < steps; s++) wgmma_rs128(P0, a[4 * s], a[4 * s + 1], a[4 * s + 2], a[4 * s + 3], wdesc(n) + s * 128, sc || s);
            wg_commit();
        };
        wg_wait<0>();
        reg_fence(acc0); reg_fence(acc1);
        wfree(29); wfree(30);
        TS(leader, 44 + uw)
        uint32_t hr[6];
#pragma unroll
        for (int i = 0; i < 6; i++) {
            const float2 r = (i & 1) ? r1 : r0;
            hr[i] = pack2(gelu2r(acc1[32 + 2 * i], r), gelu2r(acc1[33 + 2 * i], r));
        }
        if (uw) mbar_spin(bars + B_XFREE * 8, 0);
        st_peer(ra + 24576, hr[0], hr[1], hr[2], hr[3], rb + 24);
        asm volatile("st.async.shared::cluster.mbarrier::complete_tx::bytes.v2.b32 [%0], {%1, %2}, [%3];" ::"r"(ra + 26624 - wt * 8), "r"(hr[4]), "r"(hr[5]), "r"(rb + 24) : "memory");
        conv32(&acc1[0], 4);
        conv32(&acc1[16], 5);
        TS(leader, 46 + uw)
        stage(31, &ha[32], 4, 0);
#pragma unroll
        for (int b = 0; b < 4; b++) {
            conv32(&acc0[16 * b], b);
            if (b == 3) {
                fetch(2);
                mbar_spin(bars + (B_RECV + 4 * uw + 3) * 8, 0);
                const uint4 x = lds128(recv + 24576);
                const uint2 y = lds64(recv + 26624 - wt * 8);
                const uint32_t hp[6] = {x.x, x.y, x.z, x.w, y.x, y.y};
#pragma unroll
                for (int i = 0; i < 6; i++) { hx[i] = (j & 1) ? hp[i] : hr[i]; hx[6 + i] = (j & 1) ? hr[i] : hp[i]; }
            }
            if (!(b & 1)) wwait(32 + (b >> 1));
            wg_fence();
#pragma unroll
            for (int s = 0; s < 2; s++) wgmma_rs128(P0, ha[8 * b + 4 * s], ha[8 * b + 4 * s + 1], ha[8 * b + 4 * s + 2], ha[8 * b + 4 * s + 3], wdesc(32 + (b >> 1)) + (2 * (b & 1) + s) * 128, 1);
            wg_commit();
            if (!(b & 1)) { wg_wait<1>(); wfree(31 + (b >> 1)); }
        }
        TR(leader, 64 + 10 * uw)
        fresh();
        stage(34, &hb[32], 4, 1); wg_wait<1>(); wfree(33);
        fetch(0);
        stage(35, hx, 3, 1); wg_wait<1>(); wfree(34);
        fetch(1);
        stage(36, &hb[0], 4, 1); wg_wait<1>(); wfree(35);
        stage(37, &hb[16], 4, 1); wg_wait<1>(); wfree(36);
        wg_wait<0>();
        reg_fence(P0);
        pack_part<64>(pk, P0, ep);
        uint32_t all = 0;
#pragma unroll
        for (int i = 0; i < 32; i++) all |= pk[i];
        if (lane == 0) mbar_arrive_after(wempty + (37 & 7) * 8, all, 0, nil);
        TR(leader, 65 + 10 * uw)
    }
    {
        uint4* const dst = g_part + (size_t)(tile * 8 + j) * 5120 + wt;
        const uint4* const src = g_part + (size_t)tile * 40960 + j * 512 + wt;
        float F[2][32];
        uint4 gb[4];
        float rr[2];
        float2 gf[8];
        uint4 base[4], u1[4], u2[4], u3[4];
#pragma unroll
        for (int c = 2; c < 5; c++) {
            float (&P)[32] = F[c & 1];
            fresh();
#pragma unroll
            for (int s = 0; s < 27; s++) {
                const int e = s < 8 ? 0 : s < 15 ? 1 : s < 23 ? 2 : 3, o = s - (e == 0 ? 0 : e == 1 ? 8 : e == 2 ? 15 : 23), n = 30 + 4 * c + e;
                const uint32_t* a = s < 12 ? &ha[4 * s] : s < 15 ? &hx[4 * (s - 12)] : &hb[4 * (s - 15)];
                if (o == 0) wwait(n);
                if (o == 0 || s == 1) wg_fence();
                wgmma_rs64(P, a[0], a[1], a[2], a[3], wdesc(n) + o * 128, s);
                if (o == 0) { wg_commit(); wg_wait<1>(); if (c > 2 || s) wfree(n - 1); }
                if (s == 0 && c > 2) { reg_fence(F[~c & 1]); pack_part<32>(pk, F[~c & 1], ep); }
                if (c == 2 && s % 3 == 0 && s < 24) st_part(dst + g4_block(s / 12, j) * 512 + (s / 3 & 3) * 128, &pk[4 * (s / 3)]);
                if (c == 3 && s % 4 == 1 && s < 16) st_part(dst + g4_block(2, j) * 512 + s / 4 * 128, &pk[4 * (s / 4)]);
                if (c == 4 && s % ST3 == 0 && s < 4 * ST3) st_part(dst + g4_block(3, j) * 512 + s / ST3 * 128, &pk[4 * (s / ST3)]);
                if (c == 4 && s >= 4 && s < 8) base[s - 4] = ldcg128(&g_x1f[(tile * 8 + j) * 640 + (s - 4) * 128 + wt]);
                if (c == 4 && s >= 19 && s < 23) { gf[2 * s - 38] = lds64f(sb + M_GB + (16 * (s - 19) + 2 * t) * 4); gf[2 * s - 37] = lds64f(sb + M_GB + (16 * (s - 19) + 8 + 2 * t) * 4); }
                if (c == 4 && s >= 12 && s < 14) rr[s - 12] = __uint_as_float(lds32(sb + M_F1 + (64 * uw + 16 * wq + g + 8 * (s - 12)) * 4));
                if (c == 4 && s >= 8 && s < 12) u1[s - 8] = ld_part(src + (j ^ 6) * 5120 + (s - 8) * 128);
                if (c == 4 && s >= 15 && s < 19) u2[s - 15] = ld_part(src + (j ^ 4) * 5120 + (s - 15) * 128);
                if (c == 4 && s >= LD3 && s < LD3 + 4) u3[s - LD3] = ld_part(src + (j ^ 2) * 5120 + (s - LD3) * 128);
                if (27 * (c - 2) + s == R_GATE && lane == 0) mbar_arrive(bars + (B_RING + uw) * 8);
                if (s == 7 || s == 14 || s == 22 || s == 26) wg_commit();
                if (c == 4) { TR(leader && s == 7, 68 + 10 * uw) TR(leader && s == 14, 69 + 10 * uw) TR(leader && s == 22, 70 + 10 * uw) }
            }
            TR(leader, 64 + c + (c == 4 ? 3 : 0) + 10 * uw)
        }
        float (&O)[32] = F[0];
#pragma unroll
        for (int i = 0; i < 4; i++) gb[i] = scale16(gf[2 * i], gf[2 * i + 1], rr[0], rr[1]);
        uint32_t it = 0;
        while (__any_sync(~0u, (stale4(u1, ep) | stale4(u2, ep) | stale4(u3, ep)) & 1)) {
            ld_part4(u1, src + (j ^ 6) * 5120, 128); ld_part4(u2, src + (j ^ 4) * 5120, 128); ld_part4(u3, src + (j ^ 2) * 5120, 128);
            STALE(6)
            SPIN_CHECK(58)
        }
        TR(leader, 73 + 10 * uw)
#pragma unroll
        for (int i = 0; i < 4; i++) u1[i] = add2(add2(u1[i], u2[i]), u3[i]);
        TS(leader, 50 + uw)
        wg_wait<0>();
        reg_fence(O);
        TS(leader, 48 + uw)
        const uint32_t so = sb + recv_off(uw) + wq * 2048;
#pragma unroll
        for (int i = 0; i < 4; i++) {
            const float* o = &O[8 * i];
            const uint4 r = fin16(add2(u1[i], make_uint4(pack2(o[0], o[1]), pack2(o[2], o[3]), pack2(o[4], o[5]), pack2(o[6], o[7]))), base[i], gb[i]);
            stsm4(so + (lane & 15) * 128 + (((2 * i + (lane >> 4)) ^ (lane & 7)) << 4), r.x, r.y, r.z, r.w);
        }
        TR4(leader, 100 + uw)
        __syncwarp();
#pragma unroll
        for (int i = 0; i < 4; i++) {
            const int row = (lane >> 3) + 4 * i;
            stg128(out + (size_t)(row0 + row) * D_ + 64 * j + 8 * (lane & 7), lds128(so + row * 128 + (((lane & 7) ^ (row & 7)) << 4)));
        }
        TS(leader, 24 + uw)
        warp_arrive(bars + B_OWN * 8);
    }
}

typedef CUresult (*EncFn)(CUtensorMap*, CUtensorMapDataType, cuuint32_t, void*, const cuuint64_t*, const cuuint64_t*, const cuuint32_t*,
                          const cuuint32_t*, CUtensorMapInterleave, CUtensorMapSwizzle, CUtensorMapL2promotion, CUtensorMapFloatOOBfill);

static void enc(EncFn fn, CUtensorMap* m, void* p, int rank, const cuuint64_t* dims, const cuuint64_t* strides, const cuuint32_t* box, bool plain = false) {
    const CUtensorMapSwizzle sw = box[0] > 64 || plain ? CU_TENSOR_MAP_SWIZZLE_NONE : CU_TENSOR_MAP_SWIZZLE_128B;
    cuuint32_t es[5] = {1, 1, 1, 1, 1};
    CUresult r = fn(m, CU_TENSOR_MAP_DATA_TYPE_BFLOAT16, rank, p, dims, strides, box, es, CU_TENSOR_MAP_INTERLEAVE_NONE, sw,
                    CU_TENSOR_MAP_L2_PROMOTION_L2_128B, CU_TENSOR_MAP_FLOAT_OOB_FILL_NONE);
    (void)r;
}
static void enc2(EncFn fn, CUtensorMap* m, void* p, uint64_t cols, uint64_t rows, uint32_t bc, uint32_t br, bool plain = false) {
    cuuint64_t dims[2] = {cols, rows}, st[1] = {cols * 2};
    cuuint32_t box[2] = {bc, br};
    enc(fn, m, p, 2, dims, st, box, plain);
}

extern "C" void kernel_launch(void* const* d_in, const int* in_sizes, int n_in, void* d_out, int out_size) {
    static Maps mp;
    static Ptrs pp;
    static void* cached[13];
    bool same = true;
    for (int i = 0; i < 13; i++) same = same && (cached[i] == d_in[i]);
    if (!same) {
        void* fnp = nullptr;
        cudaDriverEntryPointQueryResult qr;
        cudaGetDriverEntryPoint("cuTensorMapEncodeTiled", &fnp, cudaEnableDefault, &qr);
        EncFn fn = (EncFn)fnp;
        cudaGetSymbolAddress((void**)&pp.s, g_scratch);
        void *x1T = g_x1T, *t = g_t;
        cuuint64_t dq[3] = {64, S_, 10}, sq[2] = {D_ * 2, 128};
        cuuint32_t bq[3] = {64, 16, 10};
        enc(fn, &mp.q, d_in[0], 3, dq, sq, bq);
        enc2(fn, &mp.k, d_in[1], D_, S_, 80, 67); enc2(fn, &mp.v, d_in[2], D_, S_, 80, 64);
        enc2(fn, &mp.qT, g_qT, 16 * D_, 128, 80, 128);
        enc2(fn, &mp.x[0], x1T, S_, D_, 64, 64); enc2(fn, &mp.x[1], (bf16*)t + 2 * D_, D_, S_, 64, 64);
        enc2(fn, &mp.x[2], g_x2f, 64, 320 * 64, 64, 64, true);
        enc2(fn, &mp.w1, d_in[7], D_, D_, 64, 64); enc2(fn, &mp.w1h, d_in[7], D_, D_, 64, 160); enc2(fn, &mp.w3h, d_in[9], F_, D_, 64, 160);
        enc2(fn, &mp.wmod, d_in[12], 6 * D_, D_, 64, 160);
        const cuuint64_t R = D_ * 2;
        cuuint64_t da[5] = {D_, 2, 4, 4, 16}, sa[4] = {R, 8 * R, 2 * R, 32 * R}, db[5] = {D_, 2, 2, 4, 8}, sb[4] = {R, 8 * R, 2 * R, 16 * R};
        cuuint32_t ba[5] = {64, 2, 4, 4, 4}, bb[5] = {64, 2, 2, 4, 8};
        enc(fn, &mp.w2a, d_in[8], 5, da, sa, ba); enc(fn, &mp.w2b, (bf16*)d_in[8] + 512 * D_, 5, db, sb, bb);
        cuuint64_t dw[3] = {64, D_, 27}, sw[2] = {F_ * 2, 128};
        cuuint32_t bw[3] = {64, 32, 3};
        enc(fn, &mp.w3a, d_in[9], 3, dw, sw, bw);
        enc2(fn, &mp.w3b, d_in[9], F_, D_, 24, 32);
        enc2(fn, &mp.w4[0], d_in[10], D_, F_, 64, 64); enc2(fn, &mp.w4[1], d_in[10], D_, F_, 64, 48);
        pp.q = (const bf16*)d_in[0]; pp.w_mod = (const bf16*)d_in[12]; pp.shift_k = (const bf16*)d_in[3];
        pp.ssm_k = (const bf16*)d_in[4]; pp.ssm_D = (const bf16*)d_in[5]; pp.w1 = (const bf16*)d_in[7]; pp.w2 = (const bf16*)d_in[8];
        pp.w4 = (const bf16*)d_in[10]; pp.c = (const bf16*)d_in[11];
        cudaFuncSetAttribute(fused_kernel, cudaFuncAttributeMaxDynamicSharedMemorySize, SMEM_BYTES);
        for (int i = 0; i < 13; i++) cached[i] = d_in[i];
    }
    fused_kernel<<<NCTA, NTHR, SMEM_BYTES, cudaStreamPerThread>>>(pp, (bf16*)d_out, mp);
}
```

```cpp
#include <cuda_runtime.h>
#include <cuda_bf16.h>
#include <cuda.h>
#include <stdint.h>
#include <stdio.h>

typedef __nv_bfloat16 bf16;

constexpr int S_ = 2048, D_ = 640, F_ = 1728;
constexpr int NCTA = 132, NTHR = 512;

constexpr int TAB_BYTES = 9216, VEC_BYTES = 1440;
struct Counters {
    unsigned kv[8 * 32];
    unsigned q[4 * 32], x[4 * 32];
    unsigned wr[32], tab[32], uv[32], cs[32], cs2[32], done[32];
    unsigned g1[32 * 32];
    unsigned g2[32 * 32];
};
struct Scratch {
    Counters cnt;
    unsigned epoch;
    alignas(1024) bf16 qst[2 * S_];
    alignas(1024) uint4 wr[2 * 8 * 10 * 128];
    alignas(1024) uint2 mod[2 * 6 * D_];
    alignas(1024) uint4 tab[(TAB_BYTES + 8 * VEC_BYTES) / 16];
    alignas(1024) float uv[2 * 3 * D_];
    alignas(1024) float cs3[2 * 1920];
    alignas(1024) uint4 cs3b[8 * 216];
    alignas(1024) float2 stats[32 * 8 * 64];
    alignas(1024) bf16 kvT[D_ * S_];
    alignas(1024) bf16 qT[D_ * S_];
    alignas(1024) bf16 x1T[D_ * S_];
    alignas(1024) bf16 t[(S_ + 4) * D_];
    alignas(1024) uint4 x2f[32 * 40 * 128];
    alignas(1024) uint4 x1f[32 * 8 * 5 * 128];
    alignas(1024) uint4 part[32 * 8 * 10 * 4 * 128];
};
__device__ Scratch g_scratch;
#define g_kvT (pp.s->kvT)
#define g_qT (pp.s->qT)
#define g_x1T (pp.s->x1T)
#define g_qst (pp.s->qst)
#define g_t (pp.s->t)
#define g_x2f (pp.s->x2f)
#define g_x1f (pp.s->x1f)
#define g_part (pp.s->part)
#define g_wr (pp.s->wr)
#define g_mod (pp.s->mod)
#define g_tab (pp.s->tab)
#define g_uv (pp.s->uv)
#define g_cs3 (pp.s->cs3)
#define g_cs3b (pp.s->cs3b)
#define g_stats (pp.s->stats)
#define g_cnt (pp.s->cnt)
#define g_epoch (pp.s->epoch)

struct Maps {
    CUtensorMap k, v, q;
    CUtensorMap qT;
    CUtensorMap x[3];
    CUtensorMap w1, w1h, w3h, wmod;
    CUtensorMap w2a, w2b;
    CUtensorMap w3a, w3b;
    CUtensorMap w4[2];
};

struct Ptrs {
    Scratch* s;
    uint64_t nil;
    const bf16 *q, *w_mod, *shift_k, *ssm_k, *ssm_D, *w1, *w2, *w4, *c;
};

constexpr int OFF_W = 0;
constexpr int OFF_XR = 131072;
constexpr int OFF_REM = 196608;
constexpr int OFF_TAB = OFF_REM + 5 * 4096;
constexpr int OFF_ROW = OFF_TAB + 4608;
constexpr int OFF_F1 = OFF_ROW + 4096;
constexpr int RECV_BYTES = 30720;
constexpr int OFF_M = OFF_REM + RECV_BYTES;
constexpr int OFF_OUT = OFF_XR + 32768;
static_assert(OFF_F1 + 1280 <= OFF_M, "G1 map");
constexpr int OFF_ST = 0;
constexpr int OFF_SSM = 20480;
constexpr int OFF_WM = 0;
constexpr int OFF_QIN = 49152;
constexpr int OFF_QT = 49152;
constexpr int OFF_Z = OFF_TAB;
constexpr int OFF_RING = 80896;
constexpr int OFF_KIN = OFF_RING, OFF_VIN = OFF_KIN + 2 * 10752;
constexpr int OFF_CH = OFF_RING + 3 * 16384, CH_BYTES = 13312, OFF_P = 5120;
static_assert(OFF_RING + 5 * 16384 <= OFF_CH + 3 * CH_BYTES && OFF_CH + 5 * CH_BYTES <= OFF_REM, "the last two rings replace channels 0..2");
constexpr int M_BAR = OFF_M;
constexpr int M_F1 = OFF_M + 832;
constexpr int M_GB = M_F1 + 1280, M_C = M_GB + 320, M_SB = M_C + 320, M_CI = M_SB + 320;
constexpr int M_KS = M_CI + 320;
constexpr int M_AB = M_KS + 160;
constexpr int M_EP = M_AB + 80;
constexpr int M_SINK = M_EP + 16;
constexpr int M_NUL = M_SINK + 16;
constexpr int M_TS = M_NUL + 128;
constexpr int SMEM_BYTES = M_TS;
static_assert(SMEM_BYTES <= 232448, "smem");

enum { B_WFULL = 0, B_WEMPTY = 8, B_XEMPTY = 16, B_XFULL = 24  ,
       B_RAW = 44, B_QIN = 45, B_SSM = 46, B_VEC = 47, B_VEC3 = 48, B_WM = 49, B_TAB = 50, B_QRDY = 51,
       B_MODR = 52, B_RAW2 = 53, B_RAW3 = 54, B_GATE = 56, B_SUMS = 62, B_RECV = 64  ,
       B_LAND = 72, B_AGAIN = 80, B_RETRY = 84,
       B_XS = 88, B_R1 = 89, B_BK = 90, B_KVS = 91,
       B_XFREE = 92, B_OWN = 93, B_IN = 94,
       B_RING = 96   };
#define T_KVB 1800
#define T_SSM 4200
#define PF_T0 5900
#define PF_DT 420
#define Q_UNROLL 1
#define HELP_T 1000
#define R_GATE 34
#define REG_AUX 40
#define REG_SVC 40
#define REG_MMA 216
#define STR2(x) #x
#define STR(x) STR2(x)
#define ST3 1
#define LD3 23
#define GATE_W2 7
#define GATE_W3 27
#define GATE_W3B 37
#define W3_N2 13
#define LEAD2 5
#define LEAD1 4
#define XLEAD 3

#define SPIN_FAIL(code) __trap();
#define SPIN_LIMIT (1u << 22)
#define STALE(c)
#define STALE1(c)
#define TS(c, i)
#define TG(c, i)
#define TR(c, i)
#define TR2(c, i)
#define TR4(c, i)
#define TR5(c, i)
#define SPIN_CHECK(code) asm volatile("" ::"r"(it));
#define RARE(x) __builtin_expect((x) != 0, 0)
__device__ __forceinline__ uint32_t s2u(const void* p) { return (uint32_t)__cvta_generic_to_shared(p); }
__device__ __forceinline__ bool elect() {
    uint32_t p;
    asm volatile("{.reg .pred P; elect.sync _|P, 0xffffffff; selp.u32 %0,1,0,P;}" : "=r"(p));
    return p != 0;
}
__device__ __forceinline__ void mbar_init(uint32_t b, uint32_t n) { asm volatile("mbarrier.init.shared.b64 [%0], %1;" ::"r"(b), "r"(n)); }
__device__ __forceinline__ void mbar_expect(uint32_t b, uint32_t bytes) {
    asm volatile("mbarrier.arrive.expect_tx.shared.b64 _, [%0], %1;" ::"r"(b), "r"(bytes) : "memory");
}
__device__ __forceinline__ void mbar_arrive(uint32_t b) { asm volatile("mbarrier.arrive.shared.b64 _, [%0];" ::"r"(b) : "memory"); }
__device__ __forceinline__ void mbar_arrive_after(uint32_t b, uint32_t v0, uint32_t v1, uint32_t nil) { mbar_arrive(b + ((v0 | v1) & nil)); }
__device__ __forceinline__ void warp_arrive(uint32_t b) { __syncwarp(); if (elect()) mbar_arrive(b); }
__device__ __forceinline__ uint32_t peer_addr(uint32_t a) {
    uint32_t r;
    asm("{\n.reg .b32 q;\nmov.u32 q, %%cluster_ctarank;\nxor.b32 q, q, 1;\nmapa.shared::cluster.u32 %0, %1, q;\n}" : "=r"(r) : "r"(a));
    return r;
}
__device__ __forceinline__ bool mbar_test(uint32_t b, uint32_t parity) {
    uint32_t ok;
    asm volatile("{.reg .pred P; mbarrier.test_wait.parity.shared.b64 P, [%1], %2; selp.u32 %0,1,0,P;}" : "=r"(ok) : "r"(b), "r"(parity) : "memory");
    return ok != 0;
}
__device__ __forceinline__ bool mbar_try(uint32_t b, uint32_t parity) {
    uint32_t ok;
    asm volatile("{.reg .pred P; mbarrier.try_wait.parity.shared.b64 P, [%1], %2; selp.u32 %0,1,0,P;}" : "=r"(ok) : "r"(b), "r"(parity) : "memory");
    return ok != 0;
}
__device__ __forceinline__ void mbar_wait(uint32_t b, uint32_t parity) {
    if (__all_sync(0xffffffffu, mbar_try(b, parity))) return;
    uint32_t it = 0;
    while (!__all_sync(0xffffffffu, mbar_try(b, parity))) { if (++it > SPIN_LIMIT) SPIN_FAIL((b >> 3) & 63) }
}
__device__ __forceinline__ void mbar_spin(uint32_t b, uint32_t parity) {
    asm volatile("{\n.reg .pred P;\nSPIN:\nmbarrier.try_wait.parity.shared.b64 P, [%0], %1;\n@!P bra.uni SPIN;\n}" ::"r"(b), "r"(parity) : "memory");
}
__device__ __forceinline__ void bar_sync(int id, int n) { asm volatile("bar.sync %0, %1;" ::"r"(id), "r"(n) : "memory"); }
__device__ __forceinline__ void fence_async_smem() { asm volatile("fence.proxy.async.shared::cta;" ::: "memory"); }
__device__ __forceinline__ void wait_cnt(const unsigned* p, unsigned target, bool tagged = false) {
    unsigned v, it = 0;
    do {
        asm volatile("ld.relaxed.gpu.global.u32 %0, [%1];" : "=r"(v) : "l"(p) : "memory");
        SPIN_CHECK(60 + (target & 3))
    } while (!__all_sync(0xffffffffu, v >= target));
    if (!tagged) asm volatile("fence.acquire.gpu;" ::: "memory");
}
__device__ __forceinline__ void signal_cnt(unsigned* p, int lane, int n, bool tagged = false) {
    if (tagged) asm volatile("{\n.reg .pred P;\nsetp.lt.s32 P, %1, %2;\n@P red.relaxed.gpu.global.add.u32 [%0], %3;\n}" ::"l"(p), "r"(lane), "r"(n), "r"(1) : "memory");
    else if (lane < n) asm volatile("red.release.gpu.global.add.u32 [%0], 1;" ::"l"(p) : "memory");
    __syncwarp();
}
__device__ __forceinline__ uint32_t clock_lo() { uint32_t c; asm volatile("mov.u32 %0, %%clock;" : "=r"(c)); return c; }
__device__ __forceinline__ void wait_clock(uint32_t c0, uint32_t t) {
    asm volatile("{\n.reg .pred P;\n.reg .b32 c;\nWAIT:\nnanosleep.u32 20;\nmov.u32 c, %%clock;\nsub.u32 c, c, %0;\nsetp.lt.u32 P, c, %1;\n@P bra.uni WAIT;\n}" ::"r"(c0), "r"(t) : "memory");
}
__device__ __forceinline__ void tma_ld2(uint32_t dst, const CUtensorMap* m, int c0, int c1, uint32_t bar) {
    asm volatile("cp.async.bulk.tensor.2d.shared::cluster.global.mbarrier::complete_tx::bytes [%0], [%1, {%3, %4}], [%2];"
                 ::"r"(dst), "l"(m), "r"(bar), "r"(c0), "r"(c1) : "memory");
}
__device__ __forceinline__ void tma_ld3(uint32_t dst, const CUtensorMap* m, int c0, int c1, int c2, uint32_t bar) {
    asm volatile("cp.async.bulk.tensor.3d.shared::cluster.global.mbarrier::complete_tx::bytes [%0], [%1, {%3, %4, %5}], [%2];"
                 ::"r"(dst), "l"(m), "r"(bar), "r"(c0), "r"(c1), "r"(c2) : "memory");
}
__device__ __forceinline__ void tma_ld5(uint32_t dst, const CUtensorMap* m, int col, int blk, uint32_t bar) {
    asm volatile("cp.async.bulk.tensor.5d.shared::cluster.global.mbarrier::complete_tx::bytes [%0], [%1, {%3, %4, %4, %4, %5}], [%2];"
                 ::"r"(dst), "l"(m), "r"(bar), "r"(col), "r"(0), "r"(blk) : "memory");
}
__device__ __forceinline__ void bulk_ld(uint32_t dst, const void* src, uint32_t bytes, uint32_t bar) {
    asm volatile("cp.async.bulk.shared::cluster.global.mbarrier::complete_tx::bytes [%0], [%1], %2, [%3];" ::"r"(dst), "l"(src), "r"(bytes), "r"(bar) : "memory");
}
__device__ __forceinline__ void l2_prefetch(const void* p, uint32_t bytes) {
    asm volatile("cp.async.bulk.prefetch.L2.global [%0], %1;" ::"l"(p), "r"(bytes) : "memory");
}
__device__ __forceinline__ void wg_fence() { asm volatile("wgmma.fence.sync.aligned;" ::: "memory"); }
__device__ __forceinline__ void wg_commit() { asm volatile("wgmma.commit_group.sync.aligned;" ::: "memory"); }
template <int N> __device__ __forceinline__ void wg_wait() { asm volatile("wgmma.wait_group.sync.aligned %0;" ::"n"(N) : "memory"); }
template <int N> __device__ __forceinline__ void reg_fence(float (&d)[N]) {
#pragma unroll
    for (int i = 0; i < N; i++) asm volatile("" : "+f"(d[i])::"memory");
}
template <int N> __device__ __forceinline__ void zero(float (&d)[N]) {
#pragma unroll
    for (int i = 0; i < N; i++) asm volatile("mov.b32 %0, 0;" : "=f"(d[i]));
}
__device__ __forceinline__ uint32_t lds32(uint32_t a) { uint32_t v; asm volatile("ld.shared.b32 %0, [%1];" : "=r"(v) : "r"(a)); return v; }
__device__ __forceinline__ uint2 lds64(uint32_t a) { uint2 v; asm volatile("ld.shared.v2.b32 {%0,%1}, [%2];" : "=r"(v.x), "=r"(v.y) : "r"(a)); return v; }
__device__ __forceinline__ float2 lds64f(uint32_t a) { float2 v; asm volatile("ld.shared.v2.f32 {%0,%1}, [%2];" : "=f"(v.x), "=f"(v.y) : "r"(a)); return v; }
__device__ __forceinline__ void sts32(uint32_t a, uint32_t v) { asm volatile("st.shared.b32 [%0], %1;" ::"r"(a), "r"(v) : "memory"); }
__device__ __forceinline__ void sts64f(uint32_t a, float x, float y) { asm volatile("st.shared.v2.f32 [%0], {%1,%2};" ::"r"(a), "f"(x), "f"(y) : "memory"); }
__device__ __forceinline__ void sts128(uint32_t a, uint32_t x, uint32_t y, uint32_t z, uint32_t w) {
    asm volatile("st.shared.v4.b32 [%0], {%1,%2,%3,%4};" ::"r"(a), "r"(x), "r"(y), "r"(z), "r"(w) : "memory");
}
__device__ __forceinline__ void sts128f(uint32_t a, float x, float y, float z, float w) {
    asm volatile("st.shared.v4.f32 [%0], {%1,%2,%3,%4};" ::"r"(a), "f"(x), "f"(y), "f"(z), "f"(w) : "memory");
}
__device__ __forceinline__ uint4 lds128(uint32_t a) {
    uint4 v;
    asm volatile("ld.shared.v4.b32 {%0,%1,%2,%3}, [%4];" : "=r"(v.x), "=r"(v.y), "=r"(v.z), "=r"(v.w) : "r"(a) : "memory");
    return v;
}
__device__ __forceinline__ void lds128_if(int p, uint4& v, uint32_t a) {
    asm volatile("{\n.reg .pred p;\nsetp.ne.s32 p, %5, 0;\n@p ld.shared.v4.b32 {%0,%1,%2,%3}, [%4];\n}" : "+r"(v.x), "+r"(v.y), "+r"(v.z), "+r"(v.w) : "r"(a), "r"(p) : "memory");
}
__device__ __forceinline__ float4 lds128f(uint32_t a) {
    float4 v;
    asm volatile("ld.shared.v4.f32 {%0,%1,%2,%3}, [%4];" : "=f"(v.x), "=f"(v.y), "=f"(v.z), "=f"(v.w) : "r"(a) : "memory");
    return v;
}
__device__ __forceinline__ void stg128(void* p, uint32_t x, uint32_t y, uint32_t z, uint32_t w) {
    asm volatile("st.global.v4.b32 [%0], {%1,%2,%3,%4};" ::"l"(p), "r"(x), "r"(y), "r"(z), "r"(w) : "memory");
}
__device__ __forceinline__ void stg128(void* p, uint4 v) { stg128(p, v.x, v.y, v.z, v.w); }
__device__ __forceinline__ void stg128_if(void* p, uint4 v, int on) {
    asm volatile("{\n.reg .pred p;\nsetp.ne.s32 p, %5, 0;\n@p st.global.v4.b32 [%0], {%1,%2,%3,%4};\n}" ::"l"(p), "r"(v.x), "r"(v.y), "r"(v.z), "r"(v.w), "r"(on) : "memory");
}
__device__ __forceinline__ void stg64(void* p, uint32_t x, uint32_t y) { asm volatile("st.global.v2.b32 [%0], {%1,%2};" ::"l"(p), "r"(x), "r"(y) : "memory"); }
__device__ __forceinline__ void stsm4(uint32_t a, uint32_t r0, uint32_t r1, uint32_t r2, uint32_t r3) {
    asm volatile("stmatrix.sync.aligned.m8n8.x4.shared.b16 [%0], {%1,%2,%3,%4};" ::"r"(a), "r"(r0), "r"(r1), "r"(r2), "r"(r3) : "memory");
}
__device__ __forceinline__ void stsm4t(uint32_t a, uint32_t r0, uint32_t r1, uint32_t r2, uint32_t r3) {
    asm volatile("stmatrix.sync.aligned.m8n8.x4.trans.shared.b16 [%0], {%1,%2,%3,%4};" ::"r"(a), "r"(r0), "r"(r1), "r"(r2), "r"(r3) : "memory");
}
__device__ __forceinline__ void ldsm4t_if(bool p, uint32_t a, uint32_t* r) {
    asm volatile("{\n.reg .pred p;\nsetp.ne.u32 p, %5, 0;\n@p ldmatrix.sync.aligned.m8n8.x4.trans.shared.b16 {%0,%1,%2,%3}, [%4];\n}"
                 : "+r"(r[0]), "+r"(r[1]), "+r"(r[2]), "+r"(r[3]) : "r"(a), "r"((uint32_t)p) : "memory");
}
__device__ __forceinline__ void ldsm4t(uint32_t a, uint32_t& r0, uint32_t& r1, uint32_t& r2, uint32_t& r3) {
    asm volatile("ldmatrix.sync.aligned.m8n8.x4.trans.shared.b16 {%0,%1,%2,%3}, [%4];" : "=r"(r0), "=r"(r1), "=r"(r2), "=r"(r3) : "r"(a) : "memory");
}
__device__ __forceinline__ uint32_t pack2(float lo, float hi) {
    uint32_t r;
    asm("cvt.rn.bf16x2.f32 %0, %1, %2;" : "=r"(r) : "f"(hi), "f"(lo));
    return r;
}
__device__ __forceinline__ uint32_t mul2(uint32_t a, uint32_t b) { uint32_t r; asm("mul.rn.bf16x2 %0, %1, %2;" : "=r"(r) : "r"(a), "r"(b)); return r; }
__device__ __forceinline__ uint32_t fma2(uint32_t a, uint32_t b, uint32_t c) { uint32_t r; asm("fma.rn.bf16x2 %0, %1, %2, %3;" : "=r"(r) : "r"(a), "r"(b), "r"(c)); return r; }
__device__ __forceinline__ uint32_t add2(uint32_t a, uint32_t b) { uint32_t r; asm("add.rn.bf16x2 %0, %1, %2;" : "=r"(r) : "r"(a), "r"(b)); return r; }
__device__ __forceinline__ void hmma(float (&d)[4], uint32_t a0, uint32_t a1, uint32_t a2, uint32_t a3, uint32_t b0, uint32_t b1) {
    asm volatile("mma.sync.aligned.m16n8k16.row.col.f32.bf16.bf16.f32 {%0,%1,%2,%3}, {%4,%5,%6,%7}, {%8,%9}, {%0,%1,%2,%3};"
        : "+f"(d[0]), "+f"(d[1]), "+f"(d[2]), "+f"(d[3]) : "r"(a0), "r"(a1), "r"(a2), "r"(a3), "r"(b0), "r"(b1));
}
__device__ __forceinline__ float blo(uint32_t w) { return __uint_as_float(w << 16); }
__device__ __forceinline__ float bhi(uint32_t w) { return __uint_as_float(w & 0xffff0000u); }
__device__ __forceinline__ float rbf(float x) { return __bfloat162float(__float2bfloat16_rn(x)); }
__device__ __forceinline__ uint32_t ldg32(const void* p) { uint32_t v; asm volatile("ld.global.nc.b32 %0, [%1];" : "=r"(v) : "l"(p)); return v; }
__device__ __forceinline__ uint2 ldg64(const void* p) { uint2 v; asm volatile("ld.global.nc.v2.b32 {%0,%1}, [%2];" : "=r"(v.x), "=r"(v.y) : "l"(p)); return v; }
__device__ __forceinline__ uint4 ldg128(const void* p) {
    uint4 v;
    asm volatile("ld.global.nc.v4.b32 {%0,%1,%2,%3}, [%4];" : "=r"(v.x), "=r"(v.y), "=r"(v.z), "=r"(v.w) : "l"(p));
    return v;
}
__device__ __forceinline__ uint4 ldcg128(const void* p) {
    uint4 v;
    asm volatile("ld.global.cg.v4.u32 {%0,%1,%2,%3}, [%4];" : "=r"(v.x), "=r"(v.y), "=r"(v.z), "=r"(v.w) : "l"(p) : "memory");
    return v;
}
__device__ __forceinline__ float4 ldcg128f(const void* p) {
    float4 v;
    asm volatile("ld.global.cg.v4.f32 {%0,%1,%2,%3}, [%4];" : "=f"(v.x), "=f"(v.y), "=f"(v.z), "=f"(v.w) : "l"(p) : "memory");
    return v;
}
__device__ __forceinline__ float2 ldcg64f(const void* p) { float2 v; asm volatile("ld.global.cg.v2.f32 {%0,%1}, [%2];" : "=f"(v.x), "=f"(v.y) : "l"(p) : "memory"); return v; }
__device__ __forceinline__ float ldcg32f(const void* p) { float v; asm volatile("ld.global.cg.f32 %0, [%1];" : "=f"(v) : "l"(p) : "memory"); return v; }
__device__ __forceinline__ float2 ld_stat(const float2* p) {
    float2 v;
    asm volatile("{\n.reg .b64 q;\nld.relaxed.gpu.global.b64 q, [%2];\nmov.b64 {%0, %1}, q;\n}" : "=f"(v.x), "=f"(v.y) : "l"(p) : "memory");
    return v;
}
__device__ __forceinline__ uint32_t ld_cold(const unsigned* p) { uint32_t v; asm volatile("ld.relaxed.gpu.global.u32 %0, [%1];" : "=r"(v) : "l"(p) : "memory"); return v; }
__device__ __forceinline__ uint2 ld_mod(const uint2* p) {
    uint64_t v;
    asm volatile("ld.relaxed.gpu.global.b64 %0, [%1];" : "=l"(v) : "l"(p) : "memory");
    return make_uint2((uint32_t)v, (uint32_t)(v >> 32));
}
__device__ __forceinline__ float silu(float x) {
    float e, r;
    asm("ex2.approx.ftz.f32 %0, %1;" : "=f"(e) : "f"(x * -1.4426950408889634f));
    asm("rcp.approx.ftz.f32 %0, %1;" : "=f"(r) : "f"(1.f + e));
    return x * r;
}
__device__ __forceinline__ float gelu2(float h) {
    float u = h * fmaf(h * h, 8.f * 0.0356774081f, 2.f * 0.7978845608f);
    float th;
    asm("tanh.approx.f32 %0, %1;" : "=f"(th) : "f"(u));
    return fmaf(h, th, h);
}
__device__ __forceinline__ float gelu2r(float a, float2 k) {
    float th;
    asm("tanh.approx.f32 %0, %1;" : "=f"(th) : "f"(a * fmaf(a * a, k.x, k.y)));
    return fmaf(a, th, a);
}

__device__ __forceinline__ void conv_channel(float (&d)[64], uint32_t pa, uint64_t db) {
    asm volatile("{\n.reg .b32 a0, a1, a2, a3, b0, b1, b2, b3, t0, t1;\n.reg .b64 d;\nld.shared.b32 a0, [%64];\nld.shared.b32 a1, [%64+128];\nld.shared.b32 a2, [%64+-128];\nmov.b32 a3, a0;\n"
        "ld.shared.b32 t0, [%64+256];\nld.shared.b32 t1, [%64+384];\nadd.s64 d, %65, 0;\nwgmma.fence.sync.aligned;\nwgmma.mma_async.sync.aligned.m64n128k16.f32.bf16.bf16 {%0, %1, %2, %3, %4, %5, %6, %7, %8, %9, %10, %11, %12, %13, %14, %15, %16, %17, %18, %19, %20, %21, %22, %23, %24, %25, %26, %27, %28, %29, %30, %31, %32, %33, %34, %35, %36, %37, %38, %39, %40, %41, %42, %43, %44, %45, %46, %47, %48, %49, %50, %51, %52, %53, %54, %55, %56, %57, %58, %59, %60, %61, %62, %63}, {a0, a1, a2, a3}, d, 0, 1, 1, 0;\nwgmma.commit_group.sync.aligned;\nwgmma.wait_group.sync.aligned 1;\nmov.b32 b2, a1;\nmov.b32 b0, t0;\nmov.b32 b3, t0;\nmov.b32 b1, t1;\n"
        "ld.shared.b32 t0, [%64+512];\nld.shared.b32 t1, [%64+640];\nadd.s64 d, %65, 8;\nwgmma.fence.sync.aligned;\nwgmma.mma_async.sync.aligned.m64n128k16.f32.bf16.bf16 {%0, %1, %2, %3, %4, %5, %6, %7, %8, %9, %10, %11, %12, %13, %14, %15, %16, %17, %18, %19, %20, %21, %22, %23, %24, %25, %26, %27, %28, %29, %30, %31, %32, %33, %34, %35, %36, %37, %38, %39, %40, %41, %42, %43, %44, %45, %46, %47, %48, %49, %50, %51, %52, %53, %54, %55, %56, %57, %58, %59, %60, %61, %62, %63}, {b0, b1, b2, b3}, d, 1, 1, 1, 0;\nwgmma.commit_group.sync.aligned;\nwgmma.wait_group.sync.aligned 1;\nmov.b32 a2, b1;\nmov.b32 a0, t0;\nmov.b32 a3, t0;\nmov.b32 a1, t1;\n"
        "ld.shared.b32 t0, [%64+768];\nld.shared.b32 t1, [%64+896];\nadd.s64 d, %65, 16;\nwgmma.fence.sync.aligned;\nwgmma.mma_async.sync.aligned.m64n128k16.f32.bf16.bf16 {%0, %1, %2, %3, %4, %5, %6, %7, %8, %9, %10, %11, %12, %13, %14, %15, %16, %17, %18, %19, %20, %21, %22, %23, %24, %25, %26, %27, %28, %29, %30, %31, %32, %33, %34, %35, %36, %37, %38, %39, %40, %41, %42, %43, %44, %45, %46, %47, %48, %49, %50, %51, %52, %53, %54, %55, %56, %57, %58, %59, %60, %61, %62, %63}, {a0, a1, a2, a3}, d, 1, 1, 1, 0;\nwgmma.commit_group.sync.aligned;\nwgmma.wait_group.sync.aligned 1;\nmov.b32 b2, a1;\nmov.b32 b0, t0;\nmov.b32 b3, t0;\nmov.b32 b1, t1;\n"
        "ld.shared.b32 t0, [%64+1024];\nld.shared.b32 t1, [%64+1152];\nadd.s64 d, %65, 24;\nwgmma.fence.sync.aligned;\nwgmma.mma_async.sync.aligned.m64n128k16.f32.bf16.bf16 {%0, %1, %2, %3, %4, %5, %6, %7, %8, %9, %10, %11, %12, %13, %14, %15, %16, %17, %18, %19, %20, %21, %22, %23, %24, %25, %26, %27, %28, %29, %30, %31, %32, %33, %34, %35, %36, %37, %38, %39, %40, %41, %42, %43, %44, %45, %46, %47, %48, %49, %50, %51, %52, %53, %54, %55, %56, %57, %58, %59, %60, %61, %62, %63}, {b0, b1, b2, b3}, d, 1, 1, 1, 0;\nwgmma.commit_group.sync.aligned;\nwgmma.wait_group.sync.aligned 1;\nmov.b32 a2, b1;\nmov.b32 a0, t0;\nmov.b32 a3, t0;\nmov.b32 a1, t1;\n"
        "ld.shared.b32 t0, [%64+1280];\nld.shared.b32 t1, [%64+1408];\nadd.s64 d, %65, 32;\nwgmma.fence.sync.aligned;\nwgmma.mma_async.sync.aligned.m64n128k16.f32.bf16.bf16 {%0, %1, %2, %3, %4, %5, %6, %7, %8, %9, %10, %11, %12, %13, %14, %15, %16, %17, %18, %19, %20, %21, %22, %23, %24, %25, %26, %27, %28, %29, %30, %31, %32, %33, %34, %35, %36, %37, %38, %39, %40, %41, %42, %43, %44, %45, %46, %47, %48, %49, %50, %51, %52, %53, %54, %55, %56, %57, %58, %59, %60, %61, %62, %63}, {a0, a1, a2, a3}, d, 1, 1, 1, 0;\nwgmma.commit_group.sync.aligned;\nwgmma.wait_group.sync.aligned 1;\nmov.b32 b2, a1;\nmov.b32 b0, t0;\nmov.b32 b3, t0;\nmov.b32 b1, t1;\n"
        "ld.shared.b32 t0, [%64+1536];\nld.shared.b32 t1, [%64+1664];\nadd.s64 d, %65, 40;\nwgmma.fence.sync.aligned;\nwgmma.mma_async.sync.aligned.m64n128k16.f32.bf16.bf16 {%0, %1, %2, %3, %4, %5, %6, %7, %8, %9, %10, %11, %12, %13, %14, %15, %16, %17, %18, %19, %20, %21, %22, %23, %24, %25, %26, %27, %28, %29, %30, %31, %32, %33, %34, %35, %36, %37, %38, %39, %40, %41, %42, %43, %44, %45, %46, %47, %48, %49, %50, %51, %52, %53, %54, %55, %56, %57, %58, %59, %60, %61, %62, %63}, {b0, b1, b2, b3}, d, 1, 1, 1, 0;\nwgmma.commit_group.sync.aligned;\nwgmma.wait_group.sync.aligned 1;\nmov.b32 a2, b1;\nmov.b32 a0, t0;\nmov.b32 a3, t0;\nmov.b32 a1, t1;\n"
        "ld.shared.b32 t0, [%64+1792];\nld.shared.b32 t1, [%64+1920];\nadd.s64 d, %65, 48;\nwgmma.fence.sync.aligned;\nwgmma.mma_async.sync.aligned.m64n128k16.f32.bf16.bf16 {%0, %1, %2, %3, %4, %5, %6, %7, %8, %9, %10, %11, %12, %13, %14, %15, %16, %17, %18, %19, %20, %21, %22, %23, %24, %25, %26, %27, %28, %29, %30, %31, %32, %33, %34, %35, %36, %37, %38, %39, %40, %41, %42, %43, %44, %45, %46, %47, %48, %49, %50, %51, %52, %53, %54, %55, %56, %57, %58, %59, %60, %61, %62, %63}, {a0, a1, a2, a3}, d, 1, 1, 1, 0;\nwgmma.commit_group.sync.aligned;\nwgmma.wait_group.sync.aligned 1;\nmov.b32 b2, a1;\nmov.b32 b0, t0;\nmov.b32 b3, t0;\nmov.b32 b1, t1;\n"
        "ld.shared.b32 t0, [%64+2048];\nld.shared.b32 t1, [%64+2176];\nadd.s64 d, %65, 56;\nwgmma.fence.sync.aligned;\nwgmma.mma_async.sync.aligned.m64n128k16.f32.bf16.bf16 {%0, %1, %2, %3, %4, %5, %6, %7, %8, %9, %10, %11, %12, %13, %14, %15, %16, %17, %18, %19, %20, %21, %22, %23, %24, %25, %26, %27, %28, %29, %30, %31, %32, %33, %34, %35, %36, %37, %38, %39, %40, %41, %42, %43, %44, %45, %46, %47, %48, %49, %50, %51, %52, %53, %54, %55, %56, %57, %58, %59, %60, %61, %62, %63}, {b0, b1, b2, b3}, d, 1, 1, 1, 0;\nwgmma.commit_group.sync.aligned;\nwgmma.wait_group.sync.aligned 1;\nmov.b32 a2, b1;\nmov.b32 a0, t0;\nmov.b32 a3, t0;\nmov.b32 a1, t1;\n"
        "ld.shared.b32 t0, [%64+2304];\nld.shared.b32 t1, [%64+2432];\nadd.s64 d, %65, 64;\nwgmma.fence.sync.aligned;\nwgmma.mma_async.sync.aligned.m64n96k16.f32.bf16.bf16 {%0, %1, %2, %3, %4, %5, %6, %7, %8, %9, %10, %11, %12, %13, %14, %15, %16, %17, %18, %19, %20, %21, %22, %23, %24, %25, %26, %27, %28, %29, %30, %31, %32, %33, %34, %35, %36, %37, %38, %39, %40, %41, %42, %43, %44, %45, %46, %47}, {a0, a1, a2, a3}, d, 1, 1, 1, 0;\nwgmma.commit_group.sync.aligned;\nwgmma.wait_group.sync.aligned 1;\nmov.b32 b2, a1;\nmov.b32 b0, t0;\nmov.b32 b3, t0;\nmov.b32 b1, t1;\n"
        "ld.shared.b32 t0, [%64+2560];\nld.shared.b32 t1, [%64+2688];\nadd.s64 d, %65, 72;\nwgmma.fence.sync.aligned;\nwgmma.mma_async.sync.aligned.m64n96k16.f32.bf16.bf16 {%0, %1, %2, %3, %4, %5, %6, %7, %8, %9, %10, %11, %12, %13, %14, %15, %16, %17, %18, %19, %20, %21, %22, %23, %24, %25, %26, %27, %28, %29, %30, %31, %32, %33, %34, %35, %36, %37, %38, %39, %40, %41, %42, %43, %44, %45, %46, %47}, {b0, b1, b2, b3}, d, 1, 1, 1, 0;\nwgmma.commit_group.sync.aligned;\nwgmma.wait_group.sync.aligned 1;\nmov.b32 a2, b1;\nmov.b32 a0, t0;\nmov.b32 a3, t0;\nmov.b32 a1, t1;\n"
        "ld.shared.b32 t0, [%64+2816];\nld.shared.b32 t1, [%64+2944];\nadd.s64 d, %65, 80;\nwgmma.fence.sync.aligned;\nwgmma.mma_async.sync.aligned.m64n88k16.f32.bf16.bf16 {%0, %1, %2, %3, %4, %5, %6, %7, %8, %9, %10, %11, %12, %13, %14, %15, %16, %17, %18, %19, %20, %21, %22, %23, %24, %25, %26, %27, %28, %29, %30, %31, %32, %33, %34, %35, %36, %37, %38, %39, %40, %41, %42, %43}, {a0, a1, a2, a3}, d, 1, 1, 1, 0;\nwgmma.commit_group.sync.aligned;\nwgmma.wait_group.sync.aligned 1;\nmov.b32 b2, a1;\nmov.b32 b0, t0;\nmov.b32 b3, t0;\nmov.b32 b1, t1;\n"
        "ld.shared.b32 t0, [%64+3072];\nld.shared.b32 t1, [%64+3200];\nadd.s64 d, %65, 88;\nwgmma.fence.sync.aligned;\nwgmma.mma_async.sync.aligned.m64n88k16.f32.bf16.bf16 {%0, %1, %2, %3, %4, %5, %6, %7, %8, %9, %10, %11, %12, %13, %14, %15, %16, %17, %18, %19, %20, %21, %22, %23, %24, %25, %26, %27, %28, %29, %30, %31, %32, %33, %34, %35, %36, %37, %38, %39, %40, %41, %42, %43}, {b0, b1, b2, b3}, d, 1, 1, 1, 0;\nwgmma.commit_group.sync.aligned;\nwgmma.wait_group.sync.aligned 1;\nmov.b32 a2, b1;\nmov.b32 a0, t0;\nmov.b32 a3, t0;\nmov.b32 a1, t1;\n"
        "ld.shared.b32 t0, [%64+3328];\nld.shared.b32 t1, [%64+3456];\nadd.s64 d, %65, 96;\nwgmma.fence.sync.aligned;\nwgmma.mma_async.sync.aligned.m64n80k16.f32.bf16.bf16 {%0, %1, %2, %3, %4, %5, %6, %7, %8, %9, %10, %11, %12, %13, %14, %15, %16, %17, %18, %19, %20, %21, %22, %23, %24, %25, %26, %27, %28, %29, %30, %31, %32, %33, %34, %35, %36, %37, %38, %39}, {a0, a1, a2, a3}, d, 1, 1, 1, 0;\nwgmma.commit_group.sync.aligned;\nwgmma.wait_group.sync.aligned 1;\nmov.b32 b2, a1;\nmov.b32 b0, t0;\nmov.b32 b3, t0;\nmov.b32 b1, t1;\n"
        "ld.shared.b32 t0, [%64+3584];\nld.shared.b32 t1, [%64+3712];\nadd.s64 d, %65, 104;\nwgmma.fence.sync.aligned;\nwgmma.mma_async.sync.aligned.m64n80k16.f32.bf16.bf16 {%0, %1, %2, %3, %4, %5, %6, %7, %8, %9, %10, %11, %12, %13, %14, %15, %16, %17, %18, %19, %20, %21, %22, %23, %24, %25, %26, %27, %28, %29, %30, %31, %32, %33, %34, %35, %36, %37, %38, %39}, {b0, b1, b2, b3}, d, 1, 1, 1, 0;\nwgmma.commit_group.sync.aligned;\nwgmma.wait_group.sync.aligned 1;\nmov.b32 a2, b1;\nmov.b32 a0, t0;\nmov.b32 a3, t0;\nmov.b32 a1, t1;\n"
        "ld.shared.b32 t0, [%64+3840];\nld.shared.b32 t1, [%64+3968];\nadd.s64 d, %65, 112;\nwgmma.fence.sync.aligned;\nwgmma.mma_async.sync.aligned.m64n72k16.f32.bf16.bf16 {%0, %1, %2, %3, %4, %5, %6, %7, %8, %9, %10, %11, %12, %13, %14, %15, %16, %17, %18, %19, %20, %21, %22, %23, %24, %25, %26, %27, %28, %29, %30, %31, %32, %33, %34, %35}, {a0, a1, a2, a3}, d, 1, 1, 1, 0;\nwgmma.commit_group.sync.aligned;\nwgmma.wait_group.sync.aligned 1;\nmov.b32 b2, a1;\nmov.b32 b0, t0;\nmov.b32 b3, t0;\nmov.b32 b1, t1;\n"
        "ld.shared.b32 t0, [%64+4096];\nld.shared.b32 t1, [%64+4224];\nadd.s64 d, %65, 120;\nwgmma.fence.sync.aligned;\nwgmma.mma_async.sync.aligned.m64n72k16.f32.bf16.bf16 {%0, %1, %2, %3, %4, %5, %6, %7, %8, %9, %10, %11, %12, %13, %14, %15, %16, %17, %18, %19, %20, %21, %22, %23, %24, %25, %26, %27, %28, %29, %30, %31, %32, %33, %34, %35}, {b0, b1, b2, b3}, d, 1, 1, 1, 0;\nwgmma.commit_group.sync.aligned;\nwgmma.wait_group.sync.aligned 1;\nmov.b32 a2, b1;\nmov.b32 a0, t0;\nmov.b32 a3, t0;\nmov.b32 a1, t1;\n"
        "ld.shared.b32 t0, [%64+4352];\nld.shared.b32 t1, [%64+4480];\nadd.s64 d, %65, 128;\nwgmma.fence.sync.aligned;\nwgmma.mma_async.sync.aligned.m64n64k16.f32.bf16.bf16 {%0, %1, %2, %3, %4, %5, %6, %7, %8, %9, %10, %11, %12, %13, %14, %15, %16, %17, %18, %19, %20, %21, %22, %23, %24, %25, %26, %27, %28, %29, %30, %31}, {a0, a1, a2, a3}, d, 1, 1, 1, 0;\nwgmma.commit_group.sync.aligned;\nwgmma.wait_group.sync.aligned 1;\nmov.b32 b2, a1;\nmov.b32 b0, t0;\nmov.b32 b3, t0;\nmov.b32 b1, t1;\n"
        "ld.shared.b32 t0, [%64+4608];\nld.shared.b32 t1, [%64+4736];\nadd.s64 d, %65, 136;\nwgmma.fence.sync.aligned;\nwgmma.mma_async.sync.aligned.m64n64k16.f32.bf16.bf16 {%0, %1, %2, %3, %4, %5, %6, %7, %8, %9, %10, %11, %12, %13, %14, %15, %16, %17, %18, %19, %20, %21, %22, %23, %24, %25, %26, %27, %28, %29, %30, %31}, {b0, b1, b2, b3}, d, 1, 1, 1, 0;\nwgmma.commit_group.sync.aligned;\nwgmma.wait_group.sync.aligned 1;\nmov.b32 a2, b1;\nmov.b32 a0, t0;\nmov.b32 a3, t0;\nmov.b32 a1, t1;\n"
        "ld.shared.b32 t0, [%64+4864];\nld.shared.b32 t1, [%64+4992];\nadd.s64 d, %65, 144;\nwgmma.fence.sync.aligned;\nwgmma.mma_async.sync.aligned.m64n56k16.f32.bf16.bf16 {%0, %1, %2, %3, %4, %5, %6, %7, %8, %9, %10, %11, %12, %13, %14, %15, %16, %17, %18, %19, %20, %21, %22, %23, %24, %25, %26, %27}, {a0, a1, a2, a3}, d, 1, 1, 1, 0;\nwgmma.commit_group.sync.aligned;\nwgmma.wait_group.sync.aligned 1;\nmov.b32 b2, a1;\nmov.b32 b0, t0;\nmov.b32 b3, t0;\nmov.b32 b1, t1;\n"
        "ld.shared.b32 t0, [%64+5120];\nld.shared.b32 t1, [%64+5248];\nadd.s64 d, %65, 152;\nwgmma.fence.sync.aligned;\nwgmma.mma_async.sync.aligned.m64n56k16.f32.bf16.bf16 {%0, %1, %2, %3, %4, %5, %6, %7, %8, %9, %10, %11, %12, %13, %14, %15, %16, %17, %18, %19, %20, %21, %22, %23, %24, %25, %26, %27}, {b0, b1, b2, b3}, d, 1, 1, 1, 0;\nwgmma.commit_group.sync.aligned;\nwgmma.wait_group.sync.aligned 1;\nmov.b32 a2, b1;\nmov.b32 a0, t0;\nmov.b32 a3, t0;\nmov.b32 a1, t1;\n"
        "ld.shared.b32 t0, [%64+5376];\nld.shared.b32 t1, [%64+5504];\nadd.s64 d, %65, 160;\nwgmma.fence.sync.aligned;\nwgmma.mma_async.sync.aligned.m64n48k16.f32.bf16.bf16 {%0, %1, %2, %3, %4, %5, %6, %7, %8, %9, %10, %11, %12, %13, %14, %15, %16, %17, %18, %19, %20, %21, %22, %23}, {a0, a1, a2, a3}, d, 1, 1, 1, 0;\nwgmma.commit_group.sync.aligned;\nwgmma.wait_group.sync.aligned 1;\nmov.b32 b2, a1;\nmov.b32 b0, t0;\nmov.b32 b3, t0;\nmov.b32 b1, t1;\n"
        "ld.shared.b32 t0, [%64+5632];\nld.shared.b32 t1, [%64+5760];\nadd.s64 d, %65, 168;\nwgmma.fence.sync.aligned;\nwgmma.mma_async.sync.aligned.m64n48k16.f32.bf16.bf16 {%0, %1, %2, %3, %4, %5, %6, %7, %8, %9, %10, %11, %12, %13, %14, %15, %16, %17, %18, %19, %20, %21, %22, %23}, {b0, b1, b2, b3}, d, 1, 1, 1, 0;\nwgmma.commit_group.sync.aligned;\nwgmma.wait_group.sync.aligned 1;\nmov.b32 a2, b1;\nmov.b32 a0, t0;\nmov.b32 a3, t0;\nmov.b32 a1, t1;\n"
        "ld.shared.b32 t0, [%64+5888];\nld.shared.b32 t1, [%64+6016];\nadd.s64 d, %65, 176;\nwgmma.fence.sync.aligned;\nwgmma.mma_async.sync.aligned.m64n40k16.f32.bf16.bf16 {%0, %1, %2, %3, %4, %5, %6, %7, %8, %9, %10, %11, %12, %13, %14, %15, %16, %17, %18, %19}, {a0, a1, a2, a3}, d, 1, 1, 1, 0;\nwgmma.commit_group.sync.aligned;\nwgmma.wait_group.sync.aligned 1;\nmov.b32 b2, a1;\nmov.b32 b0, t0;\nmov.b32 b3, t0;\nmov.b32 b1, t1;\n"
        "ld.shared.b32 t0, [%64+6144];\nld.shared.b32 t1, [%64+6272];\nadd.s64 d, %65, 184;\nwgmma.fence.sync.aligned;\nwgmma.mma_async.sync.aligned.m64n40k16.f32.bf16.bf16 {%0, %1, %2, %3, %4, %5, %6, %7, %8, %9, %10, %11, %12, %13, %14, %15, %16, %17, %18, %19}, {b0, b1, b2, b3}, d, 1, 1, 1, 0;\nwgmma.commit_group.sync.aligned;\nwgmma.wait_group.sync.aligned 1;\nmov.b32 a2, b1;\nmov.b32 a0, t0;\nmov.b32 a3, t0;\nmov.b32 a1, t1;\n"
        "ld.shared.b32 t0, [%64+6400];\nld.shared.b32 t1, [%64+6528];\nadd.s64 d, %65, 192;\nwgmma.fence.sync.aligned;\nwgmma.mma_async.sync.aligned.m64n32k16.f32.bf16.bf16 {%0, %1, %2, %3, %4, %5, %6, %7, %8, %9, %10, %11, %12, %13, %14, %15}, {a0, a1, a2, a3}, d, 1, 1, 1, 0;\nwgmma.commit_group.sync.aligned;\nwgmma.wait_group.sync.aligned 1;\nmov.b32 b2, a1;\nmov.b32 b0, t0;\nmov.b32 b3, t0;\nmov.b32 b1, t1;\n"
        "ld.shared.b32 t0, [%64+6656];\nld.shared.b32 t1, [%64+6784];\nadd.s64 d, %65, 200;\nwgmma.fence.sync.aligned;\nwgmma.mma_async.sync.aligned.m64n32k16.f32.bf16.bf16 {%0, %1, %2, %3, %4, %5, %6, %7, %8, %9, %10, %11, %12, %13, %14, %15}, {b0, b1, b2, b3}, d, 1, 1, 1, 0;\nwgmma.commit_group.sync.aligned;\nwgmma.wait_group.sync.aligned 1;\nmov.b32 a2, b1;\nmov.b32 a0, t0;\nmov.b32 a3, t0;\nmov.b32 a1, t1;\n"
        "ld.shared.b32 t0, [%64+6912];\nld.shared.b32 t1, [%64+7040];\nadd.s64 d, %65, 208;\nwgmma.fence.sync.aligned;\nwgmma.mma_async.sync.aligned.m64n24k16.f32.bf16.bf16 {%0, %1, %2, %3, %4, %5, %6, %7, %8, %9, %10, %11}, {a0, a1, a2, a3}, d, 1, 1, 1, 0;\nwgmma.commit_group.sync.aligned;\nwgmma.wait_group.sync.aligned 1;\nmov.b32 b2, a1;\nmov.b32 b0, t0;\nmov.b32 b3, t0;\nmov.b32 b1, t1;\n"
        "ld.shared.b32 t0, [%64+7168];\nld.shared.b32 t1, [%64+7296];\nadd.s64 d, %65, 216;\nwgmma.fence.sync.aligned;\nwgmma.mma_async.sync.aligned.m64n24k16.f32.bf16.bf16 {%0, %1, %2, %3, %4, %5, %6, %7, %8, %9, %10, %11}, {b0, b1, b2, b3}, d, 1, 1, 1, 0;\nwgmma.commit_group.sync.aligned;\nwgmma.wait_group.sync.aligned 1;\nmov.b32 a2, b1;\nmov.b32 a0, t0;\nmov.b32 a3, t0;\nmov.b32 a1, t1;\n"
        "ld.shared.b32 t0, [%64+7424];\nld.shared.b32 t1, [%64+7552];\nadd.s64 d, %65, 224;\nwgmma.fence.sync.aligned;\nwgmma.mma_async.sync.aligned.m64n16k16.f32.bf16.bf16 {%0, %1, %2, %3, %4, %5, %6, %7}, {a0, a1, a2, a3}, d, 1, 1, 1, 0;\nwgmma.commit_group.sync.aligned;\nwgmma.wait_group.sync.aligned 1;\nmov.b32 b2, a1;\nmov.b32 b0, t0;\nmov.b32 b3, t0;\nmov.b32 b1, t1;\n"
        "ld.shared.b32 t0, [%64+7680];\nld.shared.b32 t1, [%64+7808];\nadd.s64 d, %65, 232;\nwgmma.fence.sync.aligned;\nwgmma.mma_async.sync.aligned.m64n16k16.f32.bf16.bf16 {%0, %1, %2, %3, %4, %5, %6, %7}, {b0, b1, b2, b3}, d, 1, 1, 1, 0;\nwgmma.commit_group.sync.aligned;\nwgmma.wait_group.sync.aligned 1;\nmov.b32 a2, b1;\nmov.b32 a0, t0;\nmov.b32 a3, t0;\nmov.b32 a1, t1;\n"
        "ld.shared.b32 t0, [%64+7936];\nld.shared.b32 t1, [%64+8064];\nadd.s64 d, %65, 240;\nwgmma.fence.sync.aligned;\nwgmma.mma_async.sync.aligned.m64n8k16.f32.bf16.bf16 {%0, %1, %2, %3}, {a0, a1, a2, a3}, d, 1, 1, 1, 0;\nwgmma.commit_group.sync.aligned;\nwgmma.wait_group.sync.aligned 1;\nmov.b32 b2, a1;\nmov.b32 b0, t0;\nmov.b32 b3, t0;\nmov.b32 b1, t1;\n"
        "add.s64 d, %65, 248;\nwgmma.fence.sync.aligned;\nwgmma.mma_async.sync.aligned.m64n8k16.f32.bf16.bf16 {%0, %1, %2, %3}, {b0, b1, b2, b3}, d, 1, 1, 1, 0;\nwgmma.commit_group.sync.aligned;\nwgmma.wait_group.sync.aligned 0;\n"
        "}" : "+f"(d[0]), "+f"(d[1]), "+f"(d[2]), "+f"(d[3]), "+f"(d[4]), "+f"(d[5]), "+f"(d[6]), "+f"(d[7]), "+f"(d[8]), "+f"(d[9]), "+f"(d[10]), "+f"(d[11]), "+f"(d[12]), "+f"(d[13]), "+f"(d[14]), "+f"(d[15]), "+f"(d[16]), "+f"(d[17]), "+f"(d[18]), "+f"(d[19]), "+f"(d[20]), "+f"(d[21]), "+f"(d[22]), "+f"(d[23]), "+f"(d[24]), "+f"(d[25]), "+f"(d[26]), "+f"(d[27]), "+f"(d[28]), "+f"(d[29]), "+f"(d[30]), "+f"(d[31]), "+f"(d[32]), "+f"(d[33]), "+f"(d[34]), "+f"(d[35]), "+f"(d[36]), "+f"(d[37]), "+f"(d[38]), "+f"(d[39]), "+f"(d[40]), "+f"(d[41]), "+f"(d[42]), "+f"(d[43]), "+f"(d[44]), "+f"(d[45]), "+f"(d[46]), "+f"(d[47]), "+f"(d[48]), "+f"(d[49]), "+f"(d[50]), "+f"(d[51]), "+f"(d[52]), "+f"(d[53]), "+f"(d[54]), "+f"(d[55]), "+f"(d[56]), "+f"(d[57]), "+f"(d[58]), "+f"(d[59]), "+f"(d[60]), "+f"(d[61]), "+f"(d[62]), "+f"(d[63]) : "r"(pa), "l"(db) : "memory");
}
__device__ __forceinline__ void wgmma_rs80(float (&d)[40], uint32_t a0, uint32_t a1, uint32_t a2, uint32_t a3, uint64_t db, int sc) {
    asm volatile("{\n.reg .pred p;\nsetp.ne.b32 p, %45, 0;\n"
        "wgmma.mma_async.sync.aligned.m64n80k16.f32.bf16.bf16 {%0, %1, %2, %3, %4, %5, %6, %7, %8, %9, %10, %11, %12, %13, %14, %15, %16, %17, %18, %19, %20, %21, %22, %23, %24, %25, %26, %27, %28, %29, %30, %31, %32, %33, %34, %35, %36, %37, %38, %39}, {%40, %41, %42, %43}, %44, p, 1, 1, 1;\n}\n"
        : "+f"(d[0]), "+f"(d[1]), "+f"(d[2]), "+f"(d[3]), "+f"(d[4]), "+f"(d[5]), "+f"(d[6]), "+f"(d[7]), "+f"(d[8]), "+f"(d[9]), "+f"(d[10]), "+f"(d[11]), "+f"(d[12]), "+f"(d[13]), "+f"(d[14]), "+f"(d[15]), "+f"(d[16]), "+f"(d[17]), "+f"(d[18]), "+f"(d[19]), "+f"(d[20]), "+f"(d[21]), "+f"(d[22]), "+f"(d[23]), "+f"(d[24]), "+f"(d[25]), "+f"(d[26]), "+f"(d[27]), "+f"(d[28]), "+f"(d[29]), "+f"(d[30]), "+f"(d[31]), "+f"(d[32]), "+f"(d[33]), "+f"(d[34]), "+f"(d[35]), "+f"(d[36]), "+f"(d[37]), "+f"(d[38]), "+f"(d[39]) : "r"(a0), "r"(a1), "r"(a2), "r"(a3), "l"(db), "r"(sc));
}
__device__ __forceinline__ void wgmma_ss80(float (&d)[40], uint64_t da, uint64_t db, int sc) {
    asm volatile("{\n.reg .pred p;\nsetp.ne.b32 p, %42, 0;\n"
        "wgmma.mma_async.sync.aligned.m64n80k16.f32.bf16.bf16 {%0, %1, %2, %3, %4, %5, %6, %7, %8, %9, %10, %11, %12, %13, %14, %15, %16, %17, %18, %19, %20, %21, %22, %23, %24, %25, %26, %27, %28, %29, %30, %31, %32, %33, %34, %35, %36, %37, %38, %39}, %40, %41, p, 1, 1, 0, 1;\n}\n"
        : "+f"(d[0]), "+f"(d[1]), "+f"(d[2]), "+f"(d[3]), "+f"(d[4]), "+f"(d[5]), "+f"(d[6]), "+f"(d[7]), "+f"(d[8]), "+f"(d[9]), "+f"(d[10]), "+f"(d[11]), "+f"(d[12]), "+f"(d[13]), "+f"(d[14]), "+f"(d[15]), "+f"(d[16]), "+f"(d[17]), "+f"(d[18]), "+f"(d[19]), "+f"(d[20]), "+f"(d[21]), "+f"(d[22]), "+f"(d[23]), "+f"(d[24]), "+f"(d[25]), "+f"(d[26]), "+f"(d[27]), "+f"(d[28]), "+f"(d[29]), "+f"(d[30]), "+f"(d[31]), "+f"(d[32]), "+f"(d[33]), "+f"(d[34]), "+f"(d[35]), "+f"(d[36]), "+f"(d[37]), "+f"(d[38]), "+f"(d[39]) : "l"(da), "l"(db), "r"(sc));
}
__device__ __forceinline__ void wgmma_ss80t(float (&d)[40], uint64_t da, uint64_t db, int sc) {
    asm volatile("{\n.reg .pred p;\nsetp.ne.b32 p, %42, 0;\n"
        "wgmma.mma_async.sync.aligned.m64n80k16.f32.bf16.bf16 {%0, %1, %2, %3, %4, %5, %6, %7, %8, %9, %10, %11, %12, %13, %14, %15, %16, %17, %18, %19, %20, %21, %22, %23, %24, %25, %26, %27, %28, %29, %30, %31, %32, %33, %34, %35, %36, %37, %38, %39}, %40, %41, p, 1, 1, 1, 1;\n}\n"
        : "+f"(d[0]), "+f"(d[1]), "+f"(d[2]), "+f"(d[3]), "+f"(d[4]), "+f"(d[5]), "+f"(d[6]), "+f"(d[7]), "+f"(d[8]), "+f"(d[9]), "+f"(d[10]), "+f"(d[11]), "+f"(d[12]), "+f"(d[13]), "+f"(d[14]), "+f"(d[15]), "+f"(d[16]), "+f"(d[17]), "+f"(d[18]), "+f"(d[19]), "+f"(d[20]), "+f"(d[21]), "+f"(d[22]), "+f"(d[23]), "+f"(d[24]), "+f"(d[25]), "+f"(d[26]), "+f"(d[27]), "+f"(d[28]), "+f"(d[29]), "+f"(d[30]), "+f"(d[31]), "+f"(d[32]), "+f"(d[33]), "+f"(d[34]), "+f"(d[35]), "+f"(d[36]), "+f"(d[37]), "+f"(d[38]), "+f"(d[39]) : "l"(da), "l"(db), "r"(sc));
}
__device__ __forceinline__ void wgmma_ss8_ta(float (&d)[4], uint64_t da, uint64_t db, int sc) {
    asm volatile("{\n.reg .pred p;\nsetp.ne.b32 p, %6, 0;\n"
        "wgmma.mma_async.sync.aligned.m64n8k16.f32.bf16.bf16 {%0, %1, %2, %3}, %4, %5, p, 1, 1, 1, 0;\n}\n"
        : "+f"(d[0]), "+f"(d[1]), "+f"(d[2]), "+f"(d[3]) : "l"(da), "l"(db), "r"(sc));
}
__device__ __forceinline__ void wgmma_rs8(float (&d)[4], uint32_t a0, uint32_t a1, uint32_t a2, uint32_t a3, uint64_t db, int sc) {
    asm volatile("{\n.reg .pred p;\nsetp.ne.b32 p, %9, 0;\n"
        "wgmma.mma_async.sync.aligned.m64n8k16.f32.bf16.bf16 {%0, %1, %2, %3}, {%4, %5, %6, %7}, %8, p, 1, 1, 0;\n}\n"
        : "+f"(d[0]), "+f"(d[1]), "+f"(d[2]), "+f"(d[3]) : "r"(a0), "r"(a1), "r"(a2), "r"(a3), "l"(db), "r"(sc));
}
__device__ __forceinline__ void wgmma_rs128(float (&d)[64], uint32_t a0, uint32_t a1, uint32_t a2, uint32_t a3, uint64_t db, int sc) {
    asm volatile("{\n.reg .pred p;\nsetp.ne.b32 p, %69, 0;\n"
        "wgmma.mma_async.sync.aligned.m64n128k16.f32.bf16.bf16 {%0, %1, %2, %3, %4, %5, %6, %7, %8, %9, %10, %11, %12, %13, %14, %15, %16, %17, %18, %19, %20, %21, %22, %23, %24, %25, %26, %27, %28, %29, %30, %31, %32, %33, %34, %35, %36, %37, %38, %39, %40, %41, %42, %43, %44, %45, %46, %47, %48, %49, %50, %51, %52, %53, %54, %55, %56, %57, %58, %59, %60, %61, %62, %63}, {%64, %65, %66, %67}, %68, p, 1, 1, 1;\n}\n"
        : "+f"(d[0]), "+f"(d[1]), "+f"(d[2]), "+f"(d[3]), "+f"(d[4]), "+f"(d[5]), "+f"(d[6]), "+f"(d[7]), "+f"(d[8]), "+f"(d[9]), "+f"(d[10]), "+f"(d[11]), "+f"(d[12]), "+f"(d[13]), "+f"(d[14]), "+f"(d[15]), "+f"(d[16]), "+f"(d[17]), "+f"(d[18]), "+f"(d[19]), "+f"(d[20]), "+f"(d[21]), "+f"(d[22]), "+f"(d[23]), "+f"(d[24]), "+f"(d[25]), "+f"(d[26]), "+f"(d[27]), "+f"(d[28]), "+f"(d[29]), "+f"(d[30]), "+f"(d[31]), "+f"(d[32]), "+f"(d[33]), "+f"(d[34]), "+f"(d[35]), "+f"(d[36]), "+f"(d[37]), "+f"(d[38]), "+f"(d[39]), "+f"(d[40]), "+f"(d[41]), "+f"(d[42]), "+f"(d[43]), "+f"(d[44]), "+f"(d[45]), "+f"(d[46]), "+f"(d[47]), "+f"(d[48]), "+f"(d[49]), "+f"(d[50]), "+f"(d[51]), "+f"(d[52]), "+f"(d[53]), "+f"(d[54]), "+f"(d[55]), "+f"(d[56]), "+f"(d[57]), "+f"(d[58]), "+f"(d[59]), "+f"(d[60]), "+f"(d[61]), "+f"(d[62]), "+f"(d[63]) : "r"(a0), "r"(a1), "r"(a2), "r"(a3), "l"(db), "r"(sc));
}
__device__ __forceinline__ void wgmma_rs88(float (&d)[44], uint32_t a0, uint32_t a1, uint32_t a2, uint32_t a3, uint64_t db, int sc) {
    asm volatile("{\n.reg .pred p;\nsetp.ne.b32 p, %49, 0;\n"
        "wgmma.mma_async.sync.aligned.m64n88k16.f32.bf16.bf16 {%0, %1, %2, %3, %4, %5, %6, %7, %8, %9, %10, %11, %12, %13, %14, %15, %16, %17, %18, %19, %20, %21, %22, %23, %24, %25, %26, %27, %28, %29, %30, %31, %32, %33, %34, %35, %36, %37, %38, %39, %40, %41, %42, %43}, {%44, %45, %46, %47}, %48, p, 1, 1, 1;\n}\n"
        : "+f"(d[0]), "+f"(d[1]), "+f"(d[2]), "+f"(d[3]), "+f"(d[4]), "+f"(d[5]), "+f"(d[6]), "+f"(d[7]), "+f"(d[8]), "+f"(d[9]), "+f"(d[10]), "+f"(d[11]), "+f"(d[12]), "+f"(d[13]), "+f"(d[14]), "+f"(d[15]), "+f"(d[16]), "+f"(d[17]), "+f"(d[18]), "+f"(d[19]), "+f"(d[20]), "+f"(d[21]), "+f"(d[22]), "+f"(d[23]), "+f"(d[24]), "+f"(d[25]), "+f"(d[26]), "+f"(d[27]), "+f"(d[28]), "+f"(d[29]), "+f"(d[30]), "+f"(d[31]), "+f"(d[32]), "+f"(d[33]), "+f"(d[34]), "+f"(d[35]), "+f"(d[36]), "+f"(d[37]), "+f"(d[38]), "+f"(d[39]), "+f"(d[40]), "+f"(d[41]), "+f"(d[42]), "+f"(d[43]) : "r"(a0), "r"(a1), "r"(a2), "r"(a3), "l"(db), "r"(sc));
}
__device__ __forceinline__ void wgmma_rs128k(float (&d)[64], uint32_t a0, uint32_t a1, uint32_t a2, uint32_t a3, uint64_t db, int sc) {
    asm volatile("{\n.reg .pred p;\nsetp.ne.b32 p, %69, 0;\n"
        "wgmma.mma_async.sync.aligned.m64n128k16.f32.bf16.bf16 {%0, %1, %2, %3, %4, %5, %6, %7, %8, %9, %10, %11, %12, %13, %14, %15, %16, %17, %18, %19, %20, %21, %22, %23, %24, %25, %26, %27, %28, %29, %30, %31, %32, %33, %34, %35, %36, %37, %38, %39, %40, %41, %42, %43, %44, %45, %46, %47, %48, %49, %50, %51, %52, %53, %54, %55, %56, %57, %58, %59, %60, %61, %62, %63}, {%64, %65, %66, %67}, %68, p, 1, 1, 0;\n}\n"
        : "+f"(d[0]), "+f"(d[1]), "+f"(d[2]), "+f"(d[3]), "+f"(d[4]), "+f"(d[5]), "+f"(d[6]), "+f"(d[7]), "+f"(d[8]), "+f"(d[9]), "+f"(d[10]), "+f"(d[11]), "+f"(d[12]), "+f"(d[13]), "+f"(d[14]), "+f"(d[15]), "+f"(d[16]), "+f"(d[17]), "+f"(d[18]), "+f"(d[19]), "+f"(d[20]), "+f"(d[21]), "+f"(d[22]), "+f"(d[23]), "+f"(d[24]), "+f"(d[25]), "+f"(d[26]), "+f"(d[27]), "+f"(d[28]), "+f"(d[29]), "+f"(d[30]), "+f"(d[31]), "+f"(d[32]), "+f"(d[33]), "+f"(d[34]), "+f"(d[35]), "+f"(d[36]), "+f"(d[37]), "+f"(d[38]), "+f"(d[39]), "+f"(d[40]), "+f"(d[41]), "+f"(d[42]), "+f"(d[43]), "+f"(d[44]), "+f"(d[45]), "+f"(d[46]), "+f"(d[47]), "+f"(d[48]), "+f"(d[49]), "+f"(d[50]), "+f"(d[51]), "+f"(d[52]), "+f"(d[53]), "+f"(d[54]), "+f"(d[55]), "+f"(d[56]), "+f"(d[57]), "+f"(d[58]), "+f"(d[59]), "+f"(d[60]), "+f"(d[61]), "+f"(d[62]), "+f"(d[63]) : "r"(a0), "r"(a1), "r"(a2), "r"(a3), "l"(db), "r"(sc));
}
__device__ __forceinline__ void wgmma_rs88k(float (&d)[44], uint32_t a0, uint32_t a1, uint32_t a2, uint32_t a3, uint64_t db, int sc) {
    asm volatile("{\n.reg .pred p;\nsetp.ne.b32 p, %49, 0;\n"
        "wgmma.mma_async.sync.aligned.m64n88k16.f32.bf16.bf16 {%0, %1, %2, %3, %4, %5, %6, %7, %8, %9, %10, %11, %12, %13, %14, %15, %16, %17, %18, %19, %20, %21, %22, %23, %24, %25, %26, %27, %28, %29, %30, %31, %32, %33, %34, %35, %36, %37, %38, %39, %40, %41, %42, %43}, {%44, %45, %46, %47}, %48, p, 1, 1, 0;\n}\n"
        : "+f"(d[0]), "+f"(d[1]), "+f"(d[2]), "+f"(d[3]), "+f"(d[4]), "+f"(d[5]), "+f"(d[6]), "+f"(d[7]), "+f"(d[8]), "+f"(d[9]), "+f"(d[10]), "+f"(d[11]), "+f"(d[12]), "+f"(d[13]), "+f"(d[14]), "+f"(d[15]), "+f"(d[16]), "+f"(d[17]), "+f"(d[18]), "+f"(d[19]), "+f"(d[20]), "+f"(d[21]), "+f"(d[22]), "+f"(d[23]), "+f"(d[24]), "+f"(d[25]), "+f"(d[26]), "+f"(d[27]), "+f"(d[28]), "+f"(d[29]), "+f"(d[30]), "+f"(d[31]), "+f"(d[32]), "+f"(d[33]), "+f"(d[34]), "+f"(d[35]), "+f"(d[36]), "+f"(d[37]), "+f"(d[38]), "+f"(d[39]), "+f"(d[40]), "+f"(d[41]), "+f"(d[42]), "+f"(d[43]) : "r"(a0), "r"(a1), "r"(a2), "r"(a3), "l"(db), "r"(sc));
}
__device__ __forceinline__ void wgmma_rs80k(float (&d)[40], uint32_t a0, uint32_t a1, uint32_t a2, uint32_t a3, uint64_t db, int sc) {
    asm volatile("{\n.reg .pred p;\nsetp.ne.b32 p, %45, 0;\n"
        "wgmma.mma_async.sync.aligned.m64n80k16.f32.bf16.bf16 {%0, %1, %2, %3, %4, %5, %6, %7, %8, %9, %10, %11, %12, %13, %14, %15, %16, %17, %18, %19, %20, %21, %22, %23, %24, %25, %26, %27, %28, %29, %30, %31, %32, %33, %34, %35, %36, %37, %38, %39}, {%40, %41, %42, %43}, %44, p, 1, 1, 0;\n}\n"
        : "+f"(d[0]), "+f"(d[1]), "+f"(d[2]), "+f"(d[3]), "+f"(d[4]), "+f"(d[5]), "+f"(d[6]), "+f"(d[7]), "+f"(d[8]), "+f"(d[9]), "+f"(d[10]), "+f"(d[11]), "+f"(d[12]), "+f"(d[13]), "+f"(d[14]), "+f"(d[15]), "+f"(d[16]), "+f"(d[17]), "+f"(d[18]), "+f"(d[19]), "+f"(d[20]), "+f"(d[21]), "+f"(d[22]), "+f"(d[23]), "+f"(d[24]), "+f"(d[25]), "+f"(d[26]), "+f"(d[27]), "+f"(d[28]), "+f"(d[29]), "+f"(d[30]), "+f"(d[31]), "+f"(d[32]), "+f"(d[33]), "+f"(d[34]), "+f"(d[35]), "+f"(d[36]), "+f"(d[37]), "+f"(d[38]), "+f"(d[39]) : "r"(a0), "r"(a1), "r"(a2), "r"(a3), "l"(db), "r"(sc));
}
__device__ __forceinline__ void wgmma_rs64(float (&d)[32], uint32_t a0, uint32_t a1, uint32_t a2, uint32_t a3, uint64_t db, int sc) {
    asm volatile("{\n.reg .pred p;\nsetp.ne.b32 p, %37, 0;\n"
        "wgmma.mma_async.sync.aligned.m64n64k16.f32.bf16.bf16 {%0, %1, %2, %3, %4, %5, %6, %7, %8, %9, %10, %11, %12, %13, %14, %15, %16, %17, %18, %19, %20, %21, %22, %23, %24, %25, %26, %27, %28, %29, %30, %31}, {%32, %33, %34, %35}, %36, p, 1, 1, 1;\n}\n"
        : "+f"(d[0]), "+f"(d[1]), "+f"(d[2]), "+f"(d[3]), "+f"(d[4]), "+f"(d[5]), "+f"(d[6]), "+f"(d[7]), "+f"(d[8]), "+f"(d[9]), "+f"(d[10]), "+f"(d[11]), "+f"(d[12]), "+f"(d[13]), "+f"(d[14]), "+f"(d[15]), "+f"(d[16]), "+f"(d[17]), "+f"(d[18]), "+f"(d[19]), "+f"(d[20]), "+f"(d[21]), "+f"(d[22]), "+f"(d[23]), "+f"(d[24]), "+f"(d[25]), "+f"(d[26]), "+f"(d[27]), "+f"(d[28]), "+f"(d[29]), "+f"(d[30]), "+f"(d[31]) : "r"(a0), "r"(a1), "r"(a2), "r"(a3), "l"(db), "r"(sc));
}

__device__ __forceinline__ uint64_t mkdesc(uint32_t lo) { return ((uint64_t)0x40000040u << 32) | lo; }
template <int F> __device__ __forceinline__ uint32_t lop3(uint32_t a, uint32_t b, uint32_t c) { uint32_t r; asm("lop3.b32 %0, %1, %2, %3, %4;" : "=r"(r) : "r"(a), "r"(b), "r"(c), "n"(F)); return r; }
__device__ __forceinline__ void stg128_tag(void* p, uint32_t x, uint32_t y, uint32_t z, uint32_t u, uint32_t ep, int w) {
    stg128(p, lop3<0xB8>(x, w == 0, ep), lop3<0xB8>(y, w == 1, ep), lop3<0xB8>(z, w == 2, ep), lop3<0xB8>(u, w == 3, ep));
}
__device__ __forceinline__ uint32_t tag(uint32_t w, uint32_t ep) { asm("lop3.b32 %0, %0, 1, %1, 0xB8;" : "+r"(w) : "r"(ep)); return w; }
template <int N> __device__ __forceinline__ void pack_part(uint32_t (&p)[32], const float (&v)[N], uint32_t ep) {
#pragma unroll
    for (int i = 0; i < N / 2; i++) p[i] = (i & 3) ? pack2(v[2 * i], v[2 * i + 1]) : tag(pack2(v[2 * i], v[2 * i + 1]), ep);
#pragma unroll
    for (int i = 0; i < N / 2; i++) asm volatile("" : "+r"(p[i]));
}
__device__ __forceinline__ void st_part(uint4* p, const uint32_t* v) {
    asm volatile("{\n.reg .b64 l, h;\n.reg .b128 q;\nmov.b64 l, {%1, %2};\nmov.b64 h, {%3, %4};\nmov.b128 q, {l, h};\nst.relaxed.gpu.global.b128 [%0], q;\n}"
                 ::"l"(p), "r"(v[0]), "r"(v[1]), "r"(v[2]), "r"(v[3]) : "memory");
}
__device__ __forceinline__ void st_peer(uint32_t a, uint32_t x, uint32_t y, uint32_t z, uint32_t w, uint32_t bar) {
    asm volatile("st.async.shared::cluster.mbarrier::complete_tx::bytes.v4.b32 [%0], {%1, %2, %3, %4}, [%5];" ::"r"(a), "r"(x), "r"(y), "r"(z), "r"(w), "r"(bar) : "memory");
}
__device__ __forceinline__ int g4_block(int c, int j) { return c ? j ^ (8 - 2 * c) : 8 + (j & 1); }
__device__ __forceinline__ uint32_t recv_off(int w) { return w ? OFF_XR : OFF_REM; }
__device__ __forceinline__ uint4 ld_part(const void* p) {
    uint4 v;
    asm volatile("{\n.reg .b64 l, h;\n.reg .b128 q;\nld.relaxed.gpu.global.b128 q, [%4];\nmov.b128 {l, h}, q;\nmov.b64 {%0, %1}, l;\nmov.b64 {%2, %3}, h;\n}"
                 : "=r"(v.x), "=r"(v.y), "=r"(v.z), "=r"(v.w) : "l"(p) : "memory");
    return v;
}
__device__ __forceinline__ void ld_part4(uint4 (&u)[4], const uint4* p, int st) {
#pragma unroll
    for (int i = 0; i < 4; i++) u[i] = ld_part(p + i * st);
}
__device__ __forceinline__ uint32_t stale4(const uint4 (&u)[4], uint32_t ep) { return lop3<0x7E>(u[0].x, ep, u[1].x) | lop3<0x7E>(u[2].x, ep, u[3].x); }
__device__ __forceinline__ uint4 add2(uint4 a, uint4 b) { return make_uint4(add2(a.x, b.x), add2(a.y, b.y), add2(a.z, b.z), add2(a.w, b.w)); }
__device__ __forceinline__ uint4 fin16(uint4 v, uint4 b, uint4 c) { return make_uint4(fma2(c.x, v.x, b.x), fma2(c.y, v.y, b.y), fma2(c.z, v.z, b.z), fma2(c.w, v.w, b.w)); }
__device__ __forceinline__ uint4 scale16(float2 c, float2 d, float r0, float r1) {
    return make_uint4(pack2(c.x * r0, c.y * r0), pack2(c.x * r1, c.y * r1), pack2(d.x * r0, d.y * r0), pack2(d.x * r1, d.y * r1));
}
__device__ __forceinline__ uint32_t split2(float x) { const float h = rbf(x); return pack2(h, x - h); }
__device__ __forceinline__ uint32_t b80_desc(uint32_t dsb, uint32_t wn, uint32_t rn, uint32_t h) {
    const uint32_t wb = dsb + OFF_W + (wn & 7) * 16384 + h * 8192, rm = dsb + OFF_REM + rn * 4096 + h * 2048;
    return (wb >> 4) | ((rm - wb) << 12);
}
constexpr int64_t B80_STEP = 128 - (126 << 16), B80_HALF = 512 - (384 << 16);
constexpr uint32_t ring_mask(int L) {
    uint32_t m = 0;
    for (int i = L; i < 20; i++) m |= (uint32_t)(i >= 20 - L || !((i - L) & 1)) << i;
    return m;
}
constexpr int pair_pos(int w, int i) { return w ? (i < 5 - LEAD2 ? LEAD2 + 2 * i : 5 + i) : (i < LEAD2 ? i : 2 * i - LEAD2 + 1); }
constexpr uint32_t pair_mask() { uint32_t m = 0; for (int i = 0; i < 5; i++) m |= 3u << (2 * pair_pos(1, i)); return m; }
constexpr uint32_t pair_slots(int w) { uint32_t m = 0; for (int i = 0; i < 5; i++) m |= (uint32_t)((2 + pair_pos(w, i)) & 3) << (2 * i); return m; }
constexpr uint32_t M0 = ring_mask(LEAD1), M1 = pair_mask(), M2 = ring_mask(XLEAD), P0S = pair_slots(0), P1S = pair_slots(1);
__device__ __forceinline__ uint32_t ring_pos(int w, int n, int L) { return w ? (n < 10 - L ? L + 2 * n : 10 + n) : (n < L ? n : 2 * n - L + 1); }
__device__ __forceinline__ int g1_block(int n, int j) { return n < 5 ? 2 * n + (j & 1) : 2 * n - 9 - (j & 1); }

__device__ __forceinline__ int g2_block(int n) { return (0x9874326510ull >> (4 * n)) & 15; }
__device__ __forceinline__ int g3_block(int n, int j) { return n ? n - (n <= j) : j; }
struct Tile { int e, w, kb; uint32_t at; };
__device__ __forceinline__ Tile ring_tile(int n, int grp, int j) {
    const int e = (n >= 20) + (n >= 40), i = n - 20 * e;
    const uint32_t M = e == 0 ? M0 : e == 1 ? M1 : M2;
    const int w = (M >> i) & 1, c = __popc(M & ((1u << i) - 1)), kb = w ? c : i - c, tile = grp + 16 * w;
    return {e, w, kb, 64u * (e == 0 ? tile + (g1_block(kb, j) << 16) : e == 1 ? g2_block(kb) + (tile << 16) : (10 * tile + g3_block(kb, j)) << 16)};
}
__device__ __forceinline__ void load_tile(const Maps& mp, uint32_t dst, int e, uint32_t at, uint32_t bar) {
    mbar_expect(bar, 8192);
    tma_ld2(dst, &mp.x[e], at & 0xffff, at >> 16, bar);
}

template <int OCT>
__device__ __forceinline__ void gemv_tile(float (&d)[4], uint32_t a, uint32_t b, int kb0) {
    uint32_t alo = ((a & 0x3FFFF) >> 4) | 0x10000u, blo_ = ((b & 0x3FFFF) >> 4) | (OCT << 16);
#pragma unroll 1
    for (int s = 0; s < 20; s += 4) {
        const int kb = kb0 + (s >> 2);
        const uint32_t bk = blo_ + (OCT == 7 ? (kb & 1) * 288 + (kb >> 1) * 56 : kb * 64);
        wg_fence();
#pragma unroll
        for (int q = 0; q < 4; q++) wgmma_ss8_ta(d, mkdesc(alo + (s + q) * 128), ((uint64_t)8 << 32) | (bk + q * 2 * OCT), s + q);
        wg_commit();
    }
    wg_wait<0>();
    reg_fence(d);
}

__device__ __forceinline__ void flush_tile(uint32_t st, bf16* dst, int u) {
#pragma unroll
    for (int i = 0; i < 2; i++) {
        const int idx = u + 320 * i, row = idx >> 3, c = idx & 7;
        stg128(dst + (size_t)row * S_ + 8 * c, lds128(st + row * 128 + ((c ^ ((row >> 1) & 7)) << 4)));
    }
}

__device__ __forceinline__ int tid_now() { int t; asm volatile("mov.u32 %0, %%tid.x;" : "=r"(t)); return t; }
__device__ __forceinline__ float zscale(float c) { return c == 0.f ? 0x1p-30f : c; }
__device__ __forceinline__ bool bar_any(int id, bool p) {
    uint32_t r;
    asm volatile("{\n.reg .pred a, b;\nsetp.ne.u32 a, %2, 0;\nbarrier.red.or.pred.aligned b, %1, 128, a;\nselp.u32 %0, 1, 0, b;\n}" : "=r"(r) : "r"(id), "r"((uint32_t)p) : "memory");
    return r != 0;
}

__global__ void __cluster_dims__(2, 1, 1) __launch_bounds__(NTHR, 1) fused_kernel(const __grid_constant__ Ptrs pp, bf16* __restrict__ out, const __grid_constant__ Maps mp) {
    extern __shared__ __align__(1024) uint8_t smem_raw[];
    const uint32_t sb = s2u(smem_raw), bars = sb + M_BAR, dsb = sb & 0x3FFFF;
    const int id = blockIdx.x, warp = __shfl_sync(0xffffffffu, (int)threadIdx.x >> 5, 0), wg = warp >> 2;
    const uint32_t c0 = clock_lo();
#define TIDS const int tid = tid_now(), lane = tid & 31, wt = tid & 127, g = lane >> 2, t = lane & 3; (void)wt; (void)g; (void)t;
    TS(threadIdx.x == 0, 0) TG(threadIdx.x == 0, 62)

    if (id >= 128) {
        TIDS
        if (sb & 1023) __trap();
        const int hs = id - 128;
        constexpr int H_B = 204800;
        static_assert(H_B + TAB_BYTES + 8 * VEC_BYTES <= OFF_M, "helper map");
        if (warp < 10 && elect()) { mbar_init(bars + warp * 8, 1); mbar_init(bars + 80 + warp * 8, 1); asm volatile("fence.mbarrier_init.release.cluster;" ::: "memory"); }
        __syncthreads();
        const uint32_t e0 = ld_cold(&g_epoch);
        wait_clock(c0, HELP_T);
        uint4 wr[10];
#pragma unroll
        for (int u = 0; u < 10; u++) wr[u] = ldg128(((hs >> 1) ? pp.w2 : pp.w1) + (size_t)(320 * (hs & 1) + (tid >> 4) + 32 * u) * D_ + 512 + 8 * (tid & 15));
        {
            const int r = tid >> 4, c = tid & 15;
            uint4* dst[2];
#pragma unroll
            for (int e = 0; e < 2; e++) {
                const int p = !(hs >> 1) ? r : e && (hs & 1) ? (r & ~14) | ((r & 6) << 1) | ((r & 8) >> 2) : (r & ~30) | ((r & 6) << 2) | ((r & 24) >> 2);
                dst[e] = &g_wr[((hs >> 1) * 8 + (c >> 1)) * 10 * 128 + (p & 15) * 8 + ((2 * (p >> 4) + (c & 1)) ^ (p & 7))];
            }
#pragma unroll
            for (int u = 0; u < 10; u++) stg128(reinterpret_cast<uint4*>(reinterpret_cast<uintptr_t>(dst[u >= 6]) ^ (64 * (u & 1))) +
                       ((hs >> 1) ? (0x9873265410ull >> (4 * (5 * (hs & 1) + (u >> 1)))) & 15 : 5 * (hs & 1) + (u >> 1)) * 128, wr[u]);
        }
        __syncthreads();
        if (warp == 0) signal_cnt(&g_cnt.wr[0], lane, 1);
        __syncthreads();
        if (warp < 5 && elect()) {
            const int un = 5 * hs + warp;
            mbar_expect(bars + warp * 8, 40960);
            tma_ld2(sb + warp * 40960, &mp.w1h, 64 * (un >> 1), 320 * (un & 1), bars + warp * 8);
            tma_ld2(sb + warp * 40960 + 20480, &mp.w1h, 64 * (un >> 1), 320 * (un & 1) + 160, bars + warp * 8);
        }
        if (tid < 320) {
            const uint4* gm = reinterpret_cast<const uint4*>(g_mod + 3 * D_) + tid;
            const unsigned epoch = e0 + 1;
            uint4 r[6];
            unsigned it = 0;
            for (;;) {
                uint32_t bad = 0;
#pragma unroll
                for (int i = 0; i < 6; i++) { r[i] = ld_part(gm + (i >> 1) * (D_ / 2) + (i & 1) * 3 * D_); bad |= (r[i].y ^ epoch) | (r[i].w ^ epoch); }
                if (__all_sync(~0u, !bad)) break;
                if (++it > SPIN_LIMIT) SPIN_FAIL(54)
            }
            uint32_t mv[3];
#pragma unroll
            for (int i = 0; i < 3; i++) mv[i] = pack2(__uint_as_float(r[2 * i].x) + __uint_as_float(r[2 * i + 1].x), __uint_as_float(r[2 * i].z) + __uint_as_float(r[2 * i + 1].z));
            const uint32_t sw2 = mv[0], cw = add2(mv[1], 0x3f803f80u), gw = mv[2];
            const float c0 = blo(cw), c1 = bhi(cw), s0 = blo(sw2), s1 = bhi(sw2);
            const float i0 = __frcp_rn(zscale(c0)), i1 = __frcp_rn(zscale(c1));
            const uint32_t ci = pack2(i0, i1), cq = pack2(i0 * i0, i1 * i1);
            const uint32_t a = sb + H_B + ((tid >> 5) & 1) * 4608 + (tid >> 6) * 896 + ((tid >> 2) & 7) * 112 + (tid & 3) * 4;
            sts32(a, ci); sts32(a + 16, pack2(i0 - blo(ci), i1 - bhi(ci)));
            sts32(a + 32, cq); sts32(a + 48, pack2(fmaf(i0, i0, -blo(cq)), fmaf(i1, i1, -bhi(cq))));
            sts32(a + 64, cw); sts32(a + 80, sw2); sts32(a + 96, 0x3f803f80u);
            if ((tid & ~35) == 284) sts32(a + 112, 0);
            const uint32_t v = sb + H_B + TAB_BYTES + (tid < 256 ? (tid >> 5) * VEC_BYTES + (tid & 31) * 8 : ((tid - 256) >> 3) * VEC_BYTES + 256 + (tid & 7) * 8);
            sts64f(v, blo(gw), bhi(gw)); sts64f(v + 320, c0, c1); sts64f(v + 640, s0, s1); sts64f(v + 960, i0, i1);
            float k[5] = {c0 + c1, s0 + s1, fmaf(c0, c0, c1 * c1), fmaf(c0, s0, c1 * s1), fmaf(s0, s0, s1 * s1)};
#pragma unroll 1
            for (int o = 16; o; o >>= 1) {
#pragma unroll
                for (int e = 0; e < 5; e++) k[e] += __shfl_xor_sync(~0u, k[e], o);
            }
            const uint32_t ks = sb + H_B + TAB_BYTES + (lane & 7) * VEC_BYTES + 1280 + (warp >> 1) * 32;
            if ((warp & 1) && lane < 8) { sts128f(ks, k[0], k[1], k[2], k[3]); sts128f(ks + 16, k[4], 0.f, 0.f, 0.f); }
            bar_sync(3, 320);
            if (!(warp & 1) && lane < 8) {
                const float4 o = lds128f(ks);
                sts128f(ks, k[0] + o.x, k[1] + o.y, k[2] + o.z, k[3] + o.w); sts32(ks + 16, __float_as_uint(k[4] + __uint_as_float(lds32(ks + 16))));
            }
            fence_async_smem();
        }
        __syncthreads();
        if (hs == 0 && warp == 15 && elect()) {
            asm volatile("cp.async.bulk.global.shared::cta.bulk_group [%0], [%1], %2;\ncp.async.bulk.commit_group;\ncp.async.bulk.wait_group 0;"
                         ::"l"(g_tab), "r"(sb + H_B), "n"(TAB_BYTES + 8 * VEC_BYTES) : "memory");
            asm volatile("red.release.gpu.global.add.u32 [%0], 1;" ::"l"(&g_cnt.tab[0]) : "memory");
        }
        __syncwarp();
#pragma unroll 1
        for (int i = wg; i < 20; i += 4) {
            const int r = i / 5, b = i - 5 * r, un = 5 * hs + b, u3 = 20 * r + un;
            auto refill = [&](int e, int u, uint32_t fb) {
                mbar_expect(fb, 40960);
                tma_ld2(sb + e * 40960, &mp.w3h, 64 * (u >> 1), 320 * (u & 1), fb);
                tma_ld2(sb + e * 40960 + 20480, &mp.w3h, 64 * (u >> 1), 320 * (u & 1) + 160, fb);
            };
            if (i > 4 && i < 9) {
                bar_sync(1, 512);
                if (warp == 0) {
                    signal_cnt(&g_cnt.uv[0], lane, 1);
                    if (elect()) {
#pragma unroll 1
                        for (int e = 0; e < 5; e++) refill(e, 5 * hs + e, bars + (5 + e) * 8);
                        l2_prefetch(pp.w2 + (size_t)160 * hs * D_, 160 * D_ * 2);
                    }
                    __syncwarp();
                }
            }
            mbar_wait(bars + i * 8, 0);
            float d[4];
            gemv_tile<7>(d, sb + b * 40960, sb + H_B, 5 * (un & 1));
            const int col = 16 * (warp & 3) + g;
            float* dst = r ? g_cs3 + (un & 1) * 1920 + 64 * ((u3 >> 1) - 10) + col : g_uv + (un & 1) * 3 * D_ + 2 * D_ + 64 * (un >> 1) + col;
            if (t == 3) { dst[0] = d[0]; dst[8] = d[2]; }
            if (r == 0 && t == 2) { dst[-2 * D_] = d[0]; dst[8 - 2 * D_] = d[2]; dst[-D_] = d[1]; dst[8 - D_] = d[3]; }
            if (r == 1 || r == 2) {
                bar_sync(4 + wg, 128);
                if (wt == 0) refill(b, u3, bars + (i + 5) * 8);
            }
        }
        __syncthreads();
        if (warp == 0) signal_cnt(&g_cnt.cs[0], lane, 1);
        if (tid == 511) l2_prefetch(pp.w4 + (size_t)432 * hs * D_, 432 * D_ * 2);
        for (uint32_t it = 0; ld_cold(&g_cnt.cs[0]) < 4;) { if (++it > SPIN_LIMIT) SPIN_FAIL(47) }
        asm volatile("fence.acquire.gpu;" ::: "memory");
        if (tid < 432) {
            const int jj = 2 * hs + (tid >= 216), c = tid % 216;
            const float* src = g_cs3 + (c < 192 ? 192 * jj + c : 1344 + 24 * jj + c);
            const uint32_t s = split2(ldcg32f(src) + ldcg32f(src + 1920));
            stg128(&g_cs3b[432 * hs + tid], s, s & 0xffffu, 0, 0);
        }
        __syncthreads();
        if (warp == 0) signal_cnt(&g_cnt.cs2[0], lane, 1);
        if (tid == 0 && hs == 3) {
            uint32_t it = 0;
            while (ld_cold(&g_epoch) == e0) { __nanosleep(256); if (++it > (1u << 20)) SPIN_FAIL(48) }
        }
        return;
    }

    if (elect()) {
        if (warp == 15) {
            mbar_init(bars + B_IN * 8, 1); mbar_init(bars + B_IN * 8 + 8, 1);
            asm volatile("fence.mbarrier_init.release.cluster;" ::: "memory");
            mbar_expect(bars + B_IN * 8, 131 * 160);
            tma_ld2(sb + OFF_KIN, &mp.k, 80 * (id & 7), 64 * (id >> 3) - 3, bars + B_IN * 8);
            tma_ld2(sb + OFF_VIN, &mp.v, 80 * (id & 7), 64 * (id >> 3), bars + B_IN * 8);
        } else if (warp < 13) {
            const uint32_t n = (0x4C11111111881ull >> (4 * warp)) & 15;
#pragma unroll
            for (int i = 0; i < 4; i++) mbar_init(bars + warp * 64 + i * 8, n);
            if (warp == 11) { mbar_init(bars + B_XFREE * 8, 16); mbar_init(bars + B_OWN * 8, 8); }
            else {
#pragma unroll
                for (int i = 4; i < 8; i++) mbar_init(bars + warp * 64 + i * 8, n);
            }
            asm volatile("fence.mbarrier_init.release.cluster;" ::: "memory");
        }
    }
    asm volatile("" ::"l"(pp.s), "l"(pp.c), "l"(out));
    TR4((threadIdx.x & 31) == 0, warp)
    const int pr = id >> 1;
    const int grp = pr < 4 ? 15 : pr < 36 ? (pr - 4) & 7 : 8 + (pr - 36) % 7;
    const int j = 2 * (pr < 4 ? pr : pr < 36 ? (pr - 4) >> 3 : (pr - 36) / 7) + (id & 1);

    if (wg == 3) {
        TIDS
        const int sw = warp - 12;
        uint32_t ep = ld_cold(&g_epoch);
        TR4(lane == 0, 20 + sw)
        __syncthreads();
        TR4(lane == 0, 30 + sw)
        asm volatile("barrier.cluster.arrive.relaxed.aligned;" ::: "memory");
        if (sw == 0) {
#pragma unroll 1
            for (int n = 0; n < 12; n++) {
                wait_clock(c0, PF_T0 + PF_DT * n);
                if (elect()) l2_prefetch(n < 4 ? (const char*)pp.q + id * 20480 + n * 5120 : (const char*)pp.w_mod + id * 38400 + (n - 4) * 4800, n < 4 ? 5120 : 4800);
            }
        } else if (sw == 1) {
            wait_clock(c0, T_SSM);
            if (elect()) {
                mbar_expect(bars + B_SSM * 8, 20480);
                bulk_ld(sb + OFF_SSM, pp.ssm_k + (size_t)5 * id * S_, 20480, bars + B_SSM * 8);
            }
            mbar_spin(bars + B_KVS * 8, 0);
            signal_cnt(&g_cnt.kv[(id & 7) * 32], lane, 1, true);
            TS(lane == 0, 2)
            mbar_spin(bars + B_RAW * 8, 0);
            if (elect()) {
                mbar_expect(bars + B_QIN * 8, 20480);
                tma_ld3(sb + OFF_QIN, &mp.q, 0, 16 * id, 0, bars + B_QIN * 8);
            }
        } else if (sw == 2) {
            if (elect()) {
#pragma unroll 1
                for (int i = 2; i < (int)(sizeof(Maps) / sizeof(CUtensorMap)); i++) asm volatile("prefetch.tensormap [%0];" ::"l"(&mp.k + i) : "memory");
#pragma unroll 1
                for (int i = B_SUMS; i < B_LAND; i++) mbar_expect(bars + i * 8, i < B_RECV ? 2048 : (i & 3) < 3 ? 8192 : 3072);
            }
            wait_cnt(&g_cnt.kv[(id >> 4) * 32], 16, true);
            TS(lane == 0, 4)
            if (elect()) {
                mbar_expect(bars + B_RAW * 8, 12288);
                mbar_expect(bars + B_RAW2 * 8, 8192);
#pragma unroll
                for (int c = 0; c < 5; c++) bulk_ld(sb + OFF_CH + c * CH_BYTES, g_kvT + (size_t)(5 * id + c) * S_, 4096, bars + (c < 3 ? B_RAW : B_RAW2) * 8);
            }
            mbar_spin(bars + B_BK * 8, 0);
            mbar_spin(bars + B_QIN * 8, 0);
            if (id < 120 && elect()) {
                mbar_expect(bars + B_WM * 8, 40960);
                tma_ld2(sb + OFF_WM, &mp.wmod, 64 * pr, 320 * (id & 1), bars + B_WM * 8);
                tma_ld2(sb + OFF_WM + 20480, &mp.wmod, 64 * pr, 320 * (id & 1) + 160, bars + B_WM * 8);
            }
            TS(lane == 0, 57)
        } else {
            wait_clock(c0, T_KVB);
            if (elect()) {
                mbar_expect(bars + (B_IN + 1) * 8, 131 * 160);
                tma_ld2(sb + OFF_KIN + 10752, &mp.k, 80 * (id & 7), 64 * (id >> 3) + 1021, bars + (B_IN + 1) * 8);
                tma_ld2(sb + OFF_VIN + 10240, &mp.v, 80 * (id & 7), 64 * (id >> 3) + 1024, bars + (B_IN + 1) * 8);
            }
            TS(lane == 0, 53)
            if (lane == 0) sts32(sb + M_EP, ep + 1);
            sts32(sb + M_NUL + lane * 4, 0);
#pragma unroll 1
            for (int i = 0; i < 10; i++) sts128(sb + OFF_Z + i * 512 + lane * 16, 0, 0, 0, 0);
            __syncwarp();
#pragma unroll 1
            for (int i = lane; i < 160; i += 32) {
                const uint32_t c = ldg32(pp.c + 320 * (id & 1) + 2 * i);
                sts32(sb + OFF_Z + (i >> 2) * 128 + (i & 3) * 4, pack2(silu(blo(c)), silu(bhi(c))));
            }
            fence_async_smem();
            for (uint32_t ph = 0, again = 1; again; ph ^= 1) {
                mbar_spin(bars + B_RAW2 * 8, ph);
                uint32_t bad = 0;
#pragma unroll
                for (int i = 0; i < 8; i++) bad |= lop3<0x7E>(lds32(sb + OFF_CH + 3 * CH_BYTES + i * 512 + lane * 16), ~ep, lds32(sb + OFF_CH + 4 * CH_BYTES + i * 512 + lane * 16));
                again = __any_sync(~0u, bad & 1);
                if (again && elect()) {
                    mbar_expect(bars + B_RAW2 * 8, 8192);
#pragma unroll
                    for (int c = 3; c < 5; c++) bulk_ld(sb + OFF_CH + c * CH_BYTES, g_kvT + (size_t)(5 * id + c) * S_, 4096, bars + B_RAW2 * 8);
                }
            }
            if (elect()) mbar_arrive(bars + B_RAW3 * 8);
        }
        {
            mbar_spin(bars + B_QIN * 8, 0);
            asm volatile("add.u32 %0, %0, 1;" : "+r"(ep));
            TS(wt == 0, 54)
            const int tk = 8 * ((lane >> 1) & 1) + 2 * (lane >> 3) + (lane & 1), ck = 4 * (sw & 1) + ((lane >> 1) & 2);
            const uint32_t src = sb + OFF_QIN + (sw >> 1) * 2048 + tk * 128;
            bf16* dst = g_qT + (size_t)id * 16 * D_ + (32 * sw + 8 * (t & 2) + g) * 16 + 8 * (t & 1);
constexpr int QU = Q_UNROLL;
#pragma unroll QU
            for (int i = 0; i < 5; i++) {
                uint32_t r[8];
                ldsm4t(src + i * 4096 + ((ck ^ (tk & 7)) << 4), r[0], r[1], r[2], r[3]);
                ldsm4t(src + i * 4096 + (((ck + 1) ^ (tk & 7)) << 4), r[4], r[5], r[6], r[7]);
                stg128(dst + i * 2048, tag(r[0], ep), r[1], r[2], r[3]);
                stg128(dst + i * 2048 + 128, tag(r[4], ep), r[5], r[6], r[7]);
            }
            float s1 = 0.f, s2 = 0.f;
#pragma unroll 2
            for (int i = 0; i < 10; i++) {
                const uint4 w4 = lds128(sb + OFF_QIN + i * 2048 + wt * 16);
                const uint32_t w[4] = {w4.x, w4.y, w4.z, w4.w};
#pragma unroll
                for (int e = 0; e < 4; e++) { const float a = blo(w[e]), b = bhi(w[e]); s1 += a + b; s2 = fmaf(a, a, fmaf(b, b, s2)); }
            }
#pragma unroll
            for (int o = 1; o < 8; o *= 2) { s1 += __shfl_xor_sync(~0u, s1, o); s2 += __shfl_xor_sync(~0u, s2, o); }
            s1 *= 1.f / D_;
            uint32_t rs = pack2(rsqrtf(fmaxf(s2 * (1.f / D_) - s1 * s1, 0.f) + 1e-5f), 0.f);
            if (lane < 8) rs = tag(rs, ep);
            rs = pack2(blo(rs), -s1 * blo(rs));
            const uint32_t sel = lane ? 0x7632 : 0x5410;
            const uint32_t a0 = __shfl_sync(~0u, rs, 0), a1 = __shfl_sync(~0u, rs, 8), a2 = __shfl_sync(~0u, rs, 16), a3 = __shfl_sync(~0u, rs, 24);
            if (lane < 2) stg64(g_qst + lane * S_ + 16 * id + 4 * sw, tag(__byte_perm(a0, a1, sel), ep), __byte_perm(a2, a3, sel));
            TS(wt == 0, 55)
        }
        bar_sync(6, 128);
        if (sw == 3) {
            signal_cnt(&g_cnt.q[(lane & 3) * 32], lane, 4, true);
            TS(lane == 0, 3)
        }
        asm volatile("setmaxnreg.dec.sync.aligned.u32 " STR(REG_SVC) ";");
        asm volatile("barrier.cluster.wait.aligned;" ::: "memory");
        if (sw == 1) {
            mbar_spin(bars + B_XS * 8, 0);
            signal_cnt(&g_cnt.x[(lane & 3) * 32], lane, 4, true);
            TS(lane == 0, 20)
        }
        if (sw == 1 || sw == 2) {
            mbar_spin(bars + B_XS * 8, 0);
            fence_async_smem();
            int n = sw & 1;
            const uint32_t plan = ring_tile(min(2 * lane + n, 59), grp, j).at;
#pragma unroll 1
            for (int s = 0; s < 7; s++) {
                const int e = (s >= 2) + (s >= 5), end = (0ull + LEAD1 + (20 << 8) + (24 << 16) + ((20ull + 2 * LEAD2) << 24) + (40ull << 32) + ((40ull + XLEAD) << 40) + (60ull << 48)) >> (8 * s) & 255;
                if (s == 1 || s == 4 || s == 6) mbar_spin(bars + (B_GATE + 2 + e) * 8, !e);
                else if (s != 3 || grp == 15) {
                    wait_cnt(s == 0 ? &g_cnt.x[(id & 3) * 32] : s == 5 ? &g_cnt.g2[grp * 32] : &g_cnt.g1[(s == 2 ? min(max(grp - 1 + min(lane, 2), 0), 15) : 16) * 32], e ? 32 : 128, true);
                    TS(lane == 0 && sw == 2 && s != 3, 26 + 2 * e)
                }
#pragma unroll 1
                for (; n < end; n += 2) {
                    const uint32_t at = __shfl_sync(~0u, plan, n >> 1);
                    mbar_spin(bars + (B_XEMPTY + (n & 7)) * 8, ((n >> 3) & 1) ^ 1);
                    TR2(lane == 0 && n < 40, 20 + n)
                    if (elect()) {
                        if (n == 40 || n == 40 + XLEAD) {
                            mbar_arrive(bars + (B_LAND + (n & 7)) * 8);
                            asm volatile("mbarrier.arrive.shared.b64 _, [%0], 8;" ::"r"(bars + (B_XEMPTY + (n & 7)) * 8) : "memory");
                        } else load_tile(mp, sb + OFF_XR + (n & 7) * 8192, e, at, bars + (B_LAND + (n & 7)) * 8);
                    }
                }
            }
            if (sw == 1) { if (elect()) mbar_arrive(bars + (B_GATE + 5) * 8); return; }
            mbar_spin(bars + (B_GATE + 5) * 8, 0);
            mbar_spin(bars + B_VEC3 * 8, 0);
            unsigned old = 0;
            asm volatile("{\n.reg .pred P;\nsetp.eq.s32 P, %2, 0;\n@P atom.relaxed.gpu.global.add.u32 %0, [%1], %3;\n}" : "+r"(old) : "l"(&g_cnt.done[0]), "r"(lane), "r"(1) : "memory");
            if (__any_sync(~0u, old == 127)) {
#pragma unroll 1
                for (int i = lane; i < (int)(sizeof(Counters) / 128); i += 32) reinterpret_cast<unsigned*>(&g_cnt)[i * 32] = 0;
                signal_cnt(&g_epoch, lane, 1, true);
            }
        } else if (sw == 0) {
            wait_cnt(&g_cnt.wr[0], 4);
            mbar_spin(bars + B_QRDY * 8, 0);
            const uint32_t wf = bars + B_WFULL * 8, we = bars + B_WEMPTY * 8;
#pragma unroll 1
            for (int n = 0; n < 5; n++) {
                if (n == 3) { mbar_spin(bars + B_XS * 8, 0); fence_async_smem(); }
                TR2(lane == 0, 70 + n)
                if (elect()) {
                    const uint32_t fb = wf + n * 8, dst = sb + OFF_W + n * 16384;
                    mbar_expect(fb, 20480);
#pragma unroll 1
                    for (int h = 0; h < 2; h++) {
                        const int kb = g1_block(2 * n + h, j);
                        tma_ld2(dst + h * 8192, &mp.w1, 64 * j, 64 * kb, fb);
                        bulk_ld(sb + OFF_REM + n * 4096 + h * 2048, &g_wr[(j * 10 + kb) * 128], 2048, fb);
                    }
                }
            }
            mbar_spin(bars + B_GATE * 8, 0);
#pragma unroll 1
            for (int i = -3; i < 5; i++) {
                const int n = i < 0 ? 8 + i : 5 + i;
                const uint32_t fb = wf + (n & 7) * 8;
                if (i >= 0) mbar_spin(we + i * 8, 0);
                TR2(lane == 0 && i >= 0, 70 + n)
                if (elect()) {
                    if (i < 0 || i >= 3) {
                        mbar_expect(fb, 20480);
#pragma unroll 1
                        for (int h = 0; h < 2; h++) tma_ld5(sb + OFF_W + (n & 7) * 16384 + h * 8192, n < 9 ? &mp.w2a : &mp.w2b, 64 * j, n < 9 ? 2 * g2_block(2 * n - 10 + h) : 4 * h, fb);
                    }
                    if (i >= 0) bulk_ld(sb + OFF_REM + i * 4096, &g_wr[((8 + j) * 10 + 2 * i) * 128], 4096, fb);
                }
            }
            mbar_spin(bars + (B_GATE + 1) * 8, 0);
#pragma unroll 1
            for (int n = 10; n < 30; n++) {
                if (n == W3_N2) mbar_spin(bars + (B_GATE + 2) * 8, 0);
                mbar_spin(we + (n & 7) * 8, ((n >> 3) & 1) ^ 1);
                TR2(lane == 0, 70 + n)
                if (elect()) {
                    const uint32_t dst = sb + OFF_W + (n & 7) * 16384, fb = wf + (n & 7) * 8;
                    mbar_expect(fb, 13824);
                    const int row = 64 * g3_block((n - 10) >> 1, j) + 32 * (n & 1);
                    tma_ld3(dst, &mp.w3a, 0, row, 3 * j, fb);
                    tma_ld2(dst + 12288, &mp.w3b, 1536 + 24 * j, row, fb);
                }
            }
            mbar_spin(we + 6 * 8, 0);
            mbar_spin(bars + B_VEC3 * 8, 0);
            if (elect()) { mbar_expect(wf + 6 * 8, 3456); bulk_ld(sb + OFF_W + 6 * 16384, &g_cs3b[216 * j], 3456, wf + 6 * 8); }
#pragma unroll 1
            for (int n = 31; n < 50; n++) {
                const int e = n < 38 ? 4 : (n - 38) & 3, m0 = n == 35, m1 = e == 3 ? -1 : m0 | (e == 1), rem = 96 + 3 * (j >> 1);
                const int c1_ = j ^ (n < 38 ? 6 : 4 >> ((n - 38) >> 2) & 6), c0_ = n < 38 ? 8 + (j & 1) : c1_;
                const int f = (0xC840A80C204ull >> (4 * min(n - 31, e + 7))) & 15;
                const int r0 = m0 ? rem : 6 * (j ^ (f >> 3)) + (f & 6), r1 = m1 ? rem : r0 + (n < 38 ? 0 : 2);
                mbar_spin(we + (n & 7) * 8, ((n >> 3) & 1) ^ 1);
                if (elect()) {
                    const uint32_t dst = sb + OFF_W + (n & 7) * 16384, fb = wf + (n & 7) * 8;
                    mbar_expect(fb, m1 < 0 ? 8192 : 16384 - 2048 * (m0 + m1));
                    tma_ld2(dst, &mp.w4[m0], 64 * c0_, r0 * (32 >> m0), fb);
                    if (m1 >= 0) tma_ld2(dst + 8192, &mp.w4[m1], 64 * c1_, r1 * (32 >> m1), fb);
                }
            }
        } else {
            {
                wait_cnt(&g_cnt.tab[0], 1);
                mbar_spin(bars + B_QRDY * 8, 0);
                if (elect()) {
                    mbar_expect(bars + B_TAB * 8, TAB_BYTES / 2 + VEC_BYTES);
                    bulk_ld(sb + OFF_TAB, g_tab + (j & 1) * (TAB_BYTES / 32), TAB_BYTES / 2, bars + B_TAB * 8);
                    bulk_ld(sb + M_GB, g_tab + (TAB_BYTES + j * VEC_BYTES) / 16, VEC_BYTES, bars + B_TAB * 8);
                }
                TS(lane == 0, 5)
            }
            wait_cnt(&g_cnt.uv[0], 4);
#pragma unroll 1
            for (int c = lane; c < 80; c += 32) {
                const float* src = g_uv + (c < 64 ? 64 * j + c : 448 + 16 * j + c);
                const uint32_t u = split2(ldcg32f(src) + ldcg32f(src + 3 * D_)), v = split2(ldcg32f(src + D_) + ldcg32f(src + 4 * D_));
                const uint32_t s = split2(ldcg32f(src + 2 * D_) + ldcg32f(src + 5 * D_));
                sts128(sb + OFF_F1 + c * 16, u, __byte_perm(u, v, 0x5410), __byte_perm(v, 0, 0x1032), s);
                sts128(sb + M_F1 + c * 16, s & 0xffffu, 0, 0, 0);
            }
            fence_async_smem();
            warp_arrive(bars + B_VEC * 8);
            TS(lane == 0, 9)
#pragma unroll 1
            for (int e = 1; e < 3; e++) {
                wait_cnt(e == 1 ? &g_cnt.g1[min(grp + 15 + min(lane, 2), 31) * 32] : &g_cnt.g2[(grp + 16) * 32], 32, true);
                if (elect()) mbar_arrive(bars + (B_GATE + 2 + e) * 8);
                TS(lane == 0, 27 + 2 * e)
            }
            wait_cnt(&g_cnt.cs2[0], 4);
            if (elect()) mbar_arrive(bars + B_VEC3 * 8);
            TS(lane == 0, 19)
        }
        return;
    }

    {
        uint32_t ep;
        {
            TIDS
            ep = ld_cold(&g_epoch);
            const int cp = (tid + 16) % 40, cp1 = tid % 40;
            const uint4 sh0 = ldg128(pp.shift_k + (80 * (id & 7) + 2 * cp1) * 4), sh1 = ldg128(pp.shift_k + (80 * (id & 7) + 2 * cp) * 4);
            uint32_t dd;
            asm volatile("ld.global.nc.u16 %0, [%1];" : "=r"(dd) : "l"(pp.ssm_D + 5 * id + min(wg + 3 * lane, 4)));
            TR4(lane == 0, 40 + warp)
            __syncthreads();
            asm volatile("barrier.cluster.arrive.relaxed.aligned;" ::: "memory");
            asm volatile("add.u32 %0, %0, 1;" : "+r"(ep));
#pragma unroll 1
            for (int hw = 0; hw < 2; hw++) {
                if ((unsigned)(warp - 2 * hw) >= 10) continue;
                const int u = tid - 64 * hw;
                const int c = hw ? cp : cp1, oc = u / 40, line = 31 - 16 * hw - (id >> 3);
                const uint4 sh = hw ? sh1 : sh0;
                const uint32_t st = sb + OFF_ST + hw * 10240, sta = st + c * 256 + ((((6 - 2 * (oc & 3)) ^ (oc >> 2) ^ (line & 1)) ^ (c & 7)) << 4), in = oc * 1280 + c * 4;
                const uint32_t f0 = __byte_perm(sh.x, sh.z, 0x5410), f1 = __byte_perm(sh.x, sh.z, 0x7632), f2 = __byte_perm(sh.y, sh.w, 0x5410), f3 = __byte_perm(sh.y, sh.w, 0x7632);
                uint32_t kk[11], vv[8];
                mbar_spin(bars + (B_IN + hw) * 8, 0);
                TS(tid == 64, 18 + 42 * hw)
#pragma unroll
                for (int i = 0; i < 11; i++) kk[i] = lds32(sb + OFF_KIN + hw * 10752 + in + i * 160);
#pragma unroll
                for (int i = 0; i < 8; i++) vv[i] = lds32(sb + OFF_VIN + hw * 10240 + in + i * 160);
#pragma unroll
                for (int i = 0; i < 8; i++) vv[i] = mul2(fma2(kk[i + 3], f0, fma2(kk[i + 2], f1, fma2(kk[i + 1], f2, mul2(kk[i], f3)))), vv[i]);
                sts128(sta, tag(__byte_perm(vv[0], vv[1], 0x5410), ep), __byte_perm(vv[2], vv[3], 0x5410), __byte_perm(vv[4], vv[5], 0x5410), __byte_perm(vv[6], vv[7], 0x5410));
                sts128(sta + 128, tag(__byte_perm(vv[0], vv[1], 0x7632), ep), __byte_perm(vv[2], vv[3], 0x7632), __byte_perm(vv[4], vv[5], 0x7632), __byte_perm(vv[6], vv[7], 0x7632));
                bar_sync(7 + hw, 320);
                flush_tile(st, g_kvT + (size_t)(80 * (id & 7)) * S_ + 64 * line, u);
                TS(tid == 64 && hw, 1)
            }
            warp_arrive(bars + B_KVS * 8);
            if (tid < 320) sts128(sb + OFF_CH + (tid >> 6) * CH_BYTES + 4096 + (tid & 63) * 16, 0, 0, 0, 0);
            mbar_spin(bars + B_SSM * 8, 0);
            TS(tid == 0, 14)
#pragma unroll 1
            for (int u0 = wg; u0 < 20; u0 += 12) {
                uint2 w[4];
                uint32_t pv[4];
#pragma unroll
                for (int i = 0; i < 4; i++) {
                    const uint32_t a = sb + OFF_SSM + min(u0 + 3 * i, 19) * 1024 + wt * 8;
                    w[i] = lds64(a); pv[i] = lds32(a - 4);
                }
#pragma unroll
                for (int i = 0; i < 4; i++) {
                    const int un = min(u0 + 3 * i, 19);
                    sts128(sb + OFF_CH + (un >> 2) * CH_BYTES + OFF_P + (un & 3) * 2048 + wt * 16, __byte_perm(w[i].x, pv[i], 0x7610), __byte_perm(w[i].x, 0, 0x1032), __byte_perm(w[i].y, w[i].x, 0x7610), __byte_perm(w[i].y, 0, 0x1032));
                }
            }
            __syncwarp();
            if (wt < 2 - (wg >> 1)) {
                const uint32_t h = lds32(sb + OFF_SSM + (wg + 3 * wt) * 4096), h0 = pack2(blo(h) + blo(dd), 0.f);
                sts64f(sb + OFF_CH + (wg + 3 * wt) * CH_BYTES + OFF_P, __uint_as_float(h0), __uint_as_float(__byte_perm(h, h0, 0x5432)));
            }
            fence_async_smem();
            warp_arrive(bars + B_BK * 8);
            asm volatile("barrier.cluster.wait.aligned;" ::: "memory");
            mbar_spin(bars + B_BK * 8, 0);
            TS(tid == 0, 15)
        }

#pragma unroll 1
        for (int c = wg; c < 5; c += 3) {
            const uint32_t kvb = sb + OFF_CH + c * CH_BYTES;
            mbar_spin(bars + (c < 3 ? B_RAW : B_RAW3) * 8, 0);
            for (uint32_t ph = 0; c < 3; ph ^= 1) {
                const int wt = tid_now() & 127;
                if (!RARE(bar_any(1 + wg, lop3<0x7E>(lds32(kvb + wt * 16), ep, lds32(kvb + 2048 + wt * 16)) & 1))) break;
                if (wt == 0) { mbar_expect(bars + (B_RETRY + wg) * 8, 4096); bulk_ld(kvb, g_kvT + (size_t)(5 * id + c) * S_, 4096, bars + (B_RETRY + wg) * 8); }
                mbar_spin(bars + (B_RETRY + wg) * 8, ph);
                STALE1(-8)
            }
            TS(threadIdx.x == 0, c ? 13 : 11)
            float acc[64];
            {
                const int l = tid_now() & 31;
                conv_channel(acc, kvb + OFF_P + (8 * (warp & 3) + (l >> 2) - 2 * (l & 3)) * 4, (((uint64_t)0xC0000010u << 32) | ((kvb & 0x3FFFF) >> 4) | 0x10000u) + pp.nil);
            }
            TS(threadIdx.x == 0, c ? 16 : 12)
            if (c < 3) warp_arrive(bars + B_R1 * 8);
            else mbar_spin(bars + B_R1 * 8, 0);
            if (wg == 2 && id < 120) {
                TIDS
                mbar_spin(bars + B_RAW3 * 8, 0);
                mbar_spin(bars + B_WM * 8, 0);
                TS(wt == 0, 56)
                float d[4];
                gemv_tile<8>(d, sb + OFF_WM, sb + OFF_Z, 0);
                const float d2 = __shfl_up_sync(~0u, d[2], 1);
                TS(wt == 0, 7)
                if (t < 2) asm volatile("{\n.reg .b64 v;\nmov.b64 v, {%1, %2};\nst.relaxed.gpu.global.b64 [%0], v;\n}" ::"l"(g_mod + (id & 1) * 6 * D_ + 64 * pr + 16 * (warp & 3) + g + 8 * t),
                                        "r"(__float_as_uint(t ? d2 : d[0])), "r"(lds32(sb + M_EP)) : "memory");
            }
            TR4(threadIdx.x == 0, 60 + (c >= 3) * 10)
            TIDS
            const int e = 127 - 8 * (lane >> 4) - (lane & 7), u0 = (warp & 3) + 8 * (e >> 2) + (e & 3) + 4 * ((lane >> 3) & 1);
            const uint32_t ring = sb + OFF_RING + c * 16384 + (warp & 3) * 4096, wa = ring + (u0 ^ ((u0 >> 1) & 4)) * 16;
            if (lane < (warp & 3)) sts128(ring + lane * 16, 0, 0, 0, 0);
#pragma unroll
            for (int i = 0; i < 8; i++)
                stsm4t(i == 0 && u0 >= 256 ? sb + M_SINK : wa - 512 * i, pack2(acc[8 * i], acc[8 * i + 1]), pack2(acc[8 * i + 2], acc[8 * i + 3]),
                       pack2(acc[8 * i + 4], acc[8 * i + 5]), pack2(acc[8 * i + 6], acc[8 * i + 7]));
            warp_arrive(bars + (B_RING + c) * 8);
            TR4(threadIdx.x == 0, 61 + (c >= 3) * 10)
        }
        TIDS
        if (wg == 2) bar_sync(3, 128);
        if (warp == 8) {
            wait_cnt(&g_cnt.q[(id & 3) * 32], 128, true);
            if (elect()) {
                mbar_expect(bars + B_QRDY * 8, 28672);
                tma_ld2(sb + OFF_QT, &mp.qT, 80 * id, 0, bars + B_QRDY * 8);
                bulk_ld(sb + OFF_QT + 20480, g_qst, 8192, bars + B_QRDY * 8);
            }
            TS(lane == 0, 8)
        } else if (warp == 9) {
            const int v = min(lane / 5, 3);
            const uint2* gm = g_mod + (v + (v == 3)) * D_ + 5 * id + lane % 5;
            const unsigned epoch = lds32(sb + M_EP);
            uint2 r0, r1;
            unsigned it = 0;
            do {
                r0 = ld_mod(gm); r1 = ld_mod(gm + 6 * D_);
                SPIN_CHECK(55)
            } while (!__all_sync(~0u, r0.y == epoch && r1.y == epoch));
            const float m0 = __uint_as_float(r0.x), m1 = __uint_as_float(r1.x);
            const float m = rbf(m0 + m1), p = rbf(1.f + m);
            const float cz = zscale(__shfl_sync(~0u, p, 15 + lane % 5)), ga = __shfl_sync(~0u, m, 10 + lane % 5);
            if (lane < 15) sts32(sb + M_AB + lane % 5 * 16 + v * 4, lane < 10 ? __float_as_uint(cz * ga * (lane < 5 ? m : p)) : pack2(cz, cz));
            warp_arrive(bars + B_MODR * 8);
            TS(lane == 0, 6)
        }
        mbar_spin(bars + B_QRDY * 8, 0);
        uint4 rs[2], nm[2];
#pragma unroll
        for (int h = 0; h < 2; h++) { rs[h] = lds128(sb + OFF_QT + 20480 + h * 2048 + wt * 16); nm[h] = lds128(sb + OFF_QT + 24576 + h * 2048 + wt * 16); }
        mbar_spin(bars + B_MODR * 8, 0);
        TR4(threadIdx.x == 0, 72)
        uint32_t it = 0;
        while (RARE(__any_sync(~0u, (lop3<0x7E>(rs[0].x, ep, rs[0].z) | lop3<0x7E>(nm[0].x, ep, nm[0].z) | lop3<0x7E>(rs[1].x, ep, rs[1].z) | lop3<0x7E>(nm[1].x, ep, nm[1].z)) & 1))) {
#pragma unroll
            for (int h = 0; h < 2; h++) { rs[h] = ld_part(g_qst + 1024 * h + 8 * wt); nm[h] = ld_part(g_qst + S_ + 1024 * h + 8 * wt); }
            STALE(1)
            SPIN_CHECK(53)
        }
        TR4(threadIdx.x == 0, 73)
#pragma unroll 1
        for (int c = wg == 2 ? 0 : 3 + wg; c < (wg == 2 ? 3 : 4 + wg); c++) {
            uint4 q[2], p[2][4];
#pragma unroll
            for (int h = 0; h < 2; h++) q[h] = lds128(sb + OFF_QT + h * 10240 + (wt >> 1) * 160 + c * 32 + (wt & 1) * 16);
            const float4 ab = lds128f(sb + M_AB + c * 16);
            mbar_spin(bars + (B_RING + c) * 8, 0);
            TR4(wt == 0, wg == 2 ? 80 + 2 * c : 74)
#pragma unroll
            for (int i = 0; i < 8; i++) p[i >> 2][i & 3] = lds128(sb + OFF_RING + c * 16384 + (i & 3) * 4096 + (i >> 2) * 2048 + (wt ^ ((wt >> 1) & 4)) * 16);
            while (RARE(__any_sync(~0u, lop3<0x7E>(q[0].x, ep, q[1].x) & 1))) {
#pragma unroll
                for (int h = 0; h < 2; h++) q[h] = ld_part(g_qT + ((64 * h + (wt >> 1)) * D_ + 5 * id + c) * 16 + 8 * (wt & 1));
                STALE(2)
                SPIN_CHECK(52)
            }
            TR4(wt == 0, wg == 2 ? 81 + 2 * c : 75)
#pragma unroll
            for (int h = 0; h < 2; h++) {
                const uint32_t qq[4] = {q[h].x, q[h].y, q[h].z, q[h].w}, r4[4] = {rs[h].x, rs[h].y, rs[h].z, rs[h].w}, n4[4] = {nm[h].x, nm[h].y, nm[h].z, nm[h].w};
                const uint4 y = add2(add2(p[h][0], p[h][1]), add2(p[h][2], p[h][3]));
                const uint32_t yy[4] = {y.x, y.y, y.z, y.w};
                uint32_t o[4];
#pragma unroll
                for (int i = 0; i < 4; i++) {
                    const uint32_t n = fma2(qq[i], r4[i], n4[i]);
                    o[i] = fma2(pack2(fmaf(blo(n), ab.y, ab.x), fmaf(bhi(n), ab.y, ab.x)), yy[i], mul2(qq[i], __float_as_uint(ab.z)));
                }
                stg128_tag(g_x1T + (size_t)(5 * id + c) * S_ + 1024 * h + 8 * wt, o[0], o[1], o[2], o[3], ep, ((5 * id + c) >> 3) & 3);
            }
        }
        warp_arrive(bars + B_XS * 8);
        TS(tid == 0, 17)
        TS(tid == 256, 52)
    }

    const uint32_t nil = pp.nil;
    const int wq = warp & 3;
    if (wg == 2) {
        TIDS
        asm volatile("setmaxnreg.dec.sync.aligned.u32 " STR(REG_AUX) ";");
        {
            const uint32_t ep = lds32(sb + M_EP);
            uint32_t ph = 0;
            const Tile tl = ring_tile(min(4 * lane + wq, 59), grp, j);
            const uint32_t plan = bars + (B_XFULL + 10 * tl.w + tl.kb) * 8;
#pragma unroll 1
            for (int m = wq - 4; m < 60; m += 4) {
                const int n = max(m, 0);
                const uint32_t pl = __shfl_sync(~0u, plan, n >> 2), at = __shfl_sync(~0u, tl.at, n >> 2);
                const int e = (n >= 20) + (n >= 40);
                const uint32_t a = sb + OFF_XR + (n & 7) * 8192;
                uint32_t ta = a + (e == 0 ? lane * 128 + ((lane & 7) << 4) + (lane >> 3) * 4
                                 : e == 1 ? (lane & 15) * 128 + (((lane >> 4 << 1) ^ (lane & 7)) << 4) + (lane & 8) + (lane >> 4) * 4
                                          : lane * 32 + (lane >> 2) * 4);
                uint32_t tb = e == 0 ? ta ^ 32 : ta + 2048, tc = e == 2 ? ta + 1024 : ta ^ 64, td = e == 2 ? tb + 1024 : tb ^ 64;
                uint32_t live = m >= 0 && m != 40 && m != 40 + XLEAD,
                    f0 = pl;
                uint32_t f1 = m == GATE_W2 || m == GATE_W3 || m == GATE_W3B ? bars + (B_GATE + (m >= GATE_W3) + (m >= GATE_W3B)) * 8 : 0;
                if (lane) f0 = f1;
                if (lane > 1 || m < 0) f0 = 0;
                asm volatile("" : "+r"(ta), "+r"(tb), "+r"(tc), "+r"(td), "+r"(live), "+r"(f0));
                mbar_spin(bars + (m < 0 ? B_BK : B_LAND + (n & 7)) * 8, (n >> 3) & 1);
                TR5(lane == 0, n)
                while (true) {
                    uint32_t v[8];
#pragma unroll
                    for (int i = 0; i < 8; i++) v[i] = lds32(((i & 2) ? ((i & 1) ? td : tc) : (i & 1) ? tb : ta) + (i >> 2) * 4096);
                    const uint32_t bad = lop3<0xFE>(lop3<0x7E>(v[0], ep, v[1]), lop3<0x7E>(v[2], ep, v[3]), lop3<0x7E>(v[4], ep, v[5]));
                    if (!RARE(__any_sync(~0u, lop3<0xA8>(bad, lop3<0x7E>(v[6], ep, v[7]), live)))) break;
                    if (elect()) load_tile(mp, a, e, at, bars + (B_AGAIN + wq) * 8);
                    mbar_spin(bars + (B_AGAIN + wq) * 8, ph);
                    ph ^= 1;
                    STALE1(e)
                }
                TR5(lane == 0, 60 + n)
                if (f0) mbar_arrive(f0);
            }
        }
        if (wq == 0) {
#pragma unroll 1
            for (int w = 0; w < 2; w++) {
                const uint4* src = g_part + (size_t)(grp + 16 * w) * 40960;
                TR4(lane == 0, 90 + 2 * w)
                mbar_wait(bars + (B_RING + w) * 8, 1);
                TR4(lane == 0, 91 + 2 * w)
                if (elect()) {
                    const uint32_t fb = bars + (B_IN + w) * 8, rem = sb + OFF_OUT + w * 10240;
                    mbar_expect(fb, 10240);
                    bulk_ld(rem + 8192, &g_x1f[((grp + 16 * w) * 8 + j) * 640 + 512], 2048, fb);
#pragma unroll 1
                    for (int i = 0; i < 4; i++) bulk_ld(rem + i * 2048, src + ((j >> 2) + 2 * i) * 5120 + 4096 + j * 128, 2048, fb);
                }
            }
        }
#pragma unroll 1
        for (int uw = 0; uw < 2; uw++) {
            const int tile = grp + 16 * uw;
            const uint32_t ep = lds32(sb + M_EP), in = sb + OFF_OUT + uw * 10240 + wt * 16, sr = in - lane * 16;
            mbar_wait(bars + (B_IN + uw) * 8, 1);
            TR4(wt == 0, 94 + 3 * uw)
            uint4 u[4];
#pragma unroll
            for (int i = 0; i < 4; i++) u[i] = lds128(in + i * 2048);
            const uint4 base = lds128(in + 8192);
            const uint32_t ra = sb + M_F1 + (64 * uw + 16 * wq + g) * 4;
            const uint4 gr = scale16(lds64f(sb + M_GB + (64 + 2 * t) * 4), lds64f(sb + M_GB + (72 + 2 * t) * 4), __uint_as_float(lds32(ra)), __uint_as_float(lds32(ra + 32)));
            uint32_t it = 0;
            while (RARE(__any_sync(~0u, stale4(u, ep) & 1))) {
                ld_part4(u, g_part + (size_t)tile * 40960 + (j >> 2) * 5120 + 4096 + j * 128 + wt, 10240);
                STALE(3)
                if (++it > SPIN_LIMIT) SPIN_FAIL(58)
            }
            TR4(wt == 0, 95 + 3 * uw)
            const uint4 r = fin16(add2(add2(u[0], u[1]), add2(u[2], u[3])), base, gr);
            __syncwarp();
            stsm4(sr + (lane & 15) * 32 + (((lane >> 4) ^ ((lane >> 2) & 1)) << 4), r.x, r.y, r.z, r.w);
            __syncwarp();
            stg128(out + (size_t)(64 * tile + 16 * wq + (lane >> 1)) * D_ + 512 + 16 * j + 8 * (lane & 1), lds128(sr + (lane >> 1) * 32 + (((lane & 1) ^ ((lane >> 3) & 1)) << 4)));
            TR4(wt == 0, 96 + 3 * uw)
            __syncwarp();
        }
        TS(wt == 0, 21)
        if (wq == 0) {
            uint32_t it = 0;
            while (!mbar_try(bars + B_OWN * 8, 0)) { if (++it > SPIN_LIMIT) SPIN_FAIL(56) }
        }
        return;
    }

    TIDS
    const int uw = wg, tile = grp + 16 * uw, row0 = 64 * tile + 16 * wq;
    const bool leader = wt == 0; (void)leader;
    const uint32_t xfull = bars + (B_XFULL + 10 * uw) * 8, xempty = bars + B_XEMPTY * 8, wfull = bars + B_WFULL * 8, wempty = bars + B_WEMPTY * 8;
    const uint64_t dz = mkdesc(0) + pp.nil;
    auto xwait = [&](uint32_t kb, uint32_t e) { mbar_spin(xfull + kb * 8, e & 1); };
    asm volatile("setmaxnreg.inc.sync.aligned.u32 " STR(REG_MMA) ";");
    const uint32_t ep = lds32(sb + M_EP);
    uint32_t x2[20];
    uint32_t res[20] = {};
    {
        float acc[40];
        const uint32_t la = ((lane & 7) + 8 * (lane >> 4)) * 128 + (((2 * wq + ((lane >> 3) & 1)) ^ (lane & 7)) << 4);
        auto pos = [&](int n) { return ring_pos(uw, n, LEAD1) & 7; };
        auto slot = [&](int n) { return sb + OFF_XR + pos(n) * 8192; };
        float al[2], r1[2], n1[2];
        {
            float sl[4], sq[4], v[4];
            uint32_t z0[16], z1[16], zz[16];
            uint64_t bd = dz + b80_desc(dsb, 0, 0, 0), tb = (((uint64_t)8 << 32) | ((dsb + OFF_TAB) >> 4) | (7u << 16)) + pp.nil;
            auto ldfrag = [&](uint32_t (&z)[16], int n) {
#pragma unroll
                for (int q = 0; q < 4; q++) ldsm4t(slot(n) + la + q * 2048, z[4 * q], z[4 * q + 1], z[4 * q + 2], z[4 * q + 3]);
            };
            auto tile1 = [&](const uint32_t (&zc)[16], uint32_t (&zn)[16], int n, int h) {
                const bool last = h && n == 5, ok = mbar_test(xfull + (n + 1) * 8, 0), okw = !h || mbar_test(wfull + ((n + 1) >> 1) * 8, 0);
                const int kb = g1_block(n, j);
                wg_fence();
#pragma unroll
                for (int q = 0; q < 2; q++) wgmma_rs80(acc, zc[4 * q], zc[4 * q + 1], zc[4 * q + 2], zc[4 * q + 3], bd + q * B80_STEP, 1);
                wg_commit();
                wg_wait<1>();
                if (!ok) xwait(n + 1, 0);
                if (!last) ldfrag(zn, n + 1);
#pragma unroll
                for (int e = 0; e < 16; e++) zz[e] = mul2(zc[e], zc[e]);
                const uint64_t t0 = last ? ((uint64_t)8 << 32) | ((dsb + M_NUL) >> 4) : tb;
                const uint32_t ts = last ? 0 : 14;
                wg_fence();
#pragma unroll
                for (int q = 0; q < 4; q++) wgmma_rs8(sl, zc[4 * q], zc[4 * q + 1], zc[4 * q + 2], zc[4 * q + 3], t0 + q * ts, 1);
#pragma unroll
                for (int q = 0; q < 4; q++) wgmma_rs8(sq, zz[4 * q], zz[4 * q + 1], zz[4 * q + 2], zz[4 * q + 3], t0 + q * ts, 1);
#pragma unroll
                for (int q = 2; q < 4; q++) wgmma_rs80(acc, zc[4 * q], zc[4 * q + 1], zc[4 * q + 2], zc[4 * q + 3], bd + q * B80_STEP, 1);
                wg_commit();
#pragma unroll
                for (int q = 0; q < 4; q++) ldsm4t_if(kb == j, slot(n) + la + q * 2048, &res[4 * q]);
                if (!h) ldsm4t_if(kb == 8 + (j >> 2), slot(n) + la + (j & 3) * 2048, &res[16]);
                if (lane < 2) mbar_arrive_after(xempty + pos(n) * 8, res[12], res[16], nil);
                if (!h && n && lane == 0) mbar_arrive(wempty + ((n >> 1) - 1) * 8);
                tb += 56;
                bd = bd + (uint64_t)B80_HALF;
                if (!okw) mbar_spin(wfull + ((n + 1) >> 1) * 8, 0);
                TR(leader, 100 + 10 * uw + n)
            };
            zero(acc); zero(sl); zero(sq);
            mbar_spin(bars + B_TAB * 8, 0);
            mbar_spin(wfull, 0);
            xwait(0, 0);
            TS(leader, 32 + uw)
            ldfrag(z0, 0);
#pragma unroll 1
            for (int n = 0; n < 6; n += 2) { tile1(z0, z1, n, 0); tile1(z1, z0, n + 1, 1); }
#pragma unroll
            for (int n = 6; n < 10; n++) {
                const uint64_t ad = dz + (((dsb + OFF_XR + pos(n) * 8192) >> 4) | 0x10000u);
                const bool ok = n == 9 || mbar_test(xfull + (n + 1) * 8, 0), okw = n != 7 || mbar_test(wfull + 4 * 8, 0);
                wg_fence();
#pragma unroll
                for (int q = 0; q < 4; q++) wgmma_ss80t(acc, ad + q * 128, bd + q * B80_STEP, 1);
                wg_commit();
                bd = bd + (uint64_t)B80_HALF;
                if (n == 9) ldsm4t_if(9 - (j & 1) == 8 + (j >> 2), slot(9) + la + (j & 3) * 2048, &res[16]);
                wg_wait<1>();
                if (n > 6 && lane < 2) mbar_arrive(xempty + pos(n - 1) * 8);
                if (!(n & 1) && lane == 0) mbar_arrive(wempty + ((n >> 1) - 1) * 8);
                if (n == 6) {
                    reg_fence(sl); reg_fence(sq);
#pragma unroll
                    for (int e = 0; e < 2; e++) {
                        v[2 * e] = t == 0 ? sl[2 * e] + sl[2 * e + 1] : t == 1 ? sq[2 * e] + sq[2 * e + 1] : sl[2 * e];
                        v[2 * e + 1] = t == 2 ? sl[2 * e + 1] : sq[2 * e];
                    }
                    st_peer(peer_addr(sb + OFF_ROW + uw * 2048 + wt * 16), __float_as_uint(v[0]), __float_as_uint(v[1]), __float_as_uint(v[2]), __float_as_uint(v[3]), peer_addr(bars + (B_SUMS + uw) * 8));
                    TS(leader && !uw, 59)
                }
                if (!ok) xwait(n + 1, 0);
                if (!okw) mbar_spin(wfull + 4 * 8, 0);
                TR(leader, 100 + 10 * uw + n)
            }
            float4 k = lds128f(sb + M_KS);
            float k4 = __uint_as_float(lds32(sb + M_KS + 16));
#pragma unroll
            for (int w = 1; w < 5; w++) {
                const float4 o = lds128f(sb + M_KS + w * 32);
                k.x += o.x; k.y += o.y; k.z += o.z; k.w += o.w; k4 += __uint_as_float(lds32(sb + M_KS + w * 32 + 16));
            }
            mbar_spin(bars + (B_SUMS + uw) * 8, 0);
            TS(leader && !uw, 10)
            const float4 o = lds128f(sb + OFF_ROW + uw * 2048 + wt * 16);
            v[0] += o.x; v[1] += o.y; v[2] += o.z; v[3] += o.w;
            uint32_t fa[4];
#pragma unroll
            for (int h = 0; h < 2; h++) {
                const int l0 = lane & ~3;
                const float s1 = __shfl_sync(~0u, v[2 * h], l0), s2 = __shfl_sync(~0u, v[2 * h], l0 + 1), scc = __shfl_sync(~0u, v[2 * h], l0 + 2);
                const float scs = __shfl_sync(~0u, v[2 * h + 1], l0 + 2), sc = __shfl_sync(~0u, v[2 * h], l0 + 3), sqq = __shfl_sync(~0u, v[2 * h + 1], l0 + 3);
                const float m1 = s1 * (1.f / D_), va = fmaxf(s2 * (1.f / D_) - m1 * m1, 0.f) + 1e-5f, r = rsqrtf(va);
                const float m2 = (r * (sc - m1 * k.x) + k.y) * (1.f / D_);
                const float e2 = (r * (r * (sqq + m1 * (m1 * k.z - 2.f * scc)) + 2.f * (scs - m1 * k.w)) + k4) * (1.f / D_);
                al[h] = r * 0.5f * rsqrtf(fmaxf(e2 - m2 * m2, 0.f) + 1e-5f); r1[h] = r; n1[h] = -m1 * r;
                const uint32_t fb = split2(va * r), fx = split2(t == 3 ? -m2 * va * r : -m1), fc = __shfl_sync(~0u, fx, lane | 3);
                fa[h] = __byte_perm(fx, fb, t == 1 ? 0x5432 : t == 2 ? 0x7654 : 0x1010);
                fa[2 + h] = t ? 0 : fc >> 16;
            }
            mbar_spin(bars + B_VEC * 8, 0);
            wg_fence();
            wgmma_rs80k(acc, fa[0], fa[1], fa[2], fa[3], ((uint64_t)8 << 32) | ((dsb + OFF_F1) >> 4) | (((M_F1 - OFF_F1) >> 4) << 16), 1);
            wg_commit();
        }
        wg_wait<0>();
        reg_fence(acc);
        if (lane < 2) mbar_arrive_after(xempty + pos(9) * 8, res[16], 0, nil);
        if (lane == 0) mbar_arrive(wempty + 4 * 8);
        TS(leader, 34 + uw)
        {
            bf16* const trow = g_t + (size_t)(row0 + g + 2) * D_;
#pragma unroll
            for (int b = 0; b < 3; b++) {
                uint32_t p[8];
#pragma unroll
                for (int ii = 0; ii < 4; ii++) {
                    const int i = 4 * b + ii;
                    if (i >= 10) continue;
#pragma unroll
                    for (int h = 0; h < 2; h++) p[(i & 3) + 4 * h] = pack2(gelu2(acc[4 * i + 2 * h] * al[h]), gelu2(acc[4 * i + 2 * h + 1] * al[h]));
                }
                if (b < 2) {
                    const int gr = (2 * j + b) / 5, sh = (gr & 1) ? -1 - (gr >> 1) : 1 + (gr >> 1);
                    bf16* dst = trow + 64 * j + 32 * b + 8 * t;
                    const int w = (((g + sh) >> 2) & 2) + (t >> 1);
                    stg128_tag(dst + sh * D_, p[0], p[1], p[2], p[3], ep, w);
                    stg128_tag(dst + (sh + 8) * D_, p[4], p[5], p[6], p[7], ep, w ^ 2);
                    if (row0 + g < sh || row0 + g + 8 >= S_ + sh) stg128_tag(dst + (sh > 0 ? 0 : 8) * D_, 0, 0, 0, 0, ep, (sh > 0 ? 0 : 2) + (t >> 1));
                } else {
                    bf16* dst = trow + 512 + 16 * j + 4 * t;
                    const uint32_t lo = t == (g < 2), hi = t == (g >= 2), o = j & 1;
                    stg64(dst - 2 * D_, lop3<0xB8>(p[0], lo & ~o, ep), lop3<0xB8>(p[1], lo & o, ep));
                    stg64(dst + 6 * D_, lop3<0xB8>(p[4], hi & ~o, ep), lop3<0xB8>(p[5], hi & o, ep));
                    if (row0 + g + 8 >= S_ - 2) stg64(dst + 8 * D_, ep & (t == 1) & ~o, ep & (t == 1) & o);
                }
            }
        }
        signal_cnt(&g_cnt.g1[tile * 32], lane, 1, true);
        TS(leader, 36 + uw)
#pragma unroll
        for (int i = 0; i < 10; i++) {
            const float2 c = lds64f(sb + M_C + (8 * i + 2 * t) * 4), s = lds64f(sb + M_SB + (8 * i + 2 * t) * 4);
#pragma unroll
            for (int h = 0; h < 2; h++) {
                acc[4 * i + 2 * h] = fmaf(blo(res[2 * i + h]), r1[h], fmaf(n1[h], c.x, s.x));
                acc[4 * i + 2 * h + 1] = fmaf(bhi(res[2 * i + h]), r1[h], fmaf(n1[h], c.y, s.y));
            }
        }
        mbar_spin(wfull + 5 * 8, 0);
        xwait(0, 1);
        TS(leader, 22 + uw)
        uint32_t ps = uw ? P1S : P0S, xo = (ps & 3) * 16, xp = 0;
        const uint64_t ax = dz + (((dsb + OFF_XR) >> 4) | 0x10000u);
        uint64_t ad = ax + xo * 64, bd = dz + b80_desc(dsb, 5, 0, 0);
#pragma unroll 1
        for (int i = 0; i < 5; i++) {
            const uint32_t x1 = xfull + (1 + 2 * i) * 8, p1 = 1, x2 = xfull + min(2 + 2 * i, 9) * 8, p2 = 1;
            const uint32_t w2 = wfull + (min(6 + i, 9) & 7) * 8, pw = i >= 2;
            const bool ok1 = mbar_test(x1, p1);
            wg_fence();
#pragma unroll
            for (int q = 0; q < 4; q++) wgmma_ss80(acc, ad + q * 2, bd + q * B80_STEP, 1);
            wg_commit();
            wg_wait<1>();
            if (lane < 2 && i) mbar_arrive(xempty + xp);
            if (lane == 0 && i) mbar_arrive(wempty + ((4 + i) & 7) * 8);
            if (!ok1) mbar_spin(x1, p1);
            const bool ok2 = mbar_test(x2, p2), okw = mbar_test(w2, pw);
            wg_fence();
#pragma unroll
            for (int q = 0; q < 4; q++) wgmma_ss80(acc, ad + 512 + q * 2, bd + B80_HALF + q * B80_STEP, 1);
            wg_commit();
            const uint32_t xc = xo;
            ps >>= 2;
            xp = xo + 8; xo = (ps & 3) * 16;
            ad = ax + xo * 64;
            bd += i == 2 ? 2 * B80_HALF - 8192 + (8192ll << 16) : 2 * B80_HALF;
            asm volatile("" : "+l"(ad), "+l"(bd));
            wg_wait<1>();
            if (lane < 2) mbar_arrive(xempty + xc);
            if (!ok2) mbar_spin(x2, p2);
            if (!okw) mbar_spin(w2, pw);
            TR(leader, (uw ? 86 : 20) + 2 * i)
        }
        wg_wait<0>();
        reg_fence(acc);
        if (lane < 2) mbar_arrive(xempty + xp);
        if (lane == 0) mbar_arrive(wempty + (9 & 7) * 8);
        TS(leader, 38 + uw)
        float a0 = 0.f, b0 = 0.f, a1 = 0.f, b1 = 0.f;
#pragma unroll
        for (int i = 0; i < 5; i++) {
            uint32_t* p = &x2[4 * i];
#pragma unroll
            for (int e = 0; e < 4; e++) p[e] = pack2(acc[8 * i + 2 * e], acc[8 * i + 2 * e + 1]);
#pragma unroll
            for (int e = 0; e < 4; e++) p[e] = lop3<0xB8>(p[e], (((wt >> 3) ^ (wt << 2)) & 7) == e, ep);
            stg128(&g_x2f[(tile * 40 + (i < 4 ? 4 * j + i : 32 + j)) * 128 + wt], p[0], p[1], p[2], p[3]);
#pragma unroll
            for (int e = 0; e < 8; e += 4) {
                const float* u = &acc[8 * i + e];
                a0 += u[0] + u[1]; b0 = fmaf(u[0], u[0], fmaf(u[1], u[1], b0));
                a1 += u[2] + u[3]; b1 = fmaf(u[2], u[2], fmaf(u[3], u[3], b1));
            }
        }
#pragma unroll
        for (int o = 1; o < 4; o *= 2) {
            a0 += __shfl_xor_sync(~0u, a0, o); b0 += __shfl_xor_sync(~0u, b0, o);
            a1 += __shfl_xor_sync(~0u, a1, o); b1 += __shfl_xor_sync(~0u, b1, o);
        }
        if (t < 2) stg64(&g_stats[(tile * 8 + j) * 64 + 16 * wq + g + 8 * t], tag(__float_as_uint(t ? a1 : a0), ep), __float_as_uint(t ? b1 : b0));
        signal_cnt(&g_cnt.g2[tile * 32], lane, 1, true);
        TS(leader, 40 + uw)
#pragma unroll
        for (int i = 0; i < 10; i++) {
            const float2 c = lds64f(sb + M_GB + (8 * i + 2 * t) * 4), e = lds64f(sb + M_CI + (8 * i + 2 * t) * 4);
#pragma unroll
            for (int h = 0; h < 2; h++)
                res[2 * i + h] = fma2(pack2(c.x, c.y), x2[2 * i + h], pack2(e.x * blo(res[2 * i + h]), e.y * bhi(res[2 * i + h])));
        }
#pragma unroll
        for (int i = 0; i < 20; i++) asm volatile("" : "+r"(res[i]));
    }
    float acc0[64], acc1[44];
    float2 q[4];
    {
        uint4 f0, f1, f2, f3;
        auto xseq = [&](int kb) { return ring_pos(uw, kb, XLEAD) & 7; };
        auto step = [&](const uint4& f, uint64_t bd) {
            wg_fence();
            wgmma_rs128(acc0, f.x, f.y, f.z, f.w, bd, 1);
            wgmma_rs88(acc1, f.x, f.y, f.z, f.w, bd + 512, 1);
            wg_commit();
        };
        const uint32_t xa = sb + OFF_XR + wt * 16;
        const float2* const gs = &g_stats[(tile * 8 + 2 * t) * 64 + 16 * wq + g];
        zero(acc0); zero(acc1);
        uint32_t xs = 0;
        f0 = make_uint4(x2[0], x2[1], x2[2], x2[3]); f1 = make_uint4(x2[4], x2[5], x2[6], x2[7]);
        f2 = make_uint4(x2[8], x2[9], x2[10], x2[11]); f3 = make_uint4(x2[12], x2[13], x2[14], x2[15]);
#pragma unroll
        for (int i = 0; i < 4; i++) q[i] = make_float2(0.f, 0.f);
        mbar_spin(wempty + (9 & 7) * 8, 1);
        mbar_spin(wfull + (10 & 7) * 8, (10 >> 3) & 1);
#pragma unroll 1
        for (int kb = 0; kb < 10; kb++) {
            const uint32_t wn = 10 + 2 * kb;
            const uint64_t bd = dz + (((dsb + OFF_W + (wn & 7) * 16384) >> 4) | (256u << 16));
            step(f0, bd);
            wg_wait<1>();
            if (kb && lane == 0) mbar_arrive(wempty + ((wn - 1) & 7) * 8);
            lds128_if(kb, f2, xa + xs * 8192 + 4096); lds128_if(kb, f3, xa + xs * 8192 + 6144);
            const bool w1 = mbar_test(wfull + ((wn + 1) & 7) * 8, (wn >> 3) & 1), x1 = kb < 9 && mbar_test(xfull + (kb + 1) * 8, 0);
            step(f1, bd + 128);
            if (!w1) mbar_spin(wfull + ((wn + 1) & 7) * 8, (wn >> 3) & 1);
            step(f2, bd + 1024);
            if (lane < 2 && kb) mbar_arrive_after(xempty + xs * 8, f2.x, f3.x, nil);
            wg_wait<1>();
            if (lane == 0) mbar_arrive(wempty + (wn & 7) * 8);
            xs = xseq(kb + 1);
            if (x1) { f0 = lds128(xa + xs * 8192); f1 = lds128(xa + xs * 8192 + 2048); }
            const bool w2 = mbar_test(wfull + ((wn + 2) & 7) * 8, ((wn + 2) >> 3) & 1);
            step(f3, bd + 1152);
            if (kb < 9 && !x1) { xwait(kb + 1, 2); f0 = lds128(xa + xs * 8192); f1 = lds128(xa + xs * 8192 + 2048); }
            if (!w2) mbar_spin(wfull + ((wn + 2) & 7) * 8, ((wn + 2) >> 3) & 1);
            if (kb == 0) {
                TS(leader, 42 + uw)
#pragma unroll
                for (int i = 0; i < 4; i++) q[i] = ld_stat(gs + (i & 1) * 64 + 8 * (i >> 1));
            }
            if (kb == 4) {
                uint32_t it = 0;
                while (RARE(__any_sync(~0u, ((__float_as_uint(q[0].x) ^ ep) | (__float_as_uint(q[1].x) ^ ep) | (__float_as_uint(q[2].x) ^ ep) | (__float_as_uint(q[3].x) ^ ep)) & 1))) {
#pragma unroll
                    for (int i = 0; i < 4; i++) q[i] = ld_stat(gs + (i & 1) * 64 + 8 * (i >> 1));
                    SPIN_CHECK(49)
                }
                float a0 = q[0].x + q[1].x, b0 = q[0].y + q[1].y, a1 = q[2].x + q[3].x, b1 = q[2].y + q[3].y;
#pragma unroll
                for (int o = 1; o < 4; o *= 2) {
                    a0 += __shfl_xor_sync(~0u, a0, o); b0 += __shfl_xor_sync(~0u, b0, o);
                    a1 += __shfl_xor_sync(~0u, a1, o); b1 += __shfl_xor_sync(~0u, b1, o);
                }
                a0 *= 1.f / D_; a1 *= 1.f / D_;
                const float r0 = 0.5f * rsqrtf(fmaxf(b0 * (1.f / D_) - a0 * a0, 0.f) + 1e-5f), r1 = 0.5f * rsqrtf(fmaxf(b1 * (1.f / D_) - a1 * a1, 0.f) + 1e-5f);
                const uint32_t sel = t == 0 ? 0x1010 : t == 1 ? 0x4432 : 0x4444;
                if (t == 0) { sts32(sb + M_F1 + (64 * uw + 16 * wq + g) * 4, __float_as_uint(r0)); sts32(sb + M_F1 + (64 * uw + 16 * wq + g + 8) * 4, __float_as_uint(r1)); }
                q[2] = make_float2(8.f * 0.0356774081f * r0 * r0 * r0, 2.f * 0.7978845608f * r0);
                q[3] = make_float2(8.f * 0.0356774081f * r1 * r1 * r1, 2.f * 0.7978845608f * r1);
                q[1] = make_float2(__uint_as_float(__byte_perm(split2(-a0), 0, sel)), __uint_as_float(__byte_perm(split2(-a1), 0, sel)));
            }
            if (kb == 6) {
#pragma unroll
                for (int i = 0; i < 5; i++) stg128(&g_x1f[(tile * 8 + j) * 640 + i * 128 + wt], res[4 * i], res[4 * i + 1], res[4 * i + 2], res[4 * i + 3]);
            }
            if (kb == 8) asm volatile("fence.proxy.async.global;" ::: "memory");
            TR(leader, 10 * uw + kb)
        }
        const uint64_t fd = ((uint64_t)8 << 32) | ((dsb + OFF_W + 6 * 16384) >> 4);
        wg_fence();
        wgmma_rs128k(acc0, __float_as_uint(q[1].x), __float_as_uint(q[1].y), 0, 0, fd, 1);
        wgmma_rs88k(acc1, __float_as_uint(q[1].x), __float_as_uint(q[1].y), 0, 0, fd + 128, 1);
        wg_commit();
        if (lane == 0) {
            mbar_arrive(bars + B_XFREE * 8);
            asm volatile("mbarrier.arrive.shared::cluster.b64 _, [%0];" ::"r"(peer_addr(bars + B_XFREE * 8)) : "memory");
        }
    }
    const uint32_t recv = sb + recv_off(uw) + wt * 16;
    uint32_t ha[48] = {}, hb[48], hx[12];
    uint64_t wb = dz + (((dsb + OFF_W) >> 4) | (512u << 16));
    auto wdesc = [&](int n) { return wb + (n & 7) * 1024; };
    auto wwait = [&](int n) { mbar_spin(wfull + (n & 7) * 8, (n >> 3) & 1); };
    auto wfree = [&](int n) { if (lane == 0) mbar_arrive(wempty + (n & 7) * 8); };
    auto fresh = [&]() { wb += pp.nil; asm volatile("" : "+l"(wb)); };
    uint32_t pk[32];
    {
        float P0[64];
        const float2 r0 = q[2], r1 = q[3];
        const uint32_t ra = peer_addr(recv), rb = peer_addr(bars + (B_RECV + 4 * uw) * 8);
        auto conv32 = [&](const float* v, int b) {
#pragma unroll
            for (int i = 0; i < 4; i++) {
                ha[8 * b + 2 * i] = pack2(gelu2r(v[4 * i], r0), gelu2r(v[4 * i + 1], r0));
                ha[8 * b + 2 * i + 1] = pack2(gelu2r(v[4 * i + 2], r1), gelu2r(v[4 * i + 3], r1));
            }
#pragma unroll
            for (int s = 2 * b; s < 2 * b + 2; s++) st_peer(ra + s * 2048, ha[4 * s], ha[4 * s + 1], ha[4 * s + 2], ha[4 * s + 3], rb + (b >> 1) * 8);
        };
        auto fetch = [&](int k) {
            mbar_spin(bars + (B_RECV + 4 * uw + k) * 8, 0);
#pragma unroll
            for (int s = 4 * k; s < 4 * k + 4; s++) { const uint4 x = lds128(recv + s * 2048); hb[4 * s] = x.x; hb[4 * s + 1] = x.y; hb[4 * s + 2] = x.z; hb[4 * s + 3] = x.w; }
        };
        auto stage = [&](int n, const uint32_t* a, int steps, int sc) {
            wwait(n);
            wg_fence();
#pragma unroll
            for (int s = 0; s < steps; s++) wgmma_rs128(P0, a[4 * s], a[4 * s + 1], a[4 * s + 2], a[4 * s + 3], wdesc(n) + s * 128, sc || s);
            wg_commit();
        };
        wg_wait<0>();
        reg_fence(acc0); reg_fence(acc1);
        wfree(29); wfree(30);
        TS(leader, 44 + uw)
        uint32_t hr[6];
#pragma unroll
        for (int i = 0; i < 6; i++) {
            const float2 r = (i & 1) ? r1 : r0;
            hr[i] = pack2(gelu2r(acc1[32 + 2 * i], r), gelu2r(acc1[33 + 2 * i], r));
        }
        if (uw) mbar_spin(bars + B_XFREE * 8, 0);
        st_peer(ra + 24576, hr[0], hr[1], hr[2], hr[3], rb + 24);
        asm volatile("st.async.shared::cluster.mbarrier::complete_tx::bytes.v2.b32 [%0], {%1, %2}, [%3];" ::"r"(ra + 26624 - wt * 8), "r"(hr[4]), "r"(hr[5]), "r"(rb + 24) : "memory");
        conv32(&acc1[0], 4);
        conv32(&acc1[16], 5);
        TS(leader, 46 + uw)
        stage(31, &ha[32], 4, 0);
#pragma unroll
        for (int b = 0; b < 4; b++) {
            conv32(&acc0[16 * b], b);
            if (b == 3) {
                fetch(2);
                mbar_spin(bars + (B_RECV + 4 * uw + 3) * 8, 0);
                const uint4 x = lds128(recv + 24576);
                const uint2 y = lds64(recv + 26624 - wt * 8);
                const uint32_t hp[6] = {x.x, x.y, x.z, x.w, y.x, y.y};
#pragma unroll
                for (int i = 0; i < 6; i++) { hx[i] = (j & 1) ? hp[i] : hr[i]; hx[6 + i] = (j & 1) ? hr[i] : hp[i]; }
            }
            if (!(b & 1)) wwait(32 + (b >> 1));
            wg_fence();
#pragma unroll
            for (int s = 0; s < 2; s++) wgmma_rs128(P0, ha[8 * b + 4 * s], ha[8 * b + 4 * s + 1], ha[8 * b + 4 * s + 2], ha[8 * b + 4 * s + 3], wdesc(32 + (b >> 1)) + (2 * (b & 1) + s) * 128, 1);
            wg_commit();
            if (!(b & 1)) { wg_wait<1>(); wfree(31 + (b >> 1)); }
        }
        TR(leader, 64 + 10 * uw)
        fresh();
        stage(34, &hb[32], 4, 1); wg_wait<1>(); wfree(33);
        fetch(0);
        stage(35, hx, 3, 1); wg_wait<1>(); wfree(34);
        fetch(1);
        stage(36, &hb[0], 4, 1); wg_wait<1>(); wfree(35);
        stage(37, &hb[16], 4, 1); wg_wait<1>(); wfree(36);
        wg_wait<0>();
        reg_fence(P0);
        pack_part<64>(pk, P0, ep);
        uint32_t all = 0;
#pragma unroll
        for (int i = 0; i < 32; i++) all |= pk[i];
        if (lane == 0) mbar_arrive_after(wempty + (37 & 7) * 8, all, 0, nil);
        TR(leader, 65 + 10 * uw)
    }
    {
        uint4* const dst = g_part + (size_t)(tile * 8 + j) * 5120 + wt;
        const uint4* const src = g_part + (size_t)tile * 40960 + j * 512 + wt;
        float F[2][32];
        uint4 gb[4];
        float rr[2];
        float2 gf[8];
        uint4 base[4], u1[4], u2[4], u3[4];
#pragma unroll
        for (int c = 2; c < 5; c++) {
            float (&P)[32] = F[c & 1];
            fresh();
#pragma unroll
            for (int s = 0; s < 27; s++) {
                const int e = s < 8 ? 0 : s < 15 ? 1 : s < 23 ? 2 : 3, o = s - (e == 0 ? 0 : e == 1 ? 8 : e == 2 ? 15 : 23), n = 30 + 4 * c + e;
                const uint32_t* a = s < 12 ? &ha[4 * s] : s < 15 ? &hx[4 * (s - 12)] : &hb[4 * (s - 15)];
                if (o == 0) wwait(n);
                if (o == 0 || s == 1) wg_fence();
                wgmma_rs64(P, a[0], a[1], a[2], a[3], wdesc(n) + o * 128, s);
                if (o == 0) { wg_commit(); wg_wait<1>(); if (c > 2 || s) wfree(n - 1); }
                if (s == 0 && c > 2) { reg_fence(F[~c & 1]); pack_part<32>(pk, F[~c & 1], ep); }
                if (c == 2 && s % 3 == 0 && s < 24) st_part(dst + g4_block(s / 12, j) * 512 + (s / 3 & 3) * 128, &pk[4 * (s / 3)]);
                if (c == 3 && s % 4 == 1 && s < 16) st_part(dst + g4_block(2, j) * 512 + s / 4 * 128, &pk[4 * (s / 4)]);
                if (c == 4 && s % ST3 == 0 && s < 4 * ST3) st_part(dst + g4_block(3, j) * 512 + s / ST3 * 128, &pk[4 * (s / ST3)]);
                if (c == 4 && s >= 4 && s < 8) base[s - 4] = ldcg128(&g_x1f[(tile * 8 + j) * 640 + (s - 4) * 128 + wt]);
                if (c == 4 && s >= 19 && s < 23) { gf[2 * s - 38] = lds64f(sb + M_GB + (16 * (s - 19) + 2 * t) * 4); gf[2 * s - 37] = lds64f(sb + M_GB + (16 * (s - 19) + 8 + 2 * t) * 4); }
                if (c == 4 && s >= 12 && s < 14) rr[s - 12] = __uint_as_float(lds32(sb + M_F1 + (64 * uw + 16 * wq + g + 8 * (s - 12)) * 4));
                if (c == 4 && s >= 8 && s < 12) u1[s - 8] = ld_part(src + (j ^ 6) * 5120 + (s - 8) * 128);
                if (c == 4 && s >= 15 && s < 19) u2[s - 15] = ld_part(src + (j ^ 4) * 5120 + (s - 15) * 128);
                if (c == 4 && s >= LD3 && s < LD3 + 4) u3[s - LD3] = ld_part(src + (j ^ 2) * 5120 + (s - LD3) * 128);
                if (27 * (c - 2) + s == R_GATE && lane == 0) mbar_arrive(bars + (B_RING + uw) * 8);
                if (s == 7 || s == 14 || s == 22 || s == 26) wg_commit();
                if (c == 4) { TR(leader && s == 7, 68 + 10 * uw) TR(leader && s == 14, 69 + 10 * uw) TR(leader && s == 22, 70 + 10 * uw) }
            }
            TR(leader, 64 + c + (c == 4 ? 3 : 0) + 10 * uw)
        }
        float (&O)[32] = F[0];
#pragma unroll
        for (int i = 0; i < 4; i++) if (LD3 + i > 26) u3[i] = ld_part(src + (j ^ 2) * 5120 + i * 128);
#pragma unroll
        for (int i = 0; i < 4; i++) gb[i] = scale16(gf[2 * i], gf[2 * i + 1], rr[0], rr[1]);
        uint32_t it = 0;
        while (__any_sync(~0u, (stale4(u1, ep) | stale4(u2, ep) | stale4(u3, ep)) & 1)) {
            ld_part4(u1, src + (j ^ 6) * 5120, 128); ld_part4(u2, src + (j ^ 4) * 5120, 128); ld_part4(u3, src + (j ^ 2) * 5120, 128);
            STALE(6)
            SPIN_CHECK(58)
        }
        TR(leader, 73 + 10 * uw)
#pragma unroll
        for (int i = 0; i < 4; i++) u1[i] = add2(add2(u1[i], u2[i]), u3[i]);
        TS(leader, 50 + uw)
        wg_wait<0>();
        reg_fence(O);
        TS(leader, 48 + uw)
        const uint32_t so = sb + recv_off(uw) + wq * 2048;
#pragma unroll
        for (int i = 0; i < 4; i++) {
            const float* o = &O[8 * i];
            const uint4 r = fin16(add2(u1[i], make_uint4(pack2(o[0], o[1]), pack2(o[2], o[3]), pack2(o[4], o[5]), pack2(o[6], o[7]))), base[i], gb[i]);
            stsm4(so + (lane & 15) * 128 + (((2 * i + (lane >> 4)) ^ (lane & 7)) << 4), r.x, r.y, r.z, r.w);
        }
        TR4(leader, 100 + uw)
        __syncwarp();
#pragma unroll
        for (int i = 0; i < 4; i++) {
            const int row = (lane >> 3) + 4 * i;
            stg128(out + (size_t)(row0 + row) * D_ + 64 * j + 8 * (lane & 7), lds128(so + row * 128 + (((lane & 7) ^ (row & 7)) << 4)));
        }
        TS(leader, 24 + uw)
        warp_arrive(bars + B_OWN * 8);
    }
}

typedef CUresult (*EncFn)(CUtensorMap*, CUtensorMapDataType, cuuint32_t, void*, const cuuint64_t*, const cuuint64_t*, const cuuint32_t*,
                          const cuuint32_t*, CUtensorMapInterleave, CUtensorMapSwizzle, CUtensorMapL2promotion, CUtensorMapFloatOOBfill);

static void enc(EncFn fn, CUtensorMap* m, void* p, int rank, const cuuint64_t* dims, const cuuint64_t* strides, const cuuint32_t* box, bool plain = false) {
    const CUtensorMapSwizzle sw = box[0] > 64 || plain ? CU_TENSOR_MAP_SWIZZLE_NONE : CU_TENSOR_MAP_SWIZZLE_128B;
    cuuint32_t es[5] = {1, 1, 1, 1, 1};
    CUresult r = fn(m, CU_TENSOR_MAP_DATA_TYPE_BFLOAT16, rank, p, dims, strides, box, es, CU_TENSOR_MAP_INTERLEAVE_NONE, sw,
                    CU_TENSOR_MAP_L2_PROMOTION_L2_128B, CU_TENSOR_MAP_FLOAT_OOB_FILL_NONE);
    (void)r;
}
static void enc2(EncFn fn, CUtensorMap* m, void* p, uint64_t cols, uint64_t rows, uint32_t bc, uint32_t br, bool plain = false) {
    cuuint64_t dims[2] = {cols, rows}, st[1] = {cols * 2};
    cuuint32_t box[2] = {bc, br};
    enc(fn, m, p, 2, dims, st, box, plain);
}

extern "C" void kernel_launch(void* const* d_in, const int* in_sizes, int n_in, void* d_out, int out_size) {
    static Maps mp;
    static Ptrs pp;
    static void* cached[13];
    bool same = true;
    for (int i = 0; i < 13; i++) same = same && (cached[i] == d_in[i]);
    if (!same) {
        void* fnp = nullptr;
        cudaDriverEntryPointQueryResult qr;
        cudaGetDriverEntryPoint("cuTensorMapEncodeTiled", &fnp, cudaEnableDefault, &qr);
        EncFn fn = (EncFn)fnp;
        cudaGetSymbolAddress((void**)&pp.s, g_scratch);
        void *x1T = g_x1T, *t = g_t;
        cuuint64_t dq[3] = {64, S_, 10}, sq[2] = {D_ * 2, 128};
        cuuint32_t bq[3] = {64, 16, 10};
        enc(fn, &mp.q, d_in[0], 3, dq, sq, bq);
        enc2(fn, &mp.k, d_in[1], D_, S_, 80, 67); enc2(fn, &mp.v, d_in[2], D_, S_, 80, 64);
        enc2(fn, &mp.qT, g_qT, 16 * D_, 128, 80, 128);
        enc2(fn, &mp.x[0], x1T, S_, D_, 64, 64); enc2(fn, &mp.x[1], (bf16*)t + 2 * D_, D_, S_, 64, 64);
        enc2(fn, &mp.x[2], g_x2f, 64, 320 * 64, 64, 64, true);
        enc2(fn, &mp.w1, d_in[7], D_, D_, 64, 64); enc2(fn, &mp.w1h, d_in[7], D_, D_, 64, 160); enc2(fn, &mp.w3h, d_in[9], F_, D_, 64, 160);
        enc2(fn, &mp.wmod, d_in[12], 6 * D_, D_, 64, 160);
        const cuuint64_t R = D_ * 2;
        cuuint64_t da[5] = {D_, 2, 4, 4, 16}, sa[4] = {R, 8 * R, 2 * R, 32 * R}, db[5] = {D_, 2, 2, 4, 8}, sb[4] = {R, 8 * R, 2 * R, 16 * R};
        cuuint32_t ba[5] = {64, 2, 4, 4, 2}, bb[5] = {64, 2, 2, 4, 4};
        enc(fn, &mp.w2a, d_in[8], 5, da, sa, ba); enc(fn, &mp.w2b, (bf16*)d_in[8] + 512 * D_, 5, db, sb, bb);
        cuuint64_t dw[3] = {64, D_, 27}, sw[2] = {F_ * 2, 128};
        cuuint32_t bw[3] = {64, 32, 3};
        enc(fn, &mp.w3a, d_in[9], 3, dw, sw, bw);
        enc2(fn, &mp.w3b, d_in[9], F_, D_, 24, 32);
        enc2(fn, &mp.w4[0], d_in[10], D_, F_, 64, 64); enc2(fn, &mp.w4[1], d_in[10], D_, F_, 64, 48);
        pp.q = (const bf16*)d_in[0]; pp.w_mod = (const bf16*)d_in[12]; pp.shift_k = (const bf16*)d_in[3];
        pp.ssm_k = (const bf16*)d_in[4]; pp.ssm_D = (const bf16*)d_in[5]; pp.w1 = (const bf16*)d_in[7]; pp.w2 = (const bf16*)d_in[8];
        pp.w4 = (const bf16*)d_in[10]; pp.c = (const bf16*)d_in[11];
        cudaFuncSetAttribute(fused_kernel, cudaFuncAttributeMaxDynamicSharedMemorySize, SMEM_BYTES);
        for (int i = 0; i < 13; i++) cached[i] = d_in[i];
    }
    fused_kernel<<<NCTA, NTHR, SMEM_BYTES, cudaStreamPerThread>>>(pp, (bf16*)d_out, mp);
}
```

```cpp
#include <cuda_runtime.h>
#include <cuda_bf16.h>
#include <cuda.h>
#include <stdint.h>
#include <stdio.h>

typedef __nv_bfloat16 bf16;

constexpr int S_ = 2048, D_ = 640, F_ = 1728;
constexpr int NCTA = 132, NTHR = 512;

constexpr int TAB_BYTES = 9216, VEC_BYTES = 1440;
struct Counters {
    unsigned kv[8 * 32];
    unsigned q[4 * 32], x[4 * 32];
    unsigned wr[32], tab[32], uv[32], cs[32], cs2[32], done[32];
    unsigned g1[32 * 32];
    unsigned g2[32 * 32];
};
struct Scratch {
    Counters cnt;
    unsigned epoch;
    alignas(1024) bf16 qst[2 * S_];
    alignas(1024) uint4 wr[2 * 8 * 10 * 128];
    alignas(1024) uint2 mod[2 * 6 * D_];
    alignas(1024) uint4 tab[(TAB_BYTES + 8 * VEC_BYTES) / 16];
    alignas(1024) float uv[2 * 3 * D_];
    alignas(1024) float cs3[2 * 1920];
    alignas(1024) uint4 cs3b[8 * 216];
    alignas(1024) float2 stats[32 * 8 * 64];
    alignas(1024) bf16 kvT[D_ * S_];
    alignas(1024) bf16 qT[D_ * S_];
    alignas(1024) bf16 x1T[D_ * S_];
    alignas(1024) bf16 t[(S_ + 4) * D_];
    alignas(1024) uint4 x2f[32 * 40 * 128];
    alignas(1024) uint4 x1f[32 * 8 * 5 * 128];
    alignas(1024) uint4 part[32 * 8 * 10 * 4 * 128];
};
__device__ Scratch g_scratch;
#define g_kvT (pp.s->kvT)
#define g_qT (pp.s->qT)
#define g_x1T (pp.s->x1T)
#define g_qst (pp.s->qst)
#define g_t (pp.s->t)
#define g_x2f (pp.s->x2f)
#define g_x1f (pp.s->x1f)
#define g_part (pp.s->part)
#define g_wr (pp.s->wr)
#define g_mod (pp.s->mod)
#define g_tab (pp.s->tab)
#define g_uv (pp.s->uv)
#define g_cs3 (pp.s->cs3)
#define g_cs3b (pp.s->cs3b)
#define g_stats (pp.s->stats)
#define g_cnt (pp.s->cnt)
#define g_epoch (pp.s->epoch)

struct Maps {
    CUtensorMap k, v, q;
    CUtensorMap qT;
    CUtensorMap x[3];
    CUtensorMap w1, w1h, w3h, wmod;
    CUtensorMap w2a, w2b;
    CUtensorMap w3a, w3b;
    CUtensorMap w4[2];
};

struct Ptrs {
    Scratch* s;
    uint64_t nil;
    const bf16 *q, *w_mod, *shift_k, *ssm_k, *ssm_D, *w1, *w2, *w4, *c;
};

constexpr int OFF_W = 0;
constexpr int OFF_XR = 131072;
constexpr int OFF_REM = 196608;
constexpr int OFF_TAB = OFF_REM + 5 * 4096;
constexpr int OFF_ROW = OFF_TAB + 4608;
constexpr int OFF_F1 = OFF_ROW + 4096;
constexpr int RECV_BYTES = 30720;
constexpr int OFF_M = OFF_REM + RECV_BYTES;
constexpr int OFF_OUT = OFF_XR + 32768;
static_assert(OFF_F1 + 1280 <= OFF_M, "G1 map");
constexpr int OFF_ST = 0;
constexpr int OFF_SSM = 20480;
constexpr int OFF_WM = 0;
constexpr int OFF_QIN = 49152;
constexpr int OFF_QT = 49152;
constexpr int OFF_Z = OFF_TAB;
constexpr int OFF_RING = 80896;
constexpr int OFF_KIN = OFF_RING, OFF_VIN = OFF_KIN + 2 * 10752;
constexpr int OFF_CH = OFF_RING + 3 * 16384, CH_BYTES = 13312, OFF_P = 5120;
static_assert(OFF_RING + 5 * 16384 <= OFF_CH + 3 * CH_BYTES && OFF_CH + 5 * CH_BYTES <= OFF_REM, "the last two rings replace channels 0..2");
constexpr int M_BAR = OFF_M;
constexpr int M_F1 = OFF_M + 832;
constexpr int M_GB = M_F1 + 1280, M_C = M_GB + 320, M_SB = M_C + 320, M_CI = M_SB + 320;
constexpr int M_KS = M_CI + 320;
constexpr int M_AB = M_KS + 160;
constexpr int M_EP = M_AB + 80;
constexpr int M_SINK = M_EP + 16;
constexpr int M_NUL = M_SINK + 16;
constexpr int M_TS = M_NUL + 128;
constexpr int SMEM_BYTES = M_TS;
static_assert(SMEM_BYTES <= 232448, "smem");

enum { B_WFULL = 0, B_WEMPTY = 8, B_XEMPTY = 16, B_XFULL = 24  ,
       B_RAW = 44, B_QIN = 45, B_SSM = 46, B_VEC = 47, B_VEC3 = 48, B_WM = 49, B_TAB = 50, B_QRDY = 51,
       B_MODR = 52, B_RAW2 = 53, B_RAW3 = 54, B_GATE = 56, B_SUMS = 62, B_RECV = 64  ,
       B_LAND = 72, B_AGAIN = 80, B_RETRY = 84,
       B_XS = 88, B_R1 = 89, B_BK = 90, B_KVS = 91,
       B_XFREE = 92, B_OWN = 93, B_IN = 94,
       B_RING = 96   };
#define T_KVB 1800
#define T_SSM 4200
#define PF_T0 5900
#define PF_DT 420
#define Q_UNROLL 1
#define HELP_T 1000
#define R_GATE 34
#define REG_AUX 40
#define REG_SVC 40
#define REG_MMA 216
#define STR2(x) #x
#define STR(x) STR2(x)
#define ST3 1
#define LD3 23
#define GATE_W2 7
#define GATE_W3 27
#define GATE_W3B 37
#define W3_N2 13
#define COEF_AT 8
#define LEAD2 5
#define LEAD1 4
#define XLEAD 3

#define SPIN_FAIL(code) __trap();
#define SPIN_LIMIT (1u << 22)
#define STALE(c)
#define STALE1(c)
#define TS(c, i)
#define TG(c, i)
#define TR(c, i)
#define TR2(c, i)
#define TR4(c, i)
#define TR5(c, i)
#define SPIN_CHECK(code) asm volatile("" ::"r"(it));
#define RARE(x) __builtin_expect((x) != 0, 0)
__device__ __forceinline__ uint32_t s2u(const void* p) { return (uint32_t)__cvta_generic_to_shared(p); }
__device__ __forceinline__ bool elect() {
    uint32_t p;
    asm volatile("{.reg .pred P; elect.sync _|P, 0xffffffff; selp.u32 %0,1,0,P;}" : "=r"(p));
    return p != 0;
}
__device__ __forceinline__ void mbar_init(uint32_t b, uint32_t n) { asm volatile("mbarrier.init.shared.b64 [%0], %1;" ::"r"(b), "r"(n)); }
__device__ __forceinline__ void mbar_expect(uint32_t b, uint32_t bytes) {
    asm volatile("mbarrier.arrive.expect_tx.shared.b64 _, [%0], %1;" ::"r"(b), "r"(bytes) : "memory");
}
__device__ __forceinline__ void mbar_arrive(uint32_t b) { asm volatile("mbarrier.arrive.shared.b64 _, [%0];" ::"r"(b) : "memory"); }
__device__ __forceinline__ void mbar_arrive_after(uint32_t b, uint32_t v0, uint32_t v1, uint32_t nil) { mbar_arrive(b + ((v0 | v1) & nil)); }
__device__ __forceinline__ void warp_arrive(uint32_t b) { __syncwarp(); if (elect()) mbar_arrive(b); }
__device__ __forceinline__ uint32_t peer_addr(uint32_t a) {
    uint32_t r;
    asm("{\n.reg .b32 q;\nmov.u32 q, %%cluster_ctarank;\nxor.b32 q, q, 1;\nmapa.shared::cluster.u32 %0, %1, q;\n}" : "=r"(r) : "r"(a));
    return r;
}
__device__ __forceinline__ bool mbar_test(uint32_t b, uint32_t parity) {
    uint32_t ok;
    asm volatile("{.reg .pred P; mbarrier.test_wait.parity.shared.b64 P, [%1], %2; selp.u32 %0,1,0,P;}" : "=r"(ok) : "r"(b), "r"(parity) : "memory");
    return ok != 0;
}
__device__ __forceinline__ bool mbar_try(uint32_t b, uint32_t parity) {
    uint32_t ok;
    asm volatile("{.reg .pred P; mbarrier.try_wait.parity.shared.b64 P, [%1], %2; selp.u32 %0,1,0,P;}" : "=r"(ok) : "r"(b), "r"(parity) : "memory");
    return ok != 0;
}
__device__ __forceinline__ void mbar_wait(uint32_t b, uint32_t parity) {
    if (__all_sync(0xffffffffu, mbar_try(b, parity))) return;
    uint32_t it = 0;
    while (!__all_sync(0xffffffffu, mbar_try(b, parity))) { if (++it > SPIN_LIMIT) SPIN_FAIL((b >> 3) & 63) }
}
__device__ __forceinline__ void mbar_spin(uint32_t b, uint32_t parity) {
    asm volatile("{\n.reg .pred P;\nSPIN:\nmbarrier.try_wait.parity.shared.b64 P, [%0], %1;\n@!P bra.uni SPIN;\n}" ::"r"(b), "r"(parity) : "memory");
}
__device__ __forceinline__ void bar_sync(int id, int n) { asm volatile("bar.sync %0, %1;" ::"r"(id), "r"(n) : "memory"); }
__device__ __forceinline__ void fence_async_smem() { asm volatile("fence.proxy.async.shared::cta;" ::: "memory"); }
__device__ __forceinline__ void wait_cnt(const unsigned* p, unsigned target, bool tagged = false) {
    unsigned v, it = 0;
    do {
        asm volatile("ld.relaxed.gpu.global.u32 %0, [%1];" : "=r"(v) : "l"(p) : "memory");
        SPIN_CHECK(60 + (target & 3))
    } while (!__all_sync(0xffffffffu, v >= target));
    if (!tagged) asm volatile("fence.acquire.gpu;" ::: "memory");
}
__device__ __forceinline__ void signal_cnt(unsigned* p, int lane, int n, bool tagged = false) {
    if (tagged) asm volatile("{\n.reg .pred P;\nsetp.lt.s32 P, %1, %2;\n@P red.relaxed.gpu.global.add.u32 [%0], %3;\n}" ::"l"(p), "r"(lane), "r"(n), "r"(1) : "memory");
    else if (lane < n) asm volatile("red.release.gpu.global.add.u32 [%0], 1;" ::"l"(p) : "memory");
    __syncwarp();
}
__device__ __forceinline__ uint32_t clock_lo() { uint32_t c; asm volatile("mov.u32 %0, %%clock;" : "=r"(c)); return c; }
__device__ __forceinline__ void wait_clock(uint32_t c0, uint32_t t) {
    asm volatile("{\n.reg .pred P;\n.reg .b32 c;\nWAIT:\nnanosleep.u32 20;\nmov.u32 c, %%clock;\nsub.u32 c, c, %0;\nsetp.lt.u32 P, c, %1;\n@P bra.uni WAIT;\n}" ::"r"(c0), "r"(t) : "memory");
}
__device__ __forceinline__ void tma_ld2(uint32_t dst, const CUtensorMap* m, int c0, int c1, uint32_t bar) {
    asm volatile("cp.async.bulk.tensor.2d.shared::cluster.global.mbarrier::complete_tx::bytes [%0], [%1, {%3, %4}], [%2];"
                 ::"r"(dst), "l"(m), "r"(bar), "r"(c0), "r"(c1) : "memory");
}
__device__ __forceinline__ void tma_ld3(uint32_t dst, const CUtensorMap* m, int c0, int c1, int c2, uint32_t bar) {
    asm volatile("cp.async.bulk.tensor.3d.shared::cluster.global.mbarrier::complete_tx::bytes [%0], [%1, {%3, %4, %5}], [%2];"
                 ::"r"(dst), "l"(m), "r"(bar), "r"(c0), "r"(c1), "r"(c2) : "memory");
}
__device__ __forceinline__ void tma_ld5(uint32_t dst, const CUtensorMap* m, int col, int blk, uint32_t bar) {
    asm volatile("cp.async.bulk.tensor.5d.shared::cluster.global.mbarrier::complete_tx::bytes [%0], [%1, {%3, %4, %4, %4, %5}], [%2];"
                 ::"r"(dst), "l"(m), "r"(bar), "r"(col), "r"(0), "r"(blk) : "memory");
}
__device__ __forceinline__ void bulk_ld(uint32_t dst, const void* src, uint32_t bytes, uint32_t bar) {
    asm volatile("cp.async.bulk.shared::cluster.global.mbarrier::complete_tx::bytes [%0], [%1], %2, [%3];" ::"r"(dst), "l"(src), "r"(bytes), "r"(bar) : "memory");
}
__device__ __forceinline__ void l2_prefetch(const void* p, uint32_t bytes) {
    asm volatile("cp.async.bulk.prefetch.L2.global [%0], %1;" ::"l"(p), "r"(bytes) : "memory");
}
__device__ __forceinline__ void wg_fence() { asm volatile("wgmma.fence.sync.aligned;" ::: "memory"); }
__device__ __forceinline__ void wg_commit() { asm volatile("wgmma.commit_group.sync.aligned;" ::: "memory"); }
template <int N> __device__ __forceinline__ void wg_wait() { asm volatile("wgmma.wait_group.sync.aligned %0;" ::"n"(N) : "memory"); }
template <int N> __device__ __forceinline__ void reg_fence(float (&d)[N]) {
#pragma unroll
    for (int i = 0; i < N; i++) asm volatile("" : "+f"(d[i])::"memory");
}
template <int N> __device__ __forceinline__ void zero(float (&d)[N]) {
#pragma unroll
    for (int i = 0; i < N; i++) asm volatile("mov.b32 %0, 0;" : "=f"(d[i]));
}
__device__ __forceinline__ uint32_t lds32(uint32_t a) { uint32_t v; asm volatile("ld.shared.b32 %0, [%1];" : "=r"(v) : "r"(a)); return v; }
__device__ __forceinline__ uint2 lds64(uint32_t a) { uint2 v; asm volatile("ld.shared.v2.b32 {%0,%1}, [%2];" : "=r"(v.x), "=r"(v.y) : "r"(a)); return v; }
__device__ __forceinline__ float2 lds64f(uint32_t a) { float2 v; asm volatile("ld.shared.v2.f32 {%0,%1}, [%2];" : "=f"(v.x), "=f"(v.y) : "r"(a)); return v; }
__device__ __forceinline__ void sts32(uint32_t a, uint32_t v) { asm volatile("st.shared.b32 [%0], %1;" ::"r"(a), "r"(v) : "memory"); }
__device__ __forceinline__ void sts64f(uint32_t a, float x, float y) { asm volatile("st.shared.v2.f32 [%0], {%1,%2};" ::"r"(a), "f"(x), "f"(y) : "memory"); }
__device__ __forceinline__ void sts128(uint32_t a, uint32_t x, uint32_t y, uint32_t z, uint32_t w) {
    asm volatile("st.shared.v4.b32 [%0], {%1,%2,%3,%4};" ::"r"(a), "r"(x), "r"(y), "r"(z), "r"(w) : "memory");
}
__device__ __forceinline__ void sts128f(uint32_t a, float x, float y, float z, float w) {
    asm volatile("st.shared.v4.f32 [%0], {%1,%2,%3,%4};" ::"r"(a), "f"(x), "f"(y), "f"(z), "f"(w) : "memory");
}
__device__ __forceinline__ uint4 lds128(uint32_t a) {
    uint4 v;
    asm volatile("ld.shared.v4.b32 {%0,%1,%2,%3}, [%4];" : "=r"(v.x), "=r"(v.y), "=r"(v.z), "=r"(v.w) : "r"(a) : "memory");
    return v;
}
__device__ __forceinline__ void lds128_if(int p, uint4& v, uint32_t a) {
    asm volatile("{\n.reg .pred p;\nsetp.ne.s32 p, %5, 0;\n@p ld.shared.v4.b32 {%0,%1,%2,%3}, [%4];\n}" : "+r"(v.x), "+r"(v.y), "+r"(v.z), "+r"(v.w) : "r"(a), "r"(p) : "memory");
}
__device__ __forceinline__ float4 lds128f(uint32_t a) {
    float4 v;
    asm volatile("ld.shared.v4.f32 {%0,%1,%2,%3}, [%4];" : "=f"(v.x), "=f"(v.y), "=f"(v.z), "=f"(v.w) : "r"(a) : "memory");
    return v;
}
__device__ __forceinline__ void stg128(void* p, uint32_t x, uint32_t y, uint32_t z, uint32_t w) {
    asm volatile("st.global.v4.b32 [%0], {%1,%2,%3,%4};" ::"l"(p), "r"(x), "r"(y), "r"(z), "r"(w) : "memory");
}
__device__ __forceinline__ void stg128(void* p, uint4 v) { stg128(p, v.x, v.y, v.z, v.w); }
__device__ __forceinline__ void stg128_if(void* p, uint4 v, int on) {
    asm volatile("{\n.reg .pred p;\nsetp.ne.s32 p, %5, 0;\n@p st.global.v4.b32 [%0], {%1,%2,%3,%4};\n}" ::"l"(p), "r"(v.x), "r"(v.y), "r"(v.z), "r"(v.w), "r"(on) : "memory");
}
__device__ __forceinline__ void stg64(void* p, uint32_t x, uint32_t y) { asm volatile("st.global.v2.b32 [%0], {%1,%2};" ::"l"(p), "r"(x), "r"(y) : "memory"); }
__device__ __forceinline__ void stsm4(uint32_t a, uint32_t r0, uint32_t r1, uint32_t r2, uint32_t r3) {
    asm volatile("stmatrix.sync.aligned.m8n8.x4.shared.b16 [%0], {%1,%2,%3,%4};" ::"r"(a), "r"(r0), "r"(r1), "r"(r2), "r"(r3) : "memory");
}
__device__ __forceinline__ void stsm4t(uint32_t a, uint32_t r0, uint32_t r1, uint32_t r2, uint32_t r3) {
    asm volatile("stmatrix.sync.aligned.m8n8.x4.trans.shared.b16 [%0], {%1,%2,%3,%4};" ::"r"(a), "r"(r0), "r"(r1), "r"(r2), "r"(r3) : "memory");
}
__device__ __forceinline__ void ldsm4t_if(bool p, uint32_t a, uint32_t* r) {
    asm volatile("{\n.reg .pred p;\nsetp.ne.u32 p, %5, 0;\n@p ldmatrix.sync.aligned.m8n8.x4.trans.shared.b16 {%0,%1,%2,%3}, [%4];\n}"
                 : "+r"(r[0]), "+r"(r[1]), "+r"(r[2]), "+r"(r[3]) : "r"(a), "r"((uint32_t)p) : "memory");
}
__device__ __forceinline__ void ldsm4t(uint32_t a, uint32_t& r0, uint32_t& r1, uint32_t& r2, uint32_t& r3) {
    asm volatile("ldmatrix.sync.aligned.m8n8.x4.trans.shared.b16 {%0,%1,%2,%3}, [%4];" : "=r"(r0), "=r"(r1), "=r"(r2), "=r"(r3) : "r"(a) : "memory");
}
__device__ __forceinline__ uint32_t pack2(float lo, float hi) {
    uint32_t r;
    asm("cvt.rn.bf16x2.f32 %0, %1, %2;" : "=r"(r) : "f"(hi), "f"(lo));
    return r;
}
__device__ __forceinline__ uint32_t mul2(uint32_t a, uint32_t b) { uint32_t r; asm("mul.rn.bf16x2 %0, %1, %2;" : "=r"(r) : "r"(a), "r"(b)); return r; }
__device__ __forceinline__ uint32_t fma2(uint32_t a, uint32_t b, uint32_t c) { uint32_t r; asm("fma.rn.bf16x2 %0, %1, %2, %3;" : "=r"(r) : "r"(a), "r"(b), "r"(c)); return r; }
__device__ __forceinline__ uint32_t add2(uint32_t a, uint32_t b) { uint32_t r; asm("add.rn.bf16x2 %0, %1, %2;" : "=r"(r) : "r"(a), "r"(b)); return r; }
__device__ __forceinline__ void hmma(float (&d)[4], uint32_t a0, uint32_t a1, uint32_t a2, uint32_t a3, uint32_t b0, uint32_t b1) {
    asm volatile("mma.sync.aligned.m16n8k16.row.col.f32.bf16.bf16.f32 {%0,%1,%2,%3}, {%4,%5,%6,%7}, {%8,%9}, {%0,%1,%2,%3};"
        : "+f"(d[0]), "+f"(d[1]), "+f"(d[2]), "+f"(d[3]) : "r"(a0), "r"(a1), "r"(a2), "r"(a3), "r"(b0), "r"(b1));
}
__device__ __forceinline__ float blo(uint32_t w) { return __uint_as_float(w << 16); }
__device__ __forceinline__ float bhi(uint32_t w) { return __uint_as_float(w & 0xffff0000u); }
__device__ __forceinline__ float rbf(float x) { return __bfloat162float(__float2bfloat16_rn(x)); }
__device__ __forceinline__ uint32_t ldg32(const void* p) { uint32_t v; asm volatile("ld.global.nc.b32 %0, [%1];" : "=r"(v) : "l"(p)); return v; }
__device__ __forceinline__ uint2 ldg64(const void* p) { uint2 v; asm volatile("ld.global.nc.v2.b32 {%0,%1}, [%2];" : "=r"(v.x), "=r"(v.y) : "l"(p)); return v; }
__device__ __forceinline__ uint4 ldg128(const void* p) {
    uint4 v;
    asm volatile("ld.global.nc.v4.b32 {%0,%1,%2,%3}, [%4];" : "=r"(v.x), "=r"(v.y), "=r"(v.z), "=r"(v.w) : "l"(p));
    return v;
}
__device__ __forceinline__ uint4 ldcg128(const void* p) {
    uint4 v;
    asm volatile("ld.global.cg.v4.u32 {%0,%1,%2,%3}, [%4];" : "=r"(v.x), "=r"(v.y), "=r"(v.z), "=r"(v.w) : "l"(p) : "memory");
    return v;
}
__device__ __forceinline__ float4 ldcg128f(const void* p) {
    float4 v;
    asm volatile("ld.global.cg.v4.f32 {%0,%1,%2,%3}, [%4];" : "=f"(v.x), "=f"(v.y), "=f"(v.z), "=f"(v.w) : "l"(p) : "memory");
    return v;
}
__device__ __forceinline__ float2 ldcg64f(const void* p) { float2 v; asm volatile("ld.global.cg.v2.f32 {%0,%1}, [%2];" : "=f"(v.x), "=f"(v.y) : "l"(p) : "memory"); return v; }
__device__ __forceinline__ float ldcg32f(const void* p) { float v; asm volatile("ld.global.cg.f32 %0, [%1];" : "=f"(v) : "l"(p) : "memory"); return v; }
__device__ __forceinline__ float2 ld_stat(const float2* p) {
    float2 v;
    asm volatile("{\n.reg .b64 q;\nld.relaxed.gpu.global.b64 q, [%2];\nmov.b64 {%0, %1}, q;\n}" : "=f"(v.x), "=f"(v.y) : "l"(p) : "memory");
    return v;
}
__device__ __forceinline__ uint32_t ld_cold(const unsigned* p) { uint32_t v; asm volatile("ld.relaxed.gpu.global.u32 %0, [%1];" : "=r"(v) : "l"(p) : "memory"); return v; }
__device__ __forceinline__ uint2 ld_mod(const uint2* p) {
    uint64_t v;
    asm volatile("ld.relaxed.gpu.global.b64 %0, [%1];" : "=l"(v) : "l"(p) : "memory");
    return make_uint2((uint32_t)v, (uint32_t)(v >> 32));
}
__device__ __forceinline__ float silu(float x) {
    float e, r;
    asm("ex2.approx.ftz.f32 %0, %1;" : "=f"(e) : "f"(x * -1.4426950408889634f));
    asm("rcp.approx.ftz.f32 %0, %1;" : "=f"(r) : "f"(1.f + e));
    return x * r;
}
__device__ __forceinline__ float gelu2(float h) {
    float u = h * fmaf(h * h, 8.f * 0.0356774081f, 2.f * 0.7978845608f);
    float th;
    asm("tanh.approx.f32 %0, %1;" : "=f"(th) : "f"(u));
    return fmaf(h, th, h);
}
__device__ __forceinline__ float gelu2r(float a, float2 k) {
    float th;
    asm("tanh.approx.f32 %0, %1;" : "=f"(th) : "f"(a * fmaf(a * a, k.x, k.y)));
    return fmaf(a, th, a);
}

__device__ __forceinline__ void conv_channel(float (&d)[64], uint32_t pa, uint64_t db) {
    asm volatile("{\n.reg .b32 a0, a1, a2, a3, b0, b1, b2, b3, t0, t1;\n.reg .b64 d;\nld.shared.b32 a0, [%64];\nld.shared.b32 a1, [%64+128];\nld.shared.b32 a2, [%64+-128];\nmov.b32 a3, a0;\n"
        "ld.shared.b32 t0, [%64+256];\nld.shared.b32 t1, [%64+384];\nadd.s64 d, %65, 0;\nwgmma.fence.sync.aligned;\nwgmma.mma_async.sync.aligned.m64n128k16.f32.bf16.bf16 {%0, %1, %2, %3, %4, %5, %6, %7, %8, %9, %10, %11, %12, %13, %14, %15, %16, %17, %18, %19, %20, %21, %22, %23, %24, %25, %26, %27, %28, %29, %30, %31, %32, %33, %34, %35, %36, %37, %38, %39, %40, %41, %42, %43, %44, %45, %46, %47, %48, %49, %50, %51, %52, %53, %54, %55, %56, %57, %58, %59, %60, %61, %62, %63}, {a0, a1, a2, a3}, d, 0, 1, 1, 0;\nwgmma.commit_group.sync.aligned;\nwgmma.wait_group.sync.aligned 1;\nmov.b32 b2, a1;\nmov.b32 b0, t0;\nmov.b32 b3, t0;\nmov.b32 b1, t1;\n"
        "ld.shared.b32 t0, [%64+512];\nld.shared.b32 t1, [%64+640];\nadd.s64 d, %65, 8;\nwgmma.fence.sync.aligned;\nwgmma.mma_async.sync.aligned.m64n128k16.f32.bf16.bf16 {%0, %1, %2, %3, %4, %5, %6, %7, %8, %9, %10, %11, %12, %13, %14, %15, %16, %17, %18, %19, %20, %21, %22, %23, %24, %25, %26, %27, %28, %29, %30, %31, %32, %33, %34, %35, %36, %37, %38, %39, %40, %41, %42, %43, %44, %45, %46, %47, %48, %49, %50, %51, %52, %53, %54, %55, %56, %57, %58, %59, %60, %61, %62, %63}, {b0, b1, b2, b3}, d, 1, 1, 1, 0;\nwgmma.commit_group.sync.aligned;\nwgmma.wait_group.sync.aligned 1;\nmov.b32 a2, b1;\nmov.b32 a0, t0;\nmov.b32 a3, t0;\nmov.b32 a1, t1;\n"
        "ld.shared.b32 t0, [%64+768];\nld.shared.b32 t1, [%64+896];\nadd.s64 d, %65, 16;\nwgmma.fence.sync.aligned;\nwgmma.mma_async.sync.aligned.m64n128k16.f32.bf16.bf16 {%0, %1, %2, %3, %4, %5, %6, %7, %8, %9, %10, %11, %12, %13, %14, %15, %16, %17, %18, %19, %20, %21, %22, %23, %24, %25, %26, %27, %28, %29, %30, %31, %32, %33, %34, %35, %36, %37, %38, %39, %40, %41, %42, %43, %44, %45, %46, %47, %48, %49, %50, %51, %52, %53, %54, %55, %56, %57, %58, %59, %60, %61, %62, %63}, {a0, a1, a2, a3}, d, 1, 1, 1, 0;\nwgmma.commit_group.sync.aligned;\nwgmma.wait_group.sync.aligned 1;\nmov.b32 b2, a1;\nmov.b32 b0, t0;\nmov.b32 b3, t0;\nmov.b32 b1, t1;\n"
        "ld.shared.b32 t0, [%64+1024];\nld.shared.b32 t1, [%64+1152];\nadd.s64 d, %65, 24;\nwgmma.fence.sync.aligned;\nwgmma.mma_async.sync.aligned.m64n128k16.f32.bf16.bf16 {%0, %1, %2, %3, %4, %5, %6, %7, %8, %9, %10, %11, %12, %13, %14, %15, %16, %17, %18, %19, %20, %21, %22, %23, %24, %25, %26, %27, %28, %29, %30, %31, %32, %33, %34, %35, %36, %37, %38, %39, %40, %41, %42, %43, %44, %45, %46, %47, %48, %49, %50, %51, %52, %53, %54, %55, %56, %57, %58, %59, %60, %61, %62, %63}, {b0, b1, b2, b3}, d, 1, 1, 1, 0;\nwgmma.commit_group.sync.aligned;\nwgmma.wait_group.sync.aligned 1;\nmov.b32 a2, b1;\nmov.b32 a0, t0;\nmov.b32 a3, t0;\nmov.b32 a1, t1;\n"
        "ld.shared.b32 t0, [%64+1280];\nld.shared.b32 t1, [%64+1408];\nadd.s64 d, %65, 32;\nwgmma.fence.sync.aligned;\nwgmma.mma_async.sync.aligned.m64n128k16.f32.bf16.bf16 {%0, %1, %2, %3, %4, %5, %6, %7, %8, %9, %10, %11, %12, %13, %14, %15, %16, %17, %18, %19, %20, %21, %22, %23, %24, %25, %26, %27, %28, %29, %30, %31, %32, %33, %34, %35, %36, %37, %38, %39, %40, %41, %42, %43, %44, %45, %46, %47, %48, %49, %50, %51, %52, %53, %54, %55, %56, %57, %58, %59, %60, %61, %62, %63}, {a0, a1, a2, a3}, d, 1, 1, 1, 0;\nwgmma.commit_group.sync.aligned;\nwgmma.wait_group.sync.aligned 1;\nmov.b32 b2, a1;\nmov.b32 b0, t0;\nmov.b32 b3, t0;\nmov.b32 b1, t1;\n"
        "ld.shared.b32 t0, [%64+1536];\nld.shared.b32 t1, [%64+1664];\nadd.s64 d, %65, 40;\nwgmma.fence.sync.aligned;\nwgmma.mma_async.sync.aligned.m64n128k16.f32.bf16.bf16 {%0, %1, %2, %3, %4, %5, %6, %7, %8, %9, %10, %11, %12, %13, %14, %15, %16, %17, %18, %19, %20, %21, %22, %23, %24, %25, %26, %27, %28, %29, %30, %31, %32, %33, %34, %35, %36, %37, %38, %39, %40, %41, %42, %43, %44, %45, %46, %47, %48, %49, %50, %51, %52, %53, %54, %55, %56, %57, %58, %59, %60, %61, %62, %63}, {b0, b1, b2, b3}, d, 1, 1, 1, 0;\nwgmma.commit_group.sync.aligned;\nwgmma.wait_group.sync.aligned 1;\nmov.b32 a2, b1;\nmov.b32 a0, t0;\nmov.b32 a3, t0;\nmov.b32 a1, t1;\n"
        "ld.shared.b32 t0, [%64+1792];\nld.shared.b32 t1, [%64+1920];\nadd.s64 d, %65, 48;\nwgmma.fence.sync.aligned;\nwgmma.mma_async.sync.aligned.m64n128k16.f32.bf16.bf16 {%0, %1, %2, %3, %4, %5, %6, %7, %8, %9, %10, %11, %12, %13, %14, %15, %16, %17, %18, %19, %20, %21, %22, %23, %24, %25, %26, %27, %28, %29, %30, %31, %32, %33, %34, %35, %36, %37, %38, %39, %40, %41, %42, %43, %44, %45, %46, %47, %48, %49, %50, %51, %52, %53, %54, %55, %56, %57, %58, %59, %60, %61, %62, %63}, {a0, a1, a2, a3}, d, 1, 1, 1, 0;\nwgmma.commit_group.sync.aligned;\nwgmma.wait_group.sync.aligned 1;\nmov.b32 b2, a1;\nmov.b32 b0, t0;\nmov.b32 b3, t0;\nmov.b32 b1, t1;\n"
        "ld.shared.b32 t0, [%64+2048];\nld.shared.b32 t1, [%64+2176];\nadd.s64 d, %65, 56;\nwgmma.fence.sync.aligned;\nwgmma.mma_async.sync.aligned.m64n128k16.f32.bf16.bf16 {%0, %1, %2, %3, %4, %5, %6, %7, %8, %9, %10, %11, %12, %13, %14, %15, %16, %17, %18, %19, %20, %21, %22, %23, %24, %25, %26, %27, %28, %29, %30, %31, %32, %33, %34, %35, %36, %37, %38, %39, %40, %41, %42, %43, %44, %45, %46, %47, %48, %49, %50, %51, %52, %53, %54, %55, %56, %57, %58, %59, %60, %61, %62, %63}, {b0, b1, b2, b3}, d, 1, 1, 1, 0;\nwgmma.commit_group.sync.aligned;\nwgmma.wait_group.sync.aligned 1;\nmov.b32 a2, b1;\nmov.b32 a0, t0;\nmov.b32 a3, t0;\nmov.b32 a1, t1;\n"
        "ld.shared.b32 t0, [%64+2304];\nld.shared.b32 t1, [%64+2432];\nadd.s64 d, %65, 64;\nwgmma.fence.sync.aligned;\nwgmma.mma_async.sync.aligned.m64n96k16.f32.bf16.bf16 {%0, %1, %2, %3, %4, %5, %6, %7, %8, %9, %10, %11, %12, %13, %14, %15, %16, %17, %18, %19, %20, %21, %22, %23, %24, %25, %26, %27, %28, %29, %30, %31, %32, %33, %34, %35, %36, %37, %38, %39, %40, %41, %42, %43, %44, %45, %46, %47}, {a0, a1, a2, a3}, d, 1, 1, 1, 0;\nwgmma.commit_group.sync.aligned;\nwgmma.wait_group.sync.aligned 1;\nmov.b32 b2, a1;\nmov.b32 b0, t0;\nmov.b32 b3, t0;\nmov.b32 b1, t1;\n"
        "ld.shared.b32 t0, [%64+2560];\nld.shared.b32 t1, [%64+2688];\nadd.s64 d, %65, 72;\nwgmma.fence.sync.aligned;\nwgmma.mma_async.sync.aligned.m64n96k16.f32.bf16.bf16 {%0, %1, %2, %3, %4, %5, %6, %7, %8, %9, %10, %11, %12, %13, %14, %15, %16, %17, %18, %19, %20, %21, %22, %23, %24, %25, %26, %27, %28, %29, %30, %31, %32, %33, %34, %35, %36, %37, %38, %39, %40, %41, %42, %43, %44, %45, %46, %47}, {b0, b1, b2, b3}, d, 1, 1, 1, 0;\nwgmma.commit_group.sync.aligned;\nwgmma.wait_group.sync.aligned 1;\nmov.b32 a2, b1;\nmov.b32 a0, t0;\nmov.b32 a3, t0;\nmov.b32 a1, t1;\n"
        "ld.shared.b32 t0, [%64+2816];\nld.shared.b32 t1, [%64+2944];\nadd.s64 d, %65, 80;\nwgmma.fence.sync.aligned;\nwgmma.mma_async.sync.aligned.m64n88k16.f32.bf16.bf16 {%0, %1, %2, %3, %4, %5, %6, %7, %8, %9, %10, %11, %12, %13, %14, %15, %16, %17, %18, %19, %20, %21, %22, %23, %24, %25, %26, %27, %28, %29, %30, %31, %32, %33, %34, %35, %36, %37, %38, %39, %40, %41, %42, %43}, {a0, a1, a2, a3}, d, 1, 1, 1, 0;\nwgmma.commit_group.sync.aligned;\nwgmma.wait_group.sync.aligned 1;\nmov.b32 b2, a1;\nmov.b32 b0, t0;\nmov.b32 b3, t0;\nmov.b32 b1, t1;\n"
        "ld.shared.b32 t0, [%64+3072];\nld.shared.b32 t1, [%64+3200];\nadd.s64 d, %65, 88;\nwgmma.fence.sync.aligned;\nwgmma.mma_async.sync.aligned.m64n88k16.f32.bf16.bf16 {%0, %1, %2, %3, %4, %5, %6, %7, %8, %9, %10, %11, %12, %13, %14, %15, %16, %17, %18, %19, %20, %21, %22, %23, %24, %25, %26, %27, %28, %29, %30, %31, %32, %33, %34, %35, %36, %37, %38, %39, %40, %41, %42, %43}, {b0, b1, b2, b3}, d, 1, 1, 1, 0;\nwgmma.commit_group.sync.aligned;\nwgmma.wait_group.sync.aligned 1;\nmov.b32 a2, b1;\nmov.b32 a0, t0;\nmov.b32 a3, t0;\nmov.b32 a1, t1;\n"
        "ld.shared.b32 t0, [%64+3328];\nld.shared.b32 t1, [%64+3456];\nadd.s64 d, %65, 96;\nwgmma.fence.sync.aligned;\nwgmma.mma_async.sync.aligned.m64n80k16.f32.bf16.bf16 {%0, %1, %2, %3, %4, %5, %6, %7, %8, %9, %10, %11, %12, %13, %14, %15, %16, %17, %18, %19, %20, %21, %22, %23, %24, %25, %26, %27, %28, %29, %30, %31, %32, %33, %34, %35, %36, %37, %38, %39}, {a0, a1, a2, a3}, d, 1, 1, 1, 0;\nwgmma.commit_group.sync.aligned;\nwgmma.wait_group.sync.aligned 1;\nmov.b32 b2, a1;\nmov.b32 b0, t0;\nmov.b32 b3, t0;\nmov.b32 b1, t1;\n"
        "ld.shared.b32 t0, [%64+3584];\nld.shared.b32 t1, [%64+3712];\nadd.s64 d, %65, 104;\nwgmma.fence.sync.aligned;\nwgmma.mma_async.sync.aligned.m64n80k16.f32.bf16.bf16 {%0, %1, %2, %3, %4, %5, %6, %7, %8, %9, %10, %11, %12, %13, %14, %15, %16, %17, %18, %19, %20, %21, %22, %23, %24, %25, %26, %27, %28, %29, %30, %31, %32, %33, %34, %35, %36, %37, %38, %39}, {b0, b1, b2, b3}, d, 1, 1, 1, 0;\nwgmma.commit_group.sync.aligned;\nwgmma.wait_group.sync.aligned 1;\nmov.b32 a2, b1;\nmov.b32 a0, t0;\nmov.b32 a3, t0;\nmov.b32 a1, t1;\n"
        "ld.shared.b32 t0, [%64+3840];\nld.shared.b32 t1, [%64+3968];\nadd.s64 d, %65, 112;\nwgmma.fence.sync.aligned;\nwgmma.mma_async.sync.aligned.m64n72k16.f32.bf16.bf16 {%0, %1, %2, %3, %4, %5, %6, %7, %8, %9, %10, %11, %12, %13, %14, %15, %16, %17, %18, %19, %20, %21, %22, %23, %24, %25, %26, %27, %28, %29, %30, %31, %32, %33, %34, %35}, {a0, a1, a2, a3}, d, 1, 1, 1, 0;\nwgmma.commit_group.sync.aligned;\nwgmma.wait_group.sync.aligned 1;\nmov.b32 b2, a1;\nmov.b32 b0, t0;\nmov.b32 b3, t0;\nmov.b32 b1, t1;\n"
        "ld.shared.b32 t0, [%64+4096];\nld.shared.b32 t1, [%64+4224];\nadd.s64 d, %65, 120;\nwgmma.fence.sync.aligned;\nwgmma.mma_async.sync.aligned.m64n72k16.f32.bf16.bf16 {%0, %1, %2, %3, %4, %5, %6, %7, %8, %9, %10, %11, %12, %13, %14, %15, %16, %17, %18, %19, %20, %21, %22, %23, %24, %25, %26, %27, %28, %29, %30, %31, %32, %33, %34, %35}, {b0, b1, b2, b3}, d, 1, 1, 1, 0;\nwgmma.commit_group.sync.aligned;\nwgmma.wait_group.sync.aligned 1;\nmov.b32 a2, b1;\nmov.b32 a0, t0;\nmov.b32 a3, t0;\nmov.b32 a1, t1;\n"
        "ld.shared.b32 t0, [%64+4352];\nld.shared.b32 t1, [%64+4480];\nadd.s64 d, %65, 128;\nwgmma.fence.sync.aligned;\nwgmma.mma_async.sync.aligned.m64n64k16.f32.bf16.bf16 {%0, %1, %2, %3, %4, %5, %6, %7, %8, %9, %10, %11, %12, %13, %14, %15, %16, %17, %18, %19, %20, %21, %22, %23, %24, %25, %26, %27, %28, %29, %30, %31}, {a0, a1, a2, a3}, d, 1, 1, 1, 0;\nwgmma.commit_group.sync.aligned;\nwgmma.wait_group.sync.aligned 1;\nmov.b32 b2, a1;\nmov.b32 b0, t0;\nmov.b32 b3, t0;\nmov.b32 b1, t1;\n"
        "ld.shared.b32 t0, [%64+4608];\nld.shared.b32 t1, [%64+4736];\nadd.s64 d, %65, 136;\nwgmma.fence.sync.aligned;\nwgmma.mma_async.sync.aligned.m64n64k16.f32.bf16.bf16 {%0, %1, %2, %3, %4, %5, %6, %7, %8, %9, %10, %11, %12, %13, %14, %15, %16, %17, %18, %19, %20, %21, %22, %23, %24, %25, %26, %27, %28, %29, %30, %31}, {b0, b1, b2, b3}, d, 1, 1, 1, 0;\nwgmma.commit_group.sync.aligned;\nwgmma.wait_group.sync.aligned 1;\nmov.b32 a2, b1;\nmov.b32 a0, t0;\nmov.b32 a3, t0;\nmov.b32 a1, t1;\n"
        "ld.shared.b32 t0, [%64+4864];\nld.shared.b32 t1, [%64+4992];\nadd.s64 d, %65, 144;\nwgmma.fence.sync.aligned;\nwgmma.mma_async.sync.aligned.m64n56k16.f32.bf16.bf16 {%0, %1, %2, %3, %4, %5, %6, %7, %8, %9, %10, %11, %12, %13, %14, %15, %16, %17, %18, %19, %20, %21, %22, %23, %24, %25, %26, %27}, {a0, a1, a2, a3}, d, 1, 1, 1, 0;\nwgmma.commit_group.sync.aligned;\nwgmma.wait_group.sync.aligned 1;\nmov.b32 b2, a1;\nmov.b32 b0, t0;\nmov.b32 b3, t0;\nmov.b32 b1, t1;\n"
        "ld.shared.b32 t0, [%64+5120];\nld.shared.b32 t1, [%64+5248];\nadd.s64 d, %65, 152;\nwgmma.fence.sync.aligned;\nwgmma.mma_async.sync.aligned.m64n56k16.f32.bf16.bf16 {%0, %1, %2, %3, %4, %5, %6, %7, %8, %9, %10, %11, %12, %13, %14, %15, %16, %17, %18, %19, %20, %21, %22, %23, %24, %25, %26, %27}, {b0, b1, b2, b3}, d, 1, 1, 1, 0;\nwgmma.commit_group.sync.aligned;\nwgmma.wait_group.sync.aligned 1;\nmov.b32 a2, b1;\nmov.b32 a0, t0;\nmov.b32 a3, t0;\nmov.b32 a1, t1;\n"
        "ld.shared.b32 t0, [%64+5376];\nld.shared.b32 t1, [%64+5504];\nadd.s64 d, %65, 160;\nwgmma.fence.sync.aligned;\nwgmma.mma_async.sync.aligned.m64n48k16.f32.bf16.bf16 {%0, %1, %2, %3, %4, %5, %6, %7, %8, %9, %10, %11, %12, %13, %14, %15, %16, %17, %18, %19, %20, %21, %22, %23}, {a0, a1, a2, a3}, d, 1, 1, 1, 0;\nwgmma.commit_group.sync.aligned;\nwgmma.wait_group.sync.aligned 1;\nmov.b32 b2, a1;\nmov.b32 b0, t0;\nmov.b32 b3, t0;\nmov.b32 b1, t1;\n"
        "ld.shared.b32 t0, [%64+5632];\nld.shared.b32 t1, [%64+5760];\nadd.s64 d, %65, 168;\nwgmma.fence.sync.aligned;\nwgmma.mma_async.sync.aligned.m64n48k16.f32.bf16.bf16 {%0, %1, %2, %3, %4, %5, %6, %7, %8, %9, %10, %11, %12, %13, %14, %15, %16, %17, %18, %19, %20, %21, %22, %23}, {b0, b1, b2, b3}, d, 1, 1, 1, 0;\nwgmma.commit_group.sync.aligned;\nwgmma.wait_group.sync.aligned 1;\nmov.b32 a2, b1;\nmov.b32 a0, t0;\nmov.b32 a3, t0;\nmov.b32 a1, t1;\n"
        "ld.shared.b32 t0, [%64+5888];\nld.shared.b32 t1, [%64+6016];\nadd.s64 d, %65, 176;\nwgmma.fence.sync.aligned;\nwgmma.mma_async.sync.aligned.m64n40k16.f32.bf16.bf16 {%0, %1, %2, %3, %4, %5, %6, %7, %8, %9, %10, %11, %12, %13, %14, %15, %16, %17, %18, %19}, {a0, a1, a2, a3}, d, 1, 1, 1, 0;\nwgmma.commit_group.sync.aligned;\nwgmma.wait_group.sync.aligned 1;\nmov.b32 b2, a1;\nmov.b32 b0, t0;\nmov.b32 b3, t0;\nmov.b32 b1, t1;\n"
        "ld.shared.b32 t0, [%64+6144];\nld.shared.b32 t1, [%64+6272];\nadd.s64 d, %65, 184;\nwgmma.fence.sync.aligned;\nwgmma.mma_async.sync.aligned.m64n40k16.f32.bf16.bf16 {%0, %1, %2, %3, %4, %5, %6, %7, %8, %9, %10, %11, %12, %13, %14, %15, %16, %17, %18, %19}, {b0, b1, b2, b3}, d, 1, 1, 1, 0;\nwgmma.commit_group.sync.aligned;\nwgmma.wait_group.sync.aligned 1;\nmov.b32 a2, b1;\nmov.b32 a0, t0;\nmov.b32 a3, t0;\nmov.b32 a1, t1;\n"
        "ld.shared.b32 t0, [%64+6400];\nld.shared.b32 t1, [%64+6528];\nadd.s64 d, %65, 192;\nwgmma.fence.sync.aligned;\nwgmma.mma_async.sync.aligned.m64n32k16.f32.bf16.bf16 {%0, %1, %2, %3, %4, %5, %6, %7, %8, %9, %10, %11, %12, %13, %14, %15}, {a0, a1, a2, a3}, d, 1, 1, 1, 0;\nwgmma.commit_group.sync.aligned;\nwgmma.wait_group.sync.aligned 1;\nmov.b32 b2, a1;\nmov.b32 b0, t0;\nmov.b32 b3, t0;\nmov.b32 b1, t1;\n"
        "ld.shared.b32 t0, [%64+6656];\nld.shared.b32 t1, [%64+6784];\nadd.s64 d, %65, 200;\nwgmma.fence.sync.aligned;\nwgmma.mma_async.sync.aligned.m64n32k16.f32.bf16.bf16 {%0, %1, %2, %3, %4, %5, %6, %7, %8, %9, %10, %11, %12, %13, %14, %15}, {b0, b1, b2, b3}, d, 1, 1, 1, 0;\nwgmma.commit_group.sync.aligned;\nwgmma.wait_group.sync.aligned 1;\nmov.b32 a2, b1;\nmov.b32 a0, t0;\nmov.b32 a3, t0;\nmov.b32 a1, t1;\n"
        "ld.shared.b32 t0, [%64+6912];\nld.shared.b32 t1, [%64+7040];\nadd.s64 d, %65, 208;\nwgmma.fence.sync.aligned;\nwgmma.mma_async.sync.aligned.m64n24k16.f32.bf16.bf16 {%0, %1, %2, %3, %4, %5, %6, %7, %8, %9, %10, %11}, {a0, a1, a2, a3}, d, 1, 1, 1, 0;\nwgmma.commit_group.sync.aligned;\nwgmma.wait_group.sync.aligned 1;\nmov.b32 b2, a1;\nmov.b32 b0, t0;\nmov.b32 b3, t0;\nmov.b32 b1, t1;\n"
        "ld.shared.b32 t0, [%64+7168];\nld.shared.b32 t1, [%64+7296];\nadd.s64 d, %65, 216;\nwgmma.fence.sync.aligned;\nwgmma.mma_async.sync.aligned.m64n24k16.f32.bf16.bf16 {%0, %1, %2, %3, %4, %5, %6, %7, %8, %9, %10, %11}, {b0, b1, b2, b3}, d, 1, 1, 1, 0;\nwgmma.commit_group.sync.aligned;\nwgmma.wait_group.sync.aligned 1;\nmov.b32 a2, b1;\nmov.b32 a0, t0;\nmov.b32 a3, t0;\nmov.b32 a1, t1;\n"
        "ld.shared.b32 t0, [%64+7424];\nld.shared.b32 t1, [%64+7552];\nadd.s64 d, %65, 224;\nwgmma.fence.sync.aligned;\nwgmma.mma_async.sync.aligned.m64n16k16.f32.bf16.bf16 {%0, %1, %2, %3, %4, %5, %6, %7}, {a0, a1, a2, a3}, d, 1, 1, 1, 0;\nwgmma.commit_group.sync.aligned;\nwgmma.wait_group.sync.aligned 1;\nmov.b32 b2, a1;\nmov.b32 b0, t0;\nmov.b32 b3, t0;\nmov.b32 b1, t1;\n"
        "ld.shared.b32 t0, [%64+7680];\nld.shared.b32 t1, [%64+7808];\nadd.s64 d, %65, 232;\nwgmma.fence.sync.aligned;\nwgmma.mma_async.sync.aligned.m64n16k16.f32.bf16.bf16 {%0, %1, %2, %3, %4, %5, %6, %7}, {b0, b1, b2, b3}, d, 1, 1, 1, 0;\nwgmma.commit_group.sync.aligned;\nwgmma.wait_group.sync.aligned 1;\nmov.b32 a2, b1;\nmov.b32 a0, t0;\nmov.b32 a3, t0;\nmov.b32 a1, t1;\n"
        "ld.shared.b32 t0, [%64+7936];\nld.shared.b32 t1, [%64+8064];\nadd.s64 d, %65, 240;\nwgmma.fence.sync.aligned;\nwgmma.mma_async.sync.aligned.m64n8k16.f32.bf16.bf16 {%0, %1, %2, %3}, {a0, a1, a2, a3}, d, 1, 1, 1, 0;\nwgmma.commit_group.sync.aligned;\nwgmma.wait_group.sync.aligned 1;\nmov.b32 b2, a1;\nmov.b32 b0, t0;\nmov.b32 b3, t0;\nmov.b32 b1, t1;\n"
        "add.s64 d, %65, 248;\nwgmma.fence.sync.aligned;\nwgmma.mma_async.sync.aligned.m64n8k16.f32.bf16.bf16 {%0, %1, %2, %3}, {b0, b1, b2, b3}, d, 1, 1, 1, 0;\nwgmma.commit_group.sync.aligned;\nwgmma.wait_group.sync.aligned 0;\n"
        "}" : "+f"(d[0]), "+f"(d[1]), "+f"(d[2]), "+f"(d[3]), "+f"(d[4]), "+f"(d[5]), "+f"(d[6]), "+f"(d[7]), "+f"(d[8]), "+f"(d[9]), "+f"(d[10]), "+f"(d[11]), "+f"(d[12]), "+f"(d[13]), "+f"(d[14]), "+f"(d[15]), "+f"(d[16]), "+f"(d[17]), "+f"(d[18]), "+f"(d[19]), "+f"(d[20]), "+f"(d[21]), "+f"(d[22]), "+f"(d[23]), "+f"(d[24]), "+f"(d[25]), "+f"(d[26]), "+f"(d[27]), "+f"(d[28]), "+f"(d[29]), "+f"(d[30]), "+f"(d[31]), "+f"(d[32]), "+f"(d[33]), "+f"(d[34]), "+f"(d[35]), "+f"(d[36]), "+f"(d[37]), "+f"(d[38]), "+f"(d[39]), "+f"(d[40]), "+f"(d[41]), "+f"(d[42]), "+f"(d[43]), "+f"(d[44]), "+f"(d[45]), "+f"(d[46]), "+f"(d[47]), "+f"(d[48]), "+f"(d[49]), "+f"(d[50]), "+f"(d[51]), "+f"(d[52]), "+f"(d[53]), "+f"(d[54]), "+f"(d[55]), "+f"(d[56]), "+f"(d[57]), "+f"(d[58]), "+f"(d[59]), "+f"(d[60]), "+f"(d[61]), "+f"(d[62]), "+f"(d[63]) : "r"(pa), "l"(db) : "memory");
}
__device__ __forceinline__ void wgmma_rs80(float (&d)[40], uint32_t a0, uint32_t a1, uint32_t a2, uint32_t a3, uint64_t db, int sc) {
    asm volatile("{\n.reg .pred p;\nsetp.ne.b32 p, %45, 0;\n"
        "wgmma.mma_async.sync.aligned.m64n80k16.f32.bf16.bf16 {%0, %1, %2, %3, %4, %5, %6, %7, %8, %9, %10, %11, %12, %13, %14, %15, %16, %17, %18, %19, %20, %21, %22, %23, %24, %25, %26, %27, %28, %29, %30, %31, %32, %33, %34, %35, %36, %37, %38, %39}, {%40, %41, %42, %43}, %44, p, 1, 1, 1;\n}\n"
        : "+f"(d[0]), "+f"(d[1]), "+f"(d[2]), "+f"(d[3]), "+f"(d[4]), "+f"(d[5]), "+f"(d[6]), "+f"(d[7]), "+f"(d[8]), "+f"(d[9]), "+f"(d[10]), "+f"(d[11]), "+f"(d[12]), "+f"(d[13]), "+f"(d[14]), "+f"(d[15]), "+f"(d[16]), "+f"(d[17]), "+f"(d[18]), "+f"(d[19]), "+f"(d[20]), "+f"(d[21]), "+f"(d[22]), "+f"(d[23]), "+f"(d[24]), "+f"(d[25]), "+f"(d[26]), "+f"(d[27]), "+f"(d[28]), "+f"(d[29]), "+f"(d[30]), "+f"(d[31]), "+f"(d[32]), "+f"(d[33]), "+f"(d[34]), "+f"(d[35]), "+f"(d[36]), "+f"(d[37]), "+f"(d[38]), "+f"(d[39]) : "r"(a0), "r"(a1), "r"(a2), "r"(a3), "l"(db), "r"(sc));
}
__device__ __forceinline__ void wgmma_ss80(float (&d)[40], uint64_t da, uint64_t db, int sc) {
    asm volatile("{\n.reg .pred p;\nsetp.ne.b32 p, %42, 0;\n"
        "wgmma.mma_async.sync.aligned.m64n80k16.f32.bf16.bf16 {%0, %1, %2, %3, %4, %5, %6, %7, %8, %9, %10, %11, %12, %13, %14, %15, %16, %17, %18, %19, %20, %21, %22, %23, %24, %25, %26, %27, %28, %29, %30, %31, %32, %33, %34, %35, %36, %37, %38, %39}, %40, %41, p, 1, 1, 0, 1;\n}\n"
        : "+f"(d[0]), "+f"(d[1]), "+f"(d[2]), "+f"(d[3]), "+f"(d[4]), "+f"(d[5]), "+f"(d[6]), "+f"(d[7]), "+f"(d[8]), "+f"(d[9]), "+f"(d[10]), "+f"(d[11]), "+f"(d[12]), "+f"(d[13]), "+f"(d[14]), "+f"(d[15]), "+f"(d[16]), "+f"(d[17]), "+f"(d[18]), "+f"(d[19]), "+f"(d[20]), "+f"(d[21]), "+f"(d[22]), "+f"(d[23]), "+f"(d[24]), "+f"(d[25]), "+f"(d[26]), "+f"(d[27]), "+f"(d[28]), "+f"(d[29]), "+f"(d[30]), "+f"(d[31]), "+f"(d[32]), "+f"(d[33]), "+f"(d[34]), "+f"(d[35]), "+f"(d[36]), "+f"(d[37]), "+f"(d[38]), "+f"(d[39]) : "l"(da), "l"(db), "r"(sc));
}
__device__ __forceinline__ void wgmma_ss80t(float (&d)[40], uint64_t da, uint64_t db, int sc) {
    asm volatile("{\n.reg .pred p;\nsetp.ne.b32 p, %42, 0;\n"
        "wgmma.mma_async.sync.aligned.m64n80k16.f32.bf16.bf16 {%0, %1, %2, %3, %4, %5, %6, %7, %8, %9, %10, %11, %12, %13, %14, %15, %16, %17, %18, %19, %20, %21, %22, %23, %24, %25, %26, %27, %28, %29, %30, %31, %32, %33, %34, %35, %36, %37, %38, %39}, %40, %41, p, 1, 1, 1, 1;\n}\n"
        : "+f"(d[0]), "+f"(d[1]), "+f"(d[2]), "+f"(d[3]), "+f"(d[4]), "+f"(d[5]), "+f"(d[6]), "+f"(d[7]), "+f"(d[8]), "+f"(d[9]), "+f"(d[10]), "+f"(d[11]), "+f"(d[12]), "+f"(d[13]), "+f"(d[14]), "+f"(d[15]), "+f"(d[16]), "+f"(d[17]), "+f"(d[18]), "+f"(d[19]), "+f"(d[20]), "+f"(d[21]), "+f"(d[22]), "+f"(d[23]), "+f"(d[24]), "+f"(d[25]), "+f"(d[26]), "+f"(d[27]), "+f"(d[28]), "+f"(d[29]), "+f"(d[30]), "+f"(d[31]), "+f"(d[32]), "+f"(d[33]), "+f"(d[34]), "+f"(d[35]), "+f"(d[36]), "+f"(d[37]), "+f"(d[38]), "+f"(d[39]) : "l"(da), "l"(db), "r"(sc));
}
__device__ __forceinline__ void wgmma_ss8_ta(float (&d)[4], uint64_t da, uint64_t db, int sc) {
    asm volatile("{\n.reg .pred p;\nsetp.ne.b32 p, %6, 0;\n"
        "wgmma.mma_async.sync.aligned.m64n8k16.f32.bf16.bf16 {%0, %1, %2, %3}, %4, %5, p, 1, 1, 1, 0;\n}\n"
        : "+f"(d[0]), "+f"(d[1]), "+f"(d[2]), "+f"(d[3]) : "l"(da), "l"(db), "r"(sc));
}
__device__ __forceinline__ void wgmma_rs8(float (&d)[4], uint32_t a0, uint32_t a1, uint32_t a2, uint32_t a3, uint64_t db, int sc) {
    asm volatile("{\n.reg .pred p;\nsetp.ne.b32 p, %9, 0;\n"
        "wgmma.mma_async.sync.aligned.m64n8k16.f32.bf16.bf16 {%0, %1, %2, %3}, {%4, %5, %6, %7}, %8, p, 1, 1, 0;\n}\n"
        : "+f"(d[0]), "+f"(d[1]), "+f"(d[2]), "+f"(d[3]) : "r"(a0), "r"(a1), "r"(a2), "r"(a3), "l"(db), "r"(sc));
}
__device__ __forceinline__ void wgmma_rs128(float (&d)[64], uint32_t a0, uint32_t a1, uint32_t a2, uint32_t a3, uint64_t db, int sc) {
    asm volatile("{\n.reg .pred p;\nsetp.ne.b32 p, %69, 0;\n"
        "wgmma.mma_async.sync.aligned.m64n128k16.f32.bf16.bf16 {%0, %1, %2, %3, %4, %5, %6, %7, %8, %9, %10, %11, %12, %13, %14, %15, %16, %17, %18, %19, %20, %21, %22, %23, %24, %25, %26, %27, %28, %29, %30, %31, %32, %33, %34, %35, %36, %37, %38, %39, %40, %41, %42, %43, %44, %45, %46, %47, %48, %49, %50, %51, %52, %53, %54, %55, %56, %57, %58, %59, %60, %61, %62, %63}, {%64, %65, %66, %67}, %68, p, 1, 1, 1;\n}\n"
        : "+f"(d[0]), "+f"(d[1]), "+f"(d[2]), "+f"(d[3]), "+f"(d[4]), "+f"(d[5]), "+f"(d[6]), "+f"(d[7]), "+f"(d[8]), "+f"(d[9]), "+f"(d[10]), "+f"(d[11]), "+f"(d[12]), "+f"(d[13]), "+f"(d[14]), "+f"(d[15]), "+f"(d[16]), "+f"(d[17]), "+f"(d[18]), "+f"(d[19]), "+f"(d[20]), "+f"(d[21]), "+f"(d[22]), "+f"(d[23]), "+f"(d[24]), "+f"(d[25]), "+f"(d[26]), "+f"(d[27]), "+f"(d[28]), "+f"(d[29]), "+f"(d[30]), "+f"(d[31]), "+f"(d[32]), "+f"(d[33]), "+f"(d[34]), "+f"(d[35]), "+f"(d[36]), "+f"(d[37]), "+f"(d[38]), "+f"(d[39]), "+f"(d[40]), "+f"(d[41]), "+f"(d[42]), "+f"(d[43]), "+f"(d[44]), "+f"(d[45]), "+f"(d[46]), "+f"(d[47]), "+f"(d[48]), "+f"(d[49]), "+f"(d[50]), "+f"(d[51]), "+f"(d[52]), "+f"(d[53]), "+f"(d[54]), "+f"(d[55]), "+f"(d[56]), "+f"(d[57]), "+f"(d[58]), "+f"(d[59]), "+f"(d[60]), "+f"(d[61]), "+f"(d[62]), "+f"(d[63]) : "r"(a0), "r"(a1), "r"(a2), "r"(a3), "l"(db), "r"(sc));
}
__device__ __forceinline__ void wgmma_rs88(float (&d)[44], uint32_t a0, uint32_t a1, uint32_t a2, uint32_t a3, uint64_t db, int sc) {
    asm volatile("{\n.reg .pred p;\nsetp.ne.b32 p, %49, 0;\n"
        "wgmma.mma_async.sync.aligned.m64n88k16.f32.bf16.bf16 {%0, %1, %2, %3, %4, %5, %6, %7, %8, %9, %10, %11, %12, %13, %14, %15, %16, %17, %18, %19, %20, %21, %22, %23, %24, %25, %26, %27, %28, %29, %30, %31, %32, %33, %34, %35, %36, %37, %38, %39, %40, %41, %42, %43}, {%44, %45, %46, %47}, %48, p, 1, 1, 1;\n}\n"
        : "+f"(d[0]), "+f"(d[1]), "+f"(d[2]), "+f"(d[3]), "+f"(d[4]), "+f"(d[5]), "+f"(d[6]), "+f"(d[7]), "+f"(d[8]), "+f"(d[9]), "+f"(d[10]), "+f"(d[11]), "+f"(d[12]), "+f"(d[13]), "+f"(d[14]), "+f"(d[15]), "+f"(d[16]), "+f"(d[17]), "+f"(d[18]), "+f"(d[19]), "+f"(d[20]), "+f"(d[21]), "+f"(d[22]), "+f"(d[23]), "+f"(d[24]), "+f"(d[25]), "+f"(d[26]), "+f"(d[27]), "+f"(d[28]), "+f"(d[29]), "+f"(d[30]), "+f"(d[31]), "+f"(d[32]), "+f"(d[33]), "+f"(d[34]), "+f"(d[35]), "+f"(d[36]), "+f"(d[37]), "+f"(d[38]), "+f"(d[39]), "+f"(d[40]), "+f"(d[41]), "+f"(d[42]), "+f"(d[43]) : "r"(a0), "r"(a1), "r"(a2), "r"(a3), "l"(db), "r"(sc));
}
__device__ __forceinline__ void wgmma_rs128k(float (&d)[64], uint32_t a0, uint32_t a1, uint32_t a2, uint32_t a3, uint64_t db, int sc) {
    asm volatile("{\n.reg .pred p;\nsetp.ne.b32 p, %69, 0;\n"
        "wgmma.mma_async.sync.aligned.m64n128k16.f32.bf16.bf16 {%0, %1, %2, %3, %4, %5, %6, %7, %8, %9, %10, %11, %12, %13, %14, %15, %16, %17, %18, %19, %20, %21, %22, %23, %24, %25, %26, %27, %28, %29, %30, %31, %32, %33, %34, %35, %36, %37, %38, %39, %40, %41, %42, %43, %44, %45, %46, %47, %48, %49, %50, %51, %52, %53, %54, %55, %56, %57, %58, %59, %60, %61, %62, %63}, {%64, %65, %66, %67}, %68, p, 1, 1, 0;\n}\n"
        : "+f"(d[0]), "+f"(d[1]), "+f"(d[2]), "+f"(d[3]), "+f"(d[4]), "+f"(d[5]), "+f"(d[6]), "+f"(d[7]), "+f"(d[8]), "+f"(d[9]), "+f"(d[10]), "+f"(d[11]), "+f"(d[12]), "+f"(d[13]), "+f"(d[14]), "+f"(d[15]), "+f"(d[16]), "+f"(d[17]), "+f"(d[18]), "+f"(d[19]), "+f"(d[20]), "+f"(d[21]), "+f"(d[22]), "+f"(d[23]), "+f"(d[24]), "+f"(d[25]), "+f"(d[26]), "+f"(d[27]), "+f"(d[28]), "+f"(d[29]), "+f"(d[30]), "+f"(d[31]), "+f"(d[32]), "+f"(d[33]), "+f"(d[34]), "+f"(d[35]), "+f"(d[36]), "+f"(d[37]), "+f"(d[38]), "+f"(d[39]), "+f"(d[40]), "+f"(d[41]), "+f"(d[42]), "+f"(d[43]), "+f"(d[44]), "+f"(d[45]), "+f"(d[46]), "+f"(d[47]), "+f"(d[48]), "+f"(d[49]), "+f"(d[50]), "+f"(d[51]), "+f"(d[52]), "+f"(d[53]), "+f"(d[54]), "+f"(d[55]), "+f"(d[56]), "+f"(d[57]), "+f"(d[58]), "+f"(d[59]), "+f"(d[60]), "+f"(d[61]), "+f"(d[62]), "+f"(d[63]) : "r"(a0), "r"(a1), "r"(a2), "r"(a3), "l"(db), "r"(sc));
}
__device__ __forceinline__ void wgmma_rs88k(float (&d)[44], uint32_t a0, uint32_t a1, uint32_t a2, uint32_t a3, uint64_t db, int sc) {
    asm volatile("{\n.reg .pred p;\nsetp.ne.b32 p, %49, 0;\n"
        "wgmma.mma_async.sync.aligned.m64n88k16.f32.bf16.bf16 {%0, %1, %2, %3, %4, %5, %6, %7, %8, %9, %10, %11, %12, %13, %14, %15, %16, %17, %18, %19, %20, %21, %22, %23, %24, %25, %26, %27, %28, %29, %30, %31, %32, %33, %34, %35, %36, %37, %38, %39, %40, %41, %42, %43}, {%44, %45, %46, %47}, %48, p, 1, 1, 0;\n}\n"
        : "+f"(d[0]), "+f"(d[1]), "+f"(d[2]), "+f"(d[3]), "+f"(d[4]), "+f"(d[5]), "+f"(d[6]), "+f"(d[7]), "+f"(d[8]), "+f"(d[9]), "+f"(d[10]), "+f"(d[11]), "+f"(d[12]), "+f"(d[13]), "+f"(d[14]), "+f"(d[15]), "+f"(d[16]), "+f"(d[17]), "+f"(d[18]), "+f"(d[19]), "+f"(d[20]), "+f"(d[21]), "+f"(d[22]), "+f"(d[23]), "+f"(d[24]), "+f"(d[25]), "+f"(d[26]), "+f"(d[27]), "+f"(d[28]), "+f"(d[29]), "+f"(d[30]), "+f"(d[31]), "+f"(d[32]), "+f"(d[33]), "+f"(d[34]), "+f"(d[35]), "+f"(d[36]), "+f"(d[37]), "+f"(d[38]), "+f"(d[39]), "+f"(d[40]), "+f"(d[41]), "+f"(d[42]), "+f"(d[43]) : "r"(a0), "r"(a1), "r"(a2), "r"(a3), "l"(db), "r"(sc));
}
__device__ __forceinline__ void wgmma_rs80k(float (&d)[40], uint32_t a0, uint32_t a1, uint32_t a2, uint32_t a3, uint64_t db, int sc) {
    asm volatile("{\n.reg .pred p;\nsetp.ne.b32 p, %45, 0;\n"
        "wgmma.mma_async.sync.aligned.m64n80k16.f32.bf16.bf16 {%0, %1, %2, %3, %4, %5, %6, %7, %8, %9, %10, %11, %12, %13, %14, %15, %16, %17, %18, %19, %20, %21, %22, %23, %24, %25, %26, %27, %28, %29, %30, %31, %32, %33, %34, %35, %36, %37, %38, %39}, {%40, %41, %42, %43}, %44, p, 1, 1, 0;\n}\n"
        : "+f"(d[0]), "+f"(d[1]), "+f"(d[2]), "+f"(d[3]), "+f"(d[4]), "+f"(d[5]), "+f"(d[6]), "+f"(d[7]), "+f"(d[8]), "+f"(d[9]), "+f"(d[10]), "+f"(d[11]), "+f"(d[12]), "+f"(d[13]), "+f"(d[14]), "+f"(d[15]), "+f"(d[16]), "+f"(d[17]), "+f"(d[18]), "+f"(d[19]), "+f"(d[20]), "+f"(d[21]), "+f"(d[22]), "+f"(d[23]), "+f"(d[24]), "+f"(d[25]), "+f"(d[26]), "+f"(d[27]), "+f"(d[28]), "+f"(d[29]), "+f"(d[30]), "+f"(d[31]), "+f"(d[32]), "+f"(d[33]), "+f"(d[34]), "+f"(d[35]), "+f"(d[36]), "+f"(d[37]), "+f"(d[38]), "+f"(d[39]) : "r"(a0), "r"(a1), "r"(a2), "r"(a3), "l"(db), "r"(sc));
}
__device__ __forceinline__ void wgmma_rs64(float (&d)[32], uint32_t a0, uint32_t a1, uint32_t a2, uint32_t a3, uint64_t db, int sc) {
    asm volatile("{\n.reg .pred p;\nsetp.ne.b32 p, %37, 0;\n"
        "wgmma.mma_async.sync.aligned.m64n64k16.f32.bf16.bf16 {%0, %1, %2, %3, %4, %5, %6, %7, %8, %9, %10, %11, %12, %13, %14, %15, %16, %17, %18, %19, %20, %21, %22, %23, %24, %25, %26, %27, %28, %29, %30, %31}, {%32, %33, %34, %35}, %36, p, 1, 1, 1;\n}\n"
        : "+f"(d[0]), "+f"(d[1]), "+f"(d[2]), "+f"(d[3]), "+f"(d[4]), "+f"(d[5]), "+f"(d[6]), "+f"(d[7]), "+f"(d[8]), "+f"(d[9]), "+f"(d[10]), "+f"(d[11]), "+f"(d[12]), "+f"(d[13]), "+f"(d[14]), "+f"(d[15]), "+f"(d[16]), "+f"(d[17]), "+f"(d[18]), "+f"(d[19]), "+f"(d[20]), "+f"(d[21]), "+f"(d[22]), "+f"(d[23]), "+f"(d[24]), "+f"(d[25]), "+f"(d[26]), "+f"(d[27]), "+f"(d[28]), "+f"(d[29]), "+f"(d[30]), "+f"(d[31]) : "r"(a0), "r"(a1), "r"(a2), "r"(a3), "l"(db), "r"(sc));
}

__device__ __forceinline__ uint64_t mkdesc(uint32_t lo) { return ((uint64_t)0x40000040u << 32) | lo; }
template <int F> __device__ __forceinline__ uint32_t lop3(uint32_t a, uint32_t b, uint32_t c) { uint32_t r; asm("lop3.b32 %0, %1, %2, %3, %4;" : "=r"(r) : "r"(a), "r"(b), "r"(c), "n"(F)); return r; }
__device__ __forceinline__ void stg128_tag(void* p, uint32_t x, uint32_t y, uint32_t z, uint32_t u, uint32_t ep, int w) {
    stg128(p, lop3<0xB8>(x, w == 0, ep), lop3<0xB8>(y, w == 1, ep), lop3<0xB8>(z, w == 2, ep), lop3<0xB8>(u, w == 3, ep));
}
__device__ __forceinline__ uint32_t tag(uint32_t w, uint32_t ep) { asm("lop3.b32 %0, %0, 1, %1, 0xB8;" : "+r"(w) : "r"(ep)); return w; }
template <int N> __device__ __forceinline__ void pack_part(uint32_t (&p)[32], const float (&v)[N], uint32_t ep) {
#pragma unroll
    for (int i = 0; i < N / 2; i++) p[i] = (i & 3) ? pack2(v[2 * i], v[2 * i + 1]) : tag(pack2(v[2 * i], v[2 * i + 1]), ep);
#pragma unroll
    for (int i = 0; i < N / 2; i++) asm volatile("" : "+r"(p[i]));
}
__device__ __forceinline__ void st_part(uint4* p, const uint32_t* v) {
    asm volatile("{\n.reg .b64 l, h;\n.reg .b128 q;\nmov.b64 l, {%1, %2};\nmov.b64 h, {%3, %4};\nmov.b128 q, {l, h};\nst.relaxed.gpu.global.b128 [%0], q;\n}"
                 ::"l"(p), "r"(v[0]), "r"(v[1]), "r"(v[2]), "r"(v[3]) : "memory");
}
__device__ __forceinline__ void st_peer(uint32_t a, uint32_t x, uint32_t y, uint32_t z, uint32_t w, uint32_t bar) {
    asm volatile("st.async.shared::cluster.mbarrier::complete_tx::bytes.v4.b32 [%0], {%1, %2, %3, %4}, [%5];" ::"r"(a), "r"(x), "r"(y), "r"(z), "r"(w), "r"(bar) : "memory");
}
__device__ __forceinline__ int g4_block(int c, int j) { return c ? j ^ (8 - 2 * c) : 8 + (j & 1); }
__device__ __forceinline__ uint32_t recv_off(int w) { return w ? OFF_XR : OFF_REM; }
__device__ __forceinline__ uint4 ld_part(const void* p) {
    uint4 v;
    asm volatile("{\n.reg .b64 l, h;\n.reg .b128 q;\nld.relaxed.gpu.global.b128 q, [%4];\nmov.b128 {l, h}, q;\nmov.b64 {%0, %1}, l;\nmov.b64 {%2, %3}, h;\n}"
                 : "=r"(v.x), "=r"(v.y), "=r"(v.z), "=r"(v.w) : "l"(p) : "memory");
    return v;
}
__device__ __forceinline__ void ld_part4(uint4 (&u)[4], const uint4* p, int st) {
#pragma unroll
    for (int i = 0; i < 4; i++) u[i] = ld_part(p + i * st);
}
__device__ __forceinline__ uint32_t stale4(const uint4 (&u)[4], uint32_t ep) { return lop3<0x7E>(u[0].x, ep, u[1].x) | lop3<0x7E>(u[2].x, ep, u[3].x); }
__device__ __forceinline__ uint4 add2(uint4 a, uint4 b) { return make_uint4(add2(a.x, b.x), add2(a.y, b.y), add2(a.z, b.z), add2(a.w, b.w)); }
__device__ __forceinline__ uint4 fin16(uint4 v, uint4 b, uint4 c) { return make_uint4(fma2(c.x, v.x, b.x), fma2(c.y, v.y, b.y), fma2(c.z, v.z, b.z), fma2(c.w, v.w, b.w)); }
__device__ __forceinline__ uint4 scale16(float2 c, float2 d, float r0, float r1) {
    return make_uint4(pack2(c.x * r0, c.y * r0), pack2(c.x * r1, c.y * r1), pack2(d.x * r0, d.y * r0), pack2(d.x * r1, d.y * r1));
}
__device__ __forceinline__ uint32_t split2(float x) { const float h = rbf(x); return pack2(h, x - h); }
__device__ __forceinline__ uint32_t b80_desc(uint32_t dsb, uint32_t wn, uint32_t rn, uint32_t h) {
    const uint32_t wb = dsb + OFF_W + (wn & 7) * 16384 + h * 8192, rm = dsb + OFF_REM + rn * 4096 + h * 2048;
    return (wb >> 4) | ((rm - wb) << 12);
}
constexpr int64_t B80_STEP = 128 - (126 << 16), B80_HALF = 512 - (384 << 16);
constexpr uint32_t ring_mask(int L) {
    uint32_t m = 0;
    for (int i = L; i < 20; i++) m |= (uint32_t)(i >= 20 - L || !((i - L) & 1)) << i;
    return m;
}
constexpr int pair_pos(int w, int i) { return w ? (i < 5 - LEAD2 ? LEAD2 + 2 * i : 5 + i) : (i < LEAD2 ? i : 2 * i - LEAD2 + 1); }
constexpr uint32_t pair_mask() { uint32_t m = 0; for (int i = 0; i < 5; i++) m |= 3u << (2 * pair_pos(1, i)); return m; }
constexpr uint32_t pair_slots(int w) { uint32_t m = 0; for (int i = 0; i < 5; i++) m |= (uint32_t)((2 + pair_pos(w, i)) & 3) << (2 * i); return m; }
constexpr uint32_t M0 = ring_mask(LEAD1), M1 = pair_mask(), M2 = ring_mask(XLEAD), P0S = pair_slots(0), P1S = pair_slots(1);
__device__ __forceinline__ uint32_t ring_pos(int w, int n, int L) { return w ? (n < 10 - L ? L + 2 * n : 10 + n) : (n < L ? n : 2 * n - L + 1); }
__device__ __forceinline__ int g1_block(int n, int j) { return n < 5 ? 2 * n + (j & 1) : 2 * n - 9 - (j & 1); }

__device__ __forceinline__ int g2_block(int n) { return (0x9874326510ull >> (4 * n)) & 15; }
__device__ __forceinline__ int g3_block(int n, int j) { return n ? n - (n <= j) : j; }
struct Tile { int e, w, kb; uint32_t at; };
__device__ __forceinline__ Tile ring_tile(int n, int grp, int j) {
    const int e = (n >= 20) + (n >= 40), i = n - 20 * e;
    const uint32_t M = e == 0 ? M0 : e == 1 ? M1 : M2;
    const int w = (M >> i) & 1, c = __popc(M & ((1u << i) - 1)), kb = w ? c : i - c, tile = grp + 16 * w;
    return {e, w, kb, 64u * (e == 0 ? tile + (g1_block(kb, j) << 16) : e == 1 ? g2_block(kb) + (tile << 16) : (10 * tile + g3_block(kb, j)) << 16)};
}
__device__ __forceinline__ void load_tile(const Maps& mp, uint32_t dst, int e, uint32_t at, uint32_t bar) {
    mbar_expect(bar, 8192);
    tma_ld2(dst, &mp.x[e], at & 0xffff, at >> 16, bar);
}

template <int OCT>
__device__ __forceinline__ void gemv_tile(float (&d)[4], uint32_t a, uint32_t b, int kb0) {
    uint32_t alo = ((a & 0x3FFFF) >> 4) | 0x10000u, blo_ = ((b & 0x3FFFF) >> 4) | (OCT << 16);
#pragma unroll 1
    for (int s = 0; s < 20; s += 4) {
        const int kb = kb0 + (s >> 2);
        const uint32_t bk = blo_ + (OCT == 7 ? (kb & 1) * 288 + (kb >> 1) * 56 : kb * 64);
        wg_fence();
#pragma unroll
        for (int q = 0; q < 4; q++) wgmma_ss8_ta(d, mkdesc(alo + (s + q) * 128), ((uint64_t)8 << 32) | (bk + q * 2 * OCT), s + q);
        wg_commit();
    }
    wg_wait<0>();
    reg_fence(d);
}

__device__ __forceinline__ void flush_tile(uint32_t st, bf16* dst, int u) {
#pragma unroll
    for (int i = 0; i < 2; i++) {
        const int idx = u + 320 * i, row = idx >> 3, c = idx & 7;
        stg128(dst + (size_t)row * S_ + 8 * c, lds128(st + row * 128 + ((c ^ ((row >> 1) & 7)) << 4)));
    }
}

__device__ __forceinline__ int tid_now() { int t; asm volatile("mov.u32 %0, %%tid.x;" : "=r"(t)); return t; }
__device__ __forceinline__ float zscale(float c) { return c == 0.f ? 0x1p-30f : c; }
__device__ __forceinline__ bool bar_any(int id, bool p) {
    uint32_t r;
    asm volatile("{\n.reg .pred a, b;\nsetp.ne.u32 a, %2, 0;\nbarrier.red.or.pred.aligned b, %1, 128, a;\nselp.u32 %0, 1, 0, b;\n}" : "=r"(r) : "r"(id), "r"((uint32_t)p) : "memory");
    return r != 0;
}

__global__ void __cluster_dims__(2, 1, 1) __launch_bounds__(NTHR, 1) fused_kernel(const __grid_constant__ Ptrs pp, bf16* __restrict__ out, const __grid_constant__ Maps mp) {
    extern __shared__ __align__(1024) uint8_t smem_raw[];
    const uint32_t sb = s2u(smem_raw), bars = sb + M_BAR, dsb = sb & 0x3FFFF;
    const int id = blockIdx.x, warp = __shfl_sync(0xffffffffu, (int)threadIdx.x >> 5, 0), wg = warp >> 2;
    const uint32_t c0 = clock_lo();
#define TIDS const int tid = tid_now(), lane = tid & 31, wt = tid & 127, g = lane >> 2, t = lane & 3; (void)wt; (void)g; (void)t;
    TS(threadIdx.x == 0, 0) TG(threadIdx.x == 0, 62)

    if (id >= 128) {
        TIDS
        if (sb & 1023) __trap();
        const int hs = id - 128;
        constexpr int H_B = 204800;
        static_assert(H_B + TAB_BYTES + 8 * VEC_BYTES <= OFF_M, "helper map");
        if (warp < 10 && elect()) { mbar_init(bars + warp * 8, 1); mbar_init(bars + 80 + warp * 8, 1); asm volatile("fence.mbarrier_init.release.cluster;" ::: "memory"); }
        __syncthreads();
        const uint32_t e0 = ld_cold(&g_epoch);
        wait_clock(c0, HELP_T);
        uint4 wr[10];
#pragma unroll
        for (int u = 0; u < 10; u++) wr[u] = ldg128(((hs >> 1) ? pp.w2 : pp.w1) + (size_t)(320 * (hs & 1) + (tid >> 4) + 32 * u) * D_ + 512 + 8 * (tid & 15));
        {
            const int r = tid >> 4, c = tid & 15;
            uint4* dst[2];
#pragma unroll
            for (int e = 0; e < 2; e++) {
                const int p = !(hs >> 1) ? r : e && (hs & 1) ? (r & ~14) | ((r & 6) << 1) | ((r & 8) >> 2) : (r & ~30) | ((r & 6) << 2) | ((r & 24) >> 2);
                dst[e] = &g_wr[((hs >> 1) * 8 + (c >> 1)) * 10 * 128 + (p & 15) * 8 + ((2 * (p >> 4) + (c & 1)) ^ (p & 7))];
            }
#pragma unroll
            for (int u = 0; u < 10; u++) stg128(reinterpret_cast<uint4*>(reinterpret_cast<uintptr_t>(dst[u >= 6]) ^ (64 * (u & 1))) +
                       ((hs >> 1) ? (0x9873265410ull >> (4 * (5 * (hs & 1) + (u >> 1)))) & 15 : 5 * (hs & 1) + (u >> 1)) * 128, wr[u]);
        }
        __syncthreads();
        if (warp == 0) signal_cnt(&g_cnt.wr[0], lane, 1);
        __syncthreads();
        if (warp < 5 && elect()) {
            const int un = 5 * hs + warp;
            mbar_expect(bars + warp * 8, 40960);
            tma_ld2(sb + warp * 40960, &mp.w1h, 64 * (un >> 1), 320 * (un & 1), bars + warp * 8);
            tma_ld2(sb + warp * 40960 + 20480, &mp.w1h, 64 * (un >> 1), 320 * (un & 1) + 160, bars + warp * 8);
        }
        if (tid < 320) {
            const uint4* gm = reinterpret_cast<const uint4*>(g_mod + 3 * D_) + tid;
            const unsigned epoch = e0 + 1;
            uint4 r[6];
            unsigned it = 0;
            for (;;) {
                uint32_t bad = 0;
#pragma unroll
                for (int i = 0; i < 6; i++) { r[i] = ld_part(gm + (i >> 1) * (D_ / 2) + (i & 1) * 3 * D_); bad |= (r[i].y ^ epoch) | (r[i].w ^ epoch); }
                if (__all_sync(~0u, !bad)) break;
                if (++it > SPIN_LIMIT) SPIN_FAIL(54)
            }
            uint32_t mv[3];
#pragma unroll
            for (int i = 0; i < 3; i++) mv[i] = pack2(__uint_as_float(r[2 * i].x) + __uint_as_float(r[2 * i + 1].x), __uint_as_float(r[2 * i].z) + __uint_as_float(r[2 * i + 1].z));
            const uint32_t sw2 = mv[0], cw = add2(mv[1], 0x3f803f80u), gw = mv[2];
            const float c0 = blo(cw), c1 = bhi(cw), s0 = blo(sw2), s1 = bhi(sw2);
            const float i0 = __frcp_rn(zscale(c0)), i1 = __frcp_rn(zscale(c1));
            const uint32_t ci = pack2(i0, i1), cq = pack2(i0 * i0, i1 * i1);
            const uint32_t a = sb + H_B + ((tid >> 5) & 1) * 4608 + (tid >> 6) * 896 + ((tid >> 2) & 7) * 112 + (tid & 3) * 4;
            sts32(a, ci); sts32(a + 16, pack2(i0 - blo(ci), i1 - bhi(ci)));
            sts32(a + 32, cq); sts32(a + 48, pack2(fmaf(i0, i0, -blo(cq)), fmaf(i1, i1, -bhi(cq))));
            sts32(a + 64, cw); sts32(a + 80, sw2); sts32(a + 96, 0x3f803f80u);
            if ((tid & ~35) == 284) sts32(a + 112, 0);
            const uint32_t v = sb + H_B + TAB_BYTES + (tid < 256 ? (tid >> 5) * VEC_BYTES + (tid & 31) * 8 : ((tid - 256) >> 3) * VEC_BYTES + 256 + (tid & 7) * 8);
            sts64f(v, blo(gw), bhi(gw)); sts64f(v + 320, c0, c1); sts64f(v + 640, s0, s1); sts64f(v + 960, i0, i1);
            float k[5] = {c0 + c1, s0 + s1, fmaf(c0, c0, c1 * c1), fmaf(c0, s0, c1 * s1), fmaf(s0, s0, s1 * s1)};
#pragma unroll 1
            for (int o = 16; o; o >>= 1) {
#pragma unroll
                for (int e = 0; e < 5; e++) k[e] += __shfl_xor_sync(~0u, k[e], o);
            }
            const uint32_t ks = sb + H_B + TAB_BYTES + (lane & 7) * VEC_BYTES + 1280 + (warp >> 1) * 32;
            if ((warp & 1) && lane < 8) { sts128f(ks, k[0], k[1], k[2], k[3]); sts128f(ks + 16, k[4], 0.f, 0.f, 0.f); }
            bar_sync(3, 320);
            if (!(warp & 1) && lane < 8) {
                const float4 o = lds128f(ks);
                sts128f(ks, k[0] + o.x, k[1] + o.y, k[2] + o.z, k[3] + o.w); sts32(ks + 16, __float_as_uint(k[4] + __uint_as_float(lds32(ks + 16))));
            }
            fence_async_smem();
        }
        __syncthreads();
        if (hs == 0 && warp == 15 && elect()) {
            asm volatile("cp.async.bulk.global.shared::cta.bulk_group [%0], [%1], %2;\ncp.async.bulk.commit_group;\ncp.async.bulk.wait_group 0;"
                         ::"l"(g_tab), "r"(sb + H_B), "n"(TAB_BYTES + 8 * VEC_BYTES) : "memory");
            asm volatile("red.release.gpu.global.add.u32 [%0], 1;" ::"l"(&g_cnt.tab[0]) : "memory");
        }
        __syncwarp();
#pragma unroll 1
        for (int i = wg; i < 20; i += 4) {
            const int r = i / 5, b = i - 5 * r, un = 5 * hs + b, u3 = 20 * r + un;
            auto refill = [&](int e, int u, uint32_t fb) {
                mbar_expect(fb, 40960);
                tma_ld2(sb + e * 40960, &mp.w3h, 64 * (u >> 1), 320 * (u & 1), fb);
                tma_ld2(sb + e * 40960 + 20480, &mp.w3h, 64 * (u >> 1), 320 * (u & 1) + 160, fb);
            };
            if (i > 4 && i < 9) {
                bar_sync(1, 512);
                if (warp == 0) {
                    signal_cnt(&g_cnt.uv[0], lane, 1);
                    if (elect()) {
#pragma unroll 1
                        for (int e = 0; e < 5; e++) refill(e, 5 * hs + e, bars + (5 + e) * 8);
                        l2_prefetch(pp.w2 + (size_t)160 * hs * D_, 160 * D_ * 2);
                    }
                    __syncwarp();
                }
            }
            mbar_wait(bars + i * 8, 0);
            float d[4];
            gemv_tile<7>(d, sb + b * 40960, sb + H_B, 5 * (un & 1));
            const int col = 16 * (warp & 3) + g;
            float* dst = r ? g_cs3 + (un & 1) * 1920 + 64 * ((u3 >> 1) - 10) + col : g_uv + (un & 1) * 3 * D_ + 2 * D_ + 64 * (un >> 1) + col;
            if (t == 3) { dst[0] = d[0]; dst[8] = d[2]; }
            if (r == 0 && t == 2) { dst[-2 * D_] = d[0]; dst[8 - 2 * D_] = d[2]; dst[-D_] = d[1]; dst[8 - D_] = d[3]; }
            if (r == 1 || r == 2) {
                bar_sync(4 + wg, 128);
                if (wt == 0) refill(b, u3, bars + (i + 5) * 8);
            }
        }
        __syncthreads();
        if (warp == 0) signal_cnt(&g_cnt.cs[0], lane, 1);
        if (tid == 511) l2_prefetch(pp.w4 + (size_t)432 * hs * D_, 432 * D_ * 2);
        for (uint32_t it = 0; ld_cold(&g_cnt.cs[0]) < 4;) { if (++it > SPIN_LIMIT) SPIN_FAIL(47) }
        asm volatile("fence.acquire.gpu;" ::: "memory");
        if (tid < 432) {
            const int jj = 2 * hs + (tid >= 216), c = tid % 216;
            const float* src = g_cs3 + (c < 192 ? 192 * jj + c : 1344 + 24 * jj + c);
            const uint32_t s = split2(ldcg32f(src) + ldcg32f(src + 1920));
            stg128(&g_cs3b[432 * hs + tid], s, s & 0xffffu, 0, 0);
        }
        __syncthreads();
        if (warp == 0) signal_cnt(&g_cnt.cs2[0], lane, 1);
        if (tid == 0 && hs == 3) {
            uint32_t it = 0;
            while (ld_cold(&g_epoch) == e0) { __nanosleep(256); if (++it > (1u << 20)) SPIN_FAIL(48) }
        }
        return;
    }

    if (elect()) {
        if (warp == 15) {
            mbar_init(bars + B_IN * 8, 1); mbar_init(bars + B_IN * 8 + 8, 1);
            asm volatile("fence.mbarrier_init.release.cluster;" ::: "memory");
            mbar_expect(bars + B_IN * 8, 131 * 160);
            tma_ld2(sb + OFF_KIN, &mp.k, 80 * (id & 7), 64 * (id >> 3) - 3, bars + B_IN * 8);
            tma_ld2(sb + OFF_VIN, &mp.v, 80 * (id & 7), 64 * (id >> 3), bars + B_IN * 8);
        } else if (warp < 13) {
            const uint32_t n = (0x4C11111111881ull >> (4 * warp)) & 15;
#pragma unroll
            for (int i = 0; i < 4; i++) mbar_init(bars + warp * 64 + i * 8, n);
            if (warp == 11) { mbar_init(bars + B_XFREE * 8, 16); mbar_init(bars + B_OWN * 8, 8); }
            else {
#pragma unroll
                for (int i = 4; i < 8; i++) mbar_init(bars + warp * 64 + i * 8, n);
            }
            asm volatile("fence.mbarrier_init.release.cluster;" ::: "memory");
        }
    }
    asm volatile("" ::"l"(pp.s), "l"(pp.c), "l"(out));
    TR4((threadIdx.x & 31) == 0, warp)
    const int pr = id >> 1;
    const int grp = pr < 4 ? 15 : pr < 36 ? (pr - 4) & 7 : 8 + (pr - 36) % 7;
    const int j = 2 * (pr < 4 ? pr : pr < 36 ? (pr - 4) >> 3 : (pr - 36) / 7) + (id & 1);

    if (wg == 3) {
        TIDS
        const int sw = warp - 12;
        uint32_t ep = ld_cold(&g_epoch);
        TR4(lane == 0, 20 + sw)
        __syncthreads();
        TR4(lane == 0, 30 + sw)
        asm volatile("barrier.cluster.arrive.relaxed.aligned;" ::: "memory");
        if (sw == 0) {
#pragma unroll 1
            for (int n = 0; n < 12; n++) {
                wait_clock(c0, PF_T0 + PF_DT * n);
                if (elect()) l2_prefetch(n < 4 ? (const char*)pp.q + id * 20480 + n * 5120 : (const char*)pp.w_mod + id * 38400 + (n - 4) * 4800, n < 4 ? 5120 : 4800);
            }
        } else if (sw == 1) {
            wait_clock(c0, T_SSM);
            if (elect()) {
                mbar_expect(bars + B_SSM * 8, 20480);
                bulk_ld(sb + OFF_SSM, pp.ssm_k + (size_t)5 * id * S_, 20480, bars + B_SSM * 8);
            }
            mbar_spin(bars + B_KVS * 8, 0);
            signal_cnt(&g_cnt.kv[(id & 7) * 32], lane, 1, true);
            TS(lane == 0, 2)
            mbar_spin(bars + B_RAW * 8, 0);
            if (elect()) {
                mbar_expect(bars + B_QIN * 8, 20480);
                tma_ld3(sb + OFF_QIN, &mp.q, 0, 16 * id, 0, bars + B_QIN * 8);
            }
        } else if (sw == 2) {
            if (elect()) {
#pragma unroll 1
                for (int i = 2; i < (int)(sizeof(Maps) / sizeof(CUtensorMap)); i++) asm volatile("prefetch.tensormap [%0];" ::"l"(&mp.k + i) : "memory");
#pragma unroll 1
                for (int i = B_SUMS; i < B_LAND; i++) mbar_expect(bars + i * 8, i < B_RECV ? 2048 : (i & 3) < 3 ? 8192 : 3072);
            }
            wait_cnt(&g_cnt.kv[(id >> 4) * 32], 16, true);
            TS(lane == 0, 4)
            if (elect()) {
                mbar_expect(bars + B_RAW * 8, 12288);
                mbar_expect(bars + B_RAW2 * 8, 8192);
#pragma unroll
                for (int c = 0; c < 5; c++) bulk_ld(sb + OFF_CH + c * CH_BYTES, g_kvT + (size_t)(5 * id + c) * S_, 4096, bars + (c < 3 ? B_RAW : B_RAW2) * 8);
            }
            mbar_spin(bars + B_BK * 8, 0);
            mbar_spin(bars + B_QIN * 8, 0);
            if (id < 120 && elect()) {
                mbar_expect(bars + B_WM * 8, 40960);
                tma_ld2(sb + OFF_WM, &mp.wmod, 64 * pr, 320 * (id & 1), bars + B_WM * 8);
                tma_ld2(sb + OFF_WM + 20480, &mp.wmod, 64 * pr, 320 * (id & 1) + 160, bars + B_WM * 8);
            }
            TS(lane == 0, 57)
        } else {
            wait_clock(c0, T_KVB);
            if (elect()) {
                mbar_expect(bars + (B_IN + 1) * 8, 131 * 160);
                tma_ld2(sb + OFF_KIN + 10752, &mp.k, 80 * (id & 7), 64 * (id >> 3) + 1021, bars + (B_IN + 1) * 8);
                tma_ld2(sb + OFF_VIN + 10240, &mp.v, 80 * (id & 7), 64 * (id >> 3) + 1024, bars + (B_IN + 1) * 8);
            }
            TS(lane == 0, 53)
            if (lane == 0) sts32(sb + M_EP, ep + 1);
            sts32(sb + M_NUL + lane * 4, 0);
#pragma unroll 1
            for (int i = 0; i < 10; i++) sts128(sb + OFF_Z + i * 512 + lane * 16, 0, 0, 0, 0);
            __syncwarp();
#pragma unroll 1
            for (int i = lane; i < 160; i += 32) {
                const uint32_t c = ldg32(pp.c + 320 * (id & 1) + 2 * i);
                sts32(sb + OFF_Z + (i >> 2) * 128 + (i & 3) * 4, pack2(silu(blo(c)), silu(bhi(c))));
            }
            fence_async_smem();
            for (uint32_t ph = 0, again = 1; again; ph ^= 1) {
                mbar_spin(bars + B_RAW2 * 8, ph);
                uint32_t bad = 0;
#pragma unroll
                for (int i = 0; i < 8; i++) bad |= lop3<0x7E>(lds32(sb + OFF_CH + 3 * CH_BYTES + i * 512 + lane * 16), ~ep, lds32(sb + OFF_CH + 4 * CH_BYTES + i * 512 + lane * 16));
                again = __any_sync(~0u, bad & 1);
                if (again && elect()) {
                    mbar_expect(bars + B_RAW2 * 8, 8192);
#pragma unroll
                    for (int c = 3; c < 5; c++) bulk_ld(sb + OFF_CH + c * CH_BYTES, g_kvT + (size_t)(5 * id + c) * S_, 4096, bars + B_RAW2 * 8);
                }
            }
            if (elect()) mbar_arrive(bars + B_RAW3 * 8);
        }
        {
            mbar_spin(bars + B_QIN * 8, 0);
            asm volatile("add.u32 %0, %0, 1;" : "+r"(ep));
            TS(wt == 0, 54)
            const int tk = 8 * ((lane >> 1) & 1) + 2 * (lane >> 3) + (lane & 1), ck = 4 * (sw & 1) + ((lane >> 1) & 2);
            const uint32_t src = sb + OFF_QIN + (sw >> 1) * 2048 + tk * 128;
            bf16* dst = g_qT + (size_t)id * 16 * D_ + (32 * sw + 8 * (t & 2) + g) * 16 + 8 * (t & 1);
constexpr int QU = Q_UNROLL;
#pragma unroll QU
            for (int i = 0; i < 5; i++) {
                uint32_t r[8];
                ldsm4t(src + i * 4096 + ((ck ^ (tk & 7)) << 4), r[0], r[1], r[2], r[3]);
                ldsm4t(src + i * 4096 + (((ck + 1) ^ (tk & 7)) << 4), r[4], r[5], r[6], r[7]);
                stg128(dst + i * 2048, tag(r[0], ep), r[1], r[2], r[3]);
                stg128(dst + i * 2048 + 128, tag(r[4], ep), r[5], r[6], r[7]);
            }
            float s1 = 0.f, s2 = 0.f;
#pragma unroll 2
            for (int i = 0; i < 10; i++) {
                const uint4 w4 = lds128(sb + OFF_QIN + i * 2048 + wt * 16);
                const uint32_t w[4] = {w4.x, w4.y, w4.z, w4.w};
#pragma unroll
                for (int e = 0; e < 4; e++) { const float a = blo(w[e]), b = bhi(w[e]); s1 += a + b; s2 = fmaf(a, a, fmaf(b, b, s2)); }
            }
#pragma unroll
            for (int o = 1; o < 8; o *= 2) { s1 += __shfl_xor_sync(~0u, s1, o); s2 += __shfl_xor_sync(~0u, s2, o); }
            s1 *= 1.f / D_;
            uint32_t rs = pack2(rsqrtf(fmaxf(s2 * (1.f / D_) - s1 * s1, 0.f) + 1e-5f), 0.f);
            if (lane < 8) rs = tag(rs, ep);
            rs = pack2(blo(rs), -s1 * blo(rs));
            const uint32_t sel = lane ? 0x7632 : 0x5410;
            const uint32_t a0 = __shfl_sync(~0u, rs, 0), a1 = __shfl_sync(~0u, rs, 8), a2 = __shfl_sync(~0u, rs, 16), a3 = __shfl_sync(~0u, rs, 24);
            if (lane < 2) stg64(g_qst + lane * S_ + 16 * id + 4 * sw, tag(__byte_perm(a0, a1, sel), ep), __byte_perm(a2, a3, sel));
            TS(wt == 0, 55)
        }
        bar_sync(6, 128);
        if (sw == 3) {
            signal_cnt(&g_cnt.q[(lane & 3) * 32], lane, 4, true);
            TS(lane == 0, 3)
        }
        asm volatile("setmaxnreg.dec.sync.aligned.u32 " STR(REG_SVC) ";");
        asm volatile("barrier.cluster.wait.aligned;" ::: "memory");
        if (sw == 1) {
            mbar_spin(bars + B_XS * 8, 0);
            signal_cnt(&g_cnt.x[(lane & 3) * 32], lane, 4, true);
            TS(lane == 0, 20)
        }
        if (sw == 1 || sw == 2) {
            mbar_spin(bars + B_XS * 8, 0);
            fence_async_smem();
            int n = sw & 1;
            const uint32_t plan = ring_tile(min(2 * lane + n, 59), grp, j).at;
#pragma unroll 1
            for (int s = 0; s < 7; s++) {
                const int e = (s >= 2) + (s >= 5), end = (0ull + LEAD1 + (20 << 8) + (24 << 16) + ((20ull + 2 * LEAD2) << 24) + (40ull << 32) + ((40ull + XLEAD) << 40) + (60ull << 48)) >> (8 * s) & 255;
                if (s == 1 || s == 4 || s == 6) mbar_spin(bars + (B_GATE + 2 + e) * 8, !e);
                else if (s != 3 || grp == 15) {
                    wait_cnt(s == 0 ? &g_cnt.x[(id & 3) * 32] : s == 5 ? &g_cnt.g2[grp * 32] : &g_cnt.g1[(s == 2 ? min(max(grp - 1 + min(lane, 2), 0), 15) : 16) * 32], e ? 32 : 128, true);
                    TS(lane == 0 && sw == 2 && s != 3, 26 + 2 * e)
                }
#pragma unroll 1
                for (; n < end; n += 2) {
                    const uint32_t at = __shfl_sync(~0u, plan, n >> 1);
                    mbar_spin(bars + (B_XEMPTY + (n & 7)) * 8, ((n >> 3) & 1) ^ 1);
                    TR2(lane == 0 && n < 40, 20 + n)
                    if (elect()) {
                        if (n == 40 || n == 40 + XLEAD) {
                            mbar_arrive(bars + (B_LAND + (n & 7)) * 8);
                            asm volatile("mbarrier.arrive.shared.b64 _, [%0], 8;" ::"r"(bars + (B_XEMPTY + (n & 7)) * 8) : "memory");
                        } else load_tile(mp, sb + OFF_XR + (n & 7) * 8192, e, at, bars + (B_LAND + (n & 7)) * 8);
                    }
                }
            }
            if (sw == 1) { if (elect()) mbar_arrive(bars + (B_GATE + 5) * 8); return; }
            mbar_spin(bars + (B_GATE + 5) * 8, 0);
            mbar_spin(bars + B_VEC3 * 8, 0);
            unsigned old = 0;
            asm volatile("{\n.reg .pred P;\nsetp.eq.s32 P, %2, 0;\n@P atom.relaxed.gpu.global.add.u32 %0, [%1], %3;\n}" : "+r"(old) : "l"(&g_cnt.done[0]), "r"(lane), "r"(1) : "memory");
            if (__any_sync(~0u, old == 127)) {
#pragma unroll 1
                for (int i = lane; i < (int)(sizeof(Counters) / 128); i += 32) reinterpret_cast<unsigned*>(&g_cnt)[i * 32] = 0;
                signal_cnt(&g_epoch, lane, 1, true);
            }
        } else if (sw == 0) {
            wait_cnt(&g_cnt.wr[0], 4);
            mbar_spin(bars + B_QRDY * 8, 0);
            const uint32_t wf = bars + B_WFULL * 8, we = bars + B_WEMPTY * 8;
#pragma unroll 1
            for (int n = 0; n < 5; n++) {
                if (n == 3) { mbar_spin(bars + B_XS * 8, 0); fence_async_smem(); }
                TR2(lane == 0, 70 + n)
                if (elect()) {
                    const uint32_t fb = wf + n * 8, dst = sb + OFF_W + n * 16384;
                    mbar_expect(fb, 20480);
#pragma unroll 1
                    for (int h = 0; h < 2; h++) {
                        const int kb = g1_block(2 * n + h, j);
                        tma_ld2(dst + h * 8192, &mp.w1, 64 * j, 64 * kb, fb);
                        bulk_ld(sb + OFF_REM + n * 4096 + h * 2048, &g_wr[(j * 10 + kb) * 128], 2048, fb);
                    }
                }
            }
            mbar_spin(bars + B_GATE * 8, 0);
#pragma unroll 1
            for (int i = -3; i < 5; i++) {
                const int n = i < 0 ? 8 + i : 5 + i;
                const uint32_t fb = wf + (n & 7) * 8;
                if (i >= 0) mbar_spin(we + i * 8, 0);
                TR2(lane == 0 && i >= 0, 70 + n)
                if (elect()) {
                    if (i < 0 || i >= 3) {
                        mbar_expect(fb, 20480);
#pragma unroll 1
                        for (int h = 0; h < 2; h++) tma_ld5(sb + OFF_W + (n & 7) * 16384 + h * 8192, n < 9 ? &mp.w2a : &mp.w2b, 64 * j, n < 9 ? 2 * g2_block(2 * n - 10 + h) : 4 * h, fb);
                    }
                    if (i >= 0) bulk_ld(sb + OFF_REM + i * 4096, &g_wr[((8 + j) * 10 + 2 * i) * 128], 4096, fb);
                }
            }
            mbar_spin(bars + (B_GATE + 1) * 8, 0);
#pragma unroll 1
            for (int n = 10; n < 30; n++) {
                if (n == W3_N2) mbar_spin(bars + (B_GATE + 2) * 8, 0);
                mbar_spin(we + (n & 7) * 8, ((n >> 3) & 1) ^ 1);
                TR2(lane == 0, 70 + n)
                if (elect()) {
                    const uint32_t dst = sb + OFF_W + (n & 7) * 16384, fb = wf + (n & 7) * 8;
                    mbar_expect(fb, 13824);
                    const int row = 64 * g3_block((n - 10) >> 1, j) + 32 * (n & 1);
                    tma_ld3(dst, &mp.w3a, 0, row, 3 * j, fb);
                    tma_ld2(dst + 12288, &mp.w3b, 1536 + 24 * j, row, fb);
                }
            }
            mbar_spin(we + 6 * 8, 0);
            mbar_spin(bars + B_VEC3 * 8, 0);
            if (elect()) { mbar_expect(wf + 6 * 8, 3456); bulk_ld(sb + OFF_W + 6 * 16384, &g_cs3b[216 * j], 3456, wf + 6 * 8); }
#pragma unroll 1
            for (int n = 31; n < 50; n++) {
                const int e = n < 38 ? 4 : (n - 38) & 3, m0 = n == 35, m1 = e == 3 ? -1 : m0 | (e == 1), rem = 96 + 3 * (j >> 1);
                const int c1_ = j ^ (n < 38 ? 6 : 4 >> ((n - 38) >> 2) & 6), c0_ = n < 38 ? 8 + (j & 1) : c1_;
                const int f = (0xC840A80C204ull >> (4 * min(n - 31, e + 7))) & 15;
                const int r0 = m0 ? rem : 6 * (j ^ (f >> 3)) + (f & 6), r1 = m1 ? rem : r0 + (n < 38 ? 0 : 2);
                mbar_spin(we + (n & 7) * 8, ((n >> 3) & 1) ^ 1);
                if (elect()) {
                    const uint32_t dst = sb + OFF_W + (n & 7) * 16384, fb = wf + (n & 7) * 8;
                    mbar_expect(fb, m1 < 0 ? 8192 : 16384 - 2048 * (m0 + m1));
                    tma_ld2(dst, &mp.w4[m0], 64 * c0_, r0 * (32 >> m0), fb);
                    if (m1 >= 0) tma_ld2(dst + 8192, &mp.w4[m1], 64 * c1_, r1 * (32 >> m1), fb);
                }
            }
        } else {
            {
                wait_cnt(&g_cnt.tab[0], 1);
                mbar_spin(bars + B_QRDY * 8, 0);
                if (elect()) {
                    mbar_expect(bars + B_TAB * 8, TAB_BYTES / 2 + VEC_BYTES);
                    bulk_ld(sb + OFF_TAB, g_tab + (j & 1) * (TAB_BYTES / 32), TAB_BYTES / 2, bars + B_TAB * 8);
                    bulk_ld(sb + M_GB, g_tab + (TAB_BYTES + j * VEC_BYTES) / 16, VEC_BYTES, bars + B_TAB * 8);
                }
                TS(lane == 0, 5)
            }
            wait_cnt(&g_cnt.uv[0], 4);
#pragma unroll 1
            for (int c = lane; c < 80; c += 32) {
                const float* src = g_uv + (c < 64 ? 64 * j + c : 448 + 16 * j + c);
                const uint32_t u = split2(ldcg32f(src) + ldcg32f(src + 3 * D_)), v = split2(ldcg32f(src + D_) + ldcg32f(src + 4 * D_));
                const uint32_t s = split2(ldcg32f(src + 2 * D_) + ldcg32f(src + 5 * D_));
                sts128(sb + OFF_F1 + c * 16, u, __byte_perm(u, v, 0x5410), __byte_perm(v, 0, 0x1032), s);
                sts128(sb + M_F1 + c * 16, s & 0xffffu, 0, 0, 0);
            }
            fence_async_smem();
            warp_arrive(bars + B_VEC * 8);
            TS(lane == 0, 9)
#pragma unroll 1
            for (int e = 1; e < 3; e++) {
                wait_cnt(e == 1 ? &g_cnt.g1[min(grp + 15 + min(lane, 2), 31) * 32] : &g_cnt.g2[(grp + 16) * 32], 32, true);
                if (elect()) mbar_arrive(bars + (B_GATE + 2 + e) * 8);
                TS(lane == 0, 27 + 2 * e)
            }
            wait_cnt(&g_cnt.cs2[0], 4);
            if (elect()) mbar_arrive(bars + B_VEC3 * 8);
            TS(lane == 0, 19)
        }
        return;
    }

    {
        uint32_t ep;
        {
            TIDS
            ep = ld_cold(&g_epoch);
            const int cp = (tid + 16) % 40, cp1 = tid % 40;
            const uint4 sh0 = ldg128(pp.shift_k + (80 * (id & 7) + 2 * cp1) * 4), sh1 = ldg128(pp.shift_k + (80 * (id & 7) + 2 * cp) * 4);
            uint32_t dd;
            asm volatile("ld.global.nc.u16 %0, [%1];" : "=r"(dd) : "l"(pp.ssm_D + 5 * id + min(wg + 3 * lane, 4)));
            TR4(lane == 0, 40 + warp)
            __syncthreads();
            asm volatile("barrier.cluster.arrive.relaxed.aligned;" ::: "memory");
            asm volatile("add.u32 %0, %0, 1;" : "+r"(ep));
#pragma unroll 1
            for (int hw = 0; hw < 2; hw++) {
                if ((unsigned)(warp - 2 * hw) >= 10) continue;
                const int u = tid - 64 * hw;
                const int c = hw ? cp : cp1, oc = u / 40, line = 31 - 16 * hw - (id >> 3);
                const uint4 sh = hw ? sh1 : sh0;
                const uint32_t st = sb + OFF_ST + hw * 10240, sta = st + c * 256 + ((((6 - 2 * (oc & 3)) ^ (oc >> 2) ^ (line & 1)) ^ (c & 7)) << 4), in = oc * 1280 + c * 4;
                const uint32_t f0 = __byte_perm(sh.x, sh.z, 0x5410), f1 = __byte_perm(sh.x, sh.z, 0x7632), f2 = __byte_perm(sh.y, sh.w, 0x5410), f3 = __byte_perm(sh.y, sh.w, 0x7632);
                uint32_t kk[11], vv[8];
                mbar_spin(bars + (B_IN + hw) * 8, 0);
                TS(tid == 64, 18 + 42 * hw)
#pragma unroll
                for (int i = 0; i < 11; i++) kk[i] = lds32(sb + OFF_KIN + hw * 10752 + in + i * 160);
#pragma unroll
                for (int i = 0; i < 8; i++) vv[i] = lds32(sb + OFF_VIN + hw * 10240 + in + i * 160);
#pragma unroll
                for (int i = 0; i < 8; i++) vv[i] = mul2(fma2(kk[i + 3], f0, fma2(kk[i + 2], f1, fma2(kk[i + 1], f2, mul2(kk[i], f3)))), vv[i]);
                sts128(sta, tag(__byte_perm(vv[0], vv[1], 0x5410), ep), __byte_perm(vv[2], vv[3], 0x5410), __byte_perm(vv[4], vv[5], 0x5410), __byte_perm(vv[6], vv[7], 0x5410));
                sts128(sta + 128, tag(__byte_perm(vv[0], vv[1], 0x7632), ep), __byte_perm(vv[2], vv[3], 0x7632), __byte_perm(vv[4], vv[5], 0x7632), __byte_perm(vv[6], vv[7], 0x7632));
                bar_sync(7 + hw, 320);
                flush_tile(st, g_kvT + (size_t)(80 * (id & 7)) * S_ + 64 * line, u);
                TS(tid == 64 && hw, 1)
            }
            warp_arrive(bars + B_KVS * 8);
            if (tid < 320) sts128(sb + OFF_CH + (tid >> 6) * CH_BYTES + 4096 + (tid & 63) * 16, 0, 0, 0, 0);
            mbar_spin(bars + B_SSM * 8, 0);
            TS(tid == 0, 14)
#pragma unroll 1
            for (int u0 = wg; u0 < 20; u0 += 12) {
                uint2 w[4];
                uint32_t pv[4];
#pragma unroll
                for (int i = 0; i < 4; i++) {
                    const uint32_t a = sb + OFF_SSM + min(u0 + 3 * i, 19) * 1024 + wt * 8;
                    w[i] = lds64(a); pv[i] = lds32(a - 4);
                }
#pragma unroll
                for (int i = 0; i < 4; i++) {
                    const int un = min(u0 + 3 * i, 19);
                    sts128(sb + OFF_CH + (un >> 2) * CH_BYTES + OFF_P + (un & 3) * 2048 + wt * 16, __byte_perm(w[i].x, pv[i], 0x7610), __byte_perm(w[i].x, 0, 0x1032), __byte_perm(w[i].y, w[i].x, 0x7610), __byte_perm(w[i].y, 0, 0x1032));
                }
            }
            __syncwarp();
            if (wt < 2 - (wg >> 1)) {
                const uint32_t h = lds32(sb + OFF_SSM + (wg + 3 * wt) * 4096), h0 = pack2(blo(h) + blo(dd), 0.f);
                sts64f(sb + OFF_CH + (wg + 3 * wt) * CH_BYTES + OFF_P, __uint_as_float(h0), __uint_as_float(__byte_perm(h, h0, 0x5432)));
            }
            fence_async_smem();
            warp_arrive(bars + B_BK * 8);
            asm volatile("barrier.cluster.wait.aligned;" ::: "memory");
            mbar_spin(bars + B_BK * 8, 0);
            TS(tid == 0, 15)
        }

#pragma unroll 1
        for (int c = wg; c < 5; c += 3) {
            const uint32_t kvb = sb + OFF_CH + c * CH_BYTES;
            mbar_spin(bars + (c < 3 ? B_RAW : B_RAW3) * 8, 0);
            for (uint32_t ph = 0; c < 3; ph ^= 1) {
                const int wt = tid_now() & 127;
                if (!RARE(bar_any(1 + wg, lop3<0x7E>(lds32(kvb + wt * 16), ep, lds32(kvb + 2048 + wt * 16)) & 1))) break;
                if (wt == 0) { mbar_expect(bars + (B_RETRY + wg) * 8, 4096); bulk_ld(kvb, g_kvT + (size_t)(5 * id + c) * S_, 4096, bars + (B_RETRY + wg) * 8); }
                mbar_spin(bars + (B_RETRY + wg) * 8, ph);
                STALE1(-8)
            }
            TS(threadIdx.x == 0, c ? 13 : 11)
            float acc[64];
            {
                const int l = tid_now() & 31;
                conv_channel(acc, kvb + OFF_P + (8 * (warp & 3) + (l >> 2) - 2 * (l & 3)) * 4, (((uint64_t)0xC0000010u << 32) | ((kvb & 0x3FFFF) >> 4) | 0x10000u) + pp.nil);
            }
            TS(threadIdx.x == 0, c ? 16 : 12)
            if (c < 3) warp_arrive(bars + B_R1 * 8);
            else mbar_spin(bars + B_R1 * 8, 0);
            if (wg == 2 && id < 120) {
                TIDS
                mbar_spin(bars + B_RAW3 * 8, 0);
                mbar_spin(bars + B_WM * 8, 0);
                TS(wt == 0, 56)
                float d[4];
                gemv_tile<8>(d, sb + OFF_WM, sb + OFF_Z, 0);
                const float d2 = __shfl_up_sync(~0u, d[2], 1);
                TS(wt == 0, 7)
                if (t < 2) asm volatile("{\n.reg .b64 v;\nmov.b64 v, {%1, %2};\nst.relaxed.gpu.global.b64 [%0], v;\n}" ::"l"(g_mod + (id & 1) * 6 * D_ + 64 * pr + 16 * (warp & 3) + g + 8 * t),
                                        "r"(__float_as_uint(t ? d2 : d[0])), "r"(lds32(sb + M_EP)) : "memory");
            }
            TR4(threadIdx.x == 0, 60 + (c >= 3) * 10)
            TIDS
            const int e = 127 - 8 * (lane >> 4) - (lane & 7), u0 = (warp & 3) + 8 * (e >> 2) + (e & 3) + 4 * ((lane >> 3) & 1);
            const uint32_t ring = sb + OFF_RING + c * 16384 + (warp & 3) * 4096, wa = ring + (u0 ^ ((u0 >> 1) & 4)) * 16;
            if (lane < (warp & 3)) sts128(ring + lane * 16, 0, 0, 0, 0);
#pragma unroll
            for (int i = 0; i < 8; i++)
                stsm4t(i == 0 && u0 >= 256 ? sb + M_SINK : wa - 512 * i, pack2(acc[8 * i], acc[8 * i + 1]), pack2(acc[8 * i + 2], acc[8 * i + 3]),
                       pack2(acc[8 * i + 4], acc[8 * i + 5]), pack2(acc[8 * i + 6], acc[8 * i + 7]));
            warp_arrive(bars + (B_RING + c) * 8);
            TR4(threadIdx.x == 0, 61 + (c >= 3) * 10)
        }
        TIDS
        if (wg == 2) bar_sync(3, 128);
        if (warp == 8) {
            wait_cnt(&g_cnt.q[(id & 3) * 32], 128, true);
            if (elect()) {
                mbar_expect(bars + B_QRDY * 8, 28672);
                tma_ld2(sb + OFF_QT, &mp.qT, 80 * id, 0, bars + B_QRDY * 8);
                bulk_ld(sb + OFF_QT + 20480, g_qst, 8192, bars + B_QRDY * 8);
            }
            TS(lane == 0, 8)
        } else if (warp == 9) {
            const int v = min(lane / 5, 3);
            const uint2* gm = g_mod + (v + (v == 3)) * D_ + 5 * id + lane % 5;
            const unsigned epoch = lds32(sb + M_EP);
            uint2 r0, r1;
            unsigned it = 0;
            do {
                r0 = ld_mod(gm); r1 = ld_mod(gm + 6 * D_);
                SPIN_CHECK(55)
            } while (!__all_sync(~0u, r0.y == epoch && r1.y == epoch));
            const float m0 = __uint_as_float(r0.x), m1 = __uint_as_float(r1.x);
            const float m = rbf(m0 + m1), p = rbf(1.f + m);
            const float cz = zscale(__shfl_sync(~0u, p, 15 + lane % 5)), ga = __shfl_sync(~0u, m, 10 + lane % 5);
            if (lane < 15) sts32(sb + M_AB + lane % 5 * 16 + v * 4, lane < 10 ? __float_as_uint(cz * ga * (lane < 5 ? m : p)) : pack2(cz, cz));
            warp_arrive(bars + B_MODR * 8);
            TS(lane == 0, 6)
        }
        mbar_spin(bars + B_QRDY * 8, 0);
        uint4 rs[2], nm[2];
#pragma unroll
        for (int h = 0; h < 2; h++) { rs[h] = lds128(sb + OFF_QT + 20480 + h * 2048 + wt * 16); nm[h] = lds128(sb + OFF_QT + 24576 + h * 2048 + wt * 16); }
        mbar_spin(bars + B_MODR * 8, 0);
        TR4(threadIdx.x == 0, 72)
        uint32_t it = 0;
        while (RARE(__any_sync(~0u, (lop3<0x7E>(rs[0].x, ep, rs[0].z) | lop3<0x7E>(nm[0].x, ep, nm[0].z) | lop3<0x7E>(rs[1].x, ep, rs[1].z) | lop3<0x7E>(nm[1].x, ep, nm[1].z)) & 1))) {
#pragma unroll
            for (int h = 0; h < 2; h++) { rs[h] = ld_part(g_qst + 1024 * h + 8 * wt); nm[h] = ld_part(g_qst + S_ + 1024 * h + 8 * wt); }
            STALE(1)
            SPIN_CHECK(53)
        }
        TR4(threadIdx.x == 0, 73)
#pragma unroll 1
        for (int c = wg == 2 ? 0 : 3 + wg; c < (wg == 2 ? 3 : 4 + wg); c++) {
            uint4 q[2], p[2][4];
#pragma unroll
            for (int h = 0; h < 2; h++) q[h] = lds128(sb + OFF_QT + h * 10240 + (wt >> 1) * 160 + c * 32 + (wt & 1) * 16);
            const float4 ab = lds128f(sb + M_AB + c * 16);
            mbar_spin(bars + (B_RING + c) * 8, 0);
            TR4(wt == 0, wg == 2 ? 80 + 2 * c : 74)
#pragma unroll
            for (int i = 0; i < 8; i++) p[i >> 2][i & 3] = lds128(sb + OFF_RING + c * 16384 + (i & 3) * 4096 + (i >> 2) * 2048 + (wt ^ ((wt >> 1) & 4)) * 16);
            while (RARE(__any_sync(~0u, lop3<0x7E>(q[0].x, ep, q[1].x) & 1))) {
#pragma unroll
                for (int h = 0; h < 2; h++) q[h] = ld_part(g_qT + ((64 * h + (wt >> 1)) * D_ + 5 * id + c) * 16 + 8 * (wt & 1));
                STALE(2)
                SPIN_CHECK(52)
            }
            TR4(wt == 0, wg == 2 ? 81 + 2 * c : 75)
#pragma unroll
            for (int h = 0; h < 2; h++) {
                const uint32_t qq[4] = {q[h].x, q[h].y, q[h].z, q[h].w}, r4[4] = {rs[h].x, rs[h].y, rs[h].z, rs[h].w}, n4[4] = {nm[h].x, nm[h].y, nm[h].z, nm[h].w};
                const uint4 y = add2(add2(p[h][0], p[h][1]), add2(p[h][2], p[h][3]));
                const uint32_t yy[4] = {y.x, y.y, y.z, y.w};
                uint32_t o[4];
#pragma unroll
                for (int i = 0; i < 4; i++) {
                    const uint32_t n = fma2(qq[i], r4[i], n4[i]);
                    o[i] = fma2(pack2(fmaf(blo(n), ab.y, ab.x), fmaf(bhi(n), ab.y, ab.x)), yy[i], mul2(qq[i], __float_as_uint(ab.z)));
                }
                stg128_tag(g_x1T + (size_t)(5 * id + c) * S_ + 1024 * h + 8 * wt, o[0], o[1], o[2], o[3], ep, ((5 * id + c) >> 3) & 3);
            }
        }
        warp_arrive(bars + B_XS * 8);
        TS(tid == 0, 17)
        TS(tid == 256, 52)
    }

    const uint32_t nil = pp.nil;
    const int wq = warp & 3;
    if (wg == 2) {
        TIDS
        asm volatile("setmaxnreg.dec.sync.aligned.u32 " STR(REG_AUX) ";");
        {
            const uint32_t ep = lds32(sb + M_EP);
            uint32_t ph = 0;
            const Tile tl = ring_tile(min(4 * lane + wq, 59), grp, j);
            const uint32_t plan = bars + (B_XFULL + 10 * tl.w + tl.kb) * 8;
#pragma unroll 1
            for (int m = wq - 4; m < 60; m += 4) {
                const int n = max(m, 0);
                const uint32_t pl = __shfl_sync(~0u, plan, n >> 2), at = __shfl_sync(~0u, tl.at, n >> 2);
                const int e = (n >= 20) + (n >= 40);
                const uint32_t a = sb + OFF_XR + (n & 7) * 8192;
                uint32_t ta = a + (e == 0 ? lane * 128 + ((lane & 7) << 4) + (lane >> 3) * 4
                                 : e == 1 ? (lane & 15) * 128 + (((lane >> 4 << 1) ^ (lane & 7)) << 4) + (lane & 8) + (lane >> 4) * 4
                                          : lane * 32 + (lane >> 2) * 4);
                uint32_t tb = e == 0 ? ta ^ 32 : ta + 2048, tc = e == 2 ? ta + 1024 : ta ^ 64, td = e == 2 ? tb + 1024 : tb ^ 64;
                uint32_t live = m >= 0 && m != 40 && m != 40 + XLEAD,
                    f0 = pl;
                uint32_t f1 = m == GATE_W2 || m == GATE_W3 || m == GATE_W3B ? bars + (B_GATE + (m >= GATE_W3) + (m >= GATE_W3B)) * 8 : 0;
                if (lane) f0 = f1;
                if (lane > 1 || m < 0) f0 = 0;
                asm volatile("" : "+r"(ta), "+r"(tb), "+r"(tc), "+r"(td), "+r"(live), "+r"(f0));
                mbar_spin(bars + (m < 0 ? B_BK : B_LAND + (n & 7)) * 8, (n >> 3) & 1);
                TR5(lane == 0, n)
                while (true) {
                    uint32_t v[8];
#pragma unroll
                    for (int i = 0; i < 8; i++) v[i] = lds32(((i & 2) ? ((i & 1) ? td : tc) : (i & 1) ? tb : ta) + (i >> 2) * 4096);
                    const uint32_t bad = lop3<0xFE>(lop3<0x7E>(v[0], ep, v[1]), lop3<0x7E>(v[2], ep, v[3]), lop3<0x7E>(v[4], ep, v[5]));
                    if (!RARE(__any_sync(~0u, lop3<0xA8>(bad, lop3<0x7E>(v[6], ep, v[7]), live)))) break;
                    if (elect()) load_tile(mp, a, e, at, bars + (B_AGAIN + wq) * 8);
                    mbar_spin(bars + (B_AGAIN + wq) * 8, ph);
                    ph ^= 1;
                    STALE1(e)
                }
                TR5(lane == 0, 60 + n)
                if (f0) mbar_arrive(f0);
            }
        }
        if (wq == 0) {
#pragma unroll 1
            for (int w = 0; w < 2; w++) {
                const uint4* src = g_part + (size_t)(grp + 16 * w) * 40960;
                TR4(lane == 0, 90 + 2 * w)
                mbar_wait(bars + (B_RING + w) * 8, 1);
                TR4(lane == 0, 91 + 2 * w)
                if (elect()) {
                    const uint32_t fb = bars + (B_IN + w) * 8, rem = sb + OFF_OUT + w * 10240;
                    mbar_expect(fb, 10240);
                    bulk_ld(rem + 8192, &g_x1f[((grp + 16 * w) * 8 + j) * 640 + 512], 2048, fb);
#pragma unroll 1
                    for (int i = 0; i < 4; i++) bulk_ld(rem + i * 2048, src + ((j >> 2) + 2 * i) * 5120 + 4096 + j * 128, 2048, fb);
                }
            }
        }
#pragma unroll 1
        for (int uw = 0; uw < 2; uw++) {
            const int tile = grp + 16 * uw;
            const uint32_t ep = lds32(sb + M_EP), in = sb + OFF_OUT + uw * 10240 + wt * 16, sr = in - lane * 16;
            mbar_wait(bars + (B_IN + uw) * 8, 1);
            TR4(wt == 0, 94 + 3 * uw)
            uint4 u[4];
#pragma unroll
            for (int i = 0; i < 4; i++) u[i] = lds128(in + i * 2048);
            const uint4 base = lds128(in + 8192);
            const uint32_t ra = sb + M_F1 + (64 * uw + 16 * wq + g) * 4;
            const uint4 gr = scale16(lds64f(sb + M_GB + (64 + 2 * t) * 4), lds64f(sb + M_GB + (72 + 2 * t) * 4), __uint_as_float(lds32(ra)), __uint_as_float(lds32(ra + 32)));
            uint32_t it = 0;
            while (RARE(__any_sync(~0u, stale4(u, ep) & 1))) {
                ld_part4(u, g_part + (size_t)tile * 40960 + (j >> 2) * 5120 + 4096 + j * 128 + wt, 10240);
                STALE(3)
                if (++it > SPIN_LIMIT) SPIN_FAIL(58)
            }
            TR4(wt == 0, 95 + 3 * uw)
            const uint4 r = fin16(add2(add2(u[0], u[1]), add2(u[2], u[3])), base, gr);
            __syncwarp();
            stsm4(sr + (lane & 15) * 32 + (((lane >> 4) ^ ((lane >> 2) & 1)) << 4), r.x, r.y, r.z, r.w);
            __syncwarp();
            stg128(out + (size_t)(64 * tile + 16 * wq + (lane >> 1)) * D_ + 512 + 16 * j + 8 * (lane & 1), lds128(sr + (lane >> 1) * 32 + (((lane & 1) ^ ((lane >> 3) & 1)) << 4)));
            TR4(wt == 0, 96 + 3 * uw)
            __syncwarp();
        }
        TS(wt == 0, 21)
        if (wq == 0) {
            uint32_t it = 0;
            while (!mbar_try(bars + B_OWN * 8, 0)) { if (++it > SPIN_LIMIT) SPIN_FAIL(56) }
        }
        return;
    }

    TIDS
    const int uw = wg, tile = grp + 16 * uw, row0 = 64 * tile + 16 * wq;
    const bool leader = wt == 0; (void)leader;
    const uint32_t xfull = bars + (B_XFULL + 10 * uw) * 8, xempty = bars + B_XEMPTY * 8, wfull = bars + B_WFULL * 8, wempty = bars + B_WEMPTY * 8;
    const uint64_t dz = mkdesc(0) + pp.nil;
    auto xwait = [&](uint32_t kb, uint32_t e) { mbar_spin(xfull + kb * 8, e & 1); };
    asm volatile("setmaxnreg.inc.sync.aligned.u32 " STR(REG_MMA) ";");
    const uint32_t ep = lds32(sb + M_EP);
    uint32_t x2[20];
    uint32_t res[20] = {};
    {
        float acc[40];
        const uint32_t la = ((lane & 7) + 8 * (lane >> 4)) * 128 + (((2 * wq + ((lane >> 3) & 1)) ^ (lane & 7)) << 4);
        auto pos = [&](int n) { return ring_pos(uw, n, LEAD1) & 7; };
        auto slot = [&](int n) { return sb + OFF_XR + pos(n) * 8192; };
        float al[2], r1[2], n1[2];
        {
            float sl[4], sq[4], v[4];
            uint32_t z0[16], z1[16], zz[16];
            uint64_t bd = dz + b80_desc(dsb, 0, 0, 0), tb = (((uint64_t)8 << 32) | ((dsb + OFF_TAB) >> 4) | (7u << 16)) + pp.nil;
            auto ldfrag = [&](uint32_t (&z)[16], int n) {
#pragma unroll
                for (int q = 0; q < 4; q++) ldsm4t(slot(n) + la + q * 2048, z[4 * q], z[4 * q + 1], z[4 * q + 2], z[4 * q + 3]);
            };
            auto tile1 = [&](const uint32_t (&zc)[16], uint32_t (&zn)[16], int n, int h) {
                const bool last = h && n == 5, ok = mbar_test(xfull + (n + 1) * 8, 0), okw = !h || mbar_test(wfull + ((n + 1) >> 1) * 8, 0);
                const int kb = g1_block(n, j);
                wg_fence();
#pragma unroll
                for (int q = 0; q < 2; q++) wgmma_rs80(acc, zc[4 * q], zc[4 * q + 1], zc[4 * q + 2], zc[4 * q + 3], bd + q * B80_STEP, 1);
                wg_commit();
                wg_wait<1>();
                if (!ok) xwait(n + 1, 0);
                if (!last) ldfrag(zn, n + 1);
#pragma unroll
                for (int e = 0; e < 16; e++) zz[e] = mul2(zc[e], zc[e]);
                const uint64_t t0 = last ? ((uint64_t)8 << 32) | ((dsb + M_NUL) >> 4) : tb;
                const uint32_t ts = last ? 0 : 14;
                wg_fence();
#pragma unroll
                for (int q = 0; q < 4; q++) wgmma_rs8(sl, zc[4 * q], zc[4 * q + 1], zc[4 * q + 2], zc[4 * q + 3], t0 + q * ts, 1);
#pragma unroll
                for (int q = 0; q < 4; q++) wgmma_rs8(sq, zz[4 * q], zz[4 * q + 1], zz[4 * q + 2], zz[4 * q + 3], t0 + q * ts, 1);
#pragma unroll
                for (int q = 2; q < 4; q++) wgmma_rs80(acc, zc[4 * q], zc[4 * q + 1], zc[4 * q + 2], zc[4 * q + 3], bd + q * B80_STEP, 1);
                wg_commit();
#pragma unroll
                for (int q = 0; q < 4; q++) ldsm4t_if(kb == j, slot(n) + la + q * 2048, &res[4 * q]);
                if (!h) ldsm4t_if(kb == 8 + (j >> 2), slot(n) + la + (j & 3) * 2048, &res[16]);
                if (lane < 2) mbar_arrive_after(xempty + pos(n) * 8, res[12], res[16], nil);
                if (!h && n && lane == 0) mbar_arrive(wempty + ((n >> 1) - 1) * 8);
                tb += 56;
                bd = bd + (uint64_t)B80_HALF;
                if (!okw) mbar_spin(wfull + ((n + 1) >> 1) * 8, 0);
                TR(leader, 100 + 10 * uw + n)
            };
            zero(acc); zero(sl); zero(sq);
            mbar_spin(bars + B_TAB * 8, 0);
            float4 k = lds128f(sb + M_KS);
            float k4 = __uint_as_float(lds32(sb + M_KS + 16));
#pragma unroll
            for (int w = 1; w < 5; w++) {
                const float4 o = lds128f(sb + M_KS + w * 32);
                k.x += o.x; k.y += o.y; k.z += o.z; k.w += o.w; k4 += __uint_as_float(lds32(sb + M_KS + w * 32 + 16));
            }
            uint32_t fa[4];
            auto coefs = [&]() {
                mbar_spin(bars + (B_SUMS + uw) * 8, 0);
                TS(leader && !uw, 10)
                const float4 o = lds128f(sb + OFF_ROW + uw * 2048 + wt * 16);
                v[0] += o.x; v[1] += o.y; v[2] += o.z; v[3] += o.w;
#pragma unroll
                for (int h = 0; h < 2; h++) {
                    const int l0 = lane & ~3;
                    const float s1 = __shfl_sync(~0u, v[2 * h], l0), s2 = __shfl_sync(~0u, v[2 * h], l0 + 1), scc = __shfl_sync(~0u, v[2 * h], l0 + 2);
                    const float scs = __shfl_sync(~0u, v[2 * h + 1], l0 + 2), sc = __shfl_sync(~0u, v[2 * h], l0 + 3), sqq = __shfl_sync(~0u, v[2 * h + 1], l0 + 3);
                    const float m1 = s1 * (1.f / D_), va = fmaxf(s2 * (1.f / D_) - m1 * m1, 0.f) + 1e-5f, r = rsqrtf(va);
                    const float m2 = (r * (sc - m1 * k.x) + k.y) * (1.f / D_);
                    const float e2 = (r * (r * (sqq + m1 * (m1 * k.z - 2.f * scc)) + 2.f * (scs - m1 * k.w)) + k4) * (1.f / D_);
                    al[h] = r * 0.5f * rsqrtf(fmaxf(e2 - m2 * m2, 0.f) + 1e-5f); r1[h] = r; n1[h] = -m1 * r;
                    const uint32_t fb = split2(va * r), fx = split2(t == 3 ? -m2 * va * r : -m1), fc = __shfl_sync(~0u, fx, lane | 3);
                    fa[h] = __byte_perm(fx, fb, t == 1 ? 0x5432 : t == 2 ? 0x7654 : 0x1010);
                    fa[2 + h] = t ? 0 : fc >> 16;
                }
            };
            mbar_spin(wfull, 0);
            xwait(0, 0);
            TS(leader, 32 + uw)
            ldfrag(z0, 0);
#pragma unroll 1
            for (int n = 0; n < 6; n += 2) { tile1(z0, z1, n, 0); tile1(z1, z0, n + 1, 1); }
#pragma unroll
            for (int n = 6; n < 10; n++) {
                const uint64_t ad = dz + (((dsb + OFF_XR + pos(n) * 8192) >> 4) | 0x10000u);
                const bool ok = n == 9 || mbar_test(xfull + (n + 1) * 8, 0), okw = n != 7 || mbar_test(wfull + 4 * 8, 0);
                wg_fence();
#pragma unroll
                for (int q = 0; q < 4; q++) wgmma_ss80t(acc, ad + q * 128, bd + q * B80_STEP, 1);
                wg_commit();
                bd = bd + (uint64_t)B80_HALF;
                if (n == COEF_AT) coefs();
                if (n == 9) ldsm4t_if(9 - (j & 1) == 8 + (j >> 2), slot(9) + la + (j & 3) * 2048, &res[16]);
                wg_wait<1>();
                if (n > 6 && lane < 2) mbar_arrive(xempty + pos(n - 1) * 8);
                if (!(n & 1) && lane == 0) mbar_arrive(wempty + ((n >> 1) - 1) * 8);
                if (n == 6) {
                    reg_fence(sl); reg_fence(sq);
#pragma unroll
                    for (int e = 0; e < 2; e++) {
                        v[2 * e] = t == 0 ? sl[2 * e] + sl[2 * e + 1] : t == 1 ? sq[2 * e] + sq[2 * e + 1] : sl[2 * e];
                        v[2 * e + 1] = t == 2 ? sl[2 * e + 1] : sq[2 * e];
                    }
                    st_peer(peer_addr(sb + OFF_ROW + uw * 2048 + wt * 16), __float_as_uint(v[0]), __float_as_uint(v[1]), __float_as_uint(v[2]), __float_as_uint(v[3]), peer_addr(bars + (B_SUMS + uw) * 8));
                    TS(leader && !uw, 59)
                }
                if (!ok) xwait(n + 1, 0);
                if (!okw) mbar_spin(wfull + 4 * 8, 0);
                TR(leader, 100 + 10 * uw + n)
            }
            if (COEF_AT == 10) coefs();
            mbar_spin(bars + B_VEC * 8, 0);
            wg_fence();
            wgmma_rs80k(acc, fa[0], fa[1], fa[2], fa[3], ((uint64_t)8 << 32) | ((dsb + OFF_F1) >> 4) | (((M_F1 - OFF_F1) >> 4) << 16), 1);
            wg_commit();
        }
        wg_wait<0>();
        reg_fence(acc);
        if (lane < 2) mbar_arrive_after(xempty + pos(9) * 8, res[16], 0, nil);
        if (lane == 0) mbar_arrive(wempty + 4 * 8);
        TS(leader, 34 + uw)
        {
            bf16* const trow = g_t + (size_t)(row0 + g + 2) * D_;
#pragma unroll
            for (int b = 0; b < 3; b++) {
                uint32_t p[8];
#pragma unroll
                for (int ii = 0; ii < 4; ii++) {
                    const int i = 4 * b + ii;
                    if (i >= 10) continue;
#pragma unroll
                    for (int h = 0; h < 2; h++) p[(i & 3) + 4 * h] = pack2(gelu2(acc[4 * i + 2 * h] * al[h]), gelu2(acc[4 * i + 2 * h + 1] * al[h]));
                }
                if (b < 2) {
                    const int gr = (2 * j + b) / 5, sh = (gr & 1) ? -1 - (gr >> 1) : 1 + (gr >> 1);
                    bf16* dst = trow + 64 * j + 32 * b + 8 * t;
                    const int w = (((g + sh) >> 2) & 2) + (t >> 1);
                    stg128_tag(dst + sh * D_, p[0], p[1], p[2], p[3], ep, w);
                    stg128_tag(dst + (sh + 8) * D_, p[4], p[5], p[6], p[7], ep, w ^ 2);
                    if (row0 + g < sh || row0 + g + 8 >= S_ + sh) stg128_tag(dst + (sh > 0 ? 0 : 8) * D_, 0, 0, 0, 0, ep, (sh > 0 ? 0 : 2) + (t >> 1));
                } else {
                    bf16* dst = trow + 512 + 16 * j + 4 * t;
                    const uint32_t lo = t == (g < 2), hi = t == (g >= 2), o = j & 1;
                    stg64(dst - 2 * D_, lop3<0xB8>(p[0], lo & ~o, ep), lop3<0xB8>(p[1], lo & o, ep));
                    stg64(dst + 6 * D_, lop3<0xB8>(p[4], hi & ~o, ep), lop3<0xB8>(p[5], hi & o, ep));
                    if (row0 + g + 8 >= S_ - 2) stg64(dst + 8 * D_, ep & (t == 1) & ~o, ep & (t == 1) & o);
                }
            }
        }
        signal_cnt(&g_cnt.g1[tile * 32], lane, 1, true);
        TS(leader, 36 + uw)
#pragma unroll
        for (int i = 0; i < 10; i++) {
            const float2 c = lds64f(sb + M_C + (8 * i + 2 * t) * 4), s = lds64f(sb + M_SB + (8 * i + 2 * t) * 4);
#pragma unroll
            for (int h = 0; h < 2; h++) {
                acc[4 * i + 2 * h] = fmaf(blo(res[2 * i + h]), r1[h], fmaf(n1[h], c.x, s.x));
                acc[4 * i + 2 * h + 1] = fmaf(bhi(res[2 * i + h]), r1[h], fmaf(n1[h], c.y, s.y));
            }
        }
        mbar_spin(wfull + 5 * 8, 0);
        xwait(0, 1);
        TS(leader, 22 + uw)
        uint32_t ps = uw ? P1S : P0S, xo = (ps & 3) * 16, xp = 0;
        const uint64_t ax = dz + (((dsb + OFF_XR) >> 4) | 0x10000u);
        uint64_t ad = ax + xo * 64, bd = dz + b80_desc(dsb, 5, 0, 0);
#pragma unroll 1
        for (int i = 0; i < 5; i++) {
            const uint32_t x1 = xfull + (1 + 2 * i) * 8, p1 = 1, x2 = xfull + min(2 + 2 * i, 9) * 8, p2 = 1;
            const uint32_t w2 = wfull + (min(6 + i, 9) & 7) * 8, pw = i >= 2;
            const bool ok1 = mbar_test(x1, p1);
            wg_fence();
#pragma unroll
            for (int q = 0; q < 4; q++) wgmma_ss80(acc, ad + q * 2, bd + q * B80_STEP, 1);
            wg_commit();
            wg_wait<1>();
            if (lane < 2 && i) mbar_arrive(xempty + xp);
            if (lane == 0 && i) mbar_arrive(wempty + ((4 + i) & 7) * 8);
            if (!ok1) mbar_spin(x1, p1);
            const bool ok2 = mbar_test(x2, p2), okw = mbar_test(w2, pw);
            wg_fence();
#pragma unroll
            for (int q = 0; q < 4; q++) wgmma_ss80(acc, ad + 512 + q * 2, bd + B80_HALF + q * B80_STEP, 1);
            wg_commit();
            const uint32_t xc = xo;
            ps >>= 2;
            xp = xo + 8; xo = (ps & 3) * 16;
            ad = ax + xo * 64;
            bd += i == 2 ? 2 * B80_HALF - 8192 + (8192ll << 16) : 2 * B80_HALF;
            asm volatile("" : "+l"(ad), "+l"(bd));
            wg_wait<1>();
            if (lane < 2) mbar_arrive(xempty + xc);
            if (!ok2) mbar_spin(x2, p2);
            if (!okw) mbar_spin(w2, pw);
            TR(leader, (uw ? 86 : 20) + 2 * i)
        }
        wg_wait<0>();
        reg_fence(acc);
        if (lane < 2) mbar_arrive(xempty + xp);
        if (lane == 0) mbar_arrive(wempty + (9 & 7) * 8);
        TS(leader, 38 + uw)
        float a0 = 0.f, b0 = 0.f, a1 = 0.f, b1 = 0.f;
#pragma unroll
        for (int i = 0; i < 5; i++) {
            uint32_t* p = &x2[4 * i];
#pragma unroll
            for (int e = 0; e < 4; e++) p[e] = pack2(acc[8 * i + 2 * e], acc[8 * i + 2 * e + 1]);
#pragma unroll
            for (int e = 0; e < 4; e++) p[e] = lop3<0xB8>(p[e], (((wt >> 3) ^ (wt << 2)) & 7) == e, ep);
            stg128(&g_x2f[(tile * 40 + (i < 4 ? 4 * j + i : 32 + j)) * 128 + wt], p[0], p[1], p[2], p[3]);
#pragma unroll
            for (int e = 0; e < 8; e += 4) {
                const float* u = &acc[8 * i + e];
                a0 += u[0] + u[1]; b0 = fmaf(u[0], u[0], fmaf(u[1], u[1], b0));
                a1 += u[2] + u[3]; b1 = fmaf(u[2], u[2], fmaf(u[3], u[3], b1));
            }
        }
#pragma unroll
        for (int o = 1; o < 4; o *= 2) {
            a0 += __shfl_xor_sync(~0u, a0, o); b0 += __shfl_xor_sync(~0u, b0, o);
            a1 += __shfl_xor_sync(~0u, a1, o); b1 += __shfl_xor_sync(~0u, b1, o);
        }
        if (t < 2) stg64(&g_stats[(tile * 8 + j) * 64 + 16 * wq + g + 8 * t], tag(__float_as_uint(t ? a1 : a0), ep), __float_as_uint(t ? b1 : b0));
        signal_cnt(&g_cnt.g2[tile * 32], lane, 1, true);
        TS(leader, 40 + uw)
#pragma unroll
        for (int i = 0; i < 10; i++) {
            const float2 c = lds64f(sb + M_GB + (8 * i + 2 * t) * 4), e = lds64f(sb + M_CI + (8 * i + 2 * t) * 4);
#pragma unroll
            for (int h = 0; h < 2; h++)
                res[2 * i + h] = fma2(pack2(c.x, c.y), x2[2 * i + h], pack2(e.x * blo(res[2 * i + h]), e.y * bhi(res[2 * i + h])));
        }
#pragma unroll
        for (int i = 0; i < 20; i++) asm volatile("" : "+r"(res[i]));
    }
    float acc0[64], acc1[44];
    float2 q[4];
    {
        uint4 f0, f1, f2, f3;
        auto xseq = [&](int kb) { return ring_pos(uw, kb, XLEAD) & 7; };
        auto step = [&](const uint4& f, uint64_t bd) {
            wg_fence();
            wgmma_rs128(acc0, f.x, f.y, f.z, f.w, bd, 1);
            wgmma_rs88(acc1, f.x, f.y, f.z, f.w, bd + 512, 1);
            wg_commit();
        };
        const uint32_t xa = sb + OFF_XR + wt * 16;
        const float2* const gs = &g_stats[(tile * 8 + 2 * t) * 64 + 16 * wq + g];
        zero(acc0); zero(acc1);
        uint32_t xs = 0;
        f0 = make_uint4(x2[0], x2[1], x2[2], x2[3]); f1 = make_uint4(x2[4], x2[5], x2[6], x2[7]);
        f2 = make_uint4(x2[8], x2[9], x2[10], x2[11]); f3 = make_uint4(x2[12], x2[13], x2[14], x2[15]);
#pragma unroll
        for (int i = 0; i < 4; i++) q[i] = make_float2(0.f, 0.f);
        mbar_spin(wempty + (9 & 7) * 8, 1);
        mbar_spin(wfull + (10 & 7) * 8, (10 >> 3) & 1);
#pragma unroll 1
        for (int kb = 0; kb < 10; kb++) {
            const uint32_t wn = 10 + 2 * kb;
            const uint64_t bd = dz + (((dsb + OFF_W + (wn & 7) * 16384) >> 4) | (256u << 16));
            step(f0, bd);
            wg_wait<1>();
            if (kb && lane == 0) mbar_arrive(wempty + ((wn - 1) & 7) * 8);
            lds128_if(kb, f2, xa + xs * 8192 + 4096); lds128_if(kb, f3, xa + xs * 8192 + 6144);
            const bool w1 = mbar_test(wfull + ((wn + 1) & 7) * 8, (wn >> 3) & 1), x1 = kb < 9 && mbar_test(xfull + (kb + 1) * 8, 0);
            step(f1, bd + 128);
            if (!w1) mbar_spin(wfull + ((wn + 1) & 7) * 8, (wn >> 3) & 1);
            step(f2, bd + 1024);
            if (lane < 2 && kb) mbar_arrive_after(xempty + xs * 8, f2.x, f3.x, nil);
            wg_wait<1>();
            if (lane == 0) mbar_arrive(wempty + (wn & 7) * 8);
            xs = xseq(kb + 1);
            if (x1) { f0 = lds128(xa + xs * 8192); f1 = lds128(xa + xs * 8192 + 2048); }
            const bool w2 = mbar_test(wfull + ((wn + 2) & 7) * 8, ((wn + 2) >> 3) & 1);
            step(f3, bd + 1152);
            if (kb < 9 && !x1) { xwait(kb + 1, 2); f0 = lds128(xa + xs * 8192); f1 = lds128(xa + xs * 8192 + 2048); }
            if (!w2) mbar_spin(wfull + ((wn + 2) & 7) * 8, ((wn + 2) >> 3) & 1);
            if (kb == 0) {
                TS(leader, 42 + uw)
#pragma unroll
                for (int i = 0; i < 4; i++) q[i] = ld_stat(gs + (i & 1) * 64 + 8 * (i >> 1));
            }
            if (kb == 4) {
                uint32_t it = 0;
                while (RARE(__any_sync(~0u, ((__float_as_uint(q[0].x) ^ ep) | (__float_as_uint(q[1].x) ^ ep) | (__float_as_uint(q[2].x) ^ ep) | (__float_as_uint(q[3].x) ^ ep)) & 1))) {
#pragma unroll
                    for (int i = 0; i < 4; i++) q[i] = ld_stat(gs + (i & 1) * 64 + 8 * (i >> 1));
                    SPIN_CHECK(49)
                }
                float a0 = q[0].x + q[1].x, b0 = q[0].y + q[1].y, a1 = q[2].x + q[3].x, b1 = q[2].y + q[3].y;
#pragma unroll
                for (int o = 1; o < 4; o *= 2) {
                    a0 += __shfl_xor_sync(~0u, a0, o); b0 += __shfl_xor_sync(~0u, b0, o);
                    a1 += __shfl_xor_sync(~0u, a1, o); b1 += __shfl_xor_sync(~0u, b1, o);
                }
                a0 *= 1.f / D_; a1 *= 1.f / D_;
                const float r0 = 0.5f * rsqrtf(fmaxf(b0 * (1.f / D_) - a0 * a0, 0.f) + 1e-5f), r1 = 0.5f * rsqrtf(fmaxf(b1 * (1.f / D_) - a1 * a1, 0.f) + 1e-5f);
                const uint32_t sel = t == 0 ? 0x1010 : t == 1 ? 0x4432 : 0x4444;
                if (t == 0) { sts32(sb + M_F1 + (64 * uw + 16 * wq + g) * 4, __float_as_uint(r0)); sts32(sb + M_F1 + (64 * uw + 16 * wq + g + 8) * 4, __float_as_uint(r1)); }
                q[2] = make_float2(8.f * 0.0356774081f * r0 * r0 * r0, 2.f * 0.7978845608f * r0);
                q[3] = make_float2(8.f * 0.0356774081f * r1 * r1 * r1, 2.f * 0.7978845608f * r1);
                q[1] = make_float2(__uint_as_float(__byte_perm(split2(-a0), 0, sel)), __uint_as_float(__byte_perm(split2(-a1), 0, sel)));
            }
            if (kb == 6) {
#pragma unroll
                for (int i = 0; i < 5; i++) stg128(&g_x1f[(tile * 8 + j) * 640 + i * 128 + wt], res[4 * i], res[4 * i + 1], res[4 * i + 2], res[4 * i + 3]);
            }
            if (kb == 8) asm volatile("fence.proxy.async.global;" ::: "memory");
            TR(leader, 10 * uw + kb)
        }
        const uint64_t fd = ((uint64_t)8 << 32) | ((dsb + OFF_W + 6 * 16384) >> 4);
        wg_fence();
        wgmma_rs128k(acc0, __float_as_uint(q[1].x), __float_as_uint(q[1].y), 0, 0, fd, 1);
        wgmma_rs88k(acc1, __float_as_uint(q[1].x), __float_as_uint(q[1].y), 0, 0, fd + 128, 1);
        wg_commit();
        if (lane == 0) {
            mbar_arrive(bars + B_XFREE * 8);
            asm volatile("mbarrier.arrive.shared::cluster.b64 _, [%0];" ::"r"(peer_addr(bars + B_XFREE * 8)) : "memory");
        }
    }
    const uint32_t recv = sb + recv_off(uw) + wt * 16;
    uint32_t ha[48] = {}, hb[48], hx[12];
    uint64_t wb = dz + (((dsb + OFF_W) >> 4) | (512u << 16));
    auto wdesc = [&](int n) { return wb + (n & 7) * 1024; };
    auto wwait = [&](int n) { mbar_spin(wfull + (n & 7) * 8, (n >> 3) & 1); };
    auto wfree = [&](int n) { if (lane == 0) mbar_arrive(wempty + (n & 7) * 8); };
    auto fresh = [&]() { wb += pp.nil; asm volatile("" : "+l"(wb)); };
    uint32_t pk[32];
    {
        float P0[64];
        const float2 r0 = q[2], r1 = q[3];
        const uint32_t ra = peer_addr(recv), rb = peer_addr(bars + (B_RECV + 4 * uw) * 8);
        auto conv32 = [&](const float* v, int b) {
#pragma unroll
            for (int i = 0; i < 4; i++) {
                ha[8 * b + 2 * i] = pack2(gelu2r(v[4 * i], r0), gelu2r(v[4 * i + 1], r0));
                ha[8 * b + 2 * i + 1] = pack2(gelu2r(v[4 * i + 2], r1), gelu2r(v[4 * i + 3], r1));
            }
#pragma unroll
            for (int s = 2 * b; s < 2 * b + 2; s++) st_peer(ra + s * 2048, ha[4 * s], ha[4 * s + 1], ha[4 * s + 2], ha[4 * s + 3], rb + (b >> 1) * 8);
        };
        auto fetch = [&](int k) {
            mbar_spin(bars + (B_RECV + 4 * uw + k) * 8, 0);
#pragma unroll
            for (int s = 4 * k; s < 4 * k + 4; s++) { const uint4 x = lds128(recv + s * 2048); hb[4 * s] = x.x; hb[4 * s + 1] = x.y; hb[4 * s + 2] = x.z; hb[4 * s + 3] = x.w; }
        };
        auto stage = [&](int n, const uint32_t* a, int steps, int sc) {
            wwait(n);
            wg_fence();
#pragma unroll
            for (int s = 0; s < steps; s++) wgmma_rs128(P0, a[4 * s], a[4 * s + 1], a[4 * s + 2], a[4 * s + 3], wdesc(n) + s * 128, sc || s);
            wg_commit();
        };
        wg_wait<0>();
        reg_fence(acc0); reg_fence(acc1);
        wfree(29); wfree(30);
        TS(leader, 44 + uw)
        uint32_t hr[6];
#pragma unroll
        for (int i = 0; i < 6; i++) {
            const float2 r = (i & 1) ? r1 : r0;
            hr[i] = pack2(gelu2r(acc1[32 + 2 * i], r), gelu2r(acc1[33 + 2 * i], r));
        }
        if (uw) mbar_spin(bars + B_XFREE * 8, 0);
        st_peer(ra + 24576, hr[0], hr[1], hr[2], hr[3], rb + 24);
        asm volatile("st.async.shared::cluster.mbarrier::complete_tx::bytes.v2.b32 [%0], {%1, %2}, [%3];" ::"r"(ra + 26624 - wt * 8), "r"(hr[4]), "r"(hr[5]), "r"(rb + 24) : "memory");
        conv32(&acc1[0], 4);
        conv32(&acc1[16], 5);
        TS(leader, 46 + uw)
        stage(31, &ha[32], 4, 0);
#pragma unroll
        for (int b = 0; b < 4; b++) {
            conv32(&acc0[16 * b], b);
            if (b == 3) {
                fetch(2);
                mbar_spin(bars + (B_RECV + 4 * uw + 3) * 8, 0);
                const uint4 x = lds128(recv + 24576);
                const uint2 y = lds64(recv + 26624 - wt * 8);
                const uint32_t hp[6] = {x.x, x.y, x.z, x.w, y.x, y.y};
#pragma unroll
                for (int i = 0; i < 6; i++) { hx[i] = (j & 1) ? hp[i] : hr[i]; hx[6 + i] = (j & 1) ? hr[i] : hp[i]; }
            }
            if (!(b & 1)) wwait(32 + (b >> 1));
            wg_fence();
#pragma unroll
            for (int s = 0; s < 2; s++) wgmma_rs128(P0, ha[8 * b + 4 * s], ha[8 * b + 4 * s + 1], ha[8 * b + 4 * s + 2], ha[8 * b + 4 * s + 3], wdesc(32 + (b >> 1)) + (2 * (b & 1) + s) * 128, 1);
            wg_commit();
            if (!(b & 1)) { wg_wait<1>(); wfree(31 + (b >> 1)); }
        }
        TR(leader, 64 + 10 * uw)
        fresh();
        stage(34, &hb[32], 4, 1); wg_wait<1>(); wfree(33);
        fetch(0);
        stage(35, hx, 3, 1); wg_wait<1>(); wfree(34);
        fetch(1);
        stage(36, &hb[0], 4, 1); wg_wait<1>(); wfree(35);
        stage(37, &hb[16], 4, 1); wg_wait<1>(); wfree(36);
        wg_wait<0>();
        reg_fence(P0);
        pack_part<64>(pk, P0, ep);
        uint32_t all = 0;
#pragma unroll
        for (int i = 0; i < 32; i++) all |= pk[i];
        if (lane == 0) mbar_arrive_after(wempty + (37 & 7) * 8, all, 0, nil);
        TR(leader, 65 + 10 * uw)
    }
    {
        uint4* const dst = g_part + (size_t)(tile * 8 + j) * 5120 + wt;
        const uint4* const src = g_part + (size_t)tile * 40960 + j * 512 + wt;
        float F[2][32];
        uint4 gb[4];
        float rr[2];
        float2 gf[8];
        uint4 base[4], u1[4], u2[4], u3[4];
#pragma unroll
        for (int c = 2; c < 5; c++) {
            float (&P)[32] = F[c & 1];
            fresh();
#pragma unroll
            for (int s = 0; s < 27; s++) {
                const int e = s < 8 ? 0 : s < 15 ? 1 : s < 23 ? 2 : 3, o = s - (e == 0 ? 0 : e == 1 ? 8 : e == 2 ? 15 : 23), n = 30 + 4 * c + e;
                const uint32_t* a = s < 12 ? &ha[4 * s] : s < 15 ? &hx[4 * (s - 12)] : &hb[4 * (s - 15)];
                if (o == 0) wwait(n);
                if (o == 0 || s == 1) wg_fence();
                wgmma_rs64(P, a[0], a[1], a[2], a[3], wdesc(n) + o * 128, s);
                if (o == 0) { wg_commit(); wg_wait<1>(); if (c > 2 || s) wfree(n - 1); }
                if (s == 0 && c > 2) { reg_fence(F[~c & 1]); pack_part<32>(pk, F[~c & 1], ep); }
                if (c == 2 && s % 3 == 0 && s < 24) st_part(dst + g4_block(s / 12, j) * 512 + (s / 3 & 3) * 128, &pk[4 * (s / 3)]);
                if (c == 3 && s % 4 == 1 && s < 16) st_part(dst + g4_block(2, j) * 512 + s / 4 * 128, &pk[4 * (s / 4)]);
                if (c == 4 && s % ST3 == 0 && s < 4 * ST3) st_part(dst + g4_block(3, j) * 512 + s / ST3 * 128, &pk[4 * (s / ST3)]);
                if (c == 4 && s >= 4 && s < 8) base[s - 4] = ldcg128(&g_x1f[(tile * 8 + j) * 640 + (s - 4) * 128 + wt]);
                if (c == 4 && s >= 19 && s < 23) { gf[2 * s - 38] = lds64f(sb + M_GB + (16 * (s - 19) + 2 * t) * 4); gf[2 * s - 37] = lds64f(sb + M_GB + (16 * (s - 19) + 8 + 2 * t) * 4); }
                if (c == 4 && s >= 12 && s < 14) rr[s - 12] = __uint_as_float(lds32(sb + M_F1 + (64 * uw + 16 * wq + g + 8 * (s - 12)) * 4));
                if (c == 4 && s >= 8 && s < 12) u1[s - 8] = ld_part(src + (j ^ 6) * 5120 + (s - 8) * 128);
                if (c == 4 && s >= 15 && s < 19) u2[s - 15] = ld_part(src + (j ^ 4) * 5120 + (s - 15) * 128);
                if (c == 4 && s >= LD3 && s < LD3 + 4) u3[s - LD3] = ld_part(src + (j ^ 2) * 5120 + (s - LD3) * 128);
                if (27 * (c - 2) + s == R_GATE && lane == 0) mbar_arrive(bars + (B_RING + uw) * 8);
                if (s == 7 || s == 14 || s == 22 || s == 26) wg_commit();
                if (c == 4) { TR(leader && s == 7, 68 + 10 * uw) TR(leader && s == 14, 69 + 10 * uw) TR(leader && s == 22, 70 + 10 * uw) }
            }
            TR(leader, 64 + c + (c == 4 ? 3 : 0) + 10 * uw)
        }
        float (&O)[32] = F[0];
#pragma unroll
        for (int i = 0; i < 4; i++) if (LD3 + i > 26) u3[i] = ld_part(src + (j ^ 2) * 5120 + i * 128);
#pragma unroll
        for (int i = 0; i < 4; i++) gb[i] = scale16(gf[2 * i], gf[2 * i + 1], rr[0], rr[1]);
        uint32_t it = 0;
        while (__any_sync(~0u, (stale4(u1, ep) | stale4(u2, ep) | stale4(u3, ep)) & 1)) {
            ld_part4(u1, src + (j ^ 6) * 5120, 128); ld_part4(u2, src + (j ^ 4) * 5120, 128); ld_part4(u3, src + (j ^ 2) * 5120, 128);
            STALE(6)
            SPIN_CHECK(58)
        }
        TR(leader, 73 + 10 * uw)
#pragma unroll
        for (int i = 0; i < 4; i++) u1[i] = add2(add2(u1[i], u2[i]), u3[i]);
        TS(leader, 50 + uw)
        wg_wait<0>();
        reg_fence(O);
        TS(leader, 48 + uw)
        const uint32_t so = sb + recv_off(uw) + wq * 2048;
#pragma unroll
        for (int i = 0; i < 4; i++) {
            const float* o = &O[8 * i];
            const uint4 r = fin16(add2(u1[i], make_uint4(pack2(o[0], o[1]), pack2(o[2], o[3]), pack2(o[4], o[5]), pack2(o[6], o[7]))), base[i], gb[i]);
            stsm4(so + (lane & 15) * 128 + (((2 * i + (lane >> 4)) ^ (lane & 7)) << 4), r.x, r.y, r.z, r.w);
        }
        TR4(leader, 100 + uw)
        __syncwarp();
#pragma unroll
        for (int i = 0; i < 4; i++) {
            const int row = (lane >> 3) + 4 * i;
            stg128(out + (size_t)(row0 + row) * D_ + 64 * j + 8 * (lane & 7), lds128(so + row * 128 + (((lane & 7) ^ (row & 7)) << 4)));
        }
        TS(leader, 24 + uw)
        warp_arrive(bars + B_OWN * 8);
    }
}

typedef CUresult (*EncFn)(CUtensorMap*, CUtensorMapDataType, cuuint32_t, void*, const cuuint64_t*, const cuuint64_t*, const cuuint32_t*,
                          const cuuint32_t*, CUtensorMapInterleave, CUtensorMapSwizzle, CUtensorMapL2promotion, CUtensorMapFloatOOBfill);

static void enc(EncFn fn, CUtensorMap* m, void* p, int rank, const cuuint64_t* dims, const cuuint64_t* strides, const cuuint32_t* box, bool plain = false) {
    const CUtensorMapSwizzle sw = box[0] > 64 || plain ? CU_TENSOR_MAP_SWIZZLE_NONE : CU_TENSOR_MAP_SWIZZLE_128B;
    cuuint32_t es[5] = {1, 1, 1, 1, 1};
    CUresult r = fn(m, CU_TENSOR_MAP_DATA_TYPE_BFLOAT16, rank, p, dims, strides, box, es, CU_TENSOR_MAP_INTERLEAVE_NONE, sw,
                    CU_TENSOR_MAP_L2_PROMOTION_L2_128B, CU_TENSOR_MAP_FLOAT_OOB_FILL_NONE);
    (void)r;
}
static void enc2(EncFn fn, CUtensorMap* m, void* p, uint64_t cols, uint64_t rows, uint32_t bc, uint32_t br, bool plain = false) {
    cuuint64_t dims[2] = {cols, rows}, st[1] = {cols * 2};
    cuuint32_t box[2] = {bc, br};
    enc(fn, m, p, 2, dims, st, box, plain);
}

extern "C" void kernel_launch(void* const* d_in, const int* in_sizes, int n_in, void* d_out, int out_size) {
    static Maps mp;
    static Ptrs pp;
    static void* cached[13];
    bool same = true;
    for (int i = 0; i < 13; i++) same = same && (cached[i] == d_in[i]);
    if (!same) {
        void* fnp = nullptr;
        cudaDriverEntryPointQueryResult qr;
        cudaGetDriverEntryPoint("cuTensorMapEncodeTiled", &fnp, cudaEnableDefault, &qr);
        EncFn fn = (EncFn)fnp;
        cudaGetSymbolAddress((void**)&pp.s, g_scratch);
        void *x1T = g_x1T, *t = g_t;
        cuuint64_t dq[3] = {64, S_, 10}, sq[2] = {D_ * 2, 128};
        cuuint32_t bq[3] = {64, 16, 10};
        enc(fn, &mp.q, d_in[0], 3, dq, sq, bq);
        enc2(fn, &mp.k, d_in[1], D_, S_, 80, 67); enc2(fn, &mp.v, d_in[2], D_, S_, 80, 64);
        enc2(fn, &mp.qT, g_qT, 16 * D_, 128, 80, 128);
        enc2(fn, &mp.x[0], x1T, S_, D_, 64, 64); enc2(fn, &mp.x[1], (bf16*)t + 2 * D_, D_, S_, 64, 64);
        enc2(fn, &mp.x[2], g_x2f, 64, 320 * 64, 64, 64, true);
        enc2(fn, &mp.w1, d_in[7], D_, D_, 64, 64); enc2(fn, &mp.w1h, d_in[7], D_, D_, 64, 160); enc2(fn, &mp.w3h, d_in[9], F_, D_, 64, 160);
        enc2(fn, &mp.wmod, d_in[12], 6 * D_, D_, 64, 160);
        const cuuint64_t R = D_ * 2;
        cuuint64_t da[5] = {D_, 2, 4, 4, 16}, sa[4] = {R, 8 * R, 2 * R, 32 * R}, db[5] = {D_, 2, 2, 4, 8}, sb[4] = {R, 8 * R, 2 * R, 16 * R};
        cuuint32_t ba[5] = {64, 2, 4, 4, 2}, bb[5] = {64, 2, 2, 4, 4};
        enc(fn, &mp.w2a, d_in[8], 5, da, sa, ba); enc(fn, &mp.w2b, (bf16*)d_in[8] + 512 * D_, 5, db, sb, bb);
        cuuint64_t dw[3] = {64, D_, 27}, sw[2] = {F_ * 2, 128};
        cuuint32_t bw[3] = {64, 32, 3};
        enc(fn, &mp.w3a, d_in[9], 3, dw, sw, bw);
        enc2(fn, &mp.w3b, d_in[9], F_, D_, 24, 32);
        enc2(fn, &mp.w4[0], d_in[10], D_, F_, 64, 64); enc2(fn, &mp.w4[1], d_in[10], D_, F_, 64, 48);
        pp.q = (const bf16*)d_in[0]; pp.w_mod = (const bf16*)d_in[12]; pp.shift_k = (const bf16*)d_in[3];
        pp.ssm_k = (const bf16*)d_in[4]; pp.ssm_D = (const bf16*)d_in[5]; pp.w1 = (const bf16*)d_in[7]; pp.w2 = (const bf16*)d_in[8];
        pp.w4 = (const bf16*)d_in[10]; pp.c = (const bf16*)d_in[11];
        cudaFuncSetAttribute(fused_kernel, cudaFuncAttributeMaxDynamicSharedMemorySize, SMEM_BYTES);
        for (int i = 0; i < 13; i++) cached[i] = d_in[i];
    }
    fused_kernel<<<NCTA, NTHR, SMEM_BYTES, cudaStreamPerThread>>>(pp, (bf16*)d_out, mp);
}
```

```cpp
#include <cuda_runtime.h>
#include <cuda_bf16.h>
#include <cuda.h>
#include <stdint.h>
#include <stdio.h>

typedef __nv_bfloat16 bf16;

constexpr int S_ = 2048, D_ = 640, F_ = 1728;
constexpr int NCTA = 132, NTHR = 512;

constexpr int TAB_BYTES = 9216, VEC_BYTES = 1440;
struct Counters {
    unsigned kv[8 * 32];
    unsigned q[4 * 32], x[4 * 32];
    unsigned wr[32], tab[32], uv[32], cs[32], cs2[32], done[32];
    unsigned g1[32 * 32];
    unsigned g2[32 * 32];
};
struct Scratch {
    Counters cnt;
    unsigned epoch;
    alignas(1024) bf16 qst[2 * S_];
    alignas(1024) uint4 wr[2 * 8 * 10 * 128];
    alignas(1024) uint2 mod[2 * 6 * D_];
    alignas(1024) uint4 tab[(TAB_BYTES + 8 * VEC_BYTES) / 16];
    alignas(1024) float uv[2 * 3 * D_];
    alignas(1024) float cs3[2 * 1920];
    alignas(1024) uint4 cs3b[8 * 216];
    alignas(1024) float2 stats[32 * 8 * 64];
    alignas(1024) bf16 kvT[D_ * S_];
    alignas(1024) bf16 qT[D_ * S_];
    alignas(1024) bf16 x1T[D_ * S_];
    alignas(1024) bf16 t[(S_ + 4) * D_];
    alignas(1024) uint4 x2f[32 * 40 * 128];
    alignas(1024) uint4 x1f[32 * 8 * 5 * 128];
    alignas(1024) uint4 part[32 * 8 * 10 * 4 * 128];
};
__device__ Scratch g_scratch;
#define g_kvT (pp.s->kvT)
#define g_qT (pp.s->qT)
#define g_x1T (pp.s->x1T)
#define g_qst (pp.s->qst)
#define g_t (pp.s->t)
#define g_x2f (pp.s->x2f)
#define g_x1f (pp.s->x1f)
#define g_part (pp.s->part)
#define g_wr (pp.s->wr)
#define g_mod (pp.s->mod)
#define g_tab (pp.s->tab)
#define g_uv (pp.s->uv)
#define g_cs3 (pp.s->cs3)
#define g_cs3b (pp.s->cs3b)
#define g_stats (pp.s->stats)
#define g_cnt (pp.s->cnt)
#define g_epoch (pp.s->epoch)

struct Maps {
    CUtensorMap k, v, q;
    CUtensorMap qT;
    CUtensorMap x[3];
    CUtensorMap w1, w1h, w3h, wmod;
    CUtensorMap w2a, w2b;
    CUtensorMap w3a, w3b;
    CUtensorMap w4[2];
};

struct Ptrs {
    Scratch* s;
    uint64_t nil;
    const bf16 *q, *w_mod, *shift_k, *ssm_k, *ssm_D, *w1, *w2, *w4, *c;
};

constexpr int OFF_W = 0;
constexpr int OFF_XR = 131072;
constexpr int OFF_REM = 196608;
constexpr int OFF_TAB = OFF_REM + 5 * 4096;
constexpr int OFF_ROW = OFF_TAB + 4608;
constexpr int OFF_F1 = OFF_ROW + 4096;
constexpr int RECV_BYTES = 30720;
constexpr int OFF_M = OFF_REM + RECV_BYTES;
constexpr int OFF_OUT = OFF_XR + 32768;
static_assert(OFF_F1 + 1280 <= OFF_M, "G1 map");
constexpr int OFF_ST = 0;
constexpr int OFF_SSM = 20480;
constexpr int OFF_WM = 0;
constexpr int OFF_QIN = 49152;
constexpr int OFF_QT = 49152;
constexpr int OFF_Z = OFF_TAB;
constexpr int OFF_RING = 80896;
constexpr int OFF_KIN = OFF_RING, OFF_VIN = OFF_KIN + 2 * 10752;
constexpr int OFF_CH = OFF_RING + 3 * 16384, CH_BYTES = 13312, OFF_P = 5120;
static_assert(OFF_RING + 5 * 16384 <= OFF_CH + 3 * CH_BYTES && OFF_CH + 5 * CH_BYTES <= OFF_REM, "the last two rings replace channels 0..2");
constexpr int M_BAR = OFF_M;
constexpr int M_F1 = OFF_M + 832;
constexpr int M_GB = M_F1 + 1280, M_C = M_GB + 320, M_SB = M_C + 320, M_CI = M_SB + 320;
constexpr int M_KS = M_CI + 320;
constexpr int M_AB = M_KS + 160;
constexpr int M_EP = M_AB + 80;
constexpr int M_SINK = M_EP + 16;
constexpr int M_NUL = M_SINK + 16;
constexpr int M_TS = M_NUL + 128;
constexpr int SMEM_BYTES = M_TS;
static_assert(SMEM_BYTES <= 232448, "smem");

enum { B_WFULL = 0, B_WEMPTY = 8, B_XEMPTY = 16, B_XFULL = 24  ,
       B_RAW = 44, B_QIN = 45, B_SSM = 46, B_VEC = 47, B_VEC3 = 48, B_WM = 49, B_TAB = 50, B_QRDY = 51,
       B_MODR = 52, B_RAW2 = 53, B_RAW3 = 54, B_GATE = 56, B_SUMS = 62, B_RECV = 64  ,
       B_LAND = 72, B_AGAIN = 80, B_RETRY = 84,
       B_XS = 88, B_R1 = 89, B_BK = 90, B_KVS = 91,
       B_XFREE = 92, B_OWN = 93, B_IN = 94,
       B_RING = 96   };
#define T_KVB 1500
#define T_SSM 4200
#define PF_T0 5900
#define PF_DT 420
#define Q_UNROLL 1
#define HELP_T 1000
#define R_GATE 34
#define REG_AUX 48
#define REG_SVC 32
#define REG_MMA 216
#define STR2(x) #x
#define STR(x) STR2(x)
#define ST3 1
#define LD2 19
#define LD3 23
#define GATE_W2 7
#define GATE_W3 24
#define GATE_W3B 37
#define W3_N2 15
#define COEF_AT 8
#define LEAD2 5
#define LEAD1 5
#define XLEAD 4

#define SPIN_FAIL(code) __trap();
#define SPIN_LIMIT (1u << 22)
#define STALE(c)
#define STALE1(c)
#define TS(c, i)
#define TG(c, i)
#define TR(c, i)
#define TR2(c, i)
#define TR4(c, i)
#define TR5(c, i)
#define SPIN_CHECK(code) asm volatile("" ::"r"(it));
#define RARE(x) __builtin_expect((x) != 0, 0)
__device__ __forceinline__ uint32_t s2u(const void* p) { return (uint32_t)__cvta_generic_to_shared(p); }
__device__ __forceinline__ bool elect() {
    uint32_t p;
    asm volatile("{.reg .pred P; elect.sync _|P, 0xffffffff; selp.u32 %0,1,0,P;}" : "=r"(p));
    return p != 0;
}
__device__ __forceinline__ void mbar_init(uint32_t b, uint32_t n) { asm volatile("mbarrier.init.shared.b64 [%0], %1;" ::"r"(b), "r"(n)); }
__device__ __forceinline__ void mbar_expect(uint32_t b, uint32_t bytes) {
    asm volatile("mbarrier.arrive.expect_tx.shared.b64 _, [%0], %1;" ::"r"(b), "r"(bytes) : "memory");
}
__device__ __forceinline__ void mbar_arrive(uint32_t b) { asm volatile("mbarrier.arrive.shared.b64 _, [%0];" ::"r"(b) : "memory"); }
__device__ __forceinline__ void mbar_arrive_after(uint32_t b, uint32_t v0, uint32_t v1, uint32_t nil) { mbar_arrive(b + ((v0 | v1) & nil)); }
__device__ __forceinline__ void warp_arrive(uint32_t b) { __syncwarp(); if (elect()) mbar_arrive(b); }
__device__ __forceinline__ uint32_t peer_addr(uint32_t a) {
    uint32_t r;
    asm("{\n.reg .b32 q;\nmov.u32 q, %%cluster_ctarank;\nxor.b32 q, q, 1;\nmapa.shared::cluster.u32 %0, %1, q;\n}" : "=r"(r) : "r"(a));
    return r;
}
__device__ __forceinline__ bool mbar_test(uint32_t b, uint32_t parity) {
    uint32_t ok;
    asm volatile("{.reg .pred P; mbarrier.test_wait.parity.shared.b64 P, [%1], %2; selp.u32 %0,1,0,P;}" : "=r"(ok) : "r"(b), "r"(parity) : "memory");
    return ok != 0;
}
__device__ __forceinline__ bool mbar_try(uint32_t b, uint32_t parity) {
    uint32_t ok;
    asm volatile("{.reg .pred P; mbarrier.try_wait.parity.shared.b64 P, [%1], %2; selp.u32 %0,1,0,P;}" : "=r"(ok) : "r"(b), "r"(parity) : "memory");
    return ok != 0;
}
__device__ __forceinline__ void mbar_wait(uint32_t b, uint32_t parity) {
    if (__all_sync(0xffffffffu, mbar_try(b, parity))) return;
    uint32_t it = 0;
    while (!__all_sync(0xffffffffu, mbar_try(b, parity))) { if (++it > SPIN_LIMIT) SPIN_FAIL((b >> 3) & 63) }
}
__device__ __forceinline__ void mbar_spin(uint32_t b, uint32_t parity) {
    asm volatile("{\n.reg .pred P;\nSPIN:\nmbarrier.try_wait.parity.shared.b64 P, [%0], %1;\n@!P bra.uni SPIN;\n}" ::"r"(b), "r"(parity) : "memory");
}
__device__ __forceinline__ void bar_sync(int id, int n) { asm volatile("bar.sync %0, %1;" ::"r"(id), "r"(n) : "memory"); }
__device__ __forceinline__ void fence_async_smem() { asm volatile("fence.proxy.async.shared::cta;" ::: "memory"); }
__device__ __forceinline__ void wait_cnt(const unsigned* p, unsigned target, bool tagged = false) {
    unsigned v, it = 0;
    do {
        asm volatile("ld.relaxed.gpu.global.u32 %0, [%1];" : "=r"(v) : "l"(p) : "memory");
        SPIN_CHECK(60 + (target & 3))
    } while (!__all_sync(0xffffffffu, v >= target));
    if (!tagged) asm volatile("fence.acquire.gpu;" ::: "memory");
}
__device__ __forceinline__ void signal_cnt(unsigned* p, int lane, int n, bool tagged = false) {
    if (tagged) asm volatile("{\n.reg .pred P;\nsetp.lt.s32 P, %1, %2;\n@P red.relaxed.gpu.global.add.u32 [%0], %3;\n}" ::"l"(p), "r"(lane), "r"(n), "r"(1) : "memory");
    else if (lane < n) asm volatile("red.release.gpu.global.add.u32 [%0], 1;" ::"l"(p) : "memory");
    __syncwarp();
}
__device__ __forceinline__ uint32_t clock_lo() { uint32_t c; asm volatile("mov.u32 %0, %%clock;" : "=r"(c)); return c; }
__device__ __forceinline__ void wait_clock(uint32_t c0, uint32_t t) {
    asm volatile("{\n.reg .pred P;\n.reg .b32 c;\nWAIT:\nnanosleep.u32 20;\nmov.u32 c, %%clock;\nsub.u32 c, c, %0;\nsetp.lt.u32 P, c, %1;\n@P bra.uni WAIT;\n}" ::"r"(c0), "r"(t) : "memory");
}
__device__ __forceinline__ void tma_ld2(uint32_t dst, const CUtensorMap* m, int c0, int c1, uint32_t bar) {
    asm volatile("cp.async.bulk.tensor.2d.shared::cluster.global.mbarrier::complete_tx::bytes [%0], [%1, {%3, %4}], [%2];"
                 ::"r"(dst), "l"(m), "r"(bar), "r"(c0), "r"(c1) : "memory");
}
__device__ __forceinline__ void tma_ld3(uint32_t dst, const CUtensorMap* m, int c0, int c1, int c2, uint32_t bar) {
    asm volatile("cp.async.bulk.tensor.3d.shared::cluster.global.mbarrier::complete_tx::bytes [%0], [%1, {%3, %4, %5}], [%2];"
                 ::"r"(dst), "l"(m), "r"(bar), "r"(c0), "r"(c1), "r"(c2) : "memory");
}
__device__ __forceinline__ void tma_ld5(uint32_t dst, const CUtensorMap* m, int col, int blk, uint32_t bar) {
    asm volatile("cp.async.bulk.tensor.5d.shared::cluster.global.mbarrier::complete_tx::bytes [%0], [%1, {%3, %4, %4, %4, %5}], [%2];"
                 ::"r"(dst), "l"(m), "r"(bar), "r"(col), "r"(0), "r"(blk) : "memory");
}
__device__ __forceinline__ void bulk_ld(uint32_t dst, const void* src, uint32_t bytes, uint32_t bar) {
    asm volatile("cp.async.bulk.shared::cluster.global.mbarrier::complete_tx::bytes [%0], [%1], %2, [%3];" ::"r"(dst), "l"(src), "r"(bytes), "r"(bar) : "memory");
}
__device__ __forceinline__ void l2_prefetch(const void* p, uint32_t bytes) {
    asm volatile("cp.async.bulk.prefetch.L2.global [%0], %1;" ::"l"(p), "r"(bytes) : "memory");
}
__device__ __forceinline__ void wg_fence() { asm volatile("wgmma.fence.sync.aligned;" ::: "memory"); }
__device__ __forceinline__ void wg_commit() { asm volatile("wgmma.commit_group.sync.aligned;" ::: "memory"); }
template <int N> __device__ __forceinline__ void wg_wait() { asm volatile("wgmma.wait_group.sync.aligned %0;" ::"n"(N) : "memory"); }
template <int N> __device__ __forceinline__ void reg_fence(float (&d)[N]) {
#pragma unroll
    for (int i = 0; i < N; i++) asm volatile("" : "+f"(d[i])::"memory");
}
template <int N> __device__ __forceinline__ void zero(float (&d)[N]) {
#pragma unroll
    for (int i = 0; i < N; i++) asm volatile("mov.b32 %0, 0;" : "=f"(d[i]));
}
__device__ __forceinline__ uint32_t lds32(uint32_t a) { uint32_t v; asm volatile("ld.shared.b32 %0, [%1];" : "=r"(v) : "r"(a)); return v; }
__device__ __forceinline__ uint2 lds64(uint32_t a) { uint2 v; asm volatile("ld.shared.v2.b32 {%0,%1}, [%2];" : "=r"(v.x), "=r"(v.y) : "r"(a)); return v; }
__device__ __forceinline__ float2 lds64f(uint32_t a) { float2 v; asm volatile("ld.shared.v2.f32 {%0,%1}, [%2];" : "=f"(v.x), "=f"(v.y) : "r"(a)); return v; }
__device__ __forceinline__ void sts32(uint32_t a, uint32_t v) { asm volatile("st.shared.b32 [%0], %1;" ::"r"(a), "r"(v) : "memory"); }
__device__ __forceinline__ void sts64f(uint32_t a, float x, float y) { asm volatile("st.shared.v2.f32 [%0], {%1,%2};" ::"r"(a), "f"(x), "f"(y) : "memory"); }
__device__ __forceinline__ void sts128(uint32_t a, uint32_t x, uint32_t y, uint32_t z, uint32_t w) {
    asm volatile("st.shared.v4.b32 [%0], {%1,%2,%3,%4};" ::"r"(a), "r"(x), "r"(y), "r"(z), "r"(w) : "memory");
}
__device__ __forceinline__ void sts128f(uint32_t a, float x, float y, float z, float w) {
    asm volatile("st.shared.v4.f32 [%0], {%1,%2,%3,%4};" ::"r"(a), "f"(x), "f"(y), "f"(z), "f"(w) : "memory");
}
__device__ __forceinline__ uint4 lds128(uint32_t a) {
    uint4 v;
    asm volatile("ld.shared.v4.b32 {%0,%1,%2,%3}, [%4];" : "=r"(v.x), "=r"(v.y), "=r"(v.z), "=r"(v.w) : "r"(a) : "memory");
    return v;
}
__device__ __forceinline__ void lds128_if(int p, uint4& v, uint32_t a) {
    asm volatile("{\n.reg .pred p;\nsetp.ne.s32 p, %5, 0;\n@p ld.shared.v4.b32 {%0,%1,%2,%3}, [%4];\n}" : "+r"(v.x), "+r"(v.y), "+r"(v.z), "+r"(v.w) : "r"(a), "r"(p) : "memory");
}
__device__ __forceinline__ float4 lds128f(uint32_t a) {
    float4 v;
    asm volatile("ld.shared.v4.f32 {%0,%1,%2,%3}, [%4];" : "=f"(v.x), "=f"(v.y), "=f"(v.z), "=f"(v.w) : "r"(a) : "memory");
    return v;
}
__device__ __forceinline__ void stg128(void* p, uint32_t x, uint32_t y, uint32_t z, uint32_t w) {
    asm volatile("st.global.v4.b32 [%0], {%1,%2,%3,%4};" ::"l"(p), "r"(x), "r"(y), "r"(z), "r"(w) : "memory");
}
__device__ __forceinline__ void stg128(void* p, uint4 v) { stg128(p, v.x, v.y, v.z, v.w); }
__device__ __forceinline__ void stg128_if(void* p, uint4 v, int on) {
    asm volatile("{\n.reg .pred p;\nsetp.ne.s32 p, %5, 0;\n@p st.global.v4.b32 [%0], {%1,%2,%3,%4};\n}" ::"l"(p), "r"(v.x), "r"(v.y), "r"(v.z), "r"(v.w), "r"(on) : "memory");
}
__device__ __forceinline__ void stg64(void* p, uint32_t x, uint32_t y) { asm volatile("st.global.v2.b32 [%0], {%1,%2};" ::"l"(p), "r"(x), "r"(y) : "memory"); }
__device__ __forceinline__ void stsm4(uint32_t a, uint32_t r0, uint32_t r1, uint32_t r2, uint32_t r3) {
    asm volatile("stmatrix.sync.aligned.m8n8.x4.shared.b16 [%0], {%1,%2,%3,%4};" ::"r"(a), "r"(r0), "r"(r1), "r"(r2), "r"(r3) : "memory");
}
__device__ __forceinline__ void stsm4t(uint32_t a, uint32_t r0, uint32_t r1, uint32_t r2, uint32_t r3) {
    asm volatile("stmatrix.sync.aligned.m8n8.x4.trans.shared.b16 [%0], {%1,%2,%3,%4};" ::"r"(a), "r"(r0), "r"(r1), "r"(r2), "r"(r3) : "memory");
}
__device__ __forceinline__ void ldsm4t_if(bool p, uint32_t a, uint32_t* r) {
    asm volatile("{\n.reg .pred p;\nsetp.ne.u32 p, %5, 0;\n@p ldmatrix.sync.aligned.m8n8.x4.trans.shared.b16 {%0,%1,%2,%3}, [%4];\n}"
                 : "+r"(r[0]), "+r"(r[1]), "+r"(r[2]), "+r"(r[3]) : "r"(a), "r"((uint32_t)p) : "memory");
}
__device__ __forceinline__ void ldsm4t(uint32_t a, uint32_t& r0, uint32_t& r1, uint32_t& r2, uint32_t& r3) {
    asm volatile("ldmatrix.sync.aligned.m8n8.x4.trans.shared.b16 {%0,%1,%2,%3}, [%4];" : "=r"(r0), "=r"(r1), "=r"(r2), "=r"(r3) : "r"(a) : "memory");
}
__device__ __forceinline__ uint32_t pack2(float lo, float hi) {
    uint32_t r;
    asm("cvt.rn.bf16x2.f32 %0, %1, %2;" : "=r"(r) : "f"(hi), "f"(lo));
    return r;
}
__device__ __forceinline__ uint32_t mul2(uint32_t a, uint32_t b) { uint32_t r; asm("mul.rn.bf16x2 %0, %1, %2;" : "=r"(r) : "r"(a), "r"(b)); return r; }
__device__ __forceinline__ uint32_t fma2(uint32_t a, uint32_t b, uint32_t c) { uint32_t r; asm("fma.rn.bf16x2 %0, %1, %2, %3;" : "=r"(r) : "r"(a), "r"(b), "r"(c)); return r; }
__device__ __forceinline__ uint32_t add2(uint32_t a, uint32_t b) { uint32_t r; asm("add.rn.bf16x2 %0, %1, %2;" : "=r"(r) : "r"(a), "r"(b)); return r; }
__device__ __forceinline__ void hmma(float (&d)[4], uint32_t a0, uint32_t a1, uint32_t a2, uint32_t a3, uint32_t b0, uint32_t b1) {
    asm volatile("mma.sync.aligned.m16n8k16.row.col.f32.bf16.bf16.f32 {%0,%1,%2,%3}, {%4,%5,%6,%7}, {%8,%9}, {%0,%1,%2,%3};"
        : "+f"(d[0]), "+f"(d[1]), "+f"(d[2]), "+f"(d[3]) : "r"(a0), "r"(a1), "r"(a2), "r"(a3), "r"(b0), "r"(b1));
}
__device__ __forceinline__ float blo(uint32_t w) { return __uint_as_float(w << 16); }
__device__ __forceinline__ float bhi(uint32_t w) { return __uint_as_float(w & 0xffff0000u); }
__device__ __forceinline__ float rbf(float x) { return __bfloat162float(__float2bfloat16_rn(x)); }
__device__ __forceinline__ uint32_t ldg32(const void* p) { uint32_t v; asm volatile("ld.global.nc.b32 %0, [%1];" : "=r"(v) : "l"(p)); return v; }
__device__ __forceinline__ uint2 ldg64(const void* p) { uint2 v; asm volatile("ld.global.nc.v2.b32 {%0,%1}, [%2];" : "=r"(v.x), "=r"(v.y) : "l"(p)); return v; }
__device__ __forceinline__ uint4 ldg128(const void* p) {
    uint4 v;
    asm volatile("ld.global.nc.v4.b32 {%0,%1,%2,%3}, [%4];" : "=r"(v.x), "=r"(v.y), "=r"(v.z), "=r"(v.w) : "l"(p));
    return v;
}
__device__ __forceinline__ uint4 ldcg128(const void* p) {
    uint4 v;
    asm volatile("ld.global.cg.v4.u32 {%0,%1,%2,%3}, [%4];" : "=r"(v.x), "=r"(v.y), "=r"(v.z), "=r"(v.w) : "l"(p) : "memory");
    return v;
}
__device__ __forceinline__ float4 ldcg128f(const void* p) {
    float4 v;
    asm volatile("ld.global.cg.v4.f32 {%0,%1,%2,%3}, [%4];" : "=f"(v.x), "=f"(v.y), "=f"(v.z), "=f"(v.w) : "l"(p) : "memory");
    return v;
}
__device__ __forceinline__ float2 ldcg64f(const void* p) { float2 v; asm volatile("ld.global.cg.v2.f32 {%0,%1}, [%2];" : "=f"(v.x), "=f"(v.y) : "l"(p) : "memory"); return v; }
__device__ __forceinline__ float ldcg32f(const void* p) { float v; asm volatile("ld.global.cg.f32 %0, [%1];" : "=f"(v) : "l"(p) : "memory"); return v; }
__device__ __forceinline__ float2 ld_stat(const float2* p) {
    float2 v;
    asm volatile("{\n.reg .b64 q;\nld.relaxed.gpu.global.b64 q, [%2];\nmov.b64 {%0, %1}, q;\n}" : "=f"(v.x), "=f"(v.y) : "l"(p) : "memory");
    return v;
}
__device__ __forceinline__ uint32_t ld_cold(const unsigned* p) { uint32_t v; asm volatile("ld.relaxed.gpu.global.u32 %0, [%1];" : "=r"(v) : "l"(p) : "memory"); return v; }
__device__ __forceinline__ uint2 ld_mod(const uint2* p) {
    uint64_t v;
    asm volatile("ld.relaxed.gpu.global.b64 %0, [%1];" : "=l"(v) : "l"(p) : "memory");
    return make_uint2((uint32_t)v, (uint32_t)(v >> 32));
}
__device__ __forceinline__ float silu(float x) {
    float e, r;
    asm("ex2.approx.ftz.f32 %0, %1;" : "=f"(e) : "f"(x * -1.4426950408889634f));
    asm("rcp.approx.ftz.f32 %0, %1;" : "=f"(r) : "f"(1.f + e));
    return x * r;
}
__device__ __forceinline__ float gelu2(float h) {
    float u = h * fmaf(h * h, 8.f * 0.0356774081f, 2.f * 0.7978845608f);
    float th;
    asm("tanh.approx.f32 %0, %1;" : "=f"(th) : "f"(u));
    return fmaf(h, th, h);
}
__device__ __forceinline__ float gelu2r(float a, float2 k) {
    float th;
    asm("tanh.approx.f32 %0, %1;" : "=f"(th) : "f"(a * fmaf(a * a, k.x, k.y)));
    return fmaf(a, th, a);
}

__device__ __forceinline__ void conv_channel(float (&d)[64], uint32_t pa, uint64_t db) {
    asm volatile("{\n.reg .b32 a0, a1, a2, a3, b0, b1, b2, b3, t0, t1;\n.reg .b64 d;\nld.shared.b32 a0, [%64];\nld.shared.b32 a1, [%64+128];\nld.shared.b32 a2, [%64+-128];\nmov.b32 a3, a0;\n"
        "ld.shared.b32 t0, [%64+256];\nld.shared.b32 t1, [%64+384];\nadd.s64 d, %65, 0;\nwgmma.fence.sync.aligned;\nwgmma.mma_async.sync.aligned.m64n128k16.f32.bf16.bf16 {%0, %1, %2, %3, %4, %5, %6, %7, %8, %9, %10, %11, %12, %13, %14, %15, %16, %17, %18, %19, %20, %21, %22, %23, %24, %25, %26, %27, %28, %29, %30, %31, %32, %33, %34, %35, %36, %37, %38, %39, %40, %41, %42, %43, %44, %45, %46, %47, %48, %49, %50, %51, %52, %53, %54, %55, %56, %57, %58, %59, %60, %61, %62, %63}, {a0, a1, a2, a3}, d, 0, 1, 1, 0;\nwgmma.commit_group.sync.aligned;\nwgmma.wait_group.sync.aligned 1;\nmov.b32 b2, a1;\nmov.b32 b0, t0;\nmov.b32 b3, t0;\nmov.b32 b1, t1;\n"
        "ld.shared.b32 t0, [%64+512];\nld.shared.b32 t1, [%64+640];\nadd.s64 d, %65, 8;\nwgmma.fence.sync.aligned;\nwgmma.mma_async.sync.aligned.m64n128k16.f32.bf16.bf16 {%0, %1, %2, %3, %4, %5, %6, %7, %8, %9, %10, %11, %12, %13, %14, %15, %16, %17, %18, %19, %20, %21, %22, %23, %24, %25, %26, %27, %28, %29, %30, %31, %32, %33, %34, %35, %36, %37, %38, %39, %40, %41, %42, %43, %44, %45, %46, %47, %48, %49, %50, %51, %52, %53, %54, %55, %56, %57, %58, %59, %60, %61, %62, %63}, {b0, b1, b2, b3}, d, 1, 1, 1, 0;\nwgmma.commit_group.sync.aligned;\nwgmma.wait_group.sync.aligned 1;\nmov.b32 a2, b1;\nmov.b32 a0, t0;\nmov.b32 a3, t0;\nmov.b32 a1, t1;\n"
        "ld.shared.b32 t0, [%64+768];\nld.shared.b32 t1, [%64+896];\nadd.s64 d, %65, 16;\nwgmma.fence.sync.aligned;\nwgmma.mma_async.sync.aligned.m64n128k16.f32.bf16.bf16 {%0, %1, %2, %3, %4, %5, %6, %7, %8, %9, %10, %11, %12, %13, %14, %15, %16, %17, %18, %19, %20, %21, %22, %23, %24, %25, %26, %27, %28, %29, %30, %31, %32, %33, %34, %35, %36, %37, %38, %39, %40, %41, %42, %43, %44, %45, %46, %47, %48, %49, %50, %51, %52, %53, %54, %55, %56, %57, %58, %59, %60, %61, %62, %63}, {a0, a1, a2, a3}, d, 1, 1, 1, 0;\nwgmma.commit_group.sync.aligned;\nwgmma.wait_group.sync.aligned 1;\nmov.b32 b2, a1;\nmov.b32 b0, t0;\nmov.b32 b3, t0;\nmov.b32 b1, t1;\n"
        "ld.shared.b32 t0, [%64+1024];\nld.shared.b32 t1, [%64+1152];\nadd.s64 d, %65, 24;\nwgmma.fence.sync.aligned;\nwgmma.mma_async.sync.aligned.m64n128k16.f32.bf16.bf16 {%0, %1, %2, %3, %4, %5, %6, %7, %8, %9, %10, %11, %12, %13, %14, %15, %16, %17, %18, %19, %20, %21, %22, %23, %24, %25, %26, %27, %28, %29, %30, %31, %32, %33, %34, %35, %36, %37, %38, %39, %40, %41, %42, %43, %44, %45, %46, %47, %48, %49, %50, %51, %52, %53, %54, %55, %56, %57, %58, %59, %60, %61, %62, %63}, {b0, b1, b2, b3}, d, 1, 1, 1, 0;\nwgmma.commit_group.sync.aligned;\nwgmma.wait_group.sync.aligned 1;\nmov.b32 a2, b1;\nmov.b32 a0, t0;\nmov.b32 a3, t0;\nmov.b32 a1, t1;\n"
        "ld.shared.b32 t0, [%64+1280];\nld.shared.b32 t1, [%64+1408];\nadd.s64 d, %65, 32;\nwgmma.fence.sync.aligned;\nwgmma.mma_async.sync.aligned.m64n128k16.f32.bf16.bf16 {%0, %1, %2, %3, %4, %5, %6, %7, %8, %9, %10, %11, %12, %13, %14, %15, %16, %17, %18, %19, %20, %21, %22, %23, %24, %25, %26, %27, %28, %29, %30, %31, %32, %33, %34, %35, %36, %37, %38, %39, %40, %41, %42, %43, %44, %45, %46, %47, %48, %49, %50, %51, %52, %53, %54, %55, %56, %57, %58, %59, %60, %61, %62, %63}, {a0, a1, a2, a3}, d, 1, 1, 1, 0;\nwgmma.commit_group.sync.aligned;\nwgmma.wait_group.sync.aligned 1;\nmov.b32 b2, a1;\nmov.b32 b0, t0;\nmov.b32 b3, t0;\nmov.b32 b1, t1;\n"
        "ld.shared.b32 t0, [%64+1536];\nld.shared.b32 t1, [%64+1664];\nadd.s64 d, %65, 40;\nwgmma.fence.sync.aligned;\nwgmma.mma_async.sync.aligned.m64n128k16.f32.bf16.bf16 {%0, %1, %2, %3, %4, %5, %6, %7, %8, %9, %10, %11, %12, %13, %14, %15, %16, %17, %18, %19, %20, %21, %22, %23, %24, %25, %26, %27, %28, %29, %30, %31, %32, %33, %34, %35, %36, %37, %38, %39, %40, %41, %42, %43, %44, %45, %46, %47, %48, %49, %50, %51, %52, %53, %54, %55, %56, %57, %58, %59, %60, %61, %62, %63}, {b0, b1, b2, b3}, d, 1, 1, 1, 0;\nwgmma.commit_group.sync.aligned;\nwgmma.wait_group.sync.aligned 1;\nmov.b32 a2, b1;\nmov.b32 a0, t0;\nmov.b32 a3, t0;\nmov.b32 a1, t1;\n"
        "ld.shared.b32 t0, [%64+1792];\nld.shared.b32 t1, [%64+1920];\nadd.s64 d, %65, 48;\nwgmma.fence.sync.aligned;\nwgmma.mma_async.sync.aligned.m64n128k16.f32.bf16.bf16 {%0, %1, %2, %3, %4, %5, %6, %7, %8, %9, %10, %11, %12, %13, %14, %15, %16, %17, %18, %19, %20, %21, %22, %23, %24, %25, %26, %27, %28, %29, %30, %31, %32, %33, %34, %35, %36, %37, %38, %39, %40, %41, %42, %43, %44, %45, %46, %47, %48, %49, %50, %51, %52, %53, %54, %55, %56, %57, %58, %59, %60, %61, %62, %63}, {a0, a1, a2, a3}, d, 1, 1, 1, 0;\nwgmma.commit_group.sync.aligned;\nwgmma.wait_group.sync.aligned 1;\nmov.b32 b2, a1;\nmov.b32 b0, t0;\nmov.b32 b3, t0;\nmov.b32 b1, t1;\n"
        "ld.shared.b32 t0, [%64+2048];\nld.shared.b32 t1, [%64+2176];\nadd.s64 d, %65, 56;\nwgmma.fence.sync.aligned;\nwgmma.mma_async.sync.aligned.m64n128k16.f32.bf16.bf16 {%0, %1, %2, %3, %4, %5, %6, %7, %8, %9, %10, %11, %12, %13, %14, %15, %16, %17, %18, %19, %20, %21, %22, %23, %24, %25, %26, %27, %28, %29, %30, %31, %32, %33, %34, %35, %36, %37, %38, %39, %40, %41, %42, %43, %44, %45, %46, %47, %48, %49, %50, %51, %52, %53, %54, %55, %56, %57, %58, %59, %60, %61, %62, %63}, {b0, b1, b2, b3}, d, 1, 1, 1, 0;\nwgmma.commit_group.sync.aligned;\nwgmma.wait_group.sync.aligned 1;\nmov.b32 a2, b1;\nmov.b32 a0, t0;\nmov.b32 a3, t0;\nmov.b32 a1, t1;\n"
        "ld.shared.b32 t0, [%64+2304];\nld.shared.b32 t1, [%64+2432];\nadd.s64 d, %65, 64;\nwgmma.fence.sync.aligned;\nwgmma.mma_async.sync.aligned.m64n96k16.f32.bf16.bf16 {%0, %1, %2, %3, %4, %5, %6, %7, %8, %9, %10, %11, %12, %13, %14, %15, %16, %17, %18, %19, %20, %21, %22, %23, %24, %25, %26, %27, %28, %29, %30, %31, %32, %33, %34, %35, %36, %37, %38, %39, %40, %41, %42, %43, %44, %45, %46, %47}, {a0, a1, a2, a3}, d, 1, 1, 1, 0;\nwgmma.commit_group.sync.aligned;\nwgmma.wait_group.sync.aligned 1;\nmov.b32 b2, a1;\nmov.b32 b0, t0;\nmov.b32 b3, t0;\nmov.b32 b1, t1;\n"
        "ld.shared.b32 t0, [%64+2560];\nld.shared.b32 t1, [%64+2688];\nadd.s64 d, %65, 72;\nwgmma.fence.sync.aligned;\nwgmma.mma_async.sync.aligned.m64n96k16.f32.bf16.bf16 {%0, %1, %2, %3, %4, %5, %6, %7, %8, %9, %10, %11, %12, %13, %14, %15, %16, %17, %18, %19, %20, %21, %22, %23, %24, %25, %26, %27, %28, %29, %30, %31, %32, %33, %34, %35, %36, %37, %38, %39, %40, %41, %42, %43, %44, %45, %46, %47}, {b0, b1, b2, b3}, d, 1, 1, 1, 0;\nwgmma.commit_group.sync.aligned;\nwgmma.wait_group.sync.aligned 1;\nmov.b32 a2, b1;\nmov.b32 a0, t0;\nmov.b32 a3, t0;\nmov.b32 a1, t1;\n"
        "ld.shared.b32 t0, [%64+2816];\nld.shared.b32 t1, [%64+2944];\nadd.s64 d, %65, 80;\nwgmma.fence.sync.aligned;\nwgmma.mma_async.sync.aligned.m64n88k16.f32.bf16.bf16 {%0, %1, %2, %3, %4, %5, %6, %7, %8, %9, %10, %11, %12, %13, %14, %15, %16, %17, %18, %19, %20, %21, %22, %23, %24, %25, %26, %27, %28, %29, %30, %31, %32, %33, %34, %35, %36, %37, %38, %39, %40, %41, %42, %43}, {a0, a1, a2, a3}, d, 1, 1, 1, 0;\nwgmma.commit_group.sync.aligned;\nwgmma.wait_group.sync.aligned 1;\nmov.b32 b2, a1;\nmov.b32 b0, t0;\nmov.b32 b3, t0;\nmov.b32 b1, t1;\n"
        "ld.shared.b32 t0, [%64+3072];\nld.shared.b32 t1, [%64+3200];\nadd.s64 d, %65, 88;\nwgmma.fence.sync.aligned;\nwgmma.mma_async.sync.aligned.m64n88k16.f32.bf16.bf16 {%0, %1, %2, %3, %4, %5, %6, %7, %8, %9, %10, %11, %12, %13, %14, %15, %16, %17, %18, %19, %20, %21, %22, %23, %24, %25, %26, %27, %28, %29, %30, %31, %32, %33, %34, %35, %36, %37, %38, %39, %40, %41, %42, %43}, {b0, b1, b2, b3}, d, 1, 1, 1, 0;\nwgmma.commit_group.sync.aligned;\nwgmma.wait_group.sync.aligned 1;\nmov.b32 a2, b1;\nmov.b32 a0, t0;\nmov.b32 a3, t0;\nmov.b32 a1, t1;\n"
        "ld.shared.b32 t0, [%64+3328];\nld.shared.b32 t1, [%64+3456];\nadd.s64 d, %65, 96;\nwgmma.fence.sync.aligned;\nwgmma.mma_async.sync.aligned.m64n80k16.f32.bf16.bf16 {%0, %1, %2, %3, %4, %5, %6, %7, %8, %9, %10, %11, %12, %13, %14, %15, %16, %17, %18, %19, %20, %21, %22, %23, %24, %25, %26, %27, %28, %29, %30, %31, %32, %33, %34, %35, %36, %37, %38, %39}, {a0, a1, a2, a3}, d, 1, 1, 1, 0;\nwgmma.commit_group.sync.aligned;\nwgmma.wait_group.sync.aligned 1;\nmov.b32 b2, a1;\nmov.b32 b0, t0;\nmov.b32 b3, t0;\nmov.b32 b1, t1;\n"
        "ld.shared.b32 t0, [%64+3584];\nld.shared.b32 t1, [%64+3712];\nadd.s64 d, %65, 104;\nwgmma.fence.sync.aligned;\nwgmma.mma_async.sync.aligned.m64n80k16.f32.bf16.bf16 {%0, %1, %2, %3, %4, %5, %6, %7, %8, %9, %10, %11, %12, %13, %14, %15, %16, %17, %18, %19, %20, %21, %22, %23, %24, %25, %26, %27, %28, %29, %30, %31, %32, %33, %34, %35, %36, %37, %38, %39}, {b0, b1, b2, b3}, d, 1, 1, 1, 0;\nwgmma.commit_group.sync.aligned;\nwgmma.wait_group.sync.aligned 1;\nmov.b32 a2, b1;\nmov.b32 a0, t0;\nmov.b32 a3, t0;\nmov.b32 a1, t1;\n"
        "ld.shared.b32 t0, [%64+3840];\nld.shared.b32 t1, [%64+3968];\nadd.s64 d, %65, 112;\nwgmma.fence.sync.aligned;\nwgmma.mma_async.sync.aligned.m64n72k16.f32.bf16.bf16 {%0, %1, %2, %3, %4, %5, %6, %7, %8, %9, %10, %11, %12, %13, %14, %15, %16, %17, %18, %19, %20, %21, %22, %23, %24, %25, %26, %27, %28, %29, %30, %31, %32, %33, %34, %35}, {a0, a1, a2, a3}, d, 1, 1, 1, 0;\nwgmma.commit_group.sync.aligned;\nwgmma.wait_group.sync.aligned 1;\nmov.b32 b2, a1;\nmov.b32 b0, t0;\nmov.b32 b3, t0;\nmov.b32 b1, t1;\n"
        "ld.shared.b32 t0, [%64+4096];\nld.shared.b32 t1, [%64+4224];\nadd.s64 d, %65, 120;\nwgmma.fence.sync.aligned;\nwgmma.mma_async.sync.aligned.m64n72k16.f32.bf16.bf16 {%0, %1, %2, %3, %4, %5, %6, %7, %8, %9, %10, %11, %12, %13, %14, %15, %16, %17, %18, %19, %20, %21, %22, %23, %24, %25, %26, %27, %28, %29, %30, %31, %32, %33, %34, %35}, {b0, b1, b2, b3}, d, 1, 1, 1, 0;\nwgmma.commit_group.sync.aligned;\nwgmma.wait_group.sync.aligned 1;\nmov.b32 a2, b1;\nmov.b32 a0, t0;\nmov.b32 a3, t0;\nmov.b32 a1, t1;\n"
        "ld.shared.b32 t0, [%64+4352];\nld.shared.b32 t1, [%64+4480];\nadd.s64 d, %65, 128;\nwgmma.fence.sync.aligned;\nwgmma.mma_async.sync.aligned.m64n64k16.f32.bf16.bf16 {%0, %1, %2, %3, %4, %5, %6, %7, %8, %9, %10, %11, %12, %13, %14, %15, %16, %17, %18, %19, %20, %21, %22, %23, %24, %25, %26, %27, %28, %29, %30, %31}, {a0, a1, a2, a3}, d, 1, 1, 1, 0;\nwgmma.commit_group.sync.aligned;\nwgmma.wait_group.sync.aligned 1;\nmov.b32 b2, a1;\nmov.b32 b0, t0;\nmov.b32 b3, t0;\nmov.b32 b1, t1;\n"
        "ld.shared.b32 t0, [%64+4608];\nld.shared.b32 t1, [%64+4736];\nadd.s64 d, %65, 136;\nwgmma.fence.sync.aligned;\nwgmma.mma_async.sync.aligned.m64n64k16.f32.bf16.bf16 {%0, %1, %2, %3, %4, %5, %6, %7, %8, %9, %10, %11, %12, %13, %14, %15, %16, %17, %18, %19, %20, %21, %22, %23, %24, %25, %26, %27, %28, %29, %30, %31}, {b0, b1, b2, b3}, d, 1, 1, 1, 0;\nwgmma.commit_group.sync.aligned;\nwgmma.wait_group.sync.aligned 1;\nmov.b32 a2, b1;\nmov.b32 a0, t0;\nmov.b32 a3, t0;\nmov.b32 a1, t1;\n"
        "ld.shared.b32 t0, [%64+4864];\nld.shared.b32 t1, [%64+4992];\nadd.s64 d, %65, 144;\nwgmma.fence.sync.aligned;\nwgmma.mma_async.sync.aligned.m64n56k16.f32.bf16.bf16 {%0, %1, %2, %3, %4, %5, %6, %7, %8, %9, %10, %11, %12, %13, %14, %15, %16, %17, %18, %19, %20, %21, %22, %23, %24, %25, %26, %27}, {a0, a1, a2, a3}, d, 1, 1, 1, 0;\nwgmma.commit_group.sync.aligned;\nwgmma.wait_group.sync.aligned 1;\nmov.b32 b2, a1;\nmov.b32 b0, t0;\nmov.b32 b3, t0;\nmov.b32 b1, t1;\n"
        "ld.shared.b32 t0, [%64+5120];\nld.shared.b32 t1, [%64+5248];\nadd.s64 d, %65, 152;\nwgmma.fence.sync.aligned;\nwgmma.mma_async.sync.aligned.m64n56k16.f32.bf16.bf16 {%0, %1, %2, %3, %4, %5, %6, %7, %8, %9, %10, %11, %12, %13, %14, %15, %16, %17, %18, %19, %20, %21, %22, %23, %24, %25, %26, %27}, {b0, b1, b2, b3}, d, 1, 1, 1, 0;\nwgmma.commit_group.sync.aligned;\nwgmma.wait_group.sync.aligned 1;\nmov.b32 a2, b1;\nmov.b32 a0, t0;\nmov.b32 a3, t0;\nmov.b32 a1, t1;\n"
        "ld.shared.b32 t0, [%64+5376];\nld.shared.b32 t1, [%64+5504];\nadd.s64 d, %65, 160;\nwgmma.fence.sync.aligned;\nwgmma.mma_async.sync.aligned.m64n48k16.f32.bf16.bf16 {%0, %1, %2, %3, %4, %5, %6, %7, %8, %9, %10, %11, %12, %13, %14, %15, %16, %17, %18, %19, %20, %21, %22, %23}, {a0, a1, a2, a3}, d, 1, 1, 1, 0;\nwgmma.commit_group.sync.aligned;\nwgmma.wait_group.sync.aligned 1;\nmov.b32 b2, a1;\nmov.b32 b0, t0;\nmov.b32 b3, t0;\nmov.b32 b1, t1;\n"
        "ld.shared.b32 t0, [%64+5632];\nld.shared.b32 t1, [%64+5760];\nadd.s64 d, %65, 168;\nwgmma.fence.sync.aligned;\nwgmma.mma_async.sync.aligned.m64n48k16.f32.bf16.bf16 {%0, %1, %2, %3, %4, %5, %6, %7, %8, %9, %10, %11, %12, %13, %14, %15, %16, %17, %18, %19, %20, %21, %22, %23}, {b0, b1, b2, b3}, d, 1, 1, 1, 0;\nwgmma.commit_group.sync.aligned;\nwgmma.wait_group.sync.aligned 1;\nmov.b32 a2, b1;\nmov.b32 a0, t0;\nmov.b32 a3, t0;\nmov.b32 a1, t1;\n"
        "ld.shared.b32 t0, [%64+5888];\nld.shared.b32 t1, [%64+6016];\nadd.s64 d, %65, 176;\nwgmma.fence.sync.aligned;\nwgmma.mma_async.sync.aligned.m64n40k16.f32.bf16.bf16 {%0, %1, %2, %3, %4, %5, %6, %7, %8, %9, %10, %11, %12, %13, %14, %15, %16, %17, %18, %19}, {a0, a1, a2, a3}, d, 1, 1, 1, 0;\nwgmma.commit_group.sync.aligned;\nwgmma.wait_group.sync.aligned 1;\nmov.b32 b2, a1;\nmov.b32 b0, t0;\nmov.b32 b3, t0;\nmov.b32 b1, t1;\n"
        "ld.shared.b32 t0, [%64+6144];\nld.shared.b32 t1, [%64+6272];\nadd.s64 d, %65, 184;\nwgmma.fence.sync.aligned;\nwgmma.mma_async.sync.aligned.m64n40k16.f32.bf16.bf16 {%0, %1, %2, %3, %4, %5, %6, %7, %8, %9, %10, %11, %12, %13, %14, %15, %16, %17, %18, %19}, {b0, b1, b2, b3}, d, 1, 1, 1, 0;\nwgmma.commit_group.sync.aligned;\nwgmma.wait_group.sync.aligned 1;\nmov.b32 a2, b1;\nmov.b32 a0, t0;\nmov.b32 a3, t0;\nmov.b32 a1, t1;\n"
        "ld.shared.b32 t0, [%64+6400];\nld.shared.b32 t1, [%64+6528];\nadd.s64 d, %65, 192;\nwgmma.fence.sync.aligned;\nwgmma.mma_async.sync.aligned.m64n32k16.f32.bf16.bf16 {%0, %1, %2, %3, %4, %5, %6, %7, %8, %9, %10, %11, %12, %13, %14, %15}, {a0, a1, a2, a3}, d, 1, 1, 1, 0;\nwgmma.commit_group.sync.aligned;\nwgmma.wait_group.sync.aligned 1;\nmov.b32 b2, a1;\nmov.b32 b0, t0;\nmov.b32 b3, t0;\nmov.b32 b1, t1;\n"
        "ld.shared.b32 t0, [%64+6656];\nld.shared.b32 t1, [%64+6784];\nadd.s64 d, %65, 200;\nwgmma.fence.sync.aligned;\nwgmma.mma_async.sync.aligned.m64n32k16.f32.bf16.bf16 {%0, %1, %2, %3, %4, %5, %6, %7, %8, %9, %10, %11, %12, %13, %14, %15}, {b0, b1, b2, b3}, d, 1, 1, 1, 0;\nwgmma.commit_group.sync.aligned;\nwgmma.wait_group.sync.aligned 1;\nmov.b32 a2, b1;\nmov.b32 a0, t0;\nmov.b32 a3, t0;\nmov.b32 a1, t1;\n"
        "ld.shared.b32 t0, [%64+6912];\nld.shared.b32 t1, [%64+7040];\nadd.s64 d, %65, 208;\nwgmma.fence.sync.aligned;\nwgmma.mma_async.sync.aligned.m64n24k16.f32.bf16.bf16 {%0, %1, %2, %3, %4, %5, %6, %7, %8, %9, %10, %11}, {a0, a1, a2, a3}, d, 1, 1, 1, 0;\nwgmma.commit_group.sync.aligned;\nwgmma.wait_group.sync.aligned 1;\nmov.b32 b2, a1;\nmov.b32 b0, t0;\nmov.b32 b3, t0;\nmov.b32 b1, t1;\n"
        "ld.shared.b32 t0, [%64+7168];\nld.shared.b32 t1, [%64+7296];\nadd.s64 d, %65, 216;\nwgmma.fence.sync.aligned;\nwgmma.mma_async.sync.aligned.m64n24k16.f32.bf16.bf16 {%0, %1, %2, %3, %4, %5, %6, %7, %8, %9, %10, %11}, {b0, b1, b2, b3}, d, 1, 1, 1, 0;\nwgmma.commit_group.sync.aligned;\nwgmma.wait_group.sync.aligned 1;\nmov.b32 a2, b1;\nmov.b32 a0, t0;\nmov.b32 a3, t0;\nmov.b32 a1, t1;\n"
        "ld.shared.b32 t0, [%64+7424];\nld.shared.b32 t1, [%64+7552];\nadd.s64 d, %65, 224;\nwgmma.fence.sync.aligned;\nwgmma.mma_async.sync.aligned.m64n16k16.f32.bf16.bf16 {%0, %1, %2, %3, %4, %5, %6, %7}, {a0, a1, a2, a3}, d, 1, 1, 1, 0;\nwgmma.commit_group.sync.aligned;\nwgmma.wait_group.sync.aligned 1;\nmov.b32 b2, a1;\nmov.b32 b0, t0;\nmov.b32 b3, t0;\nmov.b32 b1, t1;\n"
        "ld.shared.b32 t0, [%64+7680];\nld.shared.b32 t1, [%64+7808];\nadd.s64 d, %65, 232;\nwgmma.fence.sync.aligned;\nwgmma.mma_async.sync.aligned.m64n16k16.f32.bf16.bf16 {%0, %1, %2, %3, %4, %5, %6, %7}, {b0, b1, b2, b3}, d, 1, 1, 1, 0;\nwgmma.commit_group.sync.aligned;\nwgmma.wait_group.sync.aligned 1;\nmov.b32 a2, b1;\nmov.b32 a0, t0;\nmov.b32 a3, t0;\nmov.b32 a1, t1;\n"
        "ld.shared.b32 t0, [%64+7936];\nld.shared.b32 t1, [%64+8064];\nadd.s64 d, %65, 240;\nwgmma.fence.sync.aligned;\nwgmma.mma_async.sync.aligned.m64n8k16.f32.bf16.bf16 {%0, %1, %2, %3}, {a0, a1, a2, a3}, d, 1, 1, 1, 0;\nwgmma.commit_group.sync.aligned;\nwgmma.wait_group.sync.aligned 1;\nmov.b32 b2, a1;\nmov.b32 b0, t0;\nmov.b32 b3, t0;\nmov.b32 b1, t1;\n"
        "add.s64 d, %65, 248;\nwgmma.fence.sync.aligned;\nwgmma.mma_async.sync.aligned.m64n8k16.f32.bf16.bf16 {%0, %1, %2, %3}, {b0, b1, b2, b3}, d, 1, 1, 1, 0;\nwgmma.commit_group.sync.aligned;\nwgmma.wait_group.sync.aligned 0;\n"
        "}" : "+f"(d[0]), "+f"(d[1]), "+f"(d[2]), "+f"(d[3]), "+f"(d[4]), "+f"(d[5]), "+f"(d[6]), "+f"(d[7]), "+f"(d[8]), "+f"(d[9]), "+f"(d[10]), "+f"(d[11]), "+f"(d[12]), "+f"(d[13]), "+f"(d[14]), "+f"(d[15]), "+f"(d[16]), "+f"(d[17]), "+f"(d[18]), "+f"(d[19]), "+f"(d[20]), "+f"(d[21]), "+f"(d[22]), "+f"(d[23]), "+f"(d[24]), "+f"(d[25]), "+f"(d[26]), "+f"(d[27]), "+f"(d[28]), "+f"(d[29]), "+f"(d[30]), "+f"(d[31]), "+f"(d[32]), "+f"(d[33]), "+f"(d[34]), "+f"(d[35]), "+f"(d[36]), "+f"(d[37]), "+f"(d[38]), "+f"(d[39]), "+f"(d[40]), "+f"(d[41]), "+f"(d[42]), "+f"(d[43]), "+f"(d[44]), "+f"(d[45]), "+f"(d[46]), "+f"(d[47]), "+f"(d[48]), "+f"(d[49]), "+f"(d[50]), "+f"(d[51]), "+f"(d[52]), "+f"(d[53]), "+f"(d[54]), "+f"(d[55]), "+f"(d[56]), "+f"(d[57]), "+f"(d[58]), "+f"(d[59]), "+f"(d[60]), "+f"(d[61]), "+f"(d[62]), "+f"(d[63]) : "r"(pa), "l"(db) : "memory");
}
__device__ __forceinline__ void wgmma_rs80(float (&d)[40], uint32_t a0, uint32_t a1, uint32_t a2, uint32_t a3, uint64_t db, int sc) {
    asm volatile("{\n.reg .pred p;\nsetp.ne.b32 p, %45, 0;\n"
        "wgmma.mma_async.sync.aligned.m64n80k16.f32.bf16.bf16 {%0, %1, %2, %3, %4, %5, %6, %7, %8, %9, %10, %11, %12, %13, %14, %15, %16, %17, %18, %19, %20, %21, %22, %23, %24, %25, %26, %27, %28, %29, %30, %31, %32, %33, %34, %35, %36, %37, %38, %39}, {%40, %41, %42, %43}, %44, p, 1, 1, 1;\n}\n"
        : "+f"(d[0]), "+f"(d[1]), "+f"(d[2]), "+f"(d[3]), "+f"(d[4]), "+f"(d[5]), "+f"(d[6]), "+f"(d[7]), "+f"(d[8]), "+f"(d[9]), "+f"(d[10]), "+f"(d[11]), "+f"(d[12]), "+f"(d[13]), "+f"(d[14]), "+f"(d[15]), "+f"(d[16]), "+f"(d[17]), "+f"(d[18]), "+f"(d[19]), "+f"(d[20]), "+f"(d[21]), "+f"(d[22]), "+f"(d[23]), "+f"(d[24]), "+f"(d[25]), "+f"(d[26]), "+f"(d[27]), "+f"(d[28]), "+f"(d[29]), "+f"(d[30]), "+f"(d[31]), "+f"(d[32]), "+f"(d[33]), "+f"(d[34]), "+f"(d[35]), "+f"(d[36]), "+f"(d[37]), "+f"(d[38]), "+f"(d[39]) : "r"(a0), "r"(a1), "r"(a2), "r"(a3), "l"(db), "r"(sc));
}
__device__ __forceinline__ void wgmma_ss80(float (&d)[40], uint64_t da, uint64_t db, int sc) {
    asm volatile("{\n.reg .pred p;\nsetp.ne.b32 p, %42, 0;\n"
        "wgmma.mma_async.sync.aligned.m64n80k16.f32.bf16.bf16 {%0, %1, %2, %3, %4, %5, %6, %7, %8, %9, %10, %11, %12, %13, %14, %15, %16, %17, %18, %19, %20, %21, %22, %23, %24, %25, %26, %27, %28, %29, %30, %31, %32, %33, %34, %35, %36, %37, %38, %39}, %40, %41, p, 1, 1, 0, 1;\n}\n"
        : "+f"(d[0]), "+f"(d[1]), "+f"(d[2]), "+f"(d[3]), "+f"(d[4]), "+f"(d[5]), "+f"(d[6]), "+f"(d[7]), "+f"(d[8]), "+f"(d[9]), "+f"(d[10]), "+f"(d[11]), "+f"(d[12]), "+f"(d[13]), "+f"(d[14]), "+f"(d[15]), "+f"(d[16]), "+f"(d[17]), "+f"(d[18]), "+f"(d[19]), "+f"(d[20]), "+f"(d[21]), "+f"(d[22]), "+f"(d[23]), "+f"(d[24]), "+f"(d[25]), "+f"(d[26]), "+f"(d[27]), "+f"(d[28]), "+f"(d[29]), "+f"(d[30]), "+f"(d[31]), "+f"(d[32]), "+f"(d[33]), "+f"(d[34]), "+f"(d[35]), "+f"(d[36]), "+f"(d[37]), "+f"(d[38]), "+f"(d[39]) : "l"(da), "l"(db), "r"(sc));
}
__device__ __forceinline__ void wgmma_ss80t(float (&d)[40], uint64_t da, uint64_t db, int sc) {
    asm volatile("{\n.reg .pred p;\nsetp.ne.b32 p, %42, 0;\n"
        "wgmma.mma_async.sync.aligned.m64n80k16.f32.bf16.bf16 {%0, %1, %2, %3, %4, %5, %6, %7, %8, %9, %10, %11, %12, %13, %14, %15, %16, %17, %18, %19, %20, %21, %22, %23, %24, %25, %26, %27, %28, %29, %30, %31, %32, %33, %34, %35, %36, %37, %38, %39}, %40, %41, p, 1, 1, 1, 1;\n}\n"
        : "+f"(d[0]), "+f"(d[1]), "+f"(d[2]), "+f"(d[3]), "+f"(d[4]), "+f"(d[5]), "+f"(d[6]), "+f"(d[7]), "+f"(d[8]), "+f"(d[9]), "+f"(d[10]), "+f"(d[11]), "+f"(d[12]), "+f"(d[13]), "+f"(d[14]), "+f"(d[15]), "+f"(d[16]), "+f"(d[17]), "+f"(d[18]), "+f"(d[19]), "+f"(d[20]), "+f"(d[21]), "+f"(d[22]), "+f"(d[23]), "+f"(d[24]), "+f"(d[25]), "+f"(d[26]), "+f"(d[27]), "+f"(d[28]), "+f"(d[29]), "+f"(d[30]), "+f"(d[31]), "+f"(d[32]), "+f"(d[33]), "+f"(d[34]), "+f"(d[35]), "+f"(d[36]), "+f"(d[37]), "+f"(d[38]), "+f"(d[39]) : "l"(da), "l"(db), "r"(sc));
}
__device__ __forceinline__ void wgmma_ss8_ta(float (&d)[4], uint64_t da, uint64_t db, int sc) {
    asm volatile("{\n.reg .pred p;\nsetp.ne.b32 p, %6, 0;\n"
        "wgmma.mma_async.sync.aligned.m64n8k16.f32.bf16.bf16 {%0, %1, %2, %3}, %4, %5, p, 1, 1, 1, 0;\n}\n"
        : "+f"(d[0]), "+f"(d[1]), "+f"(d[2]), "+f"(d[3]) : "l"(da), "l"(db), "r"(sc));
}
__device__ __forceinline__ void wgmma_rs8(float (&d)[4], uint32_t a0, uint32_t a1, uint32_t a2, uint32_t a3, uint64_t db, int sc) {
    asm volatile("{\n.reg .pred p;\nsetp.ne.b32 p, %9, 0;\n"
        "wgmma.mma_async.sync.aligned.m64n8k16.f32.bf16.bf16 {%0, %1, %2, %3}, {%4, %5, %6, %7}, %8, p, 1, 1, 0;\n}\n"
        : "+f"(d[0]), "+f"(d[1]), "+f"(d[2]), "+f"(d[3]) : "r"(a0), "r"(a1), "r"(a2), "r"(a3), "l"(db), "r"(sc));
}
__device__ __forceinline__ void wgmma_rs128(float (&d)[64], uint32_t a0, uint32_t a1, uint32_t a2, uint32_t a3, uint64_t db, int sc) {
    asm volatile("{\n.reg .pred p;\nsetp.ne.b32 p, %69, 0;\n"
        "wgmma.mma_async.sync.aligned.m64n128k16.f32.bf16.bf16 {%0, %1, %2, %3, %4, %5, %6, %7, %8, %9, %10, %11, %12, %13, %14, %15, %16, %17, %18, %19, %20, %21, %22, %23, %24, %25, %26, %27, %28, %29, %30, %31, %32, %33, %34, %35, %36, %37, %38, %39, %40, %41, %42, %43, %44, %45, %46, %47, %48, %49, %50, %51, %52, %53, %54, %55, %56, %57, %58, %59, %60, %61, %62, %63}, {%64, %65, %66, %67}, %68, p, 1, 1, 1;\n}\n"
        : "+f"(d[0]), "+f"(d[1]), "+f"(d[2]), "+f"(d[3]), "+f"(d[4]), "+f"(d[5]), "+f"(d[6]), "+f"(d[7]), "+f"(d[8]), "+f"(d[9]), "+f"(d[10]), "+f"(d[11]), "+f"(d[12]), "+f"(d[13]), "+f"(d[14]), "+f"(d[15]), "+f"(d[16]), "+f"(d[17]), "+f"(d[18]), "+f"(d[19]), "+f"(d[20]), "+f"(d[21]), "+f"(d[22]), "+f"(d[23]), "+f"(d[24]), "+f"(d[25]), "+f"(d[26]), "+f"(d[27]), "+f"(d[28]), "+f"(d[29]), "+f"(d[30]), "+f"(d[31]), "+f"(d[32]), "+f"(d[33]), "+f"(d[34]), "+f"(d[35]), "+f"(d[36]), "+f"(d[37]), "+f"(d[38]), "+f"(d[39]), "+f"(d[40]), "+f"(d[41]), "+f"(d[42]), "+f"(d[43]), "+f"(d[44]), "+f"(d[45]), "+f"(d[46]), "+f"(d[47]), "+f"(d[48]), "+f"(d[49]), "+f"(d[50]), "+f"(d[51]), "+f"(d[52]), "+f"(d[53]), "+f"(d[54]), "+f"(d[55]), "+f"(d[56]), "+f"(d[57]), "+f"(d[58]), "+f"(d[59]), "+f"(d[60]), "+f"(d[61]), "+f"(d[62]), "+f"(d[63]) : "r"(a0), "r"(a1), "r"(a2), "r"(a3), "l"(db), "r"(sc));
}
__device__ __forceinline__ void wgmma_rs88(float (&d)[44], uint32_t a0, uint32_t a1, uint32_t a2, uint32_t a3, uint64_t db, int sc) {
    asm volatile("{\n.reg .pred p;\nsetp.ne.b32 p, %49, 0;\n"
        "wgmma.mma_async.sync.aligned.m64n88k16.f32.bf16.bf16 {%0, %1, %2, %3, %4, %5, %6, %7, %8, %9, %10, %11, %12, %13, %14, %15, %16, %17, %18, %19, %20, %21, %22, %23, %24, %25, %26, %27, %28, %29, %30, %31, %32, %33, %34, %35, %36, %37, %38, %39, %40, %41, %42, %43}, {%44, %45, %46, %47}, %48, p, 1, 1, 1;\n}\n"
        : "+f"(d[0]), "+f"(d[1]), "+f"(d[2]), "+f"(d[3]), "+f"(d[4]), "+f"(d[5]), "+f"(d[6]), "+f"(d[7]), "+f"(d[8]), "+f"(d[9]), "+f"(d[10]), "+f"(d[11]), "+f"(d[12]), "+f"(d[13]), "+f"(d[14]), "+f"(d[15]), "+f"(d[16]), "+f"(d[17]), "+f"(d[18]), "+f"(d[19]), "+f"(d[20]), "+f"(d[21]), "+f"(d[22]), "+f"(d[23]), "+f"(d[24]), "+f"(d[25]), "+f"(d[26]), "+f"(d[27]), "+f"(d[28]), "+f"(d[29]), "+f"(d[30]), "+f"(d[31]), "+f"(d[32]), "+f"(d[33]), "+f"(d[34]), "+f"(d[35]), "+f"(d[36]), "+f"(d[37]), "+f"(d[38]), "+f"(d[39]), "+f"(d[40]), "+f"(d[41]), "+f"(d[42]), "+f"(d[43]) : "r"(a0), "r"(a1), "r"(a2), "r"(a3), "l"(db), "r"(sc));
}
__device__ __forceinline__ void wgmma_rs128k(float (&d)[64], uint32_t a0, uint32_t a1, uint32_t a2, uint32_t a3, uint64_t db, int sc) {
    asm volatile("{\n.reg .pred p;\nsetp.ne.b32 p, %69, 0;\n"
        "wgmma.mma_async.sync.aligned.m64n128k16.f32.bf16.bf16 {%0, %1, %2, %3, %4, %5, %6, %7, %8, %9, %10, %11, %12, %13, %14, %15, %16, %17, %18, %19, %20, %21, %22, %23, %24, %25, %26, %27, %28, %29, %30, %31, %32, %33, %34, %35, %36, %37, %38, %39, %40, %41, %42, %43, %44, %45, %46, %47, %48, %49, %50, %51, %52, %53, %54, %55, %56, %57, %58, %59, %60, %61, %62, %63}, {%64, %65, %66, %67}, %68, p, 1, 1, 0;\n}\n"
        : "+f"(d[0]), "+f"(d[1]), "+f"(d[2]), "+f"(d[3]), "+f"(d[4]), "+f"(d[5]), "+f"(d[6]), "+f"(d[7]), "+f"(d[8]), "+f"(d[9]), "+f"(d[10]), "+f"(d[11]), "+f"(d[12]), "+f"(d[13]), "+f"(d[14]), "+f"(d[15]), "+f"(d[16]), "+f"(d[17]), "+f"(d[18]), "+f"(d[19]), "+f"(d[20]), "+f"(d[21]), "+f"(d[22]), "+f"(d[23]), "+f"(d[24]), "+f"(d[25]), "+f"(d[26]), "+f"(d[27]), "+f"(d[28]), "+f"(d[29]), "+f"(d[30]), "+f"(d[31]), "+f"(d[32]), "+f"(d[33]), "+f"(d[34]), "+f"(d[35]), "+f"(d[36]), "+f"(d[37]), "+f"(d[38]), "+f"(d[39]), "+f"(d[40]), "+f"(d[41]), "+f"(d[42]), "+f"(d[43]), "+f"(d[44]), "+f"(d[45]), "+f"(d[46]), "+f"(d[47]), "+f"(d[48]), "+f"(d[49]), "+f"(d[50]), "+f"(d[51]), "+f"(d[52]), "+f"(d[53]), "+f"(d[54]), "+f"(d[55]), "+f"(d[56]), "+f"(d[57]), "+f"(d[58]), "+f"(d[59]), "+f"(d[60]), "+f"(d[61]), "+f"(d[62]), "+f"(d[63]) : "r"(a0), "r"(a1), "r"(a2), "r"(a3), "l"(db), "r"(sc));
}
__device__ __forceinline__ void wgmma_rs88k(float (&d)[44], uint32_t a0, uint32_t a1, uint32_t a2, uint32_t a3, uint64_t db, int sc) {
    asm volatile("{\n.reg .pred p;\nsetp.ne.b32 p, %49, 0;\n"
        "wgmma.mma_async.sync.aligned.m64n88k16.f32.bf16.bf16 {%0, %1, %2, %3, %4, %5, %6, %7, %8, %9, %10, %11, %12, %13, %14, %15, %16, %17, %18, %19, %20, %21, %22, %23, %24, %25, %26, %27, %28, %29, %30, %31, %32, %33, %34, %35, %36, %37, %38, %39, %40, %41, %42, %43}, {%44, %45, %46, %47}, %48, p, 1, 1, 0;\n}\n"
        : "+f"(d[0]), "+f"(d[1]), "+f"(d[2]), "+f"(d[3]), "+f"(d[4]), "+f"(d[5]), "+f"(d[6]), "+f"(d[7]), "+f"(d[8]), "+f"(d[9]), "+f"(d[10]), "+f"(d[11]), "+f"(d[12]), "+f"(d[13]), "+f"(d[14]), "+f"(d[15]), "+f"(d[16]), "+f"(d[17]), "+f"(d[18]), "+f"(d[19]), "+f"(d[20]), "+f"(d[21]), "+f"(d[22]), "+f"(d[23]), "+f"(d[24]), "+f"(d[25]), "+f"(d[26]), "+f"(d[27]), "+f"(d[28]), "+f"(d[29]), "+f"(d[30]), "+f"(d[31]), "+f"(d[32]), "+f"(d[33]), "+f"(d[34]), "+f"(d[35]), "+f"(d[36]), "+f"(d[37]), "+f"(d[38]), "+f"(d[39]), "+f"(d[40]), "+f"(d[41]), "+f"(d[42]), "+f"(d[43]) : "r"(a0), "r"(a1), "r"(a2), "r"(a3), "l"(db), "r"(sc));
}
__device__ __forceinline__ void wgmma_rs80k(float (&d)[40], uint32_t a0, uint32_t a1, uint32_t a2, uint32_t a3, uint64_t db, int sc) {
    asm volatile("{\n.reg .pred p;\nsetp.ne.b32 p, %45, 0;\n"
        "wgmma.mma_async.sync.aligned.m64n80k16.f32.bf16.bf16 {%0, %1, %2, %3, %4, %5, %6, %7, %8, %9, %10, %11, %12, %13, %14, %15, %16, %17, %18, %19, %20, %21, %22, %23, %24, %25, %26, %27, %28, %29, %30, %31, %32, %33, %34, %35, %36, %37, %38, %39}, {%40, %41, %42, %43}, %44, p, 1, 1, 0;\n}\n"
        : "+f"(d[0]), "+f"(d[1]), "+f"(d[2]), "+f"(d[3]), "+f"(d[4]), "+f"(d[5]), "+f"(d[6]), "+f"(d[7]), "+f"(d[8]), "+f"(d[9]), "+f"(d[10]), "+f"(d[11]), "+f"(d[12]), "+f"(d[13]), "+f"(d[14]), "+f"(d[15]), "+f"(d[16]), "+f"(d[17]), "+f"(d[18]), "+f"(d[19]), "+f"(d[20]), "+f"(d[21]), "+f"(d[22]), "+f"(d[23]), "+f"(d[24]), "+f"(d[25]), "+f"(d[26]), "+f"(d[27]), "+f"(d[28]), "+f"(d[29]), "+f"(d[30]), "+f"(d[31]), "+f"(d[32]), "+f"(d[33]), "+f"(d[34]), "+f"(d[35]), "+f"(d[36]), "+f"(d[37]), "+f"(d[38]), "+f"(d[39]) : "r"(a0), "r"(a1), "r"(a2), "r"(a3), "l"(db), "r"(sc));
}
__device__ __forceinline__ void wgmma_rs64(float (&d)[32], uint32_t a0, uint32_t a1, uint32_t a2, uint32_t a3, uint64_t db, int sc) {
    asm volatile("{\n.reg .pred p;\nsetp.ne.b32 p, %37, 0;\n"
        "wgmma.mma_async.sync.aligned.m64n64k16.f32.bf16.bf16 {%0, %1, %2, %3, %4, %5, %6, %7, %8, %9, %10, %11, %12, %13, %14, %15, %16, %17, %18, %19, %20, %21, %22, %23, %24, %25, %26, %27, %28, %29, %30, %31}, {%32, %33, %34, %35}, %36, p, 1, 1, 1;\n}\n"
        : "+f"(d[0]), "+f"(d[1]), "+f"(d[2]), "+f"(d[3]), "+f"(d[4]), "+f"(d[5]), "+f"(d[6]), "+f"(d[7]), "+f"(d[8]), "+f"(d[9]), "+f"(d[10]), "+f"(d[11]), "+f"(d[12]), "+f"(d[13]), "+f"(d[14]), "+f"(d[15]), "+f"(d[16]), "+f"(d[17]), "+f"(d[18]), "+f"(d[19]), "+f"(d[20]), "+f"(d[21]), "+f"(d[22]), "+f"(d[23]), "+f"(d[24]), "+f"(d[25]), "+f"(d[26]), "+f"(d[27]), "+f"(d[28]), "+f"(d[29]), "+f"(d[30]), "+f"(d[31]) : "r"(a0), "r"(a1), "r"(a2), "r"(a3), "l"(db), "r"(sc));
}

__device__ __forceinline__ uint64_t mkdesc(uint32_t lo) { return ((uint64_t)0x40000040u << 32) | lo; }
template <int F> __device__ __forceinline__ uint32_t lop3(uint32_t a, uint32_t b, uint32_t c) { uint32_t r; asm("lop3.b32 %0, %1, %2, %3, %4;" : "=r"(r) : "r"(a), "r"(b), "r"(c), "n"(F)); return r; }
__device__ __forceinline__ void stg128_tag(void* p, uint32_t x, uint32_t y, uint32_t z, uint32_t u, uint32_t ep, int w) {
    stg128(p, lop3<0xB8>(x, w == 0, ep), lop3<0xB8>(y, w == 1, ep), lop3<0xB8>(z, w == 2, ep), lop3<0xB8>(u, w == 3, ep));
}
__device__ __forceinline__ uint32_t tag(uint32_t w, uint32_t ep) { asm("lop3.b32 %0, %0, 1, %1, 0xB8;" : "+r"(w) : "r"(ep)); return w; }
template <int N> __device__ __forceinline__ void pack_part(uint32_t (&p)[32], const float (&v)[N], uint32_t ep) {
#pragma unroll
    for (int i = 0; i < N / 2; i++) p[i] = (i & 3) ? pack2(v[2 * i], v[2 * i + 1]) : tag(pack2(v[2 * i], v[2 * i + 1]), ep);
#pragma unroll
    for (int i = 0; i < N / 2; i++) asm volatile("" : "+r"(p[i]));
}
__device__ __forceinline__ void st_part(uint4* p, const uint32_t* v) {
    asm volatile("{\n.reg .b64 l, h;\n.reg .b128 q;\nmov.b64 l, {%1, %2};\nmov.b64 h, {%3, %4};\nmov.b128 q, {l, h};\nst.relaxed.gpu.global.b128 [%0], q;\n}"
                 ::"l"(p), "r"(v[0]), "r"(v[1]), "r"(v[2]), "r"(v[3]) : "memory");
}
__device__ __forceinline__ void st_peer(uint32_t a, uint32_t x, uint32_t y, uint32_t z, uint32_t w, uint32_t bar) {
    asm volatile("st.async.shared::cluster.mbarrier::complete_tx::bytes.v4.b32 [%0], {%1, %2, %3, %4}, [%5];" ::"r"(a), "r"(x), "r"(y), "r"(z), "r"(w), "r"(bar) : "memory");
}
__device__ __forceinline__ int g4_block(int c, int j) { return c ? j ^ (8 - 2 * c) : 8 + (j & 1); }
__device__ __forceinline__ uint32_t recv_off(int w) { return w ? OFF_XR : OFF_REM; }
__device__ __forceinline__ uint4 ld_part(const void* p) {
    uint4 v;
    asm volatile("{\n.reg .b64 l, h;\n.reg .b128 q;\nld.relaxed.gpu.global.b128 q, [%4];\nmov.b128 {l, h}, q;\nmov.b64 {%0, %1}, l;\nmov.b64 {%2, %3}, h;\n}"
                 : "=r"(v.x), "=r"(v.y), "=r"(v.z), "=r"(v.w) : "l"(p) : "memory");
    return v;
}
__device__ __forceinline__ void ld_part4(uint4 (&u)[4], const uint4* p, int st) {
#pragma unroll
    for (int i = 0; i < 4; i++) u[i] = ld_part(p + i * st);
}
__device__ __forceinline__ uint32_t stale4(const uint4 (&u)[4], uint32_t ep) { return lop3<0x7E>(u[0].x, ep, u[1].x) | lop3<0x7E>(u[2].x, ep, u[3].x); }
__device__ __forceinline__ uint4 add2(uint4 a, uint4 b) { return make_uint4(add2(a.x, b.x), add2(a.y, b.y), add2(a.z, b.z), add2(a.w, b.w)); }
__device__ __forceinline__ uint4 fin16(uint4 v, uint4 b, uint4 c) { return make_uint4(fma2(c.x, v.x, b.x), fma2(c.y, v.y, b.y), fma2(c.z, v.z, b.z), fma2(c.w, v.w, b.w)); }
__device__ __forceinline__ uint4 scale16(float2 c, float2 d, float r0, float r1) {
    return make_uint4(pack2(c.x * r0, c.y * r0), pack2(c.x * r1, c.y * r1), pack2(d.x * r0, d.y * r0), pack2(d.x * r1, d.y * r1));
}
__device__ __forceinline__ uint32_t split2(float x) { const float h = rbf(x); return pack2(h, x - h); }
__device__ __forceinline__ uint32_t b80_desc(uint32_t dsb, uint32_t wn, uint32_t rn, uint32_t h) {
    const uint32_t wb = dsb + OFF_W + (wn & 7) * 16384 + h * 8192, rm = dsb + OFF_REM + rn * 4096 + h * 2048;
    return (wb >> 4) | ((rm - wb) << 12);
}
constexpr int64_t B80_STEP = 128 - (126 << 16), B80_HALF = 512 - (384 << 16);
constexpr uint32_t ring_mask(int L) {
    uint32_t m = 0;
    for (int i = L; i < 20; i++) m |= (uint32_t)(i >= 20 - L || !((i - L) & 1)) << i;
    return m;
}
constexpr int pair_pos(int w, int i) { return w ? (i < 5 - LEAD2 ? LEAD2 + 2 * i : 5 + i) : (i < LEAD2 ? i : 2 * i - LEAD2 + 1); }
constexpr uint32_t pair_mask() { uint32_t m = 0; for (int i = 0; i < 5; i++) m |= 3u << (2 * pair_pos(1, i)); return m; }
constexpr uint32_t pair_slots(int w) { uint32_t m = 0; for (int i = 0; i < 5; i++) m |= (uint32_t)((2 + pair_pos(w, i)) & 3) << (2 * i); return m; }
constexpr uint32_t M0 = ring_mask(LEAD1), M1 = pair_mask(), M2 = ring_mask(XLEAD), P0S = pair_slots(0), P1S = pair_slots(1);
__device__ __forceinline__ uint32_t ring_pos(int w, int n, int L) { return w ? (n < 10 - L ? L + 2 * n : 10 + n) : (n < L ? n : 2 * n - L + 1); }
__device__ __forceinline__ int g1_block(int n, int j) { return n < 5 ? 2 * n + (j & 1) : 2 * n - 9 - (j & 1); }

__device__ __forceinline__ int g2_block(int n) { return (0x9874326510ull >> (4 * n)) & 15; }
__device__ __forceinline__ int g3_block(int n, int j) { return n ? n - (n <= j) : j; }
struct Tile { int e, w, kb; uint32_t at; };
__device__ __forceinline__ Tile ring_tile(int n, int grp, int j) {
    const int e = (n >= 20) + (n >= 40), i = n - 20 * e;
    const uint32_t M = e == 0 ? M0 : e == 1 ? M1 : M2;
    const int w = (M >> i) & 1, c = __popc(M & ((1u << i) - 1)), kb = w ? c : i - c, tile = grp + 16 * w;
    return {e, w, kb, 64u * (e == 0 ? tile + (g1_block(kb, j) << 16) : e == 1 ? g2_block(kb) + (tile << 16) : (10 * tile + g3_block(kb, j)) << 16)};
}
__device__ __forceinline__ void load_tile(const Maps& mp, uint32_t dst, int e, uint32_t at, uint32_t bar) {
    mbar_expect(bar, 8192);
    tma_ld2(dst, &mp.x[e], at & 0xffff, at >> 16, bar);
}

template <int OCT>
__device__ __forceinline__ void gemv_tile(float (&d)[4], uint32_t a, uint32_t b, int kb0) {
    uint32_t alo = ((a & 0x3FFFF) >> 4) | 0x10000u, blo_ = ((b & 0x3FFFF) >> 4) | (OCT << 16);
#pragma unroll 1
    for (int s = 0; s < 20; s += 4) {
        const int kb = kb0 + (s >> 2);
        const uint32_t bk = blo_ + (OCT == 7 ? (kb & 1) * 288 + (kb >> 1) * 56 : kb * 64);
        wg_fence();
#pragma unroll
        for (int q = 0; q < 4; q++) wgmma_ss8_ta(d, mkdesc(alo + (s + q) * 128), ((uint64_t)8 << 32) | (bk + q * 2 * OCT), s + q);
        wg_commit();
    }
    wg_wait<0>();
    reg_fence(d);
}

__device__ __forceinline__ void flush_tile(uint32_t st, bf16* dst, int u) {
#pragma unroll
    for (int i = 0; i < 2; i++) {
        const int idx = u + 320 * i, row = idx >> 3, c = idx & 7;
        stg128(dst + (size_t)row * S_ + 8 * c, lds128(st + row * 128 + ((c ^ ((row >> 1) & 7)) << 4)));
    }
}

__device__ __forceinline__ int tid_now() { int t; asm volatile("mov.u32 %0, %%tid.x;" : "=r"(t)); return t; }
__device__ __forceinline__ float zscale(float c) { return c == 0.f ? 0x1p-30f : c; }
__device__ __forceinline__ bool bar_any(int id, bool p) {
    uint32_t r;
    asm volatile("{\n.reg .pred a, b;\nsetp.ne.u32 a, %2, 0;\nbarrier.red.or.pred.aligned b, %1, 128, a;\nselp.u32 %0, 1, 0, b;\n}" : "=r"(r) : "r"(id), "r"((uint32_t)p) : "memory");
    return r != 0;
}

__global__ void __cluster_dims__(2, 1, 1) __launch_bounds__(NTHR, 1) fused_kernel(const __grid_constant__ Ptrs pp, bf16* __restrict__ out, const __grid_constant__ Maps mp) {
    extern __shared__ __align__(1024) uint8_t smem_raw[];
    const uint32_t sb = s2u(smem_raw), bars = sb + M_BAR, dsb = sb & 0x3FFFF;
    const int id = blockIdx.x, warp = __shfl_sync(0xffffffffu, (int)threadIdx.x >> 5, 0), wg = warp >> 2;
    const uint32_t c0 = clock_lo();
#define TIDS const int tid = tid_now(), lane = tid & 31, wt = tid & 127, g = lane >> 2, t = lane & 3; (void)wt; (void)g; (void)t;
    TS(threadIdx.x == 0, 0) TG(threadIdx.x == 0, 62)

    if (id >= 128) {
        TIDS
        if (sb & 1023) __trap();
        const int hs = id - 128;
        constexpr int H_B = 204800;
        static_assert(H_B + TAB_BYTES + 8 * VEC_BYTES <= OFF_M, "helper map");
        if (warp < 10 && elect()) { mbar_init(bars + warp * 8, 1); mbar_init(bars + 80 + warp * 8, 1); asm volatile("fence.mbarrier_init.release.cluster;" ::: "memory"); }
        __syncthreads();
        const uint32_t e0 = ld_cold(&g_epoch);
        wait_clock(c0, HELP_T);
        uint4 wr[10];
#pragma unroll
        for (int u = 0; u < 10; u++) wr[u] = ldg128(((hs >> 1) ? pp.w2 : pp.w1) + (size_t)(320 * (hs & 1) + (tid >> 4) + 32 * u) * D_ + 512 + 8 * (tid & 15));
        {
            const int r = tid >> 4, c = tid & 15;
            uint4* dst[2];
#pragma unroll
            for (int e = 0; e < 2; e++) {
                const int p = !(hs >> 1) ? r : e && (hs & 1) ? (r & ~14) | ((r & 6) << 1) | ((r & 8) >> 2) : (r & ~30) | ((r & 6) << 2) | ((r & 24) >> 2);
                dst[e] = &g_wr[((hs >> 1) * 8 + (c >> 1)) * 10 * 128 + (p & 15) * 8 + ((2 * (p >> 4) + (c & 1)) ^ (p & 7))];
            }
#pragma unroll
            for (int u = 0; u < 10; u++) stg128(reinterpret_cast<uint4*>(reinterpret_cast<uintptr_t>(dst[u >= 6]) ^ (64 * (u & 1))) +
                       ((hs >> 1) ? (0x9873265410ull >> (4 * (5 * (hs & 1) + (u >> 1)))) & 15 : 5 * (hs & 1) + (u >> 1)) * 128, wr[u]);
        }
        __syncthreads();
        if (warp == 0) signal_cnt(&g_cnt.wr[0], lane, 1);
        __syncthreads();
        if (warp < 5 && elect()) {
            const int un = 5 * hs + warp;
            mbar_expect(bars + warp * 8, 40960);
            tma_ld2(sb + warp * 40960, &mp.w1h, 64 * (un >> 1), 320 * (un & 1), bars + warp * 8);
            tma_ld2(sb + warp * 40960 + 20480, &mp.w1h, 64 * (un >> 1), 320 * (un & 1) + 160, bars + warp * 8);
        }
        if (tid < 320) {
            const uint4* gm = reinterpret_cast<const uint4*>(g_mod + 3 * D_) + tid;
            const unsigned epoch = e0 + 1;
            uint4 r[6];
            unsigned it = 0;
            for (;;) {
                uint32_t bad = 0;
#pragma unroll
                for (int i = 0; i < 6; i++) { r[i] = ld_part(gm + (i >> 1) * (D_ / 2) + (i & 1) * 3 * D_); bad |= (r[i].y ^ epoch) | (r[i].w ^ epoch); }
                if (__all_sync(~0u, !bad)) break;
                if (++it > SPIN_LIMIT) SPIN_FAIL(54)
            }
            uint32_t mv[3];
#pragma unroll
            for (int i = 0; i < 3; i++) mv[i] = pack2(__uint_as_float(r[2 * i].x) + __uint_as_float(r[2 * i + 1].x), __uint_as_float(r[2 * i].z) + __uint_as_float(r[2 * i + 1].z));
            const uint32_t sw2 = mv[0], cw = add2(mv[1], 0x3f803f80u), gw = mv[2];
            const float c0 = blo(cw), c1 = bhi(cw), s0 = blo(sw2), s1 = bhi(sw2);
            const float i0 = __frcp_rn(zscale(c0)), i1 = __frcp_rn(zscale(c1));
            const uint32_t ci = pack2(i0, i1), cq = pack2(i0 * i0, i1 * i1);
            const uint32_t a = sb + H_B + ((tid >> 5) & 1) * 4608 + (tid >> 6) * 896 + ((tid >> 2) & 7) * 112 + (tid & 3) * 4;
            sts32(a, ci); sts32(a + 16, pack2(i0 - blo(ci), i1 - bhi(ci)));
            sts32(a + 32, cq); sts32(a + 48, pack2(fmaf(i0, i0, -blo(cq)), fmaf(i1, i1, -bhi(cq))));
            sts32(a + 64, cw); sts32(a + 80, sw2); sts32(a + 96, 0x3f803f80u);
            if ((tid & ~35) == 284) sts32(a + 112, 0);
            const uint32_t v = sb + H_B + TAB_BYTES + (tid < 256 ? (tid >> 5) * VEC_BYTES + (tid & 31) * 8 : ((tid - 256) >> 3) * VEC_BYTES + 256 + (tid & 7) * 8);
            sts64f(v, blo(gw), bhi(gw)); sts64f(v + 320, c0, c1); sts64f(v + 640, s0, s1); sts64f(v + 960, i0, i1);
            float k[5] = {c0 + c1, s0 + s1, fmaf(c0, c0, c1 * c1), fmaf(c0, s0, c1 * s1), fmaf(s0, s0, s1 * s1)};
#pragma unroll 1
            for (int o = 16; o; o >>= 1) {
#pragma unroll
                for (int e = 0; e < 5; e++) k[e] += __shfl_xor_sync(~0u, k[e], o);
            }
            const uint32_t ks = sb + H_B + TAB_BYTES + (lane & 7) * VEC_BYTES + 1280 + (warp >> 1) * 32;
            if ((warp & 1) && lane < 8) { sts128f(ks, k[0], k[1], k[2], k[3]); sts128f(ks + 16, k[4], 0.f, 0.f, 0.f); }
            bar_sync(3, 320);
            if (!(warp & 1) && lane < 8) {
                const float4 o = lds128f(ks);
                sts128f(ks, k[0] + o.x, k[1] + o.y, k[2] + o.z, k[3] + o.w); sts32(ks + 16, __float_as_uint(k[4] + __uint_as_float(lds32(ks + 16))));
            }
            fence_async_smem();
        }
        __syncthreads();
        if (hs == 0 && warp == 15 && elect()) {
            asm volatile("cp.async.bulk.global.shared::cta.bulk_group [%0], [%1], %2;\ncp.async.bulk.commit_group;\ncp.async.bulk.wait_group 0;"
                         ::"l"(g_tab), "r"(sb + H_B), "n"(TAB_BYTES + 8 * VEC_BYTES) : "memory");
            asm volatile("red.release.gpu.global.add.u32 [%0], 1;" ::"l"(&g_cnt.tab[0]) : "memory");
        }
        __syncwarp();
#pragma unroll 1
        for (int i = wg; i < 20; i += 4) {
            const int r = i / 5, b = i - 5 * r, un = 5 * hs + b, u3 = 20 * r + un;
            auto refill = [&](int e, int u, uint32_t fb) {
                mbar_expect(fb, 40960);
                tma_ld2(sb + e * 40960, &mp.w3h, 64 * (u >> 1), 320 * (u & 1), fb);
                tma_ld2(sb + e * 40960 + 20480, &mp.w3h, 64 * (u >> 1), 320 * (u & 1) + 160, fb);
            };
            if (i > 4 && i < 9) {
                bar_sync(1, 512);
                if (warp == 0) {
                    signal_cnt(&g_cnt.uv[0], lane, 1);
                    if (elect()) {
#pragma unroll 1
                        for (int e = 0; e < 5; e++) refill(e, 5 * hs + e, bars + (5 + e) * 8);
                        l2_prefetch(pp.w2 + (size_t)160 * hs * D_, 160 * D_ * 2);
                    }
                    __syncwarp();
                }
            }
            mbar_wait(bars + i * 8, 0);
            float d[4];
            gemv_tile<7>(d, sb + b * 40960, sb + H_B, 5 * (un & 1));
            const int col = 16 * (warp & 3) + g;
            float* dst = r ? g_cs3 + (un & 1) * 1920 + 64 * ((u3 >> 1) - 10) + col : g_uv + (un & 1) * 3 * D_ + 2 * D_ + 64 * (un >> 1) + col;
            if (t == 3) { dst[0] = d[0]; dst[8] = d[2]; }
            if (r == 0 && t == 2) { dst[-2 * D_] = d[0]; dst[8 - 2 * D_] = d[2]; dst[-D_] = d[1]; dst[8 - D_] = d[3]; }
            if (r == 1 || r == 2) {
                bar_sync(4 + wg, 128);
                if (wt == 0) refill(b, u3, bars + (i + 5) * 8);
            }
        }
        __syncthreads();
        if (warp == 0) signal_cnt(&g_cnt.cs[0], lane, 1);
        if (tid == 511) l2_prefetch(pp.w4 + (size_t)432 * hs * D_, 432 * D_ * 2);
        for (uint32_t it = 0; ld_cold(&g_cnt.cs[0]) < 4;) { if (++it > SPIN_LIMIT) SPIN_FAIL(47) }
        asm volatile("fence.acquire.gpu;" ::: "memory");
        if (tid < 432) {
            const int jj = 2 * hs + (tid >= 216), c = tid % 216;
            const float* src = g_cs3 + (c < 192 ? 192 * jj + c : 1344 + 24 * jj + c);
            const uint32_t s = split2(ldcg32f(src) + ldcg32f(src + 1920));
            stg128(&g_cs3b[432 * hs + tid], s, s & 0xffffu, 0, 0);
        }
        __syncthreads();
        if (warp == 0) signal_cnt(&g_cnt.cs2[0], lane, 1);
        if (tid == 0 && hs == 3) {
            uint32_t it = 0;
            while (ld_cold(&g_epoch) == e0) { __nanosleep(256); if (++it > (1u << 20)) SPIN_FAIL(48) }
        }
        return;
    }

    if (elect()) {
        if (warp == 15) {
            mbar_init(bars + B_IN * 8, 1); mbar_init(bars + B_IN * 8 + 8, 1);
            asm volatile("fence.mbarrier_init.release.cluster;" ::: "memory");
            mbar_expect(bars + B_IN * 8, 131 * 160);
            tma_ld2(sb + OFF_KIN, &mp.k, 80 * (id & 7), 64 * (id >> 3) - 3, bars + B_IN * 8);
            tma_ld2(sb + OFF_VIN, &mp.v, 80 * (id & 7), 64 * (id >> 3), bars + B_IN * 8);
        } else if (warp < 13) {
            const uint32_t n = (0x4C11111111881ull >> (4 * warp)) & 15;
#pragma unroll
            for (int i = 0; i < 4; i++) mbar_init(bars + warp * 64 + i * 8, n);
            if (warp == 11) { mbar_init(bars + B_XFREE * 8, 16); mbar_init(bars + B_OWN * 8, 8); }
            else {
#pragma unroll
                for (int i = 4; i < 8; i++) mbar_init(bars + warp * 64 + i * 8, n);
            }
            asm volatile("fence.mbarrier_init.release.cluster;" ::: "memory");
        }
    }
    asm volatile("" ::"l"(pp.s), "l"(pp.c), "l"(out));
    TR4((threadIdx.x & 31) == 0, warp)
    const int pr = id >> 1;
    const int grp = pr < 4 ? 15 : pr < 36 ? (pr - 4) & 7 : 8 + (pr - 36) % 7;
    const int j = 2 * (pr < 4 ? pr : pr < 36 ? (pr - 4) >> 3 : (pr - 36) / 7) + (id & 1);

    if (wg == 3) {
        TIDS
        const int sw = warp - 12;
        uint32_t ep = ld_cold(&g_epoch);
        TR4(lane == 0, 20 + sw)
        __syncthreads();
        TR4(lane == 0, 30 + sw)
        asm volatile("barrier.cluster.arrive.relaxed.aligned;" ::: "memory");
        if (sw == 0) {
#pragma unroll 1
            for (int n = 0; n < 12; n++) {
                wait_clock(c0, PF_T0 + PF_DT * n);
                if (elect()) l2_prefetch(n < 4 ? (const char*)pp.q + id * 20480 + n * 5120 : (const char*)pp.w_mod + id * 38400 + (n - 4) * 4800, n < 4 ? 5120 : 4800);
            }
        } else if (sw == 1) {
            wait_clock(c0, T_SSM);
            if (elect()) {
                mbar_expect(bars + B_SSM * 8, 20480);
                bulk_ld(sb + OFF_SSM, pp.ssm_k + (size_t)5 * id * S_, 20480, bars + B_SSM * 8);
            }
            mbar_spin(bars + B_KVS * 8, 0);
            signal_cnt(&g_cnt.kv[(id & 7) * 32], lane, 1, true);
            TS(lane == 0, 2)
            mbar_spin(bars + B_RAW * 8, 0);
            if (elect()) {
                mbar_expect(bars + B_QIN * 8, 20480);
                tma_ld3(sb + OFF_QIN, &mp.q, 0, 16 * id, 0, bars + B_QIN * 8);
            }
        } else if (sw == 2) {
            if (elect()) {
#pragma unroll 1
                for (int i = 2; i < (int)(sizeof(Maps) / sizeof(CUtensorMap)); i++) asm volatile("prefetch.tensormap [%0];" ::"l"(&mp.k + i) : "memory");
#pragma unroll 1
                for (int i = B_SUMS; i < B_LAND; i++) mbar_expect(bars + i * 8, i < B_RECV ? 2048 : (i & 3) < 3 ? 8192 : 3072);
            }
            wait_cnt(&g_cnt.kv[(id >> 4) * 32], 16, true);
            TS(lane == 0, 4)
            if (elect()) {
                mbar_expect(bars + B_RAW * 8, 12288);
                mbar_expect(bars + B_RAW2 * 8, 8192);
#pragma unroll
                for (int c = 0; c < 5; c++) bulk_ld(sb + OFF_CH + c * CH_BYTES, g_kvT + (size_t)(5 * id + c) * S_, 4096, bars + (c < 3 ? B_RAW : B_RAW2) * 8);
            }
            mbar_spin(bars + B_BK * 8, 0);
            mbar_spin(bars + B_QIN * 8, 0);
            if (id < 120 && elect()) {
                mbar_expect(bars + B_WM * 8, 40960);
                tma_ld2(sb + OFF_WM, &mp.wmod, 64 * pr, 320 * (id & 1), bars + B_WM * 8);
                tma_ld2(sb + OFF_WM + 20480, &mp.wmod, 64 * pr, 320 * (id & 1) + 160, bars + B_WM * 8);
            }
            TS(lane == 0, 57)
        } else {
            wait_clock(c0, T_KVB);
            if (elect()) {
                mbar_expect(bars + (B_IN + 1) * 8, 131 * 160);
                tma_ld2(sb + OFF_KIN + 10752, &mp.k, 80 * (id & 7), 64 * (id >> 3) + 1021, bars + (B_IN + 1) * 8);
                tma_ld2(sb + OFF_VIN + 10240, &mp.v, 80 * (id & 7), 64 * (id >> 3) + 1024, bars + (B_IN + 1) * 8);
            }
            TS(lane == 0, 53)
            if (lane == 0) sts32(sb + M_EP, ep + 1);
            sts32(sb + M_NUL + lane * 4, 0);
#pragma unroll 1
            for (int i = 0; i < 10; i++) sts128(sb + OFF_Z + i * 512 + lane * 16, 0, 0, 0, 0);
            __syncwarp();
#pragma unroll 1
            for (int i = lane; i < 160; i += 32) {
                const uint32_t c = ldg32(pp.c + 320 * (id & 1) + 2 * i);
                sts32(sb + OFF_Z + (i >> 2) * 128 + (i & 3) * 4, pack2(silu(blo(c)), silu(bhi(c))));
            }
            fence_async_smem();
            for (uint32_t ph = 0, again = 1; again; ph ^= 1) {
                mbar_spin(bars + B_RAW2 * 8, ph);
                uint32_t bad = 0;
#pragma unroll
                for (int i = 0; i < 8; i++) bad |= lop3<0x7E>(lds32(sb + OFF_CH + 3 * CH_BYTES + i * 512 + lane * 16), ~ep, lds32(sb + OFF_CH + 4 * CH_BYTES + i * 512 + lane * 16));
                again = __any_sync(~0u, bad & 1);
                if (again && elect()) {
                    mbar_expect(bars + B_RAW2 * 8, 8192);
#pragma unroll
                    for (int c = 3; c < 5; c++) bulk_ld(sb + OFF_CH + c * CH_BYTES, g_kvT + (size_t)(5 * id + c) * S_, 4096, bars + B_RAW2 * 8);
                }
            }
            if (elect()) mbar_arrive(bars + B_RAW3 * 8);
        }
        {
            mbar_spin(bars + B_QIN * 8, 0);
            asm volatile("add.u32 %0, %0, 1;" : "+r"(ep));
            TS(wt == 0, 54)
            const int tk = 8 * ((lane >> 1) & 1) + 2 * (lane >> 3) + (lane & 1), ck = 4 * (sw & 1) + ((lane >> 1) & 2);
            const uint32_t src = sb + OFF_QIN + (sw >> 1) * 2048 + tk * 128;
            bf16* dst = g_qT + (size_t)id * 16 * D_ + (32 * sw + 8 * (t & 2) + g) * 16 + 8 * (t & 1);
constexpr int QU = Q_UNROLL;
#pragma unroll QU
            for (int i = 0; i < 5; i++) {
                uint32_t r[8];
                ldsm4t(src + i * 4096 + ((ck ^ (tk & 7)) << 4), r[0], r[1], r[2], r[3]);
                ldsm4t(src + i * 4096 + (((ck + 1) ^ (tk & 7)) << 4), r[4], r[5], r[6], r[7]);
                stg128(dst + i * 2048, tag(r[0], ep), r[1], r[2], r[3]);
                stg128(dst + i * 2048 + 128, tag(r[4], ep), r[5], r[6], r[7]);
            }
            float s1 = 0.f, s2 = 0.f;
#pragma unroll 2
            for (int i = 0; i < 10; i++) {
                const uint4 w4 = lds128(sb + OFF_QIN + i * 2048 + wt * 16);
                const uint32_t w[4] = {w4.x, w4.y, w4.z, w4.w};
#pragma unroll
                for (int e = 0; e < 4; e++) { const float a = blo(w[e]), b = bhi(w[e]); s1 += a + b; s2 = fmaf(a, a, fmaf(b, b, s2)); }
            }
#pragma unroll
            for (int o = 1; o < 8; o *= 2) { s1 += __shfl_xor_sync(~0u, s1, o); s2 += __shfl_xor_sync(~0u, s2, o); }
            s1 *= 1.f / D_;
            uint32_t rs = pack2(rsqrtf(fmaxf(s2 * (1.f / D_) - s1 * s1, 0.f) + 1e-5f), 0.f);
            if (lane < 8) rs = tag(rs, ep);
            rs = pack2(blo(rs), -s1 * blo(rs));
            const uint32_t sel = lane ? 0x7632 : 0x5410;
            const uint32_t a0 = __shfl_sync(~0u, rs, 0), a1 = __shfl_sync(~0u, rs, 8), a2 = __shfl_sync(~0u, rs, 16), a3 = __shfl_sync(~0u, rs, 24);
            if (lane < 2) stg64(g_qst + lane * S_ + 16 * id + 4 * sw, tag(__byte_perm(a0, a1, sel), ep), __byte_perm(a2, a3, sel));
            TS(wt == 0, 55)
        }
        bar_sync(6, 128);
        if (sw == 3) {
            signal_cnt(&g_cnt.q[(lane & 3) * 32], lane, 4, true);
            TS(lane == 0, 3)
        }
        asm volatile("setmaxnreg.dec.sync.aligned.u32 " STR(REG_SVC) ";");
        asm volatile("barrier.cluster.wait.aligned;" ::: "memory");
        if (sw == 1) {
            mbar_spin(bars + B_XS * 8, 0);
            signal_cnt(&g_cnt.x[(lane & 3) * 32], lane, 4, true);
            TS(lane == 0, 20)
        }
        if (sw == 1 || sw == 2) {
            mbar_spin(bars + B_XS * 8, 0);
            fence_async_smem();
            int n = sw & 1;
            const uint32_t plan = ring_tile(min(2 * lane + n, 59), grp, j).at;
#pragma unroll 1
            for (int s = 0; s < 7; s++) {
                const int e = (s >= 2) + (s >= 5), end = (0ull + LEAD1 + (20 << 8) + (24 << 16) + ((20ull + 2 * LEAD2) << 24) + (40ull << 32) + ((40ull + XLEAD) << 40) + (60ull << 48)) >> (8 * s) & 255;
                if (s == 1 || s == 4 || s == 6) mbar_spin(bars + (B_GATE + 2 + e) * 8, !e);
                else if (s != 3 || grp == 15) {
                    wait_cnt(s == 0 ? &g_cnt.x[(id & 3) * 32] : s == 5 ? &g_cnt.g2[grp * 32] : &g_cnt.g1[(s == 2 ? min(max(grp - 1 + min(lane, 2), 0), 15) : 16) * 32], e ? 32 : 128, true);
                    TS(lane == 0 && sw == 2 && s != 3, 26 + 2 * e)
                }
#pragma unroll 1
                for (; n < end; n += 2) {
                    const uint32_t at = __shfl_sync(~0u, plan, n >> 1);
                    mbar_spin(bars + (B_XEMPTY + (n & 7)) * 8, ((n >> 3) & 1) ^ 1);
                    TR2(lane == 0 && n < 40, 20 + n)
                    if (elect()) {
                        if (n == 40 || n == 40 + XLEAD) {
                            mbar_arrive(bars + (B_LAND + (n & 7)) * 8);
                            asm volatile("mbarrier.arrive.shared.b64 _, [%0], 8;" ::"r"(bars + (B_XEMPTY + (n & 7)) * 8) : "memory");
                        } else load_tile(mp, sb + OFF_XR + (n & 7) * 8192, e, at, bars + (B_LAND + (n & 7)) * 8);
                    }
                }
            }
            if (sw == 1) { if (elect()) mbar_arrive(bars + (B_GATE + 5) * 8); return; }
            mbar_spin(bars + (B_GATE + 5) * 8, 0);
            mbar_spin(bars + B_VEC3 * 8, 0);
            unsigned old = 0;
            asm volatile("{\n.reg .pred P;\nsetp.eq.s32 P, %2, 0;\n@P atom.relaxed.gpu.global.add.u32 %0, [%1], %3;\n}" : "+r"(old) : "l"(&g_cnt.done[0]), "r"(lane), "r"(1) : "memory");
            if (__any_sync(~0u, old == 127)) {
#pragma unroll 1
                for (int i = lane; i < (int)(sizeof(Counters) / 128); i += 32) reinterpret_cast<unsigned*>(&g_cnt)[i * 32] = 0;
                signal_cnt(&g_epoch, lane, 1, true);
            }
        } else if (sw == 0) {
            wait_cnt(&g_cnt.wr[0], 4);
            mbar_spin(bars + B_QRDY * 8, 0);
            const uint32_t wf = bars + B_WFULL * 8, we = bars + B_WEMPTY * 8;
#pragma unroll 1
            for (int n = 0; n < 5; n++) {
                if (n == 3) { mbar_spin(bars + B_XS * 8, 0); fence_async_smem(); }
                TR2(lane == 0, 70 + n)
                if (elect()) {
                    const uint32_t fb = wf + n * 8, dst = sb + OFF_W + n * 16384;
                    mbar_expect(fb, 20480);
#pragma unroll 1
                    for (int h = 0; h < 2; h++) {
                        const int kb = g1_block(2 * n + h, j);
                        tma_ld2(dst + h * 8192, &mp.w1, 64 * j, 64 * kb, fb);
                        bulk_ld(sb + OFF_REM + n * 4096 + h * 2048, &g_wr[(j * 10 + kb) * 128], 2048, fb);
                    }
                }
            }
            mbar_spin(bars + B_GATE * 8, 0);
#pragma unroll 1
            for (int i = -3; i < 5; i++) {
                const int n = i < 0 ? 8 + i : 5 + i;
                const uint32_t fb = wf + (n & 7) * 8;
                if (i >= 0) mbar_spin(we + i * 8, 0);
                TR2(lane == 0 && i >= 0, 70 + n)
                if (elect()) {
                    if (i < 0 || i >= 3) {
                        mbar_expect(fb, 20480);
#pragma unroll 1
                        for (int h = 0; h < 2; h++) tma_ld5(sb + OFF_W + (n & 7) * 16384 + h * 8192, n < 9 ? &mp.w2a : &mp.w2b, 64 * j, n < 9 ? 2 * g2_block(2 * n - 10 + h) : 4 * h, fb);
                    }
                    if (i >= 0) bulk_ld(sb + OFF_REM + i * 4096, &g_wr[((8 + j) * 10 + 2 * i) * 128], 4096, fb);
                }
            }
            mbar_spin(bars + (B_GATE + 1) * 8, 0);
#pragma unroll 1
            for (int n = 10; n < 30; n++) {
                if (n == W3_N2) mbar_spin(bars + (B_GATE + 2) * 8, 0);
                mbar_spin(we + (n & 7) * 8, ((n >> 3) & 1) ^ 1);
                TR2(lane == 0, 70 + n)
                if (elect()) {
                    const uint32_t dst = sb + OFF_W + (n & 7) * 16384, fb = wf + (n & 7) * 8;
                    mbar_expect(fb, 13824);
                    const int row = 64 * g3_block((n - 10) >> 1, j) + 32 * (n & 1);
                    tma_ld3(dst, &mp.w3a, 0, row, 3 * j, fb);
                    tma_ld2(dst + 12288, &mp.w3b, 1536 + 24 * j, row, fb);
                }
            }
            mbar_spin(we + 6 * 8, 0);
            mbar_spin(bars + B_VEC3 * 8, 0);
            if (elect()) { mbar_expect(wf + 6 * 8, 3456); bulk_ld(sb + OFF_W + 6 * 16384, &g_cs3b[216 * j], 3456, wf + 6 * 8); }
#pragma unroll 1
            for (int n = 31; n < 50; n++) {
                const int e = n < 38 ? 4 : (n - 38) & 3, m0 = n == 35, m1 = e == 3 ? -1 : m0 | (e == 1), rem = 96 + 3 * (j >> 1);
                const int c1_ = j ^ (n < 38 ? 6 : 4 >> ((n - 38) >> 2) & 6), c0_ = n < 38 ? 8 + (j & 1) : c1_;
                const int f = (0xC840A80C204ull >> (4 * min(n - 31, e + 7))) & 15;
                const int r0 = m0 ? rem : 6 * (j ^ (f >> 3)) + (f & 6), r1 = m1 ? rem : r0 + (n < 38 ? 0 : 2);
                mbar_spin(we + (n & 7) * 8, ((n >> 3) & 1) ^ 1);
                if (elect()) {
                    const uint32_t dst = sb + OFF_W + (n & 7) * 16384, fb = wf + (n & 7) * 8;
                    mbar_expect(fb, m1 < 0 ? 8192 : 16384 - 2048 * (m0 + m1));
                    tma_ld2(dst, &mp.w4[m0], 64 * c0_, r0 * (32 >> m0), fb);
                    if (m1 >= 0) tma_ld2(dst + 8192, &mp.w4[m1], 64 * c1_, r1 * (32 >> m1), fb);
                }
            }
        } else {
            {
                wait_cnt(&g_cnt.tab[0], 1);
                mbar_spin(bars + B_QRDY * 8, 0);
                if (elect()) {
                    mbar_expect(bars + B_TAB * 8, TAB_BYTES / 2 + VEC_BYTES);
                    bulk_ld(sb + OFF_TAB, g_tab + (j & 1) * (TAB_BYTES / 32), TAB_BYTES / 2, bars + B_TAB * 8);
                    bulk_ld(sb + M_GB, g_tab + (TAB_BYTES + j * VEC_BYTES) / 16, VEC_BYTES, bars + B_TAB * 8);
                }
                TS(lane == 0, 5)
            }
            wait_cnt(&g_cnt.uv[0], 4);
#pragma unroll 1
            for (int c = lane; c < 80; c += 32) {
                const float* src = g_uv + (c < 64 ? 64 * j + c : 448 + 16 * j + c);
                const uint32_t u = split2(ldcg32f(src) + ldcg32f(src + 3 * D_)), v = split2(ldcg32f(src + D_) + ldcg32f(src + 4 * D_));
                const uint32_t s = split2(ldcg32f(src + 2 * D_) + ldcg32f(src + 5 * D_));
                sts128(sb + OFF_F1 + c * 16, u, __byte_perm(u, v, 0x5410), __byte_perm(v, 0, 0x1032), s);
                sts128(sb + M_F1 + c * 16, s & 0xffffu, 0, 0, 0);
            }
            fence_async_smem();
            warp_arrive(bars + B_VEC * 8);
            TS(lane == 0, 9)
#pragma unroll 1
            for (int e = 1; e < 3; e++) {
                wait_cnt(e == 1 ? &g_cnt.g1[min(grp + 15 + min(lane, 2), 31) * 32] : &g_cnt.g2[(grp + 16) * 32], 32, true);
                if (elect()) mbar_arrive(bars + (B_GATE + 2 + e) * 8);
                TS(lane == 0, 27 + 2 * e)
            }
            wait_cnt(&g_cnt.cs2[0], 4);
            if (elect()) mbar_arrive(bars + B_VEC3 * 8);
            TS(lane == 0, 19)
        }
        return;
    }

    {
        uint32_t ep;
        {
            TIDS
            ep = ld_cold(&g_epoch);
            const int cp = (tid + 16) % 40, cp1 = tid % 40;
            const uint4 sh0 = ldg128(pp.shift_k + (80 * (id & 7) + 2 * cp1) * 4), sh1 = ldg128(pp.shift_k + (80 * (id & 7) + 2 * cp) * 4);
            uint32_t dd;
            asm volatile("ld.global.nc.u16 %0, [%1];" : "=r"(dd) : "l"(pp.ssm_D + 5 * id + min(wg + 3 * lane, 4)));
            TR4(lane == 0, 40 + warp)
            __syncthreads();
            asm volatile("barrier.cluster.arrive.relaxed.aligned;" ::: "memory");
            asm volatile("add.u32 %0, %0, 1;" : "+r"(ep));
#pragma unroll 1
            for (int hw = 0; hw < 2; hw++) {
                if ((unsigned)(warp - 2 * hw) >= 10) continue;
                const int u = tid - 64 * hw;
                const int c = hw ? cp : cp1, oc = u / 40, line = 31 - 16 * hw - (id >> 3);
                const uint4 sh = hw ? sh1 : sh0;
                const uint32_t st = sb + OFF_ST + hw * 10240, sta = st + c * 256 + ((((6 - 2 * (oc & 3)) ^ (oc >> 2) ^ (line & 1)) ^ (c & 7)) << 4), in = oc * 1280 + c * 4;
                const uint32_t f0 = __byte_perm(sh.x, sh.z, 0x5410), f1 = __byte_perm(sh.x, sh.z, 0x7632), f2 = __byte_perm(sh.y, sh.w, 0x5410), f3 = __byte_perm(sh.y, sh.w, 0x7632);
                uint32_t kk[11], vv[8];
                mbar_spin(bars + (B_IN + hw) * 8, 0);
                TS(tid == 64, 18 + 42 * hw)
#pragma unroll
                for (int i = 0; i < 11; i++) kk[i] = lds32(sb + OFF_KIN + hw * 10752 + in + i * 160);
#pragma unroll
                for (int i = 0; i < 8; i++) vv[i] = lds32(sb + OFF_VIN + hw * 10240 + in + i * 160);
#pragma unroll
                for (int i = 0; i < 8; i++) vv[i] = mul2(fma2(kk[i + 3], f0, fma2(kk[i + 2], f1, fma2(kk[i + 1], f2, mul2(kk[i], f3)))), vv[i]);
                sts128(sta, tag(__byte_perm(vv[0], vv[1], 0x5410), ep), __byte_perm(vv[2], vv[3], 0x5410), __byte_perm(vv[4], vv[5], 0x5410), __byte_perm(vv[6], vv[7], 0x5410));
                sts128(sta + 128, tag(__byte_perm(vv[0], vv[1], 0x7632), ep), __byte_perm(vv[2], vv[3], 0x7632), __byte_perm(vv[4], vv[5], 0x7632), __byte_perm(vv[6], vv[7], 0x7632));
                bar_sync(7 + hw, 320);
                flush_tile(st, g_kvT + (size_t)(80 * (id & 7)) * S_ + 64 * line, u);
                TS(tid == 64 && hw, 1)
            }
            warp_arrive(bars + B_KVS * 8);
            if (tid < 320) sts128(sb + OFF_CH + (tid >> 6) * CH_BYTES + 4096 + (tid & 63) * 16, 0, 0, 0, 0);
            mbar_spin(bars + B_SSM * 8, 0);
            TS(tid == 0, 14)
#pragma unroll 1
            for (int u0 = wg; u0 < 20; u0 += 12) {
                uint2 w[4];
                uint32_t pv[4];
#pragma unroll
                for (int i = 0; i < 4; i++) {
                    const uint32_t a = sb + OFF_SSM + min(u0 + 3 * i, 19) * 1024 + wt * 8;
                    w[i] = lds64(a); pv[i] = lds32(a - 4);
                }
#pragma unroll
                for (int i = 0; i < 4; i++) {
                    const int un = min(u0 + 3 * i, 19);
                    sts128(sb + OFF_CH + (un >> 2) * CH_BYTES + OFF_P + (un & 3) * 2048 + wt * 16, __byte_perm(w[i].x, pv[i], 0x7610), __byte_perm(w[i].x, 0, 0x1032), __byte_perm(w[i].y, w[i].x, 0x7610), __byte_perm(w[i].y, 0, 0x1032));
                }
            }
            __syncwarp();
            if (wt < 2 - (wg >> 1)) {
                const uint32_t h = lds32(sb + OFF_SSM + (wg + 3 * wt) * 4096), h0 = pack2(blo(h) + blo(dd), 0.f);
                sts64f(sb + OFF_CH + (wg + 3 * wt) * CH_BYTES + OFF_P, __uint_as_float(h0), __uint_as_float(__byte_perm(h, h0, 0x5432)));
            }
            fence_async_smem();
            warp_arrive(bars + B_BK * 8);
            asm volatile("barrier.cluster.wait.aligned;" ::: "memory");
            mbar_spin(bars + B_BK * 8, 0);
            TS(tid == 0, 15)
        }

#pragma unroll 1
        for (int c = wg; c < 5; c += 3) {
            const uint32_t kvb = sb + OFF_CH + c * CH_BYTES;
            mbar_spin(bars + (c < 3 ? B_RAW : B_RAW3) * 8, 0);
            for (uint32_t ph = 0; c < 3; ph ^= 1) {
                const int wt = tid_now() & 127;
                if (!RARE(bar_any(1 + wg, lop3<0x7E>(lds32(kvb + wt * 16), ep, lds32(kvb + 2048 + wt * 16)) & 1))) break;
                if (wt == 0) { mbar_expect(bars + (B_RETRY + wg) * 8, 4096); bulk_ld(kvb, g_kvT + (size_t)(5 * id + c) * S_, 4096, bars + (B_RETRY + wg) * 8); }
                mbar_spin(bars + (B_RETRY + wg) * 8, ph);
                STALE1(-8)
            }
            TS(threadIdx.x == 0, c ? 13 : 11)
            float acc[64];
            {
                const int l = tid_now() & 31;
                conv_channel(acc, kvb + OFF_P + (8 * (warp & 3) + (l >> 2) - 2 * (l & 3)) * 4, (((uint64_t)0xC0000010u << 32) | ((kvb & 0x3FFFF) >> 4) | 0x10000u) + pp.nil);
            }
            TS(threadIdx.x == 0, c ? 16 : 12)
            if (c < 3) warp_arrive(bars + B_R1 * 8);
            else mbar_spin(bars + B_R1 * 8, 0);
            if (wg == 2 && id < 120) {
                TIDS
                mbar_spin(bars + B_RAW3 * 8, 0);
                mbar_spin(bars + B_WM * 8, 0);
                TS(wt == 0, 56)
                float d[4];
                gemv_tile<8>(d, sb + OFF_WM, sb + OFF_Z, 0);
                const float d2 = __shfl_up_sync(~0u, d[2], 1);
                TS(wt == 0, 7)
                if (t < 2) asm volatile("{\n.reg .b64 v;\nmov.b64 v, {%1, %2};\nst.relaxed.gpu.global.b64 [%0], v;\n}" ::"l"(g_mod + (id & 1) * 6 * D_ + 64 * pr + 16 * (warp & 3) + g + 8 * t),
                                        "r"(__float_as_uint(t ? d2 : d[0])), "r"(lds32(sb + M_EP)) : "memory");
            }
            TR4(threadIdx.x == 0, 60 + (c >= 3) * 10)
            TIDS
            const int e = 127 - 8 * (lane >> 4) - (lane & 7), u0 = (warp & 3) + 8 * (e >> 2) + (e & 3) + 4 * ((lane >> 3) & 1);
            const uint32_t ring = sb + OFF_RING + c * 16384 + (warp & 3) * 4096, wa = ring + (u0 ^ ((u0 >> 1) & 4)) * 16;
            if (lane < (warp & 3)) sts128(ring + lane * 16, 0, 0, 0, 0);
#pragma unroll
            for (int i = 0; i < 8; i++)
                stsm4t(i == 0 && u0 >= 256 ? sb + M_SINK : wa - 512 * i, pack2(acc[8 * i], acc[8 * i + 1]), pack2(acc[8 * i + 2], acc[8 * i + 3]),
                       pack2(acc[8 * i + 4], acc[8 * i + 5]), pack2(acc[8 * i + 6], acc[8 * i + 7]));
            warp_arrive(bars + (B_RING + c) * 8);
            TR4(threadIdx.x == 0, 61 + (c >= 3) * 10)
        }
        TIDS
        if (wg == 2) bar_sync(3, 128);
        if (warp == 8) {
            wait_cnt(&g_cnt.q[(id & 3) * 32], 128, true);
            if (elect()) {
                mbar_expect(bars + B_QRDY * 8, 28672);
                tma_ld2(sb + OFF_QT, &mp.qT, 80 * id, 0, bars + B_QRDY * 8);
                bulk_ld(sb + OFF_QT + 20480, g_qst, 8192, bars + B_QRDY * 8);
            }
            TS(lane == 0, 8)
        } else if (warp == 9) {
            const int v = min(lane / 5, 3);
            const uint2* gm = g_mod + (v + (v == 3)) * D_ + 5 * id + lane % 5;
            const unsigned epoch = lds32(sb + M_EP);
            uint2 r0, r1;
            unsigned it = 0;
            do {
                r0 = ld_mod(gm); r1 = ld_mod(gm + 6 * D_);
                SPIN_CHECK(55)
            } while (!__all_sync(~0u, r0.y == epoch && r1.y == epoch));
            const float m0 = __uint_as_float(r0.x), m1 = __uint_as_float(r1.x);
            const float m = rbf(m0 + m1), p = rbf(1.f + m);
            const float cz = zscale(__shfl_sync(~0u, p, 15 + lane % 5)), ga = __shfl_sync(~0u, m, 10 + lane % 5);
            if (lane < 15) sts32(sb + M_AB + lane % 5 * 16 + v * 4, lane < 10 ? __float_as_uint(cz * ga * (lane < 5 ? m : p)) : pack2(cz, cz));
            warp_arrive(bars + B_MODR * 8);
            TS(lane == 0, 6)
        }
        mbar_spin(bars + B_QRDY * 8, 0);
        uint4 rs[2], nm[2];
#pragma unroll
        for (int h = 0; h < 2; h++) { rs[h] = lds128(sb + OFF_QT + 20480 + h * 2048 + wt * 16); nm[h] = lds128(sb + OFF_QT + 24576 + h * 2048 + wt * 16); }
        mbar_spin(bars + B_MODR * 8, 0);
        TR4(threadIdx.x == 0, 72)
        uint32_t it = 0;
        while (RARE(__any_sync(~0u, (lop3<0x7E>(rs[0].x, ep, rs[0].z) | lop3<0x7E>(nm[0].x, ep, nm[0].z) | lop3<0x7E>(rs[1].x, ep, rs[1].z) | lop3<0x7E>(nm[1].x, ep, nm[1].z)) & 1))) {
#pragma unroll
            for (int h = 0; h < 2; h++) { rs[h] = ld_part(g_qst + 1024 * h + 8 * wt); nm[h] = ld_part(g_qst + S_ + 1024 * h + 8 * wt); }
            STALE(1)
            SPIN_CHECK(53)
        }
        TR4(threadIdx.x == 0, 73)
#pragma unroll 1
        for (int c = wg == 2 ? 0 : 3 + wg; c < (wg == 2 ? 3 : 4 + wg); c++) {
            uint4 q[2], p[2][4];
#pragma unroll
            for (int h = 0; h < 2; h++) q[h] = lds128(sb + OFF_QT + h * 10240 + (wt >> 1) * 160 + c * 32 + (wt & 1) * 16);
            const float4 ab = lds128f(sb + M_AB + c * 16);
            mbar_spin(bars + (B_RING + c) * 8, 0);
            TR4(wt == 0, wg == 2 ? 80 + 2 * c : 74)
#pragma unroll
            for (int i = 0; i < 8; i++) p[i >> 2][i & 3] = lds128(sb + OFF_RING + c * 16384 + (i & 3) * 4096 + (i >> 2) * 2048 + (wt ^ ((wt >> 1) & 4)) * 16);
            while (RARE(__any_sync(~0u, lop3<0x7E>(q[0].x, ep, q[1].x) & 1))) {
#pragma unroll
                for (int h = 0; h < 2; h++) q[h] = ld_part(g_qT + ((64 * h + (wt >> 1)) * D_ + 5 * id + c) * 16 + 8 * (wt & 1));
                STALE(2)
                SPIN_CHECK(52)
            }
            TR4(wt == 0, wg == 2 ? 81 + 2 * c : 75)
#pragma unroll
            for (int h = 0; h < 2; h++) {
                const uint32_t qq[4] = {q[h].x, q[h].y, q[h].z, q[h].w}, r4[4] = {rs[h].x, rs[h].y, rs[h].z, rs[h].w}, n4[4] = {nm[h].x, nm[h].y, nm[h].z, nm[h].w};
                const uint4 y = add2(add2(p[h][0], p[h][1]), add2(p[h][2], p[h][3]));
                const uint32_t yy[4] = {y.x, y.y, y.z, y.w};
                uint32_t o[4];
#pragma unroll
                for (int i = 0; i < 4; i++) {
                    const uint32_t n = fma2(qq[i], r4[i], n4[i]);
                    o[i] = fma2(pack2(fmaf(blo(n), ab.y, ab.x), fmaf(bhi(n), ab.y, ab.x)), yy[i], mul2(qq[i], __float_as_uint(ab.z)));
                }
                stg128_tag(g_x1T + (size_t)(5 * id + c) * S_ + 1024 * h + 8 * wt, o[0], o[1], o[2], o[3], ep, ((5 * id + c) >> 3) & 3);
            }
        }
        warp_arrive(bars + B_XS * 8);
        TS(tid == 0, 17)
        TS(tid == 256, 52)
    }

    const uint32_t nil = pp.nil;
    const int wq = warp & 3;
    if (wg == 2) {
        TIDS
        asm volatile("setmaxnreg.dec.sync.aligned.u32 " STR(REG_AUX) ";");
        {
            const uint32_t ep = lds32(sb + M_EP);
            uint32_t ph = 0;
            const Tile tl = ring_tile(min(4 * lane + wq, 59), grp, j);
            const uint32_t plan = bars + (B_XFULL + 10 * tl.w + tl.kb) * 8;
#pragma unroll 1
            for (int m = wq - 4; m < 60; m += 4) {
                const int n = max(m, 0);
                const uint32_t pl = __shfl_sync(~0u, plan, n >> 2), at = __shfl_sync(~0u, tl.at, n >> 2);
                const int e = (n >= 20) + (n >= 40);
                const uint32_t a = sb + OFF_XR + (n & 7) * 8192;
                uint32_t ta = a + (e == 0 ? lane * 128 + ((lane & 7) << 4) + (lane >> 3) * 4
                                 : e == 1 ? (lane & 15) * 128 + (((lane >> 4 << 1) ^ (lane & 7)) << 4) + (lane & 8) + (lane >> 4) * 4
                                          : lane * 32 + (lane >> 2) * 4);
                uint32_t tb = e == 0 ? ta ^ 32 : ta + 2048, tc = e == 2 ? ta + 1024 : ta ^ 64, td = e == 2 ? tb + 1024 : tb ^ 64;
                uint32_t live = m >= 0 && m != 40 && m != 40 + XLEAD,
                    f0 = pl;
                uint32_t f1 = m == GATE_W2 || m == GATE_W3 || m == GATE_W3B ? bars + (B_GATE + (m >= GATE_W3) + (m >= GATE_W3B)) * 8 : 0;
                if (lane) f0 = f1;
                if (lane > 1 || m < 0) f0 = 0;
                asm volatile("" : "+r"(ta), "+r"(tb), "+r"(tc), "+r"(td), "+r"(live), "+r"(f0));
                mbar_spin(bars + (m < 0 ? B_BK : B_LAND + (n & 7)) * 8, (n >> 3) & 1);
                TR5(lane == 0, n)
                while (true) {
                    uint32_t v[8];
#pragma unroll
                    for (int i = 0; i < 8; i++) v[i] = lds32(((i & 2) ? ((i & 1) ? td : tc) : (i & 1) ? tb : ta) + (i >> 2) * 4096);
                    const uint32_t bad = lop3<0xFE>(lop3<0x7E>(v[0], ep, v[1]), lop3<0x7E>(v[2], ep, v[3]), lop3<0x7E>(v[4], ep, v[5]));
                    if (!RARE(__any_sync(~0u, lop3<0xA8>(bad, lop3<0x7E>(v[6], ep, v[7]), live)))) break;
                    if (elect()) load_tile(mp, a, e, at, bars + (B_AGAIN + wq) * 8);
                    mbar_spin(bars + (B_AGAIN + wq) * 8, ph);
                    ph ^= 1;
                    STALE1(e)
                }
                TR5(lane == 0, 60 + n)
                if (f0) mbar_arrive(f0);
            }
        }
        if (wq == 0) {
#pragma unroll 1
            for (int w = 0; w < 2; w++) {
                const uint4* src = g_part + (size_t)(grp + 16 * w) * 40960;
                TR4(lane == 0, 90 + 2 * w)
                mbar_wait(bars + (B_RING + w) * 8, 1);
                TR4(lane == 0, 91 + 2 * w)
                if (elect()) {
                    const uint32_t fb = bars + (B_IN + w) * 8, rem = sb + OFF_OUT + w * 10240;
                    mbar_expect(fb, 10240);
                    bulk_ld(rem + 8192, &g_x1f[((grp + 16 * w) * 8 + j) * 640 + 512], 2048, fb);
#pragma unroll 1
                    for (int i = 0; i < 4; i++) bulk_ld(rem + i * 2048, src + ((j >> 2) + 2 * i) * 5120 + 4096 + j * 128, 2048, fb);
                }
            }
        }
#pragma unroll 1
        for (int uw = 0; uw < 2; uw++) {
            const int tile = grp + 16 * uw;
            const uint32_t ep = lds32(sb + M_EP), in = sb + OFF_OUT + uw * 10240 + wt * 16, sr = in - lane * 16;
            mbar_wait(bars + (B_IN + uw) * 8, 1);
            TR4(wt == 0, 94 + 3 * uw)
            uint4 u[4];
#pragma unroll
            for (int i = 0; i < 4; i++) u[i] = lds128(in + i * 2048);
            const uint4 base = lds128(in + 8192);
            const uint32_t ra = sb + M_F1 + (64 * uw + 16 * wq + g) * 4;
            const uint4 gr = scale16(lds64f(sb + M_GB + (64 + 2 * t) * 4), lds64f(sb + M_GB + (72 + 2 * t) * 4), __uint_as_float(lds32(ra)), __uint_as_float(lds32(ra + 32)));
            uint32_t it = 0;
            while (RARE(__any_sync(~0u, stale4(u, ep) & 1))) {
                ld_part4(u, g_part + (size_t)tile * 40960 + (j >> 2) * 5120 + 4096 + j * 128 + wt, 10240);
                STALE(3)
                if (++it > SPIN_LIMIT) SPIN_FAIL(58)
            }
            TR4(wt == 0, 95 + 3 * uw)
            const uint4 r = fin16(add2(add2(u[0], u[1]), add2(u[2], u[3])), base, gr);
            __syncwarp();
            stsm4(sr + (lane & 15) * 32 + (((lane >> 4) ^ ((lane >> 2) & 1)) << 4), r.x, r.y, r.z, r.w);
            __syncwarp();
            stg128(out + (size_t)(64 * tile + 16 * wq + (lane >> 1)) * D_ + 512 + 16 * j + 8 * (lane & 1), lds128(sr + (lane >> 1) * 32 + (((lane & 1) ^ ((lane >> 3) & 1)) << 4)));
            TR4(wt == 0, 96 + 3 * uw)
            __syncwarp();
        }
        TS(wt == 0, 21)
        if (wq == 0) {
            uint32_t it = 0;
            while (!mbar_try(bars + B_OWN * 8, 0)) { if (++it > SPIN_LIMIT) SPIN_FAIL(56) }
        }
        return;
    }

    TIDS
    const int uw = wg, tile = grp + 16 * uw, row0 = 64 * tile + 16 * wq;
    const bool leader = wt == 0; (void)leader;
    const uint32_t xfull = bars + (B_XFULL + 10 * uw) * 8, xempty = bars + B_XEMPTY * 8, wfull = bars + B_WFULL * 8, wempty = bars + B_WEMPTY * 8;
    const uint64_t dz = mkdesc(0) + pp.nil;
    auto xwait = [&](uint32_t kb, uint32_t e) { mbar_spin(xfull + kb * 8, e & 1); };
    asm volatile("setmaxnreg.inc.sync.aligned.u32 " STR(REG_MMA) ";");
    const uint32_t ep = lds32(sb + M_EP);
    uint32_t x2[20];
    uint32_t res[20] = {};
    {
        float acc[40];
        const uint32_t la = ((lane & 7) + 8 * (lane >> 4)) * 128 + (((2 * wq + ((lane >> 3) & 1)) ^ (lane & 7)) << 4);
        auto pos = [&](int n) { return ring_pos(uw, n, LEAD1) & 7; };
        auto slot = [&](int n) { return sb + OFF_XR + pos(n) * 8192; };
        float al[2], r1[2], n1[2];
        {
            float sl[4], sq[4], v[4];
            uint32_t z0[16], z1[16], zz[16];
            uint64_t bd = dz + b80_desc(dsb, 0, 0, 0), tb = (((uint64_t)8 << 32) | ((dsb + OFF_TAB) >> 4) | (7u << 16)) + pp.nil;
            auto ldfrag = [&](uint32_t (&z)[16], int n, bool even) {
#pragma unroll
                for (int q = 0; q < 4; q++) ldsm4t(slot(n) + la + q * 2048, z[4 * q], z[4 * q + 1], z[4 * q + 2], z[4 * q + 3]);
#pragma unroll
                for (int q = 0; q < 4; q++) ldsm4t_if(n == j >> 1, slot(n) + la + q * 2048, &res[4 * q]);
                if (even) ldsm4t_if(n == 4 && !((j ^ (j >> 2)) & 1), slot(n) + la + (j & 3) * 2048, &res[16]);
            };
            auto tile1 = [&](const uint32_t (&zc)[16], uint32_t (&zn)[16], int n, int h) {
                const bool last = h && n == 5, ok = mbar_test(xfull + (n + 1) * 8, 0), okw = !h || mbar_test(wfull + ((n + 1) >> 1) * 8, 0);
                wg_fence();
#pragma unroll
                for (int q = 0; q < 2; q++) wgmma_rs80(acc, zc[4 * q], zc[4 * q + 1], zc[4 * q + 2], zc[4 * q + 3], bd + q * B80_STEP, 1);
                wg_commit();
                if (lane < 2) mbar_arrive_after(xempty + pos(n) * 8, res[12], res[16], nil);
                wg_wait<1>();
                if (!h && n && lane == 0) mbar_arrive(wempty + ((n >> 1) - 1) * 8);
                if (!ok) xwait(n + 1, 0);
                if (!last) ldfrag(zn, n + 1, h);
#pragma unroll
                for (int e = 0; e < 16; e++) zz[e] = mul2(zc[e], zc[e]);
                const uint64_t t0 = last ? ((uint64_t)8 << 32) | ((dsb + M_NUL) >> 4) : tb;
                const uint32_t ts = last ? 0 : 14;
                wg_fence();
#pragma unroll
                for (int q = 0; q < 4; q++) wgmma_rs8(sl, zc[4 * q], zc[4 * q + 1], zc[4 * q + 2], zc[4 * q + 3], t0 + q * ts, 1);
#pragma unroll
                for (int q = 0; q < 4; q++) wgmma_rs8(sq, zz[4 * q], zz[4 * q + 1], zz[4 * q + 2], zz[4 * q + 3], t0 + q * ts, 1);
#pragma unroll
                for (int q = 2; q < 4; q++) wgmma_rs80(acc, zc[4 * q], zc[4 * q + 1], zc[4 * q + 2], zc[4 * q + 3], bd + q * B80_STEP, 1);
                wg_commit();
                tb += 56;
                bd = bd + (uint64_t)B80_HALF;
                if (!okw) mbar_spin(wfull + ((n + 1) >> 1) * 8, 0);
                TR(leader, 100 + 10 * uw + n)
            };
            zero(acc); zero(sl); zero(sq);
            mbar_spin(bars + B_TAB * 8, 0);
            float4 k = lds128f(sb + M_KS);
            float k4 = __uint_as_float(lds32(sb + M_KS + 16));
#pragma unroll
            for (int w = 1; w < 5; w++) {
                const float4 o = lds128f(sb + M_KS + w * 32);
                k.x += o.x; k.y += o.y; k.z += o.z; k.w += o.w; k4 += __uint_as_float(lds32(sb + M_KS + w * 32 + 16));
            }
            uint32_t fa[4];
            auto coefs = [&]() {
                mbar_spin(bars + (B_SUMS + uw) * 8, 0);
                TS(leader && !uw, 10)
                const float4 o = lds128f(sb + OFF_ROW + uw * 2048 + wt * 16);
                v[0] += o.x; v[1] += o.y; v[2] += o.z; v[3] += o.w;
#pragma unroll
                for (int h = 0; h < 2; h++) {
                    const int l0 = lane & ~3;
                    const float s1 = __shfl_sync(~0u, v[2 * h], l0), s2 = __shfl_sync(~0u, v[2 * h], l0 + 1), scc = __shfl_sync(~0u, v[2 * h], l0 + 2);
                    const float scs = __shfl_sync(~0u, v[2 * h + 1], l0 + 2), sc = __shfl_sync(~0u, v[2 * h], l0 + 3), sqq = __shfl_sync(~0u, v[2 * h + 1], l0 + 3);
                    const float m1 = s1 * (1.f / D_), va = fmaxf(s2 * (1.f / D_) - m1 * m1, 0.f) + 1e-5f, r = rsqrtf(va);
                    const float m2 = (r * (sc - m1 * k.x) + k.y) * (1.f / D_);
                    const float e2 = (r * (r * (sqq + m1 * (m1 * k.z - 2.f * scc)) + 2.f * (scs - m1 * k.w)) + k4) * (1.f / D_);
                    al[h] = r * 0.5f * rsqrtf(fmaxf(e2 - m2 * m2, 0.f) + 1e-5f); r1[h] = r; n1[h] = -m1 * r;
                    const uint32_t fb = split2(va * r), fx = split2(t == 3 ? -m2 * va * r : -m1), fc = __shfl_sync(~0u, fx, lane | 3);
                    fa[h] = __byte_perm(fx, fb, t == 1 ? 0x5432 : t == 2 ? 0x7654 : 0x1010);
                    fa[2 + h] = t ? 0 : fc >> 16;
                }
            };
            mbar_spin(wfull, 0);
            xwait(0, 0);
            TS(leader, 32 + uw)
            ldfrag(z0, 0, false);
#pragma unroll 1
            for (int n = 0; n < 6; n += 2) { tile1(z0, z1, n, 0); tile1(z1, z0, n + 1, 1); }
#pragma unroll
            for (int n = 6; n < 10; n++) {
                const uint64_t ad = dz + (((dsb + OFF_XR + pos(n) * 8192) >> 4) | 0x10000u);
                const bool ok = n == 9 || mbar_test(xfull + (n + 1) * 8, 0), okw = n != 7 || mbar_test(wfull + 4 * 8, 0);
                wg_fence();
#pragma unroll
                for (int q = 0; q < 4; q++) wgmma_ss80t(acc, ad + q * 128, bd + q * B80_STEP, 1);
                wg_commit();
                bd = bd + (uint64_t)B80_HALF;
                if (n == COEF_AT) coefs();
                if (n == 9) ldsm4t_if(9 - (j & 1) == 8 + (j >> 2), slot(9) + la + (j & 3) * 2048, &res[16]);
                wg_wait<1>();
                if (n > 6 && lane < 2) mbar_arrive(xempty + pos(n - 1) * 8);
                if (!(n & 1) && lane == 0) mbar_arrive(wempty + ((n >> 1) - 1) * 8);
                if (n == 6) {
                    reg_fence(sl); reg_fence(sq);
#pragma unroll
                    for (int e = 0; e < 2; e++) {
                        v[2 * e] = t == 0 ? sl[2 * e] + sl[2 * e + 1] : t == 1 ? sq[2 * e] + sq[2 * e + 1] : sl[2 * e];
                        v[2 * e + 1] = t == 2 ? sl[2 * e + 1] : sq[2 * e];
                    }
                    st_peer(peer_addr(sb + OFF_ROW + uw * 2048 + wt * 16), __float_as_uint(v[0]), __float_as_uint(v[1]), __float_as_uint(v[2]), __float_as_uint(v[3]), peer_addr(bars + (B_SUMS + uw) * 8));
                    TS(leader && !uw, 59)
                }
                if (!ok) xwait(n + 1, 0);
                if (!okw) mbar_spin(wfull + 4 * 8, 0);
                TR(leader, 100 + 10 * uw + n)
            }
            if (COEF_AT == 10) coefs();
            mbar_spin(bars + B_VEC * 8, 0);
            wg_fence();
            wgmma_rs80k(acc, fa[0], fa[1], fa[2], fa[3], ((uint64_t)8 << 32) | ((dsb + OFF_F1) >> 4) | (((M_F1 - OFF_F1) >> 4) << 16), 1);
            wg_commit();
        }
        wg_wait<0>();
        reg_fence(acc);
        if (lane < 2) mbar_arrive_after(xempty + pos(9) * 8, res[16], 0, nil);
        if (lane == 0) mbar_arrive(wempty + 4 * 8);
        TS(leader, 34 + uw)
        {
            bf16* const trow = g_t + (size_t)(row0 + g + 2) * D_;
#pragma unroll
            for (int b = 0; b < 3; b++) {
                uint32_t p[8];
#pragma unroll
                for (int ii = 0; ii < 4; ii++) {
                    const int i = 4 * b + ii;
                    if (i >= 10) continue;
#pragma unroll
                    for (int h = 0; h < 2; h++) p[(i & 3) + 4 * h] = pack2(gelu2(acc[4 * i + 2 * h] * al[h]), gelu2(acc[4 * i + 2 * h + 1] * al[h]));
                }
                if (b < 2) {
                    const int gr = (2 * j + b) / 5, sh = (gr & 1) ? -1 - (gr >> 1) : 1 + (gr >> 1);
                    bf16* dst = trow + 64 * j + 32 * b + 8 * t;
                    const int w = (((g + sh) >> 2) & 2) + (t >> 1);
                    stg128_tag(dst + sh * D_, p[0], p[1], p[2], p[3], ep, w);
                    stg128_tag(dst + (sh + 8) * D_, p[4], p[5], p[6], p[7], ep, w ^ 2);
                    if (row0 + g < sh || row0 + g + 8 >= S_ + sh) stg128_tag(dst + (sh > 0 ? 0 : 8) * D_, 0, 0, 0, 0, ep, (sh > 0 ? 0 : 2) + (t >> 1));
                } else {
                    bf16* dst = trow + 512 + 16 * j + 4 * t;
                    const uint32_t lo = t == (g < 2), hi = t == (g >= 2), o = j & 1;
                    stg64(dst - 2 * D_, lop3<0xB8>(p[0], lo & ~o, ep), lop3<0xB8>(p[1], lo & o, ep));
                    stg64(dst + 6 * D_, lop3<0xB8>(p[4], hi & ~o, ep), lop3<0xB8>(p[5], hi & o, ep));
                    if (row0 + g + 8 >= S_ - 2) stg64(dst + 8 * D_, ep & (t == 1) & ~o, ep & (t == 1) & o);
                }
            }
        }
        signal_cnt(&g_cnt.g1[tile * 32], lane, 1, true);
        TS(leader, 36 + uw)
#pragma unroll
        for (int i = 0; i < 10; i++) {
            const float2 c = lds64f(sb + M_C + (8 * i + 2 * t) * 4), s = lds64f(sb + M_SB + (8 * i + 2 * t) * 4);
#pragma unroll
            for (int h = 0; h < 2; h++) {
                acc[4 * i + 2 * h] = fmaf(blo(res[2 * i + h]), r1[h], fmaf(n1[h], c.x, s.x));
                acc[4 * i + 2 * h + 1] = fmaf(bhi(res[2 * i + h]), r1[h], fmaf(n1[h], c.y, s.y));
            }
        }
        mbar_spin(wfull + 5 * 8, 0);
        xwait(0, 1);
        TS(leader, 22 + uw)
        uint32_t ps = uw ? P1S : P0S, xo = (ps & 3) * 16, xp = 0;
        const uint64_t ax = dz + (((dsb + OFF_XR) >> 4) | 0x10000u);
        uint64_t ad = ax + xo * 64, bd = dz + b80_desc(dsb, 5, 0, 0);
#pragma unroll 1
        for (int i = 0; i < 5; i++) {
            const uint32_t x1 = xfull + (1 + 2 * i) * 8, p1 = 1, x2 = xfull + min(2 + 2 * i, 9) * 8, p2 = 1;
            const uint32_t w2 = wfull + (min(6 + i, 9) & 7) * 8, pw = i >= 2;
            const bool ok1 = mbar_test(x1, p1);
            wg_fence();
#pragma unroll
            for (int q = 0; q < 4; q++) wgmma_ss80(acc, ad + q * 2, bd + q * B80_STEP, 1);
            wg_commit();
            wg_wait<1>();
            if (lane < 2 && i) mbar_arrive(xempty + xp);
            if (lane == 0 && i) mbar_arrive(wempty + ((4 + i) & 7) * 8);
            if (!ok1) mbar_spin(x1, p1);
            const bool ok2 = mbar_test(x2, p2), okw = mbar_test(w2, pw);
            wg_fence();
#pragma unroll
            for (int q = 0; q < 4; q++) wgmma_ss80(acc, ad + 512 + q * 2, bd + B80_HALF + q * B80_STEP, 1);
            wg_commit();
            const uint32_t xc = xo;
            ps >>= 2;
            xp = xo + 8; xo = (ps & 3) * 16;
            ad = ax + xo * 64;
            bd += i == 2 ? 2 * B80_HALF - 8192 + (8192ll << 16) : 2 * B80_HALF;
            asm volatile("" : "+l"(ad), "+l"(bd));
            wg_wait<1>();
            if (lane < 2) mbar_arrive(xempty + xc);
            if (!ok2) mbar_spin(x2, p2);
            if (!okw) mbar_spin(w2, pw);
            TR(leader, (uw ? 86 : 20) + 2 * i)
        }
        wg_wait<0>();
        reg_fence(acc);
        if (lane < 2) mbar_arrive(xempty + xp);
        if (lane == 0) mbar_arrive(wempty + (9 & 7) * 8);
        TS(leader, 38 + uw)
        float a0 = 0.f, b0 = 0.f, a1 = 0.f, b1 = 0.f;
#pragma unroll
        for (int i = 0; i < 5; i++) {
            uint32_t* p = &x2[4 * i];
#pragma unroll
            for (int e = 0; e < 4; e++) p[e] = pack2(acc[8 * i + 2 * e], acc[8 * i + 2 * e + 1]);
#pragma unroll
            for (int e = 0; e < 4; e++) p[e] = lop3<0xB8>(p[e], (((wt >> 3) ^ (wt << 2)) & 7) == e, ep);
            stg128(&g_x2f[(tile * 40 + (i < 4 ? 4 * j + i : 32 + j)) * 128 + wt], p[0], p[1], p[2], p[3]);
#pragma unroll
            for (int e = 0; e < 8; e += 4) {
                const float* u = &acc[8 * i + e];
                a0 += u[0] + u[1]; b0 = fmaf(u[0], u[0], fmaf(u[1], u[1], b0));
                a1 += u[2] + u[3]; b1 = fmaf(u[2], u[2], fmaf(u[3], u[3], b1));
            }
        }
#pragma unroll
        for (int o = 1; o < 4; o *= 2) {
            a0 += __shfl_xor_sync(~0u, a0, o); b0 += __shfl_xor_sync(~0u, b0, o);
            a1 += __shfl_xor_sync(~0u, a1, o); b1 += __shfl_xor_sync(~0u, b1, o);
        }
        if (t < 2) stg64(&g_stats[(tile * 8 + j) * 64 + 16 * wq + g + 8 * t], tag(__float_as_uint(t ? a1 : a0), ep), __float_as_uint(t ? b1 : b0));
        signal_cnt(&g_cnt.g2[tile * 32], lane, 1, true);
        TS(leader, 40 + uw)
#pragma unroll
        for (int i = 0; i < 10; i++) {
            const float2 c = lds64f(sb + M_GB + (8 * i + 2 * t) * 4), e = lds64f(sb + M_CI + (8 * i + 2 * t) * 4);
#pragma unroll
            for (int h = 0; h < 2; h++)
                res[2 * i + h] = fma2(pack2(c.x, c.y), x2[2 * i + h], pack2(e.x * blo(res[2 * i + h]), e.y * bhi(res[2 * i + h])));
        }
#pragma unroll
        for (int i = 0; i < 20; i++) asm volatile("" : "+r"(res[i]));
    }
    float acc0[64], acc1[44];
    float2 q[4];
    {
        uint4 f0, f1, f2, f3;
        auto xseq = [&](int kb) { return ring_pos(uw, kb, XLEAD) & 7; };
        auto step = [&](const uint4& f, uint64_t bd) {
            wg_fence();
            wgmma_rs128(acc0, f.x, f.y, f.z, f.w, bd, 1);
            wgmma_rs88(acc1, f.x, f.y, f.z, f.w, bd + 512, 1);
            wg_commit();
        };
        const uint32_t xa = sb + OFF_XR + wt * 16;
        const float2* const gs = &g_stats[(tile * 8 + 2 * t) * 64 + 16 * wq + g];
        zero(acc0); zero(acc1);
        uint32_t xs = 0;
        f0 = make_uint4(x2[0], x2[1], x2[2], x2[3]); f1 = make_uint4(x2[4], x2[5], x2[6], x2[7]);
        f2 = make_uint4(x2[8], x2[9], x2[10], x2[11]); f3 = make_uint4(x2[12], x2[13], x2[14], x2[15]);
#pragma unroll
        for (int i = 0; i < 4; i++) q[i] = make_float2(0.f, 0.f);
        mbar_spin(wempty + (9 & 7) * 8, 1);
        mbar_spin(wfull + (10 & 7) * 8, (10 >> 3) & 1);
#pragma unroll 1
        for (int kb = 0; kb < 10; kb++) {
            const uint32_t wn = 10 + 2 * kb;
            const uint64_t bd = dz + (((dsb + OFF_W + (wn & 7) * 16384) >> 4) | (256u << 16));
            step(f0, bd);
            wg_wait<1>();
            if (kb && lane == 0) mbar_arrive(wempty + ((wn - 1) & 7) * 8);
            lds128_if(kb, f2, xa + xs * 8192 + 4096); lds128_if(kb, f3, xa + xs * 8192 + 6144);
            const bool w1 = mbar_test(wfull + ((wn + 1) & 7) * 8, (wn >> 3) & 1), x1 = kb < 9 && mbar_test(xfull + (kb + 1) * 8, 0);
            step(f1, bd + 128);
            if (!w1) mbar_spin(wfull + ((wn + 1) & 7) * 8, (wn >> 3) & 1);
            step(f2, bd + 1024);
            if (lane < 2 && kb) mbar_arrive_after(xempty + xs * 8, f2.x, f3.x, nil);
            wg_wait<1>();
            if (lane == 0) mbar_arrive(wempty + (wn & 7) * 8);
            xs = xseq(kb + 1);
            if (x1) { f0 = lds128(xa + xs * 8192); f1 = lds128(xa + xs * 8192 + 2048); }
            const bool w2 = mbar_test(wfull + ((wn + 2) & 7) * 8, ((wn + 2) >> 3) & 1);
            step(f3, bd + 1152);
            if (kb < 9 && !x1) { xwait(kb + 1, 2); f0 = lds128(xa + xs * 8192); f1 = lds128(xa + xs * 8192 + 2048); }
            if (!w2) mbar_spin(wfull + ((wn + 2) & 7) * 8, ((wn + 2) >> 3) & 1);
            if (kb == 0) {
                TS(leader, 42 + uw)
#pragma unroll
                for (int i = 0; i < 4; i++) q[i] = ld_stat(gs + (i & 1) * 64 + 8 * (i >> 1));
            }
            if (kb == 4) {
                uint32_t it = 0;
                while (RARE(__any_sync(~0u, ((__float_as_uint(q[0].x) ^ ep) | (__float_as_uint(q[1].x) ^ ep) | (__float_as_uint(q[2].x) ^ ep) | (__float_as_uint(q[3].x) ^ ep)) & 1))) {
#pragma unroll
                    for (int i = 0; i < 4; i++) q[i] = ld_stat(gs + (i & 1) * 64 + 8 * (i >> 1));
                    SPIN_CHECK(49)
                }
                float a0 = q[0].x + q[1].x, b0 = q[0].y + q[1].y, a1 = q[2].x + q[3].x, b1 = q[2].y + q[3].y;
#pragma unroll
                for (int o = 1; o < 4; o *= 2) {
                    a0 += __shfl_xor_sync(~0u, a0, o); b0 += __shfl_xor_sync(~0u, b0, o);
                    a1 += __shfl_xor_sync(~0u, a1, o); b1 += __shfl_xor_sync(~0u, b1, o);
                }
                a0 *= 1.f / D_; a1 *= 1.f / D_;
                const float r0 = 0.5f * rsqrtf(fmaxf(b0 * (1.f / D_) - a0 * a0, 0.f) + 1e-5f), r1 = 0.5f * rsqrtf(fmaxf(b1 * (1.f / D_) - a1 * a1, 0.f) + 1e-5f);
                const uint32_t sel = t == 0 ? 0x1010 : t == 1 ? 0x4432 : 0x4444;
                if (t == 0) { sts32(sb + M_F1 + (64 * uw + 16 * wq + g) * 4, __float_as_uint(r0)); sts32(sb + M_F1 + (64 * uw + 16 * wq + g + 8) * 4, __float_as_uint(r1)); }
                q[2] = make_float2(8.f * 0.0356774081f * r0 * r0 * r0, 2.f * 0.7978845608f * r0);
                q[3] = make_float2(8.f * 0.0356774081f * r1 * r1 * r1, 2.f * 0.7978845608f * r1);
                q[1] = make_float2(__uint_as_float(__byte_perm(split2(-a0), 0, sel)), __uint_as_float(__byte_perm(split2(-a1), 0, sel)));
            }
            if (kb == 6) {
#pragma unroll
                for (int i = 0; i < 5; i++) stg128(&g_x1f[(tile * 8 + j) * 640 + i * 128 + wt], res[4 * i], res[4 * i + 1], res[4 * i + 2], res[4 * i + 3]);
            }
            if (kb == 8) asm volatile("fence.proxy.async.global;" ::: "memory");
            TR(leader, 10 * uw + kb)
        }
        const uint64_t fd = ((uint64_t)8 << 32) | ((dsb + OFF_W + 6 * 16384) >> 4);
        wg_fence();
        wgmma_rs128k(acc0, __float_as_uint(q[1].x), __float_as_uint(q[1].y), 0, 0, fd, 1);
        wgmma_rs88k(acc1, __float_as_uint(q[1].x), __float_as_uint(q[1].y), 0, 0, fd + 128, 1);
        wg_commit();
        if (lane == 0) {
            mbar_arrive(bars + B_XFREE * 8);
            asm volatile("mbarrier.arrive.shared::cluster.b64 _, [%0];" ::"r"(peer_addr(bars + B_XFREE * 8)) : "memory");
        }
    }
    const uint32_t recv = sb + recv_off(uw) + wt * 16;
    uint32_t ha[48] = {}, hb[48], hx[12];
    uint64_t wb = dz + (((dsb + OFF_W) >> 4) | (512u << 16));
    auto wdesc = [&](int n) { return wb + (n & 7) * 1024; };
    auto wwait = [&](int n) { mbar_spin(wfull + (n & 7) * 8, (n >> 3) & 1); };
    auto wfree = [&](int n) { if (lane == 0) mbar_arrive(wempty + (n & 7) * 8); };
    auto fresh = [&]() { wb += pp.nil; asm volatile("" : "+l"(wb)); };
    uint32_t pk[32];
    {
        float P0[64];
        const float2 r0 = q[2], r1 = q[3];
        const uint32_t ra = peer_addr(recv), rb = peer_addr(bars + (B_RECV + 4 * uw) * 8);
        auto conv32 = [&](const float* v, int b) {
#pragma unroll
            for (int i = 0; i < 4; i++) {
                ha[8 * b + 2 * i] = pack2(gelu2r(v[4 * i], r0), gelu2r(v[4 * i + 1], r0));
                ha[8 * b + 2 * i + 1] = pack2(gelu2r(v[4 * i + 2], r1), gelu2r(v[4 * i + 3], r1));
            }
#pragma unroll
            for (int s = 2 * b; s < 2 * b + 2; s++) st_peer(ra + s * 2048, ha[4 * s], ha[4 * s + 1], ha[4 * s + 2], ha[4 * s + 3], rb + (b >> 1) * 8);
        };
        auto fetch = [&](int k) {
            mbar_spin(bars + (B_RECV + 4 * uw + k) * 8, 0);
#pragma unroll
            for (int s = 4 * k; s < 4 * k + 4; s++) { const uint4 x = lds128(recv + s * 2048); hb[4 * s] = x.x; hb[4 * s + 1] = x.y; hb[4 * s + 2] = x.z; hb[4 * s + 3] = x.w; }
        };
        auto stage = [&](int n, const uint32_t* a, int steps, int sc) {
            wwait(n);
            wg_fence();
#pragma unroll
            for (int s = 0; s < steps; s++) wgmma_rs128(P0, a[4 * s], a[4 * s + 1], a[4 * s + 2], a[4 * s + 3], wdesc(n) + s * 128, sc || s);
            wg_commit();
        };
        wg_wait<0>();
        reg_fence(acc0); reg_fence(acc1);
        wfree(29); wfree(30);
        TS(leader, 44 + uw)
        if (uw) bar_sync(13, 256);
        uint32_t hr[6];
#pragma unroll
        for (int i = 0; i < 6; i++) {
            const float2 r = (i & 1) ? r1 : r0;
            hr[i] = pack2(gelu2r(acc1[32 + 2 * i], r), gelu2r(acc1[33 + 2 * i], r));
        }
        if (uw) mbar_spin(bars + B_XFREE * 8, 0);
        st_peer(ra + 24576, hr[0], hr[1], hr[2], hr[3], rb + 24);
        asm volatile("st.async.shared::cluster.mbarrier::complete_tx::bytes.v2.b32 [%0], {%1, %2}, [%3];" ::"r"(ra + 26624 - wt * 8), "r"(hr[4]), "r"(hr[5]), "r"(rb + 24) : "memory");
        conv32(&acc1[0], 4);
        conv32(&acc1[16], 5);
        TS(leader, 46 + uw)
        stage(31, &ha[32], 4, 0);
#pragma unroll
        for (int b = 0; b < 4; b++) {
            conv32(&acc0[16 * b], b);
            if (b == 0 && !uw) asm volatile("bar.arrive 13, 256;" ::: "memory");
            if (b == 3) {
                fetch(2);
                mbar_spin(bars + (B_RECV + 4 * uw + 3) * 8, 0);
                const uint4 x = lds128(recv + 24576);
                const uint2 y = lds64(recv + 26624 - wt * 8);
                const uint32_t hp[6] = {x.x, x.y, x.z, x.w, y.x, y.y};
#pragma unroll
                for (int i = 0; i < 6; i++) { hx[i] = (j & 1) ? hp[i] : hr[i]; hx[6 + i] = (j & 1) ? hr[i] : hp[i]; }
            }
            if (!(b & 1)) wwait(32 + (b >> 1));
            wg_fence();
#pragma unroll
            for (int s = 0; s < 2; s++) wgmma_rs128(P0, ha[8 * b + 4 * s], ha[8 * b + 4 * s + 1], ha[8 * b + 4 * s + 2], ha[8 * b + 4 * s + 3], wdesc(32 + (b >> 1)) + (2 * (b & 1) + s) * 128, 1);
            wg_commit();
            if (!(b & 1)) { wg_wait<1>(); wfree(31 + (b >> 1)); }
        }
        TR(leader, 64 + 10 * uw)
        fresh();
        stage(34, &hb[32], 4, 1); wg_wait<1>(); wfree(33);
        fetch(0);
        stage(35, hx, 3, 1); wg_wait<1>(); wfree(34);
        fetch(1);
        stage(36, &hb[0], 4, 1); wg_wait<1>(); wfree(35);
        stage(37, &hb[16], 4, 1); wg_wait<1>(); wfree(36);
        wg_wait<0>();
        reg_fence(P0);
        pack_part<64>(pk, P0, ep);
        uint32_t all = 0;
#pragma unroll
        for (int i = 0; i < 32; i++) all |= pk[i];
        if (lane == 0) mbar_arrive_after(wempty + (37 & 7) * 8, all, 0, nil);
        TR(leader, 65 + 10 * uw)
    }
    {
        uint4* const dst = g_part + (size_t)(tile * 8 + j) * 5120 + wt;
        const uint4* const src = g_part + (size_t)tile * 40960 + j * 512 + wt;
        float F[2][32];
        uint4 gb[4];
        float rr[2];
        float2 gf[8];
        uint4 base[4], u1[4], u2[4], u3[4];
#pragma unroll
        for (int c = 2; c < 5; c++) {
            float (&P)[32] = F[c & 1];
            fresh();
#pragma unroll
            for (int s = 0; s < 27; s++) {
                const int e = s < 8 ? 0 : s < 15 ? 1 : s < 23 ? 2 : 3, o = s - (e == 0 ? 0 : e == 1 ? 8 : e == 2 ? 15 : 23), n = 30 + 4 * c + e;
                const uint32_t* a = s < 12 ? &ha[4 * s] : s < 15 ? &hx[4 * (s - 12)] : &hb[4 * (s - 15)];
                if (o == 0) wwait(n);
                if (o == 0 || s == 1) wg_fence();
                wgmma_rs64(P, a[0], a[1], a[2], a[3], wdesc(n) + o * 128, s);
                if (o == 0) { wg_commit(); wg_wait<1>(); if (c > 2 || s) wfree(n - 1); }
                if (s == 0 && c > 2) { reg_fence(F[~c & 1]); pack_part<32>(pk, F[~c & 1], ep); }
                if (c == 2 && s % 3 == 0 && s < 24) st_part(dst + g4_block(s / 12, j) * 512 + (s / 3 & 3) * 128, &pk[4 * (s / 3)]);
                if (c == 3 && s % 4 == 1 && s < 16) st_part(dst + g4_block(2, j) * 512 + s / 4 * 128, &pk[4 * (s / 4)]);
                if (c == 4 && s % ST3 == 0 && s < 4 * ST3) st_part(dst + g4_block(3, j) * 512 + s / ST3 * 128, &pk[4 * (s / ST3)]);
                if (c == 4 && s >= 4 && s < 8) base[s - 4] = ldcg128(&g_x1f[(tile * 8 + j) * 640 + (s - 4) * 128 + wt]);
                if (c == 4 && s >= 34 - LD2 && s < 38 - LD2) { const int i = s + LD2 - 34; gf[2 * i] = lds64f(sb + M_GB + (16 * i + 2 * t) * 4); gf[2 * i + 1] = lds64f(sb + M_GB + (16 * i + 8 + 2 * t) * 4); }
                if (c == 4 && s >= 12 && s < 14) rr[s - 12] = __uint_as_float(lds32(sb + M_F1 + (64 * uw + 16 * wq + g + 8 * (s - 12)) * 4));
                if (c == 4 && s >= 8 && s < 12) u1[s - 8] = ld_part(src + (j ^ 6) * 5120 + (s - 8) * 128);
                if (c == 4 && s >= LD2 && s < LD2 + 4) u2[s - LD2] = ld_part(src + (j ^ 4) * 5120 + (s - LD2) * 128);
                if (c == 4 && s >= LD3 && s < LD3 + 4) u3[s - LD3] = ld_part(src + (j ^ 2) * 5120 + (s - LD3) * 128);
                if (27 * (c - 2) + s == R_GATE && lane == 0) mbar_arrive(bars + (B_RING + uw) * 8);
                if (s == 7 || s == 14 || s == 22 || s == 26) wg_commit();
                if (c == 4) { TR(leader && s == 7, 68 + 10 * uw) TR(leader && s == 14, 69 + 10 * uw) TR(leader && s == 22, 70 + 10 * uw) }
            }
            TR(leader, 64 + c + (c == 4 ? 3 : 0) + 10 * uw)
        }
        float (&O)[32] = F[0];
#pragma unroll
        for (int i = 0; i < 4; i++) if (LD3 + i > 26) u3[i] = ld_part(src + (j ^ 2) * 5120 + i * 128);
#pragma unroll
        for (int i = 0; i < 4; i++) gb[i] = scale16(gf[2 * i], gf[2 * i + 1], rr[0], rr[1]);
        uint32_t it = 0;
        while (__any_sync(~0u, (stale4(u1, ep) | stale4(u2, ep) | stale4(u3, ep)) & 1)) {
            STALE(__any_sync(~0u, stale4(u1, ep) & 1) ? 4 : __any_sync(~0u, stale4(u2, ep) & 1) ? 5 : 6)
            ld_part4(u1, src + (j ^ 6) * 5120, 128); ld_part4(u2, src + (j ^ 4) * 5120, 128); ld_part4(u3, src + (j ^ 2) * 5120, 128);
            SPIN_CHECK(58)
        }
        TR(leader, 73 + 10 * uw)
#pragma unroll
        for (int i = 0; i < 4; i++) u1[i] = add2(add2(u1[i], u2[i]), u3[i]);
        TS(leader, 50 + uw)
        wg_wait<0>();
        reg_fence(O);
        TS(leader, 48 + uw)
        const uint32_t so = sb + recv_off(uw) + wq * 2048;
#pragma unroll
        for (int i = 0; i < 4; i++) {
            const float* o = &O[8 * i];
            const uint4 r = fin16(add2(u1[i], make_uint4(pack2(o[0], o[1]), pack2(o[2], o[3]), pack2(o[4], o[5]), pack2(o[6], o[7]))), base[i], gb[i]);
            stsm4(so + (lane & 15) * 128 + (((2 * i + (lane >> 4)) ^ (lane & 7)) << 4), r.x, r.y, r.z, r.w);
        }
        TR4(leader, 100 + uw)
        __syncwarp();
#pragma unroll
        for (int i = 0; i < 4; i++) {
            const int row = (lane >> 3) + 4 * i;
            stg128(out + (size_t)(row0 + row) * D_ + 64 * j + 8 * (lane & 7), lds128(so + row * 128 + (((lane & 7) ^ (row & 7)) << 4)));
        }
        TS(leader, 24 + uw)
        warp_arrive(bars + B_OWN * 8);
    }
}

typedef CUresult (*EncFn)(CUtensorMap*, CUtensorMapDataType, cuuint32_t, void*, const cuuint64_t*, const cuuint64_t*, const cuuint32_t*,
                          const cuuint32_t*, CUtensorMapInterleave, CUtensorMapSwizzle, CUtensorMapL2promotion, CUtensorMapFloatOOBfill);

static void enc(EncFn fn, CUtensorMap* m, void* p, int rank, const cuuint64_t* dims, const cuuint64_t* strides, const cuuint32_t* box, bool plain = false) {
    const CUtensorMapSwizzle sw = box[0] > 64 || plain ? CU_TENSOR_MAP_SWIZZLE_NONE : CU_TENSOR_MAP_SWIZZLE_128B;
    cuuint32_t es[5] = {1, 1, 1, 1, 1};
    CUresult r = fn(m, CU_TENSOR_MAP_DATA_TYPE_BFLOAT16, rank, p, dims, strides, box, es, CU_TENSOR_MAP_INTERLEAVE_NONE, sw,
                    CU_TENSOR_MAP_L2_PROMOTION_L2_128B, CU_TENSOR_MAP_FLOAT_OOB_FILL_NONE);
    (void)r;
}
static void enc2(EncFn fn, CUtensorMap* m, void* p, uint64_t cols, uint64_t rows, uint32_t bc, uint32_t br, bool plain = false) {
    cuuint64_t dims[2] = {cols, rows}, st[1] = {cols * 2};
    cuuint32_t box[2] = {bc, br};
    enc(fn, m, p, 2, dims, st, box, plain);
}

extern "C" void kernel_launch(void* const* d_in, const int* in_sizes, int n_in, void* d_out, int out_size) {
    static Maps mp;
    static Ptrs pp;
    static void* cached[13];
    bool same = true;
    for (int i = 0; i < 13; i++) same = same && (cached[i] == d_in[i]);
    if (!same) {
        void* fnp = nullptr;
        cudaDriverEntryPointQueryResult qr;
        cudaGetDriverEntryPoint("cuTensorMapEncodeTiled", &fnp, cudaEnableDefault, &qr);
        EncFn fn = (EncFn)fnp;
        cudaGetSymbolAddress((void**)&pp.s, g_scratch);
        void *x1T = g_x1T, *t = g_t;
        cuuint64_t dq[3] = {64, S_, 10}, sq[2] = {D_ * 2, 128};
        cuuint32_t bq[3] = {64, 16, 10};
        enc(fn, &mp.q, d_in[0], 3, dq, sq, bq);
        enc2(fn, &mp.k, d_in[1], D_, S_, 80, 67); enc2(fn, &mp.v, d_in[2], D_, S_, 80, 64);
        enc2(fn, &mp.qT, g_qT, 16 * D_, 128, 80, 128);
        enc2(fn, &mp.x[0], x1T, S_, D_, 64, 64); enc2(fn, &mp.x[1], (bf16*)t + 2 * D_, D_, S_, 64, 64);
        enc2(fn, &mp.x[2], g_x2f, 64, 320 * 64, 64, 64, true);
        enc2(fn, &mp.w1, d_in[7], D_, D_, 64, 64); enc2(fn, &mp.w1h, d_in[7], D_, D_, 64, 160); enc2(fn, &mp.w3h, d_in[9], F_, D_, 64, 160);
        enc2(fn, &mp.wmod, d_in[12], 6 * D_, D_, 64, 160);
        const cuuint64_t R = D_ * 2;
        cuuint64_t da[5] = {D_, 2, 4, 4, 16}, sa[4] = {R, 8 * R, 2 * R, 32 * R}, db[5] = {D_, 2, 2, 4, 8}, sb[4] = {R, 8 * R, 2 * R, 16 * R};
        cuuint32_t ba[5] = {64, 2, 4, 4, 2}, bb[5] = {64, 2, 2, 4, 4};
        enc(fn, &mp.w2a, d_in[8], 5, da, sa, ba); enc(fn, &mp.w2b, (bf16*)d_in[8] + 512 * D_, 5, db, sb, bb);
        cuuint64_t dw[3] = {64, D_, 27}, sw[2] = {F_ * 2, 128};
        cuuint32_t bw[3] = {64, 32, 3};
        enc(fn, &mp.w3a, d_in[9], 3, dw, sw, bw);
        enc2(fn, &mp.w3b, d_in[9], F_, D_, 24, 32);
        enc2(fn, &mp.w4[0], d_in[10], D_, F_, 64, 64); enc2(fn, &mp.w4[1], d_in[10], D_, F_, 64, 48);
        pp.q = (const bf16*)d_in[0]; pp.w_mod = (const bf16*)d_in[12]; pp.shift_k = (const bf16*)d_in[3];
        pp.ssm_k = (const bf16*)d_in[4]; pp.ssm_D = (const bf16*)d_in[5]; pp.w1 = (const bf16*)d_in[7]; pp.w2 = (const bf16*)d_in[8];
        pp.w4 = (const bf16*)d_in[10]; pp.c = (const bf16*)d_in[11];
        cudaFuncSetAttribute(fused_kernel, cudaFuncAttributeMaxDynamicSharedMemorySize, SMEM_BYTES);
        for (int i = 0; i < 13; i++) cached[i] = d_in[i];
    }
    fused_kernel<<<NCTA, NTHR, SMEM_BYTES, cudaStreamPerThread>>>(pp, (bf16*)d_out, mp);
}
```

```cpp
#include <cuda_runtime.h>
#include <cuda_bf16.h>
#include <cuda.h>
#include <stdint.h>
#include <stdio.h>

typedef __nv_bfloat16 bf16;

constexpr int S_ = 2048, D_ = 640, F_ = 1728;
constexpr int NCTA = 132, NTHR = 512;

constexpr int TAB_BYTES = 9216, VEC_BYTES = 1440;
struct Counters {
    unsigned kv[8 * 32];
    unsigned q[4 * 32], x[4 * 32];
    unsigned wr[32], tab[32], uv[32], cs[32], cs2[32], done[32];
    unsigned g1[32 * 32];
    unsigned g2[32 * 32];
};
struct Scratch {
    Counters cnt;
    unsigned epoch;
    alignas(1024) bf16 qst[2 * S_];
    alignas(1024) uint4 wr[2 * 8 * 10 * 128];
    alignas(1024) uint2 mod[2 * 6 * D_];
    alignas(1024) uint4 tab[(TAB_BYTES + 8 * VEC_BYTES) / 16];
    alignas(1024) float uv[2 * 3 * D_];
    alignas(1024) float cs3[2 * 1920];
    alignas(1024) uint4 cs3b[8 * 216];
    alignas(1024) float2 stats[32 * 8 * 64];
    alignas(1024) bf16 kvT[D_ * S_];
    alignas(1024) bf16 qT[D_ * S_];
    alignas(1024) bf16 x1T[D_ * S_];
    alignas(1024) bf16 t[(S_ + 4) * D_];
    alignas(1024) uint4 x2f[32 * 40 * 128];
    alignas(1024) uint4 x1f[32 * 8 * 5 * 128];
    alignas(1024) uint4 part[32 * 8 * 10 * 4 * 128];
};
__device__ Scratch g_scratch;
#define g_kvT (pp.s->kvT)
#define g_qT (pp.s->qT)
#define g_x1T (pp.s->x1T)
#define g_qst (pp.s->qst)
#define g_t (pp.s->t)
#define g_x2f (pp.s->x2f)
#define g_x1f (pp.s->x1f)
#define g_part (pp.s->part)
#define g_wr (pp.s->wr)
#define g_mod (pp.s->mod)
#define g_tab (pp.s->tab)
#define g_uv (pp.s->uv)
#define g_cs3 (pp.s->cs3)
#define g_cs3b (pp.s->cs3b)
#define g_stats (pp.s->stats)
#define g_cnt (pp.s->cnt)
#define g_epoch (pp.s->epoch)

struct Maps {
    CUtensorMap k, v, q;
    CUtensorMap qT;
    CUtensorMap x[3];
    CUtensorMap w1, w1h, w3h, wmod;
    CUtensorMap w2a, w2b;
    CUtensorMap w3a, w3b;
    CUtensorMap w4[2];
};

struct Ptrs {
    Scratch* s;
    uint64_t nil;
    const bf16 *q, *w_mod, *shift_k, *ssm_k, *ssm_D, *w1, *w2, *w4, *c;
};

constexpr int OFF_W = 0;
constexpr int OFF_XR = 131072;
constexpr int OFF_REM = 196608;
constexpr int OFF_TAB = OFF_REM + 5 * 4096;
constexpr int OFF_ROW = OFF_TAB + 4608;
constexpr int OFF_F1 = OFF_ROW + 4096;
constexpr int RECV_BYTES = 30720;
constexpr int OFF_M = OFF_REM + RECV_BYTES;
constexpr int OFF_OUT = OFF_XR + 32768;
static_assert(OFF_F1 + 1280 <= OFF_M, "G1 map");
constexpr int OFF_ST = 0;
constexpr int OFF_SSM = 20480;
constexpr int OFF_WM = 0;
constexpr int OFF_QIN = 49152;
constexpr int OFF_QT = 49152;
constexpr int OFF_Z = OFF_TAB;
constexpr int OFF_RING = 80896;
constexpr int OFF_KIN = OFF_RING, OFF_VIN = OFF_KIN + 2 * 10752;
constexpr int OFF_CH = OFF_RING + 3 * 16384, CH_BYTES = 13312, OFF_P = 5120;
static_assert(OFF_RING + 5 * 16384 <= OFF_CH + 3 * CH_BYTES && OFF_CH + 5 * CH_BYTES <= OFF_REM, "the last two rings replace channels 0..2");
constexpr int M_BAR = OFF_M;
constexpr int M_F1 = OFF_M + 832;
constexpr int M_GB = M_F1 + 1280, M_C = M_GB + 320, M_SB = M_C + 320, M_CI = M_SB + 320;
constexpr int M_KS = M_CI + 320;
constexpr int M_AB = M_KS + 160;
constexpr int M_EP = M_AB + 80;
constexpr int M_SINK = M_EP + 16;
constexpr int M_NUL = M_SINK + 16;
constexpr int M_TS = M_NUL + 128;
constexpr int SMEM_BYTES = M_TS;
static_assert(SMEM_BYTES <= 232448, "smem");

enum { B_WFULL = 0, B_WEMPTY = 8, B_XEMPTY = 16, B_XFULL = 24  ,
       B_RAW = 44, B_QIN = 45, B_SSM = 46, B_VEC = 47, B_VEC3 = 48, B_WM = 49, B_TAB = 50, B_QRDY = 51,
       B_MODR = 52, B_RAW2 = 53, B_RAW3 = 54, B_GATE = 56, B_SUMS = 62, B_RECV = 64  ,
       B_LAND = 72, B_AGAIN = 80, B_RETRY = 84,
       B_XS = 88, B_R1 = 89, B_BK = 90, B_KVS = 91,
       B_XFREE = 92, B_OWN = 93, B_IN = 94,
       B_RING = 96   };
#define T_KVB 1500
#define T_SSM 4200
#define PF_T0 5900
#define PF_DT 420
#define Q_UNROLL 1
#define HELP_T 1000
#define R_GATE 34
#define REG_AUX 48
#define REG_SVC 32
#define REG_MMA 216
#define STR2(x) #x
#define STR(x) STR2(x)
#define ST3 1
#define LD2 19
#define LD3 23
#define GATE_W2 7
#define GATE_W3 24
#define GATE_W3B 37
#define W3_N2 15
#define COEF_AT 8
#define LEAD2 5
#define LEAD1 5
#define XLEAD 4

#define SPIN_FAIL(code) __trap();
#define SPIN_LIMIT (1u << 22)
#define STALE(c)
#define STALE1(c)
#define TS(c, i)
#define TG(c, i)
#define TR(c, i)
#define TR2(c, i)
#define TR4(c, i)
#define TR5(c, i)
#define SPIN_CHECK(code) asm volatile("" ::"r"(it));
#define RARE(x) __builtin_expect((x) != 0, 0)
__device__ __forceinline__ uint32_t s2u(const void* p) { return (uint32_t)__cvta_generic_to_shared(p); }
__device__ __forceinline__ bool elect() {
    uint32_t p;
    asm volatile("{.reg .pred P; elect.sync _|P, 0xffffffff; selp.u32 %0,1,0,P;}" : "=r"(p));
    return p != 0;
}
__device__ __forceinline__ void mbar_init(uint32_t b, uint32_t n) { asm volatile("mbarrier.init.shared.b64 [%0], %1;" ::"r"(b), "r"(n)); }
__device__ __forceinline__ void mbar_expect(uint32_t b, uint32_t bytes) {
    asm volatile("mbarrier.arrive.expect_tx.shared.b64 _, [%0], %1;" ::"r"(b), "r"(bytes) : "memory");
}
__device__ __forceinline__ void mbar_arrive(uint32_t b) { asm volatile("mbarrier.arrive.shared.b64 _, [%0];" ::"r"(b) : "memory"); }
__device__ __forceinline__ void mbar_arrive_after(uint32_t b, uint32_t v0, uint32_t v1, uint32_t nil) { mbar_arrive(b + ((v0 | v1) & nil)); }
__device__ __forceinline__ void warp_arrive(uint32_t b) { __syncwarp(); if (elect()) mbar_arrive(b); }
__device__ __forceinline__ uint32_t peer_addr(uint32_t a) {
    uint32_t r;
    asm("{\n.reg .b32 q;\nmov.u32 q, %%cluster_ctarank;\nxor.b32 q, q, 1;\nmapa.shared::cluster.u32 %0, %1, q;\n}" : "=r"(r) : "r"(a));
    return r;
}
__device__ __forceinline__ bool mbar_test(uint32_t b, uint32_t parity) {
    uint32_t ok;
    asm volatile("{.reg .pred P; mbarrier.test_wait.parity.shared.b64 P, [%1], %2; selp.u32 %0,1,0,P;}" : "=r"(ok) : "r"(b), "r"(parity) : "memory");
    return ok != 0;
}
__device__ __forceinline__ bool mbar_try(uint32_t b, uint32_t parity) {
    uint32_t ok;
    asm volatile("{.reg .pred P; mbarrier.try_wait.parity.shared.b64 P, [%1], %2; selp.u32 %0,1,0,P;}" : "=r"(ok) : "r"(b), "r"(parity) : "memory");
    return ok != 0;
}
__device__ __forceinline__ void mbar_wait(uint32_t b, uint32_t parity) {
    if (__all_sync(0xffffffffu, mbar_try(b, parity))) return;
    uint32_t it = 0;
    while (!__all_sync(0xffffffffu, mbar_try(b, parity))) { if (++it > SPIN_LIMIT) SPIN_FAIL((b >> 3) & 63) }
}
__device__ __forceinline__ void mbar_spin(uint32_t b, uint32_t parity) {
    asm volatile("{\n.reg .pred P;\nSPIN:\nmbarrier.try_wait.parity.shared.b64 P, [%0], %1;\n@!P bra.uni SPIN;\n}" ::"r"(b), "r"(parity) : "memory");
}
__device__ __forceinline__ void bar_sync(int id, int n) { asm volatile("bar.sync %0, %1;" ::"r"(id), "r"(n) : "memory"); }
__device__ __forceinline__ void fence_async_smem() { asm volatile("fence.proxy.async.shared::cta;" ::: "memory"); }
__device__ __forceinline__ void wait_cnt(const unsigned* p, unsigned target, bool tagged = false) {
    unsigned v, it = 0;
    do {
        asm volatile("ld.relaxed.gpu.global.u32 %0, [%1];" : "=r"(v) : "l"(p) : "memory");
        SPIN_CHECK(60 + (target & 3))
    } while (!__all_sync(0xffffffffu, v >= target));
    if (!tagged) asm volatile("fence.acquire.gpu;" ::: "memory");
}
__device__ __forceinline__ void signal_cnt(unsigned* p, int lane, int n, bool tagged = false) {
    if (tagged) asm volatile("{\n.reg .pred P;\nsetp.lt.s32 P, %1, %2;\n@P red.relaxed.gpu.global.add.u32 [%0], %3;\n}" ::"l"(p), "r"(lane), "r"(n), "r"(1) : "memory");
    else if (lane < n) asm volatile("red.release.gpu.global.add.u32 [%0], 1;" ::"l"(p) : "memory");
    __syncwarp();
}
__device__ __forceinline__ uint32_t clock_lo() { uint32_t c; asm volatile("mov.u32 %0, %%clock;" : "=r"(c)); return c; }
__device__ __forceinline__ void wait_clock(uint32_t c0, uint32_t t) {
    asm volatile("{\n.reg .pred P;\n.reg .b32 c;\nWAIT:\nnanosleep.u32 20;\nmov.u32 c, %%clock;\nsub.u32 c, c, %0;\nsetp.lt.u32 P, c, %1;\n@P bra.uni WAIT;\n}" ::"r"(c0), "r"(t) : "memory");
}
__device__ __forceinline__ void tma_ld2(uint32_t dst, const CUtensorMap* m, int c0, int c1, uint32_t bar) {
    asm volatile("cp.async.bulk.tensor.2d.shared::cluster.global.mbarrier::complete_tx::bytes [%0], [%1, {%3, %4}], [%2];"
                 ::"r"(dst), "l"(m), "r"(bar), "r"(c0), "r"(c1) : "memory");
}
__device__ __forceinline__ void tma_ld3(uint32_t dst, const CUtensorMap* m, int c0, int c1, int c2, uint32_t bar) {
    asm volatile("cp.async.bulk.tensor.3d.shared::cluster.global.mbarrier::complete_tx::bytes [%0], [%1, {%3, %4, %5}], [%2];"
                 ::"r"(dst), "l"(m), "r"(bar), "r"(c0), "r"(c1), "r"(c2) : "memory");
}
__device__ __forceinline__ void tma_ld5(uint32_t dst, const CUtensorMap* m, int col, int blk, uint32_t bar) {
    asm volatile("cp.async.bulk.tensor.5d.shared::cluster.global.mbarrier::complete_tx::bytes [%0], [%1, {%3, %4, %4, %4, %5}], [%2];"
                 ::"r"(dst), "l"(m), "r"(bar), "r"(col), "r"(0), "r"(blk) : "memory");
}
__device__ __forceinline__ void bulk_ld(uint32_t dst, const void* src, uint32_t bytes, uint32_t bar) {
    asm volatile("cp.async.bulk.shared::cluster.global.mbarrier::complete_tx::bytes [%0], [%1], %2, [%3];" ::"r"(dst), "l"(src), "r"(bytes), "r"(bar) : "memory");
}
__device__ __forceinline__ void l2_prefetch(const void* p, uint32_t bytes) {
    asm volatile("cp.async.bulk.prefetch.L2.global [%0], %1;" ::"l"(p), "r"(bytes) : "memory");
}
__device__ __forceinline__ void wg_fence() { asm volatile("wgmma.fence.sync.aligned;" ::: "memory"); }
__device__ __forceinline__ void wg_commit() { asm volatile("wgmma.commit_group.sync.aligned;" ::: "memory"); }
template <int N> __device__ __forceinline__ void wg_wait() { asm volatile("wgmma.wait_group.sync.aligned %0;" ::"n"(N) : "memory"); }
template <int N> __device__ __forceinline__ void reg_fence(float (&d)[N]) {
#pragma unroll
    for (int i = 0; i < N; i++) asm volatile("" : "+f"(d[i])::"memory");
}
template <int N> __device__ __forceinline__ void zero(float (&d)[N]) {
#pragma unroll
    for (int i = 0; i < N; i++) asm volatile("mov.b32 %0, 0;" : "=f"(d[i]));
}
__device__ __forceinline__ uint32_t lds32(uint32_t a) { uint32_t v; asm volatile("ld.shared.b32 %0, [%1];" : "=r"(v) : "r"(a)); return v; }
__device__ __forceinline__ uint2 lds64(uint32_t a) { uint2 v; asm volatile("ld.shared.v2.b32 {%0,%1}, [%2];" : "=r"(v.x), "=r"(v.y) : "r"(a)); return v; }
__device__ __forceinline__ float2 lds64f(uint32_t a) { float2 v; asm volatile("ld.shared.v2.f32 {%0,%1}, [%2];" : "=f"(v.x), "=f"(v.y) : "r"(a)); return v; }
__device__ __forceinline__ void sts32(uint32_t a, uint32_t v) { asm volatile("st.shared.b32 [%0], %1;" ::"r"(a), "r"(v) : "memory"); }
__device__ __forceinline__ void sts64f(uint32_t a, float x, float y) { asm volatile("st.shared.v2.f32 [%0], {%1,%2};" ::"r"(a), "f"(x), "f"(y) : "memory"); }
__device__ __forceinline__ void sts128(uint32_t a, uint32_t x, uint32_t y, uint32_t z, uint32_t w) {
    asm volatile("st.shared.v4.b32 [%0], {%1,%2,%3,%4};" ::"r"(a), "r"(x), "r"(y), "r"(z), "r"(w) : "memory");
}
__device__ __forceinline__ void sts128f(uint32_t a, float x, float y, float z, float w) {
    asm volatile("st.shared.v4.f32 [%0], {%1,%2,%3,%4};" ::"r"(a), "f"(x), "f"(y), "f"(z), "f"(w) : "memory");
}
__device__ __forceinline__ uint4 lds128(uint32_t a) {
    uint4 v;
    asm volatile("ld.shared.v4.b32 {%0,%1,%2,%3}, [%4];" : "=r"(v.x), "=r"(v.y), "=r"(v.z), "=r"(v.w) : "r"(a) : "memory");
    return v;
}
__device__ __forceinline__ void lds128_if(int p, uint4& v, uint32_t a) {
    asm volatile("{\n.reg .pred p;\nsetp.ne.s32 p, %5, 0;\n@p ld.shared.v4.b32 {%0,%1,%2,%3}, [%4];\n}" : "+r"(v.x), "+r"(v.y), "+r"(v.z), "+r"(v.w) : "r"(a), "r"(p) : "memory");
}
__device__ __forceinline__ float4 lds128f(uint32_t a) {
    float4 v;
    asm volatile("ld.shared.v4.f32 {%0,%1,%2,%3}, [%4];" : "=f"(v.x), "=f"(v.y), "=f"(v.z), "=f"(v.w) : "r"(a) : "memory");
    return v;
}
__device__ __forceinline__ void stg128(void* p, uint32_t x, uint32_t y, uint32_t z, uint32_t w) {
    asm volatile("st.global.v4.b32 [%0], {%1,%2,%3,%4};" ::"l"(p), "r"(x), "r"(y), "r"(z), "r"(w) : "memory");
}
__device__ __forceinline__ void stg128(void* p, uint4 v) { stg128(p, v.x, v.y, v.z, v.w); }
__device__ __forceinline__ void stg128_if(void* p, uint4 v, int on) {
    asm volatile("{\n.reg .pred p;\nsetp.ne.s32 p, %5, 0;\n@p st.global.v4.b32 [%0], {%1,%2,%3,%4};\n}" ::"l"(p), "r"(v.x), "r"(v.y), "r"(v.z), "r"(v.w), "r"(on) : "memory");
}
__device__ __forceinline__ void stg64(void* p, uint32_t x, uint32_t y) { asm volatile("st.global.v2.b32 [%0], {%1,%2};" ::"l"(p), "r"(x), "r"(y) : "memory"); }
__device__ __forceinline__ void stsm4(uint32_t a, uint32_t r0, uint32_t r1, uint32_t r2, uint32_t r3) {
    asm volatile("stmatrix.sync.aligned.m8n8.x4.shared.b16 [%0], {%1,%2,%3,%4};" ::"r"(a), "r"(r0), "r"(r1), "r"(r2), "r"(r3) : "memory");
}
__device__ __forceinline__ void stsm4t(uint32_t a, uint32_t r0, uint32_t r1, uint32_t r2, uint32_t r3) {
    asm volatile("stmatrix.sync.aligned.m8n8.x4.trans.shared.b16 [%0], {%1,%2,%3,%4};" ::"r"(a), "r"(r0), "r"(r1), "r"(r2), "r"(r3) : "memory");
}
__device__ __forceinline__ void ldsm4t_if(bool p, uint32_t a, uint32_t* r) {
    asm volatile("{\n.reg .pred p;\nsetp.ne.u32 p, %5, 0;\n@p ldmatrix.sync.aligned.m8n8.x4.trans.shared.b16 {%0,%1,%2,%3}, [%4];\n}"
                 : "+r"(r[0]), "+r"(r[1]), "+r"(r[2]), "+r"(r[3]) : "r"(a), "r"((uint32_t)p) : "memory");
}
__device__ __forceinline__ void ldsm4t(uint32_t a, uint32_t& r0, uint32_t& r1, uint32_t& r2, uint32_t& r3) {
    asm volatile("ldmatrix.sync.aligned.m8n8.x4.trans.shared.b16 {%0,%1,%2,%3}, [%4];" : "=r"(r0), "=r"(r1), "=r"(r2), "=r"(r3) : "r"(a) : "memory");
}
__device__ __forceinline__ uint32_t pack2(float lo, float hi) {
    uint32_t r;
    asm("cvt.rn.bf16x2.f32 %0, %1, %2;" : "=r"(r) : "f"(hi), "f"(lo));
    return r;
}
__device__ __forceinline__ uint32_t mul2(uint32_t a, uint32_t b) { uint32_t r; asm("mul.rn.bf16x2 %0, %1, %2;" : "=r"(r) : "r"(a), "r"(b)); return r; }
__device__ __forceinline__ uint32_t fma2(uint32_t a, uint32_t b, uint32_t c) { uint32_t r; asm("fma.rn.bf16x2 %0, %1, %2, %3;" : "=r"(r) : "r"(a), "r"(b), "r"(c)); return r; }
__device__ __forceinline__ uint32_t add2(uint32_t a, uint32_t b) { uint32_t r; asm("add.rn.bf16x2 %0, %1, %2;" : "=r"(r) : "r"(a), "r"(b)); return r; }
__device__ __forceinline__ void hmma(float (&d)[4], uint32_t a0, uint32_t a1, uint32_t a2, uint32_t a3, uint32_t b0, uint32_t b1) {
    asm volatile("mma.sync.aligned.m16n8k16.row.col.f32.bf16.bf16.f32 {%0,%1,%2,%3}, {%4,%5,%6,%7}, {%8,%9}, {%0,%1,%2,%3};"
        : "+f"(d[0]), "+f"(d[1]), "+f"(d[2]), "+f"(d[3]) : "r"(a0), "r"(a1), "r"(a2), "r"(a3), "r"(b0), "r"(b1));
}
__device__ __forceinline__ float blo(uint32_t w) { return __uint_as_float(w << 16); }
__device__ __forceinline__ float bhi(uint32_t w) { return __uint_as_float(w & 0xffff0000u); }
__device__ __forceinline__ float rbf(float x) { return __bfloat162float(__float2bfloat16_rn(x)); }
__device__ __forceinline__ uint32_t ldg32(const void* p) { uint32_t v; asm volatile("ld.global.nc.b32 %0, [%1];" : "=r"(v) : "l"(p)); return v; }
__device__ __forceinline__ uint2 ldg64(const void* p) { uint2 v; asm volatile("ld.global.nc.v2.b32 {%0,%1}, [%2];" : "=r"(v.x), "=r"(v.y) : "l"(p)); return v; }
__device__ __forceinline__ uint4 ldg128(const void* p) {
    uint4 v;
    asm volatile("ld.global.nc.v4.b32 {%0,%1,%2,%3}, [%4];" : "=r"(v.x), "=r"(v.y), "=r"(v.z), "=r"(v.w) : "l"(p));
    return v;
}
__device__ __forceinline__ uint4 ldcg128(const void* p) {
    uint4 v;
    asm volatile("ld.global.cg.v4.u32 {%0,%1,%2,%3}, [%4];" : "=r"(v.x), "=r"(v.y), "=r"(v.z), "=r"(v.w) : "l"(p) : "memory");
    return v;
}
__device__ __forceinline__ float4 ldcg128f(const void* p) {
    float4 v;
    asm volatile("ld.global.cg.v4.f32 {%0,%1,%2,%3}, [%4];" : "=f"(v.x), "=f"(v.y), "=f"(v.z), "=f"(v.w) : "l"(p) : "memory");
    return v;
}
__device__ __forceinline__ float2 ldcg64f(const void* p) { float2 v; asm volatile("ld.global.cg.v2.f32 {%0,%1}, [%2];" : "=f"(v.x), "=f"(v.y) : "l"(p) : "memory"); return v; }
__device__ __forceinline__ float ldcg32f(const void* p) { float v; asm volatile("ld.global.cg.f32 %0, [%1];" : "=f"(v) : "l"(p) : "memory"); return v; }
__device__ __forceinline__ float2 ld_stat(const float2* p) {
    float2 v;
    asm volatile("{\n.reg .b64 q;\nld.relaxed.gpu.global.b64 q, [%2];\nmov.b64 {%0, %1}, q;\n}" : "=f"(v.x), "=f"(v.y) : "l"(p) : "memory");
    return v;
}
__device__ __forceinline__ uint32_t ld_cold(const unsigned* p) { uint32_t v; asm volatile("ld.relaxed.gpu.global.u32 %0, [%1];" : "=r"(v) : "l"(p) : "memory"); return v; }
__device__ __forceinline__ uint2 ld_mod(const uint2* p) {
    uint64_t v;
    asm volatile("ld.relaxed.gpu.global.b64 %0, [%1];" : "=l"(v) : "l"(p) : "memory");
    return make_uint2((uint32_t)v, (uint32_t)(v >> 32));
}
__device__ __forceinline__ float silu(float x) {
    float e, r;
    asm("ex2.approx.ftz.f32 %0, %1;" : "=f"(e) : "f"(x * -1.4426950408889634f));
    asm("rcp.approx.ftz.f32 %0, %1;" : "=f"(r) : "f"(1.f + e));
    return x * r;
}
__device__ __forceinline__ float gelu2(float h) {
    float u = h * fmaf(h * h, 8.f * 0.0356774081f, 2.f * 0.7978845608f);
    float th;
    asm("tanh.approx.f32 %0, %1;" : "=f"(th) : "f"(u));
    return fmaf(h, th, h);
}
__device__ __forceinline__ float gelu2r(float a, float2 k) {
    float th;
    asm("tanh.approx.f32 %0, %1;" : "=f"(th) : "f"(a * fmaf(a * a, k.x, k.y)));
    return fmaf(a, th, a);
}

__device__ __forceinline__ void conv_channel(float (&d)[64], uint32_t pa, uint64_t db) {
    asm volatile("{\n.reg .b32 a0, a1, a2, a3, b0, b1, b2, b3, t0, t1;\n.reg .b64 d;\nld.shared.b32 a0, [%64];\nld.shared.b32 a1, [%64+128];\nld.shared.b32 a2, [%64+-128];\nmov.b32 a3, a0;\n"
        "ld.shared.b32 t0, [%64+256];\nld.shared.b32 t1, [%64+384];\nadd.s64 d, %65, 0;\nwgmma.fence.sync.aligned;\nwgmma.mma_async.sync.aligned.m64n128k16.f32.bf16.bf16 {%0, %1, %2, %3, %4, %5, %6, %7, %8, %9, %10, %11, %12, %13, %14, %15, %16, %17, %18, %19, %20, %21, %22, %23, %24, %25, %26, %27, %28, %29, %30, %31, %32, %33, %34, %35, %36, %37, %38, %39, %40, %41, %42, %43, %44, %45, %46, %47, %48, %49, %50, %51, %52, %53, %54, %55, %56, %57, %58, %59, %60, %61, %62, %63}, {a0, a1, a2, a3}, d, 0, 1, 1, 0;\nwgmma.commit_group.sync.aligned;\nwgmma.wait_group.sync.aligned 1;\nmov.b32 b2, a1;\nmov.b32 b0, t0;\nmov.b32 b3, t0;\nmov.b32 b1, t1;\n"
        "ld.shared.b32 t0, [%64+512];\nld.shared.b32 t1, [%64+640];\nadd.s64 d, %65, 8;\nwgmma.fence.sync.aligned;\nwgmma.mma_async.sync.aligned.m64n128k16.f32.bf16.bf16 {%0, %1, %2, %3, %4, %5, %6, %7, %8, %9, %10, %11, %12, %13, %14, %15, %16, %17, %18, %19, %20, %21, %22, %23, %24, %25, %26, %27, %28, %29, %30, %31, %32, %33, %34, %35, %36, %37, %38, %39, %40, %41, %42, %43, %44, %45, %46, %47, %48, %49, %50, %51, %52, %53, %54, %55, %56, %57, %58, %59, %60, %61, %62, %63}, {b0, b1, b2, b3}, d, 1, 1, 1, 0;\nwgmma.commit_group.sync.aligned;\nwgmma.wait_group.sync.aligned 1;\nmov.b32 a2, b1;\nmov.b32 a0, t0;\nmov.b32 a3, t0;\nmov.b32 a1, t1;\n"
        "ld.shared.b32 t0, [%64+768];\nld.shared.b32 t1, [%64+896];\nadd.s64 d, %65, 16;\nwgmma.fence.sync.aligned;\nwgmma.mma_async.sync.aligned.m64n128k16.f32.bf16.bf16 {%0, %1, %2, %3, %4, %5, %6, %7, %8, %9, %10, %11, %12, %13, %14, %15, %16, %17, %18, %19, %20, %21, %22, %23, %24, %25, %26, %27, %28, %29, %30, %31, %32, %33, %34, %35, %36, %37, %38, %39, %40, %41, %42, %43, %44, %45, %46, %47, %48, %49, %50, %51, %52, %53, %54, %55, %56, %57, %58, %59, %60, %61, %62, %63}, {a0, a1, a2, a3}, d, 1, 1, 1, 0;\nwgmma.commit_group.sync.aligned;\nwgmma.wait_group.sync.aligned 1;\nmov.b32 b2, a1;\nmov.b32 b0, t0;\nmov.b32 b3, t0;\nmov.b32 b1, t1;\n"
        "ld.shared.b32 t0, [%64+1024];\nld.shared.b32 t1, [%64+1152];\nadd.s64 d, %65, 24;\nwgmma.fence.sync.aligned;\nwgmma.mma_async.sync.aligned.m64n128k16.f32.bf16.bf16 {%0, %1, %2, %3, %4, %5, %6, %7, %8, %9, %10, %11, %12, %13, %14, %15, %16, %17, %18, %19, %20, %21, %22, %23, %24, %25, %26, %27, %28, %29, %30, %31, %32, %33, %34, %35, %36, %37, %38, %39, %40, %41, %42, %43, %44, %45, %46, %47, %48, %49, %50, %51, %52, %53, %54, %55, %56, %57, %58, %59, %60, %61, %62, %63}, {b0, b1, b2, b3}, d, 1, 1, 1, 0;\nwgmma.commit_group.sync.aligned;\nwgmma.wait_group.sync.aligned 1;\nmov.b32 a2, b1;\nmov.b32 a0, t0;\nmov.b32 a3, t0;\nmov.b32 a1, t1;\n"
        "ld.shared.b32 t0, [%64+1280];\nld.shared.b32 t1, [%64+1408];\nadd.s64 d, %65, 32;\nwgmma.fence.sync.aligned;\nwgmma.mma_async.sync.aligned.m64n128k16.f32.bf16.bf16 {%0, %1, %2, %3, %4, %5, %6, %7, %8, %9, %10, %11, %12, %13, %14, %15, %16, %17, %18, %19, %20, %21, %22, %23, %24, %25, %26, %27, %28, %29, %30, %31, %32, %33, %34, %35, %36, %37, %38, %39, %40, %41, %42, %43, %44, %45, %46, %47, %48, %49, %50, %51, %52, %53, %54, %55, %56, %57, %58, %59, %60, %61, %62, %63}, {a0, a1, a2, a3}, d, 1, 1, 1, 0;\nwgmma.commit_group.sync.aligned;\nwgmma.wait_group.sync.aligned 1;\nmov.b32 b2, a1;\nmov.b32 b0, t0;\nmov.b32 b3, t0;\nmov.b32 b1, t1;\n"
        "ld.shared.b32 t0, [%64+1536];\nld.shared.b32 t1, [%64+1664];\nadd.s64 d, %65, 40;\nwgmma.fence.sync.aligned;\nwgmma.mma_async.sync.aligned.m64n128k16.f32.bf16.bf16 {%0, %1, %2, %3, %4, %5, %6, %7, %8, %9, %10, %11, %12, %13, %14, %15, %16, %17, %18, %19, %20, %21, %22, %23, %24, %25, %26, %27, %28, %29, %30, %31, %32, %33, %34, %35, %36, %37, %38, %39, %40, %41, %42, %43, %44, %45, %46, %47, %48, %49, %50, %51, %52, %53, %54, %55, %56, %57, %58, %59, %60, %61, %62, %63}, {b0, b1, b2, b3}, d, 1, 1, 1, 0;\nwgmma.commit_group.sync.aligned;\nwgmma.wait_group.sync.aligned 1;\nmov.b32 a2, b1;\nmov.b32 a0, t0;\nmov.b32 a3, t0;\nmov.b32 a1, t1;\n"
        "ld.shared.b32 t0, [%64+1792];\nld.shared.b32 t1, [%64+1920];\nadd.s64 d, %65, 48;\nwgmma.fence.sync.aligned;\nwgmma.mma_async.sync.aligned.m64n128k16.f32.bf16.bf16 {%0, %1, %2, %3, %4, %5, %6, %7, %8, %9, %10, %11, %12, %13, %14, %15, %16, %17, %18, %19, %20, %21, %22, %23, %24, %25, %26, %27, %28, %29, %30, %31, %32, %33, %34, %35, %36, %37, %38, %39, %40, %41, %42, %43, %44, %45, %46, %47, %48, %49, %50, %51, %52, %53, %54, %55, %56, %57, %58, %59, %60, %61, %62, %63}, {a0, a1, a2, a3}, d, 1, 1, 1, 0;\nwgmma.commit_group.sync.aligned;\nwgmma.wait_group.sync.aligned 1;\nmov.b32 b2, a1;\nmov.b32 b0, t0;\nmov.b32 b3, t0;\nmov.b32 b1, t1;\n"
        "ld.shared.b32 t0, [%64+2048];\nld.shared.b32 t1, [%64+2176];\nadd.s64 d, %65, 56;\nwgmma.fence.sync.aligned;\nwgmma.mma_async.sync.aligned.m64n128k16.f32.bf16.bf16 {%0, %1, %2, %3, %4, %5, %6, %7, %8, %9, %10, %11, %12, %13, %14, %15, %16, %17, %18, %19, %20, %21, %22, %23, %24, %25, %26, %27, %28, %29, %30, %31, %32, %33, %34, %35, %36, %37, %38, %39, %40, %41, %42, %43, %44, %45, %46, %47, %48, %49, %50, %51, %52, %53, %54, %55, %56, %57, %58, %59, %60, %61, %62, %63}, {b0, b1, b2, b3}, d, 1, 1, 1, 0;\nwgmma.commit_group.sync.aligned;\nwgmma.wait_group.sync.aligned 1;\nmov.b32 a2, b1;\nmov.b32 a0, t0;\nmov.b32 a3, t0;\nmov.b32 a1, t1;\n"
        "ld.shared.b32 t0, [%64+2304];\nld.shared.b32 t1, [%64+2432];\nadd.s64 d, %65, 64;\nwgmma.fence.sync.aligned;\nwgmma.mma_async.sync.aligned.m64n96k16.f32.bf16.bf16 {%0, %1, %2, %3, %4, %5, %6, %7, %8, %9, %10, %11, %12, %13, %14, %15, %16, %17, %18, %19, %20, %21, %22, %23, %24, %25, %26, %27, %28, %29, %30, %31, %32, %33, %34, %35, %36, %37, %38, %39, %40, %41, %42, %43, %44, %45, %46, %47}, {a0, a1, a2, a3}, d, 1, 1, 1, 0;\nwgmma.commit_group.sync.aligned;\nwgmma.wait_group.sync.aligned 1;\nmov.b32 b2, a1;\nmov.b32 b0, t0;\nmov.b32 b3, t0;\nmov.b32 b1, t1;\n"
        "ld.shared.b32 t0, [%64+2560];\nld.shared.b32 t1, [%64+2688];\nadd.s64 d, %65, 72;\nwgmma.fence.sync.aligned;\nwgmma.mma_async.sync.aligned.m64n96k16.f32.bf16.bf16 {%0, %1, %2, %3, %4, %5, %6, %7, %8, %9, %10, %11, %12, %13, %14, %15, %16, %17, %18, %19, %20, %21, %22, %23, %24, %25, %26, %27, %28, %29, %30, %31, %32, %33, %34, %35, %36, %37, %38, %39, %40, %41, %42, %43, %44, %45, %46, %47}, {b0, b1, b2, b3}, d, 1, 1, 1, 0;\nwgmma.commit_group.sync.aligned;\nwgmma.wait_group.sync.aligned 1;\nmov.b32 a2, b1;\nmov.b32 a0, t0;\nmov.b32 a3, t0;\nmov.b32 a1, t1;\n"
        "ld.shared.b32 t0, [%64+2816];\nld.shared.b32 t1, [%64+2944];\nadd.s64 d, %65, 80;\nwgmma.fence.sync.aligned;\nwgmma.mma_async.sync.aligned.m64n88k16.f32.bf16.bf16 {%0, %1, %2, %3, %4, %5, %6, %7, %8, %9, %10, %11, %12, %13, %14, %15, %16, %17, %18, %19, %20, %21, %22, %23, %24, %25, %26, %27, %28, %29, %30, %31, %32, %33, %34, %35, %36, %37, %38, %39, %40, %41, %42, %43}, {a0, a1, a2, a3}, d, 1, 1, 1, 0;\nwgmma.commit_group.sync.aligned;\nwgmma.wait_group.sync.aligned 1;\nmov.b32 b2, a1;\nmov.b32 b0, t0;\nmov.b32 b3, t0;\nmov.b32 b1, t1;\n"
        "ld.shared.b32 t0, [%64+3072];\nld.shared.b32 t1, [%64+3200];\nadd.s64 d, %65, 88;\nwgmma.fence.sync.aligned;\nwgmma.mma_async.sync.aligned.m64n88k16.f32.bf16.bf16 {%0, %1, %2, %3, %4, %5, %6, %7, %8, %9, %10, %11, %12, %13, %14, %15, %16, %17, %18, %19, %20, %21, %22, %23, %24, %25, %26, %27, %28, %29, %30, %31, %32, %33, %34, %35, %36, %37, %38, %39, %40, %41, %42, %43}, {b0, b1, b2, b3}, d, 1, 1, 1, 0;\nwgmma.commit_group.sync.aligned;\nwgmma.wait_group.sync.aligned 1;\nmov.b32 a2, b1;\nmov.b32 a0, t0;\nmov.b32 a3, t0;\nmov.b32 a1, t1;\n"
        "ld.shared.b32 t0, [%64+3328];\nld.shared.b32 t1, [%64+3456];\nadd.s64 d, %65, 96;\nwgmma.fence.sync.aligned;\nwgmma.mma_async.sync.aligned.m64n80k16.f32.bf16.bf16 {%0, %1, %2, %3, %4, %5, %6, %7, %8, %9, %10, %11, %12, %13, %14, %15, %16, %17, %18, %19, %20, %21, %22, %23, %24, %25, %26, %27, %28, %29, %30, %31, %32, %33, %34, %35, %36, %37, %38, %39}, {a0, a1, a2, a3}, d, 1, 1, 1, 0;\nwgmma.commit_group.sync.aligned;\nwgmma.wait_group.sync.aligned 1;\nmov.b32 b2, a1;\nmov.b32 b0, t0;\nmov.b32 b3, t0;\nmov.b32 b1, t1;\n"
        "ld.shared.b32 t0, [%64+3584];\nld.shared.b32 t1, [%64+3712];\nadd.s64 d, %65, 104;\nwgmma.fence.sync.aligned;\nwgmma.mma_async.sync.aligned.m64n80k16.f32.bf16.bf16 {%0, %1, %2, %3, %4, %5, %6, %7, %8, %9, %10, %11, %12, %13, %14, %15, %16, %17, %18, %19, %20, %21, %22, %23, %24, %25, %26, %27, %28, %29, %30, %31, %32, %33, %34, %35, %36, %37, %38, %39}, {b0, b1, b2, b3}, d, 1, 1, 1, 0;\nwgmma.commit_group.sync.aligned;\nwgmma.wait_group.sync.aligned 1;\nmov.b32 a2, b1;\nmov.b32 a0, t0;\nmov.b32 a3, t0;\nmov.b32 a1, t1;\n"
        "ld.shared.b32 t0, [%64+3840];\nld.shared.b32 t1, [%64+3968];\nadd.s64 d, %65, 112;\nwgmma.fence.sync.aligned;\nwgmma.mma_async.sync.aligned.m64n72k16.f32.bf16.bf16 {%0, %1, %2, %3, %4, %5, %6, %7, %8, %9, %10, %11, %12, %13, %14, %15, %16, %17, %18, %19, %20, %21, %22, %23, %24, %25, %26, %27, %28, %29, %30, %31, %32, %33, %34, %35}, {a0, a1, a2, a3}, d, 1, 1, 1, 0;\nwgmma.commit_group.sync.aligned;\nwgmma.wait_group.sync.aligned 1;\nmov.b32 b2, a1;\nmov.b32 b0, t0;\nmov.b32 b3, t0;\nmov.b32 b1, t1;\n"
        "ld.shared.b32 t0, [%64+4096];\nld.shared.b32 t1, [%64+4224];\nadd.s64 d, %65, 120;\nwgmma.fence.sync.aligned;\nwgmma.mma_async.sync.aligned.m64n72k16.f32.bf16.bf16 {%0, %1, %2, %3, %4, %5, %6, %7, %8, %9, %10, %11, %12, %13, %14, %15, %16, %17, %18, %19, %20, %21, %22, %23, %24, %25, %26, %27, %28, %29, %30, %31, %32, %33, %34, %35}, {b0, b1, b2, b3}, d, 1, 1, 1, 0;\nwgmma.commit_group.sync.aligned;\nwgmma.wait_group.sync.aligned 1;\nmov.b32 a2, b1;\nmov.b32 a0, t0;\nmov.b32 a3, t0;\nmov.b32 a1, t1;\n"
        "ld.shared.b32 t0, [%64+4352];\nld.shared.b32 t1, [%64+4480];\nadd.s64 d, %65, 128;\nwgmma.fence.sync.aligned;\nwgmma.mma_async.sync.aligned.m64n64k16.f32.bf16.bf16 {%0, %1, %2, %3, %4, %5, %6, %7, %8, %9, %10, %11, %12, %13, %14, %15, %16, %17, %18, %19, %20, %21, %22, %23, %24, %25, %26, %27, %28, %29, %30, %31}, {a0, a1, a2, a3}, d, 1, 1, 1, 0;\nwgmma.commit_group.sync.aligned;\nwgmma.wait_group.sync.aligned 1;\nmov.b32 b2, a1;\nmov.b32 b0, t0;\nmov.b32 b3, t0;\nmov.b32 b1, t1;\n"
        "ld.shared.b32 t0, [%64+4608];\nld.shared.b32 t1, [%64+4736];\nadd.s64 d, %65, 136;\nwgmma.fence.sync.aligned;\nwgmma.mma_async.sync.aligned.m64n64k16.f32.bf16.bf16 {%0, %1, %2, %3, %4, %5, %6, %7, %8, %9, %10, %11, %12, %13, %14, %15, %16, %17, %18, %19, %20, %21, %22, %23, %24, %25, %26, %27, %28, %29, %30, %31}, {b0, b1, b2, b3}, d, 1, 1, 1, 0;\nwgmma.commit_group.sync.aligned;\nwgmma.wait_group.sync.aligned 1;\nmov.b32 a2, b1;\nmov.b32 a0, t0;\nmov.b32 a3, t0;\nmov.b32 a1, t1;\n"
        "ld.shared.b32 t0, [%64+4864];\nld.shared.b32 t1, [%64+4992];\nadd.s64 d, %65, 144;\nwgmma.fence.sync.aligned;\nwgmma.mma_async.sync.aligned.m64n56k16.f32.bf16.bf16 {%0, %1, %2, %3, %4, %5, %6, %7, %8, %9, %10, %11, %12, %13, %14, %15, %16, %17, %18, %19, %20, %21, %22, %23, %24, %25, %26, %27}, {a0, a1, a2, a3}, d, 1, 1, 1, 0;\nwgmma.commit_group.sync.aligned;\nwgmma.wait_group.sync.aligned 1;\nmov.b32 b2, a1;\nmov.b32 b0, t0;\nmov.b32 b3, t0;\nmov.b32 b1, t1;\n"
        "ld.shared.b32 t0, [%64+5120];\nld.shared.b32 t1, [%64+5248];\nadd.s64 d, %65, 152;\nwgmma.fence.sync.aligned;\nwgmma.mma_async.sync.aligned.m64n56k16.f32.bf16.bf16 {%0, %1, %2, %3, %4, %5, %6, %7, %8, %9, %10, %11, %12, %13, %14, %15, %16, %17, %18, %19, %20, %21, %22, %23, %24, %25, %26, %27}, {b0, b1, b2, b3}, d, 1, 1, 1, 0;\nwgmma.commit_group.sync.aligned;\nwgmma.wait_group.sync.aligned 1;\nmov.b32 a2, b1;\nmov.b32 a0, t0;\nmov.b32 a3, t0;\nmov.b32 a1, t1;\n"
        "ld.shared.b32 t0, [%64+5376];\nld.shared.b32 t1, [%64+5504];\nadd.s64 d, %65, 160;\nwgmma.fence.sync.aligned;\nwgmma.mma_async.sync.aligned.m64n48k16.f32.bf16.bf16 {%0, %1, %2, %3, %4, %5, %6, %7, %8, %9, %10, %11, %12, %13, %14, %15, %16, %17, %18, %19, %20, %21, %22, %23}, {a0, a1, a2, a3}, d, 1, 1, 1, 0;\nwgmma.commit_group.sync.aligned;\nwgmma.wait_group.sync.aligned 1;\nmov.b32 b2, a1;\nmov.b32 b0, t0;\nmov.b32 b3, t0;\nmov.b32 b1, t1;\n"
        "ld.shared.b32 t0, [%64+5632];\nld.shared.b32 t1, [%64+5760];\nadd.s64 d, %65, 168;\nwgmma.fence.sync.aligned;\nwgmma.mma_async.sync.aligned.m64n48k16.f32.bf16.bf16 {%0, %1, %2, %3, %4, %5, %6, %7, %8, %9, %10, %11, %12, %13, %14, %15, %16, %17, %18, %19, %20, %21, %22, %23}, {b0, b1, b2, b3}, d, 1, 1, 1, 0;\nwgmma.commit_group.sync.aligned;\nwgmma.wait_group.sync.aligned 1;\nmov.b32 a2, b1;\nmov.b32 a0, t0;\nmov.b32 a3, t0;\nmov.b32 a1, t1;\n"
        "ld.shared.b32 t0, [%64+5888];\nld.shared.b32 t1, [%64+6016];\nadd.s64 d, %65, 176;\nwgmma.fence.sync.aligned;\nwgmma.mma_async.sync.aligned.m64n40k16.f32.bf16.bf16 {%0, %1, %2, %3, %4, %5, %6, %7, %8, %9, %10, %11, %12, %13, %14, %15, %16, %17, %18, %19}, {a0, a1, a2, a3}, d, 1, 1, 1, 0;\nwgmma.commit_group.sync.aligned;\nwgmma.wait_group.sync.aligned 1;\nmov.b32 b2, a1;\nmov.b32 b0, t0;\nmov.b32 b3, t0;\nmov.b32 b1, t1;\n"
        "ld.shared.b32 t0, [%64+6144];\nld.shared.b32 t1, [%64+6272];\nadd.s64 d, %65, 184;\nwgmma.fence.sync.aligned;\nwgmma.mma_async.sync.aligned.m64n40k16.f32.bf16.bf16 {%0, %1, %2, %3, %4, %5, %6, %7, %8, %9, %10, %11, %12, %13, %14, %15, %16, %17, %18, %19}, {b0, b1, b2, b3}, d, 1, 1, 1, 0;\nwgmma.commit_group.sync.aligned;\nwgmma.wait_group.sync.aligned 1;\nmov.b32 a2, b1;\nmov.b32 a0, t0;\nmov.b32 a3, t0;\nmov.b32 a1, t1;\n"
        "ld.shared.b32 t0, [%64+6400];\nld.shared.b32 t1, [%64+6528];\nadd.s64 d, %65, 192;\nwgmma.fence.sync.aligned;\nwgmma.mma_async.sync.aligned.m64n32k16.f32.bf16.bf16 {%0, %1, %2, %3, %4, %5, %6, %7, %8, %9, %10, %11, %12, %13, %14, %15}, {a0, a1, a2, a3}, d, 1, 1, 1, 0;\nwgmma.commit_group.sync.aligned;\nwgmma.wait_group.sync.aligned 1;\nmov.b32 b2, a1;\nmov.b32 b0, t0;\nmov.b32 b3, t0;\nmov.b32 b1, t1;\n"
        "ld.shared.b32 t0, [%64+6656];\nld.shared.b32 t1, [%64+6784];\nadd.s64 d, %65, 200;\nwgmma.fence.sync.aligned;\nwgmma.mma_async.sync.aligned.m64n32k16.f32.bf16.bf16 {%0, %1, %2, %3, %4, %5, %6, %7, %8, %9, %10, %11, %12, %13, %14, %15}, {b0, b1, b2, b3}, d, 1, 1, 1, 0;\nwgmma.commit_group.sync.aligned;\nwgmma.wait_group.sync.aligned 1;\nmov.b32 a2, b1;\nmov.b32 a0, t0;\nmov.b32 a3, t0;\nmov.b32 a1, t1;\n"
        "ld.shared.b32 t0, [%64+6912];\nld.shared.b32 t1, [%64+7040];\nadd.s64 d, %65, 208;\nwgmma.fence.sync.aligned;\nwgmma.mma_async.sync.aligned.m64n24k16.f32.bf16.bf16 {%0, %1, %2, %3, %4, %5, %6, %7, %8, %9, %10, %11}, {a0, a1, a2, a3}, d, 1, 1, 1, 0;\nwgmma.commit_group.sync.aligned;\nwgmma.wait_group.sync.aligned 1;\nmov.b32 b2, a1;\nmov.b32 b0, t0;\nmov.b32 b3, t0;\nmov.b32 b1, t1;\n"
        "ld.shared.b32 t0, [%64+7168];\nld.shared.b32 t1, [%64+7296];\nadd.s64 d, %65, 216;\nwgmma.fence.sync.aligned;\nwgmma.mma_async.sync.aligned.m64n24k16.f32.bf16.bf16 {%0, %1, %2, %3, %4, %5, %6, %7, %8, %9, %10, %11}, {b0, b1, b2, b3}, d, 1, 1, 1, 0;\nwgmma.commit_group.sync.aligned;\nwgmma.wait_group.sync.aligned 1;\nmov.b32 a2, b1;\nmov.b32 a0, t0;\nmov.b32 a3, t0;\nmov.b32 a1, t1;\n"
        "ld.shared.b32 t0, [%64+7424];\nld.shared.b32 t1, [%64+7552];\nadd.s64 d, %65, 224;\nwgmma.fence.sync.aligned;\nwgmma.mma_async.sync.aligned.m64n16k16.f32.bf16.bf16 {%0, %1, %2, %3, %4, %5, %6, %7}, {a0, a1, a2, a3}, d, 1, 1, 1, 0;\nwgmma.commit_group.sync.aligned;\nwgmma.wait_group.sync.aligned 1;\nmov.b32 b2, a1;\nmov.b32 b0, t0;\nmov.b32 b3, t0;\nmov.b32 b1, t1;\n"
        "ld.shared.b32 t0, [%64+7680];\nld.shared.b32 t1, [%64+7808];\nadd.s64 d, %65, 232;\nwgmma.fence.sync.aligned;\nwgmma.mma_async.sync.aligned.m64n16k16.f32.bf16.bf16 {%0, %1, %2, %3, %4, %5, %6, %7}, {b0, b1, b2, b3}, d, 1, 1, 1, 0;\nwgmma.commit_group.sync.aligned;\nwgmma.wait_group.sync.aligned 1;\nmov.b32 a2, b1;\nmov.b32 a0, t0;\nmov.b32 a3, t0;\nmov.b32 a1, t1;\n"
        "ld.shared.b32 t0, [%64+7936];\nld.shared.b32 t1, [%64+8064];\nadd.s64 d, %65, 240;\nwgmma.fence.sync.aligned;\nwgmma.mma_async.sync.aligned.m64n8k16.f32.bf16.bf16 {%0, %1, %2, %3}, {a0, a1, a2, a3}, d, 1, 1, 1, 0;\nwgmma.commit_group.sync.aligned;\nwgmma.wait_group.sync.aligned 1;\nmov.b32 b2, a1;\nmov.b32 b0, t0;\nmov.b32 b3, t0;\nmov.b32 b1, t1;\n"
        "add.s64 d, %65, 248;\nwgmma.fence.sync.aligned;\nwgmma.mma_async.sync.aligned.m64n8k16.f32.bf16.bf16 {%0, %1, %2, %3}, {b0, b1, b2, b3}, d, 1, 1, 1, 0;\nwgmma.commit_group.sync.aligned;\nwgmma.wait_group.sync.aligned 0;\n"
        "}" : "+f"(d[0]), "+f"(d[1]), "+f"(d[2]), "+f"(d[3]), "+f"(d[4]), "+f"(d[5]), "+f"(d[6]), "+f"(d[7]), "+f"(d[8]), "+f"(d[9]), "+f"(d[10]), "+f"(d[11]), "+f"(d[12]), "+f"(d[13]), "+f"(d[14]), "+f"(d[15]), "+f"(d[16]), "+f"(d[17]), "+f"(d[18]), "+f"(d[19]), "+f"(d[20]), "+f"(d[21]), "+f"(d[22]), "+f"(d[23]), "+f"(d[24]), "+f"(d[25]), "+f"(d[26]), "+f"(d[27]), "+f"(d[28]), "+f"(d[29]), "+f"(d[30]), "+f"(d[31]), "+f"(d[32]), "+f"(d[33]), "+f"(d[34]), "+f"(d[35]), "+f"(d[36]), "+f"(d[37]), "+f"(d[38]), "+f"(d[39]), "+f"(d[40]), "+f"(d[41]), "+f"(d[42]), "+f"(d[43]), "+f"(d[44]), "+f"(d[45]), "+f"(d[46]), "+f"(d[47]), "+f"(d[48]), "+f"(d[49]), "+f"(d[50]), "+f"(d[51]), "+f"(d[52]), "+f"(d[53]), "+f"(d[54]), "+f"(d[55]), "+f"(d[56]), "+f"(d[57]), "+f"(d[58]), "+f"(d[59]), "+f"(d[60]), "+f"(d[61]), "+f"(d[62]), "+f"(d[63]) : "r"(pa), "l"(db) : "memory");
}
__device__ __forceinline__ void wgmma_rs80(float (&d)[40], uint32_t a0, uint32_t a1, uint32_t a2, uint32_t a3, uint64_t db, int sc) {
    asm volatile("{\n.reg .pred p;\nsetp.ne.b32 p, %45, 0;\n"
        "wgmma.mma_async.sync.aligned.m64n80k16.f32.bf16.bf16 {%0, %1, %2, %3, %4, %5, %6, %7, %8, %9, %10, %11, %12, %13, %14, %15, %16, %17, %18, %19, %20, %21, %22, %23, %24, %25, %26, %27, %28, %29, %30, %31, %32, %33, %34, %35, %36, %37, %38, %39}, {%40, %41, %42, %43}, %44, p, 1, 1, 1;\n}\n"
        : "+f"(d[0]), "+f"(d[1]), "+f"(d[2]), "+f"(d[3]), "+f"(d[4]), "+f"(d[5]), "+f"(d[6]), "+f"(d[7]), "+f"(d[8]), "+f"(d[9]), "+f"(d[10]), "+f"(d[11]), "+f"(d[12]), "+f"(d[13]), "+f"(d[14]), "+f"(d[15]), "+f"(d[16]), "+f"(d[17]), "+f"(d[18]), "+f"(d[19]), "+f"(d[20]), "+f"(d[21]), "+f"(d[22]), "+f"(d[23]), "+f"(d[24]), "+f"(d[25]), "+f"(d[26]), "+f"(d[27]), "+f"(d[28]), "+f"(d[29]), "+f"(d[30]), "+f"(d[31]), "+f"(d[32]), "+f"(d[33]), "+f"(d[34]), "+f"(d[35]), "+f"(d[36]), "+f"(d[37]), "+f"(d[38]), "+f"(d[39]) : "r"(a0), "r"(a1), "r"(a2), "r"(a3), "l"(db), "r"(sc));
}
__device__ __forceinline__ void wgmma_ss80(float (&d)[40], uint64_t da, uint64_t db, int sc) {
    asm volatile("{\n.reg .pred p;\nsetp.ne.b32 p, %42, 0;\n"
        "wgmma.mma_async.sync.aligned.m64n80k16.f32.bf16.bf16 {%0, %1, %2, %3, %4, %5, %6, %7, %8, %9, %10, %11, %12, %13, %14, %15, %16, %17, %18, %19, %20, %21, %22, %23, %24, %25, %26, %27, %28, %29, %30, %31, %32, %33, %34, %35, %36, %37, %38, %39}, %40, %41, p, 1, 1, 0, 1;\n}\n"
        : "+f"(d[0]), "+f"(d[1]), "+f"(d[2]), "+f"(d[3]), "+f"(d[4]), "+f"(d[5]), "+f"(d[6]), "+f"(d[7]), "+f"(d[8]), "+f"(d[9]), "+f"(d[10]), "+f"(d[11]), "+f"(d[12]), "+f"(d[13]), "+f"(d[14]), "+f"(d[15]), "+f"(d[16]), "+f"(d[17]), "+f"(d[18]), "+f"(d[19]), "+f"(d[20]), "+f"(d[21]), "+f"(d[22]), "+f"(d[23]), "+f"(d[24]), "+f"(d[25]), "+f"(d[26]), "+f"(d[27]), "+f"(d[28]), "+f"(d[29]), "+f"(d[30]), "+f"(d[31]), "+f"(d[32]), "+f"(d[33]), "+f"(d[34]), "+f"(d[35]), "+f"(d[36]), "+f"(d[37]), "+f"(d[38]), "+f"(d[39]) : "l"(da), "l"(db), "r"(sc));
}
__device__ __forceinline__ void wgmma_ss80t(float (&d)[40], uint64_t da, uint64_t db, int sc) {
    asm volatile("{\n.reg .pred p;\nsetp.ne.b32 p, %42, 0;\n"
        "wgmma.mma_async.sync.aligned.m64n80k16.f32.bf16.bf16 {%0, %1, %2, %3, %4, %5, %6, %7, %8, %9, %10, %11, %12, %13, %14, %15, %16, %17, %18, %19, %20, %21, %22, %23, %24, %25, %26, %27, %28, %29, %30, %31, %32, %33, %34, %35, %36, %37, %38, %39}, %40, %41, p, 1, 1, 1, 1;\n}\n"
        : "+f"(d[0]), "+f"(d[1]), "+f"(d[2]), "+f"(d[3]), "+f"(d[4]), "+f"(d[5]), "+f"(d[6]), "+f"(d[7]), "+f"(d[8]), "+f"(d[9]), "+f"(d[10]), "+f"(d[11]), "+f"(d[12]), "+f"(d[13]), "+f"(d[14]), "+f"(d[15]), "+f"(d[16]), "+f"(d[17]), "+f"(d[18]), "+f"(d[19]), "+f"(d[20]), "+f"(d[21]), "+f"(d[22]), "+f"(d[23]), "+f"(d[24]), "+f"(d[25]), "+f"(d[26]), "+f"(d[27]), "+f"(d[28]), "+f"(d[29]), "+f"(d[30]), "+f"(d[31]), "+f"(d[32]), "+f"(d[33]), "+f"(d[34]), "+f"(d[35]), "+f"(d[36]), "+f"(d[37]), "+f"(d[38]), "+f"(d[39]) : "l"(da), "l"(db), "r"(sc));
}
__device__ __forceinline__ void wgmma_ss8_ta(float (&d)[4], uint64_t da, uint64_t db, int sc) {
    asm volatile("{\n.reg .pred p;\nsetp.ne.b32 p, %6, 0;\n"
        "wgmma.mma_async.sync.aligned.m64n8k16.f32.bf16.bf16 {%0, %1, %2, %3}, %4, %5, p, 1, 1, 1, 0;\n}\n"
        : "+f"(d[0]), "+f"(d[1]), "+f"(d[2]), "+f"(d[3]) : "l"(da), "l"(db), "r"(sc));
}
__device__ __forceinline__ void wgmma_rs8(float (&d)[4], uint32_t a0, uint32_t a1, uint32_t a2, uint32_t a3, uint64_t db, int sc) {
    asm volatile("{\n.reg .pred p;\nsetp.ne.b32 p, %9, 0;\n"
        "wgmma.mma_async.sync.aligned.m64n8k16.f32.bf16.bf16 {%0, %1, %2, %3}, {%4, %5, %6, %7}, %8, p, 1, 1, 0;\n}\n"
        : "+f"(d[0]), "+f"(d[1]), "+f"(d[2]), "+f"(d[3]) : "r"(a0), "r"(a1), "r"(a2), "r"(a3), "l"(db), "r"(sc));
}
__device__ __forceinline__ void wgmma_rs128(float (&d)[64], uint32_t a0, uint32_t a1, uint32_t a2, uint32_t a3, uint64_t db, int sc) {
    asm volatile("{\n.reg .pred p;\nsetp.ne.b32 p, %69, 0;\n"
        "wgmma.mma_async.sync.aligned.m64n128k16.f32.bf16.bf16 {%0, %1, %2, %3, %4, %5, %6, %7, %8, %9, %10, %11, %12, %13, %14, %15, %16, %17, %18, %19, %20, %21, %22, %23, %24, %25, %26, %27, %28, %29, %30, %31, %32, %33, %34, %35, %36, %37, %38, %39, %40, %41, %42, %43, %44, %45, %46, %47, %48, %49, %50, %51, %52, %53, %54, %55, %56, %57, %58, %59, %60, %61, %62, %63}, {%64, %65, %66, %67}, %68, p, 1, 1, 1;\n}\n"
        : "+f"(d[0]), "+f"(d[1]), "+f"(d[2]), "+f"(d[3]), "+f"(d[4]), "+f"(d[5]), "+f"(d[6]), "+f"(d[7]), "+f"(d[8]), "+f"(d[9]), "+f"(d[10]), "+f"(d[11]), "+f"(d[12]), "+f"(d[13]), "+f"(d[14]), "+f"(d[15]), "+f"(d[16]), "+f"(d[17]), "+f"(d[18]), "+f"(d[19]), "+f"(d[20]), "+f"(d[21]), "+f"(d[22]), "+f"(d[23]), "+f"(d[24]), "+f"(d[25]), "+f"(d[26]), "+f"(d[27]), "+f"(d[28]), "+f"(d[29]), "+f"(d[30]), "+f"(d[31]), "+f"(d[32]), "+f"(d[33]), "+f"(d[34]), "+f"(d[35]), "+f"(d[36]), "+f"(d[37]), "+f"(d[38]), "+f"(d[39]), "+f"(d[40]), "+f"(d[41]), "+f"(d[42]), "+f"(d[43]), "+f"(d[44]), "+f"(d[45]), "+f"(d[46]), "+f"(d[47]), "+f"(d[48]), "+f"(d[49]), "+f"(d[50]), "+f"(d[51]), "+f"(d[52]), "+f"(d[53]), "+f"(d[54]), "+f"(d[55]), "+f"(d[56]), "+f"(d[57]), "+f"(d[58]), "+f"(d[59]), "+f"(d[60]), "+f"(d[61]), "+f"(d[62]), "+f"(d[63]) : "r"(a0), "r"(a1), "r"(a2), "r"(a3), "l"(db), "r"(sc));
}
__device__ __forceinline__ void wgmma_rs88(float (&d)[44], uint32_t a0, uint32_t a1, uint32_t a2, uint32_t a3, uint64_t db, int sc) {
    asm volatile("{\n.reg .pred p;\nsetp.ne.b32 p, %49, 0;\n"
        "wgmma.mma_async.sync.aligned.m64n88k16.f32.bf16.bf16 {%0, %1, %2, %3, %4, %5, %6, %7, %8, %9, %10, %11, %12, %13, %14, %15, %16, %17, %18, %19, %20, %21, %22, %23, %24, %25, %26, %27, %28, %29, %30, %31, %32, %33, %34, %35, %36, %37, %38, %39, %40, %41, %42, %43}, {%44, %45, %46, %47}, %48, p, 1, 1, 1;\n}\n"
        : "+f"(d[0]), "+f"(d[1]), "+f"(d[2]), "+f"(d[3]), "+f"(d[4]), "+f"(d[5]), "+f"(d[6]), "+f"(d[7]), "+f"(d[8]), "+f"(d[9]), "+f"(d[10]), "+f"(d[11]), "+f"(d[12]), "+f"(d[13]), "+f"(d[14]), "+f"(d[15]), "+f"(d[16]), "+f"(d[17]), "+f"(d[18]), "+f"(d[19]), "+f"(d[20]), "+f"(d[21]), "+f"(d[22]), "+f"(d[23]), "+f"(d[24]), "+f"(d[25]), "+f"(d[26]), "+f"(d[27]), "+f"(d[28]), "+f"(d[29]), "+f"(d[30]), "+f"(d[31]), "+f"(d[32]), "+f"(d[33]), "+f"(d[34]), "+f"(d[35]), "+f"(d[36]), "+f"(d[37]), "+f"(d[38]), "+f"(d[39]), "+f"(d[40]), "+f"(d[41]), "+f"(d[42]), "+f"(d[43]) : "r"(a0), "r"(a1), "r"(a2), "r"(a3), "l"(db), "r"(sc));
}
__device__ __forceinline__ void wgmma_rs128k(float (&d)[64], uint32_t a0, uint32_t a1, uint32_t a2, uint32_t a3, uint64_t db, int sc) {
    asm volatile("{\n.reg .pred p;\nsetp.ne.b32 p, %69, 0;\n"
        "wgmma.mma_async.sync.aligned.m64n128k16.f32.bf16.bf16 {%0, %1, %2, %3, %4, %5, %6, %7, %8, %9, %10, %11, %12, %13, %14, %15, %16, %17, %18, %19, %20, %21, %22, %23, %24, %25, %26, %27, %28, %29, %30, %31, %32, %33, %34, %35, %36, %37, %38, %39, %40, %41, %42, %43, %44, %45, %46, %47, %48, %49, %50, %51, %52, %53, %54, %55, %56, %57, %58, %59, %60, %61, %62, %63}, {%64, %65, %66, %67}, %68, p, 1, 1, 0;\n}\n"
        : "+f"(d[0]), "+f"(d[1]), "+f"(d[2]), "+f"(d[3]), "+f"(d[4]), "+f"(d[5]), "+f"(d[6]), "+f"(d[7]), "+f"(d[8]), "+f"(d[9]), "+f"(d[10]), "+f"(d[11]), "+f"(d[12]), "+f"(d[13]), "+f"(d[14]), "+f"(d[15]), "+f"(d[16]), "+f"(d[17]), "+f"(d[18]), "+f"(d[19]), "+f"(d[20]), "+f"(d[21]), "+f"(d[22]), "+f"(d[23]), "+f"(d[24]), "+f"(d[25]), "+f"(d[26]), "+f"(d[27]), "+f"(d[28]), "+f"(d[29]), "+f"(d[30]), "+f"(d[31]), "+f"(d[32]), "+f"(d[33]), "+f"(d[34]), "+f"(d[35]), "+f"(d[36]), "+f"(d[37]), "+f"(d[38]), "+f"(d[39]), "+f"(d[40]), "+f"(d[41]), "+f"(d[42]), "+f"(d[43]), "+f"(d[44]), "+f"(d[45]), "+f"(d[46]), "+f"(d[47]), "+f"(d[48]), "+f"(d[49]), "+f"(d[50]), "+f"(d[51]), "+f"(d[52]), "+f"(d[53]), "+f"(d[54]), "+f"(d[55]), "+f"(d[56]), "+f"(d[57]), "+f"(d[58]), "+f"(d[59]), "+f"(d[60]), "+f"(d[61]), "+f"(d[62]), "+f"(d[63]) : "r"(a0), "r"(a1), "r"(a2), "r"(a3), "l"(db), "r"(sc));
}
__device__ __forceinline__ void wgmma_rs88k(float (&d)[44], uint32_t a0, uint32_t a1, uint32_t a2, uint32_t a3, uint64_t db, int sc) {
    asm volatile("{\n.reg .pred p;\nsetp.ne.b32 p, %49, 0;\n"
        "wgmma.mma_async.sync.aligned.m64n88k16.f32.bf16.bf16 {%0, %1, %2, %3, %4, %5, %6, %7, %8, %9, %10, %11, %12, %13, %14, %15, %16, %17, %18, %19, %20, %21, %22, %23, %24, %25, %26, %27, %28, %29, %30, %31, %32, %33, %34, %35, %36, %37, %38, %39, %40, %41, %42, %43}, {%44, %45, %46, %47}, %48, p, 1, 1, 0;\n}\n"
        : "+f"(d[0]), "+f"(d[1]), "+f"(d[2]), "+f"(d[3]), "+f"(d[4]), "+f"(d[5]), "+f"(d[6]), "+f"(d[7]), "+f"(d[8]), "+f"(d[9]), "+f"(d[10]), "+f"(d[11]), "+f"(d[12]), "+f"(d[13]), "+f"(d[14]), "+f"(d[15]), "+f"(d[16]), "+f"(d[17]), "+f"(d[18]), "+f"(d[19]), "+f"(d[20]), "+f"(d[21]), "+f"(d[22]), "+f"(d[23]), "+f"(d[24]), "+f"(d[25]), "+f"(d[26]), "+f"(d[27]), "+f"(d[28]), "+f"(d[29]), "+f"(d[30]), "+f"(d[31]), "+f"(d[32]), "+f"(d[33]), "+f"(d[34]), "+f"(d[35]), "+f"(d[36]), "+f"(d[37]), "+f"(d[38]), "+f"(d[39]), "+f"(d[40]), "+f"(d[41]), "+f"(d[42]), "+f"(d[43]) : "r"(a0), "r"(a1), "r"(a2), "r"(a3), "l"(db), "r"(sc));
}
__device__ __forceinline__ void wgmma_rs80k(float (&d)[40], uint32_t a0, uint32_t a1, uint32_t a2, uint32_t a3, uint64_t db, int sc) {
    asm volatile("{\n.reg .pred p;\nsetp.ne.b32 p, %45, 0;\n"
        "wgmma.mma_async.sync.aligned.m64n80k16.f32.bf16.bf16 {%0, %1, %2, %3, %4, %5, %6, %7, %8, %9, %10, %11, %12, %13, %14, %15, %16, %17, %18, %19, %20, %21, %22, %23, %24, %25, %26, %27, %28, %29, %30, %31, %32, %33, %34, %35, %36, %37, %38, %39}, {%40, %41, %42, %43}, %44, p, 1, 1, 0;\n}\n"
        : "+f"(d[0]), "+f"(d[1]), "+f"(d[2]), "+f"(d[3]), "+f"(d[4]), "+f"(d[5]), "+f"(d[6]), "+f"(d[7]), "+f"(d[8]), "+f"(d[9]), "+f"(d[10]), "+f"(d[11]), "+f"(d[12]), "+f"(d[13]), "+f"(d[14]), "+f"(d[15]), "+f"(d[16]), "+f"(d[17]), "+f"(d[18]), "+f"(d[19]), "+f"(d[20]), "+f"(d[21]), "+f"(d[22]), "+f"(d[23]), "+f"(d[24]), "+f"(d[25]), "+f"(d[26]), "+f"(d[27]), "+f"(d[28]), "+f"(d[29]), "+f"(d[30]), "+f"(d[31]), "+f"(d[32]), "+f"(d[33]), "+f"(d[34]), "+f"(d[35]), "+f"(d[36]), "+f"(d[37]), "+f"(d[38]), "+f"(d[39]) : "r"(a0), "r"(a1), "r"(a2), "r"(a3), "l"(db), "r"(sc));
}
__device__ __forceinline__ void wgmma_rs64(float (&d)[32], uint32_t a0, uint32_t a1, uint32_t a2, uint32_t a3, uint64_t db, int sc) {
    asm volatile("{\n.reg .pred p;\nsetp.ne.b32 p, %37, 0;\n"
        "wgmma.mma_async.sync.aligned.m64n64k16.f32.bf16.bf16 {%0, %1, %2, %3, %4, %5, %6, %7, %8, %9, %10, %11, %12, %13, %14, %15, %16, %17, %18, %19, %20, %21, %22, %23, %24, %25, %26, %27, %28, %29, %30, %31}, {%32, %33, %34, %35}, %36, p, 1, 1, 1;\n}\n"
        : "+f"(d[0]), "+f"(d[1]), "+f"(d[2]), "+f"(d[3]), "+f"(d[4]), "+f"(d[5]), "+f"(d[6]), "+f"(d[7]), "+f"(d[8]), "+f"(d[9]), "+f"(d[10]), "+f"(d[11]), "+f"(d[12]), "+f"(d[13]), "+f"(d[14]), "+f"(d[15]), "+f"(d[16]), "+f"(d[17]), "+f"(d[18]), "+f"(d[19]), "+f"(d[20]), "+f"(d[21]), "+f"(d[22]), "+f"(d[23]), "+f"(d[24]), "+f"(d[25]), "+f"(d[26]), "+f"(d[27]), "+f"(d[28]), "+f"(d[29]), "+f"(d[30]), "+f"(d[31]) : "r"(a0), "r"(a1), "r"(a2), "r"(a3), "l"(db), "r"(sc));
}

__device__ __forceinline__ uint64_t mkdesc(uint32_t lo) { return ((uint64_t)0x40000040u << 32) | lo; }
template <int F> __device__ __forceinline__ uint32_t lop3(uint32_t a, uint32_t b, uint32_t c) { uint32_t r; asm("lop3.b32 %0, %1, %2, %3, %4;" : "=r"(r) : "r"(a), "r"(b), "r"(c), "n"(F)); return r; }
__device__ __forceinline__ void stg128_tag(void* p, uint32_t x, uint32_t y, uint32_t z, uint32_t u, uint32_t ep, int w) {
    stg128(p, lop3<0xB8>(x, w == 0, ep), lop3<0xB8>(y, w == 1, ep), lop3<0xB8>(z, w == 2, ep), lop3<0xB8>(u, w == 3, ep));
}
__device__ __forceinline__ uint32_t tag(uint32_t w, uint32_t ep) { asm("lop3.b32 %0, %0, 1, %1, 0xB8;" : "+r"(w) : "r"(ep)); return w; }
template <int N> __device__ __forceinline__ void pack_part(uint32_t (&p)[32], const float (&v)[N], uint32_t ep) {
#pragma unroll
    for (int i = 0; i < N / 2; i++) p[i] = (i & 3) ? pack2(v[2 * i], v[2 * i + 1]) : tag(pack2(v[2 * i], v[2 * i + 1]), ep);
#pragma unroll
    for (int i = 0; i < N / 2; i++) asm volatile("" : "+r"(p[i]));
}
__device__ __forceinline__ void st_part(uint4* p, const uint32_t* v) {
    asm volatile("{\n.reg .b64 l, h;\n.reg .b128 q;\nmov.b64 l, {%1, %2};\nmov.b64 h, {%3, %4};\nmov.b128 q, {l, h};\nst.relaxed.gpu.global.b128 [%0], q;\n}"
                 ::"l"(p), "r"(v[0]), "r"(v[1]), "r"(v[2]), "r"(v[3]) : "memory");
}
__device__ __forceinline__ void st_peer(uint32_t a, uint32_t x, uint32_t y, uint32_t z, uint32_t w, uint32_t bar) {
    asm volatile("st.async.shared::cluster.mbarrier::complete_tx::bytes.v4.b32 [%0], {%1, %2, %3, %4}, [%5];" ::"r"(a), "r"(x), "r"(y), "r"(z), "r"(w), "r"(bar) : "memory");
}
__device__ __forceinline__ int g4_block(int c, int j) { return c ? j ^ (8 - 2 * c) : 8 + (j & 1); }
__device__ __forceinline__ uint32_t recv_off(int w) { return w ? OFF_XR : OFF_REM; }
__device__ __forceinline__ uint4 ld_part(const void* p) {
    uint4 v;
    asm volatile("{\n.reg .b64 l, h;\n.reg .b128 q;\nld.relaxed.gpu.global.b128 q, [%4];\nmov.b128 {l, h}, q;\nmov.b64 {%0, %1}, l;\nmov.b64 {%2, %3}, h;\n}"
                 : "=r"(v.x), "=r"(v.y), "=r"(v.z), "=r"(v.w) : "l"(p) : "memory");
    return v;
}
__device__ __forceinline__ void ld_part4(uint4 (&u)[4], const uint4* p, int st) {
#pragma unroll
    for (int i = 0; i < 4; i++) u[i] = ld_part(p + i * st);
}
__device__ __forceinline__ uint32_t stale4(const uint4 (&u)[4], uint32_t ep) { return lop3<0x7E>(u[0].x, ep, u[1].x) | lop3<0x7E>(u[2].x, ep, u[3].x); }
__device__ __forceinline__ uint4 add2(uint4 a, uint4 b) { return make_uint4(add2(a.x, b.x), add2(a.y, b.y), add2(a.z, b.z), add2(a.w, b.w)); }
__device__ __forceinline__ uint4 fin16(uint4 v, uint4 b, uint4 c) { return make_uint4(fma2(c.x, v.x, b.x), fma2(c.y, v.y, b.y), fma2(c.z, v.z, b.z), fma2(c.w, v.w, b.w)); }
__device__ __forceinline__ uint4 scale16(float2 c, float2 d, float r0, float r1) {
    return make_uint4(pack2(c.x * r0, c.y * r0), pack2(c.x * r1, c.y * r1), pack2(d.x * r0, d.y * r0), pack2(d.x * r1, d.y * r1));
}
__device__ __forceinline__ uint32_t split2(float x) { const float h = rbf(x); return pack2(h, x - h); }
__device__ __forceinline__ uint32_t b80_desc(uint32_t dsb, uint32_t wn, uint32_t rn, uint32_t h) {
    const uint32_t wb = dsb + OFF_W + (wn & 7) * 16384 + h * 8192, rm = dsb + OFF_REM + rn * 4096 + h * 2048;
    return (wb >> 4) | ((rm - wb) << 12);
}
constexpr int64_t B80_STEP = 128 - (126 << 16), B80_HALF = 512 - (384 << 16);
constexpr uint32_t ring_mask(int L) {
    uint32_t m = 0;
    for (int i = L; i < 20; i++) m |= (uint32_t)(i >= 20 - L || !((i - L) & 1)) << i;
    return m;
}
constexpr int pair_pos(int w, int i) { return w ? (i < 5 - LEAD2 ? LEAD2 + 2 * i : 5 + i) : (i < LEAD2 ? i : 2 * i - LEAD2 + 1); }
constexpr uint32_t pair_mask() { uint32_t m = 0; for (int i = 0; i < 5; i++) m |= 3u << (2 * pair_pos(1, i)); return m; }
constexpr uint32_t pair_slots(int w) { uint32_t m = 0; for (int i = 0; i < 5; i++) m |= (uint32_t)((2 + pair_pos(w, i)) & 3) << (2 * i); return m; }
constexpr uint32_t M0 = ring_mask(LEAD1), M1 = pair_mask(), M2 = ring_mask(XLEAD), P0S = pair_slots(0), P1S = pair_slots(1);
__device__ __forceinline__ uint32_t ring_pos(int w, int n, int L) { return w ? (n < 10 - L ? L + 2 * n : 10 + n) : (n < L ? n : 2 * n - L + 1); }
__device__ __forceinline__ int g1_block(int n, int j) { return n < 5 ? 2 * n + (j & 1) : 2 * n - 9 - (j & 1); }

__device__ __forceinline__ int g2_block(int n) { return (0x9874326510ull >> (4 * n)) & 15; }
__device__ __forceinline__ int g3_block(int n, int j) { return n ? n - (n <= j) : j; }
struct Tile { int e, w, kb; uint32_t at; };
__device__ __forceinline__ Tile ring_tile(int n, int grp, int j) {
    const int e = (n >= 20) + (n >= 40), i = n - 20 * e;
    const uint32_t M = e == 0 ? M0 : e == 1 ? M1 : M2;
    const int w = (M >> i) & 1, c = __popc(M & ((1u << i) - 1)), kb = w ? c : i - c, tile = grp + 16 * w;
    return {e, w, kb, 64u * (e == 0 ? tile + (g1_block(kb, j) << 16) : e == 1 ? g2_block(kb) + (tile << 16) : (10 * tile + g3_block(kb, j)) << 16)};
}
__device__ __forceinline__ void load_tile(const Maps& mp, uint32_t dst, int e, uint32_t at, uint32_t bar) {
    mbar_expect(bar, 8192);
    tma_ld2(dst, &mp.x[e], at & 0xffff, at >> 16, bar);
}

template <int OCT>
__device__ __forceinline__ void gemv_tile(float (&d)[4], uint32_t a, uint32_t b, int kb0) {
    uint32_t alo = ((a & 0x3FFFF) >> 4) | 0x10000u, blo_ = ((b & 0x3FFFF) >> 4) | (OCT << 16);
#pragma unroll 1
    for (int s = 0; s < 20; s += 4) {
        const int kb = kb0 + (s >> 2);
        const uint32_t bk = blo_ + (OCT == 7 ? (kb & 1) * 288 + (kb >> 1) * 56 : kb * 64);
        wg_fence();
#pragma unroll
        for (int q = 0; q < 4; q++) wgmma_ss8_ta(d, mkdesc(alo + (s + q) * 128), ((uint64_t)8 << 32) | (bk + q * 2 * OCT), s + q);
        wg_commit();
    }
    wg_wait<0>();
    reg_fence(d);
}

__device__ __forceinline__ void flush_tile(uint32_t st, bf16* dst, int u) {
#pragma unroll
    for (int i = 0; i < 2; i++) {
        const int idx = u + 320 * i, row = idx >> 3, c = idx & 7;
        stg128(dst + (size_t)row * S_ + 8 * c, lds128(st + row * 128 + ((c ^ ((row >> 1) & 7)) << 4)));
    }
}

__device__ __forceinline__ int tid_now() { int t; asm volatile("mov.u32 %0, %%tid.x;" : "=r"(t)); return t; }
__device__ __forceinline__ float zscale(float c) { return c == 0.f ? 0x1p-30f : c; }
__device__ __forceinline__ bool bar_any(int id, bool p) {
    uint32_t r;
    asm volatile("{\n.reg .pred a, b;\nsetp.ne.u32 a, %2, 0;\nbarrier.red.or.pred.aligned b, %1, 128, a;\nselp.u32 %0, 1, 0, b;\n}" : "=r"(r) : "r"(id), "r"((uint32_t)p) : "memory");
    return r != 0;
}

__global__ void __cluster_dims__(2, 1, 1) __launch_bounds__(NTHR, 1) fused_kernel(const __grid_constant__ Ptrs pp, bf16* __restrict__ out, const __grid_constant__ Maps mp) {
    extern __shared__ __align__(1024) uint8_t smem_raw[];
    const uint32_t sb = s2u(smem_raw), bars = sb + M_BAR, dsb = sb & 0x3FFFF;
    const int id = blockIdx.x, warp = __shfl_sync(0xffffffffu, (int)threadIdx.x >> 5, 0), wg = warp >> 2;
    const uint32_t c0 = clock_lo();
#define TIDS const int tid = tid_now(), lane = tid & 31, wt = tid & 127, g = lane >> 2, t = lane & 3; (void)wt; (void)g; (void)t;
    TS(threadIdx.x == 0, 0) TG(threadIdx.x == 0, 62)

    if (id >= 128) {
        TIDS
        if (sb & 1023) __trap();
        const int hs = id - 128;
        constexpr int H_B = 204800;
        static_assert(H_B + TAB_BYTES + 8 * VEC_BYTES <= OFF_M, "helper map");
        if (warp < 10 && elect()) { mbar_init(bars + warp * 8, 1); mbar_init(bars + 80 + warp * 8, 1); asm volatile("fence.mbarrier_init.release.cluster;" ::: "memory"); }
        __syncthreads();
        const uint32_t e0 = ld_cold(&g_epoch);
        wait_clock(c0, HELP_T);
        uint4 wr[10];
#pragma unroll
        for (int u = 0; u < 10; u++) wr[u] = ldg128(((hs >> 1) ? pp.w2 : pp.w1) + (size_t)(320 * (hs & 1) + (tid >> 4) + 32 * u) * D_ + 512 + 8 * (tid & 15));
        {
            const int r = tid >> 4, c = tid & 15;
            uint4* dst[2];
#pragma unroll
            for (int e = 0; e < 2; e++) {
                const int p = !(hs >> 1) ? r : e && (hs & 1) ? (r & ~14) | ((r & 6) << 1) | ((r & 8) >> 2) : (r & ~30) | ((r & 6) << 2) | ((r & 24) >> 2);
                dst[e] = &g_wr[((hs >> 1) * 8 + (c >> 1)) * 10 * 128 + (p & 15) * 8 + ((2 * (p >> 4) + (c & 1)) ^ (p & 7))];
            }
#pragma unroll
            for (int u = 0; u < 10; u++) stg128(reinterpret_cast<uint4*>(reinterpret_cast<uintptr_t>(dst[u >= 6]) ^ (64 * (u & 1))) +
                       ((hs >> 1) ? (0x9873265410ull >> (4 * (5 * (hs & 1) + (u >> 1)))) & 15 : 5 * (hs & 1) + (u >> 1)) * 128, wr[u]);
        }
        __syncthreads();
        if (warp == 0) signal_cnt(&g_cnt.wr[0], lane, 1);
        __syncthreads();
        if (warp < 5 && elect()) {
            const int un = 5 * hs + warp;
            mbar_expect(bars + warp * 8, 40960);
            tma_ld2(sb + warp * 40960, &mp.w1h, 64 * (un >> 1), 320 * (un & 1), bars + warp * 8);
            tma_ld2(sb + warp * 40960 + 20480, &mp.w1h, 64 * (un >> 1), 320 * (un & 1) + 160, bars + warp * 8);
        }
        if (tid < 320) {
            const uint4* gm = reinterpret_cast<const uint4*>(g_mod + 3 * D_) + tid;
            const unsigned epoch = e0 + 1;
            uint4 r[6];
            unsigned it = 0;
            for (;;) {
                uint32_t bad = 0;
#pragma unroll
                for (int i = 0; i < 6; i++) { r[i] = ld_part(gm + (i >> 1) * (D_ / 2) + (i & 1) * 3 * D_); bad |= (r[i].y ^ epoch) | (r[i].w ^ epoch); }
                if (__all_sync(~0u, !bad)) break;
                if (++it > SPIN_LIMIT) SPIN_FAIL(54)
            }
            uint32_t mv[3];
#pragma unroll
            for (int i = 0; i < 3; i++) mv[i] = pack2(__uint_as_float(r[2 * i].x) + __uint_as_float(r[2 * i + 1].x), __uint_as_float(r[2 * i].z) + __uint_as_float(r[2 * i + 1].z));
            const uint32_t sw2 = mv[0], cw = add2(mv[1], 0x3f803f80u), gw = mv[2];
            const float c0 = blo(cw), c1 = bhi(cw), s0 = blo(sw2), s1 = bhi(sw2);
            const float i0 = __frcp_rn(zscale(c0)), i1 = __frcp_rn(zscale(c1));
            const uint32_t ci = pack2(i0, i1), cq = pack2(i0 * i0, i1 * i1);
            const uint32_t a = sb + H_B + ((tid >> 5) & 1) * 4608 + (tid >> 6) * 896 + ((tid >> 2) & 7) * 112 + (tid & 3) * 4;
            sts32(a, ci); sts32(a + 16, pack2(i0 - blo(ci), i1 - bhi(ci)));
            sts32(a + 32, cq); sts32(a + 48, pack2(fmaf(i0, i0, -blo(cq)), fmaf(i1, i1, -bhi(cq))));
            sts32(a + 64, cw); sts32(a + 80, sw2); sts32(a + 96, 0x3f803f80u);
            if ((tid & ~35) == 284) sts32(a + 112, 0);
            const uint32_t v = sb + H_B + TAB_BYTES + (tid < 256 ? (tid >> 5) * VEC_BYTES + (tid & 31) * 8 : ((tid - 256) >> 3) * VEC_BYTES + 256 + (tid & 7) * 8);
            sts64f(v, blo(gw), bhi(gw)); sts64f(v + 320, c0, c1); sts64f(v + 640, s0, s1); sts64f(v + 960, i0, i1);
            float k[5] = {c0 + c1, s0 + s1, fmaf(c0, c0, c1 * c1), fmaf(c0, s0, c1 * s1), fmaf(s0, s0, s1 * s1)};
#pragma unroll 1
            for (int o = 16; o; o >>= 1) {
#pragma unroll
                for (int e = 0; e < 5; e++) k[e] += __shfl_xor_sync(~0u, k[e], o);
            }
            const uint32_t ks = sb + H_B + TAB_BYTES + (lane & 7) * VEC_BYTES + 1280 + (warp >> 1) * 32;
            if ((warp & 1) && lane < 8) { sts128f(ks, k[0], k[1], k[2], k[3]); sts128f(ks + 16, k[4], 0.f, 0.f, 0.f); }
            bar_sync(3, 320);
            if (!(warp & 1) && lane < 8) {
                const float4 o = lds128f(ks);
                sts128f(ks, k[0] + o.x, k[1] + o.y, k[2] + o.z, k[3] + o.w); sts32(ks + 16, __float_as_uint(k[4] + __uint_as_float(lds32(ks + 16))));
            }
            fence_async_smem();
        }
        __syncthreads();
        if (hs == 0 && warp == 15 && elect()) {
            asm volatile("cp.async.bulk.global.shared::cta.bulk_group [%0], [%1], %2;\ncp.async.bulk.commit_group;\ncp.async.bulk.wait_group 0;"
                         ::"l"(g_tab), "r"(sb + H_B), "n"(TAB_BYTES + 8 * VEC_BYTES) : "memory");
            asm volatile("red.release.gpu.global.add.u32 [%0], 1;" ::"l"(&g_cnt.tab[0]) : "memory");
        }
        __syncwarp();
#pragma unroll 1
        for (int i = wg; i < 20; i += 4) {
            const int r = i / 5, b = i - 5 * r, un = 5 * hs + b, u3 = 20 * r + un;
            auto refill = [&](int e, int u, uint32_t fb) {
                mbar_expect(fb, 40960);
                tma_ld2(sb + e * 40960, &mp.w3h, 64 * (u >> 1), 320 * (u & 1), fb);
                tma_ld2(sb + e * 40960 + 20480, &mp.w3h, 64 * (u >> 1), 320 * (u & 1) + 160, fb);
            };
            if (i > 4 && i < 9) {
                bar_sync(1, 512);
                if (warp == 0) {
                    signal_cnt(&g_cnt.uv[0], lane, 1);
                    if (elect()) {
#pragma unroll 1
                        for (int e = 0; e < 5; e++) refill(e, 5 * hs + e, bars + (5 + e) * 8);
                        l2_prefetch(pp.w2 + (size_t)160 * hs * D_, 160 * D_ * 2);
                    }
                    __syncwarp();
                }
            }
            mbar_wait(bars + i * 8, 0);
            float d[4];
            gemv_tile<7>(d, sb + b * 40960, sb + H_B, 5 * (un & 1));
            const int col = 16 * (warp & 3) + g;
            float* dst = r ? g_cs3 + (un & 1) * 1920 + 64 * ((u3 >> 1) - 10) + col : g_uv + (un & 1) * 3 * D_ + 2 * D_ + 64 * (un >> 1) + col;
            if (t == 3) { dst[0] = d[0]; dst[8] = d[2]; }
            if (r == 0 && t == 2) { dst[-2 * D_] = d[0]; dst[8 - 2 * D_] = d[2]; dst[-D_] = d[1]; dst[8 - D_] = d[3]; }
            if (r == 1 || r == 2) {
                bar_sync(4 + wg, 128);
                if (wt == 0) refill(b, u3, bars + (i + 5) * 8);
            }
        }
        __syncthreads();
        if (warp == 0) signal_cnt(&g_cnt.cs[0], lane, 1);
        if (tid == 511) l2_prefetch(pp.w4 + (size_t)432 * hs * D_, 432 * D_ * 2);
        for (uint32_t it = 0; ld_cold(&g_cnt.cs[0]) < 4;) { if (++it > SPIN_LIMIT) SPIN_FAIL(47) }
        asm volatile("fence.acquire.gpu;" ::: "memory");
        if (tid < 432) {
            const int jj = 2 * hs + (tid >= 216), c = tid % 216;
            const float* src = g_cs3 + (c < 192 ? 192 * jj + c : 1344 + 24 * jj + c);
            const uint32_t s = split2(ldcg32f(src) + ldcg32f(src + 1920));
            stg128(&g_cs3b[432 * hs + tid], s, s & 0xffffu, 0, 0);
        }
        __syncthreads();
        if (warp == 0) signal_cnt(&g_cnt.cs2[0], lane, 1);
        if (tid == 0 && hs == 3) {
            uint32_t it = 0;
            while (ld_cold(&g_epoch) == e0) { __nanosleep(256); if (++it > (1u << 20)) SPIN_FAIL(48) }
        }
        return;
    }

    if (elect()) {
        if (warp == 15) {
            mbar_init(bars + B_IN * 8, 1); mbar_init(bars + B_IN * 8 + 8, 1);
            asm volatile("fence.mbarrier_init.release.cluster;" ::: "memory");
            mbar_expect(bars + B_IN * 8, 131 * 160);
            tma_ld2(sb + OFF_KIN, &mp.k, 80 * (id & 7), 64 * (id >> 3) - 3, bars + B_IN * 8);
            tma_ld2(sb + OFF_VIN, &mp.v, 80 * (id & 7), 64 * (id >> 3), bars + B_IN * 8);
        } else if (warp < 13) {
            const uint32_t n = (0x4C11111111881ull >> (4 * warp)) & 15;
#pragma unroll
            for (int i = 0; i < 4; i++) mbar_init(bars + warp * 64 + i * 8, n);
            if (warp == 11) { mbar_init(bars + B_XFREE * 8, 16); mbar_init(bars + B_OWN * 8, 8); }
            else {
#pragma unroll
                for (int i = 4; i < 8; i++) mbar_init(bars + warp * 64 + i * 8, n);
            }
            asm volatile("fence.mbarrier_init.release.cluster;" ::: "memory");
        }
    }
    asm volatile("" ::"l"(pp.s), "l"(pp.c), "l"(out));
    TR4((threadIdx.x & 31) == 0, warp)
    const int pr = id >> 1;
    const int grp = pr < 4 ? 15 : pr < 36 ? (pr - 4) & 7 : 8 + (pr - 36) % 7;
    const int j = 2 * (pr < 4 ? pr : pr < 36 ? (pr - 4) >> 3 : (pr - 36) / 7) + (id & 1);

    if (wg == 3) {
        TIDS
        const int sw = warp - 12;
        uint32_t ep = ld_cold(&g_epoch);
        TR4(lane == 0, 20 + sw)
        __syncthreads();
        TR4(lane == 0, 30 + sw)
        asm volatile("barrier.cluster.arrive.relaxed.aligned;" ::: "memory");
        if (sw == 0) {
#pragma unroll 1
            for (int n = 0; n < 12; n++) {
                wait_clock(c0, PF_T0 + PF_DT * n);
                if (elect()) l2_prefetch(n < 4 ? (const char*)pp.q + id * 20480 + n * 5120 : (const char*)pp.w_mod + id * 38400 + (n - 4) * 4800, n < 4 ? 5120 : 4800);
            }
        } else if (sw == 1) {
            wait_clock(c0, T_SSM);
            if (elect()) {
                mbar_expect(bars + B_SSM * 8, 20480);
                bulk_ld(sb + OFF_SSM, pp.ssm_k + (size_t)5 * id * S_, 20480, bars + B_SSM * 8);
            }
            mbar_spin(bars + B_KVS * 8, 0);
            signal_cnt(&g_cnt.kv[(id & 7) * 32], lane, 1, true);
            TS(lane == 0, 2)
            mbar_spin(bars + B_RAW * 8, 0);
            if (elect()) {
                mbar_expect(bars + B_QIN * 8, 20480);
                tma_ld3(sb + OFF_QIN, &mp.q, 0, 16 * id, 0, bars + B_QIN * 8);
            }
        } else if (sw == 2) {
            if (elect()) {
#pragma unroll 1
                for (int i = 2; i < (int)(sizeof(Maps) / sizeof(CUtensorMap)); i++) asm volatile("prefetch.tensormap [%0];" ::"l"(&mp.k + i) : "memory");
#pragma unroll 1
                for (int i = B_SUMS; i < B_LAND; i++) mbar_expect(bars + i * 8, i < B_RECV ? 2048 : (i & 3) < 3 ? 8192 : 3072);
            }
            wait_cnt(&g_cnt.kv[(id >> 4) * 32], 16, true);
            TS(lane == 0, 4)
            if (elect()) {
                mbar_expect(bars + B_RAW * 8, 12288);
                mbar_expect(bars + B_RAW2 * 8, 8192);
#pragma unroll
                for (int c = 0; c < 5; c++) bulk_ld(sb + OFF_CH + c * CH_BYTES, g_kvT + (size_t)(5 * id + c) * S_, 4096, bars + (c < 3 ? B_RAW : B_RAW2) * 8);
            }
            mbar_spin(bars + B_BK * 8, 0);
            mbar_spin(bars + B_QIN * 8, 0);
            if (id < 120 && elect()) {
                mbar_expect(bars + B_WM * 8, 40960);
                tma_ld2(sb + OFF_WM, &mp.wmod, 64 * pr, 320 * (id & 1), bars + B_WM * 8);
                tma_ld2(sb + OFF_WM + 20480, &mp.wmod, 64 * pr, 320 * (id & 1) + 160, bars + B_WM * 8);
            }
            TS(lane == 0, 57)
        } else {
            wait_clock(c0, T_KVB);
            if (elect()) {
                mbar_expect(bars + (B_IN + 1) * 8, 131 * 160);
                tma_ld2(sb + OFF_KIN + 10752, &mp.k, 80 * (id & 7), 64 * (id >> 3) + 1021, bars + (B_IN + 1) * 8);
                tma_ld2(sb + OFF_VIN + 10240, &mp.v, 80 * (id & 7), 64 * (id >> 3) + 1024, bars + (B_IN + 1) * 8);
            }
            TS(lane == 0, 53)
            if (lane == 0) sts32(sb + M_EP, ep + 1);
            sts32(sb + M_NUL + lane * 4, 0);
#pragma unroll 1
            for (int i = 0; i < 10; i++) sts128(sb + OFF_Z + i * 512 + lane * 16, 0, 0, 0, 0);
            __syncwarp();
#pragma unroll 1
            for (int i = lane; i < 160; i += 32) {
                const uint32_t c = ldg32(pp.c + 320 * (id & 1) + 2 * i);
                sts32(sb + OFF_Z + (i >> 2) * 128 + (i & 3) * 4, pack2(silu(blo(c)), silu(bhi(c))));
            }
            fence_async_smem();
            for (uint32_t ph = 0, again = 1; again; ph ^= 1) {
                mbar_spin(bars + B_RAW2 * 8, ph);
                uint32_t bad = 0;
#pragma unroll
                for (int i = 0; i < 8; i++) bad |= lop3<0x7E>(lds32(sb + OFF_CH + 3 * CH_BYTES + i * 512 + lane * 16), ~ep, lds32(sb + OFF_CH + 4 * CH_BYTES + i * 512 + lane * 16));
                again = __any_sync(~0u, bad & 1);
                if (again && elect()) {
                    mbar_expect(bars + B_RAW2 * 8, 8192);
#pragma unroll
                    for (int c = 3; c < 5; c++) bulk_ld(sb + OFF_CH + c * CH_BYTES, g_kvT + (size_t)(5 * id + c) * S_, 4096, bars + B_RAW2 * 8);
                }
            }
            if (elect()) mbar_arrive(bars + B_RAW3 * 8);
        }
        {
            mbar_spin(bars + B_QIN * 8, 0);
            asm volatile("add.u32 %0, %0, 1;" : "+r"(ep));
            TS(wt == 0, 54)
            const int tk = 8 * ((lane >> 1) & 1) + 2 * (lane >> 3) + (lane & 1), ck = 4 * (sw & 1) + ((lane >> 1) & 2);
            const uint32_t src = sb + OFF_QIN + (sw >> 1) * 2048 + tk * 128;
            bf16* dst = g_qT + (size_t)id * 16 * D_ + (32 * sw + 8 * (t & 2) + g) * 16 + 8 * (t & 1);
constexpr int QU = Q_UNROLL;
#pragma unroll QU
            for (int i = 0; i < 5; i++) {
                uint32_t r[8];
                ldsm4t(src + i * 4096 + ((ck ^ (tk & 7)) << 4), r[0], r[1], r[2], r[3]);
                ldsm4t(src + i * 4096 + (((ck + 1) ^ (tk & 7)) << 4), r[4], r[5], r[6], r[7]);
                stg128(dst + i * 2048, tag(r[0], ep), r[1], r[2], r[3]);
                stg128(dst + i * 2048 + 128, tag(r[4], ep), r[5], r[6], r[7]);
            }
            float s1 = 0.f, s2 = 0.f;
#pragma unroll 2
            for (int i = 0; i < 10; i++) {
                const uint4 w4 = lds128(sb + OFF_QIN + i * 2048 + wt * 16);
                const uint32_t w[4] = {w4.x, w4.y, w4.z, w4.w};
#pragma unroll
                for (int e = 0; e < 4; e++) { const float a = blo(w[e]), b = bhi(w[e]); s1 += a + b; s2 = fmaf(a, a, fmaf(b, b, s2)); }
            }
#pragma unroll
            for (int o = 1; o < 8; o *= 2) { s1 += __shfl_xor_sync(~0u, s1, o); s2 += __shfl_xor_sync(~0u, s2, o); }
            s1 *= 1.f / D_;
            uint32_t rs = pack2(rsqrtf(fmaxf(s2 * (1.f / D_) - s1 * s1, 0.f) + 1e-5f), 0.f);
            if (lane < 8) rs = tag(rs, ep);
            rs = pack2(blo(rs), -s1 * blo(rs));
            const uint32_t sel = lane ? 0x7632 : 0x5410;
            const uint32_t a0 = __shfl_sync(~0u, rs, 0), a1 = __shfl_sync(~0u, rs, 8), a2 = __shfl_sync(~0u, rs, 16), a3 = __shfl_sync(~0u, rs, 24);
            if (lane < 2) stg64(g_qst + lane * S_ + 16 * id + 4 * sw, tag(__byte_perm(a0, a1, sel), ep), __byte_perm(a2, a3, sel));
            TS(wt == 0, 55)
        }
        bar_sync(6, 128);
        if (sw == 3) {
            signal_cnt(&g_cnt.q[(lane & 3) * 32], lane, 4, true);
            TS(lane == 0, 3)
        }
        asm volatile("setmaxnreg.dec.sync.aligned.u32 " STR(REG_SVC) ";");
        asm volatile("barrier.cluster.wait.aligned;" ::: "memory");
        if (sw == 1) {
            mbar_spin(bars + B_XS * 8, 0);
            signal_cnt(&g_cnt.x[(lane & 3) * 32], lane, 4, true);
            TS(lane == 0, 20)
        }
        if (sw == 2) {
            wait_cnt(&g_cnt.q[(id & 3) * 32], 128, true);
            if (elect()) {
                mbar_expect(bars + B_QRDY * 8, 28672);
                tma_ld2(sb + OFF_QT, &mp.qT, 80 * id, 0, bars + B_QRDY * 8);
                bulk_ld(sb + OFF_QT + 20480, g_qst, 8192, bars + B_QRDY * 8);
            }
            TS(lane == 0, 8)
        }
        if (sw == 1 || sw == 2) {
            mbar_spin(bars + B_XS * 8, 0);
            fence_async_smem();
            int n = sw & 1;
            const uint32_t plan = ring_tile(min(2 * lane + n, 59), grp, j).at;
#pragma unroll 1
            for (int s = 0; s < 7; s++) {
                const int e = (s >= 2) + (s >= 5), end = (0ull + LEAD1 + (20 << 8) + (24 << 16) + ((20ull + 2 * LEAD2) << 24) + (40ull << 32) + ((40ull + XLEAD) << 40) + (60ull << 48)) >> (8 * s) & 255;
                if (s == 1 || s == 4 || s == 6) mbar_spin(bars + (B_GATE + 2 + e) * 8, !e);
                else if (s != 3 || grp == 15) {
                    wait_cnt(s == 0 ? &g_cnt.x[(id & 3) * 32] : s == 5 ? &g_cnt.g2[grp * 32] : &g_cnt.g1[(s == 2 ? min(max(grp - 1 + min(lane, 2), 0), 15) : 16) * 32], e ? 32 : 128, true);
                    TS(lane == 0 && sw == 2 && s != 3, 26 + 2 * e)
                }
#pragma unroll 1
                for (; n < end; n += 2) {
                    const uint32_t at = __shfl_sync(~0u, plan, n >> 1);
                    mbar_spin(bars + (B_XEMPTY + (n & 7)) * 8, ((n >> 3) & 1) ^ 1);
                    TR2(lane == 0 && n < 40, 20 + n)
                    if (elect()) {
                        if (n == 40 || n == 40 + XLEAD) {
                            mbar_arrive(bars + (B_LAND + (n & 7)) * 8);
                            asm volatile("mbarrier.arrive.shared.b64 _, [%0], 8;" ::"r"(bars + (B_XEMPTY + (n & 7)) * 8) : "memory");
                        } else load_tile(mp, sb + OFF_XR + (n & 7) * 8192, e, at, bars + (B_LAND + (n & 7)) * 8);
                    }
                }
            }
            if (sw == 1) { if (elect()) mbar_arrive(bars + (B_GATE + 5) * 8); return; }
            mbar_spin(bars + (B_GATE + 5) * 8, 0);
            mbar_spin(bars + B_VEC3 * 8, 0);
            unsigned old = 0;
            asm volatile("{\n.reg .pred P;\nsetp.eq.s32 P, %2, 0;\n@P atom.relaxed.gpu.global.add.u32 %0, [%1], %3;\n}" : "+r"(old) : "l"(&g_cnt.done[0]), "r"(lane), "r"(1) : "memory");
            if (__any_sync(~0u, old == 127)) {
#pragma unroll 1
                for (int i = lane; i < (int)(sizeof(Counters) / 128); i += 32) reinterpret_cast<unsigned*>(&g_cnt)[i * 32] = 0;
                signal_cnt(&g_epoch, lane, 1, true);
            }
        } else if (sw == 0) {
            wait_cnt(&g_cnt.wr[0], 4);
            mbar_spin(bars + B_QRDY * 8, 0);
            mbar_spin(bars + B_MODR * 8, 0);
            const uint32_t wf = bars + B_WFULL * 8, we = bars + B_WEMPTY * 8;
#pragma unroll 1
            for (int n = 0; n < 5; n++) {
                if (n == 3) { mbar_spin(bars + B_XS * 8, 0); fence_async_smem(); }
                TR2(lane == 0, 70 + n)
                if (elect()) {
                    const uint32_t fb = wf + n * 8, dst = sb + OFF_W + n * 16384;
                    mbar_expect(fb, 20480);
#pragma unroll 1
                    for (int h = 0; h < 2; h++) {
                        const int kb = g1_block(2 * n + h, j);
                        tma_ld2(dst + h * 8192, &mp.w1, 64 * j, 64 * kb, fb);
                        bulk_ld(sb + OFF_REM + n * 4096 + h * 2048, &g_wr[(j * 10 + kb) * 128], 2048, fb);
                    }
                }
            }
            mbar_spin(bars + B_GATE * 8, 0);
#pragma unroll 1
            for (int i = -3; i < 5; i++) {
                const int n = i < 0 ? 8 + i : 5 + i;
                const uint32_t fb = wf + (n & 7) * 8;
                if (i >= 0) mbar_spin(we + i * 8, 0);
                TR2(lane == 0 && i >= 0, 70 + n)
                if (elect()) {
                    if (i < 0 || i >= 3) {
                        mbar_expect(fb, 20480);
#pragma unroll 1
                        for (int h = 0; h < 2; h++) tma_ld5(sb + OFF_W + (n & 7) * 16384 + h * 8192, n < 9 ? &mp.w2a : &mp.w2b, 64 * j, n < 9 ? 2 * g2_block(2 * n - 10 + h) : 4 * h, fb);
                    }
                    if (i >= 0) bulk_ld(sb + OFF_REM + i * 4096, &g_wr[((8 + j) * 10 + 2 * i) * 128], 4096, fb);
                }
            }
            mbar_spin(bars + (B_GATE + 1) * 8, 0);
#pragma unroll 1
            for (int n = 10; n < 30; n++) {
                if (n == W3_N2) mbar_spin(bars + (B_GATE + 2) * 8, 0);
                mbar_spin(we + (n & 7) * 8, ((n >> 3) & 1) ^ 1);
                TR2(lane == 0, 70 + n)
                if (elect()) {
                    const uint32_t dst = sb + OFF_W + (n & 7) * 16384, fb = wf + (n & 7) * 8;
                    mbar_expect(fb, 13824);
                    const int row = 64 * g3_block((n - 10) >> 1, j) + 32 * (n & 1);
                    tma_ld3(dst, &mp.w3a, 0, row, 3 * j, fb);
                    tma_ld2(dst + 12288, &mp.w3b, 1536 + 24 * j, row, fb);
                }
            }
            mbar_spin(we + 6 * 8, 0);
            mbar_spin(bars + B_VEC3 * 8, 0);
            if (elect()) { mbar_expect(wf + 6 * 8, 3456); bulk_ld(sb + OFF_W + 6 * 16384, &g_cs3b[216 * j], 3456, wf + 6 * 8); }
#pragma unroll 1
            for (int n = 31; n < 50; n++) {
                const int e = n < 38 ? 4 : (n - 38) & 3, m0 = n == 35, m1 = e == 3 ? -1 : m0 | (e == 1), rem = 96 + 3 * (j >> 1);
                const int c1_ = j ^ (n < 38 ? 6 : 4 >> ((n - 38) >> 2) & 6), c0_ = n < 38 ? 8 + (j & 1) : c1_;
                const int f = (0xC840A80C204ull >> (4 * min(n - 31, e + 7))) & 15;
                const int r0 = m0 ? rem : 6 * (j ^ (f >> 3)) + (f & 6), r1 = m1 ? rem : r0 + (n < 38 ? 0 : 2);
                mbar_spin(we + (n & 7) * 8, ((n >> 3) & 1) ^ 1);
                if (elect()) {
                    const uint32_t dst = sb + OFF_W + (n & 7) * 16384, fb = wf + (n & 7) * 8;
                    mbar_expect(fb, m1 < 0 ? 8192 : 16384 - 2048 * (m0 + m1));
                    tma_ld2(dst, &mp.w4[m0], 64 * c0_, r0 * (32 >> m0), fb);
                    if (m1 >= 0) tma_ld2(dst + 8192, &mp.w4[m1], 64 * c1_, r1 * (32 >> m1), fb);
                }
            }
        } else {
            {
                wait_cnt(&g_cnt.tab[0], 1);
                mbar_spin(bars + B_MODR * 8, 0);
                if (elect()) {
                    mbar_expect(bars + B_TAB * 8, TAB_BYTES / 2 + VEC_BYTES);
                    bulk_ld(sb + OFF_TAB, g_tab + (j & 1) * (TAB_BYTES / 32), TAB_BYTES / 2, bars + B_TAB * 8);
                    bulk_ld(sb + M_GB, g_tab + (TAB_BYTES + j * VEC_BYTES) / 16, VEC_BYTES, bars + B_TAB * 8);
                }
                TS(lane == 0, 5)
            }
            wait_cnt(&g_cnt.uv[0], 4);
#pragma unroll 1
            for (int c = lane; c < 80; c += 32) {
                const float* src = g_uv + (c < 64 ? 64 * j + c : 448 + 16 * j + c);
                const uint32_t u = split2(ldcg32f(src) + ldcg32f(src + 3 * D_)), v = split2(ldcg32f(src + D_) + ldcg32f(src + 4 * D_));
                const uint32_t s = split2(ldcg32f(src + 2 * D_) + ldcg32f(src + 5 * D_));
                sts128(sb + OFF_F1 + c * 16, u, __byte_perm(u, v, 0x5410), __byte_perm(v, 0, 0x1032), s);
                sts128(sb + M_F1 + c * 16, s & 0xffffu, 0, 0, 0);
            }
            fence_async_smem();
            warp_arrive(bars + B_VEC * 8);
            TS(lane == 0, 9)
#pragma unroll 1
            for (int e = 1; e < 3; e++) {
                wait_cnt(e == 1 ? &g_cnt.g1[min(grp + 15 + min(lane, 2), 31) * 32] : &g_cnt.g2[(grp + 16) * 32], 32, true);
                if (elect()) mbar_arrive(bars + (B_GATE + 2 + e) * 8);
                TS(lane == 0, 27 + 2 * e)
            }
            wait_cnt(&g_cnt.cs2[0], 4);
            if (elect()) mbar_arrive(bars + B_VEC3 * 8);
            TS(lane == 0, 19)
        }
        return;
    }

    {
        uint32_t ep;
        {
            TIDS
            ep = ld_cold(&g_epoch);
            const int cp = (tid + 16) % 40, cp1 = tid % 40;
            const uint4 sh0 = ldg128(pp.shift_k + (80 * (id & 7) + 2 * cp1) * 4), sh1 = ldg128(pp.shift_k + (80 * (id & 7) + 2 * cp) * 4);
            uint32_t dd;
            asm volatile("ld.global.nc.u16 %0, [%1];" : "=r"(dd) : "l"(pp.ssm_D + 5 * id + min(wg + 3 * lane, 4)));
            TR4(lane == 0, 40 + warp)
            __syncthreads();
            asm volatile("barrier.cluster.arrive.relaxed.aligned;" ::: "memory");
            asm volatile("add.u32 %0, %0, 1;" : "+r"(ep));
#pragma unroll 1
            for (int hw = 0; hw < 2; hw++) {
                if ((unsigned)(warp - 2 * hw) >= 10) continue;
                const int u = tid - 64 * hw;
                const int c = hw ? cp : cp1, oc = u / 40, line = 31 - 16 * hw - (id >> 3);
                const uint4 sh = hw ? sh1 : sh0;
                const uint32_t st = sb + OFF_ST + hw * 10240, sta = st + c * 256 + ((((6 - 2 * (oc & 3)) ^ (oc >> 2) ^ (line & 1)) ^ (c & 7)) << 4), in = oc * 1280 + c * 4;
                const uint32_t f0 = __byte_perm(sh.x, sh.z, 0x5410), f1 = __byte_perm(sh.x, sh.z, 0x7632), f2 = __byte_perm(sh.y, sh.w, 0x5410), f3 = __byte_perm(sh.y, sh.w, 0x7632);
                uint32_t kk[11], vv[8];
                mbar_spin(bars + (B_IN + hw) * 8, 0);
                TS(tid == 64, 18 + 42 * hw)
#pragma unroll
                for (int i = 0; i < 11; i++) kk[i] = lds32(sb + OFF_KIN + hw * 10752 + in + i * 160);
#pragma unroll
                for (int i = 0; i < 8; i++) vv[i] = lds32(sb + OFF_VIN + hw * 10240 + in + i * 160);
#pragma unroll
                for (int i = 0; i < 8; i++) vv[i] = mul2(fma2(kk[i + 3], f0, fma2(kk[i + 2], f1, fma2(kk[i + 1], f2, mul2(kk[i], f3)))), vv[i]);
                sts128(sta, tag(__byte_perm(vv[0], vv[1], 0x5410), ep), __byte_perm(vv[2], vv[3], 0x5410), __byte_perm(vv[4], vv[5], 0x5410), __byte_perm(vv[6], vv[7], 0x5410));
                sts128(sta + 128, tag(__byte_perm(vv[0], vv[1], 0x7632), ep), __byte_perm(vv[2], vv[3], 0x7632), __byte_perm(vv[4], vv[5], 0x7632), __byte_perm(vv[6], vv[7], 0x7632));
                bar_sync(7 + hw, 320);
                flush_tile(st, g_kvT + (size_t)(80 * (id & 7)) * S_ + 64 * line, u);
                TS(tid == 64 && hw, 1)
            }
            warp_arrive(bars + B_KVS * 8);
            if (tid < 320) sts128(sb + OFF_CH + (tid >> 6) * CH_BYTES + 4096 + (tid & 63) * 16, 0, 0, 0, 0);
            mbar_spin(bars + B_SSM * 8, 0);
            TS(tid == 0, 14)
#pragma unroll 1
            for (int u0 = wg; u0 < 20; u0 += 12) {
                uint2 w[4];
                uint32_t pv[4];
#pragma unroll
                for (int i = 0; i < 4; i++) {
                    const uint32_t a = sb + OFF_SSM + min(u0 + 3 * i, 19) * 1024 + wt * 8;
                    w[i] = lds64(a); pv[i] = lds32(a - 4);
                }
#pragma unroll
                for (int i = 0; i < 4; i++) {
                    const int un = min(u0 + 3 * i, 19);
                    sts128(sb + OFF_CH + (un >> 2) * CH_BYTES + OFF_P + (un & 3) * 2048 + wt * 16, __byte_perm(w[i].x, pv[i], 0x7610), __byte_perm(w[i].x, 0, 0x1032), __byte_perm(w[i].y, w[i].x, 0x7610), __byte_perm(w[i].y, 0, 0x1032));
                }
            }
            __syncwarp();
            if (wt < 2 - (wg >> 1)) {
                const uint32_t h = lds32(sb + OFF_SSM + (wg + 3 * wt) * 4096), h0 = pack2(blo(h) + blo(dd), 0.f);
                sts64f(sb + OFF_CH + (wg + 3 * wt) * CH_BYTES + OFF_P, __uint_as_float(h0), __uint_as_float(__byte_perm(h, h0, 0x5432)));
            }
            fence_async_smem();
            warp_arrive(bars + B_BK * 8);
            asm volatile("barrier.cluster.wait.aligned;" ::: "memory");
            mbar_spin(bars + B_BK * 8, 0);
            TS(tid == 0, 15)
        }

#pragma unroll 1
        for (int c = wg; c < 5; c += 3) {
            const uint32_t kvb = sb + OFF_CH + c * CH_BYTES;
            mbar_spin(bars + (c < 3 ? B_RAW : B_RAW3) * 8, 0);
            for (uint32_t ph = 0; c < 3; ph ^= 1) {
                const int wt = tid_now() & 127;
                if (!RARE(bar_any(1 + wg, lop3<0x7E>(lds32(kvb + wt * 16), ep, lds32(kvb + 2048 + wt * 16)) & 1))) break;
                if (wt == 0) { mbar_expect(bars + (B_RETRY + wg) * 8, 4096); bulk_ld(kvb, g_kvT + (size_t)(5 * id + c) * S_, 4096, bars + (B_RETRY + wg) * 8); }
                mbar_spin(bars + (B_RETRY + wg) * 8, ph);
                STALE1(-8)
            }
            TS(threadIdx.x == 0, c ? 13 : 11)
            float acc[64];
            {
                const int l = tid_now() & 31;
                conv_channel(acc, kvb + OFF_P + (8 * (warp & 3) + (l >> 2) - 2 * (l & 3)) * 4, (((uint64_t)0xC0000010u << 32) | ((kvb & 0x3FFFF) >> 4) | 0x10000u) + pp.nil);
            }
            TS(threadIdx.x == 0, c ? 16 : 12)
            if (c < 3) warp_arrive(bars + B_R1 * 8);
            else mbar_spin(bars + B_R1 * 8, 0);
            if (wg == 2 && id < 120) {
                TIDS
                mbar_spin(bars + B_RAW3 * 8, 0);
                mbar_spin(bars + B_WM * 8, 0);
                TS(wt == 0, 56)
                float d[4];
                gemv_tile<8>(d, sb + OFF_WM, sb + OFF_Z, 0);
                const float d2 = __shfl_up_sync(~0u, d[2], 1);
                TS(wt == 0, 7)
                if (t < 2) asm volatile("{\n.reg .b64 v;\nmov.b64 v, {%1, %2};\nst.relaxed.gpu.global.b64 [%0], v;\n}" ::"l"(g_mod + (id & 1) * 6 * D_ + 64 * pr + 16 * (warp & 3) + g + 8 * t),
                                        "r"(__float_as_uint(t ? d2 : d[0])), "r"(lds32(sb + M_EP)) : "memory");
            }
            TR4(threadIdx.x == 0, 60 + (c >= 3) * 10)
            TIDS
            const int e = 127 - 8 * (lane >> 4) - (lane & 7), u0 = (warp & 3) + 8 * (e >> 2) + (e & 3) + 4 * ((lane >> 3) & 1);
            const uint32_t ring = sb + OFF_RING + c * 16384 + (warp & 3) * 4096, wa = ring + (u0 ^ ((u0 >> 1) & 4)) * 16;
            if (lane < (warp & 3)) sts128(ring + lane * 16, 0, 0, 0, 0);
#pragma unroll
            for (int i = 0; i < 8; i++)
                stsm4t(i == 0 && u0 >= 256 ? sb + M_SINK : wa - 512 * i, pack2(acc[8 * i], acc[8 * i + 1]), pack2(acc[8 * i + 2], acc[8 * i + 3]),
                       pack2(acc[8 * i + 4], acc[8 * i + 5]), pack2(acc[8 * i + 6], acc[8 * i + 7]));
            warp_arrive(bars + (B_RING + c) * 8);
            TR4(threadIdx.x == 0, 61 + (c >= 3) * 10)
        }
        TIDS
        if (wg == 2) bar_sync(3, 128);
        if (warp == 9) {
            const int v = min(lane / 5, 3);
            const uint2* gm = g_mod + (v + (v == 3)) * D_ + 5 * id + lane % 5;
            const unsigned epoch = lds32(sb + M_EP);
            uint2 r0, r1;
            unsigned it = 0;
            do {
                r0 = ld_mod(gm); r1 = ld_mod(gm + 6 * D_);
                SPIN_CHECK(55)
            } while (!__all_sync(~0u, r0.y == epoch && r1.y == epoch));
            const float m0 = __uint_as_float(r0.x), m1 = __uint_as_float(r1.x);
            const float m = rbf(m0 + m1), p = rbf(1.f + m);
            const float cz = zscale(__shfl_sync(~0u, p, 15 + lane % 5)), ga = __shfl_sync(~0u, m, 10 + lane % 5);
            if (lane < 15) sts32(sb + M_AB + lane % 5 * 16 + v * 4, lane < 10 ? __float_as_uint(cz * ga * (lane < 5 ? m : p)) : pack2(cz, cz));
            warp_arrive(bars + B_MODR * 8);
            TS(lane == 0, 6)
        }
        mbar_spin(bars + B_QRDY * 8, 0);
        uint4 rs[2], nm[2];
#pragma unroll
        for (int h = 0; h < 2; h++) { rs[h] = lds128(sb + OFF_QT + 20480 + h * 2048 + wt * 16); nm[h] = lds128(sb + OFF_QT + 24576 + h * 2048 + wt * 16); }
        mbar_spin(bars + B_MODR * 8, 0);
        TR4(threadIdx.x == 0, 72)
        uint32_t it = 0;
        while (RARE(__any_sync(~0u, (lop3<0x7E>(rs[0].x, ep, rs[0].z) | lop3<0x7E>(nm[0].x, ep, nm[0].z) | lop3<0x7E>(rs[1].x, ep, rs[1].z) | lop3<0x7E>(nm[1].x, ep, nm[1].z)) & 1))) {
#pragma unroll
            for (int h = 0; h < 2; h++) { rs[h] = ld_part(g_qst + 1024 * h + 8 * wt); nm[h] = ld_part(g_qst + S_ + 1024 * h + 8 * wt); }
            STALE(1)
            SPIN_CHECK(53)
        }
        TR4(threadIdx.x == 0, 73)
#pragma unroll 1
        for (int c = wg == 2 ? 0 : 3 + wg; c < (wg == 2 ? 3 : 4 + wg); c++) {
            uint4 q[2], p[2][4];
#pragma unroll
            for (int h = 0; h < 2; h++) q[h] = lds128(sb + OFF_QT + h * 10240 + (wt >> 1) * 160 + c * 32 + (wt & 1) * 16);
            const float4 ab = lds128f(sb + M_AB + c * 16);
            mbar_spin(bars + (B_RING + c) * 8, 0);
            TR4(wt == 0, wg == 2 ? 80 + 2 * c : 74)
#pragma unroll
            for (int i = 0; i < 8; i++) p[i >> 2][i & 3] = lds128(sb + OFF_RING + c * 16384 + (i & 3) * 4096 + (i >> 2) * 2048 + (wt ^ ((wt >> 1) & 4)) * 16);
            while (RARE(__any_sync(~0u, lop3<0x7E>(q[0].x, ep, q[1].x) & 1))) {
#pragma unroll
                for (int h = 0; h < 2; h++) q[h] = ld_part(g_qT + ((64 * h + (wt >> 1)) * D_ + 5 * id + c) * 16 + 8 * (wt & 1));
                STALE(2)
                SPIN_CHECK(52)
            }
            TR4(wt == 0, wg == 2 ? 81 + 2 * c : 75)
#pragma unroll
            for (int h = 0; h < 2; h++) {
                const uint32_t qq[4] = {q[h].x, q[h].y, q[h].z, q[h].w}, r4[4] = {rs[h].x, rs[h].y, rs[h].z, rs[h].w}, n4[4] = {nm[h].x, nm[h].y, nm[h].z, nm[h].w};
                const uint4 y = add2(add2(p[h][0], p[h][1]), add2(p[h][2], p[h][3]));
                const uint32_t yy[4] = {y.x, y.y, y.z, y.w};
                uint32_t o[4];
#pragma unroll
                for (int i = 0; i < 4; i++) {
                    const uint32_t n = fma2(qq[i], r4[i], n4[i]);
                    o[i] = fma2(pack2(fmaf(blo(n), ab.y, ab.x), fmaf(bhi(n), ab.y, ab.x)), yy[i], mul2(qq[i], __float_as_uint(ab.z)));
                }
                stg128_tag(g_x1T + (size_t)(5 * id + c) * S_ + 1024 * h + 8 * wt, o[0], o[1], o[2], o[3], ep, ((5 * id + c) >> 3) & 3);
            }
        }
        warp_arrive(bars + B_XS * 8);
        TS(tid == 0, 17)
        TS(tid == 256, 52)
    }

    const uint32_t nil = pp.nil;
    const int wq = warp & 3;
    if (wg == 2) {
        TIDS
        asm volatile("setmaxnreg.dec.sync.aligned.u32 " STR(REG_AUX) ";");
        {
            const uint32_t ep = lds32(sb + M_EP);
            uint32_t ph = 0;
            const Tile tl = ring_tile(min(4 * lane + wq, 59), grp, j);
            const uint32_t plan = bars + (B_XFULL + 10 * tl.w + tl.kb) * 8;
#pragma unroll 1
            for (int m = wq - 4; m < 60; m += 4) {
                const int n = max(m, 0);
                const uint32_t pl = __shfl_sync(~0u, plan, n >> 2), at = __shfl_sync(~0u, tl.at, n >> 2);
                const int e = (n >= 20) + (n >= 40);
                const uint32_t a = sb + OFF_XR + (n & 7) * 8192;
                uint32_t ta = a + (e == 0 ? lane * 128 + ((lane & 7) << 4) + (lane >> 3) * 4
                                 : e == 1 ? (lane & 15) * 128 + (((lane >> 4 << 1) ^ (lane & 7)) << 4) + (lane & 8) + (lane >> 4) * 4
                                          : lane * 32 + (lane >> 2) * 4);
                uint32_t tb = e == 0 ? ta ^ 32 : ta + 2048, tc = e == 2 ? ta + 1024 : ta ^ 64, td = e == 2 ? tb + 1024 : tb ^ 64;
                uint32_t live = m >= 0 && m != 40 && m != 40 + XLEAD,
                    f0 = pl;
                uint32_t f1 = m == GATE_W2 || m == GATE_W3 || m == GATE_W3B ? bars + (B_GATE + (m >= GATE_W3) + (m >= GATE_W3B)) * 8 : 0;
                if (lane) f0 = f1;
                if (lane > 1 || m < 0) f0 = 0;
                asm volatile("" : "+r"(ta), "+r"(tb), "+r"(tc), "+r"(td), "+r"(live), "+r"(f0));
                mbar_spin(bars + (m < 0 ? B_BK : B_LAND + (n & 7)) * 8, (n >> 3) & 1);
                TR5(lane == 0, n)
                while (true) {
                    uint32_t v[8];
#pragma unroll
                    for (int i = 0; i < 8; i++) v[i] = lds32(((i & 2) ? ((i & 1) ? td : tc) : (i & 1) ? tb : ta) + (i >> 2) * 4096);
                    const uint32_t bad = lop3<0xFE>(lop3<0x7E>(v[0], ep, v[1]), lop3<0x7E>(v[2], ep, v[3]), lop3<0x7E>(v[4], ep, v[5]));
                    if (!RARE(__any_sync(~0u, lop3<0xA8>(bad, lop3<0x7E>(v[6], ep, v[7]), live)))) break;
                    if (elect()) load_tile(mp, a, e, at, bars + (B_AGAIN + wq) * 8);
                    mbar_spin(bars + (B_AGAIN + wq) * 8, ph);
                    ph ^= 1;
                    STALE1(e)
                }
                TR5(lane == 0, 60 + n)
                if (f0) mbar_arrive(f0);
            }
        }
        if (wq == 0) {
#pragma unroll 1
            for (int w = 0; w < 2; w++) {
                const uint4* src = g_part + (size_t)(grp + 16 * w) * 40960;
                TR4(lane == 0, 90 + 2 * w)
                mbar_wait(bars + (B_RING + w) * 8, 1);
                TR4(lane == 0, 91 + 2 * w)
                if (elect()) {
                    const uint32_t fb = bars + (B_IN + w) * 8, rem = sb + OFF_OUT + w * 10240;
                    mbar_expect(fb, 10240);
                    bulk_ld(rem + 8192, &g_x1f[((grp + 16 * w) * 8 + j) * 640 + 512], 2048, fb);
#pragma unroll 1
                    for (int i = 0; i < 4; i++) bulk_ld(rem + i * 2048, src + ((j >> 2) + 2 * i) * 5120 + 4096 + j * 128, 2048, fb);
                }
            }
        }
#pragma unroll 1
        for (int uw = 0; uw < 2; uw++) {
            const int tile = grp + 16 * uw;
            const uint32_t ep = lds32(sb + M_EP), in = sb + OFF_OUT + uw * 10240 + wt * 16, sr = in - lane * 16;
            mbar_wait(bars + (B_IN + uw) * 8, 1);
            TR4(wt == 0, 94 + 3 * uw)
            uint4 u[4];
#pragma unroll
            for (int i = 0; i < 4; i++) u[i] = lds128(in + i * 2048);
            const uint4 base = lds128(in + 8192);
            const uint32_t ra = sb + M_F1 + (64 * uw + 16 * wq + g) * 4;
            const uint4 gr = scale16(lds64f(sb + M_GB + (64 + 2 * t) * 4), lds64f(sb + M_GB + (72 + 2 * t) * 4), __uint_as_float(lds32(ra)), __uint_as_float(lds32(ra + 32)));
            uint32_t it = 0;
            while (RARE(__any_sync(~0u, stale4(u, ep) & 1))) {
                ld_part4(u, g_part + (size_t)tile * 40960 + (j >> 2) * 5120 + 4096 + j * 128 + wt, 10240);
                STALE(3)
                if (++it > SPIN_LIMIT) SPIN_FAIL(58)
            }
            TR4(wt == 0, 95 + 3 * uw)
            const uint4 r = fin16(add2(add2(u[0], u[1]), add2(u[2], u[3])), base, gr);
            __syncwarp();
            stsm4(sr + (lane & 15) * 32 + (((lane >> 4) ^ ((lane >> 2) & 1)) << 4), r.x, r.y, r.z, r.w);
            __syncwarp();
            stg128(out + (size_t)(64 * tile + 16 * wq + (lane >> 1)) * D_ + 512 + 16 * j + 8 * (lane & 1), lds128(sr + (lane >> 1) * 32 + (((lane & 1) ^ ((lane >> 3) & 1)) << 4)));
            TR4(wt == 0, 96 + 3 * uw)
            __syncwarp();
        }
        TS(wt == 0, 21)
        if (wq == 0) {
            uint32_t it = 0;
            while (!mbar_try(bars + B_OWN * 8, 0)) { if (++it > SPIN_LIMIT) SPIN_FAIL(56) }
        }
        return;
    }

    TIDS
    const int uw = wg, tile = grp + 16 * uw, row0 = 64 * tile + 16 * wq;
    const bool leader = wt == 0; (void)leader;
    const uint32_t xfull = bars + (B_XFULL + 10 * uw) * 8, xempty = bars + B_XEMPTY * 8, wfull = bars + B_WFULL * 8, wempty = bars + B_WEMPTY * 8;
    const uint64_t dz = mkdesc(0) + pp.nil;
    auto xwait = [&](uint32_t kb, uint32_t e) { mbar_spin(xfull + kb * 8, e & 1); };
    asm volatile("setmaxnreg.inc.sync.aligned.u32 " STR(REG_MMA) ";");
    const uint32_t ep = lds32(sb + M_EP);
    uint32_t x2[20];
    uint32_t res[20] = {};
    {
        float acc[40];
        const uint32_t la = ((lane & 7) + 8 * (lane >> 4)) * 128 + (((2 * wq + ((lane >> 3) & 1)) ^ (lane & 7)) << 4);
        auto pos = [&](int n) { return ring_pos(uw, n, LEAD1) & 7; };
        auto slot = [&](int n) { return sb + OFF_XR + pos(n) * 8192; };
        float al[2], r1[2], n1[2];
        {
            float sl[4], sq[4], v[4];
            uint32_t z0[16], z1[16], zz[16];
            uint64_t bd = dz + b80_desc(dsb, 0, 0, 0), tb = (((uint64_t)8 << 32) | ((dsb + OFF_TAB) >> 4) | (7u << 16)) + pp.nil;
            auto ldfrag = [&](uint32_t (&z)[16], int n, bool even) {
#pragma unroll
                for (int q = 0; q < 4; q++) ldsm4t(slot(n) + la + q * 2048, z[4 * q], z[4 * q + 1], z[4 * q + 2], z[4 * q + 3]);
#pragma unroll
                for (int q = 0; q < 4; q++) ldsm4t_if(n == j >> 1, slot(n) + la + q * 2048, &res[4 * q]);
                if (even) ldsm4t_if(n == 4 && !((j ^ (j >> 2)) & 1), slot(n) + la + (j & 3) * 2048, &res[16]);
            };
            auto tile1 = [&](const uint32_t (&zc)[16], uint32_t (&zn)[16], int n, int h) {
                const bool last = h && n == 5, ok = mbar_test(xfull + (n + 1) * 8, 0), okw = !h || mbar_test(wfull + ((n + 1) >> 1) * 8, 0);
                wg_fence();
#pragma unroll
                for (int q = 0; q < 2; q++) wgmma_rs80(acc, zc[4 * q], zc[4 * q + 1], zc[4 * q + 2], zc[4 * q + 3], bd + q * B80_STEP, 1);
                wg_commit();
                if (lane < 2) mbar_arrive_after(xempty + pos(n) * 8, res[12], res[16], nil);
                wg_wait<1>();
                if (!h && n && lane == 0) mbar_arrive(wempty + ((n >> 1) - 1) * 8);
                if (!ok) xwait(n + 1, 0);
                if (!last) ldfrag(zn, n + 1, h);
#pragma unroll
                for (int e = 0; e < 16; e++) zz[e] = mul2(zc[e], zc[e]);
                const uint64_t t0 = last ? ((uint64_t)8 << 32) | ((dsb + M_NUL) >> 4) : tb;
                const uint32_t ts = last ? 0 : 14;
                wg_fence();
#pragma unroll
                for (int q = 0; q < 4; q++) wgmma_rs8(sl, zc[4 * q], zc[4 * q + 1], zc[4 * q + 2], zc[4 * q + 3], t0 + q * ts, 1);
#pragma unroll
                for (int q = 0; q < 4; q++) wgmma_rs8(sq, zz[4 * q], zz[4 * q + 1], zz[4 * q + 2], zz[4 * q + 3], t0 + q * ts, 1);
#pragma unroll
                for (int q = 2; q < 4; q++) wgmma_rs80(acc, zc[4 * q], zc[4 * q + 1], zc[4 * q + 2], zc[4 * q + 3], bd + q * B80_STEP, 1);
                wg_commit();
                tb += 56;
                bd = bd + (uint64_t)B80_HALF;
                if (!okw) mbar_spin(wfull + ((n + 1) >> 1) * 8, 0);
                TR(leader, 100 + 10 * uw + n)
            };
            zero(acc); zero(sl); zero(sq);
            mbar_spin(bars + B_TAB * 8, 0);
            float4 k = lds128f(sb + M_KS);
            float k4 = __uint_as_float(lds32(sb + M_KS + 16));
#pragma unroll
            for (int w = 1; w < 5; w++) {
                const float4 o = lds128f(sb + M_KS + w * 32);
                k.x += o.x; k.y += o.y; k.z += o.z; k.w += o.w; k4 += __uint_as_float(lds32(sb + M_KS + w * 32 + 16));
            }
            uint32_t fa[4];
            auto coefs = [&]() {
                mbar_spin(bars + (B_SUMS + uw) * 8, 0);
                TS(leader && !uw, 10)
                const float4 o = lds128f(sb + OFF_ROW + uw * 2048 + wt * 16);
                v[0] += o.x; v[1] += o.y; v[2] += o.z; v[3] += o.w;
#pragma unroll
                for (int h = 0; h < 2; h++) {
                    const int l0 = lane & ~3;
                    const float s1 = __shfl_sync(~0u, v[2 * h], l0), s2 = __shfl_sync(~0u, v[2 * h], l0 + 1), scc = __shfl_sync(~0u, v[2 * h], l0 + 2);
                    const float scs = __shfl_sync(~0u, v[2 * h + 1], l0 + 2), sc = __shfl_sync(~0u, v[2 * h], l0 + 3), sqq = __shfl_sync(~0u, v[2 * h + 1], l0 + 3);
                    const float m1 = s1 * (1.f / D_), va = fmaxf(s2 * (1.f / D_) - m1 * m1, 0.f) + 1e-5f, r = rsqrtf(va);
                    const float m2 = (r * (sc - m1 * k.x) + k.y) * (1.f / D_);
                    const float e2 = (r * (r * (sqq + m1 * (m1 * k.z - 2.f * scc)) + 2.f * (scs - m1 * k.w)) + k4) * (1.f / D_);
                    al[h] = r * 0.5f * rsqrtf(fmaxf(e2 - m2 * m2, 0.f) + 1e-5f); r1[h] = r; n1[h] = -m1 * r;
                    const uint32_t fb = split2(va * r), fx = split2(t == 3 ? -m2 * va * r : -m1), fc = __shfl_sync(~0u, fx, lane | 3);
                    fa[h] = __byte_perm(fx, fb, t == 1 ? 0x5432 : t == 2 ? 0x7654 : 0x1010);
                    fa[2 + h] = t ? 0 : fc >> 16;
                }
            };
            mbar_spin(wfull, 0);
            xwait(0, 0);
            TS(leader, 32 + uw)
            ldfrag(z0, 0, false);
#pragma unroll 1
            for (int n = 0; n < 6; n += 2) { tile1(z0, z1, n, 0); tile1(z1, z0, n + 1, 1); }
#pragma unroll
            for (int n = 6; n < 10; n++) {
                const uint64_t ad = dz + (((dsb + OFF_XR + pos(n) * 8192) >> 4) | 0x10000u);
                const bool ok = n == 9 || mbar_test(xfull + (n + 1) * 8, 0), okw = n != 7 || mbar_test(wfull + 4 * 8, 0);
                wg_fence();
#pragma unroll
                for (int q = 0; q < 4; q++) wgmma_ss80t(acc, ad + q * 128, bd + q * B80_STEP, 1);
                wg_commit();
                bd = bd + (uint64_t)B80_HALF;
                if (n == COEF_AT) coefs();
                if (n == 9) ldsm4t_if(9 - (j & 1) == 8 + (j >> 2), slot(9) + la + (j & 3) * 2048, &res[16]);
                wg_wait<1>();
                if (n > 6 && lane < 2) mbar_arrive(xempty + pos(n - 1) * 8);
                if (!(n & 1) && lane == 0) mbar_arrive(wempty + ((n >> 1) - 1) * 8);
                if (n == 6) {
                    reg_fence(sl); reg_fence(sq);
#pragma unroll
                    for (int e = 0; e < 2; e++) {
                        v[2 * e] = t == 0 ? sl[2 * e] + sl[2 * e + 1] : t == 1 ? sq[2 * e] + sq[2 * e + 1] : sl[2 * e];
                        v[2 * e + 1] = t == 2 ? sl[2 * e + 1] : sq[2 * e];
                    }
                    st_peer(peer_addr(sb + OFF_ROW + uw * 2048 + wt * 16), __float_as_uint(v[0]), __float_as_uint(v[1]), __float_as_uint(v[2]), __float_as_uint(v[3]), peer_addr(bars + (B_SUMS + uw) * 8));
                    TS(leader && !uw, 59)
                }
                if (!ok) xwait(n + 1, 0);
                if (!okw) mbar_spin(wfull + 4 * 8, 0);
                TR(leader, 100 + 10 * uw + n)
            }
            if (COEF_AT == 10) coefs();
            mbar_spin(bars + B_VEC * 8, 0);
            wg_fence();
            wgmma_rs80k(acc, fa[0], fa[1], fa[2], fa[3], ((uint64_t)8 << 32) | ((dsb + OFF_F1) >> 4) | (((M_F1 - OFF_F1) >> 4) << 16), 1);
            wg_commit();
        }
        wg_wait<0>();
        reg_fence(acc);
        if (lane < 2) mbar_arrive_after(xempty + pos(9) * 8, res[16], 0, nil);
        if (lane == 0) mbar_arrive(wempty + 4 * 8);
        TS(leader, 34 + uw)
        {
            bf16* const trow = g_t + (size_t)(row0 + g + 2) * D_;
#pragma unroll
            for (int b = 0; b < 3; b++) {
                uint32_t p[8];
#pragma unroll
                for (int ii = 0; ii < 4; ii++) {
                    const int i = 4 * b + ii;
                    if (i >= 10) continue;
#pragma unroll
                    for (int h = 0; h < 2; h++) p[(i & 3) + 4 * h] = pack2(gelu2(acc[4 * i + 2 * h] * al[h]), gelu2(acc[4 * i + 2 * h + 1] * al[h]));
                }
                if (b < 2) {
                    const int gr = (2 * j + b) / 5, sh = (gr & 1) ? -1 - (gr >> 1) : 1 + (gr >> 1);
                    bf16* dst = trow + 64 * j + 32 * b + 8 * t;
                    const int w = (((g + sh) >> 2) & 2) + (t >> 1);
                    stg128_tag(dst + sh * D_, p[0], p[1], p[2], p[3], ep, w);
                    stg128_tag(dst + (sh + 8) * D_, p[4], p[5], p[6], p[7], ep, w ^ 2);
                    if (row0 + g < sh || row0 + g + 8 >= S_ + sh) stg128_tag(dst + (sh > 0 ? 0 : 8) * D_, 0, 0, 0, 0, ep, (sh > 0 ? 0 : 2) + (t >> 1));
                } else {
                    bf16* dst = trow + 512 + 16 * j + 4 * t;
                    const uint32_t lo = t == (g < 2), hi = t == (g >= 2), o = j & 1;
                    stg64(dst - 2 * D_, lop3<0xB8>(p[0], lo & ~o, ep), lop3<0xB8>(p[1], lo & o, ep));
                    stg64(dst + 6 * D_, lop3<0xB8>(p[4], hi & ~o, ep), lop3<0xB8>(p[5], hi & o, ep));
                    if (row0 + g + 8 >= S_ - 2) stg64(dst + 8 * D_, ep & (t == 1) & ~o, ep & (t == 1) & o);
                }
            }
        }
        signal_cnt(&g_cnt.g1[tile * 32], lane, 1, true);
        TS(leader, 36 + uw)
#pragma unroll
        for (int i = 0; i < 10; i++) {
            const float2 c = lds64f(sb + M_C + (8 * i + 2 * t) * 4), s = lds64f(sb + M_SB + (8 * i + 2 * t) * 4);
#pragma unroll
            for (int h = 0; h < 2; h++) {
                acc[4 * i + 2 * h] = fmaf(blo(res[2 * i + h]), r1[h], fmaf(n1[h], c.x, s.x));
                acc[4 * i + 2 * h + 1] = fmaf(bhi(res[2 * i + h]), r1[h], fmaf(n1[h], c.y, s.y));
            }
        }
        mbar_spin(wfull + 5 * 8, 0);
        xwait(0, 1);
        TS(leader, 22 + uw)
        uint32_t ps = uw ? P1S : P0S, xo = (ps & 3) * 16, xp = 0;
        const uint64_t ax = dz + (((dsb + OFF_XR) >> 4) | 0x10000u);
        uint64_t ad = ax + xo * 64, bd = dz + b80_desc(dsb, 5, 0, 0);
#pragma unroll 1
        for (int i = 0; i < 5; i++) {
            const uint32_t x1 = xfull + (1 + 2 * i) * 8, p1 = 1, x2 = xfull + min(2 + 2 * i, 9) * 8, p2 = 1;
            const uint32_t w2 = wfull + (min(6 + i, 9) & 7) * 8, pw = i >= 2;
            const bool ok1 = mbar_test(x1, p1);
            wg_fence();
#pragma unroll
            for (int q = 0; q < 4; q++) wgmma_ss80(acc, ad + q * 2, bd + q * B80_STEP, 1);
            wg_commit();
            wg_wait<1>();
            if (lane < 2 && i) mbar_arrive(xempty + xp);
            if (lane == 0 && i) mbar_arrive(wempty + ((4 + i) & 7) * 8);
            if (!ok1) mbar_spin(x1, p1);
            const bool ok2 = mbar_test(x2, p2), okw = mbar_test(w2, pw);
            wg_fence();
#pragma unroll
            for (int q = 0; q < 4; q++) wgmma_ss80(acc, ad + 512 + q * 2, bd + B80_HALF + q * B80_STEP, 1);
            wg_commit();
            const uint32_t xc = xo;
            ps >>= 2;
            xp = xo + 8; xo = (ps & 3) * 16;
            ad = ax + xo * 64;
            bd += i == 2 ? 2 * B80_HALF - 8192 + (8192ll << 16) : 2 * B80_HALF;
            asm volatile("" : "+l"(ad), "+l"(bd));
            wg_wait<1>();
            if (lane < 2) mbar_arrive(xempty + xc);
            if (!ok2) mbar_spin(x2, p2);
            if (!okw) mbar_spin(w2, pw);
            TR(leader, (uw ? 86 : 20) + 2 * i)
        }
        wg_wait<0>();
        reg_fence(acc);
        if (lane < 2) mbar_arrive(xempty + xp);
        if (lane == 0) mbar_arrive(wempty + (9 & 7) * 8);
        TS(leader, 38 + uw)
        float a0 = 0.f, b0 = 0.f, a1 = 0.f, b1 = 0.f;
#pragma unroll
        for (int i = 0; i < 5; i++) {
            uint32_t* p = &x2[4 * i];
#pragma unroll
            for (int e = 0; e < 4; e++) p[e] = pack2(acc[8 * i + 2 * e], acc[8 * i + 2 * e + 1]);
#pragma unroll
            for (int e = 0; e < 4; e++) p[e] = lop3<0xB8>(p[e], (((wt >> 3) ^ (wt << 2)) & 7) == e, ep);
            stg128(&g_x2f[(tile * 40 + (i < 4 ? 4 * j + i : 32 + j)) * 128 + wt], p[0], p[1], p[2], p[3]);
#pragma unroll
            for (int e = 0; e < 8; e += 4) {
                const float* u = &acc[8 * i + e];
                a0 += u[0] + u[1]; b0 = fmaf(u[0], u[0], fmaf(u[1], u[1], b0));
                a1 += u[2] + u[3]; b1 = fmaf(u[2], u[2], fmaf(u[3], u[3], b1));
            }
        }
#pragma unroll
        for (int o = 1; o < 4; o *= 2) {
            a0 += __shfl_xor_sync(~0u, a0, o); b0 += __shfl_xor_sync(~0u, b0, o);
            a1 += __shfl_xor_sync(~0u, a1, o); b1 += __shfl_xor_sync(~0u, b1, o);
        }
        if (t < 2) stg64(&g_stats[(tile * 8 + j) * 64 + 16 * wq + g + 8 * t], tag(__float_as_uint(t ? a1 : a0), ep), __float_as_uint(t ? b1 : b0));
        signal_cnt(&g_cnt.g2[tile * 32], lane, 1, true);
        TS(leader, 40 + uw)
#pragma unroll
        for (int i = 0; i < 10; i++) {
            const float2 c = lds64f(sb + M_GB + (8 * i + 2 * t) * 4), e = lds64f(sb + M_CI + (8 * i + 2 * t) * 4);
#pragma unroll
            for (int h = 0; h < 2; h++)
                res[2 * i + h] = fma2(pack2(c.x, c.y), x2[2 * i + h], pack2(e.x * blo(res[2 * i + h]), e.y * bhi(res[2 * i + h])));
        }
#pragma unroll
        for (int i = 0; i < 20; i++) asm volatile("" : "+r"(res[i]));
    }
    float acc0[64], acc1[44];
    float2 q[4];
    {
        uint4 f0, f1, f2, f3;
        auto xseq = [&](int kb) { return ring_pos(uw, kb, XLEAD) & 7; };
        auto step = [&](const uint4& f, uint64_t bd) {
            wg_fence();
            wgmma_rs128(acc0, f.x, f.y, f.z, f.w, bd, 1);
            wgmma_rs88(acc1, f.x, f.y, f.z, f.w, bd + 512, 1);
            wg_commit();
        };
        const uint32_t xa = sb + OFF_XR + wt * 16;
        const float2* const gs = &g_stats[(tile * 8 + 2 * t) * 64 + 16 * wq + g];
        zero(acc0); zero(acc1);
        uint32_t xs = 0;
        f0 = make_uint4(x2[0], x2[1], x2[2], x2[3]); f1 = make_uint4(x2[4], x2[5], x2[6], x2[7]);
        f2 = make_uint4(x2[8], x2[9], x2[10], x2[11]); f3 = make_uint4(x2[12], x2[13], x2[14], x2[15]);
#pragma unroll
        for (int i = 0; i < 4; i++) q[i] = make_float2(0.f, 0.f);
        mbar_spin(wempty + (9 & 7) * 8, 1);
        mbar_spin(wfull + (10 & 7) * 8, (10 >> 3) & 1);
#pragma unroll 1
        for (int kb = 0; kb < 10; kb++) {
            const uint32_t wn = 10 + 2 * kb;
            const uint64_t bd = dz + (((dsb + OFF_W + (wn & 7) * 16384) >> 4) | (256u << 16));
            step(f0, bd);
            wg_wait<1>();
            if (kb && lane == 0) mbar_arrive(wempty + ((wn - 1) & 7) * 8);
            lds128_if(kb, f2, xa + xs * 8192 + 4096); lds128_if(kb, f3, xa + xs * 8192 + 6144);
            const bool w1 = mbar_test(wfull + ((wn + 1) & 7) * 8, (wn >> 3) & 1), x1 = kb < 9 && mbar_test(xfull + (kb + 1) * 8, 0);
            step(f1, bd + 128);
            if (!w1) mbar_spin(wfull + ((wn + 1) & 7) * 8, (wn >> 3) & 1);
            step(f2, bd + 1024);
            if (lane < 2 && kb) mbar_arrive_after(xempty + xs * 8, f2.x, f3.x, nil);
            wg_wait<1>();
            if (lane == 0) mbar_arrive(wempty + (wn & 7) * 8);
            xs = xseq(kb + 1);
            if (x1) { f0 = lds128(xa + xs * 8192); f1 = lds128(xa + xs * 8192 + 2048); }
            const bool w2 = mbar_test(wfull + ((wn + 2) & 7) * 8, ((wn + 2) >> 3) & 1);
            step(f3, bd + 1152);
            if (kb < 9 && !x1) { xwait(kb + 1, 2); f0 = lds128(xa + xs * 8192); f1 = lds128(xa + xs * 8192 + 2048); }
            if (!w2) mbar_spin(wfull + ((wn + 2) & 7) * 8, ((wn + 2) >> 3) & 1);
            if (kb == 0) {
                TS(leader, 42 + uw)
#pragma unroll
                for (int i = 0; i < 4; i++) q[i] = ld_stat(gs + (i & 1) * 64 + 8 * (i >> 1));
            }
            if (kb == 4) {
                uint32_t it = 0;
                while (RARE(__any_sync(~0u, ((__float_as_uint(q[0].x) ^ ep) | (__float_as_uint(q[1].x) ^ ep) | (__float_as_uint(q[2].x) ^ ep) | (__float_as_uint(q[3].x) ^ ep)) & 1))) {
#pragma unroll
                    for (int i = 0; i < 4; i++) q[i] = ld_stat(gs + (i & 1) * 64 + 8 * (i >> 1));
                    SPIN_CHECK(49)
                }
                float a0 = q[0].x + q[1].x, b0 = q[0].y + q[1].y, a1 = q[2].x + q[3].x, b1 = q[2].y + q[3].y;
#pragma unroll
                for (int o = 1; o < 4; o *= 2) {
                    a0 += __shfl_xor_sync(~0u, a0, o); b0 += __shfl_xor_sync(~0u, b0, o);
                    a1 += __shfl_xor_sync(~0u, a1, o); b1 += __shfl_xor_sync(~0u, b1, o);
                }
                a0 *= 1.f / D_; a1 *= 1.f / D_;
                const float r0 = 0.5f * rsqrtf(fmaxf(b0 * (1.f / D_) - a0 * a0, 0.f) + 1e-5f), r1 = 0.5f * rsqrtf(fmaxf(b1 * (1.f / D_) - a1 * a1, 0.f) + 1e-5f);
                const uint32_t sel = t == 0 ? 0x1010 : t == 1 ? 0x4432 : 0x4444;
                if (t == 0) { sts32(sb + M_F1 + (64 * uw + 16 * wq + g) * 4, __float_as_uint(r0)); sts32(sb + M_F1 + (64 * uw + 16 * wq + g + 8) * 4, __float_as_uint(r1)); }
                q[2] = make_float2(8.f * 0.0356774081f * r0 * r0 * r0, 2.f * 0.7978845608f * r0);
                q[3] = make_float2(8.f * 0.0356774081f * r1 * r1 * r1, 2.f * 0.7978845608f * r1);
                q[1] = make_float2(__uint_as_float(__byte_perm(split2(-a0), 0, sel)), __uint_as_float(__byte_perm(split2(-a1), 0, sel)));
            }
            if (kb == 6) {
#pragma unroll
                for (int i = 0; i < 5; i++) stg128(&g_x1f[(tile * 8 + j) * 640 + i * 128 + wt], res[4 * i], res[4 * i + 1], res[4 * i + 2], res[4 * i + 3]);
            }
            if (kb == 8) asm volatile("fence.proxy.async.global;" ::: "memory");
            TR(leader, 10 * uw + kb)
        }
        const uint64_t fd = ((uint64_t)8 << 32) | ((dsb + OFF_W + 6 * 16384) >> 4);
        wg_fence();
        wgmma_rs128k(acc0, __float_as_uint(q[1].x), __float_as_uint(q[1].y), 0, 0, fd, 1);
        wgmma_rs88k(acc1, __float_as_uint(q[1].x), __float_as_uint(q[1].y), 0, 0, fd + 128, 1);
        wg_commit();
        if (lane == 0) {
            mbar_arrive(bars + B_XFREE * 8);
            asm volatile("mbarrier.arrive.shared::cluster.b64 _, [%0];" ::"r"(peer_addr(bars + B_XFREE * 8)) : "memory");
        }
    }
    const uint32_t recv = sb + recv_off(uw) + wt * 16;
    uint32_t ha[48] = {}, hb[48], hx[12];
    uint64_t wb = dz + (((dsb + OFF_W) >> 4) | (512u << 16));
    auto wdesc = [&](int n) { return wb + (n & 7) * 1024; };
    auto wwait = [&](int n) { mbar_spin(wfull + (n & 7) * 8, (n >> 3) & 1); };
    auto wfree = [&](int n) { if (lane == 0) mbar_arrive(wempty + (n & 7) * 8); };
    auto fresh = [&]() { wb += pp.nil; asm volatile("" : "+l"(wb)); };
    uint32_t pk[32];
    {
        float P0[64];
        const float2 r0 = q[2], r1 = q[3];
        const uint32_t ra = peer_addr(recv), rb = peer_addr(bars + (B_RECV + 4 * uw) * 8);
        auto conv32 = [&](const float* v, int b) {
#pragma unroll
            for (int i = 0; i < 4; i++) {
                ha[8 * b + 2 * i] = pack2(gelu2r(v[4 * i], r0), gelu2r(v[4 * i + 1], r0));
                ha[8 * b + 2 * i + 1] = pack2(gelu2r(v[4 * i + 2], r1), gelu2r(v[4 * i + 3], r1));
            }
#pragma unroll
            for (int s = 2 * b; s < 2 * b + 2; s++) st_peer(ra + s * 2048, ha[4 * s], ha[4 * s + 1], ha[4 * s + 2], ha[4 * s + 3], rb + (b >> 1) * 8);
        };
        auto fetch = [&](int k) {
            mbar_spin(bars + (B_RECV + 4 * uw + k) * 8, 0);
#pragma unroll
            for (int s = 4 * k; s < 4 * k + 4; s++) { const uint4 x = lds128(recv + s * 2048); hb[4 * s] = x.x; hb[4 * s + 1] = x.y; hb[4 * s + 2] = x.z; hb[4 * s + 3] = x.w; }
        };
        auto stage = [&](int n, const uint32_t* a, int steps, int sc) {
            wwait(n);
            wg_fence();
#pragma unroll
            for (int s = 0; s < steps; s++) wgmma_rs128(P0, a[4 * s], a[4 * s + 1], a[4 * s + 2], a[4 * s + 3], wdesc(n) + s * 128, sc || s);
            wg_commit();
        };
        wg_wait<0>();
        reg_fence(acc0); reg_fence(acc1);
        wfree(29); wfree(30);
        TS(leader, 44 + uw)
        if (uw) bar_sync(13, 256);
        uint32_t hr[6];
#pragma unroll
        for (int i = 0; i < 6; i++) {
            const float2 r = (i & 1) ? r1 : r0;
            hr[i] = pack2(gelu2r(acc1[32 + 2 * i], r), gelu2r(acc1[33 + 2 * i], r));
        }
        if (uw) mbar_spin(bars + B_XFREE * 8, 0);
        st_peer(ra + 24576, hr[0], hr[1], hr[2], hr[3], rb + 24);
        asm volatile("st.async.shared::cluster.mbarrier::complete_tx::bytes.v2.b32 [%0], {%1, %2}, [%3];" ::"r"(ra + 26624 - wt * 8), "r"(hr[4]), "r"(hr[5]), "r"(rb + 24) : "memory");
        conv32(&acc1[0], 4);
        conv32(&acc1[16], 5);
        TS(leader, 46 + uw)
        stage(31, &ha[32], 4, 0);
#pragma unroll
        for (int b = 0; b < 4; b++) {
            conv32(&acc0[16 * b], b);
            if (b == 0 && !uw) asm volatile("bar.arrive 13, 256;" ::: "memory");
            if (b == 3) {
                fetch(2);
                mbar_spin(bars + (B_RECV + 4 * uw + 3) * 8, 0);
                const uint4 x = lds128(recv + 24576);
                const uint2 y = lds64(recv + 26624 - wt * 8);
                const uint32_t hp[6] = {x.x, x.y, x.z, x.w, y.x, y.y};
#pragma unroll
                for (int i = 0; i < 6; i++) { hx[i] = (j & 1) ? hp[i] : hr[i]; hx[6 + i] = (j & 1) ? hr[i] : hp[i]; }
            }
            if (!(b & 1)) wwait(32 + (b >> 1));
            wg_fence();
#pragma unroll
            for (int s = 0; s < 2; s++) wgmma_rs128(P0, ha[8 * b + 4 * s], ha[8 * b + 4 * s + 1], ha[8 * b + 4 * s + 2], ha[8 * b + 4 * s + 3], wdesc(32 + (b >> 1)) + (2 * (b & 1) + s) * 128, 1);
            wg_commit();
            if (!(b & 1)) { wg_wait<1>(); wfree(31 + (b >> 1)); }
        }
        TR(leader, 64 + 10 * uw)
        fresh();
        stage(34, &hb[32], 4, 1); wg_wait<1>(); wfree(33);
        fetch(0);
        stage(35, hx, 3, 1); wg_wait<1>(); wfree(34);
        fetch(1);
        stage(36, &hb[0], 4, 1); wg_wait<1>(); wfree(35);
        stage(37, &hb[16], 4, 1); wg_wait<1>(); wfree(36);
        wg_wait<0>();
        reg_fence(P0);
        pack_part<64>(pk, P0, ep);
        uint32_t all = 0;
#pragma unroll
        for (int i = 0; i < 32; i++) all |= pk[i];
        if (lane == 0) mbar_arrive_after(wempty + (37 & 7) * 8, all, 0, nil);
        TR(leader, 65 + 10 * uw)
    }
    {
        uint4* const dst = g_part + (size_t)(tile * 8 + j) * 5120 + wt;
        const uint4* const src = g_part + (size_t)tile * 40960 + j * 512 + wt;
        float F[2][32];
        uint4 gb[4];
        float rr[2];
        float2 gf[8];
        uint4 base[4], u1[4], u2[4], u3[4];
#pragma unroll
        for (int c = 2; c < 5; c++) {
            float (&P)[32] = F[c & 1];
            fresh();
#pragma unroll
            for (int s = 0; s < 27; s++) {
                const int e = s < 8 ? 0 : s < 15 ? 1 : s < 23 ? 2 : 3, o = s - (e == 0 ? 0 : e == 1 ? 8 : e == 2 ? 15 : 23), n = 30 + 4 * c + e;
                const uint32_t* a = s < 12 ? &ha[4 * s] : s < 15 ? &hx[4 * (s - 12)] : &hb[4 * (s - 15)];
                if (o == 0) wwait(n);
                if (o == 0 || s == 1) wg_fence();
                wgmma_rs64(P, a[0], a[1], a[2], a[3], wdesc(n) + o * 128, s);
                if (o == 0) { wg_commit(); wg_wait<1>(); if (c > 2 || s) wfree(n - 1); }
                if (s == 0 && c > 2) { reg_fence(F[~c & 1]); pack_part<32>(pk, F[~c & 1], ep); }
                if (c == 2 && s % 3 == 0 && s < 24) st_part(dst + g4_block(s / 12, j) * 512 + (s / 3 & 3) * 128, &pk[4 * (s / 3)]);
                if (c == 3 && s % 4 == 1 && s < 16) st_part(dst + g4_block(2, j) * 512 + s / 4 * 128, &pk[4 * (s / 4)]);
                if (c == 4 && s % ST3 == 0 && s < 4 * ST3) st_part(dst + g4_block(3, j) * 512 + s / ST3 * 128, &pk[4 * (s / ST3)]);
                if (c == 4 && s >= 4 && s < 8) base[s - 4] = ldcg128(&g_x1f[(tile * 8 + j) * 640 + (s - 4) * 128 + wt]);
                if (c == 4 && s >= 34 - LD2 && s < 38 - LD2) { const int i = s + LD2 - 34; gf[2 * i] = lds64f(sb + M_GB + (16 * i + 2 * t) * 4); gf[2 * i + 1] = lds64f(sb + M_GB + (16 * i + 8 + 2 * t) * 4); }
                if (c == 4 && s >= 12 && s < 14) rr[s - 12] = __uint_as_float(lds32(sb + M_F1 + (64 * uw + 16 * wq + g + 8 * (s - 12)) * 4));
                if (c == 4 && s >= 8 && s < 12) u1[s - 8] = ld_part(src + (j ^ 6) * 5120 + (s - 8) * 128);
                if (c == 4 && s >= LD2 && s < LD2 + 4) u2[s - LD2] = ld_part(src + (j ^ 4) * 5120 + (s - LD2) * 128);
                if (c == 4 && s >= LD3 && s < LD3 + 4) u3[s - LD3] = ld_part(src + (j ^ 2) * 5120 + (s - LD3) * 128);
                if (27 * (c - 2) + s == R_GATE && lane == 0) mbar_arrive(bars + (B_RING + uw) * 8);
                if (s == 7 || s == 14 || s == 22 || s == 26) wg_commit();
                if (c == 4) { TR(leader && s == 7, 68 + 10 * uw) TR(leader && s == 14, 69 + 10 * uw) TR(leader && s == 22, 70 + 10 * uw) }
            }
            TR(leader, 64 + c + (c == 4 ? 3 : 0) + 10 * uw)
        }
        float (&O)[32] = F[0];
#pragma unroll
        for (int i = 0; i < 4; i++) if (LD3 + i > 26) u3[i] = ld_part(src + (j ^ 2) * 5120 + i * 128);
#pragma unroll
        for (int i = 0; i < 4; i++) gb[i] = scale16(gf[2 * i], gf[2 * i + 1], rr[0], rr[1]);
        uint32_t it = 0;
        while (__any_sync(~0u, (stale4(u1, ep) | stale4(u2, ep) | stale4(u3, ep)) & 1)) {
            STALE(__any_sync(~0u, stale4(u1, ep) & 1) ? 4 : __any_sync(~0u, stale4(u2, ep) & 1) ? 5 : 6)
            ld_part4(u1, src + (j ^ 6) * 5120, 128); ld_part4(u2, src + (j ^ 4) * 5120, 128); ld_part4(u3, src + (j ^ 2) * 5120, 128);
            SPIN_CHECK(58)
        }
        TR(leader, 73 + 10 * uw)
#pragma unroll
        for (int i = 0; i < 4; i++) u1[i] = add2(add2(u1[i], u2[i]), u3[i]);
        TS(leader, 50 + uw)
        wg_wait<0>();
        reg_fence(O);
        TS(leader, 48 + uw)
        const uint32_t so = sb + recv_off(uw) + wq * 2048;
#pragma unroll
        for (int i = 0; i < 4; i++) {
            const float* o = &O[8 * i];
            const uint4 r = fin16(add2(u1[i], make_uint4(pack2(o[0], o[1]), pack2(o[2], o[3]), pack2(o[4], o[5]), pack2(o[6], o[7]))), base[i], gb[i]);
            stsm4(so + (lane & 15) * 128 + (((2 * i + (lane >> 4)) ^ (lane & 7)) << 4), r.x, r.y, r.z, r.w);
        }
        TR4(leader, 100 + uw)
        __syncwarp();
#pragma unroll
        for (int i = 0; i < 4; i++) {
            const int row = (lane >> 3) + 4 * i;
            stg128(out + (size_t)(row0 + row) * D_ + 64 * j + 8 * (lane & 7), lds128(so + row * 128 + (((lane & 7) ^ (row & 7)) << 4)));
        }
        TS(leader, 24 + uw)
        warp_arrive(bars + B_OWN * 8);
    }
}

typedef CUresult (*EncFn)(CUtensorMap*, CUtensorMapDataType, cuuint32_t, void*, const cuuint64_t*, const cuuint64_t*, const cuuint32_t*,
                          const cuuint32_t*, CUtensorMapInterleave, CUtensorMapSwizzle, CUtensorMapL2promotion, CUtensorMapFloatOOBfill);

static void enc(EncFn fn, CUtensorMap* m, void* p, int rank, const cuuint64_t* dims, const cuuint64_t* strides, const cuuint32_t* box, bool plain = false) {
    const CUtensorMapSwizzle sw = box[0] > 64 || plain ? CU_TENSOR_MAP_SWIZZLE_NONE : CU_TENSOR_MAP_SWIZZLE_128B;
    cuuint32_t es[5] = {1, 1, 1, 1, 1};
    CUresult r = fn(m, CU_TENSOR_MAP_DATA_TYPE_BFLOAT16, rank, p, dims, strides, box, es, CU_TENSOR_MAP_INTERLEAVE_NONE, sw,
                    CU_TENSOR_MAP_L2_PROMOTION_L2_128B, CU_TENSOR_MAP_FLOAT_OOB_FILL_NONE);
    (void)r;
}
static void enc2(EncFn fn, CUtensorMap* m, void* p, uint64_t cols, uint64_t rows, uint32_t bc, uint32_t br, bool plain = false) {
    cuuint64_t dims[2] = {cols, rows}, st[1] = {cols * 2};
    cuuint32_t box[2] = {bc, br};
    enc(fn, m, p, 2, dims, st, box, plain);
}

extern "C" void kernel_launch(void* const* d_in, const int* in_sizes, int n_in, void* d_out, int out_size) {
    static Maps mp;
    static Ptrs pp;
    static void* cached[13];
    bool same = true;
    for (int i = 0; i < 13; i++) same = same && (cached[i] == d_in[i]);
    if (!same) {
        void* fnp = nullptr;
        cudaDriverEntryPointQueryResult qr;
        cudaGetDriverEntryPoint("cuTensorMapEncodeTiled", &fnp, cudaEnableDefault, &qr);
        EncFn fn = (EncFn)fnp;
        cudaGetSymbolAddress((void**)&pp.s, g_scratch);
        void *x1T = g_x1T, *t = g_t;
        cuuint64_t dq[3] = {64, S_, 10}, sq[2] = {D_ * 2, 128};
        cuuint32_t bq[3] = {64, 16, 10};
        enc(fn, &mp.q, d_in[0], 3, dq, sq, bq);
        enc2(fn, &mp.k, d_in[1], D_, S_, 80, 67); enc2(fn, &mp.v, d_in[2], D_, S_, 80, 64);
        enc2(fn, &mp.qT, g_qT, 16 * D_, 128, 80, 128);
        enc2(fn, &mp.x[0], x1T, S_, D_, 64, 64); enc2(fn, &mp.x[1], (bf16*)t + 2 * D_, D_, S_, 64, 64);
        enc2(fn, &mp.x[2], g_x2f, 64, 320 * 64, 64, 64, true);
        enc2(fn, &mp.w1, d_in[7], D_, D_, 64, 64); enc2(fn, &mp.w1h, d_in[7], D_, D_, 64, 160); enc2(fn, &mp.w3h, d_in[9], F_, D_, 64, 160);
        enc2(fn, &mp.wmod, d_in[12], 6 * D_, D_, 64, 160);
        const cuuint64_t R = D_ * 2;
        cuuint64_t da[5] = {D_, 2, 4, 4, 16}, sa[4] = {R, 8 * R, 2 * R, 32 * R}, db[5] = {D_, 2, 2, 4, 8}, sb[4] = {R, 8 * R, 2 * R, 16 * R};
        cuuint32_t ba[5] = {64, 2, 4, 4, 2}, bb[5] = {64, 2, 2, 4, 4};
        enc(fn, &mp.w2a, d_in[8], 5, da, sa, ba); enc(fn, &mp.w2b, (bf16*)d_in[8] + 512 * D_, 5, db, sb, bb);
        cuuint64_t dw[3] = {64, D_, 27}, sw[2] = {F_ * 2, 128};
        cuuint32_t bw[3] = {64, 32, 3};
        enc(fn, &mp.w3a, d_in[9], 3, dw, sw, bw);
        enc2(fn, &mp.w3b, d_in[9], F_, D_, 24, 32);
        enc2(fn, &mp.w4[0], d_in[10], D_, F_, 64, 64); enc2(fn, &mp.w4[1], d_in[10], D_, F_, 64, 48);
        pp.q = (const bf16*)d_in[0]; pp.w_mod = (const bf16*)d_in[12]; pp.shift_k = (const bf16*)d_in[3];
        pp.ssm_k = (const bf16*)d_in[4]; pp.ssm_D = (const bf16*)d_in[5]; pp.w1 = (const bf16*)d_in[7]; pp.w2 = (const bf16*)d_in[8];
        pp.w4 = (const bf16*)d_in[10]; pp.c = (const bf16*)d_in[11];
        cudaFuncSetAttribute(fused_kernel, cudaFuncAttributeMaxDynamicSharedMemorySize, SMEM_BYTES);
        for (int i = 0; i < 13; i++) cached[i] = d_in[i];
    }
    fused_kernel<<<NCTA, NTHR, SMEM_BYTES, cudaStreamPerThread>>>(pp, (bf16*)d_out, mp);
}
```

```cpp
#include <cuda_runtime.h>
#include <cuda_bf16.h>
#include <cuda.h>
#include <stdint.h>
#include <stdio.h>

typedef __nv_bfloat16 bf16;

constexpr int S_ = 2048, D_ = 640, F_ = 1728;
constexpr int NCTA = 132, NTHR = 512;

constexpr int TAB_BYTES = 9216, VEC_BYTES = 1440;
struct Counters {
    unsigned kv[8 * 32];
    unsigned q[4 * 32], x[4 * 32];
    unsigned wr[32], tab[32], uv[32], cs[32], cs2[32], done[32];
    unsigned g1[32 * 32];
    unsigned g2[32 * 32];
};
struct Scratch {
    Counters cnt;
    unsigned epoch;
    alignas(1024) bf16 qst[2 * S_];
    alignas(1024) uint4 wr[2 * 8 * 10 * 128];
    alignas(1024) uint2 mod[2 * 6 * D_];
    alignas(1024) uint4 tab[(TAB_BYTES + 8 * VEC_BYTES) / 16];
    alignas(1024) float uv[2 * 3 * D_];
    alignas(1024) float cs3[2 * 1920];
    alignas(1024) uint4 cs3b[8 * 216];
    alignas(1024) float2 stats[32 * 8 * 64];
    alignas(1024) bf16 kvT[D_ * S_];
    alignas(1024) bf16 qT[D_ * S_];
    alignas(1024) bf16 x1T[D_ * S_];
    alignas(1024) bf16 t[(S_ + 4) * D_];
    alignas(1024) uint4 x2f[32 * 40 * 128];
    alignas(1024) uint4 x1f[32 * 8 * 5 * 128];
    alignas(1024) uint4 part[32 * 8 * 10 * 4 * 128];
};
__device__ Scratch g_scratch;
#define g_kvT (pp.s->kvT)
#define g_qT (pp.s->qT)
#define g_x1T (pp.s->x1T)
#define g_qst (pp.s->qst)
#define g_t (pp.s->t)
#define g_x2f (pp.s->x2f)
#define g_x1f (pp.s->x1f)
#define g_part (pp.s->part)
#define g_wr (pp.s->wr)
#define g_mod (pp.s->mod)
#define g_tab (pp.s->tab)
#define g_uv (pp.s->uv)
#define g_cs3 (pp.s->cs3)
#define g_cs3b (pp.s->cs3b)
#define g_stats (pp.s->stats)
#define g_cnt (pp.s->cnt)
#define g_epoch (pp.s->epoch)

struct Maps {
    CUtensorMap k, v, q;
    CUtensorMap qT;
    CUtensorMap x[3];
    CUtensorMap w1, w1h, w3h, wmod;
    CUtensorMap w2a, w2b;
    CUtensorMap w3a, w3b;
    CUtensorMap w4[2];
};

struct Ptrs {
    Scratch* s;
    uint64_t nil;
    const bf16 *q, *w_mod, *shift_k, *ssm_k, *ssm_D, *w1, *w2, *w4, *c;
};

constexpr int OFF_W = 0;
constexpr int OFF_XR = 131072;
constexpr int OFF_REM = 196608;
constexpr int OFF_TAB = OFF_REM + 5 * 4096;
constexpr int OFF_ROW = OFF_TAB + 4608;
constexpr int OFF_F1 = OFF_ROW + 4096;
constexpr int RECV_BYTES = 30720;
constexpr int OFF_M = OFF_REM + RECV_BYTES;
constexpr int OFF_OUT = OFF_XR + 32768;
static_assert(OFF_F1 + 1280 <= OFF_M, "G1 map");
constexpr int OFF_ST = 0;
constexpr int OFF_SSM = 20480;
constexpr int OFF_WM = 0;
constexpr int OFF_QIN = 49152;
constexpr int OFF_QT = 49152;
constexpr int OFF_Z = OFF_TAB;
constexpr int OFF_RING = 80896;
constexpr int OFF_KIN = OFF_RING, OFF_VIN = OFF_KIN + 2 * 10752;
constexpr int OFF_CH = OFF_RING + 3 * 16384, CH_BYTES = 13312, OFF_P = 5120;
static_assert(OFF_RING + 5 * 16384 <= OFF_CH + 3 * CH_BYTES && OFF_CH + 5 * CH_BYTES <= OFF_REM, "the last two rings replace channels 0..2");
constexpr int M_BAR = OFF_M;
constexpr int M_F1 = OFF_M + 832;
constexpr int M_GB = M_F1 + 1280, M_C = M_GB + 320, M_SB = M_C + 320, M_CI = M_SB + 320;
constexpr int M_KS = M_CI + 320;
constexpr int M_AB = M_KS + 160;
constexpr int M_EP = M_AB + 80;
constexpr int M_SINK = M_EP + 16;
constexpr int M_NUL = M_SINK + 16;
constexpr int M_TS = M_NUL + 128;
constexpr int SMEM_BYTES = M_TS;
static_assert(SMEM_BYTES <= 232448, "smem");

enum { B_WFULL = 0, B_WEMPTY = 8, B_XEMPTY = 16, B_XFULL = 24  ,
       B_RAW = 44, B_QIN = 45, B_SSM = 46, B_VEC = 47, B_VEC3 = 48, B_WM = 49, B_TAB = 50, B_QRDY = 51,
       B_MODR = 52, B_RAW2 = 53, B_RAW3 = 54, B_GATE = 56, B_SUMS = 62, B_RECV = 64  ,
       B_LAND = 72, B_AGAIN = 80, B_RETRY = 84,
       B_XS = 88, B_R1 = 89, B_BK = 90, B_KVS = 91,
       B_XFREE = 92, B_OWN = 93, B_IN = 94,
       B_RING = 96   };
#define T_KVB 1500
#define T_SSM 4200
#define PF_T0 5900
#define PF_DT 420
#define HELP_T 1000
#define R_GATE 34
#define GATE_W2 7
#define GATE_W3 24
#define GATE_W3B 37
#define W3_N2 15
#define LEAD1 5
#define XLEAD 4

#define SPIN_FAIL(code) __trap();
#define SPIN_LIMIT (1u << 22)
#define STALE(c)
#define STALE1(c)
#define TS(c, i)
#define TG(c, i)
#define TR(c, i)
#define TR2(c, i)
#define TR4(c, i)
#define TR5(c, i)
#define SPIN_CHECK(code) asm volatile("" ::"r"(it));
#define RARE(x) __builtin_expect((x) != 0, 0)
__device__ __forceinline__ uint32_t s2u(const void* p) { return (uint32_t)__cvta_generic_to_shared(p); }
__device__ __forceinline__ bool elect() {
    uint32_t p;
    asm volatile("{.reg .pred P; elect.sync _|P, 0xffffffff; selp.u32 %0,1,0,P;}" : "=r"(p));
    return p != 0;
}
__device__ __forceinline__ void mbar_init(uint32_t b, uint32_t n) { asm volatile("mbarrier.init.shared.b64 [%0], %1;" ::"r"(b), "r"(n)); }
__device__ __forceinline__ void mbar_expect(uint32_t b, uint32_t bytes) {
    asm volatile("mbarrier.arrive.expect_tx.shared.b64 _, [%0], %1;" ::"r"(b), "r"(bytes) : "memory");
}
__device__ __forceinline__ void mbar_arrive(uint32_t b) { asm volatile("mbarrier.arrive.shared.b64 _, [%0];" ::"r"(b) : "memory"); }
__device__ __forceinline__ void mbar_arrive_after(uint32_t b, uint32_t v0, uint32_t v1, uint32_t nil) { mbar_arrive(b + ((v0 | v1) & nil)); }
__device__ __forceinline__ void warp_arrive(uint32_t b) { __syncwarp(); if (elect()) mbar_arrive(b); }
__device__ __forceinline__ uint32_t peer_addr(uint32_t a) {
    uint32_t r;
    asm("{\n.reg .b32 q;\nmov.u32 q, %%cluster_ctarank;\nxor.b32 q, q, 1;\nmapa.shared::cluster.u32 %0, %1, q;\n}" : "=r"(r) : "r"(a));
    return r;
}
__device__ __forceinline__ bool mbar_test(uint32_t b, uint32_t parity) {
    uint32_t ok;
    asm volatile("{.reg .pred P; mbarrier.test_wait.parity.shared.b64 P, [%1], %2; selp.u32 %0,1,0,P;}" : "=r"(ok) : "r"(b), "r"(parity) : "memory");
    return ok != 0;
}
__device__ __forceinline__ bool mbar_try(uint32_t b, uint32_t parity) {
    uint32_t ok;
    asm volatile("{.reg .pred P; mbarrier.try_wait.parity.shared.b64 P, [%1], %2; selp.u32 %0,1,0,P;}" : "=r"(ok) : "r"(b), "r"(parity) : "memory");
    return ok != 0;
}
__device__ __forceinline__ void mbar_wait(uint32_t b, uint32_t parity) {
    if (__all_sync(0xffffffffu, mbar_try(b, parity))) return;
    uint32_t it = 0;
    while (!__all_sync(0xffffffffu, mbar_try(b, parity))) { if (++it > SPIN_LIMIT) SPIN_FAIL((b >> 3) & 63) }
}
__device__ __forceinline__ void mbar_spin(uint32_t b, uint32_t parity) {
    asm volatile("{\n.reg .pred P;\nSPIN:\nmbarrier.try_wait.parity.shared.b64 P, [%0], %1;\n@!P bra.uni SPIN;\n}" ::"r"(b), "r"(parity) : "memory");
}
__device__ __forceinline__ void bar_sync(int id, int n) { asm volatile("bar.sync %0, %1;" ::"r"(id), "r"(n) : "memory"); }
__device__ __forceinline__ void fence_async_smem() { asm volatile("fence.proxy.async.shared::cta;" ::: "memory"); }
__device__ __forceinline__ void wait_cnt(const unsigned* p, unsigned target, bool tagged = false) {
    unsigned v, it = 0;
    do {
        asm volatile("ld.relaxed.gpu.global.u32 %0, [%1];" : "=r"(v) : "l"(p) : "memory");
        SPIN_CHECK(60 + (target & 3))
    } while (!__all_sync(0xffffffffu, v >= target));
    if (!tagged) asm volatile("fence.acquire.gpu;" ::: "memory");
}
__device__ __forceinline__ void signal_cnt(unsigned* p, int lane, int n, bool tagged = false) {
    if (tagged) asm volatile("{\n.reg .pred P;\nsetp.lt.s32 P, %1, %2;\n@P red.relaxed.gpu.global.add.u32 [%0], %3;\n}" ::"l"(p), "r"(lane), "r"(n), "r"(1) : "memory");
    else if (lane < n) asm volatile("red.release.gpu.global.add.u32 [%0], 1;" ::"l"(p) : "memory");
    __syncwarp();
}
__device__ __forceinline__ uint32_t clock_lo() { uint32_t c; asm volatile("mov.u32 %0, %%clock;" : "=r"(c)); return c; }
__device__ __forceinline__ void wait_clock(uint32_t c0, uint32_t t) {
    asm volatile("{\n.reg .pred P;\n.reg .b32 c;\nWAIT:\nnanosleep.u32 20;\nmov.u32 c, %%clock;\nsub.u32 c, c, %0;\nsetp.lt.u32 P, c, %1;\n@P bra.uni WAIT;\n}" ::"r"(c0), "r"(t) : "memory");
}
__device__ __forceinline__ void tma_ld2(uint32_t dst, const CUtensorMap* m, int c0, int c1, uint32_t bar) {
    asm volatile("cp.async.bulk.tensor.2d.shared::cluster.global.mbarrier::complete_tx::bytes [%0], [%1, {%3, %4}], [%2];"
                 ::"r"(dst), "l"(m), "r"(bar), "r"(c0), "r"(c1) : "memory");
}
__device__ __forceinline__ void tma_ld3(uint32_t dst, const CUtensorMap* m, int c0, int c1, int c2, uint32_t bar) {
    asm volatile("cp.async.bulk.tensor.3d.shared::cluster.global.mbarrier::complete_tx::bytes [%0], [%1, {%3, %4, %5}], [%2];"
                 ::"r"(dst), "l"(m), "r"(bar), "r"(c0), "r"(c1), "r"(c2) : "memory");
}
__device__ __forceinline__ void tma_ld5(uint32_t dst, const CUtensorMap* m, int col, int blk, uint32_t bar) {
    asm volatile("cp.async.bulk.tensor.5d.shared::cluster.global.mbarrier::complete_tx::bytes [%0], [%1, {%3, %4, %4, %4, %5}], [%2];"
                 ::"r"(dst), "l"(m), "r"(bar), "r"(col), "r"(0), "r"(blk) : "memory");
}
__device__ __forceinline__ void bulk_ld(uint32_t dst, const void* src, uint32_t bytes, uint32_t bar) {
    asm volatile("cp.async.bulk.shared::cluster.global.mbarrier::complete_tx::bytes [%0], [%1], %2, [%3];" ::"r"(dst), "l"(src), "r"(bytes), "r"(bar) : "memory");
}
__device__ __forceinline__ void l2_prefetch(const void* p, uint32_t bytes) {
    asm volatile("cp.async.bulk.prefetch.L2.global [%0], %1;" ::"l"(p), "r"(bytes) : "memory");
}
__device__ __forceinline__ void wg_fence() { asm volatile("wgmma.fence.sync.aligned;" ::: "memory"); }
__device__ __forceinline__ void wg_commit() { asm volatile("wgmma.commit_group.sync.aligned;" ::: "memory"); }
template <int N> __device__ __forceinline__ void wg_wait() { asm volatile("wgmma.wait_group.sync.aligned %0;" ::"n"(N) : "memory"); }
template <int N> __device__ __forceinline__ void reg_fence(float (&d)[N]) {
#pragma unroll
    for (int i = 0; i < N; i++) asm volatile("" : "+f"(d[i])::"memory");
}
template <int N> __device__ __forceinline__ void zero(float (&d)[N]) {
#pragma unroll
    for (int i = 0; i < N; i++) asm volatile("mov.b32 %0, 0;" : "=f"(d[i]));
}
__device__ __forceinline__ uint32_t lds32(uint32_t a) { uint32_t v; asm volatile("ld.shared.b32 %0, [%1];" : "=r"(v) : "r"(a)); return v; }
__device__ __forceinline__ uint2 lds64(uint32_t a) { uint2 v; asm volatile("ld.shared.v2.b32 {%0,%1}, [%2];" : "=r"(v.x), "=r"(v.y) : "r"(a)); return v; }
__device__ __forceinline__ float2 lds64f(uint32_t a) { float2 v; asm volatile("ld.shared.v2.f32 {%0,%1}, [%2];" : "=f"(v.x), "=f"(v.y) : "r"(a)); return v; }
__device__ __forceinline__ void sts32(uint32_t a, uint32_t v) { asm volatile("st.shared.b32 [%0], %1;" ::"r"(a), "r"(v) : "memory"); }
__device__ __forceinline__ void sts64f(uint32_t a, float x, float y) { asm volatile("st.shared.v2.f32 [%0], {%1,%2};" ::"r"(a), "f"(x), "f"(y) : "memory"); }
__device__ __forceinline__ void sts128(uint32_t a, uint32_t x, uint32_t y, uint32_t z, uint32_t w) {
    asm volatile("st.shared.v4.b32 [%0], {%1,%2,%3,%4};" ::"r"(a), "r"(x), "r"(y), "r"(z), "r"(w) : "memory");
}
__device__ __forceinline__ void sts128f(uint32_t a, float x, float y, float z, float w) {
    asm volatile("st.shared.v4.f32 [%0], {%1,%2,%3,%4};" ::"r"(a), "f"(x), "f"(y), "f"(z), "f"(w) : "memory");
}
__device__ __forceinline__ uint4 lds128(uint32_t a) {
    uint4 v;
    asm volatile("ld.shared.v4.b32 {%0,%1,%2,%3}, [%4];" : "=r"(v.x), "=r"(v.y), "=r"(v.z), "=r"(v.w) : "r"(a) : "memory");
    return v;
}
__device__ __forceinline__ void lds128_if(int p, uint4& v, uint32_t a) {
    asm volatile("{\n.reg .pred p;\nsetp.ne.s32 p, %5, 0;\n@p ld.shared.v4.b32 {%0,%1,%2,%3}, [%4];\n}" : "+r"(v.x), "+r"(v.y), "+r"(v.z), "+r"(v.w) : "r"(a), "r"(p) : "memory");
}
__device__ __forceinline__ float4 lds128f(uint32_t a) {
    float4 v;
    asm volatile("ld.shared.v4.f32 {%0,%1,%2,%3}, [%4];" : "=f"(v.x), "=f"(v.y), "=f"(v.z), "=f"(v.w) : "r"(a) : "memory");
    return v;
}
__device__ __forceinline__ void stg128(void* p, uint32_t x, uint32_t y, uint32_t z, uint32_t w) {
    asm volatile("st.global.v4.b32 [%0], {%1,%2,%3,%4};" ::"l"(p), "r"(x), "r"(y), "r"(z), "r"(w) : "memory");
}
__device__ __forceinline__ void stg128(void* p, uint4 v) { stg128(p, v.x, v.y, v.z, v.w); }
__device__ __forceinline__ void stg64(void* p, uint32_t x, uint32_t y) { asm volatile("st.global.v2.b32 [%0], {%1,%2};" ::"l"(p), "r"(x), "r"(y) : "memory"); }
__device__ __forceinline__ void stsm4(uint32_t a, uint32_t r0, uint32_t r1, uint32_t r2, uint32_t r3) {
    asm volatile("stmatrix.sync.aligned.m8n8.x4.shared.b16 [%0], {%1,%2,%3,%4};" ::"r"(a), "r"(r0), "r"(r1), "r"(r2), "r"(r3) : "memory");
}
__device__ __forceinline__ void stsm4t(uint32_t a, uint32_t r0, uint32_t r1, uint32_t r2, uint32_t r3) {
    asm volatile("stmatrix.sync.aligned.m8n8.x4.trans.shared.b16 [%0], {%1,%2,%3,%4};" ::"r"(a), "r"(r0), "r"(r1), "r"(r2), "r"(r3) : "memory");
}
__device__ __forceinline__ void ldsm4t_if(bool p, uint32_t a, uint32_t* r) {
    asm volatile("{\n.reg .pred p;\nsetp.ne.u32 p, %5, 0;\n@p ldmatrix.sync.aligned.m8n8.x4.trans.shared.b16 {%0,%1,%2,%3}, [%4];\n}"
                 : "+r"(r[0]), "+r"(r[1]), "+r"(r[2]), "+r"(r[3]) : "r"(a), "r"((uint32_t)p) : "memory");
}
__device__ __forceinline__ void ldsm4t(uint32_t a, uint32_t& r0, uint32_t& r1, uint32_t& r2, uint32_t& r3) {
    asm volatile("ldmatrix.sync.aligned.m8n8.x4.trans.shared.b16 {%0,%1,%2,%3}, [%4];" : "=r"(r0), "=r"(r1), "=r"(r2), "=r"(r3) : "r"(a) : "memory");
}
__device__ __forceinline__ uint32_t pack2(float lo, float hi) {
    uint32_t r;
    asm("cvt.rn.bf16x2.f32 %0, %1, %2;" : "=r"(r) : "f"(hi), "f"(lo));
    return r;
}
__device__ __forceinline__ uint32_t mul2(uint32_t a, uint32_t b) { uint32_t r; asm("mul.rn.bf16x2 %0, %1, %2;" : "=r"(r) : "r"(a), "r"(b)); return r; }
__device__ __forceinline__ uint32_t fma2(uint32_t a, uint32_t b, uint32_t c) { uint32_t r; asm("fma.rn.bf16x2 %0, %1, %2, %3;" : "=r"(r) : "r"(a), "r"(b), "r"(c)); return r; }
__device__ __forceinline__ uint32_t add2(uint32_t a, uint32_t b) { uint32_t r; asm("add.rn.bf16x2 %0, %1, %2;" : "=r"(r) : "r"(a), "r"(b)); return r; }
__device__ __forceinline__ float blo(uint32_t w) { return __uint_as_float(w << 16); }
__device__ __forceinline__ float bhi(uint32_t w) { return __uint_as_float(w & 0xffff0000u); }
__device__ __forceinline__ float rbf(float x) { return __bfloat162float(__float2bfloat16_rn(x)); }
__device__ __forceinline__ uint32_t ldg32(const void* p) { uint32_t v; asm volatile("ld.global.nc.b32 %0, [%1];" : "=r"(v) : "l"(p)); return v; }
__device__ __forceinline__ uint4 ldg128(const void* p) {
    uint4 v;
    asm volatile("ld.global.nc.v4.b32 {%0,%1,%2,%3}, [%4];" : "=r"(v.x), "=r"(v.y), "=r"(v.z), "=r"(v.w) : "l"(p));
    return v;
}
__device__ __forceinline__ uint4 ldcg128(const void* p) {
    uint4 v;
    asm volatile("ld.global.cg.v4.u32 {%0,%1,%2,%3}, [%4];" : "=r"(v.x), "=r"(v.y), "=r"(v.z), "=r"(v.w) : "l"(p) : "memory");
    return v;
}
__device__ __forceinline__ float ldcg32f(const void* p) { float v; asm volatile("ld.global.cg.f32 %0, [%1];" : "=f"(v) : "l"(p) : "memory"); return v; }
__device__ __forceinline__ float2 ld_stat(const float2* p) {
    float2 v;
    asm volatile("{\n.reg .b64 q;\nld.relaxed.gpu.global.b64 q, [%2];\nmov.b64 {%0, %1}, q;\n}" : "=f"(v.x), "=f"(v.y) : "l"(p) : "memory");
    return v;
}
__device__ __forceinline__ uint32_t ld_cold(const unsigned* p) { uint32_t v; asm volatile("ld.relaxed.gpu.global.u32 %0, [%1];" : "=r"(v) : "l"(p) : "memory"); return v; }
__device__ __forceinline__ uint2 ld_mod(const uint2* p) {
    uint64_t v;
    asm volatile("ld.relaxed.gpu.global.b64 %0, [%1];" : "=l"(v) : "l"(p) : "memory");
    return make_uint2((uint32_t)v, (uint32_t)(v >> 32));
}
__device__ __forceinline__ float silu(float x) {
    float e, r;
    asm("ex2.approx.ftz.f32 %0, %1;" : "=f"(e) : "f"(x * -1.4426950408889634f));
    asm("rcp.approx.ftz.f32 %0, %1;" : "=f"(r) : "f"(1.f + e));
    return x * r;
}
__device__ __forceinline__ float gelu2(float h) {
    float u = h * fmaf(h * h, 8.f * 0.0356774081f, 2.f * 0.7978845608f);
    float th;
    asm("tanh.approx.f32 %0, %1;" : "=f"(th) : "f"(u));
    return fmaf(h, th, h);
}
__device__ __forceinline__ float gelu2r(float a, float2 k) {
    float th;
    asm("tanh.approx.f32 %0, %1;" : "=f"(th) : "f"(a * fmaf(a * a, k.x, k.y)));
    return fmaf(a, th, a);
}

__device__ __forceinline__ void conv_channel(float (&d)[64], uint32_t pa, uint64_t db) {
    asm volatile("{\n.reg .b32 a0, a1, a2, a3, b0, b1, b2, b3, t0, t1;\n.reg .b64 d;\nld.shared.b32 a0, [%64];\nld.shared.b32 a1, [%64+128];\nld.shared.b32 a2, [%64+-128];\nmov.b32 a3, a0;\n"
        "ld.shared.b32 t0, [%64+256];\nld.shared.b32 t1, [%64+384];\nadd.s64 d, %65, 0;\nwgmma.fence.sync.aligned;\nwgmma.mma_async.sync.aligned.m64n128k16.f32.bf16.bf16 {%0, %1, %2, %3, %4, %5, %6, %7, %8, %9, %10, %11, %12, %13, %14, %15, %16, %17, %18, %19, %20, %21, %22, %23, %24, %25, %26, %27, %28, %29, %30, %31, %32, %33, %34, %35, %36, %37, %38, %39, %40, %41, %42, %43, %44, %45, %46, %47, %48, %49, %50, %51, %52, %53, %54, %55, %56, %57, %58, %59, %60, %61, %62, %63}, {a0, a1, a2, a3}, d, 0, 1, 1, 0;\nwgmma.commit_group.sync.aligned;\nwgmma.wait_group.sync.aligned 1;\nmov.b32 b2, a1;\nmov.b32 b0, t0;\nmov.b32 b3, t0;\nmov.b32 b1, t1;\n"
        "ld.shared.b32 t0, [%64+512];\nld.shared.b32 t1, [%64+640];\nadd.s64 d, %65, 8;\nwgmma.fence.sync.aligned;\nwgmma.mma_async.sync.aligned.m64n128k16.f32.bf16.bf16 {%0, %1, %2, %3, %4, %5, %6, %7, %8, %9, %10, %11, %12, %13, %14, %15, %16, %17, %18, %19, %20, %21, %22, %23, %24, %25, %26, %27, %28, %29, %30, %31, %32, %33, %34, %35, %36, %37, %38, %39, %40, %41, %42, %43, %44, %45, %46, %47, %48, %49, %50, %51, %52, %53, %54, %55, %56, %57, %58, %59, %60, %61, %62, %63}, {b0, b1, b2, b3}, d, 1, 1, 1, 0;\nwgmma.commit_group.sync.aligned;\nwgmma.wait_group.sync.aligned 1;\nmov.b32 a2, b1;\nmov.b32 a0, t0;\nmov.b32 a3, t0;\nmov.b32 a1, t1;\n"
        "ld.shared.b32 t0, [%64+768];\nld.shared.b32 t1, [%64+896];\nadd.s64 d, %65, 16;\nwgmma.fence.sync.aligned;\nwgmma.mma_async.sync.aligned.m64n128k16.f32.bf16.bf16 {%0, %1, %2, %3, %4, %5, %6, %7, %8, %9, %10, %11, %12, %13, %14, %15, %16, %17, %18, %19, %20, %21, %22, %23, %24, %25, %26, %27, %28, %29, %30, %31, %32, %33, %34, %35, %36, %37, %38, %39, %40, %41, %42, %43, %44, %45, %46, %47, %48, %49, %50, %51, %52, %53, %54, %55, %56, %57, %58, %59, %60, %61, %62, %63}, {a0, a1, a2, a3}, d, 1, 1, 1, 0;\nwgmma.commit_group.sync.aligned;\nwgmma.wait_group.sync.aligned 1;\nmov.b32 b2, a1;\nmov.b32 b0, t0;\nmov.b32 b3, t0;\nmov.b32 b1, t1;\n"
        "ld.shared.b32 t0, [%64+1024];\nld.shared.b32 t1, [%64+1152];\nadd.s64 d, %65, 24;\nwgmma.fence.sync.aligned;\nwgmma.mma_async.sync.aligned.m64n128k16.f32.bf16.bf16 {%0, %1, %2, %3, %4, %5, %6, %7, %8, %9, %10, %11, %12, %13, %14, %15, %16, %17, %18, %19, %20, %21, %22, %23, %24, %25, %26, %27, %28, %29, %30, %31, %32, %33, %34, %35, %36, %37, %38, %39, %40, %41, %42, %43, %44, %45, %46, %47, %48, %49, %50, %51, %52, %53, %54, %55, %56, %57, %58, %59, %60, %61, %62, %63}, {b0, b1, b2, b3}, d, 1, 1, 1, 0;\nwgmma.commit_group.sync.aligned;\nwgmma.wait_group.sync.aligned 1;\nmov.b32 a2, b1;\nmov.b32 a0, t0;\nmov.b32 a3, t0;\nmov.b32 a1, t1;\n"
        "ld.shared.b32 t0, [%64+1280];\nld.shared.b32 t1, [%64+1408];\nadd.s64 d, %65, 32;\nwgmma.fence.sync.aligned;\nwgmma.mma_async.sync.aligned.m64n128k16.f32.bf16.bf16 {%0, %1, %2, %3, %4, %5, %6, %7, %8, %9, %10, %11, %12, %13, %14, %15, %16, %17, %18, %19, %20, %21, %22, %23, %24, %25, %26, %27, %28, %29, %30, %31, %32, %33, %34, %35, %36, %37, %38, %39, %40, %41, %42, %43, %44, %45, %46, %47, %48, %49, %50, %51, %52, %53, %54, %55, %56, %57, %58, %59, %60, %61, %62, %63}, {a0, a1, a2, a3}, d, 1, 1, 1, 0;\nwgmma.commit_group.sync.aligned;\nwgmma.wait_group.sync.aligned 1;\nmov.b32 b2, a1;\nmov.b32 b0, t0;\nmov.b32 b3, t0;\nmov.b32 b1, t1;\n"
        "ld.shared.b32 t0, [%64+1536];\nld.shared.b32 t1, [%64+1664];\nadd.s64 d, %65, 40;\nwgmma.fence.sync.aligned;\nwgmma.mma_async.sync.aligned.m64n128k16.f32.bf16.bf16 {%0, %1, %2, %3, %4, %5, %6, %7, %8, %9, %10, %11, %12, %13, %14, %15, %16, %17, %18, %19, %20, %21, %22, %23, %24, %25, %26, %27, %28, %29, %30, %31, %32, %33, %34, %35, %36, %37, %38, %39, %40, %41, %42, %43, %44, %45, %46, %47, %48, %49, %50, %51, %52, %53, %54, %55, %56, %57, %58, %59, %60, %61, %62, %63}, {b0, b1, b2, b3}, d, 1, 1, 1, 0;\nwgmma.commit_group.sync.aligned;\nwgmma.wait_group.sync.aligned 1;\nmov.b32 a2, b1;\nmov.b32 a0, t0;\nmov.b32 a3, t0;\nmov.b32 a1, t1;\n"
        "ld.shared.b32 t0, [%64+1792];\nld.shared.b32 t1, [%64+1920];\nadd.s64 d, %65, 48;\nwgmma.fence.sync.aligned;\nwgmma.mma_async.sync.aligned.m64n128k16.f32.bf16.bf16 {%0, %1, %2, %3, %4, %5, %6, %7, %8, %9, %10, %11, %12, %13, %14, %15, %16, %17, %18, %19, %20, %21, %22, %23, %24, %25, %26, %27, %28, %29, %30, %31, %32, %33, %34, %35, %36, %37, %38, %39, %40, %41, %42, %43, %44, %45, %46, %47, %48, %49, %50, %51, %52, %53, %54, %55, %56, %57, %58, %59, %60, %61, %62, %63}, {a0, a1, a2, a3}, d, 1, 1, 1, 0;\nwgmma.commit_group.sync.aligned;\nwgmma.wait_group.sync.aligned 1;\nmov.b32 b2, a1;\nmov.b32 b0, t0;\nmov.b32 b3, t0;\nmov.b32 b1, t1;\n"
        "ld.shared.b32 t0, [%64+2048];\nld.shared.b32 t1, [%64+2176];\nadd.s64 d, %65, 56;\nwgmma.fence.sync.aligned;\nwgmma.mma_async.sync.aligned.m64n128k16.f32.bf16.bf16 {%0, %1, %2, %3, %4, %5, %6, %7, %8, %9, %10, %11, %12, %13, %14, %15, %16, %17, %18, %19, %20, %21, %22, %23, %24, %25, %26, %27, %28, %29, %30, %31, %32, %33, %34, %35, %36, %37, %38, %39, %40, %41, %42, %43, %44, %45, %46, %47, %48, %49, %50, %51, %52, %53, %54, %55, %56, %57, %58, %59, %60, %61, %62, %63}, {b0, b1, b2, b3}, d, 1, 1, 1, 0;\nwgmma.commit_group.sync.aligned;\nwgmma.wait_group.sync.aligned 1;\nmov.b32 a2, b1;\nmov.b32 a0, t0;\nmov.b32 a3, t0;\nmov.b32 a1, t1;\n"
        "ld.shared.b32 t0, [%64+2304];\nld.shared.b32 t1, [%64+2432];\nadd.s64 d, %65, 64;\nwgmma.fence.sync.aligned;\nwgmma.mma_async.sync.aligned.m64n96k16.f32.bf16.bf16 {%0, %1, %2, %3, %4, %5, %6, %7, %8, %9, %10, %11, %12, %13, %14, %15, %16, %17, %18, %19, %20, %21, %22, %23, %24, %25, %26, %27, %28, %29, %30, %31, %32, %33, %34, %35, %36, %37, %38, %39, %40, %41, %42, %43, %44, %45, %46, %47}, {a0, a1, a2, a3}, d, 1, 1, 1, 0;\nwgmma.commit_group.sync.aligned;\nwgmma.wait_group.sync.aligned 1;\nmov.b32 b2, a1;\nmov.b32 b0, t0;\nmov.b32 b3, t0;\nmov.b32 b1, t1;\n"
        "ld.shared.b32 t0, [%64+2560];\nld.shared.b32 t1, [%64+2688];\nadd.s64 d, %65, 72;\nwgmma.fence.sync.aligned;\nwgmma.mma_async.sync.aligned.m64n96k16.f32.bf16.bf16 {%0, %1, %2, %3, %4, %5, %6, %7, %8, %9, %10, %11, %12, %13, %14, %15, %16, %17, %18, %19, %20, %21, %22, %23, %24, %25, %26, %27, %28, %29, %30, %31, %32, %33, %34, %35, %36, %37, %38, %39, %40, %41, %42, %43, %44, %45, %46, %47}, {b0, b1, b2, b3}, d, 1, 1, 1, 0;\nwgmma.commit_group.sync.aligned;\nwgmma.wait_group.sync.aligned 1;\nmov.b32 a2, b1;\nmov.b32 a0, t0;\nmov.b32 a3, t0;\nmov.b32 a1, t1;\n"
        "ld.shared.b32 t0, [%64+2816];\nld.shared.b32 t1, [%64+2944];\nadd.s64 d, %65, 80;\nwgmma.fence.sync.aligned;\nwgmma.mma_async.sync.aligned.m64n88k16.f32.bf16.bf16 {%0, %1, %2, %3, %4, %5, %6, %7, %8, %9, %10, %11, %12, %13, %14, %15, %16, %17, %18, %19, %20, %21, %22, %23, %24, %25, %26, %27, %28, %29, %30, %31, %32, %33, %34, %35, %36, %37, %38, %39, %40, %41, %42, %43}, {a0, a1, a2, a3}, d, 1, 1, 1, 0;\nwgmma.commit_group.sync.aligned;\nwgmma.wait_group.sync.aligned 1;\nmov.b32 b2, a1;\nmov.b32 b0, t0;\nmov.b32 b3, t0;\nmov.b32 b1, t1;\n"
        "ld.shared.b32 t0, [%64+3072];\nld.shared.b32 t1, [%64+3200];\nadd.s64 d, %65, 88;\nwgmma.fence.sync.aligned;\nwgmma.mma_async.sync.aligned.m64n88k16.f32.bf16.bf16 {%0, %1, %2, %3, %4, %5, %6, %7, %8, %9, %10, %11, %12, %13, %14, %15, %16, %17, %18, %19, %20, %21, %22, %23, %24, %25, %26, %27, %28, %29, %30, %31, %32, %33, %34, %35, %36, %37, %38, %39, %40, %41, %42, %43}, {b0, b1, b2, b3}, d, 1, 1, 1, 0;\nwgmma.commit_group.sync.aligned;\nwgmma.wait_group.sync.aligned 1;\nmov.b32 a2, b1;\nmov.b32 a0, t0;\nmov.b32 a3, t0;\nmov.b32 a1, t1;\n"
        "ld.shared.b32 t0, [%64+3328];\nld.shared.b32 t1, [%64+3456];\nadd.s64 d, %65, 96;\nwgmma.fence.sync.aligned;\nwgmma.mma_async.sync.aligned.m64n80k16.f32.bf16.bf16 {%0, %1, %2, %3, %4, %5, %6, %7, %8, %9, %10, %11, %12, %13, %14, %15, %16, %17, %18, %19, %20, %21, %22, %23, %24, %25, %26, %27, %28, %29, %30, %31, %32, %33, %34, %35, %36, %37, %38, %39}, {a0, a1, a2, a3}, d, 1, 1, 1, 0;\nwgmma.commit_group.sync.aligned;\nwgmma.wait_group.sync.aligned 1;\nmov.b32 b2, a1;\nmov.b32 b0, t0;\nmov.b32 b3, t0;\nmov.b32 b1, t1;\n"
        "ld.shared.b32 t0, [%64+3584];\nld.shared.b32 t1, [%64+3712];\nadd.s64 d, %65, 104;\nwgmma.fence.sync.aligned;\nwgmma.mma_async.sync.aligned.m64n80k16.f32.bf16.bf16 {%0, %1, %2, %3, %4, %5, %6, %7, %8, %9, %10, %11, %12, %13, %14, %15, %16, %17, %18, %19, %20, %21, %22, %23, %24, %25, %26, %27, %28, %29, %30, %31, %32, %33, %34, %35, %36, %37, %38, %39}, {b0, b1, b2, b3}, d, 1, 1, 1, 0;\nwgmma.commit_group.sync.aligned;\nwgmma.wait_group.sync.aligned 1;\nmov.b32 a2, b1;\nmov.b32 a0, t0;\nmov.b32 a3, t0;\nmov.b32 a1, t1;\n"
        "ld.shared.b32 t0, [%64+3840];\nld.shared.b32 t1, [%64+3968];\nadd.s64 d, %65, 112;\nwgmma.fence.sync.aligned;\nwgmma.mma_async.sync.aligned.m64n72k16.f32.bf16.bf16 {%0, %1, %2, %3, %4, %5, %6, %7, %8, %9, %10, %11, %12, %13, %14, %15, %16, %17, %18, %19, %20, %21, %22, %23, %24, %25, %26, %27, %28, %29, %30, %31, %32, %33, %34, %35}, {a0, a1, a2, a3}, d, 1, 1, 1, 0;\nwgmma.commit_group.sync.aligned;\nwgmma.wait_group.sync.aligned 1;\nmov.b32 b2, a1;\nmov.b32 b0, t0;\nmov.b32 b3, t0;\nmov.b32 b1, t1;\n"
        "ld.shared.b32 t0, [%64+4096];\nld.shared.b32 t1, [%64+4224];\nadd.s64 d, %65, 120;\nwgmma.fence.sync.aligned;\nwgmma.mma_async.sync.aligned.m64n72k16.f32.bf16.bf16 {%0, %1, %2, %3, %4, %5, %6, %7, %8, %9, %10, %11, %12, %13, %14, %15, %16, %17, %18, %19, %20, %21, %22, %23, %24, %25, %26, %27, %28, %29, %30, %31, %32, %33, %34, %35}, {b0, b1, b2, b3}, d, 1, 1, 1, 0;\nwgmma.commit_group.sync.aligned;\nwgmma.wait_group.sync.aligned 1;\nmov.b32 a2, b1;\nmov.b32 a0, t0;\nmov.b32 a3, t0;\nmov.b32 a1, t1;\n"
        "ld.shared.b32 t0, [%64+4352];\nld.shared.b32 t1, [%64+4480];\nadd.s64 d, %65, 128;\nwgmma.fence.sync.aligned;\nwgmma.mma_async.sync.aligned.m64n64k16.f32.bf16.bf16 {%0, %1, %2, %3, %4, %5, %6, %7, %8, %9, %10, %11, %12, %13, %14, %15, %16, %17, %18, %19, %20, %21, %22, %23, %24, %25, %26, %27, %28, %29, %30, %31}, {a0, a1, a2, a3}, d, 1, 1, 1, 0;\nwgmma.commit_group.sync.aligned;\nwgmma.wait_group.sync.aligned 1;\nmov.b32 b2, a1;\nmov.b32 b0, t0;\nmov.b32 b3, t0;\nmov.b32 b1, t1;\n"
        "ld.shared.b32 t0, [%64+4608];\nld.shared.b32 t1, [%64+4736];\nadd.s64 d, %65, 136;\nwgmma.fence.sync.aligned;\nwgmma.mma_async.sync.aligned.m64n64k16.f32.bf16.bf16 {%0, %1, %2, %3, %4, %5, %6, %7, %8, %9, %10, %11, %12, %13, %14, %15, %16, %17, %18, %19, %20, %21, %22, %23, %24, %25, %26, %27, %28, %29, %30, %31}, {b0, b1, b2, b3}, d, 1, 1, 1, 0;\nwgmma.commit_group.sync.aligned;\nwgmma.wait_group.sync.aligned 1;\nmov.b32 a2, b1;\nmov.b32 a0, t0;\nmov.b32 a3, t0;\nmov.b32 a1, t1;\n"
        "ld.shared.b32 t0, [%64+4864];\nld.shared.b32 t1, [%64+4992];\nadd.s64 d, %65, 144;\nwgmma.fence.sync.aligned;\nwgmma.mma_async.sync.aligned.m64n56k16.f32.bf16.bf16 {%0, %1, %2, %3, %4, %5, %6, %7, %8, %9, %10, %11, %12, %13, %14, %15, %16, %17, %18, %19, %20, %21, %22, %23, %24, %25, %26, %27}, {a0, a1, a2, a3}, d, 1, 1, 1, 0;\nwgmma.commit_group.sync.aligned;\nwgmma.wait_group.sync.aligned 1;\nmov.b32 b2, a1;\nmov.b32 b0, t0;\nmov.b32 b3, t0;\nmov.b32 b1, t1;\n"
        "ld.shared.b32 t0, [%64+5120];\nld.shared.b32 t1, [%64+5248];\nadd.s64 d, %65, 152;\nwgmma.fence.sync.aligned;\nwgmma.mma_async.sync.aligned.m64n56k16.f32.bf16.bf16 {%0, %1, %2, %3, %4, %5, %6, %7, %8, %9, %10, %11, %12, %13, %14, %15, %16, %17, %18, %19, %20, %21, %22, %23, %24, %25, %26, %27}, {b0, b1, b2, b3}, d, 1, 1, 1, 0;\nwgmma.commit_group.sync.aligned;\nwgmma.wait_group.sync.aligned 1;\nmov.b32 a2, b1;\nmov.b32 a0, t0;\nmov.b32 a3, t0;\nmov.b32 a1, t1;\n"
        "ld.shared.b32 t0, [%64+5376];\nld.shared.b32 t1, [%64+5504];\nadd.s64 d, %65, 160;\nwgmma.fence.sync.aligned;\nwgmma.mma_async.sync.aligned.m64n48k16.f32.bf16.bf16 {%0, %1, %2, %3, %4, %5, %6, %7, %8, %9, %10, %11, %12, %13, %14, %15, %16, %17, %18, %19, %20, %21, %22, %23}, {a0, a1, a2, a3}, d, 1, 1, 1, 0;\nwgmma.commit_group.sync.aligned;\nwgmma.wait_group.sync.aligned 1;\nmov.b32 b2, a1;\nmov.b32 b0, t0;\nmov.b32 b3, t0;\nmov.b32 b1, t1;\n"
        "ld.shared.b32 t0, [%64+5632];\nld.shared.b32 t1, [%64+5760];\nadd.s64 d, %65, 168;\nwgmma.fence.sync.aligned;\nwgmma.mma_async.sync.aligned.m64n48k16.f32.bf16.bf16 {%0, %1, %2, %3, %4, %5, %6, %7, %8, %9, %10, %11, %12, %13, %14, %15, %16, %17, %18, %19, %20, %21, %22, %23}, {b0, b1, b2, b3}, d, 1, 1, 1, 0;\nwgmma.commit_group.sync.aligned;\nwgmma.wait_group.sync.aligned 1;\nmov.b32 a2, b1;\nmov.b32 a0, t0;\nmov.b32 a3, t0;\nmov.b32 a1, t1;\n"
        "ld.shared.b32 t0, [%64+5888];\nld.shared.b32 t1, [%64+6016];\nadd.s64 d, %65, 176;\nwgmma.fence.sync.aligned;\nwgmma.mma_async.sync.aligned.m64n40k16.f32.bf16.bf16 {%0, %1, %2, %3, %4, %5, %6, %7, %8, %9, %10, %11, %12, %13, %14, %15, %16, %17, %18, %19}, {a0, a1, a2, a3}, d, 1, 1, 1, 0;\nwgmma.commit_group.sync.aligned;\nwgmma.wait_group.sync.aligned 1;\nmov.b32 b2, a1;\nmov.b32 b0, t0;\nmov.b32 b3, t0;\nmov.b32 b1, t1;\n"
        "ld.shared.b32 t0, [%64+6144];\nld.shared.b32 t1, [%64+6272];\nadd.s64 d, %65, 184;\nwgmma.fence.sync.aligned;\nwgmma.mma_async.sync.aligned.m64n40k16.f32.bf16.bf16 {%0, %1, %2, %3, %4, %5, %6, %7, %8, %9, %10, %11, %12, %13, %14, %15, %16, %17, %18, %19}, {b0, b1, b2, b3}, d, 1, 1, 1, 0;\nwgmma.commit_group.sync.aligned;\nwgmma.wait_group.sync.aligned 1;\nmov.b32 a2, b1;\nmov.b32 a0, t0;\nmov.b32 a3, t0;\nmov.b32 a1, t1;\n"
        "ld.shared.b32 t0, [%64+6400];\nld.shared.b32 t1, [%64+6528];\nadd.s64 d, %65, 192;\nwgmma.fence.sync.aligned;\nwgmma.mma_async.sync.aligned.m64n32k16.f32.bf16.bf16 {%0, %1, %2, %3, %4, %5, %6, %7, %8, %9, %10, %11, %12, %13, %14, %15}, {a0, a1, a2, a3}, d, 1, 1, 1, 0;\nwgmma.commit_group.sync.aligned;\nwgmma.wait_group.sync.aligned 1;\nmov.b32 b2, a1;\nmov.b32 b0, t0;\nmov.b32 b3, t0;\nmov.b32 b1, t1;\n"
        "ld.shared.b32 t0, [%64+6656];\nld.shared.b32 t1, [%64+6784];\nadd.s64 d, %65, 200;\nwgmma.fence.sync.aligned;\nwgmma.mma_async.sync.aligned.m64n32k16.f32.bf16.bf16 {%0, %1, %2, %3, %4, %5, %6, %7, %8, %9, %10, %11, %12, %13, %14, %15}, {b0, b1, b2, b3}, d, 1, 1, 1, 0;\nwgmma.commit_group.sync.aligned;\nwgmma.wait_group.sync.aligned 1;\nmov.b32 a2, b1;\nmov.b32 a0, t0;\nmov.b32 a3, t0;\nmov.b32 a1, t1;\n"
        "ld.shared.b32 t0, [%64+6912];\nld.shared.b32 t1, [%64+7040];\nadd.s64 d, %65, 208;\nwgmma.fence.sync.aligned;\nwgmma.mma_async.sync.aligned.m64n24k16.f32.bf16.bf16 {%0, %1, %2, %3, %4, %5, %6, %7, %8, %9, %10, %11}, {a0, a1, a2, a3}, d, 1, 1, 1, 0;\nwgmma.commit_group.sync.aligned;\nwgmma.wait_group.sync.aligned 1;\nmov.b32 b2, a1;\nmov.b32 b0, t0;\nmov.b32 b3, t0;\nmov.b32 b1, t1;\n"
        "ld.shared.b32 t0, [%64+7168];\nld.shared.b32 t1, [%64+7296];\nadd.s64 d, %65, 216;\nwgmma.fence.sync.aligned;\nwgmma.mma_async.sync.aligned.m64n24k16.f32.bf16.bf16 {%0, %1, %2, %3, %4, %5, %6, %7, %8, %9, %10, %11}, {b0, b1, b2, b3}, d, 1, 1, 1, 0;\nwgmma.commit_group.sync.aligned;\nwgmma.wait_group.sync.aligned 1;\nmov.b32 a2, b1;\nmov.b32 a0, t0;\nmov.b32 a3, t0;\nmov.b32 a1, t1;\n"
        "ld.shared.b32 t0, [%64+7424];\nld.shared.b32 t1, [%64+7552];\nadd.s64 d, %65, 224;\nwgmma.fence.sync.aligned;\nwgmma.mma_async.sync.aligned.m64n16k16.f32.bf16.bf16 {%0, %1, %2, %3, %4, %5, %6, %7}, {a0, a1, a2, a3}, d, 1, 1, 1, 0;\nwgmma.commit_group.sync.aligned;\nwgmma.wait_group.sync.aligned 1;\nmov.b32 b2, a1;\nmov.b32 b0, t0;\nmov.b32 b3, t0;\nmov.b32 b1, t1;\n"
        "ld.shared.b32 t0, [%64+7680];\nld.shared.b32 t1, [%64+7808];\nadd.s64 d, %65, 232;\nwgmma.fence.sync.aligned;\nwgmma.mma_async.sync.aligned.m64n16k16.f32.bf16.bf16 {%0, %1, %2, %3, %4, %5, %6, %7}, {b0, b1, b2, b3}, d, 1, 1, 1, 0;\nwgmma.commit_group.sync.aligned;\nwgmma.wait_group.sync.aligned 1;\nmov.b32 a2, b1;\nmov.b32 a0, t0;\nmov.b32 a3, t0;\nmov.b32 a1, t1;\n"
        "ld.shared.b32 t0, [%64+7936];\nld.shared.b32 t1, [%64+8064];\nadd.s64 d, %65, 240;\nwgmma.fence.sync.aligned;\nwgmma.mma_async.sync.aligned.m64n8k16.f32.bf16.bf16 {%0, %1, %2, %3}, {a0, a1, a2, a3}, d, 1, 1, 1, 0;\nwgmma.commit_group.sync.aligned;\nwgmma.wait_group.sync.aligned 1;\nmov.b32 b2, a1;\nmov.b32 b0, t0;\nmov.b32 b3, t0;\nmov.b32 b1, t1;\n"
        "add.s64 d, %65, 248;\nwgmma.fence.sync.aligned;\nwgmma.mma_async.sync.aligned.m64n8k16.f32.bf16.bf16 {%0, %1, %2, %3}, {b0, b1, b2, b3}, d, 1, 1, 1, 0;\nwgmma.commit_group.sync.aligned;\nwgmma.wait_group.sync.aligned 0;\n"
        "}" : "+f"(d[0]), "+f"(d[1]), "+f"(d[2]), "+f"(d[3]), "+f"(d[4]), "+f"(d[5]), "+f"(d[6]), "+f"(d[7]), "+f"(d[8]), "+f"(d[9]), "+f"(d[10]), "+f"(d[11]), "+f"(d[12]), "+f"(d[13]), "+f"(d[14]), "+f"(d[15]), "+f"(d[16]), "+f"(d[17]), "+f"(d[18]), "+f"(d[19]), "+f"(d[20]), "+f"(d[21]), "+f"(d[22]), "+f"(d[23]), "+f"(d[24]), "+f"(d[25]), "+f"(d[26]), "+f"(d[27]), "+f"(d[28]), "+f"(d[29]), "+f"(d[30]), "+f"(d[31]), "+f"(d[32]), "+f"(d[33]), "+f"(d[34]), "+f"(d[35]), "+f"(d[36]), "+f"(d[37]), "+f"(d[38]), "+f"(d[39]), "+f"(d[40]), "+f"(d[41]), "+f"(d[42]), "+f"(d[43]), "+f"(d[44]), "+f"(d[45]), "+f"(d[46]), "+f"(d[47]), "+f"(d[48]), "+f"(d[49]), "+f"(d[50]), "+f"(d[51]), "+f"(d[52]), "+f"(d[53]), "+f"(d[54]), "+f"(d[55]), "+f"(d[56]), "+f"(d[57]), "+f"(d[58]), "+f"(d[59]), "+f"(d[60]), "+f"(d[61]), "+f"(d[62]), "+f"(d[63]) : "r"(pa), "l"(db) : "memory");
}
__device__ __forceinline__ void wgmma_rs80(float (&d)[40], uint32_t a0, uint32_t a1, uint32_t a2, uint32_t a3, uint64_t db, int sc) {
    asm volatile("{\n.reg .pred p;\nsetp.ne.b32 p, %45, 0;\n"
        "wgmma.mma_async.sync.aligned.m64n80k16.f32.bf16.bf16 {%0, %1, %2, %3, %4, %5, %6, %7, %8, %9, %10, %11, %12, %13, %14, %15, %16, %17, %18, %19, %20, %21, %22, %23, %24, %25, %26, %27, %28, %29, %30, %31, %32, %33, %34, %35, %36, %37, %38, %39}, {%40, %41, %42, %43}, %44, p, 1, 1, 1;\n}\n"
        : "+f"(d[0]), "+f"(d[1]), "+f"(d[2]), "+f"(d[3]), "+f"(d[4]), "+f"(d[5]), "+f"(d[6]), "+f"(d[7]), "+f"(d[8]), "+f"(d[9]), "+f"(d[10]), "+f"(d[11]), "+f"(d[12]), "+f"(d[13]), "+f"(d[14]), "+f"(d[15]), "+f"(d[16]), "+f"(d[17]), "+f"(d[18]), "+f"(d[19]), "+f"(d[20]), "+f"(d[21]), "+f"(d[22]), "+f"(d[23]), "+f"(d[24]), "+f"(d[25]), "+f"(d[26]), "+f"(d[27]), "+f"(d[28]), "+f"(d[29]), "+f"(d[30]), "+f"(d[31]), "+f"(d[32]), "+f"(d[33]), "+f"(d[34]), "+f"(d[35]), "+f"(d[36]), "+f"(d[37]), "+f"(d[38]), "+f"(d[39]) : "r"(a0), "r"(a1), "r"(a2), "r"(a3), "l"(db), "r"(sc));
}
__device__ __forceinline__ void wgmma_ss80(float (&d)[40], uint64_t da, uint64_t db, int sc) {
    asm volatile("{\n.reg .pred p;\nsetp.ne.b32 p, %42, 0;\n"
        "wgmma.mma_async.sync.aligned.m64n80k16.f32.bf16.bf16 {%0, %1, %2, %3, %4, %5, %6, %7, %8, %9, %10, %11, %12, %13, %14, %15, %16, %17, %18, %19, %20, %21, %22, %23, %24, %25, %26, %27, %28, %29, %30, %31, %32, %33, %34, %35, %36, %37, %38, %39}, %40, %41, p, 1, 1, 0, 1;\n}\n"
        : "+f"(d[0]), "+f"(d[1]), "+f"(d[2]), "+f"(d[3]), "+f"(d[4]), "+f"(d[5]), "+f"(d[6]), "+f"(d[7]), "+f"(d[8]), "+f"(d[9]), "+f"(d[10]), "+f"(d[11]), "+f"(d[12]), "+f"(d[13]), "+f"(d[14]), "+f"(d[15]), "+f"(d[16]), "+f"(d[17]), "+f"(d[18]), "+f"(d[19]), "+f"(d[20]), "+f"(d[21]), "+f"(d[22]), "+f"(d[23]), "+f"(d[24]), "+f"(d[25]), "+f"(d[26]), "+f"(d[27]), "+f"(d[28]), "+f"(d[29]), "+f"(d[30]), "+f"(d[31]), "+f"(d[32]), "+f"(d[33]), "+f"(d[34]), "+f"(d[35]), "+f"(d[36]), "+f"(d[37]), "+f"(d[38]), "+f"(d[39]) : "l"(da), "l"(db), "r"(sc));
}
__device__ __forceinline__ void wgmma_ss80t(float (&d)[40], uint64_t da, uint64_t db, int sc) {
    asm volatile("{\n.reg .pred p;\nsetp.ne.b32 p, %42, 0;\n"
        "wgmma.mma_async.sync.aligned.m64n80k16.f32.bf16.bf16 {%0, %1, %2, %3, %4, %5, %6, %7, %8, %9, %10, %11, %12, %13, %14, %15, %16, %17, %18, %19, %20, %21, %22, %23, %24, %25, %26, %27, %28, %29, %30, %31, %32, %33, %34, %35, %36, %37, %38, %39}, %40, %41, p, 1, 1, 1, 1;\n}\n"
        : "+f"(d[0]), "+f"(d[1]), "+f"(d[2]), "+f"(d[3]), "+f"(d[4]), "+f"(d[5]), "+f"(d[6]), "+f"(d[7]), "+f"(d[8]), "+f"(d[9]), "+f"(d[10]), "+f"(d[11]), "+f"(d[12]), "+f"(d[13]), "+f"(d[14]), "+f"(d[15]), "+f"(d[16]), "+f"(d[17]), "+f"(d[18]), "+f"(d[19]), "+f"(d[20]), "+f"(d[21]), "+f"(d[22]), "+f"(d[23]), "+f"(d[24]), "+f"(d[25]), "+f"(d[26]), "+f"(d[27]), "+f"(d[28]), "+f"(d[29]), "+f"(d[30]), "+f"(d[31]), "+f"(d[32]), "+f"(d[33]), "+f"(d[34]), "+f"(d[35]), "+f"(d[36]), "+f"(d[37]), "+f"(d[38]), "+f"(d[39]) : "l"(da), "l"(db), "r"(sc));
}
__device__ __forceinline__ void wgmma_ss8_ta(float (&d)[4], uint64_t da, uint64_t db, int sc) {
    asm volatile("{\n.reg .pred p;\nsetp.ne.b32 p, %6, 0;\n"
        "wgmma.mma_async.sync.aligned.m64n8k16.f32.bf16.bf16 {%0, %1, %2, %3}, %4, %5, p, 1, 1, 1, 0;\n}\n"
        : "+f"(d[0]), "+f"(d[1]), "+f"(d[2]), "+f"(d[3]) : "l"(da), "l"(db), "r"(sc));
}
__device__ __forceinline__ void wgmma_rs8(float (&d)[4], uint32_t a0, uint32_t a1, uint32_t a2, uint32_t a3, uint64_t db, int sc) {
    asm volatile("{\n.reg .pred p;\nsetp.ne.b32 p, %9, 0;\n"
        "wgmma.mma_async.sync.aligned.m64n8k16.f32.bf16.bf16 {%0, %1, %2, %3}, {%4, %5, %6, %7}, %8, p, 1, 1, 0;\n}\n"
        : "+f"(d[0]), "+f"(d[1]), "+f"(d[2]), "+f"(d[3]) : "r"(a0), "r"(a1), "r"(a2), "r"(a3), "l"(db), "r"(sc));
}
__device__ __forceinline__ void wgmma_rs128(float (&d)[64], uint32_t a0, uint32_t a1, uint32_t a2, uint32_t a3, uint64_t db, int sc) {
    asm volatile("{\n.reg .pred p;\nsetp.ne.b32 p, %69, 0;\n"
        "wgmma.mma_async.sync.aligned.m64n128k16.f32.bf16.bf16 {%0, %1, %2, %3, %4, %5, %6, %7, %8, %9, %10, %11, %12, %13, %14, %15, %16, %17, %18, %19, %20, %21, %22, %23, %24, %25, %26, %27, %28, %29, %30, %31, %32, %33, %34, %35, %36, %37, %38, %39, %40, %41, %42, %43, %44, %45, %46, %47, %48, %49, %50, %51, %52, %53, %54, %55, %56, %57, %58, %59, %60, %61, %62, %63}, {%64, %65, %66, %67}, %68, p, 1, 1, 1;\n}\n"
        : "+f"(d[0]), "+f"(d[1]), "+f"(d[2]), "+f"(d[3]), "+f"(d[4]), "+f"(d[5]), "+f"(d[6]), "+f"(d[7]), "+f"(d[8]), "+f"(d[9]), "+f"(d[10]), "+f"(d[11]), "+f"(d[12]), "+f"(d[13]), "+f"(d[14]), "+f"(d[15]), "+f"(d[16]), "+f"(d[17]), "+f"(d[18]), "+f"(d[19]), "+f"(d[20]), "+f"(d[21]), "+f"(d[22]), "+f"(d[23]), "+f"(d[24]), "+f"(d[25]), "+f"(d[26]), "+f"(d[27]), "+f"(d[28]), "+f"(d[29]), "+f"(d[30]), "+f"(d[31]), "+f"(d[32]), "+f"(d[33]), "+f"(d[34]), "+f"(d[35]), "+f"(d[36]), "+f"(d[37]), "+f"(d[38]), "+f"(d[39]), "+f"(d[40]), "+f"(d[41]), "+f"(d[42]), "+f"(d[43]), "+f"(d[44]), "+f"(d[45]), "+f"(d[46]), "+f"(d[47]), "+f"(d[48]), "+f"(d[49]), "+f"(d[50]), "+f"(d[51]), "+f"(d[52]), "+f"(d[53]), "+f"(d[54]), "+f"(d[55]), "+f"(d[56]), "+f"(d[57]), "+f"(d[58]), "+f"(d[59]), "+f"(d[60]), "+f"(d[61]), "+f"(d[62]), "+f"(d[63]) : "r"(a0), "r"(a1), "r"(a2), "r"(a3), "l"(db), "r"(sc));
}
__device__ __forceinline__ void wgmma_rs88(float (&d)[44], uint32_t a0, uint32_t a1, uint32_t a2, uint32_t a3, uint64_t db, int sc) {
    asm volatile("{\n.reg .pred p;\nsetp.ne.b32 p, %49, 0;\n"
        "wgmma.mma_async.sync.aligned.m64n88k16.f32.bf16.bf16 {%0, %1, %2, %3, %4, %5, %6, %7, %8, %9, %10, %11, %12, %13, %14, %15, %16, %17, %18, %19, %20, %21, %22, %23, %24, %25, %26, %27, %28, %29, %30, %31, %32, %33, %34, %35, %36, %37, %38, %39, %40, %41, %42, %43}, {%44, %45, %46, %47}, %48, p, 1, 1, 1;\n}\n"
        : "+f"(d[0]), "+f"(d[1]), "+f"(d[2]), "+f"(d[3]), "+f"(d[4]), "+f"(d[5]), "+f"(d[6]), "+f"(d[7]), "+f"(d[8]), "+f"(d[9]), "+f"(d[10]), "+f"(d[11]), "+f"(d[12]), "+f"(d[13]), "+f"(d[14]), "+f"(d[15]), "+f"(d[16]), "+f"(d[17]), "+f"(d[18]), "+f"(d[19]), "+f"(d[20]), "+f"(d[21]), "+f"(d[22]), "+f"(d[23]), "+f"(d[24]), "+f"(d[25]), "+f"(d[26]), "+f"(d[27]), "+f"(d[28]), "+f"(d[29]), "+f"(d[30]), "+f"(d[31]), "+f"(d[32]), "+f"(d[33]), "+f"(d[34]), "+f"(d[35]), "+f"(d[36]), "+f"(d[37]), "+f"(d[38]), "+f"(d[39]), "+f"(d[40]), "+f"(d[41]), "+f"(d[42]), "+f"(d[43]) : "r"(a0), "r"(a1), "r"(a2), "r"(a3), "l"(db), "r"(sc));
}
__device__ __forceinline__ void wgmma_rs128k(float (&d)[64], uint32_t a0, uint32_t a1, uint32_t a2, uint32_t a3, uint64_t db, int sc) {
    asm volatile("{\n.reg .pred p;\nsetp.ne.b32 p, %69, 0;\n"
        "wgmma.mma_async.sync.aligned.m64n128k16.f32.bf16.bf16 {%0, %1, %2, %3, %4, %5, %6, %7, %8, %9, %10, %11, %12, %13, %14, %15, %16, %17, %18, %19, %20, %21, %22, %23, %24, %25, %26, %27, %28, %29, %30, %31, %32, %33, %34, %35, %36, %37, %38, %39, %40, %41, %42, %43, %44, %45, %46, %47, %48, %49, %50, %51, %52, %53, %54, %55, %56, %57, %58, %59, %60, %61, %62, %63}, {%64, %65, %66, %67}, %68, p, 1, 1, 0;\n}\n"
        : "+f"(d[0]), "+f"(d[1]), "+f"(d[2]), "+f"(d[3]), "+f"(d[4]), "+f"(d[5]), "+f"(d[6]), "+f"(d[7]), "+f"(d[8]), "+f"(d[9]), "+f"(d[10]), "+f"(d[11]), "+f"(d[12]), "+f"(d[13]), "+f"(d[14]), "+f"(d[15]), "+f"(d[16]), "+f"(d[17]), "+f"(d[18]), "+f"(d[19]), "+f"(d[20]), "+f"(d[21]), "+f"(d[22]), "+f"(d[23]), "+f"(d[24]), "+f"(d[25]), "+f"(d[26]), "+f"(d[27]), "+f"(d[28]), "+f"(d[29]), "+f"(d[30]), "+f"(d[31]), "+f"(d[32]), "+f"(d[33]), "+f"(d[34]), "+f"(d[35]), "+f"(d[36]), "+f"(d[37]), "+f"(d[38]), "+f"(d[39]), "+f"(d[40]), "+f"(d[41]), "+f"(d[42]), "+f"(d[43]), "+f"(d[44]), "+f"(d[45]), "+f"(d[46]), "+f"(d[47]), "+f"(d[48]), "+f"(d[49]), "+f"(d[50]), "+f"(d[51]), "+f"(d[52]), "+f"(d[53]), "+f"(d[54]), "+f"(d[55]), "+f"(d[56]), "+f"(d[57]), "+f"(d[58]), "+f"(d[59]), "+f"(d[60]), "+f"(d[61]), "+f"(d[62]), "+f"(d[63]) : "r"(a0), "r"(a1), "r"(a2), "r"(a3), "l"(db), "r"(sc));
}
__device__ __forceinline__ void wgmma_rs88k(float (&d)[44], uint32_t a0, uint32_t a1, uint32_t a2, uint32_t a3, uint64_t db, int sc) {
    asm volatile("{\n.reg .pred p;\nsetp.ne.b32 p, %49, 0;\n"
        "wgmma.mma_async.sync.aligned.m64n88k16.f32.bf16.bf16 {%0, %1, %2, %3, %4, %5, %6, %7, %8, %9, %10, %11, %12, %13, %14, %15, %16, %17, %18, %19, %20, %21, %22, %23, %24, %25, %26, %27, %28, %29, %30, %31, %32, %33, %34, %35, %36, %37, %38, %39, %40, %41, %42, %43}, {%44, %45, %46, %47}, %48, p, 1, 1, 0;\n}\n"
        : "+f"(d[0]), "+f"(d[1]), "+f"(d[2]), "+f"(d[3]), "+f"(d[4]), "+f"(d[5]), "+f"(d[6]), "+f"(d[7]), "+f"(d[8]), "+f"(d[9]), "+f"(d[10]), "+f"(d[11]), "+f"(d[12]), "+f"(d[13]), "+f"(d[14]), "+f"(d[15]), "+f"(d[16]), "+f"(d[17]), "+f"(d[18]), "+f"(d[19]), "+f"(d[20]), "+f"(d[21]), "+f"(d[22]), "+f"(d[23]), "+f"(d[24]), "+f"(d[25]), "+f"(d[26]), "+f"(d[27]), "+f"(d[28]), "+f"(d[29]), "+f"(d[30]), "+f"(d[31]), "+f"(d[32]), "+f"(d[33]), "+f"(d[34]), "+f"(d[35]), "+f"(d[36]), "+f"(d[37]), "+f"(d[38]), "+f"(d[39]), "+f"(d[40]), "+f"(d[41]), "+f"(d[42]), "+f"(d[43]) : "r"(a0), "r"(a1), "r"(a2), "r"(a3), "l"(db), "r"(sc));
}
__device__ __forceinline__ void wgmma_rs80k(float (&d)[40], uint32_t a0, uint32_t a1, uint32_t a2, uint32_t a3, uint64_t db, int sc) {
    asm volatile("{\n.reg .pred p;\nsetp.ne.b32 p, %45, 0;\n"
        "wgmma.mma_async.sync.aligned.m64n80k16.f32.bf16.bf16 {%0, %1, %2, %3, %4, %5, %6, %7, %8, %9, %10, %11, %12, %13, %14, %15, %16, %17, %18, %19, %20, %21, %22, %23, %24, %25, %26, %27, %28, %29, %30, %31, %32, %33, %34, %35, %36, %37, %38, %39}, {%40, %41, %42, %43}, %44, p, 1, 1, 0;\n}\n"
        : "+f"(d[0]), "+f"(d[1]), "+f"(d[2]), "+f"(d[3]), "+f"(d[4]), "+f"(d[5]), "+f"(d[6]), "+f"(d[7]), "+f"(d[8]), "+f"(d[9]), "+f"(d[10]), "+f"(d[11]), "+f"(d[12]), "+f"(d[13]), "+f"(d[14]), "+f"(d[15]), "+f"(d[16]), "+f"(d[17]), "+f"(d[18]), "+f"(d[19]), "+f"(d[20]), "+f"(d[21]), "+f"(d[22]), "+f"(d[23]), "+f"(d[24]), "+f"(d[25]), "+f"(d[26]), "+f"(d[27]), "+f"(d[28]), "+f"(d[29]), "+f"(d[30]), "+f"(d[31]), "+f"(d[32]), "+f"(d[33]), "+f"(d[34]), "+f"(d[35]), "+f"(d[36]), "+f"(d[37]), "+f"(d[38]), "+f"(d[39]) : "r"(a0), "r"(a1), "r"(a2), "r"(a3), "l"(db), "r"(sc));
}
__device__ __forceinline__ void wgmma_rs64(float (&d)[32], uint32_t a0, uint32_t a1, uint32_t a2, uint32_t a3, uint64_t db, int sc) {
    asm volatile("{\n.reg .pred p;\nsetp.ne.b32 p, %37, 0;\n"
        "wgmma.mma_async.sync.aligned.m64n64k16.f32.bf16.bf16 {%0, %1, %2, %3, %4, %5, %6, %7, %8, %9, %10, %11, %12, %13, %14, %15, %16, %17, %18, %19, %20, %21, %22, %23, %24, %25, %26, %27, %28, %29, %30, %31}, {%32, %33, %34, %35}, %36, p, 1, 1, 1;\n}\n"
        : "+f"(d[0]), "+f"(d[1]), "+f"(d[2]), "+f"(d[3]), "+f"(d[4]), "+f"(d[5]), "+f"(d[6]), "+f"(d[7]), "+f"(d[8]), "+f"(d[9]), "+f"(d[10]), "+f"(d[11]), "+f"(d[12]), "+f"(d[13]), "+f"(d[14]), "+f"(d[15]), "+f"(d[16]), "+f"(d[17]), "+f"(d[18]), "+f"(d[19]), "+f"(d[20]), "+f"(d[21]), "+f"(d[22]), "+f"(d[23]), "+f"(d[24]), "+f"(d[25]), "+f"(d[26]), "+f"(d[27]), "+f"(d[28]), "+f"(d[29]), "+f"(d[30]), "+f"(d[31]) : "r"(a0), "r"(a1), "r"(a2), "r"(a3), "l"(db), "r"(sc));
}

__device__ __forceinline__ uint64_t mkdesc(uint32_t lo) { return ((uint64_t)0x40000040u << 32) | lo; }
template <int F> __device__ __forceinline__ uint32_t lop3(uint32_t a, uint32_t b, uint32_t c) { uint32_t r; asm("lop3.b32 %0, %1, %2, %3, %4;" : "=r"(r) : "r"(a), "r"(b), "r"(c), "n"(F)); return r; }
__device__ __forceinline__ void stg128_tag(void* p, uint32_t x, uint32_t y, uint32_t z, uint32_t u, uint32_t ep, int w) {
    stg128(p, lop3<0xB8>(x, w == 0, ep), lop3<0xB8>(y, w == 1, ep), lop3<0xB8>(z, w == 2, ep), lop3<0xB8>(u, w == 3, ep));
}
__device__ __forceinline__ uint32_t tag(uint32_t w, uint32_t ep) { asm("lop3.b32 %0, %0, 1, %1, 0xB8;" : "+r"(w) : "r"(ep)); return w; }
template <int N> __device__ __forceinline__ void pack_part(uint32_t (&p)[32], const float (&v)[N], uint32_t ep) {
#pragma unroll
    for (int i = 0; i < N / 2; i++) p[i] = (i & 3) ? pack2(v[2 * i], v[2 * i + 1]) : tag(pack2(v[2 * i], v[2 * i + 1]), ep);
#pragma unroll
    for (int i = 0; i < N / 2; i++) asm volatile("" : "+r"(p[i]));
}
__device__ __forceinline__ void st_part(uint4* p, const uint32_t* v) {
    asm volatile("{\n.reg .b64 l, h;\n.reg .b128 q;\nmov.b64 l, {%1, %2};\nmov.b64 h, {%3, %4};\nmov.b128 q, {l, h};\nst.relaxed.gpu.global.b128 [%0], q;\n}"
                 ::"l"(p), "r"(v[0]), "r"(v[1]), "r"(v[2]), "r"(v[3]) : "memory");
}
__device__ __forceinline__ void st_peer(uint32_t a, uint32_t x, uint32_t y, uint32_t z, uint32_t w, uint32_t bar) {
    asm volatile("st.async.shared::cluster.mbarrier::complete_tx::bytes.v4.b32 [%0], {%1, %2, %3, %4}, [%5];" ::"r"(a), "r"(x), "r"(y), "r"(z), "r"(w), "r"(bar) : "memory");
}
__device__ __forceinline__ int g4_block(int c, int j) { return c ? j ^ (8 - 2 * c) : 8 + (j & 1); }
__device__ __forceinline__ uint32_t recv_off(int w) { return w ? OFF_XR : OFF_REM; }
__device__ __forceinline__ uint4 ld_part(const void* p) {
    uint4 v;
    asm volatile("{\n.reg .b64 l, h;\n.reg .b128 q;\nld.relaxed.gpu.global.b128 q, [%4];\nmov.b128 {l, h}, q;\nmov.b64 {%0, %1}, l;\nmov.b64 {%2, %3}, h;\n}"
                 : "=r"(v.x), "=r"(v.y), "=r"(v.z), "=r"(v.w) : "l"(p) : "memory");
    return v;
}
__device__ __forceinline__ void ld_part4(uint4 (&u)[4], const uint4* p, int st) {
#pragma unroll
    for (int i = 0; i < 4; i++) u[i] = ld_part(p + i * st);
}
__device__ __forceinline__ uint32_t stale4(const uint4 (&u)[4], uint32_t ep) { return lop3<0x7E>(u[0].x, ep, u[1].x) | lop3<0x7E>(u[2].x, ep, u[3].x); }
__device__ __forceinline__ uint4 add2(uint4 a, uint4 b) { return make_uint4(add2(a.x, b.x), add2(a.y, b.y), add2(a.z, b.z), add2(a.w, b.w)); }
__device__ __forceinline__ uint4 fin16(uint4 v, uint4 b, uint4 c) { return make_uint4(fma2(c.x, v.x, b.x), fma2(c.y, v.y, b.y), fma2(c.z, v.z, b.z), fma2(c.w, v.w, b.w)); }
__device__ __forceinline__ uint4 scale16(float2 c, float2 d, float r0, float r1) {
    return make_uint4(pack2(c.x * r0, c.y * r0), pack2(c.x * r1, c.y * r1), pack2(d.x * r0, d.y * r0), pack2(d.x * r1, d.y * r1));
}
__device__ __forceinline__ uint32_t split2(float x) { const float h = rbf(x); return pack2(h, x - h); }
__device__ __forceinline__ uint32_t b80_desc(uint32_t dsb, uint32_t wn, uint32_t rn, uint32_t h) {
    const uint32_t wb = dsb + OFF_W + (wn & 7) * 16384 + h * 8192, rm = dsb + OFF_REM + rn * 4096 + h * 2048;
    return (wb >> 4) | ((rm - wb) << 12);
}
constexpr int64_t B80_STEP = 128 - (126 << 16), B80_HALF = 512 - (384 << 16);
constexpr uint32_t ring_mask(int L) {
    uint32_t m = 0;
    for (int i = L; i < 20; i++) m |= (uint32_t)(i >= 20 - L || !((i - L) & 1)) << i;
    return m;
}
constexpr uint32_t M0 = ring_mask(LEAD1), M1 = ring_mask(10), M2 = ring_mask(XLEAD);
__device__ __forceinline__ uint32_t ring_pos(int w, int n, int L) { return w ? (n < 10 - L ? L + 2 * n : 10 + n) : (n < L ? n : 2 * n - L + 1); }
__device__ __forceinline__ int g1_block(int n, int j) { return n < 5 ? 2 * n + (j & 1) : 2 * n - 9 - (j & 1); }

__device__ __forceinline__ int g2_block(int n) { return (0x9874326510ull >> (4 * n)) & 15; }
__device__ __forceinline__ int g3_block(int n, int j) { return n ? n - (n <= j) : j; }
struct Tile { int e, w, kb; uint32_t at; };
__device__ __forceinline__ Tile ring_tile(int n, int grp, int j) {
    const int e = (n >= 20) + (n >= 40), i = n - 20 * e;
    const uint32_t M = e == 0 ? M0 : e == 1 ? M1 : M2;
    const int w = (M >> i) & 1, c = __popc(M & ((1u << i) - 1)), kb = w ? c : i - c, tile = grp + 16 * w;
    return {e, w, kb, 64u * (e == 0 ? tile + (g1_block(kb, j) << 16) : e == 1 ? g2_block(kb) + (tile << 16) : (10 * tile + g3_block(kb, j)) << 16)};
}
__device__ __forceinline__ void load_tile(const Maps& mp, uint32_t dst, int e, uint32_t at, uint32_t bar) {
    mbar_expect(bar, 8192);
    tma_ld2(dst, &mp.x[e], at & 0xffff, at >> 16, bar);
}

template <int OCT>
__device__ __forceinline__ void gemv_tile(float (&d)[4], uint32_t a, uint32_t b, int kb0) {
    uint32_t alo = ((a & 0x3FFFF) >> 4) | 0x10000u, blo_ = ((b & 0x3FFFF) >> 4) | (OCT << 16);
#pragma unroll 1
    for (int s = 0; s < 20; s += 4) {
        const int kb = kb0 + (s >> 2);
        const uint32_t bk = blo_ + (OCT == 7 ? (kb & 1) * 288 + (kb >> 1) * 56 : kb * 64);
        wg_fence();
#pragma unroll
        for (int q = 0; q < 4; q++) wgmma_ss8_ta(d, mkdesc(alo + (s + q) * 128), ((uint64_t)8 << 32) | (bk + q * 2 * OCT), s + q);
        wg_commit();
    }
    wg_wait<0>();
    reg_fence(d);
}

__device__ __forceinline__ void flush_tile(uint32_t st, bf16* dst, int u) {
#pragma unroll
    for (int i = 0; i < 2; i++) {
        const int idx = u + 320 * i, row = idx >> 3, c = idx & 7;
        stg128(dst + (size_t)row * S_ + 8 * c, lds128(st + row * 128 + ((c ^ ((row >> 1) & 7)) << 4)));
    }
}

__device__ __forceinline__ int tid_now() { int t; asm volatile("mov.u32 %0, %%tid.x;" : "=r"(t)); return t; }
__device__ __forceinline__ float zscale(float c) { return c == 0.f ? 0x1p-30f : c; }
__device__ __forceinline__ bool bar_any(int id, bool p) {
    uint32_t r;
    asm volatile("{\n.reg .pred a, b;\nsetp.ne.u32 a, %2, 0;\nbarrier.red.or.pred.aligned b, %1, 128, a;\nselp.u32 %0, 1, 0, b;\n}" : "=r"(r) : "r"(id), "r"((uint32_t)p) : "memory");
    return r != 0;
}

__global__ void __cluster_dims__(2, 1, 1) __launch_bounds__(NTHR, 1) fused_kernel(const __grid_constant__ Ptrs pp, bf16* __restrict__ out, const __grid_constant__ Maps mp) {
    extern __shared__ __align__(1024) uint8_t smem_raw[];
    const uint32_t sb = s2u(smem_raw), bars = sb + M_BAR, dsb = sb & 0x3FFFF;
    const int id = blockIdx.x, warp = __shfl_sync(0xffffffffu, (int)threadIdx.x >> 5, 0), wg = warp >> 2;
    const uint32_t c0 = clock_lo();
#define TIDS const int tid = tid_now(), lane = tid & 31, wt = tid & 127, g = lane >> 2, t = lane & 3; (void)wt; (void)g; (void)t;
    TS(threadIdx.x == 0, 0) TG(threadIdx.x == 0, 62)

    if (id >= 128) {
        TIDS
        if (sb & 1023) __trap();
        const int hs = id - 128;
        constexpr int H_B = 204800;
        static_assert(H_B + TAB_BYTES + 8 * VEC_BYTES <= OFF_M, "helper map");
        if (warp < 10 && elect()) { mbar_init(bars + warp * 8, 1); mbar_init(bars + 80 + warp * 8, 1); asm volatile("fence.mbarrier_init.release.cluster;" ::: "memory"); }
        __syncthreads();
        const uint32_t e0 = ld_cold(&g_epoch);
        wait_clock(c0, HELP_T);
        uint4 wr[10];
#pragma unroll
        for (int u = 0; u < 10; u++) wr[u] = ldg128(((hs >> 1) ? pp.w2 : pp.w1) + (size_t)(320 * (hs & 1) + (tid >> 4) + 32 * u) * D_ + 512 + 8 * (tid & 15));
        {
            const int r = tid >> 4, c = tid & 15;
            uint4* dst[2];
#pragma unroll
            for (int e = 0; e < 2; e++) {
                const int p = !(hs >> 1) ? r : e && (hs & 1) ? (r & ~14) | ((r & 6) << 1) | ((r & 8) >> 2) : (r & ~30) | ((r & 6) << 2) | ((r & 24) >> 2);
                dst[e] = &g_wr[((hs >> 1) * 8 + (c >> 1)) * 10 * 128 + (p & 15) * 8 + ((2 * (p >> 4) + (c & 1)) ^ (p & 7))];
            }
#pragma unroll
            for (int u = 0; u < 10; u++) stg128(reinterpret_cast<uint4*>(reinterpret_cast<uintptr_t>(dst[u >= 6]) ^ (64 * (u & 1))) +
                       ((hs >> 1) ? (0x9873265410ull >> (4 * (5 * (hs & 1) + (u >> 1)))) & 15 : 5 * (hs & 1) + (u >> 1)) * 128, wr[u]);
        }
        __syncthreads();
        if (warp == 0) signal_cnt(&g_cnt.wr[0], lane, 1);
        __syncthreads();
        if (warp < 5 && elect()) {
            const int un = 5 * hs + warp;
            mbar_expect(bars + warp * 8, 40960);
            tma_ld2(sb + warp * 40960, &mp.w1h, 64 * (un >> 1), 320 * (un & 1), bars + warp * 8);
            tma_ld2(sb + warp * 40960 + 20480, &mp.w1h, 64 * (un >> 1), 320 * (un & 1) + 160, bars + warp * 8);
        }
        if (tid < 320) {
            const uint4* gm = reinterpret_cast<const uint4*>(g_mod + 3 * D_) + tid;
            const unsigned epoch = e0 + 1;
            uint4 r[6];
            unsigned it = 0;
            for (;;) {
                uint32_t bad = 0;
#pragma unroll
                for (int i = 0; i < 6; i++) { r[i] = ld_part(gm + (i >> 1) * (D_ / 2) + (i & 1) * 3 * D_); bad |= (r[i].y ^ epoch) | (r[i].w ^ epoch); }
                if (__all_sync(~0u, !bad)) break;
                if (++it > SPIN_LIMIT) SPIN_FAIL(54)
            }
            uint32_t mv[3];
#pragma unroll
            for (int i = 0; i < 3; i++) mv[i] = pack2(__uint_as_float(r[2 * i].x) + __uint_as_float(r[2 * i + 1].x), __uint_as_float(r[2 * i].z) + __uint_as_float(r[2 * i + 1].z));
            const uint32_t sw2 = mv[0], cw = add2(mv[1], 0x3f803f80u), gw = mv[2];
            const float c0 = blo(cw), c1 = bhi(cw), s0 = blo(sw2), s1 = bhi(sw2);
            const float i0 = __frcp_rn(zscale(c0)), i1 = __frcp_rn(zscale(c1));
            const uint32_t ci = pack2(i0, i1), cq = pack2(i0 * i0, i1 * i1);
            const uint32_t a = sb + H_B + ((tid >> 5) & 1) * 4608 + (tid >> 6) * 896 + ((tid >> 2) & 7) * 112 + (tid & 3) * 4;
            sts32(a, ci); sts32(a + 16, pack2(i0 - blo(ci), i1 - bhi(ci)));
            sts32(a + 32, cq); sts32(a + 48, pack2(fmaf(i0, i0, -blo(cq)), fmaf(i1, i1, -bhi(cq))));
            sts32(a + 64, cw); sts32(a + 80, sw2); sts32(a + 96, 0x3f803f80u);
            if ((tid & ~35) == 284) sts32(a + 112, 0);
            const uint32_t v = sb + H_B + TAB_BYTES + (tid < 256 ? (tid >> 5) * VEC_BYTES + (tid & 31) * 8 : ((tid - 256) >> 3) * VEC_BYTES + 256 + (tid & 7) * 8);
            sts64f(v, blo(gw), bhi(gw)); sts64f(v + 320, c0, c1); sts64f(v + 640, s0, s1); sts64f(v + 960, i0, i1);
            float k[5] = {c0 + c1, s0 + s1, fmaf(c0, c0, c1 * c1), fmaf(c0, s0, c1 * s1), fmaf(s0, s0, s1 * s1)};
#pragma unroll 1
            for (int o = 16; o; o >>= 1) {
#pragma unroll
                for (int e = 0; e < 5; e++) k[e] += __shfl_xor_sync(~0u, k[e], o);
            }
            const uint32_t ks = sb + H_B + TAB_BYTES + (lane & 7) * VEC_BYTES + 1280 + (warp >> 1) * 32;
            if ((warp & 1) && lane < 8) { sts128f(ks, k[0], k[1], k[2], k[3]); sts128f(ks + 16, k[4], 0.f, 0.f, 0.f); }
            bar_sync(3, 320);
            if (!(warp & 1) && lane < 8) {
                const float4 o = lds128f(ks);
                sts128f(ks, k[0] + o.x, k[1] + o.y, k[2] + o.z, k[3] + o.w); sts32(ks + 16, __float_as_uint(k[4] + __uint_as_float(lds32(ks + 16))));
            }
            fence_async_smem();
        }
        __syncthreads();
        if (hs == 0 && warp == 15 && elect()) {
            asm volatile("cp.async.bulk.global.shared::cta.bulk_group [%0], [%1], %2;\ncp.async.bulk.commit_group;\ncp.async.bulk.wait_group 0;"
                         ::"l"(g_tab), "r"(sb + H_B), "n"(TAB_BYTES + 8 * VEC_BYTES) : "memory");
            asm volatile("red.release.gpu.global.add.u32 [%0], 1;" ::"l"(&g_cnt.tab[0]) : "memory");
        }
        __syncwarp();
#pragma unroll 1
        for (int i = wg; i < 20; i += 4) {
            const int r = i / 5, b = i - 5 * r, un = 5 * hs + b, u3 = 20 * r + un;
            auto refill = [&](int e, int u, uint32_t fb) {
                mbar_expect(fb, 40960);
                tma_ld2(sb + e * 40960, &mp.w3h, 64 * (u >> 1), 320 * (u & 1), fb);
                tma_ld2(sb + e * 40960 + 20480, &mp.w3h, 64 * (u >> 1), 320 * (u & 1) + 160, fb);
            };
            if (i > 4 && i < 9) {
                bar_sync(1, 512);
                if (warp == 0) {
                    signal_cnt(&g_cnt.uv[0], lane, 1);
                    if (elect()) {
#pragma unroll 1
                        for (int e = 0; e < 5; e++) refill(e, 5 * hs + e, bars + (5 + e) * 8);
                        l2_prefetch(pp.w2 + (size_t)160 * hs * D_, 160 * D_ * 2);
                    }
                    __syncwarp();
                }
            }
            mbar_wait(bars + i * 8, 0);
            float d[4];
            gemv_tile<7>(d, sb + b * 40960, sb + H_B, 5 * (un & 1));
            const int col = 16 * (warp & 3) + g;
            float* dst = r ? g_cs3 + (un & 1) * 1920 + 64 * ((u3 >> 1) - 10) + col : g_uv + (un & 1) * 3 * D_ + 2 * D_ + 64 * (un >> 1) + col;
            if (t == 3) { dst[0] = d[0]; dst[8] = d[2]; }
            if (r == 0 && t == 2) { dst[-2 * D_] = d[0]; dst[8 - 2 * D_] = d[2]; dst[-D_] = d[1]; dst[8 - D_] = d[3]; }
            if (r == 1 || r == 2) {
                bar_sync(4 + wg, 128);
                if (wt == 0) refill(b, u3, bars + (i + 5) * 8);
            }
        }
        __syncthreads();
        if (warp == 0) signal_cnt(&g_cnt.cs[0], lane, 1);
        if (tid == 511) l2_prefetch(pp.w4 + (size_t)432 * hs * D_, 432 * D_ * 2);
        for (uint32_t it = 0; ld_cold(&g_cnt.cs[0]) < 4;) { if (++it > SPIN_LIMIT) SPIN_FAIL(47) }
        asm volatile("fence.acquire.gpu;" ::: "memory");
        if (tid < 432) {
            const int jj = 2 * hs + (tid >= 216), c = tid % 216;
            const float* src = g_cs3 + (c < 192 ? 192 * jj + c : 1344 + 24 * jj + c);
            const uint32_t s = split2(ldcg32f(src) + ldcg32f(src + 1920));
            stg128(&g_cs3b[432 * hs + tid], s, s & 0xffffu, 0, 0);
        }
        __syncthreads();
        if (warp == 0) signal_cnt(&g_cnt.cs2[0], lane, 1);
        if (tid == 0 && hs == 3) {
            uint32_t it = 0;
            while (ld_cold(&g_epoch) == e0) { __nanosleep(256); if (++it > (1u << 20)) SPIN_FAIL(48) }
        }
        return;
    }

    if (elect()) {
        if (warp == 15) {
            mbar_init(bars + B_IN * 8, 1); mbar_init(bars + B_IN * 8 + 8, 1);
            asm volatile("fence.mbarrier_init.release.cluster;" ::: "memory");
            mbar_expect(bars + B_IN * 8, 131 * 160);
            tma_ld2(sb + OFF_KIN, &mp.k, 80 * (id & 7), 64 * (id >> 3) - 3, bars + B_IN * 8);
            tma_ld2(sb + OFF_VIN, &mp.v, 80 * (id & 7), 64 * (id >> 3), bars + B_IN * 8);
        } else if (warp < 13) {
            const uint32_t n = (0x4C11111111881ull >> (4 * warp)) & 15;
#pragma unroll
            for (int i = 0; i < 4; i++) mbar_init(bars + warp * 64 + i * 8, n);
            if (warp == 11) { mbar_init(bars + B_XFREE * 8, 16); mbar_init(bars + B_OWN * 8, 8); }
            else {
#pragma unroll
                for (int i = 4; i < 8; i++) mbar_init(bars + warp * 64 + i * 8, n);
            }
            asm volatile("fence.mbarrier_init.release.cluster;" ::: "memory");
        }
    }
    asm volatile("" ::"l"(pp.s), "l"(pp.c), "l"(out));
    TR4((threadIdx.x & 31) == 0, warp)
    const int pr = id >> 1;
    const int grp = pr < 4 ? 15 : pr < 36 ? (pr - 4) & 7 : 8 + (pr - 36) % 7;
    const int j = 2 * (pr < 4 ? pr : pr < 36 ? (pr - 4) >> 3 : (pr - 36) / 7) + (id & 1);

    if (wg == 3) {
        TIDS
        const int sw = warp - 12;
        uint32_t ep = ld_cold(&g_epoch);
        TR4(lane == 0, 20 + sw)
        __syncthreads();
        TR4(lane == 0, 30 + sw)
        asm volatile("barrier.cluster.arrive.relaxed.aligned;" ::: "memory");
        if (sw == 0) {
#pragma unroll 1
            for (int n = 0; n < 12; n++) {
                wait_clock(c0, PF_T0 + PF_DT * n);
                if (elect()) l2_prefetch(n < 4 ? (const char*)pp.q + id * 20480 + n * 5120 : (const char*)pp.w_mod + id * 38400 + (n - 4) * 4800, n < 4 ? 5120 : 4800);
            }
        } else if (sw == 1) {
            wait_clock(c0, T_SSM);
            if (elect()) {
                mbar_expect(bars + B_SSM * 8, 20480);
                bulk_ld(sb + OFF_SSM, pp.ssm_k + (size_t)5 * id * S_, 20480, bars + B_SSM * 8);
            }
            mbar_spin(bars + B_KVS * 8, 0);
            signal_cnt(&g_cnt.kv[(id & 7) * 32], lane, 1, true);
            TS(lane == 0, 2)
            mbar_spin(bars + B_RAW * 8, 0);
            if (elect()) {
                mbar_expect(bars + B_QIN * 8, 20480);
                tma_ld3(sb + OFF_QIN, &mp.q, 0, 16 * id, 0, bars + B_QIN * 8);
            }
        } else if (sw == 2) {
            if (elect()) {
#pragma unroll 1
                for (int i = 2; i < (int)(sizeof(Maps) / sizeof(CUtensorMap)); i++) asm volatile("prefetch.tensormap [%0];" ::"l"(&mp.k + i) : "memory");
#pragma unroll 1
                for (int i = B_SUMS; i < B_LAND; i++) mbar_expect(bars + i * 8, i < B_RECV ? 2048 : (i & 3) < 3 ? 8192 : 3072);
            }
            wait_cnt(&g_cnt.kv[(id >> 4) * 32], 16, true);
            TS(lane == 0, 4)
            if (elect()) {
                mbar_expect(bars + B_RAW * 8, 12288);
                mbar_expect(bars + B_RAW2 * 8, 8192);
#pragma unroll
                for (int c = 0; c < 5; c++) bulk_ld(sb + OFF_CH + c * CH_BYTES, g_kvT + (size_t)(5 * id + c) * S_, 4096, bars + (c < 3 ? B_RAW : B_RAW2) * 8);
            }
            mbar_spin(bars + B_BK * 8, 0);
            mbar_spin(bars + B_QIN * 8, 0);
            if (id < 120 && elect()) {
                mbar_expect(bars + B_WM * 8, 40960);
                tma_ld2(sb + OFF_WM, &mp.wmod, 64 * pr, 320 * (id & 1), bars + B_WM * 8);
                tma_ld2(sb + OFF_WM + 20480, &mp.wmod, 64 * pr, 320 * (id & 1) + 160, bars + B_WM * 8);
            }
            TS(lane == 0, 57)
        } else {
            wait_clock(c0, T_KVB);
            if (elect()) {
                mbar_expect(bars + (B_IN + 1) * 8, 131 * 160);
                tma_ld2(sb + OFF_KIN + 10752, &mp.k, 80 * (id & 7), 64 * (id >> 3) + 1021, bars + (B_IN + 1) * 8);
                tma_ld2(sb + OFF_VIN + 10240, &mp.v, 80 * (id & 7), 64 * (id >> 3) + 1024, bars + (B_IN + 1) * 8);
            }
            TS(lane == 0, 53)
            if (lane == 0) sts32(sb + M_EP, ep + 1);
            sts32(sb + M_NUL + lane * 4, 0);
#pragma unroll 1
            for (int i = 0; i < 10; i++) sts128(sb + OFF_Z + i * 512 + lane * 16, 0, 0, 0, 0);
            __syncwarp();
#pragma unroll 1
            for (int i = lane; i < 160; i += 32) {
                const uint32_t c = ldg32(pp.c + 320 * (id & 1) + 2 * i);
                sts32(sb + OFF_Z + (i >> 2) * 128 + (i & 3) * 4, pack2(silu(blo(c)), silu(bhi(c))));
            }
            fence_async_smem();
            for (uint32_t ph = 0, again = 1; again; ph ^= 1) {
                mbar_spin(bars + B_RAW2 * 8, ph);
                uint32_t bad = 0;
#pragma unroll
                for (int i = 0; i < 8; i++) bad |= lop3<0x7E>(lds32(sb + OFF_CH + 3 * CH_BYTES + i * 512 + lane * 16), ~ep, lds32(sb + OFF_CH + 4 * CH_BYTES + i * 512 + lane * 16));
                again = __any_sync(~0u, bad & 1);
                if (again && elect()) {
                    mbar_expect(bars + B_RAW2 * 8, 8192);
#pragma unroll
                    for (int c = 3; c < 5; c++) bulk_ld(sb + OFF_CH + c * CH_BYTES, g_kvT + (size_t)(5 * id + c) * S_, 4096, bars + B_RAW2 * 8);
                }
            }
            if (elect()) mbar_arrive(bars + B_RAW3 * 8);
        }
        {
            mbar_spin(bars + B_QIN * 8, 0);
            asm volatile("add.u32 %0, %0, 1;" : "+r"(ep));
            TS(wt == 0, 54)
            const int tk = 8 * ((lane >> 1) & 1) + 2 * (lane >> 3) + (lane & 1), ck = 4 * (sw & 1) + ((lane >> 1) & 2);
            const uint32_t src = sb + OFF_QIN + (sw >> 1) * 2048 + tk * 128;
            bf16* dst = g_qT + (size_t)id * 16 * D_ + (32 * sw + 8 * (t & 2) + g) * 16 + 8 * (t & 1);
#pragma unroll 1
            for (int i = 0; i < 5; i++) {
                uint32_t r[8];
                ldsm4t(src + i * 4096 + ((ck ^ (tk & 7)) << 4), r[0], r[1], r[2], r[3]);
                ldsm4t(src + i * 4096 + (((ck + 1) ^ (tk & 7)) << 4), r[4], r[5], r[6], r[7]);
                stg128(dst + i * 2048, tag(r[0], ep), r[1], r[2], r[3]);
                stg128(dst + i * 2048 + 128, tag(r[4], ep), r[5], r[6], r[7]);
            }
            float s1 = 0.f, s2 = 0.f;
#pragma unroll 2
            for (int i = 0; i < 10; i++) {
                const uint4 w4 = lds128(sb + OFF_QIN + i * 2048 + wt * 16);
                const uint32_t w[4] = {w4.x, w4.y, w4.z, w4.w};
#pragma unroll
                for (int e = 0; e < 4; e++) { const float a = blo(w[e]), b = bhi(w[e]); s1 += a + b; s2 = fmaf(a, a, fmaf(b, b, s2)); }
            }
#pragma unroll
            for (int o = 1; o < 8; o *= 2) { s1 += __shfl_xor_sync(~0u, s1, o); s2 += __shfl_xor_sync(~0u, s2, o); }
            s1 *= 1.f / D_;
            uint32_t rs = pack2(rsqrtf(fmaxf(s2 * (1.f / D_) - s1 * s1, 0.f) + 1e-5f), 0.f);
            if (lane < 8) rs = tag(rs, ep);
            rs = pack2(blo(rs), -s1 * blo(rs));
            const uint32_t sel = lane ? 0x7632 : 0x5410;
            const uint32_t a0 = __shfl_sync(~0u, rs, 0), a1 = __shfl_sync(~0u, rs, 8), a2 = __shfl_sync(~0u, rs, 16), a3 = __shfl_sync(~0u, rs, 24);
            if (lane < 2) stg64(g_qst + lane * S_ + 16 * id + 4 * sw, tag(__byte_perm(a0, a1, sel), ep), __byte_perm(a2, a3, sel));
            TS(wt == 0, 55)
        }
        bar_sync(6, 128);
        if (sw == 3) {
            signal_cnt(&g_cnt.q[(lane & 3) * 32], lane, 4, true);
            TS(lane == 0, 3)
        }
        asm volatile("setmaxnreg.dec.sync.aligned.u32 32;");
        asm volatile("barrier.cluster.wait.aligned;" ::: "memory");
        if (sw == 1) {
            mbar_spin(bars + B_XS * 8, 0);
            signal_cnt(&g_cnt.x[(lane & 3) * 32], lane, 4, true);
            TS(lane == 0, 20)
        }
        if (sw == 2) {
            wait_cnt(&g_cnt.q[(id & 3) * 32], 128, true);
            if (elect()) {
                mbar_expect(bars + B_QRDY * 8, 28672);
                tma_ld2(sb + OFF_QT, &mp.qT, 80 * id, 0, bars + B_QRDY * 8);
                bulk_ld(sb + OFF_QT + 20480, g_qst, 8192, bars + B_QRDY * 8);
            }
            TS(lane == 0, 8)
        }
        if (sw == 1 || sw == 2) {
            mbar_spin(bars + B_XS * 8, 0);
            fence_async_smem();
            int n = sw & 1;
            const uint32_t plan = ring_tile(min(2 * lane + n, 59), grp, j).at;
#pragma unroll 1
            for (int s = 0; s < 7; s++) {
                const int e = (s >= 2) + (s >= 5), end = (0ull + LEAD1 + (20 << 8) + (24 << 16) + (30ull << 24) + (40ull << 32) + ((40ull + XLEAD) << 40) + (60ull << 48)) >> (8 * s) & 255;
                if (s == 1 || s == 4 || s == 6) mbar_spin(bars + (B_GATE + 2 + e) * 8, !e);
                else if (s != 3 || grp == 15) {
                    wait_cnt(s == 0 ? &g_cnt.x[(id & 3) * 32] : s == 5 ? &g_cnt.g2[grp * 32] : &g_cnt.g1[(s == 2 ? min(max(grp - 1 + min(lane, 2), 0), 15) : 16) * 32], e ? 32 : 128, true);
                    TS(lane == 0 && sw == 2 && s != 3, 26 + 2 * e)
                }
#pragma unroll 1
                for (; n < end; n += 2) {
                    const uint32_t at = __shfl_sync(~0u, plan, n >> 1);
                    mbar_spin(bars + (B_XEMPTY + (n & 7)) * 8, ((n >> 3) & 1) ^ 1);
                    TR2(lane == 0 && n < 40, 20 + n)
                    if (elect()) {
                        if (n == 40 || n == 40 + XLEAD) {
                            mbar_arrive(bars + (B_LAND + (n & 7)) * 8);
                            asm volatile("mbarrier.arrive.shared.b64 _, [%0], 8;" ::"r"(bars + (B_XEMPTY + (n & 7)) * 8) : "memory");
                        } else load_tile(mp, sb + OFF_XR + (n & 7) * 8192, e, at, bars + (B_LAND + (n & 7)) * 8);
                    }
                }
            }
            if (sw == 1) { if (elect()) mbar_arrive(bars + (B_GATE + 5) * 8); return; }
            mbar_spin(bars + (B_GATE + 5) * 8, 0);
            mbar_spin(bars + B_VEC3 * 8, 0);
            unsigned old = 0;
            asm volatile("{\n.reg .pred P;\nsetp.eq.s32 P, %2, 0;\n@P atom.relaxed.gpu.global.add.u32 %0, [%1], %3;\n}" : "+r"(old) : "l"(&g_cnt.done[0]), "r"(lane), "r"(1) : "memory");
            if (__any_sync(~0u, old == 127)) {
#pragma unroll 1
                for (int i = lane; i < (int)(sizeof(Counters) / 128); i += 32) reinterpret_cast<unsigned*>(&g_cnt)[i * 32] = 0;
                signal_cnt(&g_epoch, lane, 1, true);
            }
        } else if (sw == 0) {
            wait_cnt(&g_cnt.wr[0], 4);
            mbar_spin(bars + B_QRDY * 8, 0);
            mbar_spin(bars + B_MODR * 8, 0);
            const uint32_t wf = bars + B_WFULL * 8, we = bars + B_WEMPTY * 8;
#pragma unroll 1
            for (int n = 0; n < 5; n++) {
                if (n == 3) { mbar_spin(bars + B_XS * 8, 0); fence_async_smem(); }
                TR2(lane == 0, 70 + n)
                if (elect()) {
                    const uint32_t fb = wf + n * 8, dst = sb + OFF_W + n * 16384;
                    mbar_expect(fb, 20480);
#pragma unroll 1
                    for (int h = 0; h < 2; h++) {
                        const int kb = g1_block(2 * n + h, j);
                        tma_ld2(dst + h * 8192, &mp.w1, 64 * j, 64 * kb, fb);
                        bulk_ld(sb + OFF_REM + n * 4096 + h * 2048, &g_wr[(j * 10 + kb) * 128], 2048, fb);
                    }
                }
            }
            mbar_spin(bars + B_GATE * 8, 0);
#pragma unroll 1
            for (int i = -3; i < 5; i++) {
                const int n = i < 0 ? 8 + i : 5 + i;
                const uint32_t fb = wf + (n & 7) * 8;
                if (i >= 0) mbar_spin(we + i * 8, 0);
                TR2(lane == 0 && i >= 0, 70 + n)
                if (elect()) {
                    if (i < 0 || i >= 3) {
                        mbar_expect(fb, 20480);
#pragma unroll 1
                        for (int h = 0; h < 2; h++) tma_ld5(sb + OFF_W + (n & 7) * 16384 + h * 8192, n < 9 ? &mp.w2a : &mp.w2b, 64 * j, n < 9 ? 2 * g2_block(2 * n - 10 + h) : 4 * h, fb);
                    }
                    if (i >= 0) bulk_ld(sb + OFF_REM + i * 4096, &g_wr[((8 + j) * 10 + 2 * i) * 128], 4096, fb);
                }
            }
            mbar_spin(bars + (B_GATE + 1) * 8, 0);
#pragma unroll 1
            for (int n = 10; n < 30; n++) {
                if (n == W3_N2) mbar_spin(bars + (B_GATE + 2) * 8, 0);
                mbar_spin(we + (n & 7) * 8, ((n >> 3) & 1) ^ 1);
                TR2(lane == 0, 70 + n)
                if (elect()) {
                    const uint32_t dst = sb + OFF_W + (n & 7) * 16384, fb = wf + (n & 7) * 8;
                    mbar_expect(fb, 13824);
                    const int row = 64 * g3_block((n - 10) >> 1, j) + 32 * (n & 1);
                    tma_ld3(dst, &mp.w3a, 0, row, 3 * j, fb);
                    tma_ld2(dst + 12288, &mp.w3b, 1536 + 24 * j, row, fb);
                }
            }
            mbar_spin(we + 6 * 8, 0);
            mbar_spin(bars + B_VEC3 * 8, 0);
            if (elect()) { mbar_expect(wf + 6 * 8, 3456); bulk_ld(sb + OFF_W + 6 * 16384, &g_cs3b[216 * j], 3456, wf + 6 * 8); }
#pragma unroll 1
            for (int n = 31; n < 50; n++) {
                const int e = n < 38 ? 4 : (n - 38) & 3, m0 = n == 35, m1 = e == 3 ? -1 : m0 | (e == 1), rem = 96 + 3 * (j >> 1);
                const int c1_ = j ^ (n < 38 ? 6 : 4 >> ((n - 38) >> 2) & 6), c0_ = n < 38 ? 8 + (j & 1) : c1_;
                const int f = (0xC840A80C204ull >> (4 * min(n - 31, e + 7))) & 15;
                const int r0 = m0 ? rem : 6 * (j ^ (f >> 3)) + (f & 6), r1 = m1 ? rem : r0 + (n < 38 ? 0 : 2);
                mbar_spin(we + (n & 7) * 8, ((n >> 3) & 1) ^ 1);
                if (elect()) {
                    const uint32_t dst = sb + OFF_W + (n & 7) * 16384, fb = wf + (n & 7) * 8;
                    mbar_expect(fb, m1 < 0 ? 8192 : 16384 - 2048 * (m0 + m1));
                    tma_ld2(dst, &mp.w4[m0], 64 * c0_, r0 * (32 >> m0), fb);
                    if (m1 >= 0) tma_ld2(dst + 8192, &mp.w4[m1], 64 * c1_, r1 * (32 >> m1), fb);
                }
            }
        } else {
            {
                wait_cnt(&g_cnt.tab[0], 1);
                mbar_spin(bars + B_MODR * 8, 0);
                if (elect()) {
                    mbar_expect(bars + B_TAB * 8, TAB_BYTES / 2 + VEC_BYTES);
                    bulk_ld(sb + OFF_TAB, g_tab + (j & 1) * (TAB_BYTES / 32), TAB_BYTES / 2, bars + B_TAB * 8);
                    bulk_ld(sb + M_GB, g_tab + (TAB_BYTES + j * VEC_BYTES) / 16, VEC_BYTES, bars + B_TAB * 8);
                }
                TS(lane == 0, 5)
            }
            wait_cnt(&g_cnt.uv[0], 4);
#pragma unroll 1
            for (int c = lane; c < 80; c += 32) {
                const float* src = g_uv + (c < 64 ? 64 * j + c : 448 + 16 * j + c);
                const uint32_t u = split2(ldcg32f(src) + ldcg32f(src + 3 * D_)), v = split2(ldcg32f(src + D_) + ldcg32f(src + 4 * D_));
                const uint32_t s = split2(ldcg32f(src + 2 * D_) + ldcg32f(src + 5 * D_));
                sts128(sb + OFF_F1 + c * 16, u, __byte_perm(u, v, 0x5410), __byte_perm(v, 0, 0x1032), s);
                sts128(sb + M_F1 + c * 16, s & 0xffffu, 0, 0, 0);
            }
            fence_async_smem();
            warp_arrive(bars + B_VEC * 8);
            TS(lane == 0, 9)
#pragma unroll 1
            for (int e = 1; e < 3; e++) {
                wait_cnt(e == 1 ? &g_cnt.g1[min(grp + 15 + min(lane, 2), 31) * 32] : &g_cnt.g2[(grp + 16) * 32], 32, true);
                if (elect()) mbar_arrive(bars + (B_GATE + 2 + e) * 8);
                TS(lane == 0, 27 + 2 * e)
            }
            wait_cnt(&g_cnt.cs2[0], 4);
            if (elect()) mbar_arrive(bars + B_VEC3 * 8);
            TS(lane == 0, 19)
        }
        return;
    }

    {
        uint32_t ep;
        {
            TIDS
            ep = ld_cold(&g_epoch);
            const int cp = (tid + 16) % 40, cp1 = tid % 40;
            const uint4 sh0 = ldg128(pp.shift_k + (80 * (id & 7) + 2 * cp1) * 4), sh1 = ldg128(pp.shift_k + (80 * (id & 7) + 2 * cp) * 4);
            uint32_t dd;
            asm volatile("ld.global.nc.u16 %0, [%1];" : "=r"(dd) : "l"(pp.ssm_D + 5 * id + min(wg + 3 * lane, 4)));
            TR4(lane == 0, 40 + warp)
            __syncthreads();
            asm volatile("barrier.cluster.arrive.relaxed.aligned;" ::: "memory");
            asm volatile("add.u32 %0, %0, 1;" : "+r"(ep));
#pragma unroll 1
            for (int hw = 0; hw < 2; hw++) {
                if ((unsigned)(warp - 2 * hw) >= 10) continue;
                const int u = tid - 64 * hw;
                const int c = hw ? cp : cp1, oc = u / 40, line = 31 - 16 * hw - (id >> 3);
                const uint4 sh = hw ? sh1 : sh0;
                const uint32_t st = sb + OFF_ST + hw * 10240, sta = st + c * 256 + ((((6 - 2 * (oc & 3)) ^ (oc >> 2) ^ (line & 1)) ^ (c & 7)) << 4), in = oc * 1280 + c * 4;
                const uint32_t f0 = __byte_perm(sh.x, sh.z, 0x5410), f1 = __byte_perm(sh.x, sh.z, 0x7632), f2 = __byte_perm(sh.y, sh.w, 0x5410), f3 = __byte_perm(sh.y, sh.w, 0x7632);
                uint32_t kk[11], vv[8];
                mbar_spin(bars + (B_IN + hw) * 8, 0);
                TS(tid == 64, 18 + 42 * hw)
#pragma unroll
                for (int i = 0; i < 11; i++) kk[i] = lds32(sb + OFF_KIN + hw * 10752 + in + i * 160);
#pragma unroll
                for (int i = 0; i < 8; i++) vv[i] = lds32(sb + OFF_VIN + hw * 10240 + in + i * 160);
#pragma unroll
                for (int i = 0; i < 8; i++) vv[i] = mul2(fma2(kk[i + 3], f0, fma2(kk[i + 2], f1, fma2(kk[i + 1], f2, mul2(kk[i], f3)))), vv[i]);
                sts128(sta, tag(__byte_perm(vv[0], vv[1], 0x5410), ep), __byte_perm(vv[2], vv[3], 0x5410), __byte_perm(vv[4], vv[5], 0x5410), __byte_perm(vv[6], vv[7], 0x5410));
                sts128(sta + 128, tag(__byte_perm(vv[0], vv[1], 0x7632), ep), __byte_perm(vv[2], vv[3], 0x7632), __byte_perm(vv[4], vv[5], 0x7632), __byte_perm(vv[6], vv[7], 0x7632));
                bar_sync(7 + hw, 320);
                flush_tile(st, g_kvT + (size_t)(80 * (id & 7)) * S_ + 64 * line, u);
                TS(tid == 64 && hw, 1)
            }
            warp_arrive(bars + B_KVS * 8);
            if (tid < 320) sts128(sb + OFF_CH + (tid >> 6) * CH_BYTES + 4096 + (tid & 63) * 16, 0, 0, 0, 0);
            mbar_spin(bars + B_SSM * 8, 0);
            TS(tid == 0, 14)
#pragma unroll 1
            for (int u0 = wg; u0 < 20; u0 += 12) {
                uint2 w[4];
                uint32_t pv[4];
#pragma unroll
                for (int i = 0; i < 4; i++) {
                    const uint32_t a = sb + OFF_SSM + min(u0 + 3 * i, 19) * 1024 + wt * 8;
                    w[i] = lds64(a); pv[i] = lds32(a - 4);
                }
#pragma unroll
                for (int i = 0; i < 4; i++) {
                    const int un = min(u0 + 3 * i, 19);
                    sts128(sb + OFF_CH + (un >> 2) * CH_BYTES + OFF_P + (un & 3) * 2048 + wt * 16, __byte_perm(w[i].x, pv[i], 0x7610), __byte_perm(w[i].x, 0, 0x1032), __byte_perm(w[i].y, w[i].x, 0x7610), __byte_perm(w[i].y, 0, 0x1032));
                }
            }
            __syncwarp();
            if (wt < 2 - (wg >> 1)) {
                const uint32_t h = lds32(sb + OFF_SSM + (wg + 3 * wt) * 4096), h0 = pack2(blo(h) + blo(dd), 0.f);
                sts64f(sb + OFF_CH + (wg + 3 * wt) * CH_BYTES + OFF_P, __uint_as_float(h0), __uint_as_float(__byte_perm(h, h0, 0x5432)));
            }
            fence_async_smem();
            warp_arrive(bars + B_BK * 8);
            asm volatile("barrier.cluster.wait.aligned;" ::: "memory");
            mbar_spin(bars + B_BK * 8, 0);
            TS(tid == 0, 15)
        }

#pragma unroll 1
        for (int c = wg; c < 5; c += 3) {
            const uint32_t kvb = sb + OFF_CH + c * CH_BYTES;
            mbar_spin(bars + (c < 3 ? B_RAW : B_RAW3) * 8, 0);
            for (uint32_t ph = 0; c < 3; ph ^= 1) {
                const int wt = tid_now() & 127;
                if (!RARE(bar_any(1 + wg, lop3<0x7E>(lds32(kvb + wt * 16), ep, lds32(kvb + 2048 + wt * 16)) & 1))) break;
                if (wt == 0) { mbar_expect(bars + (B_RETRY + wg) * 8, 4096); bulk_ld(kvb, g_kvT + (size_t)(5 * id + c) * S_, 4096, bars + (B_RETRY + wg) * 8); }
                mbar_spin(bars + (B_RETRY + wg) * 8, ph);
                STALE1(-8)
            }
            TS(threadIdx.x == 0, c ? 13 : 11)
            float acc[64];
            {
                const int l = tid_now() & 31;
                conv_channel(acc, kvb + OFF_P + (8 * (warp & 3) + (l >> 2) - 2 * (l & 3)) * 4, (((uint64_t)0xC0000010u << 32) | ((kvb & 0x3FFFF) >> 4) | 0x10000u) + pp.nil);
            }
            TS(threadIdx.x == 0, c ? 16 : 12)
            if (c < 3) warp_arrive(bars + B_R1 * 8);
            else mbar_spin(bars + B_R1 * 8, 0);
            if (wg == 2 && id < 120) {
                TIDS
                mbar_spin(bars + B_RAW3 * 8, 0);
                mbar_spin(bars + B_WM * 8, 0);
                TS(wt == 0, 56)
                float d[4];
                gemv_tile<8>(d, sb + OFF_WM, sb + OFF_Z, 0);
                const float d2 = __shfl_up_sync(~0u, d[2], 1);
                TS(wt == 0, 7)
                if (t < 2) asm volatile("{\n.reg .b64 v;\nmov.b64 v, {%1, %2};\nst.relaxed.gpu.global.b64 [%0], v;\n}" ::"l"(g_mod + (id & 1) * 6 * D_ + 64 * pr + 16 * (warp & 3) + g + 8 * t),
                                        "r"(__float_as_uint(t ? d2 : d[0])), "r"(lds32(sb + M_EP)) : "memory");
            }
            TR4(threadIdx.x == 0, 60 + (c >= 3) * 10)
            TIDS
            const int e = 127 - 8 * (lane >> 4) - (lane & 7), u0 = (warp & 3) + 8 * (e >> 2) + (e & 3) + 4 * ((lane >> 3) & 1);
            const uint32_t ring = sb + OFF_RING + c * 16384 + (warp & 3) * 4096, wa = ring + (u0 ^ ((u0 >> 1) & 4)) * 16;
            if (lane < (warp & 3)) sts128(ring + lane * 16, 0, 0, 0, 0);
#pragma unroll
            for (int i = 0; i < 8; i++)
                stsm4t(i == 0 && u0 >= 256 ? sb + M_SINK : wa - 512 * i, pack2(acc[8 * i], acc[8 * i + 1]), pack2(acc[8 * i + 2], acc[8 * i + 3]),
                       pack2(acc[8 * i + 4], acc[8 * i + 5]), pack2(acc[8 * i + 6], acc[8 * i + 7]));
            warp_arrive(bars + (B_RING + c) * 8);
            TR4(threadIdx.x == 0, 61 + (c >= 3) * 10)
        }
        TIDS
        if (wg == 2) bar_sync(3, 128);
        if (warp == 9) {
            const int v = min(lane / 5, 3);
            const uint2* gm = g_mod + (v + (v == 3)) * D_ + 5 * id + lane % 5;
            const unsigned epoch = lds32(sb + M_EP);
            uint2 r0, r1;
            unsigned it = 0;
            do {
                r0 = ld_mod(gm); r1 = ld_mod(gm + 6 * D_);
                SPIN_CHECK(55)
            } while (!__all_sync(~0u, r0.y == epoch && r1.y == epoch));
            const float m0 = __uint_as_float(r0.x), m1 = __uint_as_float(r1.x);
            const float m = rbf(m0 + m1), p = rbf(1.f + m);
            const float cz = zscale(__shfl_sync(~0u, p, 15 + lane % 5)), ga = __shfl_sync(~0u, m, 10 + lane % 5);
            if (lane < 15) sts32(sb + M_AB + lane % 5 * 16 + v * 4, lane < 10 ? __float_as_uint(cz * ga * (lane < 5 ? m : p)) : pack2(cz, cz));
            warp_arrive(bars + B_MODR * 8);
            TS(lane == 0, 6)
        }
        mbar_spin(bars + B_QRDY * 8, 0);
        uint4 rs[2], nm[2];
#pragma unroll
        for (int h = 0; h < 2; h++) { rs[h] = lds128(sb + OFF_QT + 20480 + h * 2048 + wt * 16); nm[h] = lds128(sb + OFF_QT + 24576 + h * 2048 + wt * 16); }
        mbar_spin(bars + B_MODR * 8, 0);
        TR4(threadIdx.x == 0, 72)
        uint32_t it = 0;
        while (RARE(__any_sync(~0u, (lop3<0x7E>(rs[0].x, ep, rs[0].z) | lop3<0x7E>(nm[0].x, ep, nm[0].z) | lop3<0x7E>(rs[1].x, ep, rs[1].z) | lop3<0x7E>(nm[1].x, ep, nm[1].z)) & 1))) {
#pragma unroll
            for (int h = 0; h < 2; h++) { rs[h] = ld_part(g_qst + 1024 * h + 8 * wt); nm[h] = ld_part(g_qst + S_ + 1024 * h + 8 * wt); }
            STALE(1)
            SPIN_CHECK(53)
        }
        TR4(threadIdx.x == 0, 73)
#pragma unroll 1
        for (int c = wg == 2 ? 0 : 3 + wg; c < (wg == 2 ? 3 : 4 + wg); c++) {
            uint4 q[2], p[2][4];
#pragma unroll
            for (int h = 0; h < 2; h++) q[h] = lds128(sb + OFF_QT + h * 10240 + (wt >> 1) * 160 + c * 32 + (wt & 1) * 16);
            const float4 ab = lds128f(sb + M_AB + c * 16);
            mbar_spin(bars + (B_RING + c) * 8, 0);
            TR4(wt == 0, wg == 2 ? 80 + 2 * c : 74)
#pragma unroll
            for (int i = 0; i < 8; i++) p[i >> 2][i & 3] = lds128(sb + OFF_RING + c * 16384 + (i & 3) * 4096 + (i >> 2) * 2048 + (wt ^ ((wt >> 1) & 4)) * 16);
            while (RARE(__any_sync(~0u, lop3<0x7E>(q[0].x, ep, q[1].x) & 1))) {
#pragma unroll
                for (int h = 0; h < 2; h++) q[h] = ld_part(g_qT + ((64 * h + (wt >> 1)) * D_ + 5 * id + c) * 16 + 8 * (wt & 1));
                STALE(2)
                SPIN_CHECK(52)
            }
            TR4(wt == 0, wg == 2 ? 81 + 2 * c : 75)
#pragma unroll
            for (int h = 0; h < 2; h++) {
                const uint32_t qq[4] = {q[h].x, q[h].y, q[h].z, q[h].w}, r4[4] = {rs[h].x, rs[h].y, rs[h].z, rs[h].w}, n4[4] = {nm[h].x, nm[h].y, nm[h].z, nm[h].w};
                const uint4 y = add2(add2(p[h][0], p[h][1]), add2(p[h][2], p[h][3]));
                const uint32_t yy[4] = {y.x, y.y, y.z, y.w};
                uint32_t o[4];
#pragma unroll
                for (int i = 0; i < 4; i++) {
                    const uint32_t n = fma2(qq[i], r4[i], n4[i]);
                    o[i] = fma2(pack2(fmaf(blo(n), ab.y, ab.x), fmaf(bhi(n), ab.y, ab.x)), yy[i], mul2(qq[i], __float_as_uint(ab.z)));
                }
                stg128_tag(g_x1T + (size_t)(5 * id + c) * S_ + 1024 * h + 8 * wt, o[0], o[1], o[2], o[3], ep, ((5 * id + c) >> 3) & 3);
            }
        }
        warp_arrive(bars + B_XS * 8);
        TS(tid == 0, 17)
        TS(tid == 256, 52)
    }

    const uint32_t nil = pp.nil;
    const int wq = warp & 3;
    if (wg == 2) {
        TIDS
        asm volatile("setmaxnreg.dec.sync.aligned.u32 48;");
        {
            const uint32_t ep = lds32(sb + M_EP);
            uint32_t ph = 0;
            const Tile tl = ring_tile(min(4 * lane + wq, 59), grp, j);
            const uint32_t plan = bars + (B_XFULL + 10 * tl.w + tl.kb) * 8;
#pragma unroll 1
            for (int m = wq - 4; m < 60; m += 4) {
                const int n = max(m, 0);
                const uint32_t pl = __shfl_sync(~0u, plan, n >> 2), at = __shfl_sync(~0u, tl.at, n >> 2);
                const int e = (n >= 20) + (n >= 40);
                const uint32_t a = sb + OFF_XR + (n & 7) * 8192;
                uint32_t ta = a + (e == 0 ? lane * 128 + ((lane & 7) << 4) + (lane >> 3) * 4
                                 : e == 1 ? (lane & 15) * 128 + (((lane >> 4 << 1) ^ (lane & 7)) << 4) + (lane & 8) + (lane >> 4) * 4
                                          : lane * 32 + (lane >> 2) * 4);
                uint32_t tb = e == 0 ? ta ^ 32 : ta + 2048, tc = e == 2 ? ta + 1024 : ta ^ 64, td = e == 2 ? tb + 1024 : tb ^ 64;
                uint32_t live = m >= 0 && m != 40 && m != 40 + XLEAD,
                    f0 = pl;
                uint32_t f1 = m == GATE_W2 || m == GATE_W3 || m == GATE_W3B ? bars + (B_GATE + (m >= GATE_W3) + (m >= GATE_W3B)) * 8 : 0;
                if (lane) f0 = f1;
                if (lane > 1 || m < 0) f0 = 0;
                asm volatile("" : "+r"(ta), "+r"(tb), "+r"(tc), "+r"(td), "+r"(live), "+r"(f0));
                mbar_spin(bars + (m < 0 ? B_BK : B_LAND + (n & 7)) * 8, (n >> 3) & 1);
                TR5(lane == 0, n)
                while (true) {
                    uint32_t v[8];
#pragma unroll
                    for (int i = 0; i < 8; i++) v[i] = lds32(((i & 2) ? ((i & 1) ? td : tc) : (i & 1) ? tb : ta) + (i >> 2) * 4096);
                    const uint32_t bad = lop3<0xFE>(lop3<0x7E>(v[0], ep, v[1]), lop3<0x7E>(v[2], ep, v[3]), lop3<0x7E>(v[4], ep, v[5]));
                    if (!RARE(__any_sync(~0u, lop3<0xA8>(bad, lop3<0x7E>(v[6], ep, v[7]), live)))) break;
                    if (elect()) load_tile(mp, a, e, at, bars + (B_AGAIN + wq) * 8);
                    mbar_spin(bars + (B_AGAIN + wq) * 8, ph);
                    ph ^= 1;
                    STALE1(e)
                }
                TR5(lane == 0, 60 + n)
                if (f0) mbar_arrive(f0);
            }
        }
        if (wq == 0) {
#pragma unroll 1
            for (int w = 0; w < 2; w++) {
                const uint4* src = g_part + (size_t)(grp + 16 * w) * 40960;
                TR4(lane == 0, 90 + 2 * w)
                mbar_wait(bars + (B_RING + w) * 8, 1);
                TR4(lane == 0, 91 + 2 * w)
                if (elect()) {
                    const uint32_t fb = bars + (B_IN + w) * 8, rem = sb + OFF_OUT + w * 10240;
                    mbar_expect(fb, 10240);
                    bulk_ld(rem + 8192, &g_x1f[((grp + 16 * w) * 8 + j) * 640 + 512], 2048, fb);
#pragma unroll 1
                    for (int i = 0; i < 4; i++) bulk_ld(rem + i * 2048, src + ((j >> 2) + 2 * i) * 5120 + 4096 + j * 128, 2048, fb);
                }
            }
        }
#pragma unroll 1
        for (int uw = 0; uw < 2; uw++) {
            const int tile = grp + 16 * uw;
            const uint32_t ep = lds32(sb + M_EP), in = sb + OFF_OUT + uw * 10240 + wt * 16, sr = in - lane * 16;
            mbar_wait(bars + (B_IN + uw) * 8, 1);
            TR4(wt == 0, 94 + 3 * uw)
            uint4 u[4];
#pragma unroll
            for (int i = 0; i < 4; i++) u[i] = lds128(in + i * 2048);
            const uint4 base = lds128(in + 8192);
            const uint32_t ra = sb + M_F1 + (64 * uw + 16 * wq + g) * 4;
            const uint4 gr = scale16(lds64f(sb + M_GB + (64 + 2 * t) * 4), lds64f(sb + M_GB + (72 + 2 * t) * 4), __uint_as_float(lds32(ra)), __uint_as_float(lds32(ra + 32)));
            uint32_t it = 0;
            while (RARE(__any_sync(~0u, stale4(u, ep) & 1))) {
                ld_part4(u, g_part + (size_t)tile * 40960 + (j >> 2) * 5120 + 4096 + j * 128 + wt, 10240);
                STALE(3)
                if (++it > SPIN_LIMIT) SPIN_FAIL(58)
            }
            TR4(wt == 0, 95 + 3 * uw)
            const uint4 r = fin16(add2(add2(u[0], u[1]), add2(u[2], u[3])), base, gr);
            __syncwarp();
            stsm4(sr + (lane & 15) * 32 + (((lane >> 4) ^ ((lane >> 2) & 1)) << 4), r.x, r.y, r.z, r.w);
            __syncwarp();
            stg128(out + (size_t)(64 * tile + 16 * wq + (lane >> 1)) * D_ + 512 + 16 * j + 8 * (lane & 1), lds128(sr + (lane >> 1) * 32 + (((lane & 1) ^ ((lane >> 3) & 1)) << 4)));
            TR4(wt == 0, 96 + 3 * uw)
            __syncwarp();
        }
        TS(wt == 0, 21)
        if (wq == 0) {
            uint32_t it = 0;
            while (!mbar_try(bars + B_OWN * 8, 0)) { if (++it > SPIN_LIMIT) SPIN_FAIL(56) }
        }
        return;
    }

    TIDS
    const int uw = wg, tile = grp + 16 * uw, row0 = 64 * tile + 16 * wq;
    const bool leader = wt == 0; (void)leader;
    const uint32_t xfull = bars + (B_XFULL + 10 * uw) * 8, xempty = bars + B_XEMPTY * 8, wfull = bars + B_WFULL * 8, wempty = bars + B_WEMPTY * 8;
    const uint64_t dz = mkdesc(0) + pp.nil;
    auto xwait = [&](uint32_t kb, uint32_t e) { mbar_spin(xfull + kb * 8, e & 1); };
    asm volatile("setmaxnreg.inc.sync.aligned.u32 216;");
    const uint32_t ep = lds32(sb + M_EP);
    uint32_t x2[20];
    uint32_t res[20] = {};
    {
        float acc[40];
        const uint32_t la = ((lane & 7) + 8 * (lane >> 4)) * 128 + (((2 * wq + ((lane >> 3) & 1)) ^ (lane & 7)) << 4);
        auto pos = [&](int n) { return ring_pos(uw, n, LEAD1) & 7; };
        auto slot = [&](int n) { return sb + OFF_XR + pos(n) * 8192; };
        float al[2], r1[2], n1[2];
        {
            float sl[4], sq[4], v[4] = {};
            uint32_t z0[16], z1[16], zz[16];
            uint64_t bd = dz + b80_desc(dsb, 0, 0, 0), tb = (((uint64_t)8 << 32) | ((dsb + OFF_TAB) >> 4) | (7u << 16)) + pp.nil;
            auto ldfrag = [&](uint32_t (&z)[16], int n, bool even) {
#pragma unroll
                for (int q = 0; q < 4; q++) ldsm4t(slot(n) + la + q * 2048, z[4 * q], z[4 * q + 1], z[4 * q + 2], z[4 * q + 3]);
#pragma unroll
                for (int q = 0; q < 4; q++) ldsm4t_if(n == j >> 1, slot(n) + la + q * 2048, &res[4 * q]);
                if (even) ldsm4t_if(n == 4 && !((j ^ (j >> 2)) & 1), slot(n) + la + (j & 3) * 2048, &res[16]);
            };
            auto tile1 = [&](const uint32_t (&zc)[16], uint32_t (&zn)[16], int n, int h) {
                const bool last = h && n == 5, ok = mbar_test(xfull + (n + 1) * 8, 0), okw = !h || mbar_test(wfull + ((n + 1) >> 1) * 8, 0);
                wg_fence();
#pragma unroll
                for (int q = 0; q < 2; q++) wgmma_rs80(acc, zc[4 * q], zc[4 * q + 1], zc[4 * q + 2], zc[4 * q + 3], bd + q * B80_STEP, 1);
                wg_commit();
                if (lane < 2) mbar_arrive_after(xempty + pos(n) * 8, res[12], res[16], nil);
                wg_wait<1>();
                if (!h && n && lane == 0) mbar_arrive(wempty + ((n >> 1) - 1) * 8);
                if (!ok) xwait(n + 1, 0);
                if (!last) ldfrag(zn, n + 1, h);
#pragma unroll
                for (int e = 0; e < 16; e++) zz[e] = mul2(zc[e], zc[e]);
                const uint64_t t0 = last ? ((uint64_t)8 << 32) | ((dsb + M_NUL) >> 4) : tb;
                const uint32_t ts = last ? 0 : 14;
                wg_fence();
#pragma unroll
                for (int q = 0; q < 4; q++) wgmma_rs8(sl, zc[4 * q], zc[4 * q + 1], zc[4 * q + 2], zc[4 * q + 3], t0 + q * ts, 1);
#pragma unroll
                for (int q = 0; q < 4; q++) wgmma_rs8(sq, zz[4 * q], zz[4 * q + 1], zz[4 * q + 2], zz[4 * q + 3], t0 + q * ts, 1);
#pragma unroll
                for (int q = 2; q < 4; q++) wgmma_rs80(acc, zc[4 * q], zc[4 * q + 1], zc[4 * q + 2], zc[4 * q + 3], bd + q * B80_STEP, 1);
                wg_commit();
                tb += 56;
                bd = bd + (uint64_t)B80_HALF;
                if (!okw) mbar_spin(wfull + ((n + 1) >> 1) * 8, 0);
                TR(leader, 100 + 10 * uw + n)
            };
            zero(acc); zero(sl); zero(sq);
            mbar_spin(bars + B_TAB * 8, 0);
            float4 k = lds128f(sb + M_KS);
            float k4 = __uint_as_float(lds32(sb + M_KS + 16));
#pragma unroll
            for (int w = 1; w < 5; w++) {
                const float4 o = lds128f(sb + M_KS + w * 32);
                k.x += o.x; k.y += o.y; k.z += o.z; k.w += o.w; k4 += __uint_as_float(lds32(sb + M_KS + w * 32 + 16));
            }
            uint32_t fa[4];
            auto coefs = [&]() {
                mbar_spin(bars + (B_SUMS + uw) * 8, 0);
                TS(leader && !uw, 10)
                const float4 o = lds128f(sb + OFF_ROW + uw * 2048 + wt * 16);
                v[0] += o.x; v[1] += o.y; v[2] += o.z; v[3] += o.w;
#pragma unroll
                for (int h = 0; h < 2; h++) {
                    const int l0 = lane & ~3;
                    const float s1 = __shfl_sync(~0u, v[2 * h], l0), s2 = __shfl_sync(~0u, v[2 * h], l0 + 1), scc = __shfl_sync(~0u, v[2 * h], l0 + 2);
                    const float scs = __shfl_sync(~0u, v[2 * h + 1], l0 + 2), sc = __shfl_sync(~0u, v[2 * h], l0 + 3), sqq = __shfl_sync(~0u, v[2 * h + 1], l0 + 3);
                    const float m1 = s1 * (1.f / D_), va = fmaxf(s2 * (1.f / D_) - m1 * m1, 0.f) + 1e-5f, r = rsqrtf(va);
                    const float m2 = (r * (sc - m1 * k.x) + k.y) * (1.f / D_);
                    const float e2 = (r * (r * (sqq + m1 * (m1 * k.z - 2.f * scc)) + 2.f * (scs - m1 * k.w)) + k4) * (1.f / D_);
                    al[h] = r * 0.5f * rsqrtf(fmaxf(e2 - m2 * m2, 0.f) + 1e-5f); r1[h] = r; n1[h] = -m1 * r;
                    const uint32_t fb = split2(va * r), fx = split2(t == 3 ? -m2 * va * r : -m1), fc = __shfl_sync(~0u, fx, lane | 3);
                    fa[h] = __byte_perm(fx, fb, t == 1 ? 0x5432 : t == 2 ? 0x7654 : 0x1010);
                    fa[2 + h] = t ? 0 : fc >> 16;
                }
            };
            mbar_spin(wfull, 0);
            xwait(0, 0);
            TS(leader, 32 + uw)
            ldfrag(z0, 0, false);
#pragma unroll 1
            for (int n = 0; n < 6; n += 2) { tile1(z0, z1, n, 0); tile1(z1, z0, n + 1, 1); }
#pragma unroll
            for (int n = 6; n < 10; n++) {
                const uint64_t ad = dz + (((dsb + OFF_XR + pos(n) * 8192) >> 4) | 0x10000u);
                const bool ok = n == 9 || mbar_test(xfull + (n + 1) * 8, 0), okw = n != 7 || mbar_test(wfull + 4 * 8, 0);
                wg_fence();
#pragma unroll
                for (int q = 0; q < 4; q++) wgmma_ss80t(acc, ad + q * 128, bd + q * B80_STEP, 1);
                wg_commit();
                bd = bd + (uint64_t)B80_HALF;
                if (n == 8) coefs();
                if (n == 9) ldsm4t_if(9 - (j & 1) == 8 + (j >> 2), slot(9) + la + (j & 3) * 2048, &res[16]);
                wg_wait<1>();
                if (n > 6 && lane < 2) mbar_arrive(xempty + pos(n - 1) * 8);
                if (!(n & 1) && lane == 0) mbar_arrive(wempty + ((n >> 1) - 1) * 8);
                if (n == 6) {
                    reg_fence(sl); reg_fence(sq);
#pragma unroll
                    for (int e = 0; e < 2; e++) {
                        v[2 * e] = t == 0 ? sl[2 * e] + sl[2 * e + 1] : t == 1 ? sq[2 * e] + sq[2 * e + 1] : sl[2 * e];
                        v[2 * e + 1] = t == 2 ? sl[2 * e + 1] : sq[2 * e];
                    }
                    st_peer(peer_addr(sb + OFF_ROW + uw * 2048 + wt * 16), __float_as_uint(v[0]), __float_as_uint(v[1]), __float_as_uint(v[2]), __float_as_uint(v[3]), peer_addr(bars + (B_SUMS + uw) * 8));
                    TS(leader && !uw, 59)
                }
                if (!ok) xwait(n + 1, 0);
                if (!okw) mbar_spin(wfull + 4 * 8, 0);
                TR(leader, 100 + 10 * uw + n)
            }
            mbar_spin(bars + B_VEC * 8, 0);
            wg_fence();
            wgmma_rs80k(acc, fa[0], fa[1], fa[2], fa[3], ((uint64_t)8 << 32) | ((dsb + OFF_F1) >> 4) | (((M_F1 - OFF_F1) >> 4) << 16), 1);
            wg_commit();
        }
        wg_wait<0>();
        reg_fence(acc);
        if (lane < 2) mbar_arrive_after(xempty + pos(9) * 8, res[16], 0, nil);
        if (lane == 0) mbar_arrive(wempty + 4 * 8);
        TS(leader, 34 + uw)
        {
            bf16* const trow = g_t + (size_t)(row0 + g + 2) * D_;
#pragma unroll
            for (int b = 0; b < 3; b++) {
                uint32_t p[8];
#pragma unroll
                for (int ii = 0; ii < 4; ii++) {
                    const int i = 4 * b + ii;
                    if (i >= 10) continue;
#pragma unroll
                    for (int h = 0; h < 2; h++) p[(i & 3) + 4 * h] = pack2(gelu2(acc[4 * i + 2 * h] * al[h]), gelu2(acc[4 * i + 2 * h + 1] * al[h]));
                }
                if (b < 2) {
                    const int gr = (2 * j + b) / 5, sh = (gr & 1) ? -1 - (gr >> 1) : 1 + (gr >> 1);
                    bf16* dst = trow + 64 * j + 32 * b + 8 * t;
                    const int w = (((g + sh) >> 2) & 2) + (t >> 1);
                    stg128_tag(dst + sh * D_, p[0], p[1], p[2], p[3], ep, w);
                    stg128_tag(dst + (sh + 8) * D_, p[4], p[5], p[6], p[7], ep, w ^ 2);
                    if (row0 + g < sh || row0 + g + 8 >= S_ + sh) stg128_tag(dst + (sh > 0 ? 0 : 8) * D_, 0, 0, 0, 0, ep, (sh > 0 ? 0 : 2) + (t >> 1));
                } else {
                    bf16* dst = trow + 512 + 16 * j + 4 * t;
                    const uint32_t lo = t == (g < 2), hi = t == (g >= 2), o = j & 1;
                    stg64(dst - 2 * D_, lop3<0xB8>(p[0], lo & ~o, ep), lop3<0xB8>(p[1], lo & o, ep));
                    stg64(dst + 6 * D_, lop3<0xB8>(p[4], hi & ~o, ep), lop3<0xB8>(p[5], hi & o, ep));
                    if (row0 + g + 8 >= S_ - 2) stg64(dst + 8 * D_, ep & (t == 1) & ~o, ep & (t == 1) & o);
                }
            }
        }
        signal_cnt(&g_cnt.g1[tile * 32], lane, 1, true);
        TS(leader, 36 + uw)
#pragma unroll
        for (int i = 0; i < 10; i++) {
            const float2 c = lds64f(sb + M_C + (8 * i + 2 * t) * 4), s = lds64f(sb + M_SB + (8 * i + 2 * t) * 4);
#pragma unroll
            for (int h = 0; h < 2; h++) {
                acc[4 * i + 2 * h] = fmaf(blo(res[2 * i + h]), r1[h], fmaf(n1[h], c.x, s.x));
                acc[4 * i + 2 * h + 1] = fmaf(bhi(res[2 * i + h]), r1[h], fmaf(n1[h], c.y, s.y));
            }
        }
        mbar_spin(wfull + 5 * 8, 0);
        xwait(0, 1);
        TS(leader, 22 + uw)
        uint32_t xo = 32 + 16 * uw, xp = 0;
        const uint64_t ax = dz + (((dsb + OFF_XR) >> 4) | 0x10000u);
        uint64_t ad = ax + xo * 64, bd = dz + b80_desc(dsb, 5, 0, 0);
#pragma unroll 1
        for (int i = 0; i < 5; i++) {
            const uint32_t x1 = xfull + (1 + 2 * i) * 8, p1 = 1, x2 = xfull + min(2 + 2 * i, 9) * 8, p2 = 1;
            const uint32_t w2 = wfull + (min(6 + i, 9) & 7) * 8, pw = i >= 2;
            const bool ok1 = mbar_test(x1, p1);
            wg_fence();
#pragma unroll
            for (int q = 0; q < 4; q++) wgmma_ss80(acc, ad + q * 2, bd + q * B80_STEP, 1);
            wg_commit();
            wg_wait<1>();
            if (lane < 2 && i) mbar_arrive(xempty + xp);
            if (lane == 0 && i) mbar_arrive(wempty + ((4 + i) & 7) * 8);
            if (!ok1) mbar_spin(x1, p1);
            const bool ok2 = mbar_test(x2, p2), okw = mbar_test(w2, pw);
            wg_fence();
#pragma unroll
            for (int q = 0; q < 4; q++) wgmma_ss80(acc, ad + 512 + q * 2, bd + (uint64_t)(B80_HALF + q * B80_STEP), 1);
            wg_commit();
            const uint32_t xc = xo;
            xp = xo + 8; xo = (xo + 16) & 48;
            ad = ax + xo * 64;
            bd += i == 2 ? 2 * B80_HALF - 8192 + (8192ll << 16) : 2 * B80_HALF;
            asm volatile("" : "+l"(ad), "+l"(bd));
            wg_wait<1>();
            if (lane < 2) mbar_arrive(xempty + xc);
            if (!ok2) mbar_spin(x2, p2);
            if (!okw) mbar_spin(w2, pw);
            TR(leader, (uw ? 86 : 20) + 2 * i)
        }
        wg_wait<0>();
        reg_fence(acc);
        if (lane < 2) mbar_arrive(xempty + xp);
        if (lane == 0) mbar_arrive(wempty + (9 & 7) * 8);
        TS(leader, 38 + uw)
        float a0 = 0.f, b0 = 0.f, a1 = 0.f, b1 = 0.f;
#pragma unroll
        for (int i = 0; i < 5; i++) {
            uint32_t* p = &x2[4 * i];
#pragma unroll
            for (int e = 0; e < 4; e++) p[e] = pack2(acc[8 * i + 2 * e], acc[8 * i + 2 * e + 1]);
#pragma unroll
            for (int e = 0; e < 4; e++) p[e] = lop3<0xB8>(p[e], (((wt >> 3) ^ (wt << 2)) & 7) == e, ep);
            stg128(&g_x2f[(tile * 40 + (i < 4 ? 4 * j + i : 32 + j)) * 128 + wt], p[0], p[1], p[2], p[3]);
#pragma unroll
            for (int e = 0; e < 8; e += 4) {
                const float* u = &acc[8 * i + e];
                a0 += u[0] + u[1]; b0 = fmaf(u[0], u[0], fmaf(u[1], u[1], b0));
                a1 += u[2] + u[3]; b1 = fmaf(u[2], u[2], fmaf(u[3], u[3], b1));
            }
        }
#pragma unroll
        for (int o = 1; o < 4; o *= 2) {
            a0 += __shfl_xor_sync(~0u, a0, o); b0 += __shfl_xor_sync(~0u, b0, o);
            a1 += __shfl_xor_sync(~0u, a1, o); b1 += __shfl_xor_sync(~0u, b1, o);
        }
        if (t < 2) stg64(&g_stats[(tile * 8 + j) * 64 + 16 * wq + g + 8 * t], tag(__float_as_uint(t ? a1 : a0), ep), __float_as_uint(t ? b1 : b0));
        signal_cnt(&g_cnt.g2[tile * 32], lane, 1, true);
        TS(leader, 40 + uw)
#pragma unroll
        for (int i = 0; i < 10; i++) {
            const float2 c = lds64f(sb + M_GB + (8 * i + 2 * t) * 4), e = lds64f(sb + M_CI + (8 * i + 2 * t) * 4);
#pragma unroll
            for (int h = 0; h < 2; h++)
                res[2 * i + h] = fma2(pack2(c.x, c.y), x2[2 * i + h], pack2(e.x * blo(res[2 * i + h]), e.y * bhi(res[2 * i + h])));
        }
#pragma unroll
        for (int i = 0; i < 20; i++) asm volatile("" : "+r"(res[i]));
    }
    float acc0[64], acc1[44];
    float2 q[4];
    {
        uint4 f0, f1, f2, f3;
        auto xseq = [&](int kb) { return ring_pos(uw, kb, XLEAD) & 7; };
        auto step = [&](const uint4& f, uint64_t bd) {
            wg_fence();
            wgmma_rs128(acc0, f.x, f.y, f.z, f.w, bd, 1);
            wgmma_rs88(acc1, f.x, f.y, f.z, f.w, bd + 512, 1);
            wg_commit();
        };
        const uint32_t xa = sb + OFF_XR + wt * 16;
        const float2* const gs = &g_stats[(tile * 8 + 2 * t) * 64 + 16 * wq + g];
        zero(acc0); zero(acc1);
        uint32_t xs = 0;
        f0 = make_uint4(x2[0], x2[1], x2[2], x2[3]); f1 = make_uint4(x2[4], x2[5], x2[6], x2[7]);
        f2 = make_uint4(x2[8], x2[9], x2[10], x2[11]); f3 = make_uint4(x2[12], x2[13], x2[14], x2[15]);
#pragma unroll
        for (int i = 0; i < 4; i++) q[i] = make_float2(0.f, 0.f);
        mbar_spin(wempty + (9 & 7) * 8, 1);
        mbar_spin(wfull + (10 & 7) * 8, (10 >> 3) & 1);
#pragma unroll 1
        for (int kb = 0; kb < 10; kb++) {
            const uint32_t wn = 10 + 2 * kb;
            const uint64_t bd = dz + (((dsb + OFF_W + (wn & 7) * 16384) >> 4) | (256u << 16));
            step(f0, bd);
            wg_wait<1>();
            if (kb && lane == 0) mbar_arrive(wempty + ((wn - 1) & 7) * 8);
            lds128_if(kb, f2, xa + xs * 8192 + 4096); lds128_if(kb, f3, xa + xs * 8192 + 6144);
            const bool w1 = mbar_test(wfull + ((wn + 1) & 7) * 8, (wn >> 3) & 1), x1 = kb < 9 && mbar_test(xfull + (kb + 1) * 8, 0);
            step(f1, bd + 128);
            if (!w1) mbar_spin(wfull + ((wn + 1) & 7) * 8, (wn >> 3) & 1);
            step(f2, bd + 1024);
            if (lane < 2 && kb) mbar_arrive_after(xempty + xs * 8, f2.x, f3.x, nil);
            wg_wait<1>();
            if (lane == 0) mbar_arrive(wempty + (wn & 7) * 8);
            xs = xseq(kb + 1);
            if (x1) { f0 = lds128(xa + xs * 8192); f1 = lds128(xa + xs * 8192 + 2048); }
            const bool w2 = mbar_test(wfull + ((wn + 2) & 7) * 8, ((wn + 2) >> 3) & 1);
            step(f3, bd + 1152);
            if (kb < 9 && !x1) { xwait(kb + 1, 2); f0 = lds128(xa + xs * 8192); f1 = lds128(xa + xs * 8192 + 2048); }
            if (!w2) mbar_spin(wfull + ((wn + 2) & 7) * 8, ((wn + 2) >> 3) & 1);
            if (kb == 0) {
                TS(leader, 42 + uw)
#pragma unroll
                for (int i = 0; i < 4; i++) q[i] = ld_stat(gs + (i & 1) * 64 + 8 * (i >> 1));
            }
            if (kb == 4) {
                uint32_t it = 0;
                while (RARE(__any_sync(~0u, ((__float_as_uint(q[0].x) ^ ep) | (__float_as_uint(q[1].x) ^ ep) | (__float_as_uint(q[2].x) ^ ep) | (__float_as_uint(q[3].x) ^ ep)) & 1))) {
#pragma unroll
                    for (int i = 0; i < 4; i++) q[i] = ld_stat(gs + (i & 1) * 64 + 8 * (i >> 1));
                    SPIN_CHECK(49)
                }
                float a0 = q[0].x + q[1].x, b0 = q[0].y + q[1].y, a1 = q[2].x + q[3].x, b1 = q[2].y + q[3].y;
#pragma unroll
                for (int o = 1; o < 4; o *= 2) {
                    a0 += __shfl_xor_sync(~0u, a0, o); b0 += __shfl_xor_sync(~0u, b0, o);
                    a1 += __shfl_xor_sync(~0u, a1, o); b1 += __shfl_xor_sync(~0u, b1, o);
                }
                a0 *= 1.f / D_; a1 *= 1.f / D_;
                const float r0 = 0.5f * rsqrtf(fmaxf(b0 * (1.f / D_) - a0 * a0, 0.f) + 1e-5f), r1 = 0.5f * rsqrtf(fmaxf(b1 * (1.f / D_) - a1 * a1, 0.f) + 1e-5f);
                const uint32_t sel = t == 0 ? 0x1010 : t == 1 ? 0x4432 : 0x4444;
                if (t == 0) { sts32(sb + M_F1 + (64 * uw + 16 * wq + g) * 4, __float_as_uint(r0)); sts32(sb + M_F1 + (64 * uw + 16 * wq + g + 8) * 4, __float_as_uint(r1)); }
                q[2] = make_float2(8.f * 0.0356774081f * r0 * r0 * r0, 2.f * 0.7978845608f * r0);
                q[3] = make_float2(8.f * 0.0356774081f * r1 * r1 * r1, 2.f * 0.7978845608f * r1);
                q[1] = make_float2(__uint_as_float(__byte_perm(split2(-a0), 0, sel)), __uint_as_float(__byte_perm(split2(-a1), 0, sel)));
            }
            if (kb == 6) {
#pragma unroll
                for (int i = 0; i < 5; i++) stg128(&g_x1f[(tile * 8 + j) * 640 + i * 128 + wt], res[4 * i], res[4 * i + 1], res[4 * i + 2], res[4 * i + 3]);
            }
            if (kb == 8) asm volatile("fence.proxy.async.global;" ::: "memory");
            TR(leader, 10 * uw + kb)
        }
        const uint64_t fd = ((uint64_t)8 << 32) | ((dsb + OFF_W + 6 * 16384) >> 4);
        wg_fence();
        wgmma_rs128k(acc0, __float_as_uint(q[1].x), __float_as_uint(q[1].y), 0, 0, fd, 1);
        wgmma_rs88k(acc1, __float_as_uint(q[1].x), __float_as_uint(q[1].y), 0, 0, fd + 128, 1);
        wg_commit();
        if (lane == 0) {
            mbar_arrive(bars + B_XFREE * 8);
            asm volatile("mbarrier.arrive.shared::cluster.b64 _, [%0];" ::"r"(peer_addr(bars + B_XFREE * 8)) : "memory");
        }
    }
    const uint32_t recv = sb + recv_off(uw) + wt * 16;
    uint32_t ha[48] = {}, hb[48], hx[12];
    uint64_t wb = dz + (((dsb + OFF_W) >> 4) | (512u << 16));
    auto wdesc = [&](int n) { return wb + (n & 7) * 1024; };
    auto wwait = [&](int n) { mbar_spin(wfull + (n & 7) * 8, (n >> 3) & 1); };
    auto wfree = [&](int n) { if (lane == 0) mbar_arrive(wempty + (n & 7) * 8); };
    auto fresh = [&]() { wb += pp.nil; asm volatile("" : "+l"(wb)); };
    uint32_t pk[32];
    {
        float P0[64];
        const float2 r0 = q[2], r1 = q[3];
        const uint32_t ra = peer_addr(recv), rb = peer_addr(bars + (B_RECV + 4 * uw) * 8);
        auto conv32 = [&](const float* v, int b) {
#pragma unroll
            for (int i = 0; i < 4; i++) {
                ha[8 * b + 2 * i] = pack2(gelu2r(v[4 * i], r0), gelu2r(v[4 * i + 1], r0));
                ha[8 * b + 2 * i + 1] = pack2(gelu2r(v[4 * i + 2], r1), gelu2r(v[4 * i + 3], r1));
            }
#pragma unroll
            for (int s = 2 * b; s < 2 * b + 2; s++) st_peer(ra + s * 2048, ha[4 * s], ha[4 * s + 1], ha[4 * s + 2], ha[4 * s + 3], rb + (b >> 1) * 8);
        };
        auto fetch = [&](int k) {
            mbar_spin(bars + (B_RECV + 4 * uw + k) * 8, 0);
#pragma unroll
            for (int s = 4 * k; s < 4 * k + 4; s++) { const uint4 x = lds128(recv + s * 2048); hb[4 * s] = x.x; hb[4 * s + 1] = x.y; hb[4 * s + 2] = x.z; hb[4 * s + 3] = x.w; }
        };
        auto stage = [&](int n, const uint32_t* a, int steps, int sc) {
            wwait(n);
            wg_fence();
#pragma unroll
            for (int s = 0; s < steps; s++) wgmma_rs128(P0, a[4 * s], a[4 * s + 1], a[4 * s + 2], a[4 * s + 3], wdesc(n) + s * 128, sc || s);
            wg_commit();
        };
        wg_wait<0>();
        reg_fence(acc0); reg_fence(acc1);
        wfree(29); wfree(30);
        TS(leader, 44 + uw)
        if (uw) bar_sync(13, 256);
        uint32_t hr[6];
#pragma unroll
        for (int i = 0; i < 6; i++) {
            const float2 r = (i & 1) ? r1 : r0;
            hr[i] = pack2(gelu2r(acc1[32 + 2 * i], r), gelu2r(acc1[33 + 2 * i], r));
        }
        if (uw) mbar_spin(bars + B_XFREE * 8, 0);
        st_peer(ra + 24576, hr[0], hr[1], hr[2], hr[3], rb + 24);
        asm volatile("st.async.shared::cluster.mbarrier::complete_tx::bytes.v2.b32 [%0], {%1, %2}, [%3];" ::"r"(ra + 26624 - wt * 8), "r"(hr[4]), "r"(hr[5]), "r"(rb + 24) : "memory");
        conv32(&acc1[0], 4);
        conv32(&acc1[16], 5);
        TS(leader, 46 + uw)
        stage(31, &ha[32], 4, 0);
#pragma unroll
        for (int b = 0; b < 4; b++) {
            conv32(&acc0[16 * b], b);
            if (b == 0 && !uw) asm volatile("bar.arrive 13, 256;" ::: "memory");
            if (b == 3) {
                fetch(2);
                mbar_spin(bars + (B_RECV + 4 * uw + 3) * 8, 0);
                const uint4 x = lds128(recv + 24576);
                const uint2 y = lds64(recv + 26624 - wt * 8);
                const uint32_t hp[6] = {x.x, x.y, x.z, x.w, y.x, y.y};
#pragma unroll
                for (int i = 0; i < 6; i++) { hx[i] = (j & 1) ? hp[i] : hr[i]; hx[6 + i] = (j & 1) ? hr[i] : hp[i]; }
            }
            if (!(b & 1)) wwait(32 + (b >> 1));
            wg_fence();
#pragma unroll
            for (int s = 0; s < 2; s++) wgmma_rs128(P0, ha[8 * b + 4 * s], ha[8 * b + 4 * s + 1], ha[8 * b + 4 * s + 2], ha[8 * b + 4 * s + 3], wdesc(32 + (b >> 1)) + (2 * (b & 1) + s) * 128, 1);
            wg_commit();
            if (!(b & 1)) { wg_wait<1>(); wfree(31 + (b >> 1)); }
        }
        TR(leader, 64 + 10 * uw)
        fresh();
        stage(34, &hb[32], 4, 1); wg_wait<1>(); wfree(33);
        fetch(0);
        stage(35, hx, 3, 1); wg_wait<1>(); wfree(34);
        fetch(1);
        stage(36, &hb[0], 4, 1); wg_wait<1>(); wfree(35);
        stage(37, &hb[16], 4, 1); wg_wait<1>(); wfree(36);
        wg_wait<0>();
        reg_fence(P0);
        pack_part<64>(pk, P0, ep);
        uint32_t all = 0;
#pragma unroll
        for (int i = 0; i < 32; i++) all |= pk[i];
        if (lane == 0) mbar_arrive_after(wempty + (37 & 7) * 8, all, 0, nil);
        TR(leader, 65 + 10 * uw)
    }
    {
        uint4* const dst = g_part + (size_t)(tile * 8 + j) * 5120 + wt;
        const uint4* const src = g_part + (size_t)tile * 40960 + j * 512 + wt;
        float F[2][32];
        uint4 gb[4];
        float rr[2];
        float2 gf[8];
        uint4 base[4], u1[4], u2[4], u3[4];
#pragma unroll
        for (int c = 2; c < 5; c++) {
            float (&P)[32] = F[c & 1];
            fresh();
#pragma unroll
            for (int s = 0; s < 27; s++) {
                const int e = s < 8 ? 0 : s < 15 ? 1 : s < 23 ? 2 : 3, o = s - (e == 0 ? 0 : e == 1 ? 8 : e == 2 ? 15 : 23), n = 30 + 4 * c + e;
                const uint32_t* a = s < 12 ? &ha[4 * s] : s < 15 ? &hx[4 * (s - 12)] : &hb[4 * (s - 15)];
                if (o == 0) wwait(n);
                if (o == 0 || s == 1) wg_fence();
                wgmma_rs64(P, a[0], a[1], a[2], a[3], wdesc(n) + o * 128, s);
                if (o == 0) { wg_commit(); wg_wait<1>(); if (c > 2 || s) wfree(n - 1); }
                if (s == 0 && c > 2) { reg_fence(F[~c & 1]); pack_part<32>(pk, F[~c & 1], ep); }
                if (c == 2 && s % 3 == 0 && s < 24) st_part(dst + g4_block(s / 12, j) * 512 + (s / 3 & 3) * 128, &pk[4 * (s / 3)]);
                if (c == 3 && s % 4 == 1 && s < 16) st_part(dst + g4_block(2, j) * 512 + s / 4 * 128, &pk[4 * (s / 4)]);
                if (c == 4 && s < 4) st_part(dst + g4_block(3, j) * 512 + s * 128, &pk[4 * s]);
                if (c == 4 && s >= 4 && s < 8) base[s - 4] = ldcg128(&g_x1f[(tile * 8 + j) * 640 + (s - 4) * 128 + wt]);
                if (c == 4 && s >= 15 && s < 19) { const int i = s - 15; gf[2 * i] = lds64f(sb + M_GB + (16 * i + 2 * t) * 4); gf[2 * i + 1] = lds64f(sb + M_GB + (16 * i + 8 + 2 * t) * 4); }
                if (c == 4 && s >= 12 && s < 14) rr[s - 12] = __uint_as_float(lds32(sb + M_F1 + (64 * uw + 16 * wq + g + 8 * (s - 12)) * 4));
                if (c == 4 && s >= 8 && s < 12) u1[s - 8] = ld_part(src + (j ^ 6) * 5120 + (s - 8) * 128);
                if (c == 4 && s >= 19 && s < 23) u2[s - 19] = ld_part(src + (j ^ 4) * 5120 + (s - 19) * 128);
                if (c == 4 && s >= 23) u3[s - 23] = ld_part(src + (j ^ 2) * 5120 + (s - 23) * 128);
                if (27 * (c - 2) + s == R_GATE && lane == 0) mbar_arrive(bars + (B_RING + uw) * 8);
                if (s == 7 || s == 14 || s == 22 || s == 26) wg_commit();
                if (c == 4) { TR(leader && s == 7, 68 + 10 * uw) TR(leader && s == 14, 69 + 10 * uw) TR(leader && s == 22, 70 + 10 * uw) }
            }
            TR(leader, 64 + c + (c == 4 ? 3 : 0) + 10 * uw)
        }
        float (&O)[32] = F[0];
#pragma unroll
        for (int i = 0; i < 4; i++) gb[i] = scale16(gf[2 * i], gf[2 * i + 1], rr[0], rr[1]);
        uint32_t it = 0;
        while (__any_sync(~0u, (stale4(u1, ep) | stale4(u2, ep) | stale4(u3, ep)) & 1)) {
            STALE(__any_sync(~0u, stale4(u1, ep) & 1) ? 4 : __any_sync(~0u, stale4(u2, ep) & 1) ? 5 : 6)
            ld_part4(u1, src + (j ^ 6) * 5120, 128); ld_part4(u2, src + (j ^ 4) * 5120, 128); ld_part4(u3, src + (j ^ 2) * 5120, 128);
            SPIN_CHECK(58)
        }
        TR(leader, 73 + 10 * uw)
#pragma unroll
        for (int i = 0; i < 4; i++) u1[i] = add2(add2(u1[i], u2[i]), u3[i]);
        TS(leader, 50 + uw)
        wg_wait<0>();
        reg_fence(O);
        TS(leader, 48 + uw)
        const uint32_t so = sb + recv_off(uw) + wq * 2048;
#pragma unroll
        for (int i = 0; i < 4; i++) {
            const float* o = &O[8 * i];
            const uint4 r = fin16(add2(u1[i], make_uint4(pack2(o[0], o[1]), pack2(o[2], o[3]), pack2(o[4], o[5]), pack2(o[6], o[7]))), base[i], gb[i]);
            stsm4(so + (lane & 15) * 128 + (((2 * i + (lane >> 4)) ^ (lane & 7)) << 4), r.x, r.y, r.z, r.w);
        }
        TR4(leader, 100 + uw)
        __syncwarp();
#pragma unroll
        for (int i = 0; i < 4; i++) {
            const int row = (lane >> 3) + 4 * i;
            stg128(out + (size_t)(row0 + row) * D_ + 64 * j + 8 * (lane & 7), lds128(so + row * 128 + (((lane & 7) ^ (row & 7)) << 4)));
        }
        TS(leader, 24 + uw)
        warp_arrive(bars + B_OWN * 8);
    }
}

typedef CUresult (*EncFn)(CUtensorMap*, CUtensorMapDataType, cuuint32_t, void*, const cuuint64_t*, const cuuint64_t*, const cuuint32_t*,
                          const cuuint32_t*, CUtensorMapInterleave, CUtensorMapSwizzle, CUtensorMapL2promotion, CUtensorMapFloatOOBfill);

static void enc(EncFn fn, CUtensorMap* m, void* p, int rank, const cuuint64_t* dims, const cuuint64_t* strides, const cuuint32_t* box, bool plain = false) {
    const CUtensorMapSwizzle sw = box[0] > 64 || plain ? CU_TENSOR_MAP_SWIZZLE_NONE : CU_TENSOR_MAP_SWIZZLE_128B;
    cuuint32_t es[5] = {1, 1, 1, 1, 1};
    CUresult r = fn(m, CU_TENSOR_MAP_DATA_TYPE_BFLOAT16, rank, p, dims, strides, box, es, CU_TENSOR_MAP_INTERLEAVE_NONE, sw,
                    CU_TENSOR_MAP_L2_PROMOTION_L2_128B, CU_TENSOR_MAP_FLOAT_OOB_FILL_NONE);
    (void)r;
}
static void enc2(EncFn fn, CUtensorMap* m, void* p, uint64_t cols, uint64_t rows, uint32_t bc, uint32_t br, bool plain = false) {
    cuuint64_t dims[2] = {cols, rows}, st[1] = {cols * 2};
    cuuint32_t box[2] = {bc, br};
    enc(fn, m, p, 2, dims, st, box, plain);
}

extern "C" void kernel_launch(void* const* d_in, const int* in_sizes, int n_in, void* d_out, int out_size) {
    static Maps mp;
    static Ptrs pp;
    static void* cached[13];
    bool same = true;
    for (int i = 0; i < 13; i++) same = same && (cached[i] == d_in[i]);
    if (!same) {
        void* fnp = nullptr;
        cudaDriverEntryPointQueryResult qr;
        cudaGetDriverEntryPoint("cuTensorMapEncodeTiled", &fnp, cudaEnableDefault, &qr);
        EncFn fn = (EncFn)fnp;
        cudaGetSymbolAddress((void**)&pp.s, g_scratch);
        void *x1T = g_x1T, *t = g_t;
        cuuint64_t dq[3] = {64, S_, 10}, sq[2] = {D_ * 2, 128};
        cuuint32_t bq[3] = {64, 16, 10};
        enc(fn, &mp.q, d_in[0], 3, dq, sq, bq);
        enc2(fn, &mp.k, d_in[1], D_, S_, 80, 67); enc2(fn, &mp.v, d_in[2], D_, S_, 80, 64);
        enc2(fn, &mp.qT, g_qT, 16 * D_, 128, 80, 128);
        enc2(fn, &mp.x[0], x1T, S_, D_, 64, 64); enc2(fn, &mp.x[1], (bf16*)t + 2 * D_, D_, S_, 64, 64);
        enc2(fn, &mp.x[2], g_x2f, 64, 320 * 64, 64, 64, true);
        enc2(fn, &mp.w1, d_in[7], D_, D_, 64, 64); enc2(fn, &mp.w1h, d_in[7], D_, D_, 64, 160); enc2(fn, &mp.w3h, d_in[9], F_, D_, 64, 160);
        enc2(fn, &mp.wmod, d_in[12], 6 * D_, D_, 64, 160);
        const cuuint64_t R = D_ * 2;
        cuuint64_t da[5] = {D_, 2, 4, 4, 16}, sa[4] = {R, 8 * R, 2 * R, 32 * R}, db[5] = {D_, 2, 2, 4, 8}, sb[4] = {R, 8 * R, 2 * R, 16 * R};
        cuuint32_t ba[5] = {64, 2, 4, 4, 2}, bb[5] = {64, 2, 2, 4, 4};
        enc(fn, &mp.w2a, d_in[8], 5, da, sa, ba); enc(fn, &mp.w2b, (bf16*)d_in[8] + 512 * D_, 5, db, sb, bb);
        cuuint64_t dw[3] = {64, D_, 27}, sw[2] = {F_ * 2, 128};
        cuuint32_t bw[3] = {64, 32, 3};
        enc(fn, &mp.w3a, d_in[9], 3, dw, sw, bw);
        enc2(fn, &mp.w3b, d_in[9], F_, D_, 24, 32);
        enc2(fn, &mp.w4[0], d_in[10], D_, F_, 64, 64); enc2(fn, &mp.w4[1], d_in[10], D_, F_, 64, 48);
        pp.q = (const bf16*)d_in[0]; pp.w_mod = (const bf16*)d_in[12]; pp.shift_k = (const bf16*)d_in[3];
        pp.ssm_k = (const bf16*)d_in[4]; pp.ssm_D = (const bf16*)d_in[5]; pp.w1 = (const bf16*)d_in[7]; pp.w2 = (const bf16*)d_in[8];
        pp.w4 = (const bf16*)d_in[10]; pp.c = (const bf16*)d_in[11];
        cudaFuncSetAttribute(fused_kernel, cudaFuncAttributeMaxDynamicSharedMemorySize, SMEM_BYTES);
        for (int i = 0; i < 13; i++) cached[i] = d_in[i];
    }
    fused_kernel<<<NCTA, NTHR, SMEM_BYTES, cudaStreamPerThread>>>(pp, (bf16*)d_out, mp);
}
```

```cpp
#include <cuda_runtime.h>
#include <cuda_bf16.h>
#include <cuda.h>
#include <stdint.h>
#include <stdio.h>

typedef __nv_bfloat16 bf16;

constexpr int S_ = 2048, D_ = 640, F_ = 1728;
constexpr int NCTA = 132, NTHR = 512;

constexpr int TAB_BYTES = 9216, VEC_BYTES = 1440;
struct Counters {
    unsigned kv[8 * 32];
    unsigned q[4 * 32], x[4 * 32];
    unsigned wr[32], tab[32], uv[32], cs[32], cs2[32], done[32];
    unsigned g1[32 * 32];
    unsigned g2[32 * 32];
};
struct Scratch {
    Counters cnt;
    unsigned epoch;
    alignas(1024) bf16 qst[2 * S_];
    alignas(1024) uint4 wr[2 * 8 * 10 * 128];
    alignas(1024) uint2 mod[2 * 6 * D_];
    alignas(1024) uint4 tab[(TAB_BYTES + 8 * VEC_BYTES) / 16];
    alignas(1024) float uv[2 * 3 * D_];
    alignas(1024) float cs3[2 * 1920];
    alignas(1024) uint4 cs3b[8 * 216];
    alignas(1024) float2 stats[32 * 8 * 64];
    alignas(1024) bf16 kvT[D_ * S_];
    alignas(1024) bf16 qT[D_ * S_];
    alignas(1024) bf16 x1T[D_ * S_];
    alignas(1024) bf16 t[(S_ + 4) * D_];
    alignas(1024) uint4 x2f[32 * 40 * 128];
    alignas(1024) uint4 x1f[32 * 8 * 5 * 128];
    alignas(1024) uint4 part[32 * 8 * 10 * 4 * 128];
};
__device__ Scratch g_scratch;
#define g_kvT (pp.s->kvT)
#define g_qT (pp.s->qT)
#define g_x1T (pp.s->x1T)
#define g_qst (pp.s->qst)
#define g_t (pp.s->t)
#define g_x2f (pp.s->x2f)
#define g_x1f (pp.s->x1f)
#define g_part (pp.s->part)
#define g_wr (pp.s->wr)
#define g_mod (pp.s->mod)
#define g_tab (pp.s->tab)
#define g_uv (pp.s->uv)
#define g_cs3 (pp.s->cs3)
#define g_cs3b (pp.s->cs3b)
#define g_stats (pp.s->stats)
#define g_cnt (pp.s->cnt)
#define g_epoch (pp.s->epoch)

struct Maps {
    CUtensorMap k, v, q;
    CUtensorMap qT;
    CUtensorMap x[3];
    CUtensorMap w1, w1h, w3h, wmod;
    CUtensorMap w2a, w2b;
    CUtensorMap w3a, w3b;
    CUtensorMap w4[2];
};

struct Ptrs {
    Scratch* s;
    uint64_t nil;
    const bf16 *q, *w_mod, *shift_k, *ssm_k, *ssm_D, *w1, *w2, *w4, *c;
};

constexpr int OFF_W = 0;
constexpr int OFF_XR = 131072;
constexpr int OFF_REM = 196608;
constexpr int OFF_TAB = OFF_REM + 5 * 4096;
constexpr int OFF_ROW = OFF_TAB + 4608;
constexpr int OFF_F1 = OFF_ROW + 4096;
constexpr int RECV_BYTES = 30720;
constexpr int OFF_M = OFF_REM + RECV_BYTES;
constexpr int OFF_OUT = OFF_XR + 32768;
static_assert(OFF_F1 + 1280 <= OFF_M, "G1 map");
constexpr int OFF_ST = 0;
constexpr int OFF_SSM = 20480;
constexpr int OFF_WM = 0;
constexpr int OFF_QIN = 49152;
constexpr int OFF_QT = 49152;
constexpr int OFF_Z = OFF_TAB;
constexpr int OFF_RING = 80896;
constexpr int OFF_KIN = OFF_RING, OFF_VIN = OFF_KIN + 2 * 10752;
constexpr int OFF_CH = OFF_RING + 3 * 16384, CH_BYTES = 13312, OFF_P = 5120;
static_assert(OFF_RING + 5 * 16384 <= OFF_CH + 3 * CH_BYTES && OFF_CH + 5 * CH_BYTES <= OFF_REM, "the last two rings replace channels 0..2");
constexpr int M_BAR = OFF_M;
constexpr int M_F1 = OFF_M + 832;
constexpr int M_GB = M_F1 + 1280, M_C = M_GB + 320, M_SB = M_C + 320, M_CI = M_SB + 320;
constexpr int M_KS = M_CI + 320;
constexpr int M_AB = M_KS + 160;
constexpr int M_EP = M_AB + 80;
constexpr int M_SINK = M_EP + 16;
constexpr int M_NUL = M_SINK + 16;
constexpr int M_TS = M_NUL + 128;
constexpr int SMEM_BYTES = M_TS;
static_assert(SMEM_BYTES <= 232448, "smem");

enum { B_WFULL = 0, B_WEMPTY = 8, B_XEMPTY = 16, B_XFULL = 24  ,
       B_RAW = 44, B_QIN = 45, B_SSM = 46, B_VEC = 47, B_VEC3 = 48, B_WM = 49, B_TAB = 50, B_QRDY = 51,
       B_MODR = 52, B_RAW2 = 53, B_RAW3 = 54, B_GATE = 56, B_SUMS = 62, B_RECV = 64  ,
       B_LAND = 72, B_AGAIN = 80, B_RETRY = 84,
       B_XS = 88, B_R1 = 89, B_BK = 90, B_KVS = 91,
       B_XFREE = 92, B_OWN = 93, B_IN = 94,
       B_RING = 96   };
#define T_KVB 1500
#define T_SSM 4200
#define PF_T0 5900
#define PF_N 12
#define PF_DT 420
#define SKIP_KV 2
#define SKIP_Q 32
#define SKIP_X 64
#define SKIP_G1 20
#define SKIP_G2 16
#define HELP_T 1000
#define R_GATE 34
#define GATE_W2 7
#define GATE_W3 24
#define GATE_W3B 37
#define W3_N2 15
#define LEAD1 5
#define XLEAD 4

#define SPIN_FAIL(code) __trap();
#define SPIN_LIMIT (1u << 22)
#define STALE(c)
#define STALE1(c)
#define TS(c, i)
#define TG(c, i)
#define TR(c, i)
#define TR2(c, i)
#define TR4(c, i)
#define TR5(c, i)
#define SPIN_CHECK(code) asm volatile("" ::"r"(it));
#define RARE(x) __builtin_expect((x) != 0, 0)
__device__ __forceinline__ uint32_t s2u(const void* p) { return (uint32_t)__cvta_generic_to_shared(p); }
__device__ __forceinline__ bool elect() {
    uint32_t p;
    asm volatile("{.reg .pred P; elect.sync _|P, 0xffffffff; selp.u32 %0,1,0,P;}" : "=r"(p));
    return p != 0;
}
__device__ __forceinline__ void mbar_init(uint32_t b, uint32_t n) { asm volatile("mbarrier.init.shared.b64 [%0], %1;" ::"r"(b), "r"(n)); }
__device__ __forceinline__ void mbar_expect(uint32_t b, uint32_t bytes) {
    asm volatile("mbarrier.arrive.expect_tx.shared.b64 _, [%0], %1;" ::"r"(b), "r"(bytes) : "memory");
}
__device__ __forceinline__ void mbar_arrive(uint32_t b) { asm volatile("mbarrier.arrive.shared.b64 _, [%0];" ::"r"(b) : "memory"); }
__device__ __forceinline__ void mbar_arrive_after(uint32_t b, uint32_t v0, uint32_t v1, uint32_t nil) { mbar_arrive(b + ((v0 | v1) & nil)); }
__device__ __forceinline__ void warp_arrive(uint32_t b) { __syncwarp(); if (elect()) mbar_arrive(b); }
__device__ __forceinline__ uint32_t peer_addr(uint32_t a) {
    uint32_t r;
    asm("{\n.reg .b32 q;\nmov.u32 q, %%cluster_ctarank;\nxor.b32 q, q, 1;\nmapa.shared::cluster.u32 %0, %1, q;\n}" : "=r"(r) : "r"(a));
    return r;
}
__device__ __forceinline__ bool mbar_test(uint32_t b, uint32_t parity) {
    uint32_t ok;
    asm volatile("{.reg .pred P; mbarrier.test_wait.parity.shared.b64 P, [%1], %2; selp.u32 %0,1,0,P;}" : "=r"(ok) : "r"(b), "r"(parity) : "memory");
    return ok != 0;
}
__device__ __forceinline__ bool mbar_try(uint32_t b, uint32_t parity) {
    uint32_t ok;
    asm volatile("{.reg .pred P; mbarrier.try_wait.parity.shared.b64 P, [%1], %2; selp.u32 %0,1,0,P;}" : "=r"(ok) : "r"(b), "r"(parity) : "memory");
    return ok != 0;
}
__device__ __forceinline__ void mbar_wait(uint32_t b, uint32_t parity) {
    if (__all_sync(0xffffffffu, mbar_try(b, parity))) return;
    uint32_t it = 0;
    while (!__all_sync(0xffffffffu, mbar_try(b, parity))) { if (++it > SPIN_LIMIT) SPIN_FAIL((b >> 3) & 63) }
}
__device__ __forceinline__ void mbar_spin(uint32_t b, uint32_t parity) {
    asm volatile("{\n.reg .pred P;\nSPIN:\nmbarrier.try_wait.parity.shared.b64 P, [%0], %1;\n@!P bra.uni SPIN;\n}" ::"r"(b), "r"(parity) : "memory");
}
__device__ __forceinline__ void bar_sync(int id, int n) { asm volatile("bar.sync %0, %1;" ::"r"(id), "r"(n) : "memory"); }
__device__ __forceinline__ void fence_async_smem() { asm volatile("fence.proxy.async.shared::cta;" ::: "memory"); }
__device__ __forceinline__ void wait_cnt(const unsigned* p, unsigned target, bool tagged = false) {
    unsigned v, it = 0;
    do {
        asm volatile("ld.relaxed.gpu.global.u32 %0, [%1];" : "=r"(v) : "l"(p) : "memory");
        SPIN_CHECK(60 + (target & 3))
    } while (!__all_sync(0xffffffffu, (int)(v - target) >= 0));
    if (!tagged) asm volatile("fence.acquire.gpu;" ::: "memory");
}
__device__ __forceinline__ void signal_cnt(unsigned* p, int lane, int n, bool tagged = false) {
    if (tagged) asm volatile("{\n.reg .pred P;\nsetp.lt.s32 P, %1, %2;\n@P red.relaxed.gpu.global.add.u32 [%0], %3;\n}" ::"l"(p), "r"(lane), "r"(n), "r"(1) : "memory");
    else if (lane < n) asm volatile("red.release.gpu.global.add.u32 [%0], 1;" ::"l"(p) : "memory");
    __syncwarp();
}
__device__ __forceinline__ uint32_t clock_lo() { uint32_t c; asm volatile("mov.u32 %0, %%clock;" : "=r"(c)); return c; }
__device__ __forceinline__ void wait_clock(uint32_t c0, uint32_t t) {
    asm volatile("{\n.reg .pred P;\n.reg .b32 c;\nWAIT:\nnanosleep.u32 20;\nmov.u32 c, %%clock;\nsub.u32 c, c, %0;\nsetp.lt.u32 P, c, %1;\n@P bra.uni WAIT;\n}" ::"r"(c0), "r"(t) : "memory");
}
__device__ __forceinline__ void tma_ld2(uint32_t dst, const CUtensorMap* m, int c0, int c1, uint32_t bar) {
    asm volatile("cp.async.bulk.tensor.2d.shared::cluster.global.mbarrier::complete_tx::bytes [%0], [%1, {%3, %4}], [%2];"
                 ::"r"(dst), "l"(m), "r"(bar), "r"(c0), "r"(c1) : "memory");
}
__device__ __forceinline__ void tma_ld3(uint32_t dst, const CUtensorMap* m, int c0, int c1, int c2, uint32_t bar) {
    asm volatile("cp.async.bulk.tensor.3d.shared::cluster.global.mbarrier::complete_tx::bytes [%0], [%1, {%3, %4, %5}], [%2];"
                 ::"r"(dst), "l"(m), "r"(bar), "r"(c0), "r"(c1), "r"(c2) : "memory");
}
__device__ __forceinline__ void tma_ld5(uint32_t dst, const CUtensorMap* m, int col, int blk, uint32_t bar) {
    asm volatile("cp.async.bulk.tensor.5d.shared::cluster.global.mbarrier::complete_tx::bytes [%0], [%1, {%3, %4, %4, %4, %5}], [%2];"
                 ::"r"(dst), "l"(m), "r"(bar), "r"(col), "r"(0), "r"(blk) : "memory");
}
__device__ __forceinline__ void bulk_ld(uint32_t dst, const void* src, uint32_t bytes, uint32_t bar) {
    asm volatile("cp.async.bulk.shared::cluster.global.mbarrier::complete_tx::bytes [%0], [%1], %2, [%3];" ::"r"(dst), "l"(src), "r"(bytes), "r"(bar) : "memory");
}
__device__ __forceinline__ void l2_prefetch(const void* p, uint32_t bytes) {
    asm volatile("cp.async.bulk.prefetch.L2.global [%0], %1;" ::"l"(p), "r"(bytes) : "memory");
}
__device__ __forceinline__ void wg_fence() { asm volatile("wgmma.fence.sync.aligned;" ::: "memory"); }
__device__ __forceinline__ void wg_commit() { asm volatile("wgmma.commit_group.sync.aligned;" ::: "memory"); }
template <int N> __device__ __forceinline__ void wg_wait() { asm volatile("wgmma.wait_group.sync.aligned %0;" ::"n"(N) : "memory"); }
template <int N> __device__ __forceinline__ void reg_fence(float (&d)[N]) {
#pragma unroll
    for (int i = 0; i < N; i++) asm volatile("" : "+f"(d[i])::"memory");
}
template <int N> __device__ __forceinline__ void zero(float (&d)[N]) {
#pragma unroll
    for (int i = 0; i < N; i++) asm volatile("mov.b32 %0, 0;" : "=f"(d[i]));
}
__device__ __forceinline__ uint32_t lds32(uint32_t a) { uint32_t v; asm volatile("ld.shared.b32 %0, [%1];" : "=r"(v) : "r"(a)); return v; }
__device__ __forceinline__ uint2 lds64(uint32_t a) { uint2 v; asm volatile("ld.shared.v2.b32 {%0,%1}, [%2];" : "=r"(v.x), "=r"(v.y) : "r"(a)); return v; }
__device__ __forceinline__ float2 lds64f(uint32_t a) { float2 v; asm volatile("ld.shared.v2.f32 {%0,%1}, [%2];" : "=f"(v.x), "=f"(v.y) : "r"(a)); return v; }
__device__ __forceinline__ void sts32(uint32_t a, uint32_t v) { asm volatile("st.shared.b32 [%0], %1;" ::"r"(a), "r"(v) : "memory"); }
__device__ __forceinline__ void sts64f(uint32_t a, float x, float y) { asm volatile("st.shared.v2.f32 [%0], {%1,%2};" ::"r"(a), "f"(x), "f"(y) : "memory"); }
__device__ __forceinline__ void sts128(uint32_t a, uint32_t x, uint32_t y, uint32_t z, uint32_t w) {
    asm volatile("st.shared.v4.b32 [%0], {%1,%2,%3,%4};" ::"r"(a), "r"(x), "r"(y), "r"(z), "r"(w) : "memory");
}
__device__ __forceinline__ void sts128f(uint32_t a, float x, float y, float z, float w) {
    asm volatile("st.shared.v4.f32 [%0], {%1,%2,%3,%4};" ::"r"(a), "f"(x), "f"(y), "f"(z), "f"(w) : "memory");
}
__device__ __forceinline__ uint4 lds128(uint32_t a) {
    uint4 v;
    asm volatile("ld.shared.v4.b32 {%0,%1,%2,%3}, [%4];" : "=r"(v.x), "=r"(v.y), "=r"(v.z), "=r"(v.w) : "r"(a) : "memory");
    return v;
}
__device__ __forceinline__ void lds128_if(int p, uint4& v, uint32_t a) {
    asm volatile("{\n.reg .pred p;\nsetp.ne.s32 p, %5, 0;\n@p ld.shared.v4.b32 {%0,%1,%2,%3}, [%4];\n}" : "+r"(v.x), "+r"(v.y), "+r"(v.z), "+r"(v.w) : "r"(a), "r"(p) : "memory");
}
__device__ __forceinline__ float4 lds128f(uint32_t a) {
    float4 v;
    asm volatile("ld.shared.v4.f32 {%0,%1,%2,%3}, [%4];" : "=f"(v.x), "=f"(v.y), "=f"(v.z), "=f"(v.w) : "r"(a) : "memory");
    return v;
}
__device__ __forceinline__ void stg128(void* p, uint32_t x, uint32_t y, uint32_t z, uint32_t w) {
    asm volatile("st.global.v4.b32 [%0], {%1,%2,%3,%4};" ::"l"(p), "r"(x), "r"(y), "r"(z), "r"(w) : "memory");
}
__device__ __forceinline__ void stg128(void* p, uint4 v) { stg128(p, v.x, v.y, v.z, v.w); }
__device__ __forceinline__ void stg64(void* p, uint32_t x, uint32_t y) { asm volatile("st.global.v2.b32 [%0], {%1,%2};" ::"l"(p), "r"(x), "r"(y) : "memory"); }
__device__ __forceinline__ void stsm4(uint32_t a, uint32_t r0, uint32_t r1, uint32_t r2, uint32_t r3) {
    asm volatile("stmatrix.sync.aligned.m8n8.x4.shared.b16 [%0], {%1,%2,%3,%4};" ::"r"(a), "r"(r0), "r"(r1), "r"(r2), "r"(r3) : "memory");
}
__device__ __forceinline__ void stsm4t(uint32_t a, uint32_t r0, uint32_t r1, uint32_t r2, uint32_t r3) {
    asm volatile("stmatrix.sync.aligned.m8n8.x4.trans.shared.b16 [%0], {%1,%2,%3,%4};" ::"r"(a), "r"(r0), "r"(r1), "r"(r2), "r"(r3) : "memory");
}
__device__ __forceinline__ void ldsm4t_if(bool p, uint32_t a, uint32_t* r) {
    asm volatile("{\n.reg .pred p;\nsetp.ne.u32 p, %5, 0;\n@p ldmatrix.sync.aligned.m8n8.x4.trans.shared.b16 {%0,%1,%2,%3}, [%4];\n}"
                 : "+r"(r[0]), "+r"(r[1]), "+r"(r[2]), "+r"(r[3]) : "r"(a), "r"((uint32_t)p) : "memory");
}
__device__ __forceinline__ void ldsm4t(uint32_t a, uint32_t& r0, uint32_t& r1, uint32_t& r2, uint32_t& r3) {
    asm volatile("ldmatrix.sync.aligned.m8n8.x4.trans.shared.b16 {%0,%1,%2,%3}, [%4];" : "=r"(r0), "=r"(r1), "=r"(r2), "=r"(r3) : "r"(a) : "memory");
}
__device__ __forceinline__ uint32_t pack2(float lo, float hi) {
    uint32_t r;
    asm("cvt.rn.bf16x2.f32 %0, %1, %2;" : "=r"(r) : "f"(hi), "f"(lo));
    return r;
}
__device__ __forceinline__ uint32_t mul2(uint32_t a, uint32_t b) { uint32_t r; asm("mul.rn.bf16x2 %0, %1, %2;" : "=r"(r) : "r"(a), "r"(b)); return r; }
__device__ __forceinline__ uint32_t fma2(uint32_t a, uint32_t b, uint32_t c) { uint32_t r; asm("fma.rn.bf16x2 %0, %1, %2, %3;" : "=r"(r) : "r"(a), "r"(b), "r"(c)); return r; }
__device__ __forceinline__ uint32_t add2(uint32_t a, uint32_t b) { uint32_t r; asm("add.rn.bf16x2 %0, %1, %2;" : "=r"(r) : "r"(a), "r"(b)); return r; }
__device__ __forceinline__ float blo(uint32_t w) { return __uint_as_float(w << 16); }
__device__ __forceinline__ float bhi(uint32_t w) { return __uint_as_float(w & 0xffff0000u); }
__device__ __forceinline__ float rbf(float x) { return __bfloat162float(__float2bfloat16_rn(x)); }
__device__ __forceinline__ uint32_t ldg32(const void* p) { uint32_t v; asm volatile("ld.global.nc.b32 %0, [%1];" : "=r"(v) : "l"(p)); return v; }
__device__ __forceinline__ uint4 ldg128(const void* p) {
    uint4 v;
    asm volatile("ld.global.nc.v4.b32 {%0,%1,%2,%3}, [%4];" : "=r"(v.x), "=r"(v.y), "=r"(v.z), "=r"(v.w) : "l"(p));
    return v;
}
__device__ __forceinline__ uint4 ldcg128(const void* p) {
    uint4 v;
    asm volatile("ld.global.cg.v4.u32 {%0,%1,%2,%3}, [%4];" : "=r"(v.x), "=r"(v.y), "=r"(v.z), "=r"(v.w) : "l"(p) : "memory");
    return v;
}
__device__ __forceinline__ float ldcg32f(const void* p) { float v; asm volatile("ld.global.cg.f32 %0, [%1];" : "=f"(v) : "l"(p) : "memory"); return v; }
__device__ __forceinline__ float2 ld_stat(const float2* p) {
    float2 v;
    asm volatile("{\n.reg .b64 q;\nld.relaxed.gpu.global.b64 q, [%2];\nmov.b64 {%0, %1}, q;\n}" : "=f"(v.x), "=f"(v.y) : "l"(p) : "memory");
    return v;
}
__device__ __forceinline__ uint32_t ld_cold(const unsigned* p) { uint32_t v; asm volatile("ld.relaxed.gpu.global.u32 %0, [%1];" : "=r"(v) : "l"(p) : "memory"); return v; }
__device__ __forceinline__ uint2 ld_mod(const uint2* p) {
    uint64_t v;
    asm volatile("ld.relaxed.gpu.global.b64 %0, [%1];" : "=l"(v) : "l"(p) : "memory");
    return make_uint2((uint32_t)v, (uint32_t)(v >> 32));
}
__device__ __forceinline__ float silu(float x) {
    float e, r;
    asm("ex2.approx.ftz.f32 %0, %1;" : "=f"(e) : "f"(x * -1.4426950408889634f));
    asm("rcp.approx.ftz.f32 %0, %1;" : "=f"(r) : "f"(1.f + e));
    return x * r;
}
__device__ __forceinline__ float gelu2(float h) {
    float u = h * fmaf(h * h, 8.f * 0.0356774081f, 2.f * 0.7978845608f);
    float th;
    asm("tanh.approx.f32 %0, %1;" : "=f"(th) : "f"(u));
    return fmaf(h, th, h);
}
__device__ __forceinline__ float gelu2r(float a, float2 k) {
    float th;
    asm("tanh.approx.f32 %0, %1;" : "=f"(th) : "f"(a * fmaf(a * a, k.x, k.y)));
    return fmaf(a, th, a);
}

__device__ __forceinline__ void conv_channel(float (&d)[64], uint32_t pa, uint64_t db) {
    asm volatile("{\n.reg .b32 a0, a1, a2, a3, b0, b1, b2, b3, t0, t1;\n.reg .b64 d;\nld.shared.b32 a0, [%64];\nld.shared.b32 a1, [%64+128];\nld.shared.b32 a2, [%64+-128];\nmov.b32 a3, a0;\n"
        "ld.shared.b32 t0, [%64+256];\nld.shared.b32 t1, [%64+384];\nadd.s64 d, %65, 0;\nwgmma.fence.sync.aligned;\nwgmma.mma_async.sync.aligned.m64n128k16.f32.bf16.bf16 {%0, %1, %2, %3, %4, %5, %6, %7, %8, %9, %10, %11, %12, %13, %14, %15, %16, %17, %18, %19, %20, %21, %22, %23, %24, %25, %26, %27, %28, %29, %30, %31, %32, %33, %34, %35, %36, %37, %38, %39, %40, %41, %42, %43, %44, %45, %46, %47, %48, %49, %50, %51, %52, %53, %54, %55, %56, %57, %58, %59, %60, %61, %62, %63}, {a0, a1, a2, a3}, d, 0, 1, 1, 0;\nwgmma.commit_group.sync.aligned;\nwgmma.wait_group.sync.aligned 1;\nmov.b32 b2, a1;\nmov.b32 b0, t0;\nmov.b32 b3, t0;\nmov.b32 b1, t1;\n"
        "ld.shared.b32 t0, [%64+512];\nld.shared.b32 t1, [%64+640];\nadd.s64 d, %65, 8;\nwgmma.fence.sync.aligned;\nwgmma.mma_async.sync.aligned.m64n128k16.f32.bf16.bf16 {%0, %1, %2, %3, %4, %5, %6, %7, %8, %9, %10, %11, %12, %13, %14, %15, %16, %17, %18, %19, %20, %21, %22, %23, %24, %25, %26, %27, %28, %29, %30, %31, %32, %33, %34, %35, %36, %37, %38, %39, %40, %41, %42, %43, %44, %45, %46, %47, %48, %49, %50, %51, %52, %53, %54, %55, %56, %57, %58, %59, %60, %61, %62, %63}, {b0, b1, b2, b3}, d, 1, 1, 1, 0;\nwgmma.commit_group.sync.aligned;\nwgmma.wait_group.sync.aligned 1;\nmov.b32 a2, b1;\nmov.b32 a0, t0;\nmov.b32 a3, t0;\nmov.b32 a1, t1;\n"
        "ld.shared.b32 t0, [%64+768];\nld.shared.b32 t1, [%64+896];\nadd.s64 d, %65, 16;\nwgmma.fence.sync.aligned;\nwgmma.mma_async.sync.aligned.m64n128k16.f32.bf16.bf16 {%0, %1, %2, %3, %4, %5, %6, %7, %8, %9, %10, %11, %12, %13, %14, %15, %16, %17, %18, %19, %20, %21, %22, %23, %24, %25, %26, %27, %28, %29, %30, %31, %32, %33, %34, %35, %36, %37, %38, %39, %40, %41, %42, %43, %44, %45, %46, %47, %48, %49, %50, %51, %52, %53, %54, %55, %56, %57, %58, %59, %60, %61, %62, %63}, {a0, a1, a2, a3}, d, 1, 1, 1, 0;\nwgmma.commit_group.sync.aligned;\nwgmma.wait_group.sync.aligned 1;\nmov.b32 b2, a1;\nmov.b32 b0, t0;\nmov.b32 b3, t0;\nmov.b32 b1, t1;\n"
        "ld.shared.b32 t0, [%64+1024];\nld.shared.b32 t1, [%64+1152];\nadd.s64 d, %65, 24;\nwgmma.fence.sync.aligned;\nwgmma.mma_async.sync.aligned.m64n128k16.f32.bf16.bf16 {%0, %1, %2, %3, %4, %5, %6, %7, %8, %9, %10, %11, %12, %13, %14, %15, %16, %17, %18, %19, %20, %21, %22, %23, %24, %25, %26, %27, %28, %29, %30, %31, %32, %33, %34, %35, %36, %37, %38, %39, %40, %41, %42, %43, %44, %45, %46, %47, %48, %49, %50, %51, %52, %53, %54, %55, %56, %57, %58, %59, %60, %61, %62, %63}, {b0, b1, b2, b3}, d, 1, 1, 1, 0;\nwgmma.commit_group.sync.aligned;\nwgmma.wait_group.sync.aligned 1;\nmov.b32 a2, b1;\nmov.b32 a0, t0;\nmov.b32 a3, t0;\nmov.b32 a1, t1;\n"
        "ld.shared.b32 t0, [%64+1280];\nld.shared.b32 t1, [%64+1408];\nadd.s64 d, %65, 32;\nwgmma.fence.sync.aligned;\nwgmma.mma_async.sync.aligned.m64n128k16.f32.bf16.bf16 {%0, %1, %2, %3, %4, %5, %6, %7, %8, %9, %10, %11, %12, %13, %14, %15, %16, %17, %18, %19, %20, %21, %22, %23, %24, %25, %26, %27, %28, %29, %30, %31, %32, %33, %34, %35, %36, %37, %38, %39, %40, %41, %42, %43, %44, %45, %46, %47, %48, %49, %50, %51, %52, %53, %54, %55, %56, %57, %58, %59, %60, %61, %62, %63}, {a0, a1, a2, a3}, d, 1, 1, 1, 0;\nwgmma.commit_group.sync.aligned;\nwgmma.wait_group.sync.aligned 1;\nmov.b32 b2, a1;\nmov.b32 b0, t0;\nmov.b32 b3, t0;\nmov.b32 b1, t1;\n"
        "ld.shared.b32 t0, [%64+1536];\nld.shared.b32 t1, [%64+1664];\nadd.s64 d, %65, 40;\nwgmma.fence.sync.aligned;\nwgmma.mma_async.sync.aligned.m64n128k16.f32.bf16.bf16 {%0, %1, %2, %3, %4, %5, %6, %7, %8, %9, %10, %11, %12, %13, %14, %15, %16, %17, %18, %19, %20, %21, %22, %23, %24, %25, %26, %27, %28, %29, %30, %31, %32, %33, %34, %35, %36, %37, %38, %39, %40, %41, %42, %43, %44, %45, %46, %47, %48, %49, %50, %51, %52, %53, %54, %55, %56, %57, %58, %59, %60, %61, %62, %63}, {b0, b1, b2, b3}, d, 1, 1, 1, 0;\nwgmma.commit_group.sync.aligned;\nwgmma.wait_group.sync.aligned 1;\nmov.b32 a2, b1;\nmov.b32 a0, t0;\nmov.b32 a3, t0;\nmov.b32 a1, t1;\n"
        "ld.shared.b32 t0, [%64+1792];\nld.shared.b32 t1, [%64+1920];\nadd.s64 d, %65, 48;\nwgmma.fence.sync.aligned;\nwgmma.mma_async.sync.aligned.m64n128k16.f32.bf16.bf16 {%0, %1, %2, %3, %4, %5, %6, %7, %8, %9, %10, %11, %12, %13, %14, %15, %16, %17, %18, %19, %20, %21, %22, %23, %24, %25, %26, %27, %28, %29, %30, %31, %32, %33, %34, %35, %36, %37, %38, %39, %40, %41, %42, %43, %44, %45, %46, %47, %48, %49, %50, %51, %52, %53, %54, %55, %56, %57, %58, %59, %60, %61, %62, %63}, {a0, a1, a2, a3}, d, 1, 1, 1, 0;\nwgmma.commit_group.sync.aligned;\nwgmma.wait_group.sync.aligned 1;\nmov.b32 b2, a1;\nmov.b32 b0, t0;\nmov.b32 b3, t0;\nmov.b32 b1, t1;\n"
        "ld.shared.b32 t0, [%64+2048];\nld.shared.b32 t1, [%64+2176];\nadd.s64 d, %65, 56;\nwgmma.fence.sync.aligned;\nwgmma.mma_async.sync.aligned.m64n128k16.f32.bf16.bf16 {%0, %1, %2, %3, %4, %5, %6, %7, %8, %9, %10, %11, %12, %13, %14, %15, %16, %17, %18, %19, %20, %21, %22, %23, %24, %25, %26, %27, %28, %29, %30, %31, %32, %33, %34, %35, %36, %37, %38, %39, %40, %41, %42, %43, %44, %45, %46, %47, %48, %49, %50, %51, %52, %53, %54, %55, %56, %57, %58, %59, %60, %61, %62, %63}, {b0, b1, b2, b3}, d, 1, 1, 1, 0;\nwgmma.commit_group.sync.aligned;\nwgmma.wait_group.sync.aligned 1;\nmov.b32 a2, b1;\nmov.b32 a0, t0;\nmov.b32 a3, t0;\nmov.b32 a1, t1;\n"
        "ld.shared.b32 t0, [%64+2304];\nld.shared.b32 t1, [%64+2432];\nadd.s64 d, %65, 64;\nwgmma.fence.sync.aligned;\nwgmma.mma_async.sync.aligned.m64n96k16.f32.bf16.bf16 {%0, %1, %2, %3, %4, %5, %6, %7, %8, %9, %10, %11, %12, %13, %14, %15, %16, %17, %18, %19, %20, %21, %22, %23, %24, %25, %26, %27, %28, %29, %30, %31, %32, %33, %34, %35, %36, %37, %38, %39, %40, %41, %42, %43, %44, %45, %46, %47}, {a0, a1, a2, a3}, d, 1, 1, 1, 0;\nwgmma.commit_group.sync.aligned;\nwgmma.wait_group.sync.aligned 1;\nmov.b32 b2, a1;\nmov.b32 b0, t0;\nmov.b32 b3, t0;\nmov.b32 b1, t1;\n"
        "ld.shared.b32 t0, [%64+2560];\nld.shared.b32 t1, [%64+2688];\nadd.s64 d, %65, 72;\nwgmma.fence.sync.aligned;\nwgmma.mma_async.sync.aligned.m64n96k16.f32.bf16.bf16 {%0, %1, %2, %3, %4, %5, %6, %7, %8, %9, %10, %11, %12, %13, %14, %15, %16, %17, %18, %19, %20, %21, %22, %23, %24, %25, %26, %27, %28, %29, %30, %31, %32, %33, %34, %35, %36, %37, %38, %39, %40, %41, %42, %43, %44, %45, %46, %47}, {b0, b1, b2, b3}, d, 1, 1, 1, 0;\nwgmma.commit_group.sync.aligned;\nwgmma.wait_group.sync.aligned 1;\nmov.b32 a2, b1;\nmov.b32 a0, t0;\nmov.b32 a3, t0;\nmov.b32 a1, t1;\n"
        "ld.shared.b32 t0, [%64+2816];\nld.shared.b32 t1, [%64+2944];\nadd.s64 d, %65, 80;\nwgmma.fence.sync.aligned;\nwgmma.mma_async.sync.aligned.m64n88k16.f32.bf16.bf16 {%0, %1, %2, %3, %4, %5, %6, %7, %8, %9, %10, %11, %12, %13, %14, %15, %16, %17, %18, %19, %20, %21, %22, %23, %24, %25, %26, %27, %28, %29, %30, %31, %32, %33, %34, %35, %36, %37, %38, %39, %40, %41, %42, %43}, {a0, a1, a2, a3}, d, 1, 1, 1, 0;\nwgmma.commit_group.sync.aligned;\nwgmma.wait_group.sync.aligned 1;\nmov.b32 b2, a1;\nmov.b32 b0, t0;\nmov.b32 b3, t0;\nmov.b32 b1, t1;\n"
        "ld.shared.b32 t0, [%64+3072];\nld.shared.b32 t1, [%64+3200];\nadd.s64 d, %65, 88;\nwgmma.fence.sync.aligned;\nwgmma.mma_async.sync.aligned.m64n88k16.f32.bf16.bf16 {%0, %1, %2, %3, %4, %5, %6, %7, %8, %9, %10, %11, %12, %13, %14, %15, %16, %17, %18, %19, %20, %21, %22, %23, %24, %25, %26, %27, %28, %29, %30, %31, %32, %33, %34, %35, %36, %37, %38, %39, %40, %41, %42, %43}, {b0, b1, b2, b3}, d, 1, 1, 1, 0;\nwgmma.commit_group.sync.aligned;\nwgmma.wait_group.sync.aligned 1;\nmov.b32 a2, b1;\nmov.b32 a0, t0;\nmov.b32 a3, t0;\nmov.b32 a1, t1;\n"
        "ld.shared.b32 t0, [%64+3328];\nld.shared.b32 t1, [%64+3456];\nadd.s64 d, %65, 96;\nwgmma.fence.sync.aligned;\nwgmma.mma_async.sync.aligned.m64n80k16.f32.bf16.bf16 {%0, %1, %2, %3, %4, %5, %6, %7, %8, %9, %10, %11, %12, %13, %14, %15, %16, %17, %18, %19, %20, %21, %22, %23, %24, %25, %26, %27, %28, %29, %30, %31, %32, %33, %34, %35, %36, %37, %38, %39}, {a0, a1, a2, a3}, d, 1, 1, 1, 0;\nwgmma.commit_group.sync.aligned;\nwgmma.wait_group.sync.aligned 1;\nmov.b32 b2, a1;\nmov.b32 b0, t0;\nmov.b32 b3, t0;\nmov.b32 b1, t1;\n"
        "ld.shared.b32 t0, [%64+3584];\nld.shared.b32 t1, [%64+3712];\nadd.s64 d, %65, 104;\nwgmma.fence.sync.aligned;\nwgmma.mma_async.sync.aligned.m64n80k16.f32.bf16.bf16 {%0, %1, %2, %3, %4, %5, %6, %7, %8, %9, %10, %11, %12, %13, %14, %15, %16, %17, %18, %19, %20, %21, %22, %23, %24, %25, %26, %27, %28, %29, %30, %31, %32, %33, %34, %35, %36, %37, %38, %39}, {b0, b1, b2, b3}, d, 1, 1, 1, 0;\nwgmma.commit_group.sync.aligned;\nwgmma.wait_group.sync.aligned 1;\nmov.b32 a2, b1;\nmov.b32 a0, t0;\nmov.b32 a3, t0;\nmov.b32 a1, t1;\n"
        "ld.shared.b32 t0, [%64+3840];\nld.shared.b32 t1, [%64+3968];\nadd.s64 d, %65, 112;\nwgmma.fence.sync.aligned;\nwgmma.mma_async.sync.aligned.m64n72k16.f32.bf16.bf16 {%0, %1, %2, %3, %4, %5, %6, %7, %8, %9, %10, %11, %12, %13, %14, %15, %16, %17, %18, %19, %20, %21, %22, %23, %24, %25, %26, %27, %28, %29, %30, %31, %32, %33, %34, %35}, {a0, a1, a2, a3}, d, 1, 1, 1, 0;\nwgmma.commit_group.sync.aligned;\nwgmma.wait_group.sync.aligned 1;\nmov.b32 b2, a1;\nmov.b32 b0, t0;\nmov.b32 b3, t0;\nmov.b32 b1, t1;\n"
        "ld.shared.b32 t0, [%64+4096];\nld.shared.b32 t1, [%64+4224];\nadd.s64 d, %65, 120;\nwgmma.fence.sync.aligned;\nwgmma.mma_async.sync.aligned.m64n72k16.f32.bf16.bf16 {%0, %1, %2, %3, %4, %5, %6, %7, %8, %9, %10, %11, %12, %13, %14, %15, %16, %17, %18, %19, %20, %21, %22, %23, %24, %25, %26, %27, %28, %29, %30, %31, %32, %33, %34, %35}, {b0, b1, b2, b3}, d, 1, 1, 1, 0;\nwgmma.commit_group.sync.aligned;\nwgmma.wait_group.sync.aligned 1;\nmov.b32 a2, b1;\nmov.b32 a0, t0;\nmov.b32 a3, t0;\nmov.b32 a1, t1;\n"
        "ld.shared.b32 t0, [%64+4352];\nld.shared.b32 t1, [%64+4480];\nadd.s64 d, %65, 128;\nwgmma.fence.sync.aligned;\nwgmma.mma_async.sync.aligned.m64n64k16.f32.bf16.bf16 {%0, %1, %2, %3, %4, %5, %6, %7, %8, %9, %10, %11, %12, %13, %14, %15, %16, %17, %18, %19, %20, %21, %22, %23, %24, %25, %26, %27, %28, %29, %30, %31}, {a0, a1, a2, a3}, d, 1, 1, 1, 0;\nwgmma.commit_group.sync.aligned;\nwgmma.wait_group.sync.aligned 1;\nmov.b32 b2, a1;\nmov.b32 b0, t0;\nmov.b32 b3, t0;\nmov.b32 b1, t1;\n"
        "ld.shared.b32 t0, [%64+4608];\nld.shared.b32 t1, [%64+4736];\nadd.s64 d, %65, 136;\nwgmma.fence.sync.aligned;\nwgmma.mma_async.sync.aligned.m64n64k16.f32.bf16.bf16 {%0, %1, %2, %3, %4, %5, %6, %7, %8, %9, %10, %11, %12, %13, %14, %15, %16, %17, %18, %19, %20, %21, %22, %23, %24, %25, %26, %27, %28, %29, %30, %31}, {b0, b1, b2, b3}, d, 1, 1, 1, 0;\nwgmma.commit_group.sync.aligned;\nwgmma.wait_group.sync.aligned 1;\nmov.b32 a2, b1;\nmov.b32 a0, t0;\nmov.b32 a3, t0;\nmov.b32 a1, t1;\n"
        "ld.shared.b32 t0, [%64+4864];\nld.shared.b32 t1, [%64+4992];\nadd.s64 d, %65, 144;\nwgmma.fence.sync.aligned;\nwgmma.mma_async.sync.aligned.m64n56k16.f32.bf16.bf16 {%0, %1, %2, %3, %4, %5, %6, %7, %8, %9, %10, %11, %12, %13, %14, %15, %16, %17, %18, %19, %20, %21, %22, %23, %24, %25, %26, %27}, {a0, a1, a2, a3}, d, 1, 1, 1, 0;\nwgmma.commit_group.sync.aligned;\nwgmma.wait_group.sync.aligned 1;\nmov.b32 b2, a1;\nmov.b32 b0, t0;\nmov.b32 b3, t0;\nmov.b32 b1, t1;\n"
        "ld.shared.b32 t0, [%64+5120];\nld.shared.b32 t1, [%64+5248];\nadd.s64 d, %65, 152;\nwgmma.fence.sync.aligned;\nwgmma.mma_async.sync.aligned.m64n56k16.f32.bf16.bf16 {%0, %1, %2, %3, %4, %5, %6, %7, %8, %9, %10, %11, %12, %13, %14, %15, %16, %17, %18, %19, %20, %21, %22, %23, %24, %25, %26, %27}, {b0, b1, b2, b3}, d, 1, 1, 1, 0;\nwgmma.commit_group.sync.aligned;\nwgmma.wait_group.sync.aligned 1;\nmov.b32 a2, b1;\nmov.b32 a0, t0;\nmov.b32 a3, t0;\nmov.b32 a1, t1;\n"
        "ld.shared.b32 t0, [%64+5376];\nld.shared.b32 t1, [%64+5504];\nadd.s64 d, %65, 160;\nwgmma.fence.sync.aligned;\nwgmma.mma_async.sync.aligned.m64n48k16.f32.bf16.bf16 {%0, %1, %2, %3, %4, %5, %6, %7, %8, %9, %10, %11, %12, %13, %14, %15, %16, %17, %18, %19, %20, %21, %22, %23}, {a0, a1, a2, a3}, d, 1, 1, 1, 0;\nwgmma.commit_group.sync.aligned;\nwgmma.wait_group.sync.aligned 1;\nmov.b32 b2, a1;\nmov.b32 b0, t0;\nmov.b32 b3, t0;\nmov.b32 b1, t1;\n"
        "ld.shared.b32 t0, [%64+5632];\nld.shared.b32 t1, [%64+5760];\nadd.s64 d, %65, 168;\nwgmma.fence.sync.aligned;\nwgmma.mma_async.sync.aligned.m64n48k16.f32.bf16.bf16 {%0, %1, %2, %3, %4, %5, %6, %7, %8, %9, %10, %11, %12, %13, %14, %15, %16, %17, %18, %19, %20, %21, %22, %23}, {b0, b1, b2, b3}, d, 1, 1, 1, 0;\nwgmma.commit_group.sync.aligned;\nwgmma.wait_group.sync.aligned 1;\nmov.b32 a2, b1;\nmov.b32 a0, t0;\nmov.b32 a3, t0;\nmov.b32 a1, t1;\n"
        "ld.shared.b32 t0, [%64+5888];\nld.shared.b32 t1, [%64+6016];\nadd.s64 d, %65, 176;\nwgmma.fence.sync.aligned;\nwgmma.mma_async.sync.aligned.m64n40k16.f32.bf16.bf16 {%0, %1, %2, %3, %4, %5, %6, %7, %8, %9, %10, %11, %12, %13, %14, %15, %16, %17, %18, %19}, {a0, a1, a2, a3}, d, 1, 1, 1, 0;\nwgmma.commit_group.sync.aligned;\nwgmma.wait_group.sync.aligned 1;\nmov.b32 b2, a1;\nmov.b32 b0, t0;\nmov.b32 b3, t0;\nmov.b32 b1, t1;\n"
        "ld.shared.b32 t0, [%64+6144];\nld.shared.b32 t1, [%64+6272];\nadd.s64 d, %65, 184;\nwgmma.fence.sync.aligned;\nwgmma.mma_async.sync.aligned.m64n40k16.f32.bf16.bf16 {%0, %1, %2, %3, %4, %5, %6, %7, %8, %9, %10, %11, %12, %13, %14, %15, %16, %17, %18, %19}, {b0, b1, b2, b3}, d, 1, 1, 1, 0;\nwgmma.commit_group.sync.aligned;\nwgmma.wait_group.sync.aligned 1;\nmov.b32 a2, b1;\nmov.b32 a0, t0;\nmov.b32 a3, t0;\nmov.b32 a1, t1;\n"
        "ld.shared.b32 t0, [%64+6400];\nld.shared.b32 t1, [%64+6528];\nadd.s64 d, %65, 192;\nwgmma.fence.sync.aligned;\nwgmma.mma_async.sync.aligned.m64n32k16.f32.bf16.bf16 {%0, %1, %2, %3, %4, %5, %6, %7, %8, %9, %10, %11, %12, %13, %14, %15}, {a0, a1, a2, a3}, d, 1, 1, 1, 0;\nwgmma.commit_group.sync.aligned;\nwgmma.wait_group.sync.aligned 1;\nmov.b32 b2, a1;\nmov.b32 b0, t0;\nmov.b32 b3, t0;\nmov.b32 b1, t1;\n"
        "ld.shared.b32 t0, [%64+6656];\nld.shared.b32 t1, [%64+6784];\nadd.s64 d, %65, 200;\nwgmma.fence.sync.aligned;\nwgmma.mma_async.sync.aligned.m64n32k16.f32.bf16.bf16 {%0, %1, %2, %3, %4, %5, %6, %7, %8, %9, %10, %11, %12, %13, %14, %15}, {b0, b1, b2, b3}, d, 1, 1, 1, 0;\nwgmma.commit_group.sync.aligned;\nwgmma.wait_group.sync.aligned 1;\nmov.b32 a2, b1;\nmov.b32 a0, t0;\nmov.b32 a3, t0;\nmov.b32 a1, t1;\n"
        "ld.shared.b32 t0, [%64+6912];\nld.shared.b32 t1, [%64+7040];\nadd.s64 d, %65, 208;\nwgmma.fence.sync.aligned;\nwgmma.mma_async.sync.aligned.m64n24k16.f32.bf16.bf16 {%0, %1, %2, %3, %4, %5, %6, %7, %8, %9, %10, %11}, {a0, a1, a2, a3}, d, 1, 1, 1, 0;\nwgmma.commit_group.sync.aligned;\nwgmma.wait_group.sync.aligned 1;\nmov.b32 b2, a1;\nmov.b32 b0, t0;\nmov.b32 b3, t0;\nmov.b32 b1, t1;\n"
        "ld.shared.b32 t0, [%64+7168];\nld.shared.b32 t1, [%64+7296];\nadd.s64 d, %65, 216;\nwgmma.fence.sync.aligned;\nwgmma.mma_async.sync.aligned.m64n24k16.f32.bf16.bf16 {%0, %1, %2, %3, %4, %5, %6, %7, %8, %9, %10, %11}, {b0, b1, b2, b3}, d, 1, 1, 1, 0;\nwgmma.commit_group.sync.aligned;\nwgmma.wait_group.sync.aligned 1;\nmov.b32 a2, b1;\nmov.b32 a0, t0;\nmov.b32 a3, t0;\nmov.b32 a1, t1;\n"
        "ld.shared.b32 t0, [%64+7424];\nld.shared.b32 t1, [%64+7552];\nadd.s64 d, %65, 224;\nwgmma.fence.sync.aligned;\nwgmma.mma_async.sync.aligned.m64n16k16.f32.bf16.bf16 {%0, %1, %2, %3, %4, %5, %6, %7}, {a0, a1, a2, a3}, d, 1, 1, 1, 0;\nwgmma.commit_group.sync.aligned;\nwgmma.wait_group.sync.aligned 1;\nmov.b32 b2, a1;\nmov.b32 b0, t0;\nmov.b32 b3, t0;\nmov.b32 b1, t1;\n"
        "ld.shared.b32 t0, [%64+7680];\nld.shared.b32 t1, [%64+7808];\nadd.s64 d, %65, 232;\nwgmma.fence.sync.aligned;\nwgmma.mma_async.sync.aligned.m64n16k16.f32.bf16.bf16 {%0, %1, %2, %3, %4, %5, %6, %7}, {b0, b1, b2, b3}, d, 1, 1, 1, 0;\nwgmma.commit_group.sync.aligned;\nwgmma.wait_group.sync.aligned 1;\nmov.b32 a2, b1;\nmov.b32 a0, t0;\nmov.b32 a3, t0;\nmov.b32 a1, t1;\n"
        "ld.shared.b32 t0, [%64+7936];\nld.shared.b32 t1, [%64+8064];\nadd.s64 d, %65, 240;\nwgmma.fence.sync.aligned;\nwgmma.mma_async.sync.aligned.m64n8k16.f32.bf16.bf16 {%0, %1, %2, %3}, {a0, a1, a2, a3}, d, 1, 1, 1, 0;\nwgmma.commit_group.sync.aligned;\nwgmma.wait_group.sync.aligned 1;\nmov.b32 b2, a1;\nmov.b32 b0, t0;\nmov.b32 b3, t0;\nmov.b32 b1, t1;\n"
        "add.s64 d, %65, 248;\nwgmma.fence.sync.aligned;\nwgmma.mma_async.sync.aligned.m64n8k16.f32.bf16.bf16 {%0, %1, %2, %3}, {b0, b1, b2, b3}, d, 1, 1, 1, 0;\nwgmma.commit_group.sync.aligned;\nwgmma.wait_group.sync.aligned 0;\n"
        "}" : "+f"(d[0]), "+f"(d[1]), "+f"(d[2]), "+f"(d[3]), "+f"(d[4]), "+f"(d[5]), "+f"(d[6]), "+f"(d[7]), "+f"(d[8]), "+f"(d[9]), "+f"(d[10]), "+f"(d[11]), "+f"(d[12]), "+f"(d[13]), "+f"(d[14]), "+f"(d[15]), "+f"(d[16]), "+f"(d[17]), "+f"(d[18]), "+f"(d[19]), "+f"(d[20]), "+f"(d[21]), "+f"(d[22]), "+f"(d[23]), "+f"(d[24]), "+f"(d[25]), "+f"(d[26]), "+f"(d[27]), "+f"(d[28]), "+f"(d[29]), "+f"(d[30]), "+f"(d[31]), "+f"(d[32]), "+f"(d[33]), "+f"(d[34]), "+f"(d[35]), "+f"(d[36]), "+f"(d[37]), "+f"(d[38]), "+f"(d[39]), "+f"(d[40]), "+f"(d[41]), "+f"(d[42]), "+f"(d[43]), "+f"(d[44]), "+f"(d[45]), "+f"(d[46]), "+f"(d[47]), "+f"(d[48]), "+f"(d[49]), "+f"(d[50]), "+f"(d[51]), "+f"(d[52]), "+f"(d[53]), "+f"(d[54]), "+f"(d[55]), "+f"(d[56]), "+f"(d[57]), "+f"(d[58]), "+f"(d[59]), "+f"(d[60]), "+f"(d[61]), "+f"(d[62]), "+f"(d[63]) : "r"(pa), "l"(db) : "memory");
}
__device__ __forceinline__ void wgmma_rs80(float (&d)[40], uint32_t a0, uint32_t a1, uint32_t a2, uint32_t a3, uint64_t db, int sc) {
    asm volatile("{\n.reg .pred p;\nsetp.ne.b32 p, %45, 0;\n"
        "wgmma.mma_async.sync.aligned.m64n80k16.f32.bf16.bf16 {%0, %1, %2, %3, %4, %5, %6, %7, %8, %9, %10, %11, %12, %13, %14, %15, %16, %17, %18, %19, %20, %21, %22, %23, %24, %25, %26, %27, %28, %29, %30, %31, %32, %33, %34, %35, %36, %37, %38, %39}, {%40, %41, %42, %43}, %44, p, 1, 1, 1;\n}\n"
        : "+f"(d[0]), "+f"(d[1]), "+f"(d[2]), "+f"(d[3]), "+f"(d[4]), "+f"(d[5]), "+f"(d[6]), "+f"(d[7]), "+f"(d[8]), "+f"(d[9]), "+f"(d[10]), "+f"(d[11]), "+f"(d[12]), "+f"(d[13]), "+f"(d[14]), "+f"(d[15]), "+f"(d[16]), "+f"(d[17]), "+f"(d[18]), "+f"(d[19]), "+f"(d[20]), "+f"(d[21]), "+f"(d[22]), "+f"(d[23]), "+f"(d[24]), "+f"(d[25]), "+f"(d[26]), "+f"(d[27]), "+f"(d[28]), "+f"(d[29]), "+f"(d[30]), "+f"(d[31]), "+f"(d[32]), "+f"(d[33]), "+f"(d[34]), "+f"(d[35]), "+f"(d[36]), "+f"(d[37]), "+f"(d[38]), "+f"(d[39]) : "r"(a0), "r"(a1), "r"(a2), "r"(a3), "l"(db), "r"(sc));
}
__device__ __forceinline__ void wgmma_ss80(float (&d)[40], uint64_t da, uint64_t db, int sc) {
    asm volatile("{\n.reg .pred p;\nsetp.ne.b32 p, %42, 0;\n"
        "wgmma.mma_async.sync.aligned.m64n80k16.f32.bf16.bf16 {%0, %1, %2, %3, %4, %5, %6, %7, %8, %9, %10, %11, %12, %13, %14, %15, %16, %17, %18, %19, %20, %21, %22, %23, %24, %25, %26, %27, %28, %29, %30, %31, %32, %33, %34, %35, %36, %37, %38, %39}, %40, %41, p, 1, 1, 0, 1;\n}\n"
        : "+f"(d[0]), "+f"(d[1]), "+f"(d[2]), "+f"(d[3]), "+f"(d[4]), "+f"(d[5]), "+f"(d[6]), "+f"(d[7]), "+f"(d[8]), "+f"(d[9]), "+f"(d[10]), "+f"(d[11]), "+f"(d[12]), "+f"(d[13]), "+f"(d[14]), "+f"(d[15]), "+f"(d[16]), "+f"(d[17]), "+f"(d[18]), "+f"(d[19]), "+f"(d[20]), "+f"(d[21]), "+f"(d[22]), "+f"(d[23]), "+f"(d[24]), "+f"(d[25]), "+f"(d[26]), "+f"(d[27]), "+f"(d[28]), "+f"(d[29]), "+f"(d[30]), "+f"(d[31]), "+f"(d[32]), "+f"(d[33]), "+f"(d[34]), "+f"(d[35]), "+f"(d[36]), "+f"(d[37]), "+f"(d[38]), "+f"(d[39]) : "l"(da), "l"(db), "r"(sc));
}
__device__ __forceinline__ void wgmma_ss80t(float (&d)[40], uint64_t da, uint64_t db, int sc) {
    asm volatile("{\n.reg .pred p;\nsetp.ne.b32 p, %42, 0;\n"
        "wgmma.mma_async.sync.aligned.m64n80k16.f32.bf16.bf16 {%0, %1, %2, %3, %4, %5, %6, %7, %8, %9, %10, %11, %12, %13, %14, %15, %16, %17, %18, %19, %20, %21, %22, %23, %24, %25, %26, %27, %28, %29, %30, %31, %32, %33, %34, %35, %36, %37, %38, %39}, %40, %41, p, 1, 1, 1, 1;\n}\n"
        : "+f"(d[0]), "+f"(d[1]), "+f"(d[2]), "+f"(d[3]), "+f"(d[4]), "+f"(d[5]), "+f"(d[6]), "+f"(d[7]), "+f"(d[8]), "+f"(d[9]), "+f"(d[10]), "+f"(d[11]), "+f"(d[12]), "+f"(d[13]), "+f"(d[14]), "+f"(d[15]), "+f"(d[16]), "+f"(d[17]), "+f"(d[18]), "+f"(d[19]), "+f"(d[20]), "+f"(d[21]), "+f"(d[22]), "+f"(d[23]), "+f"(d[24]), "+f"(d[25]), "+f"(d[26]), "+f"(d[27]), "+f"(d[28]), "+f"(d[29]), "+f"(d[30]), "+f"(d[31]), "+f"(d[32]), "+f"(d[33]), "+f"(d[34]), "+f"(d[35]), "+f"(d[36]), "+f"(d[37]), "+f"(d[38]), "+f"(d[39]) : "l"(da), "l"(db), "r"(sc));
}
__device__ __forceinline__ void wgmma_ss8_ta(float (&d)[4], uint64_t da, uint64_t db, int sc) {
    asm volatile("{\n.reg .pred p;\nsetp.ne.b32 p, %6, 0;\n"
        "wgmma.mma_async.sync.aligned.m64n8k16.f32.bf16.bf16 {%0, %1, %2, %3}, %4, %5, p, 1, 1, 1, 0;\n}\n"
        : "+f"(d[0]), "+f"(d[1]), "+f"(d[2]), "+f"(d[3]) : "l"(da), "l"(db), "r"(sc));
}
__device__ __forceinline__ void wgmma_rs8(float (&d)[4], uint32_t a0, uint32_t a1, uint32_t a2, uint32_t a3, uint64_t db, int sc) {
    asm volatile("{\n.reg .pred p;\nsetp.ne.b32 p, %9, 0;\n"
        "wgmma.mma_async.sync.aligned.m64n8k16.f32.bf16.bf16 {%0, %1, %2, %3}, {%4, %5, %6, %7}, %8, p, 1, 1, 0;\n}\n"
        : "+f"(d[0]), "+f"(d[1]), "+f"(d[2]), "+f"(d[3]) : "r"(a0), "r"(a1), "r"(a2), "r"(a3), "l"(db), "r"(sc));
}
__device__ __forceinline__ void wgmma_rs128(float (&d)[64], uint32_t a0, uint32_t a1, uint32_t a2, uint32_t a3, uint64_t db, int sc) {
    asm volatile("{\n.reg .pred p;\nsetp.ne.b32 p, %69, 0;\n"
        "wgmma.mma_async.sync.aligned.m64n128k16.f32.bf16.bf16 {%0, %1, %2, %3, %4, %5, %6, %7, %8, %9, %10, %11, %12, %13, %14, %15, %16, %17, %18, %19, %20, %21, %22, %23, %24, %25, %26, %27, %28, %29, %30, %31, %32, %33, %34, %35, %36, %37, %38, %39, %40, %41, %42, %43, %44, %45, %46, %47, %48, %49, %50, %51, %52, %53, %54, %55, %56, %57, %58, %59, %60, %61, %62, %63}, {%64, %65, %66, %67}, %68, p, 1, 1, 1;\n}\n"
        : "+f"(d[0]), "+f"(d[1]), "+f"(d[2]), "+f"(d[3]), "+f"(d[4]), "+f"(d[5]), "+f"(d[6]), "+f"(d[7]), "+f"(d[8]), "+f"(d[9]), "+f"(d[10]), "+f"(d[11]), "+f"(d[12]), "+f"(d[13]), "+f"(d[14]), "+f"(d[15]), "+f"(d[16]), "+f"(d[17]), "+f"(d[18]), "+f"(d[19]), "+f"(d[20]), "+f"(d[21]), "+f"(d[22]), "+f"(d[23]), "+f"(d[24]), "+f"(d[25]), "+f"(d[26]), "+f"(d[27]), "+f"(d[28]), "+f"(d[29]), "+f"(d[30]), "+f"(d[31]), "+f"(d[32]), "+f"(d[33]), "+f"(d[34]), "+f"(d[35]), "+f"(d[36]), "+f"(d[37]), "+f"(d[38]), "+f"(d[39]), "+f"(d[40]), "+f"(d[41]), "+f"(d[42]), "+f"(d[43]), "+f"(d[44]), "+f"(d[45]), "+f"(d[46]), "+f"(d[47]), "+f"(d[48]), "+f"(d[49]), "+f"(d[50]), "+f"(d[51]), "+f"(d[52]), "+f"(d[53]), "+f"(d[54]), "+f"(d[55]), "+f"(d[56]), "+f"(d[57]), "+f"(d[58]), "+f"(d[59]), "+f"(d[60]), "+f"(d[61]), "+f"(d[62]), "+f"(d[63]) : "r"(a0), "r"(a1), "r"(a2), "r"(a3), "l"(db), "r"(sc));
}
__device__ __forceinline__ void wgmma_rs88(float (&d)[44], uint32_t a0, uint32_t a1, uint32_t a2, uint32_t a3, uint64_t db, int sc) {
    asm volatile("{\n.reg .pred p;\nsetp.ne.b32 p, %49, 0;\n"
        "wgmma.mma_async.sync.aligned.m64n88k16.f32.bf16.bf16 {%0, %1, %2, %3, %4, %5, %6, %7, %8, %9, %10, %11, %12, %13, %14, %15, %16, %17, %18, %19, %20, %21, %22, %23, %24, %25, %26, %27, %28, %29, %30, %31, %32, %33, %34, %35, %36, %37, %38, %39, %40, %41, %42, %43}, {%44, %45, %46, %47}, %48, p, 1, 1, 1;\n}\n"
        : "+f"(d[0]), "+f"(d[1]), "+f"(d[2]), "+f"(d[3]), "+f"(d[4]), "+f"(d[5]), "+f"(d[6]), "+f"(d[7]), "+f"(d[8]), "+f"(d[9]), "+f"(d[10]), "+f"(d[11]), "+f"(d[12]), "+f"(d[13]), "+f"(d[14]), "+f"(d[15]), "+f"(d[16]), "+f"(d[17]), "+f"(d[18]), "+f"(d[19]), "+f"(d[20]), "+f"(d[21]), "+f"(d[22]), "+f"(d[23]), "+f"(d[24]), "+f"(d[25]), "+f"(d[26]), "+f"(d[27]), "+f"(d[28]), "+f"(d[29]), "+f"(d[30]), "+f"(d[31]), "+f"(d[32]), "+f"(d[33]), "+f"(d[34]), "+f"(d[35]), "+f"(d[36]), "+f"(d[37]), "+f"(d[38]), "+f"(d[39]), "+f"(d[40]), "+f"(d[41]), "+f"(d[42]), "+f"(d[43]) : "r"(a0), "r"(a1), "r"(a2), "r"(a3), "l"(db), "r"(sc));
}
__device__ __forceinline__ void wgmma_rs128k(float (&d)[64], uint32_t a0, uint32_t a1, uint32_t a2, uint32_t a3, uint64_t db, int sc) {
    asm volatile("{\n.reg .pred p;\nsetp.ne.b32 p, %69, 0;\n"
        "wgmma.mma_async.sync.aligned.m64n128k16.f32.bf16.bf16 {%0, %1, %2, %3, %4, %5, %6, %7, %8, %9, %10, %11, %12, %13, %14, %15, %16, %17, %18, %19, %20, %21, %22, %23, %24, %25, %26, %27, %28, %29, %30, %31, %32, %33, %34, %35, %36, %37, %38, %39, %40, %41, %42, %43, %44, %45, %46, %47, %48, %49, %50, %51, %52, %53, %54, %55, %56, %57, %58, %59, %60, %61, %62, %63}, {%64, %65, %66, %67}, %68, p, 1, 1, 0;\n}\n"
        : "+f"(d[0]), "+f"(d[1]), "+f"(d[2]), "+f"(d[3]), "+f"(d[4]), "+f"(d[5]), "+f"(d[6]), "+f"(d[7]), "+f"(d[8]), "+f"(d[9]), "+f"(d[10]), "+f"(d[11]), "+f"(d[12]), "+f"(d[13]), "+f"(d[14]), "+f"(d[15]), "+f"(d[16]), "+f"(d[17]), "+f"(d[18]), "+f"(d[19]), "+f"(d[20]), "+f"(d[21]), "+f"(d[22]), "+f"(d[23]), "+f"(d[24]), "+f"(d[25]), "+f"(d[26]), "+f"(d[27]), "+f"(d[28]), "+f"(d[29]), "+f"(d[30]), "+f"(d[31]), "+f"(d[32]), "+f"(d[33]), "+f"(d[34]), "+f"(d[35]), "+f"(d[36]), "+f"(d[37]), "+f"(d[38]), "+f"(d[39]), "+f"(d[40]), "+f"(d[41]), "+f"(d[42]), "+f"(d[43]), "+f"(d[44]), "+f"(d[45]), "+f"(d[46]), "+f"(d[47]), "+f"(d[48]), "+f"(d[49]), "+f"(d[50]), "+f"(d[51]), "+f"(d[52]), "+f"(d[53]), "+f"(d[54]), "+f"(d[55]), "+f"(d[56]), "+f"(d[57]), "+f"(d[58]), "+f"(d[59]), "+f"(d[60]), "+f"(d[61]), "+f"(d[62]), "+f"(d[63]) : "r"(a0), "r"(a1), "r"(a2), "r"(a3), "l"(db), "r"(sc));
}
__device__ __forceinline__ void wgmma_rs88k(float (&d)[44], uint32_t a0, uint32_t a1, uint32_t a2, uint32_t a3, uint64_t db, int sc) {
    asm volatile("{\n.reg .pred p;\nsetp.ne.b32 p, %49, 0;\n"
        "wgmma.mma_async.sync.aligned.m64n88k16.f32.bf16.bf16 {%0, %1, %2, %3, %4, %5, %6, %7, %8, %9, %10, %11, %12, %13, %14, %15, %16, %17, %18, %19, %20, %21, %22, %23, %24, %25, %26, %27, %28, %29, %30, %31, %32, %33, %34, %35, %36, %37, %38, %39, %40, %41, %42, %43}, {%44, %45, %46, %47}, %48, p, 1, 1, 0;\n}\n"
        : "+f"(d[0]), "+f"(d[1]), "+f"(d[2]), "+f"(d[3]), "+f"(d[4]), "+f"(d[5]), "+f"(d[6]), "+f"(d[7]), "+f"(d[8]), "+f"(d[9]), "+f"(d[10]), "+f"(d[11]), "+f"(d[12]), "+f"(d[13]), "+f"(d[14]), "+f"(d[15]), "+f"(d[16]), "+f"(d[17]), "+f"(d[18]), "+f"(d[19]), "+f"(d[20]), "+f"(d[21]), "+f"(d[22]), "+f"(d[23]), "+f"(d[24]), "+f"(d[25]), "+f"(d[26]), "+f"(d[27]), "+f"(d[28]), "+f"(d[29]), "+f"(d[30]), "+f"(d[31]), "+f"(d[32]), "+f"(d[33]), "+f"(d[34]), "+f"(d[35]), "+f"(d[36]), "+f"(d[37]), "+f"(d[38]), "+f"(d[39]), "+f"(d[40]), "+f"(d[41]), "+f"(d[42]), "+f"(d[43]) : "r"(a0), "r"(a1), "r"(a2), "r"(a3), "l"(db), "r"(sc));
}
__device__ __forceinline__ void wgmma_rs80k(float (&d)[40], uint32_t a0, uint32_t a1, uint32_t a2, uint32_t a3, uint64_t db, int sc) {
    asm volatile("{\n.reg .pred p;\nsetp.ne.b32 p, %45, 0;\n"
        "wgmma.mma_async.sync.aligned.m64n80k16.f32.bf16.bf16 {%0, %1, %2, %3, %4, %5, %6, %7, %8, %9, %10, %11, %12, %13, %14, %15, %16, %17, %18, %19, %20, %21, %22, %23, %24, %25, %26, %27, %28, %29, %30, %31, %32, %33, %34, %35, %36, %37, %38, %39}, {%40, %41, %42, %43}, %44, p, 1, 1, 0;\n}\n"
        : "+f"(d[0]), "+f"(d[1]), "+f"(d[2]), "+f"(d[3]), "+f"(d[4]), "+f"(d[5]), "+f"(d[6]), "+f"(d[7]), "+f"(d[8]), "+f"(d[9]), "+f"(d[10]), "+f"(d[11]), "+f"(d[12]), "+f"(d[13]), "+f"(d[14]), "+f"(d[15]), "+f"(d[16]), "+f"(d[17]), "+f"(d[18]), "+f"(d[19]), "+f"(d[20]), "+f"(d[21]), "+f"(d[22]), "+f"(d[23]), "+f"(d[24]), "+f"(d[25]), "+f"(d[26]), "+f"(d[27]), "+f"(d[28]), "+f"(d[29]), "+f"(d[30]), "+f"(d[31]), "+f"(d[32]), "+f"(d[33]), "+f"(d[34]), "+f"(d[35]), "+f"(d[36]), "+f"(d[37]), "+f"(d[38]), "+f"(d[39]) : "r"(a0), "r"(a1), "r"(a2), "r"(a3), "l"(db), "r"(sc));
}
__device__ __forceinline__ void wgmma_rs64(float (&d)[32], uint32_t a0, uint32_t a1, uint32_t a2, uint32_t a3, uint64_t db, int sc) {
    asm volatile("{\n.reg .pred p;\nsetp.ne.b32 p, %37, 0;\n"
        "wgmma.mma_async.sync.aligned.m64n64k16.f32.bf16.bf16 {%0, %1, %2, %3, %4, %5, %6, %7, %8, %9, %10, %11, %12, %13, %14, %15, %16, %17, %18, %19, %20, %21, %22, %23, %24, %25, %26, %27, %28, %29, %30, %31}, {%32, %33, %34, %35}, %36, p, 1, 1, 1;\n}\n"
        : "+f"(d[0]), "+f"(d[1]), "+f"(d[2]), "+f"(d[3]), "+f"(d[4]), "+f"(d[5]), "+f"(d[6]), "+f"(d[7]), "+f"(d[8]), "+f"(d[9]), "+f"(d[10]), "+f"(d[11]), "+f"(d[12]), "+f"(d[13]), "+f"(d[14]), "+f"(d[15]), "+f"(d[16]), "+f"(d[17]), "+f"(d[18]), "+f"(d[19]), "+f"(d[20]), "+f"(d[21]), "+f"(d[22]), "+f"(d[23]), "+f"(d[24]), "+f"(d[25]), "+f"(d[26]), "+f"(d[27]), "+f"(d[28]), "+f"(d[29]), "+f"(d[30]), "+f"(d[31]) : "r"(a0), "r"(a1), "r"(a2), "r"(a3), "l"(db), "r"(sc));
}

__device__ __forceinline__ uint64_t mkdesc(uint32_t lo) { return ((uint64_t)0x40000040u << 32) | lo; }
template <int F> __device__ __forceinline__ uint32_t lop3(uint32_t a, uint32_t b, uint32_t c) { uint32_t r; asm("lop3.b32 %0, %1, %2, %3, %4;" : "=r"(r) : "r"(a), "r"(b), "r"(c), "n"(F)); return r; }
__device__ __forceinline__ void stg128_tag(void* p, uint32_t x, uint32_t y, uint32_t z, uint32_t u, uint32_t ep, int w) {
    stg128(p, lop3<0xB8>(x, w == 0, ep), lop3<0xB8>(y, w == 1, ep), lop3<0xB8>(z, w == 2, ep), lop3<0xB8>(u, w == 3, ep));
}
__device__ __forceinline__ uint32_t tag(uint32_t w, uint32_t ep) { asm("lop3.b32 %0, %0, 1, %1, 0xB8;" : "+r"(w) : "r"(ep)); return w; }
template <int N> __device__ __forceinline__ void pack_part(uint32_t (&p)[32], const float (&v)[N], uint32_t ep) {
#pragma unroll
    for (int i = 0; i < N / 2; i++) p[i] = (i & 3) ? pack2(v[2 * i], v[2 * i + 1]) : tag(pack2(v[2 * i], v[2 * i + 1]), ep);
#pragma unroll
    for (int i = 0; i < N / 2; i++) asm volatile("" : "+r"(p[i]));
}
__device__ __forceinline__ void st_part(uint4* p, const uint32_t* v) {
    asm volatile("{\n.reg .b64 l, h;\n.reg .b128 q;\nmov.b64 l, {%1, %2};\nmov.b64 h, {%3, %4};\nmov.b128 q, {l, h};\nst.relaxed.gpu.global.b128 [%0], q;\n}"
                 ::"l"(p), "r"(v[0]), "r"(v[1]), "r"(v[2]), "r"(v[3]) : "memory");
}
__device__ __forceinline__ void st_peer(uint32_t a, uint32_t x, uint32_t y, uint32_t z, uint32_t w, uint32_t bar) {
    asm volatile("st.async.shared::cluster.mbarrier::complete_tx::bytes.v4.b32 [%0], {%1, %2, %3, %4}, [%5];" ::"r"(a), "r"(x), "r"(y), "r"(z), "r"(w), "r"(bar) : "memory");
}
__device__ __forceinline__ int g4_block(int c, int j) { return c ? j ^ (8 - 2 * c) : 8 + (j & 1); }
__device__ __forceinline__ uint32_t recv_off(int w) { return w ? OFF_XR : OFF_REM; }
__device__ __forceinline__ uint4 ld_part(const void* p) {
    uint4 v;
    asm volatile("{\n.reg .b64 l, h;\n.reg .b128 q;\nld.relaxed.gpu.global.b128 q, [%4];\nmov.b128 {l, h}, q;\nmov.b64 {%0, %1}, l;\nmov.b64 {%2, %3}, h;\n}"
                 : "=r"(v.x), "=r"(v.y), "=r"(v.z), "=r"(v.w) : "l"(p) : "memory");
    return v;
}
__device__ __forceinline__ void ld_part4(uint4 (&u)[4], const uint4* p, int st) {
#pragma unroll
    for (int i = 0; i < 4; i++) u[i] = ld_part(p + i * st);
}
__device__ __forceinline__ uint32_t stale4(const uint4 (&u)[4], uint32_t ep) { return lop3<0x7E>(u[0].x, ep, u[1].x) | lop3<0x7E>(u[2].x, ep, u[3].x); }
__device__ __forceinline__ uint4 add2(uint4 a, uint4 b) { return make_uint4(add2(a.x, b.x), add2(a.y, b.y), add2(a.z, b.z), add2(a.w, b.w)); }
__device__ __forceinline__ uint4 fin16(uint4 v, uint4 b, uint4 c) { return make_uint4(fma2(c.x, v.x, b.x), fma2(c.y, v.y, b.y), fma2(c.z, v.z, b.z), fma2(c.w, v.w, b.w)); }
__device__ __forceinline__ uint4 scale16(float2 c, float2 d, float r0, float r1) {
    return make_uint4(pack2(c.x * r0, c.y * r0), pack2(c.x * r1, c.y * r1), pack2(d.x * r0, d.y * r0), pack2(d.x * r1, d.y * r1));
}
__device__ __forceinline__ uint32_t split2(float x) { const float h = rbf(x); return pack2(h, x - h); }
__device__ __forceinline__ uint32_t b80_desc(uint32_t dsb, uint32_t wn, uint32_t rn, uint32_t h) {
    const uint32_t wb = dsb + OFF_W + (wn & 7) * 16384 + h * 8192, rm = dsb + OFF_REM + rn * 4096 + h * 2048;
    return (wb >> 4) | ((rm - wb) << 12);
}
constexpr int64_t B80_STEP = 128 - (126 << 16), B80_HALF = 512 - (384 << 16);
constexpr uint32_t ring_mask(int L) {
    uint32_t m = 0;
    for (int i = L; i < 20; i++) m |= (uint32_t)(i >= 20 - L || !((i - L) & 1)) << i;
    return m;
}
constexpr uint32_t M0 = ring_mask(LEAD1), M1 = ring_mask(10), M2 = ring_mask(XLEAD);
static_assert(LEAD1 >= 5 && XLEAD >= 3 && XLEAD <= 5, "checked orders: a tile is consumed before its successor in the next phase is issued");
__device__ __forceinline__ uint32_t ring_pos(int w, int n, int L) { return w ? (n < 10 - L ? L + 2 * n : 10 + n) : (n < L ? n : 2 * n - L + 1); }
__device__ __forceinline__ int g1_block(int n, int j) { return n < 5 ? 2 * n + (j & 1) : 2 * n - 9 - (j & 1); }

__device__ __forceinline__ int g2_block(int n) { return (0x9874326510ull >> (4 * n)) & 15; }
__device__ __forceinline__ int g3_block(int n, int j) { return n ? n - (n <= j) : j; }
struct Tile { int e, w, kb; uint32_t at; };
__device__ __forceinline__ Tile ring_tile(int n, int grp, int j) {
    const int e = (n >= 20) + (n >= 40), i = n - 20 * e;
    const uint32_t M = e == 0 ? M0 : e == 1 ? M1 : M2;
    const int w = (M >> i) & 1, c = __popc(M & ((1u << i) - 1)), kb = w ? c : i - c, tile = grp + 16 * w;
    return {e, w, kb, 64u * (e == 0 ? tile + (g1_block(kb, j) << 16) : e == 1 ? g2_block(kb) + (tile << 16) : (10 * tile + g3_block(kb, j)) << 16)};
}
__device__ __forceinline__ void load_tile(const Maps& mp, uint32_t dst, int e, uint32_t at, uint32_t bar) {
    mbar_expect(bar, 8192);
    tma_ld2(dst, &mp.x[e], at & 0xffff, at >> 16, bar);
}

template <int OCT>
__device__ __forceinline__ void gemv_tile(float (&d)[4], uint32_t a, uint32_t b, int kb0) {
    uint32_t alo = ((a & 0x3FFFF) >> 4) | 0x10000u, blo_ = ((b & 0x3FFFF) >> 4) | (OCT << 16);
#pragma unroll 1
    for (int s = 0; s < 20; s += 4) {
        const int kb = kb0 + (s >> 2);
        const uint32_t bk = blo_ + (OCT == 7 ? (kb & 1) * 288 + (kb >> 1) * 56 : kb * 64);
        wg_fence();
#pragma unroll
        for (int q = 0; q < 4; q++) wgmma_ss8_ta(d, mkdesc(alo + (s + q) * 128), ((uint64_t)8 << 32) | (bk + q * 2 * OCT), s + q);
        wg_commit();
    }
    wg_wait<0>();
    reg_fence(d);
}

__device__ __forceinline__ void flush_tile(uint32_t st, bf16* dst, int u) {
#pragma unroll
    for (int i = 0; i < 2; i++) {
        const int idx = u + 320 * i, row = idx >> 3, c = idx & 7;
        stg128(dst + (size_t)row * S_ + 8 * c, lds128(st + row * 128 + ((c ^ ((row >> 1) & 7)) << 4)));
    }
}

__device__ __forceinline__ int tid_now() { int t; asm volatile("mov.u32 %0, %%tid.x;" : "=r"(t)); return t; }
__device__ __forceinline__ float zscale(float c) { return c == 0.f ? 0x1p-30f : c; }
__device__ __forceinline__ bool bar_any(int id, bool p) {
    uint32_t r;
    asm volatile("{\n.reg .pred a, b;\nsetp.ne.u32 a, %2, 0;\nbarrier.red.or.pred.aligned b, %1, 128, a;\nselp.u32 %0, 1, 0, b;\n}" : "=r"(r) : "r"(id), "r"((uint32_t)p) : "memory");
    return r != 0;
}

__global__ void __cluster_dims__(2, 1, 1) __launch_bounds__(NTHR, 1) fused_kernel(const __grid_constant__ Ptrs pp, bf16* __restrict__ out, const __grid_constant__ Maps mp) {
    extern __shared__ __align__(1024) uint8_t smem_raw[];
    const uint32_t sb = s2u(smem_raw), bars = sb + M_BAR, dsb = sb & 0x3FFFF;
    const int id = blockIdx.x, warp = __shfl_sync(0xffffffffu, (int)threadIdx.x >> 5, 0), wg = warp >> 2;
    const uint32_t c0 = clock_lo();
#define TIDS const int tid = tid_now(), lane = tid & 31, wt = tid & 127, g = lane >> 2, t = lane & 3; (void)wt; (void)g; (void)t;
    TS(threadIdx.x == 0, 0) TG(threadIdx.x == 0, 62)

    if (id >= 128) {
        TIDS
        if (sb & 1023) __trap();
        const int hs = id - 128;
        constexpr int H_B = 204800;
        static_assert(H_B + TAB_BYTES + 8 * VEC_BYTES <= OFF_M, "helper map");
        if (warp < 10 && elect()) { mbar_init(bars + warp * 8, 1); mbar_init(bars + 80 + warp * 8, 1); asm volatile("fence.mbarrier_init.release.cluster;" ::: "memory"); }
        __syncthreads();
        const uint32_t e0 = ld_cold(&g_epoch);
        wait_clock(c0, HELP_T);
        uint4 wr[10];
#pragma unroll
        for (int u = 0; u < 10; u++) wr[u] = ldg128(((hs >> 1) ? pp.w2 : pp.w1) + (size_t)(320 * (hs & 1) + (tid >> 4) + 32 * u) * D_ + 512 + 8 * (tid & 15));
        {
            const int r = tid >> 4, c = tid & 15;
            uint4* dst[2];
#pragma unroll
            for (int e = 0; e < 2; e++) {
                const int p = !(hs >> 1) ? r : e && (hs & 1) ? (r & ~14) | ((r & 6) << 1) | ((r & 8) >> 2) : (r & ~30) | ((r & 6) << 2) | ((r & 24) >> 2);
                dst[e] = &g_wr[((hs >> 1) * 8 + (c >> 1)) * 10 * 128 + (p & 15) * 8 + ((2 * (p >> 4) + (c & 1)) ^ (p & 7))];
            }
#pragma unroll
            for (int u = 0; u < 10; u++) stg128(reinterpret_cast<uint4*>(reinterpret_cast<uintptr_t>(dst[u >= 6]) ^ (64 * (u & 1))) +
                       ((hs >> 1) ? (0x9873265410ull >> (4 * (5 * (hs & 1) + (u >> 1)))) & 15 : 5 * (hs & 1) + (u >> 1)) * 128, wr[u]);
        }
        __syncthreads();
        if (warp == 0) signal_cnt(&g_cnt.wr[0], lane, 1);
        __syncthreads();
        if (warp < 5 && elect()) {
            const int un = 5 * hs + warp;
            mbar_expect(bars + warp * 8, 40960);
            tma_ld2(sb + warp * 40960, &mp.w1h, 64 * (un >> 1), 320 * (un & 1), bars + warp * 8);
            tma_ld2(sb + warp * 40960 + 20480, &mp.w1h, 64 * (un >> 1), 320 * (un & 1) + 160, bars + warp * 8);
        }
        if (tid < 320) {
            const uint4* gm = reinterpret_cast<const uint4*>(g_mod + 3 * D_) + tid;
            const unsigned epoch = e0 + 1;
            uint4 r[6];
            unsigned it = 0;
            for (;;) {
                uint32_t bad = 0;
#pragma unroll
                for (int i = 0; i < 6; i++) { r[i] = ld_part(gm + (i >> 1) * (D_ / 2) + (i & 1) * 3 * D_); bad |= (r[i].y ^ epoch) | (r[i].w ^ epoch); }
                if (__all_sync(~0u, !bad)) break;
                if (++it > SPIN_LIMIT) SPIN_FAIL(54)
            }
            uint32_t mv[3];
#pragma unroll
            for (int i = 0; i < 3; i++) mv[i] = pack2(__uint_as_float(r[2 * i].x) + __uint_as_float(r[2 * i + 1].x), __uint_as_float(r[2 * i].z) + __uint_as_float(r[2 * i + 1].z));
            const uint32_t sw2 = mv[0], cw = add2(mv[1], 0x3f803f80u), gw = mv[2];
            const float c0 = blo(cw), c1 = bhi(cw), s0 = blo(sw2), s1 = bhi(sw2);
            const float i0 = __frcp_rn(zscale(c0)), i1 = __frcp_rn(zscale(c1));
            const uint32_t ci = pack2(i0, i1), cq = pack2(i0 * i0, i1 * i1);
            const uint32_t a = sb + H_B + ((tid >> 5) & 1) * 4608 + (tid >> 6) * 896 + ((tid >> 2) & 7) * 112 + (tid & 3) * 4;
            sts32(a, ci); sts32(a + 16, pack2(i0 - blo(ci), i1 - bhi(ci)));
            sts32(a + 32, cq); sts32(a + 48, pack2(fmaf(i0, i0, -blo(cq)), fmaf(i1, i1, -bhi(cq))));
            sts32(a + 64, cw); sts32(a + 80, sw2); sts32(a + 96, 0x3f803f80u);
            if ((tid & ~35) == 284) sts32(a + 112, 0);
            const uint32_t v = sb + H_B + TAB_BYTES + (tid < 256 ? (tid >> 5) * VEC_BYTES + (tid & 31) * 8 : ((tid - 256) >> 3) * VEC_BYTES + 256 + (tid & 7) * 8);
            sts64f(v, blo(gw), bhi(gw)); sts64f(v + 320, c0, c1); sts64f(v + 640, s0, s1); sts64f(v + 960, i0, i1);
            float k[5] = {c0 + c1, s0 + s1, fmaf(c0, c0, c1 * c1), fmaf(c0, s0, c1 * s1), fmaf(s0, s0, s1 * s1)};
#pragma unroll 1
            for (int o = 16; o; o >>= 1) {
#pragma unroll
                for (int e = 0; e < 5; e++) k[e] += __shfl_xor_sync(~0u, k[e], o);
            }
            const uint32_t ks = sb + H_B + TAB_BYTES + (lane & 7) * VEC_BYTES + 1280 + (warp >> 1) * 32;
            if ((warp & 1) && lane < 8) { sts128f(ks, k[0], k[1], k[2], k[3]); sts128f(ks + 16, k[4], 0.f, 0.f, 0.f); }
            bar_sync(3, 320);
            if (!(warp & 1) && lane < 8) {
                const float4 o = lds128f(ks);
                sts128f(ks, k[0] + o.x, k[1] + o.y, k[2] + o.z, k[3] + o.w); sts32(ks + 16, __float_as_uint(k[4] + __uint_as_float(lds32(ks + 16))));
            }
            fence_async_smem();
        }
        __syncthreads();
        if (hs == 0 && warp == 15 && elect()) {
            asm volatile("cp.async.bulk.global.shared::cta.bulk_group [%0], [%1], %2;\ncp.async.bulk.commit_group;\ncp.async.bulk.wait_group 0;"
                         ::"l"(g_tab), "r"(sb + H_B), "n"(TAB_BYTES + 8 * VEC_BYTES) : "memory");
            asm volatile("red.release.gpu.global.add.u32 [%0], 1;" ::"l"(&g_cnt.tab[0]) : "memory");
        }
        __syncwarp();
#pragma unroll 1
        for (int i = wg; i < 20; i += 4) {
            const int r = i / 5, b = i - 5 * r, un = 5 * hs + b, u3 = 20 * r + un;
            auto refill = [&](int e, int u, uint32_t fb) {
                mbar_expect(fb, 40960);
                tma_ld2(sb + e * 40960, &mp.w3h, 64 * (u >> 1), 320 * (u & 1), fb);
                tma_ld2(sb + e * 40960 + 20480, &mp.w3h, 64 * (u >> 1), 320 * (u & 1) + 160, fb);
            };
            if (i > 4 && i < 9) {
                bar_sync(1, 512);
                if (warp == 0) {
                    signal_cnt(&g_cnt.uv[0], lane, 1);
                    if (elect()) {
#pragma unroll 1
                        for (int e = 0; e < 5; e++) refill(e, 5 * hs + e, bars + (5 + e) * 8);
                        l2_prefetch(pp.w2 + (size_t)160 * hs * D_, 160 * D_ * 2);
                    }
                    __syncwarp();
                }
            }
            mbar_wait(bars + i * 8, 0);
            float d[4];
            gemv_tile<7>(d, sb + b * 40960, sb + H_B, 5 * (un & 1));
            const int col = 16 * (warp & 3) + g;
            float* dst = r ? g_cs3 + (un & 1) * 1920 + 64 * ((u3 >> 1) - 10) + col : g_uv + (un & 1) * 3 * D_ + 2 * D_ + 64 * (un >> 1) + col;
            if (t == 3) { dst[0] = d[0]; dst[8] = d[2]; }
            if (r == 0 && t == 2) { dst[-2 * D_] = d[0]; dst[8 - 2 * D_] = d[2]; dst[-D_] = d[1]; dst[8 - D_] = d[3]; }
            if (r == 1 || r == 2) {
                bar_sync(4 + wg, 128);
                if (wt == 0) refill(b, u3, bars + (i + 5) * 8);
            }
        }
        __syncthreads();
        if (warp == 0) signal_cnt(&g_cnt.cs[0], lane, 1);
        if (tid == 511) l2_prefetch(pp.w4 + (size_t)432 * hs * D_, 432 * D_ * 2);
        for (uint32_t it = 0; (int)(ld_cold(&g_cnt.cs[0]) - 4 * (e0 + 1)) < 0;) { if (++it > SPIN_LIMIT) SPIN_FAIL(47) }
        asm volatile("fence.acquire.gpu;" ::: "memory");
        if (tid < 432) {
            const int jj = 2 * hs + (tid >= 216), c = tid % 216;
            const float* src = g_cs3 + (c < 192 ? 192 * jj + c : 1344 + 24 * jj + c);
            const uint32_t s = split2(ldcg32f(src) + ldcg32f(src + 1920));
            stg128(&g_cs3b[432 * hs + tid], s, s & 0xffffu, 0, 0);
        }
        __syncthreads();
        if (warp == 0) signal_cnt(&g_cnt.cs2[0], lane, 1);
        if (tid == 0 && hs == 3) {
            uint32_t it = 0;
            while (ld_cold(&g_epoch) == e0) { __nanosleep(256); if (++it > (1u << 20)) SPIN_FAIL(48) }
        }
        return;
    }

    if (elect()) {
        if (warp == 15) {
            mbar_init(bars + B_IN * 8, 1); mbar_init(bars + B_IN * 8 + 8, 1);
            asm volatile("fence.mbarrier_init.release.cluster;" ::: "memory");
            mbar_expect(bars + B_IN * 8, 131 * 160);
            tma_ld2(sb + OFF_KIN, &mp.k, 80 * (id & 7), 64 * (id >> 3) - 3, bars + B_IN * 8);
            tma_ld2(sb + OFF_VIN, &mp.v, 80 * (id & 7), 64 * (id >> 3), bars + B_IN * 8);
        } else if (warp < 13) {
            const uint32_t n = (0x4C11111111881ull >> (4 * warp)) & 15;
#pragma unroll
            for (int i = 0; i < 4; i++) mbar_init(bars + warp * 64 + i * 8, n);
            if (warp == 11) { mbar_init(bars + B_XFREE * 8, 16); mbar_init(bars + B_OWN * 8, 8); }
            else {
#pragma unroll
                for (int i = 4; i < 8; i++) mbar_init(bars + warp * 64 + i * 8, n);
            }
            asm volatile("fence.mbarrier_init.release.cluster;" ::: "memory");
        }
    }
    asm volatile("" ::"l"(pp.s), "l"(pp.c), "l"(out));
    TR4((threadIdx.x & 31) == 0, warp)
    const int pr = id >> 1;
    const int grp = pr < 4 ? 15 : pr < 36 ? (pr - 4) & 7 : 8 + (pr - 36) % 7;
    const int j = 2 * (pr < 4 ? pr : pr < 36 ? (pr - 4) >> 3 : (pr - 36) / 7) + (id & 1);

    if (wg == 3) {
        TIDS
        const int sw = warp - 12;
        uint32_t ep = ld_cold(&g_epoch);
        TR4(lane == 0, 20 + sw)
        __syncthreads();
        TR4(lane == 0, 30 + sw)
        asm volatile("barrier.cluster.arrive.relaxed.aligned;" ::: "memory");
        if (sw == 0) {
#pragma unroll 1
            for (int n = 0; n < PF_N; n++) {
                wait_clock(c0, PF_T0 + PF_DT * n);
                if (elect()) l2_prefetch(n < 4 ? (const char*)pp.q + id * 20480 + n * 5120 : (const char*)pp.w_mod + id * 38400 + (n - 4) * 4800, n < 4 ? 5120 : 4800);
            }
        } else if (sw == 1) {
            wait_clock(c0, T_SSM);
            if (elect()) {
                mbar_expect(bars + B_SSM * 8, 20480);
                bulk_ld(sb + OFF_SSM, pp.ssm_k + (size_t)5 * id * S_, 20480, bars + B_SSM * 8);
            }
            mbar_spin(bars + B_KVS * 8, 0);
            signal_cnt(&g_cnt.kv[(id & 7) * 32], lane, 1, true);
            TS(lane == 0, 2)
            mbar_spin(bars + B_RAW * 8, 0);
            if (elect()) {
                mbar_expect(bars + B_QIN * 8, 20480);
                tma_ld3(sb + OFF_QIN, &mp.q, 0, 16 * id, 0, bars + B_QIN * 8);
            }
        } else if (sw == 2) {
            if (elect()) {
#pragma unroll 1
                for (int i = 2; i < (int)(sizeof(Maps) / sizeof(CUtensorMap)); i++) asm volatile("prefetch.tensormap [%0];" ::"l"(&mp.k + i) : "memory");
#pragma unroll 1
                for (int i = B_SUMS; i < B_LAND; i++) mbar_expect(bars + i * 8, i < B_RECV ? 2048 : (i & 3) < 3 ? 8192 : 3072);
            }
            wait_cnt(&g_cnt.kv[(id >> 4) * 32], 16 * ep + 16 - SKIP_KV, true);
            TS(lane == 0, 4)
            if (elect()) {
                mbar_expect(bars + B_RAW * 8, 12288);
                mbar_expect(bars + B_RAW2 * 8, 8192);
#pragma unroll
                for (int c = 0; c < 5; c++) bulk_ld(sb + OFF_CH + c * CH_BYTES, g_kvT + (size_t)(5 * id + c) * S_, 4096, bars + (c < 3 ? B_RAW : B_RAW2) * 8);
            }
            mbar_spin(bars + B_BK * 8, 0);
            mbar_spin(bars + B_QIN * 8, 0);
            if (id < 120 && elect()) {
                mbar_expect(bars + B_WM * 8, 40960);
                tma_ld2(sb + OFF_WM, &mp.wmod, 64 * pr, 320 * (id & 1), bars + B_WM * 8);
                tma_ld2(sb + OFF_WM + 20480, &mp.wmod, 64 * pr, 320 * (id & 1) + 160, bars + B_WM * 8);
            }
            TS(lane == 0, 57)
        } else {
            wait_clock(c0, T_KVB);
            if (elect()) {
                mbar_expect(bars + (B_IN + 1) * 8, 131 * 160);
                tma_ld2(sb + OFF_KIN + 10752, &mp.k, 80 * (id & 7), 64 * (id >> 3) + 1021, bars + (B_IN + 1) * 8);
                tma_ld2(sb + OFF_VIN + 10240, &mp.v, 80 * (id & 7), 64 * (id >> 3) + 1024, bars + (B_IN + 1) * 8);
            }
            TS(lane == 0, 53)
            if (lane == 0) sts32(sb + M_EP, ep + 1);
            sts32(sb + M_NUL + lane * 4, 0);
#pragma unroll 1
            for (int i = 0; i < 10; i++) sts128(sb + OFF_Z + i * 512 + lane * 16, 0, 0, 0, 0);
            __syncwarp();
#pragma unroll 1
            for (int i = lane; i < 160; i += 32) {
                const uint32_t c = ldg32(pp.c + 320 * (id & 1) + 2 * i);
                sts32(sb + OFF_Z + (i >> 2) * 128 + (i & 3) * 4, pack2(silu(blo(c)), silu(bhi(c))));
            }
            fence_async_smem();
            for (uint32_t ph = 0, again = 1; again; ph ^= 1) {
                mbar_spin(bars + B_RAW2 * 8, ph);
                uint32_t bad = 0;
#pragma unroll
                for (int i = 0; i < 8; i++) bad |= lop3<0x7E>(lds32(sb + OFF_CH + 3 * CH_BYTES + i * 512 + lane * 16), ~ep, lds32(sb + OFF_CH + 4 * CH_BYTES + i * 512 + lane * 16));
                again = __any_sync(~0u, bad & 1);
                if (again && elect()) {
                    mbar_expect(bars + B_RAW2 * 8, 8192);
#pragma unroll
                    for (int c = 3; c < 5; c++) bulk_ld(sb + OFF_CH + c * CH_BYTES, g_kvT + (size_t)(5 * id + c) * S_, 4096, bars + B_RAW2 * 8);
                }
            }
            if (elect()) mbar_arrive(bars + B_RAW3 * 8);
        }
        {
            mbar_spin(bars + B_QIN * 8, 0);
            asm volatile("add.u32 %0, %0, 1;" : "+r"(ep));
            TS(wt == 0, 54)
            const int tk = 8 * ((lane >> 1) & 1) + 2 * (lane >> 3) + (lane & 1), ck = 4 * (sw & 1) + ((lane >> 1) & 2);
            const uint32_t src = sb + OFF_QIN + (sw >> 1) * 2048 + tk * 128;
            bf16* dst = g_qT + (size_t)id * 16 * D_ + (32 * sw + 8 * (t & 2) + g) * 16 + 8 * (t & 1);
#pragma unroll 1
            for (int i = 0; i < 5; i++) {
                uint32_t r[8];
                ldsm4t(src + i * 4096 + ((ck ^ (tk & 7)) << 4), r[0], r[1], r[2], r[3]);
                ldsm4t(src + i * 4096 + (((ck + 1) ^ (tk & 7)) << 4), r[4], r[5], r[6], r[7]);
                stg128(dst + i * 2048, tag(r[0], ep), r[1], r[2], r[3]);
                stg128(dst + i * 2048 + 128, tag(r[4], ep), r[5], r[6], r[7]);
            }
            float s1 = 0.f, s2 = 0.f;
#pragma unroll 2
            for (int i = 0; i < 10; i++) {
                const uint4 w4 = lds128(sb + OFF_QIN + i * 2048 + wt * 16);
                const uint32_t w[4] = {w4.x, w4.y, w4.z, w4.w};
#pragma unroll
                for (int e = 0; e < 4; e++) { const float a = blo(w[e]), b = bhi(w[e]); s1 += a + b; s2 = fmaf(a, a, fmaf(b, b, s2)); }
            }
#pragma unroll
            for (int o = 1; o < 8; o *= 2) { s1 += __shfl_xor_sync(~0u, s1, o); s2 += __shfl_xor_sync(~0u, s2, o); }
            s1 *= 1.f / D_;
            uint32_t rs = pack2(rsqrtf(fmaxf(s2 * (1.f / D_) - s1 * s1, 0.f) + 1e-5f), 0.f);
            if (lane < 8) rs = tag(rs, ep);
            rs = pack2(blo(rs), -s1 * blo(rs));
            const uint32_t sel = lane ? 0x7632 : 0x5410;
            const uint32_t a0 = __shfl_sync(~0u, rs, 0), a1 = __shfl_sync(~0u, rs, 8), a2 = __shfl_sync(~0u, rs, 16), a3 = __shfl_sync(~0u, rs, 24);
            if (lane < 2) stg64(g_qst + lane * S_ + 16 * id + 4 * sw, tag(__byte_perm(a0, a1, sel), ep), __byte_perm(a2, a3, sel));
            TS(wt == 0, 55)
        }
        bar_sync(6, 128);
        if (sw == 3) {
            signal_cnt(&g_cnt.q[(lane & 3) * 32], lane, 4, true);
            TS(lane == 0, 3)
        }
        asm volatile("setmaxnreg.dec.sync.aligned.u32 32;");
        asm volatile("barrier.cluster.wait.aligned;" ::: "memory");
        if (sw == 1) {
            mbar_spin(bars + B_XS * 8, 0);
            signal_cnt(&g_cnt.x[(lane & 3) * 32], lane, 4, true);
            TS(lane == 0, 20)
        }
        if (sw == 2) {
            wait_cnt(&g_cnt.q[(id & 3) * 32], 128 * ep - SKIP_Q, true);
            if (elect()) {
                mbar_expect(bars + B_QRDY * 8, 28672);
                tma_ld2(sb + OFF_QT, &mp.qT, 80 * id, 0, bars + B_QRDY * 8);
                bulk_ld(sb + OFF_QT + 20480, g_qst, 8192, bars + B_QRDY * 8);
            }
            TS(lane == 0, 8)
        }
        if (sw == 1 || sw == 2) {
            mbar_spin(bars + B_XS * 8, 0);
            fence_async_smem();
            int n = sw & 1;
            const uint32_t plan = ring_tile(min(2 * lane + n, 59), grp, j).at;
#pragma unroll 1
            for (int s = 0; s < 7; s++) {
                const int e = (s >= 2) + (s >= 5), end = (0ull + LEAD1 + (20 << 8) + (24 << 16) + (30ull << 24) + (40ull << 32) + ((40ull + XLEAD) << 40) + (60ull << 48)) >> (8 * s) & 255;
                if (s == 1 || s == 4 || s == 6) mbar_spin(bars + (B_GATE + 2 + e) * 8, !e);
                else if (s != 3 || grp == 15) {
                    wait_cnt(s == 0 ? &g_cnt.x[(id & 3) * 32] : s == 5 ? &g_cnt.g2[grp * 32] : &g_cnt.g1[(s == 2 ? min(max(grp - 1 + min(lane, 2), 0), 15) : 16) * 32],
                             e == 0 ? 128 * ep - SKIP_X : 32 * ep - (e == 1 ? SKIP_G1 : SKIP_G2), true);
                    TS(lane == 0 && sw == 2 && s != 3, 26 + 2 * e)
                }
#pragma unroll 1
                for (; n < end; n += 2) {
                    const uint32_t at = __shfl_sync(~0u, plan, n >> 1);
                    mbar_spin(bars + (B_XEMPTY + (n & 7)) * 8, ((n >> 3) & 1) ^ 1);
                    TR2(lane == 0 && n < 40, 20 + n)
                    if (elect()) {
                        if (n == 40 || n == 40 + XLEAD) {
                            mbar_arrive(bars + (B_LAND + (n & 7)) * 8);
                            asm volatile("mbarrier.arrive.shared.b64 _, [%0], 8;" ::"r"(bars + (B_XEMPTY + (n & 7)) * 8) : "memory");
                        } else load_tile(mp, sb + OFF_XR + (n & 7) * 8192, e, at, bars + (B_LAND + (n & 7)) * 8);
                    }
                }
            }
            if (sw == 1) return;
            unsigned old = 0;
            asm volatile("{\n.reg .pred P;\nsetp.eq.s32 P, %2, 0;\n@P atom.relaxed.gpu.global.add.u32 %0, [%1], %3;\n}" : "+r"(old) : "l"(&g_cnt.done[0]), "r"(lane), "r"(1) : "memory");
            signal_cnt(&g_epoch, lane, old == 128 * ep - 1, true);
        } else if (sw == 0) {
            wait_cnt(&g_cnt.wr[0], 4 * ep);
            mbar_spin(bars + B_QRDY * 8, 0);
            mbar_spin(bars + B_MODR * 8, 0);
            const uint32_t wf = bars + B_WFULL * 8, we = bars + B_WEMPTY * 8;
#pragma unroll 1
            for (int n = 0; n < 5; n++) {
                if (n == 3) { mbar_spin(bars + B_XS * 8, 0); fence_async_smem(); }
                TR2(lane == 0, 70 + n)
                if (elect()) {
                    const uint32_t fb = wf + n * 8, dst = sb + OFF_W + n * 16384;
                    mbar_expect(fb, 20480);
#pragma unroll 1
                    for (int h = 0; h < 2; h++) {
                        const int kb = g1_block(2 * n + h, j);
                        tma_ld2(dst + h * 8192, &mp.w1, 64 * j, 64 * kb, fb);
                        bulk_ld(sb + OFF_REM + n * 4096 + h * 2048, &g_wr[(j * 10 + kb) * 128], 2048, fb);
                    }
                }
            }
            mbar_spin(bars + B_GATE * 8, 0);
#pragma unroll 1
            for (int i = -3; i < 5; i++) {
                const int n = i < 0 ? 8 + i : 5 + i;
                const uint32_t fb = wf + (n & 7) * 8;
                if (i >= 0) mbar_spin(we + i * 8, 0);
                TR2(lane == 0 && i >= 0, 70 + n)
                if (elect()) {
                    if (i < 0 || i >= 3) {
                        mbar_expect(fb, 20480);
#pragma unroll 1
                        for (int h = 0; h < 2; h++) tma_ld5(sb + OFF_W + (n & 7) * 16384 + h * 8192, n < 9 ? &mp.w2a : &mp.w2b, 64 * j, n < 9 ? 2 * g2_block(2 * n - 10 + h) : 4 * h, fb);
                    }
                    if (i >= 0) bulk_ld(sb + OFF_REM + i * 4096, &g_wr[((8 + j) * 10 + 2 * i) * 128], 4096, fb);
                }
            }
            mbar_spin(bars + (B_GATE + 1) * 8, 0);
#pragma unroll 1
            for (int n = 10; n < 30; n++) {
                if (n == W3_N2) mbar_spin(bars + (B_GATE + 2) * 8, 0);
                mbar_spin(we + (n & 7) * 8, ((n >> 3) & 1) ^ 1);
                TR2(lane == 0, 70 + n)
                if (elect()) {
                    const uint32_t dst = sb + OFF_W + (n & 7) * 16384, fb = wf + (n & 7) * 8;
                    mbar_expect(fb, 13824);
                    const int row = 64 * g3_block((n - 10) >> 1, j) + 32 * (n & 1);
                    tma_ld3(dst, &mp.w3a, 0, row, 3 * j, fb);
                    tma_ld2(dst + 12288, &mp.w3b, 1536 + 24 * j, row, fb);
                }
            }
            mbar_spin(we + 6 * 8, 0);
            mbar_spin(bars + B_VEC3 * 8, 0);
            if (elect()) { mbar_expect(wf + 6 * 8, 3456); bulk_ld(sb + OFF_W + 6 * 16384, &g_cs3b[216 * j], 3456, wf + 6 * 8); }
#pragma unroll 1
            for (int n = 31; n < 50; n++) {
                const int e = n < 38 ? 4 : (n - 38) & 3, m0 = n == 35, m1 = e == 3 ? -1 : m0 | (e == 1), rem = 96 + 3 * (j >> 1);
                const int c1_ = j ^ (n < 38 ? 6 : 4 >> ((n - 38) >> 2) & 6), c0_ = n < 38 ? 8 + (j & 1) : c1_;
                const int f = (0xC840A80C204ull >> (4 * min(n - 31, e + 7))) & 15;
                const int r0 = m0 ? rem : 6 * (j ^ (f >> 3)) + (f & 6), r1 = m1 ? rem : r0 + (n < 38 ? 0 : 2);
                mbar_spin(we + (n & 7) * 8, ((n >> 3) & 1) ^ 1);
                if (elect()) {
                    const uint32_t dst = sb + OFF_W + (n & 7) * 16384, fb = wf + (n & 7) * 8;
                    mbar_expect(fb, m1 < 0 ? 8192 : 16384 - 2048 * (m0 + m1));
                    tma_ld2(dst, &mp.w4[m0], 64 * c0_, r0 * (32 >> m0), fb);
                    if (m1 >= 0) tma_ld2(dst + 8192, &mp.w4[m1], 64 * c1_, r1 * (32 >> m1), fb);
                }
            }
        } else {
            {
                wait_cnt(&g_cnt.tab[0], ep);
                mbar_spin(bars + B_MODR * 8, 0);
                if (elect()) {
                    mbar_expect(bars + B_TAB * 8, TAB_BYTES / 2 + VEC_BYTES);
                    bulk_ld(sb + OFF_TAB, g_tab + (j & 1) * (TAB_BYTES / 32), TAB_BYTES / 2, bars + B_TAB * 8);
                    bulk_ld(sb + M_GB, g_tab + (TAB_BYTES + j * VEC_BYTES) / 16, VEC_BYTES, bars + B_TAB * 8);
                }
                TS(lane == 0, 5)
            }
            wait_cnt(&g_cnt.uv[0], 4 * ep);
#pragma unroll 1
            for (int c = lane; c < 80; c += 32) {
                const float* src = g_uv + (c < 64 ? 64 * j + c : 448 + 16 * j + c);
                const uint32_t u = split2(ldcg32f(src) + ldcg32f(src + 3 * D_)), v = split2(ldcg32f(src + D_) + ldcg32f(src + 4 * D_));
                const uint32_t s = split2(ldcg32f(src + 2 * D_) + ldcg32f(src + 5 * D_));
                sts128(sb + OFF_F1 + c * 16, u, __byte_perm(u, v, 0x5410), __byte_perm(v, 0, 0x1032), s);
                sts128(sb + M_F1 + c * 16, s & 0xffffu, 0, 0, 0);
            }
            fence_async_smem();
            warp_arrive(bars + B_VEC * 8);
            TS(lane == 0, 9)
#pragma unroll 1
            for (int e = 1; e < 3; e++) {
                wait_cnt(e == 1 ? &g_cnt.g1[min(grp + 15 + min(lane, 2), 31) * 32] : &g_cnt.g2[(grp + 16) * 32], 32 * ep - (e == 1 ? SKIP_G1 : SKIP_G2), true);
                if (elect()) mbar_arrive(bars + (B_GATE + 2 + e) * 8);
                TS(lane == 0, 27 + 2 * e)
            }
            wait_cnt(&g_cnt.cs2[0], 4 * ep);
            if (elect()) mbar_arrive(bars + B_VEC3 * 8);
            TS(lane == 0, 19)
        }
        return;
    }

    {
        uint32_t ep;
        {
            TIDS
            ep = ld_cold(&g_epoch);
            const int cp = (tid + 16) % 40, cp1 = tid % 40;
            const uint4 sh0 = ldg128(pp.shift_k + (80 * (id & 7) + 2 * cp1) * 4), sh1 = ldg128(pp.shift_k + (80 * (id & 7) + 2 * cp) * 4);
            uint32_t dd;
            asm volatile("ld.global.nc.u16 %0, [%1];" : "=r"(dd) : "l"(pp.ssm_D + 5 * id + min(wg + 3 * lane, 4)));
            TR4(lane == 0, 40 + warp)
            __syncthreads();
            asm volatile("barrier.cluster.arrive.relaxed.aligned;" ::: "memory");
            asm volatile("add.u32 %0, %0, 1;" : "+r"(ep));
#pragma unroll 1
            for (int hw = 0; hw < 2; hw++) {
                if ((unsigned)(warp - 2 * hw) >= 10) continue;
                const int u = tid - 64 * hw;
                const int c = hw ? cp : cp1, oc = u / 40, line = 31 - 16 * hw - (id >> 3);
                const uint4 sh = hw ? sh1 : sh0;
                const uint32_t st = sb + OFF_ST + hw * 10240, sta = st + c * 256 + ((((6 - 2 * (oc & 3)) ^ (oc >> 2) ^ (line & 1)) ^ (c & 7)) << 4), in = oc * 1280 + c * 4;
                const uint32_t f0 = __byte_perm(sh.x, sh.z, 0x5410), f1 = __byte_perm(sh.x, sh.z, 0x7632), f2 = __byte_perm(sh.y, sh.w, 0x5410), f3 = __byte_perm(sh.y, sh.w, 0x7632);
                uint32_t kk[11], vv[8];
                mbar_spin(bars + (B_IN + hw) * 8, 0);
                TS(tid == 64, 18 + 42 * hw)
#pragma unroll
                for (int i = 0; i < 11; i++) kk[i] = lds32(sb + OFF_KIN + hw * 10752 + in + i * 160);
#pragma unroll
                for (int i = 0; i < 8; i++) vv[i] = lds32(sb + OFF_VIN + hw * 10240 + in + i * 160);
#pragma unroll
                for (int i = 0; i < 8; i++) vv[i] = mul2(fma2(kk[i + 3], f0, fma2(kk[i + 2], f1, fma2(kk[i + 1], f2, mul2(kk[i], f3)))), vv[i]);
                sts128(sta, tag(__byte_perm(vv[0], vv[1], 0x5410), ep), __byte_perm(vv[2], vv[3], 0x5410), __byte_perm(vv[4], vv[5], 0x5410), __byte_perm(vv[6], vv[7], 0x5410));
                sts128(sta + 128, tag(__byte_perm(vv[0], vv[1], 0x7632), ep), __byte_perm(vv[2], vv[3], 0x7632), __byte_perm(vv[4], vv[5], 0x7632), __byte_perm(vv[6], vv[7], 0x7632));
                bar_sync(7 + hw, 320);
                flush_tile(st, g_kvT + (size_t)(80 * (id & 7)) * S_ + 64 * line, u);
                TS(tid == 64 && hw, 1)
            }
            warp_arrive(bars + B_KVS * 8);
            if (tid < 320) sts128(sb + OFF_CH + (tid >> 6) * CH_BYTES + 4096 + (tid & 63) * 16, 0, 0, 0, 0);
            mbar_spin(bars + B_SSM * 8, 0);
            TS(tid == 0, 14)
#pragma unroll 1
            for (int u0 = wg; u0 < 20; u0 += 12) {
                uint2 w[4];
                uint32_t pv[4];
#pragma unroll
                for (int i = 0; i < 4; i++) {
                    const uint32_t a = sb + OFF_SSM + min(u0 + 3 * i, 19) * 1024 + wt * 8;
                    w[i] = lds64(a); pv[i] = lds32(a - 4);
                }
#pragma unroll
                for (int i = 0; i < 4; i++) {
                    const int un = min(u0 + 3 * i, 19);
                    sts128(sb + OFF_CH + (un >> 2) * CH_BYTES + OFF_P + (un & 3) * 2048 + wt * 16, __byte_perm(w[i].x, pv[i], 0x7610), __byte_perm(w[i].x, 0, 0x1032), __byte_perm(w[i].y, w[i].x, 0x7610), __byte_perm(w[i].y, 0, 0x1032));
                }
            }
            __syncwarp();
            if (wt < 2 - (wg >> 1)) {
                const uint32_t h = lds32(sb + OFF_SSM + (wg + 3 * wt) * 4096), h0 = pack2(blo(h) + blo(dd), 0.f);
                sts64f(sb + OFF_CH + (wg + 3 * wt) * CH_BYTES + OFF_P, __uint_as_float(h0), __uint_as_float(__byte_perm(h, h0, 0x5432)));
            }
            fence_async_smem();
            warp_arrive(bars + B_BK * 8);
            asm volatile("barrier.cluster.wait.aligned;" ::: "memory");
            mbar_spin(bars + B_BK * 8, 0);
            TS(tid == 0, 15)
        }

#pragma unroll 1
        for (int c = wg; c < 5; c += 3) {
            const uint32_t kvb = sb + OFF_CH + c * CH_BYTES;
            mbar_spin(bars + (c < 3 ? B_RAW : B_RAW3) * 8, 0);
            for (uint32_t ph = 0; c < 3; ph ^= 1) {
                const int wt = tid_now() & 127;
                if (!RARE(bar_any(1 + wg, lop3<0x7E>(lds32(kvb + wt * 16), ep, lds32(kvb + 2048 + wt * 16)) & 1))) break;
                if (wt == 0) { mbar_expect(bars + (B_RETRY + wg) * 8, 4096); bulk_ld(kvb, g_kvT + (size_t)(5 * id + c) * S_, 4096, bars + (B_RETRY + wg) * 8); }
                mbar_spin(bars + (B_RETRY + wg) * 8, ph);
            }
            TS(threadIdx.x == 0, c ? 13 : 11)
            float acc[64];
            {
                const int l = tid_now() & 31;
                conv_channel(acc, kvb + OFF_P + (8 * (warp & 3) + (l >> 2) - 2 * (l & 3)) * 4, (((uint64_t)0xC0000010u << 32) | ((kvb & 0x3FFFF) >> 4) | 0x10000u) + pp.nil);
            }
            TS(threadIdx.x == 0, c ? 16 : 12)
            if (c < 3) warp_arrive(bars + B_R1 * 8);
            else mbar_spin(bars + B_R1 * 8, 0);
            if (wg == 2 && id < 120) {
                TIDS
                mbar_spin(bars + B_RAW3 * 8, 0);
                mbar_spin(bars + B_WM * 8, 0);
                TS(wt == 0, 56)
                float d[4];
                gemv_tile<8>(d, sb + OFF_WM, sb + OFF_Z, 0);
                const float d2 = __shfl_up_sync(~0u, d[2], 1);
                TS(wt == 0, 7)
                if (t < 2) asm volatile("{\n.reg .b64 v;\nmov.b64 v, {%1, %2};\nst.relaxed.gpu.global.b64 [%0], v;\n}" ::"l"(g_mod + (id & 1) * 6 * D_ + 64 * pr + 16 * (warp & 3) + g + 8 * t),
                                        "r"(__float_as_uint(t ? d2 : d[0])), "r"(lds32(sb + M_EP)) : "memory");
            }
            TR4(threadIdx.x == 0, 60 + (c >= 3) * 10)
            TIDS
            const int e = 127 - 8 * (lane >> 4) - (lane & 7), u0 = (warp & 3) + 8 * (e >> 2) + (e & 3) + 4 * ((lane >> 3) & 1);
            const uint32_t ring = sb + OFF_RING + c * 16384 + (warp & 3) * 4096, wa = ring + (u0 ^ ((u0 >> 1) & 4)) * 16;
            if (lane < (warp & 3)) sts128(ring + lane * 16, 0, 0, 0, 0);
#pragma unroll
            for (int i = 0; i < 8; i++)
                stsm4t(i == 0 && u0 >= 256 ? sb + M_SINK : wa - 512 * i, pack2(acc[8 * i], acc[8 * i + 1]), pack2(acc[8 * i + 2], acc[8 * i + 3]),
                       pack2(acc[8 * i + 4], acc[8 * i + 5]), pack2(acc[8 * i + 6], acc[8 * i + 7]));
            warp_arrive(bars + (B_RING + c) * 8);
            TR4(threadIdx.x == 0, 61 + (c >= 3) * 10)
        }
        TIDS
        if (wg == 2) bar_sync(3, 128);
        if (warp == 9) {
            const int v = min(lane / 5, 3);
            const uint2* gm = g_mod + (v + (v == 3)) * D_ + 5 * id + lane % 5;
            const unsigned epoch = lds32(sb + M_EP);
            uint2 r0, r1;
            unsigned it = 0;
            do {
                r0 = ld_mod(gm); r1 = ld_mod(gm + 6 * D_);
                SPIN_CHECK(55)
            } while (!__all_sync(~0u, r0.y == epoch && r1.y == epoch));
            const float m0 = __uint_as_float(r0.x), m1 = __uint_as_float(r1.x);
            const float m = rbf(m0 + m1), p = rbf(1.f + m);
            const float cz = zscale(__shfl_sync(~0u, p, 15 + lane % 5)), ga = __shfl_sync(~0u, m, 10 + lane % 5);
            if (lane < 15) sts32(sb + M_AB + lane % 5 * 16 + v * 4, lane < 10 ? __float_as_uint(cz * ga * (lane < 5 ? m : p)) : pack2(cz, cz));
            warp_arrive(bars + B_MODR * 8);
            TS(lane == 0, 6)
        }
        mbar_spin(bars + B_QRDY * 8, 0);
        uint4 rs[2], nm[2];
#pragma unroll
        for (int h = 0; h < 2; h++) { rs[h] = lds128(sb + OFF_QT + 20480 + h * 2048 + wt * 16); nm[h] = lds128(sb + OFF_QT + 24576 + h * 2048 + wt * 16); }
        mbar_spin(bars + B_MODR * 8, 0);
        TR4(threadIdx.x == 0, 72)
        uint32_t it = 0;
        while (RARE(__any_sync(~0u, (lop3<0x7E>(rs[0].x, ep, rs[0].z) | lop3<0x7E>(nm[0].x, ep, nm[0].z) | lop3<0x7E>(rs[1].x, ep, rs[1].z) | lop3<0x7E>(nm[1].x, ep, nm[1].z)) & 1))) {
#pragma unroll
            for (int h = 0; h < 2; h++) { rs[h] = ld_part(g_qst + 1024 * h + 8 * wt); nm[h] = ld_part(g_qst + S_ + 1024 * h + 8 * wt); }
            STALE(1)
            SPIN_CHECK(53)
        }
        TR4(threadIdx.x == 0, 73)
#pragma unroll 1
        for (int c = wg == 2 ? 0 : 3 + wg; c < (wg == 2 ? 3 : 4 + wg); c++) {
            uint4 q[2], p[2][4];
#pragma unroll
            for (int h = 0; h < 2; h++) q[h] = lds128(sb + OFF_QT + h * 10240 + (wt >> 1) * 160 + c * 32 + (wt & 1) * 16);
            const float4 ab = lds128f(sb + M_AB + c * 16);
            mbar_spin(bars + (B_RING + c) * 8, 0);
            TR4(wt == 0, wg == 2 ? 80 + 2 * c : 74)
#pragma unroll
            for (int i = 0; i < 8; i++) p[i >> 2][i & 3] = lds128(sb + OFF_RING + c * 16384 + (i & 3) * 4096 + (i >> 2) * 2048 + (wt ^ ((wt >> 1) & 4)) * 16);
            while (RARE(__any_sync(~0u, lop3<0x7E>(q[0].x, ep, q[1].x) & 1))) {
#pragma unroll
                for (int h = 0; h < 2; h++) q[h] = ld_part(g_qT + ((64 * h + (wt >> 1)) * D_ + 5 * id + c) * 16 + 8 * (wt & 1));
                STALE(2)
                SPIN_CHECK(52)
            }
            TR4(wt == 0, wg == 2 ? 81 + 2 * c : 75)
#pragma unroll
            for (int h = 0; h < 2; h++) {
                const uint32_t qq[4] = {q[h].x, q[h].y, q[h].z, q[h].w}, r4[4] = {rs[h].x, rs[h].y, rs[h].z, rs[h].w}, n4[4] = {nm[h].x, nm[h].y, nm[h].z, nm[h].w};
                const uint4 y = add2(add2(p[h][0], p[h][1]), add2(p[h][2], p[h][3]));
                const uint32_t yy[4] = {y.x, y.y, y.z, y.w};
                uint32_t o[4];
#pragma unroll
                for (int i = 0; i < 4; i++) {
                    const uint32_t n = fma2(qq[i], r4[i], n4[i]);
                    o[i] = fma2(pack2(fmaf(blo(n), ab.y, ab.x), fmaf(bhi(n), ab.y, ab.x)), yy[i], mul2(qq[i], __float_as_uint(ab.z)));
                }
                stg128_tag(g_x1T + (size_t)(5 * id + c) * S_ + 1024 * h + 8 * wt, o[0], o[1], o[2], o[3], ep, ((5 * id + c) >> 3) & 3);
            }
        }
        warp_arrive(bars + B_XS * 8);
        TS(tid == 0, 17)
        TS(tid == 256, 52)
    }

    const uint32_t nil = pp.nil;
    const int wq = warp & 3;
    if (wg == 2) {
        TIDS
        asm volatile("setmaxnreg.dec.sync.aligned.u32 48;");
        {
            const uint32_t ep = lds32(sb + M_EP);
            uint32_t ph = 0;
            const Tile tl = ring_tile(min(4 * lane + wq, 59), grp, j);
            const uint32_t plan = bars + (B_XFULL + 10 * tl.w + tl.kb) * 8;
#pragma unroll 1
            for (int m = wq - 4; m < 60; m += 4) {
                const int n = max(m, 0);
                const uint32_t pl = __shfl_sync(~0u, plan, n >> 2), at = __shfl_sync(~0u, tl.at, n >> 2);
                const int e = (n >= 20) + (n >= 40);
                const uint32_t a = sb + OFF_XR + (n & 7) * 8192;
                uint32_t ta = a + (e == 0 ? lane * 128 + ((lane & 7) << 4) + (lane >> 3) * 4
                                 : e == 1 ? (lane & 15) * 128 + (((lane >> 4 << 1) ^ (lane & 7)) << 4) + (lane & 8) + (lane >> 4) * 4
                                          : lane * 32 + (lane >> 2) * 4);
                uint32_t tb = e == 0 ? ta ^ 32 : ta + 2048, tc = e == 2 ? ta + 1024 : ta ^ 64, td = e == 2 ? tb + 1024 : tb ^ 64;
                uint32_t live = m >= 0 && m != 40 && m != 40 + XLEAD,
                    f0 = pl;
                uint32_t f1 = m == GATE_W2 || m == GATE_W3 || m == GATE_W3B ? bars + (B_GATE + (m >= GATE_W3) + (m >= GATE_W3B)) * 8 : 0;
                if (lane) f0 = f1;
                if (lane > 1 || m < 0) f0 = 0;
                asm volatile("" : "+r"(ta), "+r"(tb), "+r"(tc), "+r"(td), "+r"(live), "+r"(f0));
                mbar_spin(bars + (m < 0 ? B_BK : B_LAND + (n & 7)) * 8, (n >> 3) & 1);
                TR5(lane == 0, n)
                while (true) {
                    uint32_t v[8];
#pragma unroll
                    for (int i = 0; i < 8; i++) v[i] = lds32(((i & 2) ? ((i & 1) ? td : tc) : (i & 1) ? tb : ta) + (i >> 2) * 4096);
                    const uint32_t bad = lop3<0xFE>(lop3<0x7E>(v[0], ep, v[1]), lop3<0x7E>(v[2], ep, v[3]), lop3<0x7E>(v[4], ep, v[5]));
                    if (!RARE(__any_sync(~0u, lop3<0xA8>(bad, lop3<0x7E>(v[6], ep, v[7]), live)))) break;
                    if (elect()) load_tile(mp, a, e, at, bars + (B_AGAIN + wq) * 8);
                    mbar_spin(bars + (B_AGAIN + wq) * 8, ph);
                    ph ^= 1;
                    STALE1(e)
                }
                TR5(lane == 0, 60 + n)
                if (f0) mbar_arrive(f0);
            }
        }
        if (wq == 0) {
#pragma unroll 1
            for (int w = 0; w < 2; w++) {
                const uint4* src = g_part + (size_t)(grp + 16 * w) * 40960;
                TR4(lane == 0, 90 + 2 * w)
                mbar_wait(bars + (B_RING + w) * 8, 1);
                TR4(lane == 0, 91 + 2 * w)
                if (elect()) {
                    const uint32_t fb = bars + (B_IN + w) * 8, rem = sb + OFF_OUT + w * 10240;
                    mbar_expect(fb, 10240);
                    bulk_ld(rem + 8192, &g_x1f[((grp + 16 * w) * 8 + j) * 640 + 512], 2048, fb);
#pragma unroll 1
                    for (int i = 0; i < 4; i++) bulk_ld(rem + i * 2048, src + ((j >> 2) + 2 * i) * 5120 + 4096 + j * 128, 2048, fb);
                }
            }
        }
#pragma unroll 1
        for (int uw = 0; uw < 2; uw++) {
            const int tile = grp + 16 * uw;
            const uint32_t ep = lds32(sb + M_EP), in = sb + OFF_OUT + uw * 10240 + wt * 16, sr = in - lane * 16;
            mbar_wait(bars + (B_IN + uw) * 8, 1);
            TR4(wt == 0, 94 + 3 * uw)
            uint4 u[4];
#pragma unroll
            for (int i = 0; i < 4; i++) u[i] = lds128(in + i * 2048);
            const uint4 base = lds128(in + 8192);
            const uint32_t ra = sb + M_F1 + (64 * uw + 16 * wq + g) * 4;
            const uint4 gr = scale16(lds64f(sb + M_GB + (64 + 2 * t) * 4), lds64f(sb + M_GB + (72 + 2 * t) * 4), __uint_as_float(lds32(ra)), __uint_as_float(lds32(ra + 32)));
            uint32_t it = 0;
            while (RARE(__any_sync(~0u, stale4(u, ep) & 1))) {
                ld_part4(u, g_part + (size_t)tile * 40960 + (j >> 2) * 5120 + 4096 + j * 128 + wt, 10240);
                STALE(3)
                if (++it > SPIN_LIMIT) SPIN_FAIL(58)
            }
            TR4(wt == 0, 95 + 3 * uw)
            const uint4 r = fin16(add2(add2(u[0], u[1]), add2(u[2], u[3])), base, gr);
            __syncwarp();
            stsm4(sr + (lane & 15) * 32 + (((lane >> 4) ^ ((lane >> 2) & 1)) << 4), r.x, r.y, r.z, r.w);
            __syncwarp();
            stg128(out + (size_t)(64 * tile + 16 * wq + (lane >> 1)) * D_ + 512 + 16 * j + 8 * (lane & 1), lds128(sr + (lane >> 1) * 32 + (((lane & 1) ^ ((lane >> 3) & 1)) << 4)));
            TR4(wt == 0, 96 + 3 * uw)
            __syncwarp();
        }
        TS(wt == 0, 21)
        if (wq == 0) {
            uint32_t it = 0;
            while (!mbar_try(bars + B_OWN * 8, 0)) { if (++it > SPIN_LIMIT) SPIN_FAIL(56) }
        }
        return;
    }

    TIDS
    const int uw = wg, tile = grp + 16 * uw, row0 = 64 * tile + 16 * wq;
    const bool leader = wt == 0; (void)leader;
    const uint32_t xfull = bars + (B_XFULL + 10 * uw) * 8, xempty = bars + B_XEMPTY * 8, wfull = bars + B_WFULL * 8, wempty = bars + B_WEMPTY * 8;
    const uint64_t dz = mkdesc(0) + pp.nil;
    auto xwait = [&](uint32_t kb, uint32_t e) { mbar_spin(xfull + kb * 8, e & 1); };
    asm volatile("setmaxnreg.inc.sync.aligned.u32 216;");
    const uint32_t ep = lds32(sb + M_EP);
    uint32_t x2[20];
    uint32_t res[20] = {};
    {
        float acc[40];
        const uint32_t la = ((lane & 7) + 8 * (lane >> 4)) * 128 + (((2 * wq + ((lane >> 3) & 1)) ^ (lane & 7)) << 4);
        auto pos = [&](int n) { return ring_pos(uw, n, LEAD1) & 7; };
        auto slot = [&](int n) { return sb + OFF_XR + pos(n) * 8192; };
        float al[2], r1[2], n1[2];
        {
            float sl[4], sq[4], v[4] = {};
            uint32_t z0[16], z1[16], zz[16];
            uint64_t bd = dz + b80_desc(dsb, 0, 0, 0), tb = (((uint64_t)8 << 32) | ((dsb + OFF_TAB) >> 4) | (7u << 16)) + pp.nil;
            auto ldfrag = [&](uint32_t (&z)[16], int n, bool even) {
#pragma unroll
                for (int q = 0; q < 4; q++) ldsm4t(slot(n) + la + q * 2048, z[4 * q], z[4 * q + 1], z[4 * q + 2], z[4 * q + 3]);
#pragma unroll
                for (int q = 0; q < 4; q++) ldsm4t_if(n == j >> 1, slot(n) + la + q * 2048, &res[4 * q]);
                if (even) ldsm4t_if(n == 4 && !((j ^ (j >> 2)) & 1), slot(n) + la + (j & 3) * 2048, &res[16]);
            };
            auto tile1 = [&](const uint32_t (&zc)[16], uint32_t (&zn)[16], int n, int h) {
                const bool last = h && n == 5, ok = mbar_test(xfull + (n + 1) * 8, 0), okw = !h || mbar_test(wfull + ((n + 1) >> 1) * 8, 0);
                wg_fence();
#pragma unroll
                for (int q = 0; q < 2; q++) wgmma_rs80(acc, zc[4 * q], zc[4 * q + 1], zc[4 * q + 2], zc[4 * q + 3], bd + q * B80_STEP, 1);
                wg_commit();
                if (lane < 2) mbar_arrive_after(xempty + pos(n) * 8, res[12], res[16], nil);
                wg_wait<1>();
                if (!h && n && lane == 0) mbar_arrive(wempty + ((n >> 1) - 1) * 8);
                if (!ok) xwait(n + 1, 0);
                if (!last) ldfrag(zn, n + 1, h);
#pragma unroll
                for (int e = 0; e < 16; e++) zz[e] = mul2(zc[e], zc[e]);
                const uint64_t t0 = last ? ((uint64_t)8 << 32) | ((dsb + M_NUL) >> 4) : tb;
                const uint32_t ts = last ? 0 : 14;
                wg_fence();
#pragma unroll
                for (int q = 0; q < 4; q++) wgmma_rs8(sl, zc[4 * q], zc[4 * q + 1], zc[4 * q + 2], zc[4 * q + 3], t0 + q * ts, 1);
#pragma unroll
                for (int q = 0; q < 4; q++) wgmma_rs8(sq, zz[4 * q], zz[4 * q + 1], zz[4 * q + 2], zz[4 * q + 3], t0 + q * ts, 1);
#pragma unroll
                for (int q = 2; q < 4; q++) wgmma_rs80(acc, zc[4 * q], zc[4 * q + 1], zc[4 * q + 2], zc[4 * q + 3], bd + q * B80_STEP, 1);
                wg_commit();
                tb += 56;
                bd = bd + (uint64_t)B80_HALF;
                if (!okw) mbar_spin(wfull + ((n + 1) >> 1) * 8, 0);
                TR(leader, 100 + 10 * uw + n)
            };
            zero(acc); zero(sl); zero(sq);
            mbar_spin(bars + B_TAB * 8, 0);
            float4 k = lds128f(sb + M_KS);
            float k4 = __uint_as_float(lds32(sb + M_KS + 16));
#pragma unroll
            for (int w = 1; w < 5; w++) {
                const float4 o = lds128f(sb + M_KS + w * 32);
                k.x += o.x; k.y += o.y; k.z += o.z; k.w += o.w; k4 += __uint_as_float(lds32(sb + M_KS + w * 32 + 16));
            }
            uint32_t fa[4];
            auto coefs = [&]() {
                mbar_spin(bars + (B_SUMS + uw) * 8, 0);
                TS(leader && !uw, 10)
                const float4 o = lds128f(sb + OFF_ROW + uw * 2048 + wt * 16);
                v[0] += o.x; v[1] += o.y; v[2] += o.z; v[3] += o.w;
#pragma unroll
                for (int h = 0; h < 2; h++) {
                    const int l0 = lane & ~3;
                    const float s1 = __shfl_sync(~0u, v[2 * h], l0), s2 = __shfl_sync(~0u, v[2 * h], l0 + 1), scc = __shfl_sync(~0u, v[2 * h], l0 + 2);
                    const float scs = __shfl_sync(~0u, v[2 * h + 1], l0 + 2), sc = __shfl_sync(~0u, v[2 * h], l0 + 3), sqq = __shfl_sync(~0u, v[2 * h + 1], l0 + 3);
                    const float m1 = s1 * (1.f / D_), va = fmaxf(s2 * (1.f / D_) - m1 * m1, 0.f) + 1e-5f, r = rsqrtf(va);
                    const float m2 = (r * (sc - m1 * k.x) + k.y) * (1.f / D_);
                    const float e2 = (r * (r * (sqq + m1 * (m1 * k.z - 2.f * scc)) + 2.f * (scs - m1 * k.w)) + k4) * (1.f / D_);
                    al[h] = r * 0.5f * rsqrtf(fmaxf(e2 - m2 * m2, 0.f) + 1e-5f); r1[h] = r; n1[h] = -m1 * r;
                    const uint32_t fb = split2(va * r), fx = split2(t == 3 ? -m2 * va * r : -m1), fc = __shfl_sync(~0u, fx, lane | 3);
                    fa[h] = __byte_perm(fx, fb, t == 1 ? 0x5432 : t == 2 ? 0x7654 : 0x1010);
                    fa[2 + h] = t ? 0 : fc >> 16;
                }
            };
            mbar_spin(wfull, 0);
            xwait(0, 0);
            TS(leader, 32 + uw)
            ldfrag(z0, 0, false);
#pragma unroll 1
            for (int n = 0; n < 6; n += 2) { tile1(z0, z1, n, 0); tile1(z1, z0, n + 1, 1); }
#pragma unroll
            for (int n = 6; n < 10; n++) {
                const uint64_t ad = dz + (((dsb + OFF_XR + pos(n) * 8192) >> 4) | 0x10000u);
                const bool ok = n == 9 || mbar_test(xfull + (n + 1) * 8, 0), okw = n != 7 || mbar_test(wfull + 4 * 8, 0);
                wg_fence();
#pragma unroll
                for (int q = 0; q < 4; q++) wgmma_ss80t(acc, ad + q * 128, bd + q * B80_STEP, 1);
                wg_commit();
                bd = bd + (uint64_t)B80_HALF;
                if (n == 8) coefs();
                if (n == 9) ldsm4t_if(9 - (j & 1) == 8 + (j >> 2), slot(9) + la + (j & 3) * 2048, &res[16]);
                wg_wait<1>();
                if (n > 6 && lane < 2) mbar_arrive(xempty + pos(n - 1) * 8);
                if (!(n & 1) && lane == 0) mbar_arrive(wempty + ((n >> 1) - 1) * 8);
                if (n == 6) {
                    reg_fence(sl); reg_fence(sq);
#pragma unroll
                    for (int e = 0; e < 2; e++) {
                        v[2 * e] = t == 0 ? sl[2 * e] + sl[2 * e + 1] : t == 1 ? sq[2 * e] + sq[2 * e + 1] : sl[2 * e];
                        v[2 * e + 1] = t == 2 ? sl[2 * e + 1] : sq[2 * e];
                    }
                    st_peer(peer_addr(sb + OFF_ROW + uw * 2048 + wt * 16), __float_as_uint(v[0]), __float_as_uint(v[1]), __float_as_uint(v[2]), __float_as_uint(v[3]), peer_addr(bars + (B_SUMS + uw) * 8));
                    TS(leader && !uw, 59)
                }
                if (!ok) xwait(n + 1, 0);
                if (!okw) mbar_spin(wfull + 4 * 8, 0);
                TR(leader, 100 + 10 * uw + n)
            }
            mbar_spin(bars + B_VEC * 8, 0);
            wg_fence();
            wgmma_rs80k(acc, fa[0], fa[1], fa[2], fa[3], ((uint64_t)8 << 32) | ((dsb + OFF_F1) >> 4) | (((M_F1 - OFF_F1) >> 4) << 16), 1);
            wg_commit();
        }
        wg_wait<0>();
        reg_fence(acc);
        if (lane < 2) mbar_arrive_after(xempty + pos(9) * 8, res[16], 0, nil);
        if (lane == 0) mbar_arrive(wempty + 4 * 8);
        TS(leader, 34 + uw)
        {
            bf16* const trow = g_t + (size_t)(row0 + g + 2) * D_;
#pragma unroll
            for (int b = 0; b < 3; b++) {
                uint32_t p[8];
#pragma unroll
                for (int ii = 0; ii < 4; ii++) {
                    const int i = 4 * b + ii;
                    if (i >= 10) continue;
#pragma unroll
                    for (int h = 0; h < 2; h++) p[(i & 3) + 4 * h] = pack2(gelu2(acc[4 * i + 2 * h] * al[h]), gelu2(acc[4 * i + 2 * h + 1] * al[h]));
                }
                if (b < 2) {
                    const int gr = (2 * j + b) / 5, sh = (gr & 1) ? -1 - (gr >> 1) : 1 + (gr >> 1);
                    bf16* dst = trow + 64 * j + 32 * b + 8 * t;
                    const int w = (((g + sh) >> 2) & 2) + (t >> 1);
                    stg128_tag(dst + sh * D_, p[0], p[1], p[2], p[3], ep, w);
                    stg128_tag(dst + (sh + 8) * D_, p[4], p[5], p[6], p[7], ep, w ^ 2);
                    if (row0 + g < sh || row0 + g + 8 >= S_ + sh) stg128_tag(dst + (sh > 0 ? 0 : 8) * D_, 0, 0, 0, 0, ep, (sh > 0 ? 0 : 2) + (t >> 1));
                } else {
                    bf16* dst = trow + 512 + 16 * j + 4 * t;
                    const uint32_t lo = t == (g < 2), hi = t == (g >= 2), o = j & 1;
                    stg64(dst - 2 * D_, lop3<0xB8>(p[0], lo & ~o, ep), lop3<0xB8>(p[1], lo & o, ep));
                    stg64(dst + 6 * D_, lop3<0xB8>(p[4], hi & ~o, ep), lop3<0xB8>(p[5], hi & o, ep));
                    if (row0 + g + 8 >= S_ - 2) stg64(dst + 8 * D_, ep & (t == 1) & ~o, ep & (t == 1) & o);
                }
            }
        }
        signal_cnt(&g_cnt.g1[tile * 32], lane, 1, true);
        TS(leader, 36 + uw)
#pragma unroll
        for (int i = 0; i < 10; i++) {
            const float2 c = lds64f(sb + M_C + (8 * i + 2 * t) * 4), s = lds64f(sb + M_SB + (8 * i + 2 * t) * 4);
#pragma unroll
            for (int h = 0; h < 2; h++) {
                acc[4 * i + 2 * h] = fmaf(blo(res[2 * i + h]), r1[h], fmaf(n1[h], c.x, s.x));
                acc[4 * i + 2 * h + 1] = fmaf(bhi(res[2 * i + h]), r1[h], fmaf(n1[h], c.y, s.y));
            }
        }
        mbar_spin(wfull + 5 * 8, 0);
        xwait(0, 1);
        TS(leader, 22 + uw)
        uint32_t xo = 32 + 16 * uw, xp = 0;
        const uint64_t ax = dz + (((dsb + OFF_XR) >> 4) | 0x10000u);
        uint64_t ad = ax + xo * 64, bd = dz + b80_desc(dsb, 5, 0, 0);
#pragma unroll 1
        for (int i = 0; i < 5; i++) {
            const uint32_t x1 = xfull + (1 + 2 * i) * 8, p1 = 1, x2 = xfull + min(2 + 2 * i, 9) * 8, p2 = 1;
            const uint32_t w2 = wfull + (min(6 + i, 9) & 7) * 8, pw = i >= 2;
            const bool ok1 = mbar_test(x1, p1);
            wg_fence();
#pragma unroll
            for (int q = 0; q < 4; q++) wgmma_ss80(acc, ad + q * 2, bd + q * B80_STEP, 1);
            wg_commit();
            wg_wait<1>();
            if (lane < 2 && i) mbar_arrive(xempty + xp);
            if (lane == 0 && i) mbar_arrive(wempty + ((4 + i) & 7) * 8);
            if (!ok1) mbar_spin(x1, p1);
            const bool ok2 = mbar_test(x2, p2), okw = mbar_test(w2, pw);
            wg_fence();
#pragma unroll
            for (int q = 0; q < 4; q++) wgmma_ss80(acc, ad + 512 + q * 2, bd + (uint64_t)(B80_HALF + q * B80_STEP), 1);
            wg_commit();
            const uint32_t xc = xo;
            xp = xo + 8; xo = (xo + 16) & 48;
            ad = ax + xo * 64;
            bd += i == 2 ? 2 * B80_HALF - 8192 + (8192ll << 16) : 2 * B80_HALF;
            asm volatile("" : "+l"(ad), "+l"(bd));
            wg_wait<1>();
            if (lane < 2) mbar_arrive(xempty + xc);
            if (!ok2) mbar_spin(x2, p2);
            if (!okw) mbar_spin(w2, pw);
            TR(leader, (uw ? 86 : 20) + 2 * i)
        }
        wg_wait<0>();
        reg_fence(acc);
        if (lane < 2) mbar_arrive(xempty + xp);
        if (lane == 0) mbar_arrive(wempty + (9 & 7) * 8);
        TS(leader, 38 + uw)
        float a0 = 0.f, b0 = 0.f, a1 = 0.f, b1 = 0.f;
#pragma unroll
        for (int i = 0; i < 5; i++) {
            uint32_t* p = &x2[4 * i];
#pragma unroll
            for (int e = 0; e < 4; e++) p[e] = pack2(acc[8 * i + 2 * e], acc[8 * i + 2 * e + 1]);
#pragma unroll
            for (int e = 0; e < 4; e++) p[e] = lop3<0xB8>(p[e], (((wt >> 3) ^ (wt << 2)) & 7) == e, ep);
            stg128(&g_x2f[(tile * 40 + (i < 4 ? 4 * j + i : 32 + j)) * 128 + wt], p[0], p[1], p[2], p[3]);
#pragma unroll
            for (int e = 0; e < 8; e += 4) {
                const float* u = &acc[8 * i + e];
                a0 += u[0] + u[1]; b0 = fmaf(u[0], u[0], fmaf(u[1], u[1], b0));
                a1 += u[2] + u[3]; b1 = fmaf(u[2], u[2], fmaf(u[3], u[3], b1));
            }
        }
#pragma unroll
        for (int o = 1; o < 4; o *= 2) {
            a0 += __shfl_xor_sync(~0u, a0, o); b0 += __shfl_xor_sync(~0u, b0, o);
            a1 += __shfl_xor_sync(~0u, a1, o); b1 += __shfl_xor_sync(~0u, b1, o);
        }
        if (t < 2) stg64(&g_stats[(tile * 8 + j) * 64 + 16 * wq + g + 8 * t], tag(__float_as_uint(t ? a1 : a0), ep), __float_as_uint(t ? b1 : b0));
        signal_cnt(&g_cnt.g2[tile * 32], lane, 1, true);
        TS(leader, 40 + uw)
#pragma unroll
        for (int i = 0; i < 10; i++) {
            const float2 c = lds64f(sb + M_GB + (8 * i + 2 * t) * 4), e = lds64f(sb + M_CI + (8 * i + 2 * t) * 4);
#pragma unroll
            for (int h = 0; h < 2; h++)
                res[2 * i + h] = fma2(pack2(c.x, c.y), x2[2 * i + h], pack2(e.x * blo(res[2 * i + h]), e.y * bhi(res[2 * i + h])));
        }
#pragma unroll
        for (int i = 0; i < 20; i++) asm volatile("" : "+r"(res[i]));
    }
    float acc0[64], acc1[44];
    float2 q[4];
    {
        uint4 f0, f1, f2, f3;
        auto xseq = [&](int kb) { return ring_pos(uw, kb, XLEAD) & 7; };
        auto step = [&](const uint4& f, uint64_t bd) {
            wg_fence();
            wgmma_rs128(acc0, f.x, f.y, f.z, f.w, bd, 1);
            wgmma_rs88(acc1, f.x, f.y, f.z, f.w, bd + 512, 1);
            wg_commit();
        };
        const uint32_t xa = sb + OFF_XR + wt * 16;
        const float2* const gs = &g_stats[(tile * 8 + 2 * t) * 64 + 16 * wq + g];
        zero(acc0); zero(acc1);
        uint32_t xs = 0;
        f0 = make_uint4(x2[0], x2[1], x2[2], x2[3]); f1 = make_uint4(x2[4], x2[5], x2[6], x2[7]);
        f2 = make_uint4(x2[8], x2[9], x2[10], x2[11]); f3 = make_uint4(x2[12], x2[13], x2[14], x2[15]);
#pragma unroll
        for (int i = 0; i < 4; i++) q[i] = make_float2(0.f, 0.f);
        mbar_spin(wempty + (9 & 7) * 8, 1);
        mbar_spin(wfull + (10 & 7) * 8, (10 >> 3) & 1);
#pragma unroll 1
        for (int kb = 0; kb < 10; kb++) {
            const uint32_t wn = 10 + 2 * kb;
            const uint64_t bd = dz + (((dsb + OFF_W + (wn & 7) * 16384) >> 4) | (256u << 16));
            step(f0, bd);
            wg_wait<1>();
            if (kb && lane == 0) mbar_arrive(wempty + ((wn - 1) & 7) * 8);
            lds128_if(kb, f2, xa + xs * 8192 + 4096); lds128_if(kb, f3, xa + xs * 8192 + 6144);
            const bool w1 = mbar_test(wfull + ((wn + 1) & 7) * 8, (wn >> 3) & 1), x1 = kb < 9 && mbar_test(xfull + (kb + 1) * 8, 0);
            step(f1, bd + 128);
            if (!w1) mbar_spin(wfull + ((wn + 1) & 7) * 8, (wn >> 3) & 1);
            step(f2, bd + 1024);
            if (lane < 2 && kb) mbar_arrive_after(xempty + xs * 8, f2.x, f3.x, nil);
            wg_wait<1>();
            if (lane == 0) mbar_arrive(wempty + (wn & 7) * 8);
            xs = xseq(kb + 1);
            if (x1) { f0 = lds128(xa + xs * 8192); f1 = lds128(xa + xs * 8192 + 2048); }
            const bool w2 = mbar_test(wfull + ((wn + 2) & 7) * 8, ((wn + 2) >> 3) & 1);
            step(f3, bd + 1152);
            if (kb < 9 && !x1) { xwait(kb + 1, 2); f0 = lds128(xa + xs * 8192); f1 = lds128(xa + xs * 8192 + 2048); }
            if (!w2) mbar_spin(wfull + ((wn + 2) & 7) * 8, ((wn + 2) >> 3) & 1);
            if (kb == 0) {
                TS(leader, 42 + uw)
#pragma unroll
                for (int i = 0; i < 4; i++) q[i] = ld_stat(gs + (i & 1) * 64 + 8 * (i >> 1));
            }
            if (kb == 4) {
                uint32_t it = 0;
                while (RARE(__any_sync(~0u, ((__float_as_uint(q[0].x) ^ ep) | (__float_as_uint(q[1].x) ^ ep) | (__float_as_uint(q[2].x) ^ ep) | (__float_as_uint(q[3].x) ^ ep)) & 1))) {
#pragma unroll
                    for (int i = 0; i < 4; i++) q[i] = ld_stat(gs + (i & 1) * 64 + 8 * (i >> 1));
                    SPIN_CHECK(49)
                }
                float a0 = q[0].x + q[1].x, b0 = q[0].y + q[1].y, a1 = q[2].x + q[3].x, b1 = q[2].y + q[3].y;
#pragma unroll
                for (int o = 1; o < 4; o *= 2) {
                    a0 += __shfl_xor_sync(~0u, a0, o); b0 += __shfl_xor_sync(~0u, b0, o);
                    a1 += __shfl_xor_sync(~0u, a1, o); b1 += __shfl_xor_sync(~0u, b1, o);
                }
                a0 *= 1.f / D_; a1 *= 1.f / D_;
                const float r0 = 0.5f * rsqrtf(fmaxf(b0 * (1.f / D_) - a0 * a0, 0.f) + 1e-5f), r1 = 0.5f * rsqrtf(fmaxf(b1 * (1.f / D_) - a1 * a1, 0.f) + 1e-5f);
                const uint32_t sel = t == 0 ? 0x1010 : t == 1 ? 0x4432 : 0x4444;
                if (t == 0) { sts32(sb + M_F1 + (64 * uw + 16 * wq + g) * 4, __float_as_uint(r0)); sts32(sb + M_F1 + (64 * uw + 16 * wq + g + 8) * 4, __float_as_uint(r1)); }
                q[2] = make_float2(8.f * 0.0356774081f * r0 * r0 * r0, 2.f * 0.7978845608f * r0);
                q[3] = make_float2(8.f * 0.0356774081f * r1 * r1 * r1, 2.f * 0.7978845608f * r1);
                q[1] = make_float2(__uint_as_float(__byte_perm(split2(-a0), 0, sel)), __uint_as_float(__byte_perm(split2(-a1), 0, sel)));
            }
            if (kb == 6) {
#pragma unroll
                for (int i = 0; i < 5; i++) stg128(&g_x1f[(tile * 8 + j) * 640 + i * 128 + wt], res[4 * i], res[4 * i + 1], res[4 * i + 2], res[4 * i + 3]);
            }
            if (kb == 8) asm volatile("fence.proxy.async.global;" ::: "memory");
            TR(leader, 10 * uw + kb)
        }
        const uint64_t fd = ((uint64_t)8 << 32) | ((dsb + OFF_W + 6 * 16384) >> 4);
        wg_fence();
        wgmma_rs128k(acc0, __float_as_uint(q[1].x), __float_as_uint(q[1].y), 0, 0, fd, 1);
        wgmma_rs88k(acc1, __float_as_uint(q[1].x), __float_as_uint(q[1].y), 0, 0, fd + 128, 1);
        wg_commit();
        if (lane == 0) {
            mbar_arrive(bars + B_XFREE * 8);
            asm volatile("mbarrier.arrive.shared::cluster.b64 _, [%0];" ::"r"(peer_addr(bars + B_XFREE * 8)) : "memory");
        }
    }
    const uint32_t recv = sb + recv_off(uw) + wt * 16;
    uint32_t ha[48] = {}, hb[48], hx[12];
    uint64_t wb = dz + (((dsb + OFF_W) >> 4) | (512u << 16));
    auto wdesc = [&](int n) { return wb + (n & 7) * 1024; };
    auto wwait = [&](int n) { mbar_spin(wfull + (n & 7) * 8, (n >> 3) & 1); };
    auto wfree = [&](int n) { if (lane == 0) mbar_arrive(wempty + (n & 7) * 8); };
    auto fresh = [&]() { wb += pp.nil; asm volatile("" : "+l"(wb)); };
    uint32_t pk[32];
    {
        float P0[64];
        const float2 r0 = q[2], r1 = q[3];
        const uint32_t ra = peer_addr(recv), rb = peer_addr(bars + (B_RECV + 4 * uw) * 8);
        auto conv32 = [&](const float* v, int b) {
#pragma unroll
            for (int i = 0; i < 4; i++) {
                ha[8 * b + 2 * i] = pack2(gelu2r(v[4 * i], r0), gelu2r(v[4 * i + 1], r0));
                ha[8 * b + 2 * i + 1] = pack2(gelu2r(v[4 * i + 2], r1), gelu2r(v[4 * i + 3], r1));
            }
#pragma unroll
            for (int s = 2 * b; s < 2 * b + 2; s++) st_peer(ra + s * 2048, ha[4 * s], ha[4 * s + 1], ha[4 * s + 2], ha[4 * s + 3], rb + (b >> 1) * 8);
        };
        auto fetch = [&](int k) {
            mbar_spin(bars + (B_RECV + 4 * uw + k) * 8, 0);
#pragma unroll
            for (int s = 4 * k; s < 4 * k + 4; s++) { const uint4 x = lds128(recv + s * 2048); hb[4 * s] = x.x; hb[4 * s + 1] = x.y; hb[4 * s + 2] = x.z; hb[4 * s + 3] = x.w; }
        };
        auto stage = [&](int n, const uint32_t* a, int steps, int sc) {
            wwait(n);
            wg_fence();
#pragma unroll
            for (int s = 0; s < steps; s++) wgmma_rs128(P0, a[4 * s], a[4 * s + 1], a[4 * s + 2], a[4 * s + 3], wdesc(n) + s * 128, sc || s);
            wg_commit();
        };
        wg_wait<0>();
        reg_fence(acc0); reg_fence(acc1);
        wfree(29); wfree(30);
        TS(leader, 44 + uw)
        if (uw) bar_sync(13, 256);
        uint32_t hr[6];
#pragma unroll
        for (int i = 0; i < 6; i++) {
            const float2 r = (i & 1) ? r1 : r0;
            hr[i] = pack2(gelu2r(acc1[32 + 2 * i], r), gelu2r(acc1[33 + 2 * i], r));
        }
        if (uw) mbar_spin(bars + B_XFREE * 8, 0);
        st_peer(ra + 24576, hr[0], hr[1], hr[2], hr[3], rb + 24);
        asm volatile("st.async.shared::cluster.mbarrier::complete_tx::bytes.v2.b32 [%0], {%1, %2}, [%3];" ::"r"(ra + 26624 - wt * 8), "r"(hr[4]), "r"(hr[5]), "r"(rb + 24) : "memory");
        conv32(&acc1[0], 4);
        conv32(&acc1[16], 5);
        TS(leader, 46 + uw)
        stage(31, &ha[32], 4, 0);
#pragma unroll
        for (int b = 0; b < 4; b++) {
            conv32(&acc0[16 * b], b);
            if (b == 0 && !uw) asm volatile("bar.arrive 13, 256;" ::: "memory");
            if (b == 3) {
                fetch(2);
                mbar_spin(bars + (B_RECV + 4 * uw + 3) * 8, 0);
                const uint4 x = lds128(recv + 24576);
                const uint2 y = lds64(recv + 26624 - wt * 8);
                const uint32_t hp[6] = {x.x, x.y, x.z, x.w, y.x, y.y};
#pragma unroll
                for (int i = 0; i < 6; i++) { hx[i] = (j & 1) ? hp[i] : hr[i]; hx[6 + i] = (j & 1) ? hr[i] : hp[i]; }
            }
            if (!(b & 1)) wwait(32 + (b >> 1));
            wg_fence();
#pragma unroll
            for (int s = 0; s < 2; s++) wgmma_rs128(P0, ha[8 * b + 4 * s], ha[8 * b + 4 * s + 1], ha[8 * b + 4 * s + 2], ha[8 * b + 4 * s + 3], wdesc(32 + (b >> 1)) + (2 * (b & 1) + s) * 128, 1);
            wg_commit();
            if (!(b & 1)) { wg_wait<1>(); wfree(31 + (b >> 1)); }
        }
        TR(leader, 64 + 10 * uw)
        fresh();
        stage(34, &hb[32], 4, 1); wg_wait<1>(); wfree(33);
        fetch(0);
        stage(35, hx, 3, 1); wg_wait<1>(); wfree(34);
        fetch(1);
        stage(36, &hb[0], 4, 1); wg_wait<1>(); wfree(35);
        stage(37, &hb[16], 4, 1); wg_wait<1>(); wfree(36);
        wg_wait<0>();
        reg_fence(P0);
        pack_part<64>(pk, P0, ep);
        uint32_t all = 0;
#pragma unroll
        for (int i = 0; i < 32; i++) all |= pk[i];
        if (lane == 0) mbar_arrive_after(wempty + (37 & 7) * 8, all, 0, nil);
        TR(leader, 65 + 10 * uw)
    }
    {
        uint4* const dst = g_part + (size_t)(tile * 8 + j) * 5120 + wt;
        const uint4* const src = g_part + (size_t)tile * 40960 + j * 512 + wt;
        float F[2][32];
        uint4 gb[4];
        float rr[2];
        float2 gf[8];
        uint4 base[4], u1[4], u2[4], u3[4];
#pragma unroll
        for (int c = 2; c < 5; c++) {
            float (&P)[32] = F[c & 1];
            fresh();
#pragma unroll
            for (int s = 0; s < 27; s++) {
                const int e = s < 8 ? 0 : s < 15 ? 1 : s < 23 ? 2 : 3, o = s - (e == 0 ? 0 : e == 1 ? 8 : e == 2 ? 15 : 23), n = 30 + 4 * c + e;
                const uint32_t* a = s < 12 ? &ha[4 * s] : s < 15 ? &hx[4 * (s - 12)] : &hb[4 * (s - 15)];
                if (o == 0) wwait(n);
                if (o == 0 || s == 1) wg_fence();
                wgmma_rs64(P, a[0], a[1], a[2], a[3], wdesc(n) + o * 128, s);
                if (o == 0) { wg_commit(); wg_wait<1>(); if (c > 2 || s) wfree(n - 1); }
                if (s == 0 && c > 2) { reg_fence(F[~c & 1]); pack_part<32>(pk, F[~c & 1], ep); }
                if (c == 2 && s % 3 == 0 && s < 24) st_part(dst + g4_block(s / 12, j) * 512 + (s / 3 & 3) * 128, &pk[4 * (s / 3)]);
                if (c == 3 && s % 4 == 1 && s < 16) st_part(dst + g4_block(2, j) * 512 + s / 4 * 128, &pk[4 * (s / 4)]);
                if (c == 4 && s < 4) st_part(dst + g4_block(3, j) * 512 + s * 128, &pk[4 * s]);
                if (c == 4 && s >= 4 && s < 8) base[s - 4] = ldcg128(&g_x1f[(tile * 8 + j) * 640 + (s - 4) * 128 + wt]);
                if (c == 4 && s >= 15 && s < 19) { const int i = s - 15; gf[2 * i] = lds64f(sb + M_GB + (16 * i + 2 * t) * 4); gf[2 * i + 1] = lds64f(sb + M_GB + (16 * i + 8 + 2 * t) * 4); }
                if (c == 4 && s >= 12 && s < 14) rr[s - 12] = __uint_as_float(lds32(sb + M_F1 + (64 * uw + 16 * wq + g + 8 * (s - 12)) * 4));
                if (c == 4 && s >= 8 && s < 12) u1[s - 8] = ld_part(src + (j ^ 6) * 5120 + (s - 8) * 128);
                if (c == 4 && s >= 19 && s < 23) u2[s - 19] = ld_part(src + (j ^ 4) * 5120 + (s - 19) * 128);
                if (c == 4 && s >= 23) u3[s - 23] = ld_part(src + (j ^ 2) * 5120 + (s - 23) * 128);
                if (27 * (c - 2) + s == R_GATE && lane == 0) mbar_arrive(bars + (B_RING + uw) * 8);
                if (s == 7 || s == 14 || s == 22 || s == 26) wg_commit();
                if (c == 4) { TR(leader && s == 7, 68 + 10 * uw) TR(leader && s == 14, 69 + 10 * uw) TR(leader && s == 22, 70 + 10 * uw) }
            }
            TR(leader, 64 + c + (c == 4 ? 3 : 0) + 10 * uw)
        }
        float (&O)[32] = F[0];
#pragma unroll
        for (int i = 0; i < 4; i++) gb[i] = scale16(gf[2 * i], gf[2 * i + 1], rr[0], rr[1]);
        uint32_t it = 0;
        while (__any_sync(~0u, (stale4(u1, ep) | stale4(u2, ep) | stale4(u3, ep)) & 1)) {
            STALE(__any_sync(~0u, stale4(u1, ep) & 1) ? 4 : __any_sync(~0u, stale4(u2, ep) & 1) ? 5 : 6)
            ld_part4(u1, src + (j ^ 6) * 5120, 128); ld_part4(u2, src + (j ^ 4) * 5120, 128); ld_part4(u3, src + (j ^ 2) * 5120, 128);
            SPIN_CHECK(58)
        }
        TR(leader, 73 + 10 * uw)
#pragma unroll
        for (int i = 0; i < 4; i++) u1[i] = add2(add2(u1[i], u2[i]), u3[i]);
        TS(leader, 50 + uw)
        wg_wait<0>();
        reg_fence(O);
        TS(leader, 48 + uw)
        const uint32_t so = sb + recv_off(uw) + wq * 2048;
#pragma unroll
        for (int i = 0; i < 4; i++) {
            const float* o = &O[8 * i];
            const uint4 r = fin16(add2(u1[i], make_uint4(pack2(o[0], o[1]), pack2(o[2], o[3]), pack2(o[4], o[5]), pack2(o[6], o[7]))), base[i], gb[i]);
            stsm4(so + (lane & 15) * 128 + (((2 * i + (lane >> 4)) ^ (lane & 7)) << 4), r.x, r.y, r.z, r.w);
        }
        TR4(leader, 100 + uw)
        __syncwarp();
#pragma unroll
        for (int i = 0; i < 4; i++) {
            const int row = (lane >> 3) + 4 * i;
            stg128(out + (size_t)(row0 + row) * D_ + 64 * j + 8 * (lane & 7), lds128(so + row * 128 + (((lane & 7) ^ (row & 7)) << 4)));
        }
        TS(leader, 24 + uw)
        warp_arrive(bars + B_OWN * 8);
    }
}

typedef CUresult (*EncFn)(CUtensorMap*, CUtensorMapDataType, cuuint32_t, void*, const cuuint64_t*, const cuuint64_t*, const cuuint32_t*,
                          const cuuint32_t*, CUtensorMapInterleave, CUtensorMapSwizzle, CUtensorMapL2promotion, CUtensorMapFloatOOBfill);

static void enc(EncFn fn, CUtensorMap* m, void* p, int rank, const cuuint64_t* dims, const cuuint64_t* strides, const cuuint32_t* box, bool plain = false) {
    const CUtensorMapSwizzle sw = box[0] > 64 || plain ? CU_TENSOR_MAP_SWIZZLE_NONE : CU_TENSOR_MAP_SWIZZLE_128B;
    cuuint32_t es[5] = {1, 1, 1, 1, 1};
    CUresult r = fn(m, CU_TENSOR_MAP_DATA_TYPE_BFLOAT16, rank, p, dims, strides, box, es, CU_TENSOR_MAP_INTERLEAVE_NONE, sw,
                    CU_TENSOR_MAP_L2_PROMOTION_L2_128B, CU_TENSOR_MAP_FLOAT_OOB_FILL_NONE);
    (void)r;
}
static void enc2(EncFn fn, CUtensorMap* m, void* p, uint64_t cols, uint64_t rows, uint32_t bc, uint32_t br, bool plain = false) {
    cuuint64_t dims[2] = {cols, rows}, st[1] = {cols * 2};
    cuuint32_t box[2] = {bc, br};
    enc(fn, m, p, 2, dims, st, box, plain);
}

extern "C" void kernel_launch(void* const* d_in, const int* in_sizes, int n_in, void* d_out, int out_size) {
    static Maps mp;
    static Ptrs pp;
    static void* cached[13];
    bool same = true;
    for (int i = 0; i < 13; i++) same = same && (cached[i] == d_in[i]);
    if (!same) {
        void* fnp = nullptr;
        cudaDriverEntryPointQueryResult qr;
        cudaGetDriverEntryPoint("cuTensorMapEncodeTiled", &fnp, cudaEnableDefault, &qr);
        EncFn fn = (EncFn)fnp;
        cudaGetSymbolAddress((void**)&pp.s, g_scratch);
        void *x1T = g_x1T, *t = g_t;
        cuuint64_t dq[3] = {64, S_, 10}, sq[2] = {D_ * 2, 128};
        cuuint32_t bq[3] = {64, 16, 10};
        enc(fn, &mp.q, d_in[0], 3, dq, sq, bq);
        enc2(fn, &mp.k, d_in[1], D_, S_, 80, 67); enc2(fn, &mp.v, d_in[2], D_, S_, 80, 64);
        enc2(fn, &mp.qT, g_qT, 16 * D_, 128, 80, 128);
        enc2(fn, &mp.x[0], x1T, S_, D_, 64, 64); enc2(fn, &mp.x[1], (bf16*)t + 2 * D_, D_, S_, 64, 64);
        enc2(fn, &mp.x[2], g_x2f, 64, 320 * 64, 64, 64, true);
        enc2(fn, &mp.w1, d_in[7], D_, D_, 64, 64); enc2(fn, &mp.w1h, d_in[7], D_, D_, 64, 160); enc2(fn, &mp.w3h, d_in[9], F_, D_, 64, 160);
        enc2(fn, &mp.wmod, d_in[12], 6 * D_, D_, 64, 160);
        const cuuint64_t R = D_ * 2;
        cuuint64_t da[5] = {D_, 2, 4, 4, 16}, sa[4] = {R, 8 * R, 2 * R, 32 * R}, db[5] = {D_, 2, 2, 4, 8}, sb[4] = {R, 8 * R, 2 * R, 16 * R};
        cuuint32_t ba[5] = {64, 2, 4, 4, 2}, bb[5] = {64, 2, 2, 4, 4};
        enc(fn, &mp.w2a, d_in[8], 5, da, sa, ba); enc(fn, &mp.w2b, (bf16*)d_in[8] + 512 * D_, 5, db, sb, bb);
        cuuint64_t dw[3] = {64, D_, 27}, sw[2] = {F_ * 2, 128};
        cuuint32_t bw[3] = {64, 32, 3};
        enc(fn, &mp.w3a, d_in[9], 3, dw, sw, bw);
        enc2(fn, &mp.w3b, d_in[9], F_, D_, 24, 32);
        enc2(fn, &mp.w4[0], d_in[10], D_, F_, 64, 64); enc2(fn, &mp.w4[1], d_in[10], D_, F_, 64, 48);
        pp.q = (const bf16*)d_in[0]; pp.w_mod = (const bf16*)d_in[12]; pp.shift_k = (const bf16*)d_in[3];
        pp.ssm_k = (const bf16*)d_in[4]; pp.ssm_D = (const bf16*)d_in[5]; pp.w1 = (const bf16*)d_in[7]; pp.w2 = (const bf16*)d_in[8];
        pp.w4 = (const bf16*)d_in[10]; pp.c = (const bf16*)d_in[11];
        cudaFuncSetAttribute(fused_kernel, cudaFuncAttributeMaxDynamicSharedMemorySize, SMEM_BYTES);
        for (int i = 0; i < 13; i++) cached[i] = d_in[i];
    }
    fused_kernel<<<NCTA, NTHR, SMEM_BYTES, cudaStreamPerThread>>>(pp, (bf16*)d_out, mp);
}
```

```cpp
#include <cuda_runtime.h>
#include <cuda_bf16.h>
#include <cuda.h>
#include <stdint.h>
#include <stdio.h>

typedef __nv_bfloat16 bf16;

constexpr int S_ = 2048, D_ = 640, F_ = 1728;
constexpr int NCTA = 132, NTHR = 512;

constexpr int TAB_BYTES = 9216, VEC_BYTES = 1440;
struct Counters {
    unsigned kv[8 * 32];
    unsigned q[4 * 32], x[4 * 32];
    unsigned wr[32], tab[32], uv[32], cs[32], cs2[32], done[32];
    unsigned g1[32 * 32];
    unsigned g2[32 * 32];
};
struct Scratch {
    Counters cnt;
    unsigned epoch;
    alignas(1024) bf16 qst[2 * S_];
    alignas(1024) uint4 wr[2 * 8 * 10 * 128];
    alignas(1024) uint2 mod[2 * 6 * D_];
    alignas(1024) uint4 tab[(TAB_BYTES + 8 * VEC_BYTES) / 16];
    alignas(1024) float uv[2 * 3 * D_];
    alignas(1024) float cs3[2 * 1920];
    alignas(1024) uint4 cs3b[8 * 216];
    alignas(1024) float2 stats[32 * 8 * 64];
    alignas(1024) bf16 kvT[D_ * S_];
    alignas(1024) bf16 qT[D_ * S_];
    alignas(1024) bf16 x1T[D_ * S_];
    alignas(1024) bf16 t[(S_ + 4) * D_];
    alignas(1024) uint4 x2f[32 * 40 * 128];
    alignas(1024) uint4 x1f[32 * 8 * 5 * 128];
    alignas(1024) uint4 part[32 * 8 * 10 * 4 * 128];
};
__device__ Scratch g_scratch;
#define g_kvT (pp.s->kvT)
#define g_qT (pp.s->qT)
#define g_x1T (pp.s->x1T)
#define g_qst (pp.s->qst)
#define g_t (pp.s->t)
#define g_x2f (pp.s->x2f)
#define g_x1f (pp.s->x1f)
#define g_part (pp.s->part)
#define g_wr (pp.s->wr)
#define g_mod (pp.s->mod)
#define g_tab (pp.s->tab)
#define g_uv (pp.s->uv)
#define g_cs3 (pp.s->cs3)
#define g_cs3b (pp.s->cs3b)
#define g_stats (pp.s->stats)
#define g_cnt (pp.s->cnt)
#define g_epoch (pp.s->epoch)

struct Maps {
    CUtensorMap k, v, q;
    CUtensorMap qT;
    CUtensorMap x[3];
    CUtensorMap w1, w1h, w3h, wmod;
    CUtensorMap w2a, w2b;
    CUtensorMap w3a, w3b;
    CUtensorMap w4[2];
};

struct Ptrs {
    Scratch* s;
    uint64_t nil;
    const bf16 *q, *w_mod, *shift_k, *ssm_k, *ssm_D, *w1, *w2, *w4, *c;
};

constexpr int OFF_W = 0;
constexpr int OFF_XR = 131072;
constexpr int OFF_REM = 196608;
constexpr int OFF_TAB = OFF_REM + 5 * 4096;
constexpr int OFF_ROW = OFF_TAB + 4608;
constexpr int OFF_F1 = OFF_ROW + 4096;
constexpr int RECV_BYTES = 30720;
constexpr int OFF_M = OFF_REM + RECV_BYTES;
constexpr int OFF_OUT = OFF_XR + 32768;
static_assert(OFF_F1 + 1280 <= OFF_M, "G1 map");
constexpr int OFF_ST = 0;
constexpr int OFF_SSM = 20480;
constexpr int OFF_WM = 0;
constexpr int OFF_QIN = 49152;
constexpr int OFF_QT = 49152;
constexpr int OFF_Z = OFF_TAB;
constexpr int OFF_RING = 80896;
constexpr int OFF_KIN = OFF_RING, OFF_VIN = OFF_KIN + 2 * 10752;
constexpr int OFF_CH = OFF_RING + 3 * 16384, CH_BYTES = 13312, OFF_P = 5120;
static_assert(OFF_RING + 5 * 16384 <= OFF_CH + 3 * CH_BYTES && OFF_CH + 5 * CH_BYTES <= OFF_REM, "the last two rings replace channels 0..2");
constexpr int M_BAR = OFF_M;
constexpr int M_F1 = OFF_M + 832;
constexpr int M_GB = M_F1 + 1280, M_C = M_GB + 320, M_SB = M_C + 320, M_CI = M_SB + 320;
constexpr int M_KS = M_CI + 320;
constexpr int M_AB = M_KS + 160;
constexpr int M_EP = M_AB + 80;
constexpr int M_SINK = M_EP + 16;
constexpr int M_NUL = M_SINK + 16;
constexpr int M_TS = M_NUL + 128;
constexpr int SMEM_BYTES = M_TS;
static_assert(SMEM_BYTES <= 232448, "smem");

enum { B_WFULL = 0, B_WEMPTY = 8, B_XEMPTY = 16, B_XFULL = 24  ,
       B_RAW = 44, B_QIN = 45, B_SSM = 46, B_VEC = 47, B_VEC3 = 48, B_WM = 49, B_TAB = 50, B_QRDY = 51,
       B_MODR = 52, B_RAW2 = 53, B_RAW3 = 54, B_GATE = 56, B_SUMS = 62, B_RECV = 64  ,
       B_LAND = 72, B_AGAIN = 80, B_RETRY = 84,
       B_XS = 88, B_R1 = 89, B_BK = 90,
       B_XFREE = 92, B_OWN = 93, B_IN = 94,
       B_RING = 96   };
#define T_KVB 1500
#define T_SSM 4200
#define PF_T0 5900
#define PF_N 10
#define PF_DT 420
#define G_ALL 1
#define SKIP_KV 2
#define SKIP_Q 32
#define SKIP_X 64
#define SKIP_G1 20
#define SKIP_G2 16
#define HELP_T 1000
#define R_GATE 34
#define GATE_W2 7
#define GATE_W3 24
#define GATE_W3B 37
#define W3_N2 15
#define LEAD1 5
#define XLEAD 4

#define SPIN_FAIL(code) __trap();
#define SPIN_LIMIT (1u << 22)
#define STALE(c)
#define STALE1(c)
#define TS(c, i)
#define TG(c, i)
#define TR(c, i)
#define TR2(c, i)
#define TR4(c, i)
#define TR5(c, i)
#define SPIN_CHECK(code) asm volatile("" ::"r"(it));
#define RARE(x) __builtin_expect((x) != 0, 0)
__device__ __forceinline__ uint32_t s2u(const void* p) { return (uint32_t)__cvta_generic_to_shared(p); }
__device__ __forceinline__ bool elect() {
    uint32_t p;
    asm volatile("{.reg .pred P; elect.sync _|P, 0xffffffff; selp.u32 %0,1,0,P;}" : "=r"(p));
    return p != 0;
}
__device__ __forceinline__ void mbar_init(uint32_t b, uint32_t n) { asm volatile("mbarrier.init.shared.b64 [%0], %1;" ::"r"(b), "r"(n)); }
__device__ __forceinline__ void mbar_expect(uint32_t b, uint32_t bytes) {
    asm volatile("mbarrier.arrive.expect_tx.shared.b64 _, [%0], %1;" ::"r"(b), "r"(bytes) : "memory");
}
__device__ __forceinline__ void mbar_arrive(uint32_t b) { asm volatile("mbarrier.arrive.shared.b64 _, [%0];" ::"r"(b) : "memory"); }
__device__ __forceinline__ void mbar_arrive_after(uint32_t b, uint32_t v0, uint32_t v1, uint32_t nil) { mbar_arrive(b + ((v0 | v1) & nil)); }
__device__ __forceinline__ void warp_arrive(uint32_t b) { __syncwarp(); if (elect()) mbar_arrive(b); }
__device__ __forceinline__ uint32_t peer_addr(uint32_t a) {
    uint32_t r;
    asm("{\n.reg .b32 q;\nmov.u32 q, %%cluster_ctarank;\nxor.b32 q, q, 1;\nmapa.shared::cluster.u32 %0, %1, q;\n}" : "=r"(r) : "r"(a));
    return r;
}
__device__ __forceinline__ bool mbar_test(uint32_t b, uint32_t parity) {
    uint32_t ok;
    asm volatile("{.reg .pred P; mbarrier.test_wait.parity.shared.b64 P, [%1], %2; selp.u32 %0,1,0,P;}" : "=r"(ok) : "r"(b), "r"(parity) : "memory");
    return ok != 0;
}
__device__ __forceinline__ bool mbar_try(uint32_t b, uint32_t parity) {
    uint32_t ok;
    asm volatile("{.reg .pred P; mbarrier.try_wait.parity.shared.b64 P, [%1], %2; selp.u32 %0,1,0,P;}" : "=r"(ok) : "r"(b), "r"(parity) : "memory");
    return ok != 0;
}
__device__ __forceinline__ void mbar_wait(uint32_t b, uint32_t parity) {
    if (__all_sync(0xffffffffu, mbar_try(b, parity))) return;
    uint32_t it = 0;
    while (!__all_sync(0xffffffffu, mbar_try(b, parity))) { if (++it > SPIN_LIMIT) SPIN_FAIL((b >> 3) & 63) }
}
__device__ __forceinline__ void mbar_spin(uint32_t b, uint32_t parity) {
    asm volatile("{\n.reg .pred P;\nSPIN:\nmbarrier.try_wait.parity.shared.b64 P, [%0], %1;\n@!P bra.uni SPIN;\n}" ::"r"(b), "r"(parity) : "memory");
}
__device__ __forceinline__ void bar_sync(int id, int n) { asm volatile("bar.sync %0, %1;" ::"r"(id), "r"(n) : "memory"); }
__device__ __forceinline__ void fence_async_smem() { asm volatile("fence.proxy.async.shared::cta;" ::: "memory"); }
__device__ __forceinline__ void wait_cnt(const unsigned* p, unsigned target, bool tagged = false) {
    unsigned v, it = 0;
    do {
        asm volatile("ld.relaxed.gpu.global.u32 %0, [%1];" : "=r"(v) : "l"(p) : "memory");
        SPIN_CHECK(60 + (target & 3))
    } while (!__all_sync(0xffffffffu, (int)(v - target) >= 0));
    if (!tagged) asm volatile("fence.acquire.gpu;" ::: "memory");
}
__device__ __forceinline__ void signal_cnt(unsigned* p, int lane, int n, bool tagged = false) {
    if (tagged) asm volatile("{\n.reg .pred P;\nsetp.lt.s32 P, %1, %2;\n@P red.relaxed.gpu.global.add.u32 [%0], %3;\n}" ::"l"(p), "r"(lane), "r"(n), "r"(1) : "memory");
    else if (lane < n) asm volatile("red.release.gpu.global.add.u32 [%0], 1;" ::"l"(p) : "memory");
    __syncwarp();
}
__device__ __forceinline__ uint32_t clock_lo() { uint32_t c; asm volatile("mov.u32 %0, %%clock;" : "=r"(c)); return c; }
__device__ __forceinline__ void wait_clock(uint32_t c0, uint32_t t) {
    asm volatile("{\n.reg .pred P;\n.reg .b32 c;\nWAIT:\nnanosleep.u32 20;\nmov.u32 c, %%clock;\nsub.u32 c, c, %0;\nsetp.lt.u32 P, c, %1;\n@P bra.uni WAIT;\n}" ::"r"(c0), "r"(t) : "memory");
}
__device__ __forceinline__ void tma_ld2(uint32_t dst, const CUtensorMap* m, int c0, int c1, uint32_t bar) {
    asm volatile("cp.async.bulk.tensor.2d.shared::cluster.global.mbarrier::complete_tx::bytes [%0], [%1, {%3, %4}], [%2];"
                 ::"r"(dst), "l"(m), "r"(bar), "r"(c0), "r"(c1) : "memory");
}
__device__ __forceinline__ void tma_ld3(uint32_t dst, const CUtensorMap* m, int c0, int c1, int c2, uint32_t bar) {
    asm volatile("cp.async.bulk.tensor.3d.shared::cluster.global.mbarrier::complete_tx::bytes [%0], [%1, {%3, %4, %5}], [%2];"
                 ::"r"(dst), "l"(m), "r"(bar), "r"(c0), "r"(c1), "r"(c2) : "memory");
}
__device__ __forceinline__ void tma_ld5(uint32_t dst, const CUtensorMap* m, int col, int blk, uint32_t bar) {
    asm volatile("cp.async.bulk.tensor.5d.shared::cluster.global.mbarrier::complete_tx::bytes [%0], [%1, {%3, %4, %4, %4, %5}], [%2];"
                 ::"r"(dst), "l"(m), "r"(bar), "r"(col), "r"(0), "r"(blk) : "memory");
}
__device__ __forceinline__ void bulk_ld(uint32_t dst, const void* src, uint32_t bytes, uint32_t bar) {
    asm volatile("cp.async.bulk.shared::cluster.global.mbarrier::complete_tx::bytes [%0], [%1], %2, [%3];" ::"r"(dst), "l"(src), "r"(bytes), "r"(bar) : "memory");
}
__device__ __forceinline__ void l2_prefetch(const void* p, uint32_t bytes) {
    asm volatile("cp.async.bulk.prefetch.L2.global [%0], %1;" ::"l"(p), "r"(bytes) : "memory");
}
__device__ __forceinline__ void wg_fence() { asm volatile("wgmma.fence.sync.aligned;" ::: "memory"); }
__device__ __forceinline__ void wg_commit() { asm volatile("wgmma.commit_group.sync.aligned;" ::: "memory"); }
template <int N> __device__ __forceinline__ void wg_wait() { asm volatile("wgmma.wait_group.sync.aligned %0;" ::"n"(N) : "memory"); }
template <int N> __device__ __forceinline__ void reg_fence(float (&d)[N]) {
#pragma unroll
    for (int i = 0; i < N; i++) asm volatile("" : "+f"(d[i])::"memory");
}
template <int N> __device__ __forceinline__ void zero(float (&d)[N]) {
#pragma unroll
    for (int i = 0; i < N; i++) asm volatile("mov.b32 %0, 0;" : "=f"(d[i]));
}
__device__ __forceinline__ uint32_t lds32(uint32_t a) { uint32_t v; asm volatile("ld.shared.b32 %0, [%1];" : "=r"(v) : "r"(a)); return v; }
__device__ __forceinline__ uint2 lds64(uint32_t a) { uint2 v; asm volatile("ld.shared.v2.b32 {%0,%1}, [%2];" : "=r"(v.x), "=r"(v.y) : "r"(a)); return v; }
__device__ __forceinline__ float2 lds64f(uint32_t a) { float2 v; asm volatile("ld.shared.v2.f32 {%0,%1}, [%2];" : "=f"(v.x), "=f"(v.y) : "r"(a)); return v; }
__device__ __forceinline__ void sts32(uint32_t a, uint32_t v) { asm volatile("st.shared.b32 [%0], %1;" ::"r"(a), "r"(v) : "memory"); }
__device__ __forceinline__ void sts64f(uint32_t a, float x, float y) { asm volatile("st.shared.v2.f32 [%0], {%1,%2};" ::"r"(a), "f"(x), "f"(y) : "memory"); }
__device__ __forceinline__ void sts128(uint32_t a, uint32_t x, uint32_t y, uint32_t z, uint32_t w) {
    asm volatile("st.shared.v4.b32 [%0], {%1,%2,%3,%4};" ::"r"(a), "r"(x), "r"(y), "r"(z), "r"(w) : "memory");
}
__device__ __forceinline__ void sts128f(uint32_t a, float x, float y, float z, float w) {
    asm volatile("st.shared.v4.f32 [%0], {%1,%2,%3,%4};" ::"r"(a), "f"(x), "f"(y), "f"(z), "f"(w) : "memory");
}
__device__ __forceinline__ uint4 lds128(uint32_t a) {
    uint4 v;
    asm volatile("ld.shared.v4.b32 {%0,%1,%2,%3}, [%4];" : "=r"(v.x), "=r"(v.y), "=r"(v.z), "=r"(v.w) : "r"(a) : "memory");
    return v;
}
__device__ __forceinline__ void lds128_if(int p, uint4& v, uint32_t a) {
    asm volatile("{\n.reg .pred p;\nsetp.ne.s32 p, %5, 0;\n@p ld.shared.v4.b32 {%0,%1,%2,%3}, [%4];\n}" : "+r"(v.x), "+r"(v.y), "+r"(v.z), "+r"(v.w) : "r"(a), "r"(p) : "memory");
}
__device__ __forceinline__ float4 lds128f(uint32_t a) {
    float4 v;
    asm volatile("ld.shared.v4.f32 {%0,%1,%2,%3}, [%4];" : "=f"(v.x), "=f"(v.y), "=f"(v.z), "=f"(v.w) : "r"(a) : "memory");
    return v;
}
__device__ __forceinline__ void stg128(void* p, uint32_t x, uint32_t y, uint32_t z, uint32_t w) {
    asm volatile("st.global.v4.b32 [%0], {%1,%2,%3,%4};" ::"l"(p), "r"(x), "r"(y), "r"(z), "r"(w) : "memory");
}
__device__ __forceinline__ void stg128(void* p, uint4 v) { stg128(p, v.x, v.y, v.z, v.w); }
__device__ __forceinline__ void stg64(void* p, uint32_t x, uint32_t y) { asm volatile("st.global.v2.b32 [%0], {%1,%2};" ::"l"(p), "r"(x), "r"(y) : "memory"); }
__device__ __forceinline__ void stsm4(uint32_t a, uint32_t r0, uint32_t r1, uint32_t r2, uint32_t r3) {
    asm volatile("stmatrix.sync.aligned.m8n8.x4.shared.b16 [%0], {%1,%2,%3,%4};" ::"r"(a), "r"(r0), "r"(r1), "r"(r2), "r"(r3) : "memory");
}
__device__ __forceinline__ void stsm4t(uint32_t a, uint32_t r0, uint32_t r1, uint32_t r2, uint32_t r3) {
    asm volatile("stmatrix.sync.aligned.m8n8.x4.trans.shared.b16 [%0], {%1,%2,%3,%4};" ::"r"(a), "r"(r0), "r"(r1), "r"(r2), "r"(r3) : "memory");
}
__device__ __forceinline__ void ldsm4t_if(bool p, uint32_t a, uint32_t* r) {
    asm volatile("{\n.reg .pred p;\nsetp.ne.u32 p, %5, 0;\n@p ldmatrix.sync.aligned.m8n8.x4.trans.shared.b16 {%0,%1,%2,%3}, [%4];\n}"
                 : "+r"(r[0]), "+r"(r[1]), "+r"(r[2]), "+r"(r[3]) : "r"(a), "r"((uint32_t)p) : "memory");
}
__device__ __forceinline__ void ldsm4t(uint32_t a, uint32_t& r0, uint32_t& r1, uint32_t& r2, uint32_t& r3) {
    asm volatile("ldmatrix.sync.aligned.m8n8.x4.trans.shared.b16 {%0,%1,%2,%3}, [%4];" : "=r"(r0), "=r"(r1), "=r"(r2), "=r"(r3) : "r"(a) : "memory");
}
__device__ __forceinline__ uint32_t pack2(float lo, float hi) {
    uint32_t r;
    asm("cvt.rn.bf16x2.f32 %0, %1, %2;" : "=r"(r) : "f"(hi), "f"(lo));
    return r;
}
__device__ __forceinline__ uint32_t mul2(uint32_t a, uint32_t b) { uint32_t r; asm("mul.rn.bf16x2 %0, %1, %2;" : "=r"(r) : "r"(a), "r"(b)); return r; }
__device__ __forceinline__ uint32_t fma2(uint32_t a, uint32_t b, uint32_t c) { uint32_t r; asm("fma.rn.bf16x2 %0, %1, %2, %3;" : "=r"(r) : "r"(a), "r"(b), "r"(c)); return r; }
__device__ __forceinline__ uint32_t add2(uint32_t a, uint32_t b) { uint32_t r; asm("add.rn.bf16x2 %0, %1, %2;" : "=r"(r) : "r"(a), "r"(b)); return r; }
__device__ __forceinline__ float blo(uint32_t w) { return __uint_as_float(w << 16); }
__device__ __forceinline__ float bhi(uint32_t w) { return __uint_as_float(w & 0xffff0000u); }
__device__ __forceinline__ float rbf(float x) { return __bfloat162float(__float2bfloat16_rn(x)); }
__device__ __forceinline__ uint32_t ldg32(const void* p) { uint32_t v; asm volatile("ld.global.nc.b32 %0, [%1];" : "=r"(v) : "l"(p)); return v; }
__device__ __forceinline__ uint4 ldg128(const void* p) {
    uint4 v;
    asm volatile("ld.global.nc.v4.b32 {%0,%1,%2,%3}, [%4];" : "=r"(v.x), "=r"(v.y), "=r"(v.z), "=r"(v.w) : "l"(p));
    return v;
}
__device__ __forceinline__ uint4 ldcg128(const void* p) {
    uint4 v;
    asm volatile("ld.global.cg.v4.u32 {%0,%1,%2,%3}, [%4];" : "=r"(v.x), "=r"(v.y), "=r"(v.z), "=r"(v.w) : "l"(p) : "memory");
    return v;
}
__device__ __forceinline__ float ldcg32f(const void* p) { float v; asm volatile("ld.global.cg.f32 %0, [%1];" : "=f"(v) : "l"(p) : "memory"); return v; }
__device__ __forceinline__ float2 ld_stat(const float2* p) {
    float2 v;
    asm volatile("{\n.reg .b64 q;\nld.relaxed.gpu.global.b64 q, [%2];\nmov.b64 {%0, %1}, q;\n}" : "=f"(v.x), "=f"(v.y) : "l"(p) : "memory");
    return v;
}
__device__ __forceinline__ uint32_t ld_cold(const unsigned* p) { uint32_t v; asm volatile("ld.relaxed.gpu.global.u32 %0, [%1];" : "=r"(v) : "l"(p) : "memory"); return v; }
__device__ __forceinline__ uint2 ld_mod(const uint2* p) {
    uint64_t v;
    asm volatile("ld.relaxed.gpu.global.b64 %0, [%1];" : "=l"(v) : "l"(p) : "memory");
    return make_uint2((uint32_t)v, (uint32_t)(v >> 32));
}
__device__ __forceinline__ float silu(float x) {
    float e, r;
    asm("ex2.approx.ftz.f32 %0, %1;" : "=f"(e) : "f"(x * -1.4426950408889634f));
    asm("rcp.approx.ftz.f32 %0, %1;" : "=f"(r) : "f"(1.f + e));
    return x * r;
}
__device__ __forceinline__ float gelu2(float h) {
    float u = h * fmaf(h * h, 8.f * 0.0356774081f, 2.f * 0.7978845608f);
    float th;
    asm("tanh.approx.f32 %0, %1;" : "=f"(th) : "f"(u));
    return fmaf(h, th, h);
}
__device__ __forceinline__ float gelu2r(float a, float2 k) {
    float th;
    asm("tanh.approx.f32 %0, %1;" : "=f"(th) : "f"(a * fmaf(a * a, k.x, k.y)));
    return fmaf(a, th, a);
}

__device__ __forceinline__ void conv_channel(float (&d)[64], uint32_t pa, uint64_t db) {
    asm volatile("{\n.reg .b32 a0, a1, a2, a3, b0, b1, b2, b3, t0, t1;\n.reg .b64 d;\nld.shared.b32 a0, [%64];\nld.shared.b32 a1, [%64+128];\nld.shared.b32 a2, [%64+-128];\nmov.b32 a3, a0;\n"
        "ld.shared.b32 t0, [%64+256];\nld.shared.b32 t1, [%64+384];\nadd.s64 d, %65, 0;\nwgmma.fence.sync.aligned;\nwgmma.mma_async.sync.aligned.m64n128k16.f32.bf16.bf16 {%0, %1, %2, %3, %4, %5, %6, %7, %8, %9, %10, %11, %12, %13, %14, %15, %16, %17, %18, %19, %20, %21, %22, %23, %24, %25, %26, %27, %28, %29, %30, %31, %32, %33, %34, %35, %36, %37, %38, %39, %40, %41, %42, %43, %44, %45, %46, %47, %48, %49, %50, %51, %52, %53, %54, %55, %56, %57, %58, %59, %60, %61, %62, %63}, {a0, a1, a2, a3}, d, 0, 1, 1, 0;\nwgmma.commit_group.sync.aligned;\nwgmma.wait_group.sync.aligned 1;\nmov.b32 b2, a1;\nmov.b32 b0, t0;\nmov.b32 b3, t0;\nmov.b32 b1, t1;\n"
        "ld.shared.b32 t0, [%64+512];\nld.shared.b32 t1, [%64+640];\nadd.s64 d, %65, 8;\nwgmma.fence.sync.aligned;\nwgmma.mma_async.sync.aligned.m64n128k16.f32.bf16.bf16 {%0, %1, %2, %3, %4, %5, %6, %7, %8, %9, %10, %11, %12, %13, %14, %15, %16, %17, %18, %19, %20, %21, %22, %23, %24, %25, %26, %27, %28, %29, %30, %31, %32, %33, %34, %35, %36, %37, %38, %39, %40, %41, %42, %43, %44, %45, %46, %47, %48, %49, %50, %51, %52, %53, %54, %55, %56, %57, %58, %59, %60, %61, %62, %63}, {b0, b1, b2, b3}, d, 1, 1, 1, 0;\nwgmma.commit_group.sync.aligned;\nwgmma.wait_group.sync.aligned 1;\nmov.b32 a2, b1;\nmov.b32 a0, t0;\nmov.b32 a3, t0;\nmov.b32 a1, t1;\n"
        "ld.shared.b32 t0, [%64+768];\nld.shared.b32 t1, [%64+896];\nadd.s64 d, %65, 16;\nwgmma.fence.sync.aligned;\nwgmma.mma_async.sync.aligned.m64n128k16.f32.bf16.bf16 {%0, %1, %2, %3, %4, %5, %6, %7, %8, %9, %10, %11, %12, %13, %14, %15, %16, %17, %18, %19, %20, %21, %22, %23, %24, %25, %26, %27, %28, %29, %30, %31, %32, %33, %34, %35, %36, %37, %38, %39, %40, %41, %42, %43, %44, %45, %46, %47, %48, %49, %50, %51, %52, %53, %54, %55, %56, %57, %58, %59, %60, %61, %62, %63}, {a0, a1, a2, a3}, d, 1, 1, 1, 0;\nwgmma.commit_group.sync.aligned;\nwgmma.wait_group.sync.aligned 1;\nmov.b32 b2, a1;\nmov.b32 b0, t0;\nmov.b32 b3, t0;\nmov.b32 b1, t1;\n"
        "ld.shared.b32 t0, [%64+1024];\nld.shared.b32 t1, [%64+1152];\nadd.s64 d, %65, 24;\nwgmma.fence.sync.aligned;\nwgmma.mma_async.sync.aligned.m64n128k16.f32.bf16.bf16 {%0, %1, %2, %3, %4, %5, %6, %7, %8, %9, %10, %11, %12, %13, %14, %15, %16, %17, %18, %19, %20, %21, %22, %23, %24, %25, %26, %27, %28, %29, %30, %31, %32, %33, %34, %35, %36, %37, %38, %39, %40, %41, %42, %43, %44, %45, %46, %47, %48, %49, %50, %51, %52, %53, %54, %55, %56, %57, %58, %59, %60, %61, %62, %63}, {b0, b1, b2, b3}, d, 1, 1, 1, 0;\nwgmma.commit_group.sync.aligned;\nwgmma.wait_group.sync.aligned 1;\nmov.b32 a2, b1;\nmov.b32 a0, t0;\nmov.b32 a3, t0;\nmov.b32 a1, t1;\n"
        "ld.shared.b32 t0, [%64+1280];\nld.shared.b32 t1, [%64+1408];\nadd.s64 d, %65, 32;\nwgmma.fence.sync.aligned;\nwgmma.mma_async.sync.aligned.m64n128k16.f32.bf16.bf16 {%0, %1, %2, %3, %4, %5, %6, %7, %8, %9, %10, %11, %12, %13, %14, %15, %16, %17, %18, %19, %20, %21, %22, %23, %24, %25, %26, %27, %28, %29, %30, %31, %32, %33, %34, %35, %36, %37, %38, %39, %40, %41, %42, %43, %44, %45, %46, %47, %48, %49, %50, %51, %52, %53, %54, %55, %56, %57, %58, %59, %60, %61, %62, %63}, {a0, a1, a2, a3}, d, 1, 1, 1, 0;\nwgmma.commit_group.sync.aligned;\nwgmma.wait_group.sync.aligned 1;\nmov.b32 b2, a1;\nmov.b32 b0, t0;\nmov.b32 b3, t0;\nmov.b32 b1, t1;\n"
        "ld.shared.b32 t0, [%64+1536];\nld.shared.b32 t1, [%64+1664];\nadd.s64 d, %65, 40;\nwgmma.fence.sync.aligned;\nwgmma.mma_async.sync.aligned.m64n128k16.f32.bf16.bf16 {%0, %1, %2, %3, %4, %5, %6, %7, %8, %9, %10, %11, %12, %13, %14, %15, %16, %17, %18, %19, %20, %21, %22, %23, %24, %25, %26, %27, %28, %29, %30, %31, %32, %33, %34, %35, %36, %37, %38, %39, %40, %41, %42, %43, %44, %45, %46, %47, %48, %49, %50, %51, %52, %53, %54, %55, %56, %57, %58, %59, %60, %61, %62, %63}, {b0, b1, b2, b3}, d, 1, 1, 1, 0;\nwgmma.commit_group.sync.aligned;\nwgmma.wait_group.sync.aligned 1;\nmov.b32 a2, b1;\nmov.b32 a0, t0;\nmov.b32 a3, t0;\nmov.b32 a1, t1;\n"
        "ld.shared.b32 t0, [%64+1792];\nld.shared.b32 t1, [%64+1920];\nadd.s64 d, %65, 48;\nwgmma.fence.sync.aligned;\nwgmma.mma_async.sync.aligned.m64n128k16.f32.bf16.bf16 {%0, %1, %2, %3, %4, %5, %6, %7, %8, %9, %10, %11, %12, %13, %14, %15, %16, %17, %18, %19, %20, %21, %22, %23, %24, %25, %26, %27, %28, %29, %30, %31, %32, %33, %34, %35, %36, %37, %38, %39, %40, %41, %42, %43, %44, %45, %46, %47, %48, %49, %50, %51, %52, %53, %54, %55, %56, %57, %58, %59, %60, %61, %62, %63}, {a0, a1, a2, a3}, d, 1, 1, 1, 0;\nwgmma.commit_group.sync.aligned;\nwgmma.wait_group.sync.aligned 1;\nmov.b32 b2, a1;\nmov.b32 b0, t0;\nmov.b32 b3, t0;\nmov.b32 b1, t1;\n"
        "ld.shared.b32 t0, [%64+2048];\nld.shared.b32 t1, [%64+2176];\nadd.s64 d, %65, 56;\nwgmma.fence.sync.aligned;\nwgmma.mma_async.sync.aligned.m64n128k16.f32.bf16.bf16 {%0, %1, %2, %3, %4, %5, %6, %7, %8, %9, %10, %11, %12, %13, %14, %15, %16, %17, %18, %19, %20, %21, %22, %23, %24, %25, %26, %27, %28, %29, %30, %31, %32, %33, %34, %35, %36, %37, %38, %39, %40, %41, %42, %43, %44, %45, %46, %47, %48, %49, %50, %51, %52, %53, %54, %55, %56, %57, %58, %59, %60, %61, %62, %63}, {b0, b1, b2, b3}, d, 1, 1, 1, 0;\nwgmma.commit_group.sync.aligned;\nwgmma.wait_group.sync.aligned 1;\nmov.b32 a2, b1;\nmov.b32 a0, t0;\nmov.b32 a3, t0;\nmov.b32 a1, t1;\n"
        "ld.shared.b32 t0, [%64+2304];\nld.shared.b32 t1, [%64+2432];\nadd.s64 d, %65, 64;\nwgmma.fence.sync.aligned;\nwgmma.mma_async.sync.aligned.m64n96k16.f32.bf16.bf16 {%0, %1, %2, %3, %4, %5, %6, %7, %8, %9, %10, %11, %12, %13, %14, %15, %16, %17, %18, %19, %20, %21, %22, %23, %24, %25, %26, %27, %28, %29, %30, %31, %32, %33, %34, %35, %36, %37, %38, %39, %40, %41, %42, %43, %44, %45, %46, %47}, {a0, a1, a2, a3}, d, 1, 1, 1, 0;\nwgmma.commit_group.sync.aligned;\nwgmma.wait_group.sync.aligned 1;\nmov.b32 b2, a1;\nmov.b32 b0, t0;\nmov.b32 b3, t0;\nmov.b32 b1, t1;\n"
        "ld.shared.b32 t0, [%64+2560];\nld.shared.b32 t1, [%64+2688];\nadd.s64 d, %65, 72;\nwgmma.fence.sync.aligned;\nwgmma.mma_async.sync.aligned.m64n96k16.f32.bf16.bf16 {%0, %1, %2, %3, %4, %5, %6, %7, %8, %9, %10, %11, %12, %13, %14, %15, %16, %17, %18, %19, %20, %21, %22, %23, %24, %25, %26, %27, %28, %29, %30, %31, %32, %33, %34, %35, %36, %37, %38, %39, %40, %41, %42, %43, %44, %45, %46, %47}, {b0, b1, b2, b3}, d, 1, 1, 1, 0;\nwgmma.commit_group.sync.aligned;\nwgmma.wait_group.sync.aligned 1;\nmov.b32 a2, b1;\nmov.b32 a0, t0;\nmov.b32 a3, t0;\nmov.b32 a1, t1;\n"
        "ld.shared.b32 t0, [%64+2816];\nld.shared.b32 t1, [%64+2944];\nadd.s64 d, %65, 80;\nwgmma.fence.sync.aligned;\nwgmma.mma_async.sync.aligned.m64n88k16.f32.bf16.bf16 {%0, %1, %2, %3, %4, %5, %6, %7, %8, %9, %10, %11, %12, %13, %14, %15, %16, %17, %18, %19, %20, %21, %22, %23, %24, %25, %26, %27, %28, %29, %30, %31, %32, %33, %34, %35, %36, %37, %38, %39, %40, %41, %42, %43}, {a0, a1, a2, a3}, d, 1, 1, 1, 0;\nwgmma.commit_group.sync.aligned;\nwgmma.wait_group.sync.aligned 1;\nmov.b32 b2, a1;\nmov.b32 b0, t0;\nmov.b32 b3, t0;\nmov.b32 b1, t1;\n"
        "ld.shared.b32 t0, [%64+3072];\nld.shared.b32 t1, [%64+3200];\nadd.s64 d, %65, 88;\nwgmma.fence.sync.aligned;\nwgmma.mma_async.sync.aligned.m64n88k16.f32.bf16.bf16 {%0, %1, %2, %3, %4, %5, %6, %7, %8, %9, %10, %11, %12, %13, %14, %15, %16, %17, %18, %19, %20, %21, %22, %23, %24, %25, %26, %27, %28, %29, %30, %31, %32, %33, %34, %35, %36, %37, %38, %39, %40, %41, %42, %43}, {b0, b1, b2, b3}, d, 1, 1, 1, 0;\nwgmma.commit_group.sync.aligned;\nwgmma.wait_group.sync.aligned 1;\nmov.b32 a2, b1;\nmov.b32 a0, t0;\nmov.b32 a3, t0;\nmov.b32 a1, t1;\n"
        "ld.shared.b32 t0, [%64+3328];\nld.shared.b32 t1, [%64+3456];\nadd.s64 d, %65, 96;\nwgmma.fence.sync.aligned;\nwgmma.mma_async.sync.aligned.m64n80k16.f32.bf16.bf16 {%0, %1, %2, %3, %4, %5, %6, %7, %8, %9, %10, %11, %12, %13, %14, %15, %16, %17, %18, %19, %20, %21, %22, %23, %24, %25, %26, %27, %28, %29, %30, %31, %32, %33, %34, %35, %36, %37, %38, %39}, {a0, a1, a2, a3}, d, 1, 1, 1, 0;\nwgmma.commit_group.sync.aligned;\nwgmma.wait_group.sync.aligned 1;\nmov.b32 b2, a1;\nmov.b32 b0, t0;\nmov.b32 b3, t0;\nmov.b32 b1, t1;\n"
        "ld.shared.b32 t0, [%64+3584];\nld.shared.b32 t1, [%64+3712];\nadd.s64 d, %65, 104;\nwgmma.fence.sync.aligned;\nwgmma.mma_async.sync.aligned.m64n80k16.f32.bf16.bf16 {%0, %1, %2, %3, %4, %5, %6, %7, %8, %9, %10, %11, %12, %13, %14, %15, %16, %17, %18, %19, %20, %21, %22, %23, %24, %25, %26, %27, %28, %29, %30, %31, %32, %33, %34, %35, %36, %37, %38, %39}, {b0, b1, b2, b3}, d, 1, 1, 1, 0;\nwgmma.commit_group.sync.aligned;\nwgmma.wait_group.sync.aligned 1;\nmov.b32 a2, b1;\nmov.b32 a0, t0;\nmov.b32 a3, t0;\nmov.b32 a1, t1;\n"
        "ld.shared.b32 t0, [%64+3840];\nld.shared.b32 t1, [%64+3968];\nadd.s64 d, %65, 112;\nwgmma.fence.sync.aligned;\nwgmma.mma_async.sync.aligned.m64n72k16.f32.bf16.bf16 {%0, %1, %2, %3, %4, %5, %6, %7, %8, %9, %10, %11, %12, %13, %14, %15, %16, %17, %18, %19, %20, %21, %22, %23, %24, %25, %26, %27, %28, %29, %30, %31, %32, %33, %34, %35}, {a0, a1, a2, a3}, d, 1, 1, 1, 0;\nwgmma.commit_group.sync.aligned;\nwgmma.wait_group.sync.aligned 1;\nmov.b32 b2, a1;\nmov.b32 b0, t0;\nmov.b32 b3, t0;\nmov.b32 b1, t1;\n"
        "ld.shared.b32 t0, [%64+4096];\nld.shared.b32 t1, [%64+4224];\nadd.s64 d, %65, 120;\nwgmma.fence.sync.aligned;\nwgmma.mma_async.sync.aligned.m64n72k16.f32.bf16.bf16 {%0, %1, %2, %3, %4, %5, %6, %7, %8, %9, %10, %11, %12, %13, %14, %15, %16, %17, %18, %19, %20, %21, %22, %23, %24, %25, %26, %27, %28, %29, %30, %31, %32, %33, %34, %35}, {b0, b1, b2, b3}, d, 1, 1, 1, 0;\nwgmma.commit_group.sync.aligned;\nwgmma.wait_group.sync.aligned 1;\nmov.b32 a2, b1;\nmov.b32 a0, t0;\nmov.b32 a3, t0;\nmov.b32 a1, t1;\n"
        "ld.shared.b32 t0, [%64+4352];\nld.shared.b32 t1, [%64+4480];\nadd.s64 d, %65, 128;\nwgmma.fence.sync.aligned;\nwgmma.mma_async.sync.aligned.m64n64k16.f32.bf16.bf16 {%0, %1, %2, %3, %4, %5, %6, %7, %8, %9, %10, %11, %12, %13, %14, %15, %16, %17, %18, %19, %20, %21, %22, %23, %24, %25, %26, %27, %28, %29, %30, %31}, {a0, a1, a2, a3}, d, 1, 1, 1, 0;\nwgmma.commit_group.sync.aligned;\nwgmma.wait_group.sync.aligned 1;\nmov.b32 b2, a1;\nmov.b32 b0, t0;\nmov.b32 b3, t0;\nmov.b32 b1, t1;\n"
        "ld.shared.b32 t0, [%64+4608];\nld.shared.b32 t1, [%64+4736];\nadd.s64 d, %65, 136;\nwgmma.fence.sync.aligned;\nwgmma.mma_async.sync.aligned.m64n64k16.f32.bf16.bf16 {%0, %1, %2, %3, %4, %5, %6, %7, %8, %9, %10, %11, %12, %13, %14, %15, %16, %17, %18, %19, %20, %21, %22, %23, %24, %25, %26, %27, %28, %29, %30, %31}, {b0, b1, b2, b3}, d, 1, 1, 1, 0;\nwgmma.commit_group.sync.aligned;\nwgmma.wait_group.sync.aligned 1;\nmov.b32 a2, b1;\nmov.b32 a0, t0;\nmov.b32 a3, t0;\nmov.b32 a1, t1;\n"
        "ld.shared.b32 t0, [%64+4864];\nld.shared.b32 t1, [%64+4992];\nadd.s64 d, %65, 144;\nwgmma.fence.sync.aligned;\nwgmma.mma_async.sync.aligned.m64n56k16.f32.bf16.bf16 {%0, %1, %2, %3, %4, %5, %6, %7, %8, %9, %10, %11, %12, %13, %14, %15, %16, %17, %18, %19, %20, %21, %22, %23, %24, %25, %26, %27}, {a0, a1, a2, a3}, d, 1, 1, 1, 0;\nwgmma.commit_group.sync.aligned;\nwgmma.wait_group.sync.aligned 1;\nmov.b32 b2, a1;\nmov.b32 b0, t0;\nmov.b32 b3, t0;\nmov.b32 b1, t1;\n"
        "ld.shared.b32 t0, [%64+5120];\nld.shared.b32 t1, [%64+5248];\nadd.s64 d, %65, 152;\nwgmma.fence.sync.aligned;\nwgmma.mma_async.sync.aligned.m64n56k16.f32.bf16.bf16 {%0, %1, %2, %3, %4, %5, %6, %7, %8, %9, %10, %11, %12, %13, %14, %15, %16, %17, %18, %19, %20, %21, %22, %23, %24, %25, %26, %27}, {b0, b1, b2, b3}, d, 1, 1, 1, 0;\nwgmma.commit_group.sync.aligned;\nwgmma.wait_group.sync.aligned 1;\nmov.b32 a2, b1;\nmov.b32 a0, t0;\nmov.b32 a3, t0;\nmov.b32 a1, t1;\n"
        "ld.shared.b32 t0, [%64+5376];\nld.shared.b32 t1, [%64+5504];\nadd.s64 d, %65, 160;\nwgmma.fence.sync.aligned;\nwgmma.mma_async.sync.aligned.m64n48k16.f32.bf16.bf16 {%0, %1, %2, %3, %4, %5, %6, %7, %8, %9, %10, %11, %12, %13, %14, %15, %16, %17, %18, %19, %20, %21, %22, %23}, {a0, a1, a2, a3}, d, 1, 1, 1, 0;\nwgmma.commit_group.sync.aligned;\nwgmma.wait_group.sync.aligned 1;\nmov.b32 b2, a1;\nmov.b32 b0, t0;\nmov.b32 b3, t0;\nmov.b32 b1, t1;\n"
        "ld.shared.b32 t0, [%64+5632];\nld.shared.b32 t1, [%64+5760];\nadd.s64 d, %65, 168;\nwgmma.fence.sync.aligned;\nwgmma.mma_async.sync.aligned.m64n48k16.f32.bf16.bf16 {%0, %1, %2, %3, %4, %5, %6, %7, %8, %9, %10, %11, %12, %13, %14, %15, %16, %17, %18, %19, %20, %21, %22, %23}, {b0, b1, b2, b3}, d, 1, 1, 1, 0;\nwgmma.commit_group.sync.aligned;\nwgmma.wait_group.sync.aligned 1;\nmov.b32 a2, b1;\nmov.b32 a0, t0;\nmov.b32 a3, t0;\nmov.b32 a1, t1;\n"
        "ld.shared.b32 t0, [%64+5888];\nld.shared.b32 t1, [%64+6016];\nadd.s64 d, %65, 176;\nwgmma.fence.sync.aligned;\nwgmma.mma_async.sync.aligned.m64n40k16.f32.bf16.bf16 {%0, %1, %2, %3, %4, %5, %6, %7, %8, %9, %10, %11, %12, %13, %14, %15, %16, %17, %18, %19}, {a0, a1, a2, a3}, d, 1, 1, 1, 0;\nwgmma.commit_group.sync.aligned;\nwgmma.wait_group.sync.aligned 1;\nmov.b32 b2, a1;\nmov.b32 b0, t0;\nmov.b32 b3, t0;\nmov.b32 b1, t1;\n"
        "ld.shared.b32 t0, [%64+6144];\nld.shared.b32 t1, [%64+6272];\nadd.s64 d, %65, 184;\nwgmma.fence.sync.aligned;\nwgmma.mma_async.sync.aligned.m64n40k16.f32.bf16.bf16 {%0, %1, %2, %3, %4, %5, %6, %7, %8, %9, %10, %11, %12, %13, %14, %15, %16, %17, %18, %19}, {b0, b1, b2, b3}, d, 1, 1, 1, 0;\nwgmma.commit_group.sync.aligned;\nwgmma.wait_group.sync.aligned 1;\nmov.b32 a2, b1;\nmov.b32 a0, t0;\nmov.b32 a3, t0;\nmov.b32 a1, t1;\n"
        "ld.shared.b32 t0, [%64+6400];\nld.shared.b32 t1, [%64+6528];\nadd.s64 d, %65, 192;\nwgmma.fence.sync.aligned;\nwgmma.mma_async.sync.aligned.m64n32k16.f32.bf16.bf16 {%0, %1, %2, %3, %4, %5, %6, %7, %8, %9, %10, %11, %12, %13, %14, %15}, {a0, a1, a2, a3}, d, 1, 1, 1, 0;\nwgmma.commit_group.sync.aligned;\nwgmma.wait_group.sync.aligned 1;\nmov.b32 b2, a1;\nmov.b32 b0, t0;\nmov.b32 b3, t0;\nmov.b32 b1, t1;\n"
        "ld.shared.b32 t0, [%64+6656];\nld.shared.b32 t1, [%64+6784];\nadd.s64 d, %65, 200;\nwgmma.fence.sync.aligned;\nwgmma.mma_async.sync.aligned.m64n32k16.f32.bf16.bf16 {%0, %1, %2, %3, %4, %5, %6, %7, %8, %9, %10, %11, %12, %13, %14, %15}, {b0, b1, b2, b3}, d, 1, 1, 1, 0;\nwgmma.commit_group.sync.aligned;\nwgmma.wait_group.sync.aligned 1;\nmov.b32 a2, b1;\nmov.b32 a0, t0;\nmov.b32 a3, t0;\nmov.b32 a1, t1;\n"
        "ld.shared.b32 t0, [%64+6912];\nld.shared.b32 t1, [%64+7040];\nadd.s64 d, %65, 208;\nwgmma.fence.sync.aligned;\nwgmma.mma_async.sync.aligned.m64n24k16.f32.bf16.bf16 {%0, %1, %2, %3, %4, %5, %6, %7, %8, %9, %10, %11}, {a0, a1, a2, a3}, d, 1, 1, 1, 0;\nwgmma.commit_group.sync.aligned;\nwgmma.wait_group.sync.aligned 1;\nmov.b32 b2, a1;\nmov.b32 b0, t0;\nmov.b32 b3, t0;\nmov.b32 b1, t1;\n"
        "ld.shared.b32 t0, [%64+7168];\nld.shared.b32 t1, [%64+7296];\nadd.s64 d, %65, 216;\nwgmma.fence.sync.aligned;\nwgmma.mma_async.sync.aligned.m64n24k16.f32.bf16.bf16 {%0, %1, %2, %3, %4, %5, %6, %7, %8, %9, %10, %11}, {b0, b1, b2, b3}, d, 1, 1, 1, 0;\nwgmma.commit_group.sync.aligned;\nwgmma.wait_group.sync.aligned 1;\nmov.b32 a2, b1;\nmov.b32 a0, t0;\nmov.b32 a3, t0;\nmov.b32 a1, t1;\n"
        "ld.shared.b32 t0, [%64+7424];\nld.shared.b32 t1, [%64+7552];\nadd.s64 d, %65, 224;\nwgmma.fence.sync.aligned;\nwgmma.mma_async.sync.aligned.m64n16k16.f32.bf16.bf16 {%0, %1, %2, %3, %4, %5, %6, %7}, {a0, a1, a2, a3}, d, 1, 1, 1, 0;\nwgmma.commit_group.sync.aligned;\nwgmma.wait_group.sync.aligned 1;\nmov.b32 b2, a1;\nmov.b32 b0, t0;\nmov.b32 b3, t0;\nmov.b32 b1, t1;\n"
        "ld.shared.b32 t0, [%64+7680];\nld.shared.b32 t1, [%64+7808];\nadd.s64 d, %65, 232;\nwgmma.fence.sync.aligned;\nwgmma.mma_async.sync.aligned.m64n16k16.f32.bf16.bf16 {%0, %1, %2, %3, %4, %5, %6, %7}, {b0, b1, b2, b3}, d, 1, 1, 1, 0;\nwgmma.commit_group.sync.aligned;\nwgmma.wait_group.sync.aligned 1;\nmov.b32 a2, b1;\nmov.b32 a0, t0;\nmov.b32 a3, t0;\nmov.b32 a1, t1;\n"
        "ld.shared.b32 t0, [%64+7936];\nld.shared.b32 t1, [%64+8064];\nadd.s64 d, %65, 240;\nwgmma.fence.sync.aligned;\nwgmma.mma_async.sync.aligned.m64n8k16.f32.bf16.bf16 {%0, %1, %2, %3}, {a0, a1, a2, a3}, d, 1, 1, 1, 0;\nwgmma.commit_group.sync.aligned;\nwgmma.wait_group.sync.aligned 1;\nmov.b32 b2, a1;\nmov.b32 b0, t0;\nmov.b32 b3, t0;\nmov.b32 b1, t1;\n"
        "add.s64 d, %65, 248;\nwgmma.fence.sync.aligned;\nwgmma.mma_async.sync.aligned.m64n8k16.f32.bf16.bf16 {%0, %1, %2, %3}, {b0, b1, b2, b3}, d, 1, 1, 1, 0;\nwgmma.commit_group.sync.aligned;\nwgmma.wait_group.sync.aligned 0;\n"
        "}" : "+f"(d[0]), "+f"(d[1]), "+f"(d[2]), "+f"(d[3]), "+f"(d[4]), "+f"(d[5]), "+f"(d[6]), "+f"(d[7]), "+f"(d[8]), "+f"(d[9]), "+f"(d[10]), "+f"(d[11]), "+f"(d[12]), "+f"(d[13]), "+f"(d[14]), "+f"(d[15]), "+f"(d[16]), "+f"(d[17]), "+f"(d[18]), "+f"(d[19]), "+f"(d[20]), "+f"(d[21]), "+f"(d[22]), "+f"(d[23]), "+f"(d[24]), "+f"(d[25]), "+f"(d[26]), "+f"(d[27]), "+f"(d[28]), "+f"(d[29]), "+f"(d[30]), "+f"(d[31]), "+f"(d[32]), "+f"(d[33]), "+f"(d[34]), "+f"(d[35]), "+f"(d[36]), "+f"(d[37]), "+f"(d[38]), "+f"(d[39]), "+f"(d[40]), "+f"(d[41]), "+f"(d[42]), "+f"(d[43]), "+f"(d[44]), "+f"(d[45]), "+f"(d[46]), "+f"(d[47]), "+f"(d[48]), "+f"(d[49]), "+f"(d[50]), "+f"(d[51]), "+f"(d[52]), "+f"(d[53]), "+f"(d[54]), "+f"(d[55]), "+f"(d[56]), "+f"(d[57]), "+f"(d[58]), "+f"(d[59]), "+f"(d[60]), "+f"(d[61]), "+f"(d[62]), "+f"(d[63]) : "r"(pa), "l"(db) : "memory");
}
__device__ __forceinline__ void wgmma_rs80(float (&d)[40], uint32_t a0, uint32_t a1, uint32_t a2, uint32_t a3, uint64_t db, int sc) {
    asm volatile("{\n.reg .pred p;\nsetp.ne.b32 p, %45, 0;\n"
        "wgmma.mma_async.sync.aligned.m64n80k16.f32.bf16.bf16 {%0, %1, %2, %3, %4, %5, %6, %7, %8, %9, %10, %11, %12, %13, %14, %15, %16, %17, %18, %19, %20, %21, %22, %23, %24, %25, %26, %27, %28, %29, %30, %31, %32, %33, %34, %35, %36, %37, %38, %39}, {%40, %41, %42, %43}, %44, p, 1, 1, 1;\n}\n"
        : "+f"(d[0]), "+f"(d[1]), "+f"(d[2]), "+f"(d[3]), "+f"(d[4]), "+f"(d[5]), "+f"(d[6]), "+f"(d[7]), "+f"(d[8]), "+f"(d[9]), "+f"(d[10]), "+f"(d[11]), "+f"(d[12]), "+f"(d[13]), "+f"(d[14]), "+f"(d[15]), "+f"(d[16]), "+f"(d[17]), "+f"(d[18]), "+f"(d[19]), "+f"(d[20]), "+f"(d[21]), "+f"(d[22]), "+f"(d[23]), "+f"(d[24]), "+f"(d[25]), "+f"(d[26]), "+f"(d[27]), "+f"(d[28]), "+f"(d[29]), "+f"(d[30]), "+f"(d[31]), "+f"(d[32]), "+f"(d[33]), "+f"(d[34]), "+f"(d[35]), "+f"(d[36]), "+f"(d[37]), "+f"(d[38]), "+f"(d[39]) : "r"(a0), "r"(a1), "r"(a2), "r"(a3), "l"(db), "r"(sc));
}
__device__ __forceinline__ void wgmma_ss80(float (&d)[40], uint64_t da, uint64_t db, int sc) {
    asm volatile("{\n.reg .pred p;\nsetp.ne.b32 p, %42, 0;\n"
        "wgmma.mma_async.sync.aligned.m64n80k16.f32.bf16.bf16 {%0, %1, %2, %3, %4, %5, %6, %7, %8, %9, %10, %11, %12, %13, %14, %15, %16, %17, %18, %19, %20, %21, %22, %23, %24, %25, %26, %27, %28, %29, %30, %31, %32, %33, %34, %35, %36, %37, %38, %39}, %40, %41, p, 1, 1, 0, 1;\n}\n"
        : "+f"(d[0]), "+f"(d[1]), "+f"(d[2]), "+f"(d[3]), "+f"(d[4]), "+f"(d[5]), "+f"(d[6]), "+f"(d[7]), "+f"(d[8]), "+f"(d[9]), "+f"(d[10]), "+f"(d[11]), "+f"(d[12]), "+f"(d[13]), "+f"(d[14]), "+f"(d[15]), "+f"(d[16]), "+f"(d[17]), "+f"(d[18]), "+f"(d[19]), "+f"(d[20]), "+f"(d[21]), "+f"(d[22]), "+f"(d[23]), "+f"(d[24]), "+f"(d[25]), "+f"(d[26]), "+f"(d[27]), "+f"(d[28]), "+f"(d[29]), "+f"(d[30]), "+f"(d[31]), "+f"(d[32]), "+f"(d[33]), "+f"(d[34]), "+f"(d[35]), "+f"(d[36]), "+f"(d[37]), "+f"(d[38]), "+f"(d[39]) : "l"(da), "l"(db), "r"(sc));
}
__device__ __forceinline__ void wgmma_ss80t(float (&d)[40], uint64_t da, uint64_t db, int sc) {
    asm volatile("{\n.reg .pred p;\nsetp.ne.b32 p, %42, 0;\n"
        "wgmma.mma_async.sync.aligned.m64n80k16.f32.bf16.bf16 {%0, %1, %2, %3, %4, %5, %6, %7, %8, %9, %10, %11, %12, %13, %14, %15, %16, %17, %18, %19, %20, %21, %22, %23, %24, %25, %26, %27, %28, %29, %30, %31, %32, %33, %34, %35, %36, %37, %38, %39}, %40, %41, p, 1, 1, 1, 1;\n}\n"
        : "+f"(d[0]), "+f"(d[1]), "+f"(d[2]), "+f"(d[3]), "+f"(d[4]), "+f"(d[5]), "+f"(d[6]), "+f"(d[7]), "+f"(d[8]), "+f"(d[9]), "+f"(d[10]), "+f"(d[11]), "+f"(d[12]), "+f"(d[13]), "+f"(d[14]), "+f"(d[15]), "+f"(d[16]), "+f"(d[17]), "+f"(d[18]), "+f"(d[19]), "+f"(d[20]), "+f"(d[21]), "+f"(d[22]), "+f"(d[23]), "+f"(d[24]), "+f"(d[25]), "+f"(d[26]), "+f"(d[27]), "+f"(d[28]), "+f"(d[29]), "+f"(d[30]), "+f"(d[31]), "+f"(d[32]), "+f"(d[33]), "+f"(d[34]), "+f"(d[35]), "+f"(d[36]), "+f"(d[37]), "+f"(d[38]), "+f"(d[39]) : "l"(da), "l"(db), "r"(sc));
}
__device__ __forceinline__ void wgmma_ss8_ta(float (&d)[4], uint64_t da, uint64_t db, int sc) {
    asm volatile("{\n.reg .pred p;\nsetp.ne.b32 p, %6, 0;\n"
        "wgmma.mma_async.sync.aligned.m64n8k16.f32.bf16.bf16 {%0, %1, %2, %3}, %4, %5, p, 1, 1, 1, 0;\n}\n"
        : "+f"(d[0]), "+f"(d[1]), "+f"(d[2]), "+f"(d[3]) : "l"(da), "l"(db), "r"(sc));
}
__device__ __forceinline__ void wgmma_rs8(float (&d)[4], uint32_t a0, uint32_t a1, uint32_t a2, uint32_t a3, uint64_t db, int sc) {
    asm volatile("{\n.reg .pred p;\nsetp.ne.b32 p, %9, 0;\n"
        "wgmma.mma_async.sync.aligned.m64n8k16.f32.bf16.bf16 {%0, %1, %2, %3}, {%4, %5, %6, %7}, %8, p, 1, 1, 0;\n}\n"
        : "+f"(d[0]), "+f"(d[1]), "+f"(d[2]), "+f"(d[3]) : "r"(a0), "r"(a1), "r"(a2), "r"(a3), "l"(db), "r"(sc));
}
__device__ __forceinline__ void wgmma_rs128(float (&d)[64], uint32_t a0, uint32_t a1, uint32_t a2, uint32_t a3, uint64_t db, int sc) {
    asm volatile("{\n.reg .pred p;\nsetp.ne.b32 p, %69, 0;\n"
        "wgmma.mma_async.sync.aligned.m64n128k16.f32.bf16.bf16 {%0, %1, %2, %3, %4, %5, %6, %7, %8, %9, %10, %11, %12, %13, %14, %15, %16, %17, %18, %19, %20, %21, %22, %23, %24, %25, %26, %27, %28, %29, %30, %31, %32, %33, %34, %35, %36, %37, %38, %39, %40, %41, %42, %43, %44, %45, %46, %47, %48, %49, %50, %51, %52, %53, %54, %55, %56, %57, %58, %59, %60, %61, %62, %63}, {%64, %65, %66, %67}, %68, p, 1, 1, 1;\n}\n"
        : "+f"(d[0]), "+f"(d[1]), "+f"(d[2]), "+f"(d[3]), "+f"(d[4]), "+f"(d[5]), "+f"(d[6]), "+f"(d[7]), "+f"(d[8]), "+f"(d[9]), "+f"(d[10]), "+f"(d[11]), "+f"(d[12]), "+f"(d[13]), "+f"(d[14]), "+f"(d[15]), "+f"(d[16]), "+f"(d[17]), "+f"(d[18]), "+f"(d[19]), "+f"(d[20]), "+f"(d[21]), "+f"(d[22]), "+f"(d[23]), "+f"(d[24]), "+f"(d[25]), "+f"(d[26]), "+f"(d[27]), "+f"(d[28]), "+f"(d[29]), "+f"(d[30]), "+f"(d[31]), "+f"(d[32]), "+f"(d[33]), "+f"(d[34]), "+f"(d[35]), "+f"(d[36]), "+f"(d[37]), "+f"(d[38]), "+f"(d[39]), "+f"(d[40]), "+f"(d[41]), "+f"(d[42]), "+f"(d[43]), "+f"(d[44]), "+f"(d[45]), "+f"(d[46]), "+f"(d[47]), "+f"(d[48]), "+f"(d[49]), "+f"(d[50]), "+f"(d[51]), "+f"(d[52]), "+f"(d[53]), "+f"(d[54]), "+f"(d[55]), "+f"(d[56]), "+f"(d[57]), "+f"(d[58]), "+f"(d[59]), "+f"(d[60]), "+f"(d[61]), "+f"(d[62]), "+f"(d[63]) : "r"(a0), "r"(a1), "r"(a2), "r"(a3), "l"(db), "r"(sc));
}
__device__ __forceinline__ void wgmma_rs88(float (&d)[44], uint32_t a0, uint32_t a1, uint32_t a2, uint32_t a3, uint64_t db, int sc) {
    asm volatile("{\n.reg .pred p;\nsetp.ne.b32 p, %49, 0;\n"
        "wgmma.mma_async.sync.aligned.m64n88k16.f32.bf16.bf16 {%0, %1, %2, %3, %4, %5, %6, %7, %8, %9, %10, %11, %12, %13, %14, %15, %16, %17, %18, %19, %20, %21, %22, %23, %24, %25, %26, %27, %28, %29, %30, %31, %32, %33, %34, %35, %36, %37, %38, %39, %40, %41, %42, %43}, {%44, %45, %46, %47}, %48, p, 1, 1, 1;\n}\n"
        : "+f"(d[0]), "+f"(d[1]), "+f"(d[2]), "+f"(d[3]), "+f"(d[4]), "+f"(d[5]), "+f"(d[6]), "+f"(d[7]), "+f"(d[8]), "+f"(d[9]), "+f"(d[10]), "+f"(d[11]), "+f"(d[12]), "+f"(d[13]), "+f"(d[14]), "+f"(d[15]), "+f"(d[16]), "+f"(d[17]), "+f"(d[18]), "+f"(d[19]), "+f"(d[20]), "+f"(d[21]), "+f"(d[22]), "+f"(d[23]), "+f"(d[24]), "+f"(d[25]), "+f"(d[26]), "+f"(d[27]), "+f"(d[28]), "+f"(d[29]), "+f"(d[30]), "+f"(d[31]), "+f"(d[32]), "+f"(d[33]), "+f"(d[34]), "+f"(d[35]), "+f"(d[36]), "+f"(d[37]), "+f"(d[38]), "+f"(d[39]), "+f"(d[40]), "+f"(d[41]), "+f"(d[42]), "+f"(d[43]) : "r"(a0), "r"(a1), "r"(a2), "r"(a3), "l"(db), "r"(sc));
}
__device__ __forceinline__ void wgmma_rs128k(float (&d)[64], uint32_t a0, uint32_t a1, uint32_t a2, uint32_t a3, uint64_t db, int sc) {
    asm volatile("{\n.reg .pred p;\nsetp.ne.b32 p, %69, 0;\n"
        "wgmma.mma_async.sync.aligned.m64n128k16.f32.bf16.bf16 {%0, %1, %2, %3, %4, %5, %6, %7, %8, %9, %10, %11, %12, %13, %14, %15, %16, %17, %18, %19, %20, %21, %22, %23, %24, %25, %26, %27, %28, %29, %30, %31, %32, %33, %34, %35, %36, %37, %38, %39, %40, %41, %42, %43, %44, %45, %46, %47, %48, %49, %50, %51, %52, %53, %54, %55, %56, %57, %58, %59, %60, %61, %62, %63}, {%64, %65, %66, %67}, %68, p, 1, 1, 0;\n}\n"
        : "+f"(d[0]), "+f"(d[1]), "+f"(d[2]), "+f"(d[3]), "+f"(d[4]), "+f"(d[5]), "+f"(d[6]), "+f"(d[7]), "+f"(d[8]), "+f"(d[9]), "+f"(d[10]), "+f"(d[11]), "+f"(d[12]), "+f"(d[13]), "+f"(d[14]), "+f"(d[15]), "+f"(d[16]), "+f"(d[17]), "+f"(d[18]), "+f"(d[19]), "+f"(d[20]), "+f"(d[21]), "+f"(d[22]), "+f"(d[23]), "+f"(d[24]), "+f"(d[25]), "+f"(d[26]), "+f"(d[27]), "+f"(d[28]), "+f"(d[29]), "+f"(d[30]), "+f"(d[31]), "+f"(d[32]), "+f"(d[33]), "+f"(d[34]), "+f"(d[35]), "+f"(d[36]), "+f"(d[37]), "+f"(d[38]), "+f"(d[39]), "+f"(d[40]), "+f"(d[41]), "+f"(d[42]), "+f"(d[43]), "+f"(d[44]), "+f"(d[45]), "+f"(d[46]), "+f"(d[47]), "+f"(d[48]), "+f"(d[49]), "+f"(d[50]), "+f"(d[51]), "+f"(d[52]), "+f"(d[53]), "+f"(d[54]), "+f"(d[55]), "+f"(d[56]), "+f"(d[57]), "+f"(d[58]), "+f"(d[59]), "+f"(d[60]), "+f"(d[61]), "+f"(d[62]), "+f"(d[63]) : "r"(a0), "r"(a1), "r"(a2), "r"(a3), "l"(db), "r"(sc));
}
__device__ __forceinline__ void wgmma_rs88k(float (&d)[44], uint32_t a0, uint32_t a1, uint32_t a2, uint32_t a3, uint64_t db, int sc) {
    asm volatile("{\n.reg .pred p;\nsetp.ne.b32 p, %49, 0;\n"
        "wgmma.mma_async.sync.aligned.m64n88k16.f32.bf16.bf16 {%0, %1, %2, %3, %4, %5, %6, %7, %8, %9, %10, %11, %12, %13, %14, %15, %16, %17, %18, %19, %20, %21, %22, %23, %24, %25, %26, %27, %28, %29, %30, %31, %32, %33, %34, %35, %36, %37, %38, %39, %40, %41, %42, %43}, {%44, %45, %46, %47}, %48, p, 1, 1, 0;\n}\n"
        : "+f"(d[0]), "+f"(d[1]), "+f"(d[2]), "+f"(d[3]), "+f"(d[4]), "+f"(d[5]), "+f"(d[6]), "+f"(d[7]), "+f"(d[8]), "+f"(d[9]), "+f"(d[10]), "+f"(d[11]), "+f"(d[12]), "+f"(d[13]), "+f"(d[14]), "+f"(d[15]), "+f"(d[16]), "+f"(d[17]), "+f"(d[18]), "+f"(d[19]), "+f"(d[20]), "+f"(d[21]), "+f"(d[22]), "+f"(d[23]), "+f"(d[24]), "+f"(d[25]), "+f"(d[26]), "+f"(d[27]), "+f"(d[28]), "+f"(d[29]), "+f"(d[30]), "+f"(d[31]), "+f"(d[32]), "+f"(d[33]), "+f"(d[34]), "+f"(d[35]), "+f"(d[36]), "+f"(d[37]), "+f"(d[38]), "+f"(d[39]), "+f"(d[40]), "+f"(d[41]), "+f"(d[42]), "+f"(d[43]) : "r"(a0), "r"(a1), "r"(a2), "r"(a3), "l"(db), "r"(sc));
}
__device__ __forceinline__ void wgmma_rs80k(float (&d)[40], uint32_t a0, uint32_t a1, uint32_t a2, uint32_t a3, uint64_t db, int sc) {
    asm volatile("{\n.reg .pred p;\nsetp.ne.b32 p, %45, 0;\n"
        "wgmma.mma_async.sync.aligned.m64n80k16.f32.bf16.bf16 {%0, %1, %2, %3, %4, %5, %6, %7, %8, %9, %10, %11, %12, %13, %14, %15, %16, %17, %18, %19, %20, %21, %22, %23, %24, %25, %26, %27, %28, %29, %30, %31, %32, %33, %34, %35, %36, %37, %38, %39}, {%40, %41, %42, %43}, %44, p, 1, 1, 0;\n}\n"
        : "+f"(d[0]), "+f"(d[1]), "+f"(d[2]), "+f"(d[3]), "+f"(d[4]), "+f"(d[5]), "+f"(d[6]), "+f"(d[7]), "+f"(d[8]), "+f"(d[9]), "+f"(d[10]), "+f"(d[11]), "+f"(d[12]), "+f"(d[13]), "+f"(d[14]), "+f"(d[15]), "+f"(d[16]), "+f"(d[17]), "+f"(d[18]), "+f"(d[19]), "+f"(d[20]), "+f"(d[21]), "+f"(d[22]), "+f"(d[23]), "+f"(d[24]), "+f"(d[25]), "+f"(d[26]), "+f"(d[27]), "+f"(d[28]), "+f"(d[29]), "+f"(d[30]), "+f"(d[31]), "+f"(d[32]), "+f"(d[33]), "+f"(d[34]), "+f"(d[35]), "+f"(d[36]), "+f"(d[37]), "+f"(d[38]), "+f"(d[39]) : "r"(a0), "r"(a1), "r"(a2), "r"(a3), "l"(db), "r"(sc));
}
__device__ __forceinline__ void wgmma_rs64(float (&d)[32], uint32_t a0, uint32_t a1, uint32_t a2, uint32_t a3, uint64_t db, int sc) {
    asm volatile("{\n.reg .pred p;\nsetp.ne.b32 p, %37, 0;\n"
        "wgmma.mma_async.sync.aligned.m64n64k16.f32.bf16.bf16 {%0, %1, %2, %3, %4, %5, %6, %7, %8, %9, %10, %11, %12, %13, %14, %15, %16, %17, %18, %19, %20, %21, %22, %23, %24, %25, %26, %27, %28, %29, %30, %31}, {%32, %33, %34, %35}, %36, p, 1, 1, 1;\n}\n"
        : "+f"(d[0]), "+f"(d[1]), "+f"(d[2]), "+f"(d[3]), "+f"(d[4]), "+f"(d[5]), "+f"(d[6]), "+f"(d[7]), "+f"(d[8]), "+f"(d[9]), "+f"(d[10]), "+f"(d[11]), "+f"(d[12]), "+f"(d[13]), "+f"(d[14]), "+f"(d[15]), "+f"(d[16]), "+f"(d[17]), "+f"(d[18]), "+f"(d[19]), "+f"(d[20]), "+f"(d[21]), "+f"(d[22]), "+f"(d[23]), "+f"(d[24]), "+f"(d[25]), "+f"(d[26]), "+f"(d[27]), "+f"(d[28]), "+f"(d[29]), "+f"(d[30]), "+f"(d[31]) : "r"(a0), "r"(a1), "r"(a2), "r"(a3), "l"(db), "r"(sc));
}

__device__ __forceinline__ uint64_t mkdesc(uint32_t lo) { return ((uint64_t)0x40000040u << 32) | lo; }
template <int F> __device__ __forceinline__ uint32_t lop3(uint32_t a, uint32_t b, uint32_t c) { uint32_t r; asm("lop3.b32 %0, %1, %2, %3, %4;" : "=r"(r) : "r"(a), "r"(b), "r"(c), "n"(F)); return r; }
__device__ __forceinline__ void stg128_tag(void* p, uint32_t x, uint32_t y, uint32_t z, uint32_t u, uint32_t ep, int w) {
    stg128(p, lop3<0xB8>(x, w == 0, ep), lop3<0xB8>(y, w == 1, ep), lop3<0xB8>(z, w == 2, ep), lop3<0xB8>(u, w == 3, ep));
}
__device__ __forceinline__ uint32_t tag(uint32_t w, uint32_t ep) { asm("lop3.b32 %0, %0, 1, %1, 0xB8;" : "+r"(w) : "r"(ep)); return w; }
template <int N> __device__ __forceinline__ void pack_part(uint32_t (&p)[32], const float (&v)[N], uint32_t ep) {
#pragma unroll
    for (int i = 0; i < N / 2; i++) p[i] = (i & 3) ? pack2(v[2 * i], v[2 * i + 1]) : tag(pack2(v[2 * i], v[2 * i + 1]), ep);
#pragma unroll
    for (int i = 0; i < N / 2; i++) asm volatile("" : "+r"(p[i]));
}
__device__ __forceinline__ void st_part(uint4* p, const uint32_t* v) {
    asm volatile("{\n.reg .b64 l, h;\n.reg .b128 q;\nmov.b64 l, {%1, %2};\nmov.b64 h, {%3, %4};\nmov.b128 q, {l, h};\nst.relaxed.gpu.global.b128 [%0], q;\n}"
                 ::"l"(p), "r"(v[0]), "r"(v[1]), "r"(v[2]), "r"(v[3]) : "memory");
}
__device__ __forceinline__ void st_peer(uint32_t a, uint32_t x, uint32_t y, uint32_t z, uint32_t w, uint32_t bar) {
    asm volatile("st.async.shared::cluster.mbarrier::complete_tx::bytes.v4.b32 [%0], {%1, %2, %3, %4}, [%5];" ::"r"(a), "r"(x), "r"(y), "r"(z), "r"(w), "r"(bar) : "memory");
}
__device__ __forceinline__ int g4_block(int c, int j) { return c ? j ^ (8 - 2 * c) : 8 + (j & 1); }
__device__ __forceinline__ uint32_t recv_off(int w) { return w ? OFF_XR : OFF_REM; }
__device__ __forceinline__ uint4 ld_part(const void* p) {
    uint4 v;
    asm volatile("{\n.reg .b64 l, h;\n.reg .b128 q;\nld.relaxed.gpu.global.b128 q, [%4];\nmov.b128 {l, h}, q;\nmov.b64 {%0, %1}, l;\nmov.b64 {%2, %3}, h;\n}"
                 : "=r"(v.x), "=r"(v.y), "=r"(v.z), "=r"(v.w) : "l"(p) : "memory");
    return v;
}
__device__ __forceinline__ void ld_part4(uint4 (&u)[4], const uint4* p, int st) {
#pragma unroll
    for (int i = 0; i < 4; i++) u[i] = ld_part(p + i * st);
}
__device__ __forceinline__ uint32_t stale4(const uint4 (&u)[4], uint32_t ep) { return lop3<0x7E>(u[0].x, ep, u[1].x) | lop3<0x7E>(u[2].x, ep, u[3].x); }
__device__ __forceinline__ uint4 add2(uint4 a, uint4 b) { return make_uint4(add2(a.x, b.x), add2(a.y, b.y), add2(a.z, b.z), add2(a.w, b.w)); }
__device__ __forceinline__ uint4 fin16(uint4 v, uint4 b, uint4 c) { return make_uint4(fma2(c.x, v.x, b.x), fma2(c.y, v.y, b.y), fma2(c.z, v.z, b.z), fma2(c.w, v.w, b.w)); }
__device__ __forceinline__ uint4 scale16(float2 c, float2 d, float r0, float r1) {
    return make_uint4(pack2(c.x * r0, c.y * r0), pack2(c.x * r1, c.y * r1), pack2(d.x * r0, d.y * r0), pack2(d.x * r1, d.y * r1));
}
__device__ __forceinline__ uint32_t split2(float x) { const float h = rbf(x); return pack2(h, x - h); }
__device__ __forceinline__ uint32_t b80_desc(uint32_t dsb, uint32_t wn, uint32_t rn, uint32_t h) {
    const uint32_t wb = dsb + OFF_W + (wn & 7) * 16384 + h * 8192, rm = dsb + OFF_REM + rn * 4096 + h * 2048;
    return (wb >> 4) | ((rm - wb) << 12);
}
constexpr int64_t B80_STEP = 128 - (126 << 16), B80_HALF = 512 - (384 << 16);
constexpr uint32_t ring_mask(int L) {
    uint32_t m = 0;
    for (int i = L; i < 20; i++) m |= (uint32_t)(i >= 20 - L || !((i - L) & 1)) << i;
    return m;
}
constexpr uint32_t M0 = ring_mask(LEAD1), M1 = ring_mask(10), M2 = ring_mask(XLEAD);
static_assert(LEAD1 >= 5 && XLEAD >= 3 && XLEAD <= 5, "checked orders: a tile is consumed before its successor in the next phase is issued");
__device__ __forceinline__ uint32_t ring_pos(int w, int n, int L) { return w ? (n < 10 - L ? L + 2 * n : 10 + n) : (n < L ? n : 2 * n - L + 1); }
__device__ __forceinline__ int g1_block(int n, int j) { return n < 5 ? 2 * n + (j & 1) : 2 * n - 9 - (j & 1); }

__device__ __forceinline__ int g2_block(int n) { return (0x9874326510ull >> (4 * n)) & 15; }
__device__ __forceinline__ int g3_block(int n, int j) { return n ? n - (n <= j) : j; }
struct Tile { int e, w, kb; uint32_t at; };
__device__ __forceinline__ Tile ring_tile(int n, int grp, int j) {
    const int e = (n >= 20) + (n >= 40), i = n - 20 * e;
    const uint32_t M = e == 0 ? M0 : e == 1 ? M1 : M2;
    const int w = (M >> i) & 1, c = __popc(M & ((1u << i) - 1)), kb = w ? c : i - c, tile = grp + 16 * w;
    return {e, w, kb, 64u * (e == 0 ? tile + (g1_block(kb, j) << 16) : e == 1 ? g2_block(kb) + (tile << 16) : (10 * tile + g3_block(kb, j)) << 16)};
}
__device__ __forceinline__ void load_tile(const Maps& mp, uint32_t dst, int e, uint32_t at, uint32_t bar) {
    mbar_expect(bar, 8192);
    tma_ld2(dst, &mp.x[e], at & 0xffff, at >> 16, bar);
}

template <int OCT>
__device__ __forceinline__ void gemv_tile(float (&d)[4], uint32_t a, uint32_t b, int kb0) {
    uint32_t alo = ((a & 0x3FFFF) >> 4) | 0x10000u, blo_ = ((b & 0x3FFFF) >> 4) | (OCT << 16);
#pragma unroll 1
    for (int s = 0; s < 20; s += 4) {
        const int kb = kb0 + (s >> 2);
        const uint32_t bk = blo_ + (OCT == 7 ? (kb & 1) * 288 + (kb >> 1) * 56 : kb * 64);
        wg_fence();
#pragma unroll
        for (int q = 0; q < 4; q++) wgmma_ss8_ta(d, mkdesc(alo + (s + q) * 128), ((uint64_t)8 << 32) | (bk + q * 2 * OCT), s + q);
        wg_commit();
    }
    wg_wait<0>();
    reg_fence(d);
}

__device__ __forceinline__ void flush_tile(uint32_t st, bf16* dst, int u) {
#pragma unroll
    for (int i = 0; i < 2; i++) {
        const int idx = u + 320 * i, row = idx >> 3, c = idx & 7;
        stg128(dst + (size_t)row * S_ + 8 * c, lds128(st + row * 128 + ((c ^ ((row >> 1) & 7)) << 4)));
    }
}

__device__ __forceinline__ int tid_now() { int t; asm volatile("mov.u32 %0, %%tid.x;" : "=r"(t)); return t; }
__device__ __forceinline__ float zscale(float c) { return c == 0.f ? 0x1p-30f : c; }
__device__ __forceinline__ bool bar_any(int id, bool p) {
    uint32_t r;
    asm volatile("{\n.reg .pred a, b;\nsetp.ne.u32 a, %2, 0;\nbarrier.red.or.pred.aligned b, %1, 128, a;\nselp.u32 %0, 1, 0, b;\n}" : "=r"(r) : "r"(id), "r"((uint32_t)p) : "memory");
    return r != 0;
}

__global__ void __cluster_dims__(2, 1, 1) __launch_bounds__(NTHR, 1) fused_kernel(const __grid_constant__ Ptrs pp, bf16* __restrict__ out, const __grid_constant__ Maps mp) {
    extern __shared__ __align__(1024) uint8_t smem_raw[];
    const uint32_t sb = s2u(smem_raw), bars = sb + M_BAR, dsb = sb & 0x3FFFF;
    const int id = blockIdx.x, warp = __shfl_sync(0xffffffffu, (int)threadIdx.x >> 5, 0), wg = warp >> 2;
    const uint32_t c0 = clock_lo();
#define TIDS const int tid = tid_now(), lane = tid & 31, wt = tid & 127, g = lane >> 2, t = lane & 3; (void)wt; (void)g; (void)t;
    TS(threadIdx.x == 0, 0) TG(threadIdx.x == 0, 62)

    if (id >= 128) {
        TIDS
        if (sb & 1023) __trap();
        const int hs = id - 128;
        constexpr int H_B = 204800;
        static_assert(H_B + TAB_BYTES + 8 * VEC_BYTES <= OFF_M, "helper map");
        if (warp < 10 && elect()) { mbar_init(bars + warp * 8, 1); mbar_init(bars + 80 + warp * 8, 1); asm volatile("fence.mbarrier_init.release.cluster;" ::: "memory"); }
        __syncthreads();
        const uint32_t e0 = ld_cold(&g_epoch);
        wait_clock(c0, HELP_T);
        uint4 wr[10];
#pragma unroll
        for (int u = 0; u < 10; u++) wr[u] = ldg128(((hs >> 1) ? pp.w2 : pp.w1) + (size_t)(320 * (hs & 1) + (tid >> 4) + 32 * u) * D_ + 512 + 8 * (tid & 15));
        {
            const int r = tid >> 4, c = tid & 15;
            uint4* dst[2];
#pragma unroll
            for (int e = 0; e < 2; e++) {
                const int p = !(hs >> 1) ? r : e && (hs & 1) ? (r & ~14) | ((r & 6) << 1) | ((r & 8) >> 2) : (r & ~30) | ((r & 6) << 2) | ((r & 24) >> 2);
                dst[e] = &g_wr[((hs >> 1) * 8 + (c >> 1)) * 10 * 128 + (p & 15) * 8 + ((2 * (p >> 4) + (c & 1)) ^ (p & 7))];
            }
#pragma unroll
            for (int u = 0; u < 10; u++) stg128(reinterpret_cast<uint4*>(reinterpret_cast<uintptr_t>(dst[u >= 6]) ^ (64 * (u & 1))) +
                       ((hs >> 1) ? (0x9873265410ull >> (4 * (5 * (hs & 1) + (u >> 1)))) & 15 : 5 * (hs & 1) + (u >> 1)) * 128, wr[u]);
        }
        __syncthreads();
        if (warp == 0) signal_cnt(&g_cnt.wr[0], lane, 1);
        __syncthreads();
        if (warp < 5 && elect()) {
            const int un = 5 * hs + warp;
            mbar_expect(bars + warp * 8, 40960);
            tma_ld2(sb + warp * 40960, &mp.w1h, 64 * (un >> 1), 320 * (un & 1), bars + warp * 8);
            tma_ld2(sb + warp * 40960 + 20480, &mp.w1h, 64 * (un >> 1), 320 * (un & 1) + 160, bars + warp * 8);
        }
        if (tid < 320) {
            const uint4* gm = reinterpret_cast<const uint4*>(g_mod + 3 * D_) + tid;
            const unsigned epoch = e0 + 1;
            uint4 r[6];
            unsigned it = 0;
            for (;;) {
                uint32_t bad = 0;
#pragma unroll
                for (int i = 0; i < 6; i++) { r[i] = ld_part(gm + (i >> 1) * (D_ / 2) + (i & 1) * 3 * D_); bad |= (r[i].y ^ epoch) | (r[i].w ^ epoch); }
                if (__all_sync(~0u, !bad)) break;
                if (++it > SPIN_LIMIT) SPIN_FAIL(54)
            }
            uint32_t mv[3];
#pragma unroll
            for (int i = 0; i < 3; i++) mv[i] = pack2(__uint_as_float(r[2 * i].x) + __uint_as_float(r[2 * i + 1].x), __uint_as_float(r[2 * i].z) + __uint_as_float(r[2 * i + 1].z));
            const uint32_t sw2 = mv[0], cw = add2(mv[1], 0x3f803f80u), gw = mv[2];
            const float c0 = blo(cw), c1 = bhi(cw), s0 = blo(sw2), s1 = bhi(sw2);
            const float i0 = __frcp_rn(zscale(c0)), i1 = __frcp_rn(zscale(c1));
            const uint32_t ci = pack2(i0, i1), cq = pack2(i0 * i0, i1 * i1);
            const uint32_t a = sb + H_B + ((tid >> 5) & 1) * 4608 + (tid >> 6) * 896 + ((tid >> 2) & 7) * 112 + (tid & 3) * 4;
            sts32(a, ci); sts32(a + 16, pack2(i0 - blo(ci), i1 - bhi(ci)));
            sts32(a + 32, cq); sts32(a + 48, pack2(fmaf(i0, i0, -blo(cq)), fmaf(i1, i1, -bhi(cq))));
            sts32(a + 64, cw); sts32(a + 80, sw2); sts32(a + 96, 0x3f803f80u);
            if ((tid & ~35) == 284) sts32(a + 112, 0);
            const uint32_t v = sb + H_B + TAB_BYTES + (tid < 256 ? (tid >> 5) * VEC_BYTES + (tid & 31) * 8 : ((tid - 256) >> 3) * VEC_BYTES + 256 + (tid & 7) * 8);
            sts64f(v, blo(gw), bhi(gw)); sts64f(v + 320, c0, c1); sts64f(v + 640, s0, s1); sts64f(v + 960, i0, i1);
            float k[5] = {c0 + c1, s0 + s1, fmaf(c0, c0, c1 * c1), fmaf(c0, s0, c1 * s1), fmaf(s0, s0, s1 * s1)};
#pragma unroll 1
            for (int o = 16; o; o >>= 1) {
#pragma unroll
                for (int e = 0; e < 5; e++) k[e] += __shfl_xor_sync(~0u, k[e], o);
            }
            const uint32_t ks = sb + H_B + TAB_BYTES + (lane & 7) * VEC_BYTES + 1280 + (warp >> 1) * 32;
            if ((warp & 1) && lane < 8) { sts128f(ks, k[0], k[1], k[2], k[3]); sts128f(ks + 16, k[4], 0.f, 0.f, 0.f); }
            bar_sync(3, 320);
            if (!(warp & 1) && lane < 8) {
                const float4 o = lds128f(ks);
                sts128f(ks, k[0] + o.x, k[1] + o.y, k[2] + o.z, k[3] + o.w); sts32(ks + 16, __float_as_uint(k[4] + __uint_as_float(lds32(ks + 16))));
            }
            fence_async_smem();
        }
        __syncthreads();
        if (hs == 0 && warp == 15 && elect()) {
            asm volatile("cp.async.bulk.global.shared::cta.bulk_group [%0], [%1], %2;\ncp.async.bulk.commit_group;\ncp.async.bulk.wait_group 0;"
                         ::"l"(g_tab), "r"(sb + H_B), "n"(TAB_BYTES + 8 * VEC_BYTES) : "memory");
            asm volatile("red.release.gpu.global.add.u32 [%0], 1;" ::"l"(&g_cnt.tab[0]) : "memory");
        }
        __syncwarp();
#pragma unroll 1
        for (int i = wg; i < 20; i += 4) {
            const int r = i / 5, b = i - 5 * r, un = 5 * hs + b, u3 = 20 * r + un;
            auto refill = [&](int e, int u, uint32_t fb) {
                mbar_expect(fb, 40960);
                tma_ld2(sb + e * 40960, &mp.w3h, 64 * (u >> 1), 320 * (u & 1), fb);
                tma_ld2(sb + e * 40960 + 20480, &mp.w3h, 64 * (u >> 1), 320 * (u & 1) + 160, fb);
            };
            if (i > 4 && i < 9) {
                bar_sync(1, 512);
                if (warp == 0) {
                    signal_cnt(&g_cnt.uv[0], lane, 1);
                    if (elect()) {
#pragma unroll 1
                        for (int e = 0; e < 5; e++) refill(e, 5 * hs + e, bars + (5 + e) * 8);
                        l2_prefetch(pp.w2 + (size_t)160 * hs * D_, 160 * D_ * 2);
                    }
                    __syncwarp();
                }
            }
            mbar_wait(bars + i * 8, 0);
            float d[4];
            gemv_tile<7>(d, sb + b * 40960, sb + H_B, 5 * (un & 1));
            const int col = 16 * (warp & 3) + g;
            float* dst = r ? g_cs3 + (un & 1) * 1920 + 64 * ((u3 >> 1) - 10) + col : g_uv + (un & 1) * 3 * D_ + 2 * D_ + 64 * (un >> 1) + col;
            if (t == 3) { dst[0] = d[0]; dst[8] = d[2]; }
            if (r == 0 && t == 2) { dst[-2 * D_] = d[0]; dst[8 - 2 * D_] = d[2]; dst[-D_] = d[1]; dst[8 - D_] = d[3]; }
            if (r == 1 || r == 2) {
                bar_sync(4 + wg, 128);
                if (wt == 0) refill(b, u3, bars + (i + 5) * 8);
            }
        }
        __syncthreads();
        if (warp == 0) signal_cnt(&g_cnt.cs[0], lane, 1);
        if (tid == 511) l2_prefetch(pp.w4 + (size_t)432 * hs * D_, 432 * D_ * 2);
        for (uint32_t it = 0; (int)(ld_cold(&g_cnt.cs[0]) - 4 * (e0 + 1)) < 0;) { if (++it > SPIN_LIMIT) SPIN_FAIL(47) }
        asm volatile("fence.acquire.gpu;" ::: "memory");
        if (tid < 432) {
            const int jj = 2 * hs + (tid >= 216), c = tid % 216;
            const float* src = g_cs3 + (c < 192 ? 192 * jj + c : 1344 + 24 * jj + c);
            const uint32_t s = split2(ldcg32f(src) + ldcg32f(src + 1920));
            stg128(&g_cs3b[432 * hs + tid], s, s & 0xffffu, 0, 0);
        }
        __syncthreads();
        if (warp == 0) signal_cnt(&g_cnt.cs2[0], lane, 1);
        if (tid == 0 && hs == 3) {
            uint32_t it = 0;
            while (ld_cold(&g_epoch) == e0) { __nanosleep(256); if (++it > (1u << 20)) SPIN_FAIL(48) }
        }
        return;
    }

    if (elect()) {
        if (warp == 15) {
            mbar_init(bars + B_IN * 8, 1); mbar_init(bars + B_IN * 8 + 8, 1);
            asm volatile("fence.mbarrier_init.release.cluster;" ::: "memory");
            mbar_expect(bars + B_IN * 8, 131 * 160);
            tma_ld2(sb + OFF_KIN, &mp.k, 80 * (id & 7), 64 * (id >> 3) - 3, bars + B_IN * 8);
            tma_ld2(sb + OFF_VIN, &mp.v, 80 * (id & 7), 64 * (id >> 3), bars + B_IN * 8);
        } else if (warp < 13) {
            const uint32_t n = (0x4C11111111881ull >> (4 * warp)) & 15;
#pragma unroll
            for (int i = 0; i < 4; i++) mbar_init(bars + warp * 64 + i * 8, n);
            if (warp == 11) { mbar_init(bars + B_XFREE * 8, 16); mbar_init(bars + B_OWN * 8, 8); }
            else {
#pragma unroll
                for (int i = 4; i < 8; i++) mbar_init(bars + warp * 64 + i * 8, n);
            }
            asm volatile("fence.mbarrier_init.release.cluster;" ::: "memory");
        }
    }
    asm volatile("" ::"l"(pp.s), "l"(pp.c), "l"(out));
    TR4((threadIdx.x & 31) == 0, warp)
    const int pr = id >> 1;
    const int grp = pr < 4 ? 15 : pr < 36 ? (pr - 4) & 7 : 8 + (pr - 36) % 7;
    const int j = 2 * (pr < 4 ? pr : pr < 36 ? (pr - 4) >> 3 : (pr - 36) / 7) + (id & 1);

    if (wg == 3) {
        TIDS
        const int sw = warp - 12;
        uint32_t ep = ld_cold(&g_epoch);
        TR4(lane == 0, 20 + sw)
        __syncthreads();
        TR4(lane == 0, 30 + sw)
        asm volatile("barrier.cluster.arrive.relaxed.aligned;" ::: "memory");
        if (sw == 0) {
#pragma unroll 1
            for (int n = 0; n < PF_N; n++) {
                wait_clock(c0, PF_T0 + PF_DT * n);
                if (elect()) l2_prefetch(n < 4 ? (const char*)pp.q + id * 20480 + n * 5120 : (const char*)pp.w_mod + id * 38400 + (n - 4) * 4800, n < 4 ? 5120 : 4800);
            }
        } else if (sw == 1) {
            wait_clock(c0, T_SSM);
            if (elect()) {
                mbar_expect(bars + B_SSM * 8, 20480);
                bulk_ld(sb + OFF_SSM, pp.ssm_k + (size_t)5 * id * S_, 20480, bars + B_SSM * 8);
            }
            mbar_spin(bars + B_RAW * 8, 0);
            if (elect()) {
                mbar_expect(bars + B_QIN * 8, 20480);
                tma_ld3(sb + OFF_QIN, &mp.q, 0, 16 * id, 0, bars + B_QIN * 8);
            }
        } else if (sw == 2) {
            if (elect()) {
#pragma unroll 1
                for (int i = 2; i < (int)(sizeof(Maps) / sizeof(CUtensorMap)); i++) asm volatile("prefetch.tensormap [%0];" ::"l"(&mp.k + i) : "memory");
#pragma unroll 1
                for (int i = B_SUMS; i < B_LAND; i++) mbar_expect(bars + i * 8, i < B_RECV ? 2048 : (i & 3) < 3 ? 8192 : 3072);
            }
            wait_cnt(&g_cnt.kv[(id >> 4) * 32], 16 * ep + 16 - SKIP_KV, true);
            TS(lane == 0, 4)
            if (elect()) {
                mbar_expect(bars + B_RAW * 8, 12288);
                mbar_expect(bars + B_RAW2 * 8, 8192);
#pragma unroll
                for (int c = 0; c < 5; c++) bulk_ld(sb + OFF_CH + c * CH_BYTES, g_kvT + (size_t)(5 * id + c) * S_, 4096, bars + (c < 3 ? B_RAW : B_RAW2) * 8);
            }
            mbar_spin(bars + B_BK * 8, 0);
            mbar_spin(bars + B_QIN * 8, 0);
            if (id < 120 && elect()) {
                mbar_expect(bars + B_WM * 8, 40960);
                tma_ld2(sb + OFF_WM, &mp.wmod, 64 * pr, 320 * (id & 1), bars + B_WM * 8);
                tma_ld2(sb + OFF_WM + 20480, &mp.wmod, 64 * pr, 320 * (id & 1) + 160, bars + B_WM * 8);
            }
            TS(lane == 0, 57)
        } else {
            wait_clock(c0, T_KVB);
            if (elect()) {
                mbar_expect(bars + (B_IN + 1) * 8, 131 * 160);
                tma_ld2(sb + OFF_KIN + 10752, &mp.k, 80 * (id & 7), 64 * (id >> 3) + 1021, bars + (B_IN + 1) * 8);
                tma_ld2(sb + OFF_VIN + 10240, &mp.v, 80 * (id & 7), 64 * (id >> 3) + 1024, bars + (B_IN + 1) * 8);
            }
            TS(lane == 0, 53)
            if (lane == 0) sts32(sb + M_EP, ep + 1);
            sts32(sb + M_NUL + lane * 4, 0);
#pragma unroll 1
            for (int i = 0; i < 10; i++) sts128(sb + OFF_Z + i * 512 + lane * 16, 0, 0, 0, 0);
            __syncwarp();
#pragma unroll 1
            for (int i = lane; i < 160; i += 32) {
                const uint32_t c = ldg32(pp.c + 320 * (id & 1) + 2 * i);
                sts32(sb + OFF_Z + (i >> 2) * 128 + (i & 3) * 4, pack2(silu(blo(c)), silu(bhi(c))));
            }
            fence_async_smem();
            for (uint32_t ph = 0, again = 1; again; ph ^= 1) {
                mbar_spin(bars + B_RAW2 * 8, ph);
                uint32_t bad = 0;
#pragma unroll
                for (int i = 0; i < 8; i++) bad |= lop3<0x7E>(lds32(sb + OFF_CH + 3 * CH_BYTES + i * 512 + lane * 16), ~ep, lds32(sb + OFF_CH + 4 * CH_BYTES + i * 512 + lane * 16));
                again = __any_sync(~0u, bad & 1);
                if (again && elect()) {
                    mbar_expect(bars + B_RAW2 * 8, 8192);
#pragma unroll
                    for (int c = 3; c < 5; c++) bulk_ld(sb + OFF_CH + c * CH_BYTES, g_kvT + (size_t)(5 * id + c) * S_, 4096, bars + B_RAW2 * 8);
                }
            }
            if (elect()) mbar_arrive(bars + B_RAW3 * 8);
        }
        {
            mbar_spin(bars + B_QIN * 8, 0);
            asm volatile("add.u32 %0, %0, 1;" : "+r"(ep));
            TS(wt == 0, 54)
            const int tk = 8 * ((lane >> 1) & 1) + 2 * (lane >> 3) + (lane & 1), ck = 4 * (sw & 1) + ((lane >> 1) & 2);
            const uint32_t src = sb + OFF_QIN + (sw >> 1) * 2048 + tk * 128;
            bf16* dst = g_qT + (size_t)id * 16 * D_ + (32 * sw + 8 * (t & 2) + g) * 16 + 8 * (t & 1);
#pragma unroll 1
            for (int i = 0; i < 5; i++) {
                uint32_t r[8];
                ldsm4t(src + i * 4096 + ((ck ^ (tk & 7)) << 4), r[0], r[1], r[2], r[3]);
                ldsm4t(src + i * 4096 + (((ck + 1) ^ (tk & 7)) << 4), r[4], r[5], r[6], r[7]);
                stg128(dst + i * 2048, tag(r[0], ep), r[1], r[2], r[3]);
                stg128(dst + i * 2048 + 128, tag(r[4], ep), r[5], r[6], r[7]);
            }
            float s1 = 0.f, s2 = 0.f;
#pragma unroll 2
            for (int i = 0; i < 10; i++) {
                const uint4 w4 = lds128(sb + OFF_QIN + i * 2048 + wt * 16);
                const uint32_t w[4] = {w4.x, w4.y, w4.z, w4.w};
#pragma unroll
                for (int e = 0; e < 4; e++) { const float a = blo(w[e]), b = bhi(w[e]); s1 += a + b; s2 = fmaf(a, a, fmaf(b, b, s2)); }
            }
#pragma unroll
            for (int o = 1; o < 8; o *= 2) { s1 += __shfl_xor_sync(~0u, s1, o); s2 += __shfl_xor_sync(~0u, s2, o); }
            s1 *= 1.f / D_;
            uint32_t rs = pack2(rsqrtf(fmaxf(s2 * (1.f / D_) - s1 * s1, 0.f) + 1e-5f), 0.f);
            if (lane < 8) rs = tag(rs, ep);
            rs = pack2(blo(rs), -s1 * blo(rs));
            const uint32_t sel = lane ? 0x7632 : 0x5410;
            const uint32_t a0 = __shfl_sync(~0u, rs, 0), a1 = __shfl_sync(~0u, rs, 8), a2 = __shfl_sync(~0u, rs, 16), a3 = __shfl_sync(~0u, rs, 24);
            if (lane < 2) stg64(g_qst + lane * S_ + 16 * id + 4 * sw, tag(__byte_perm(a0, a1, sel), ep), __byte_perm(a2, a3, sel));
            TS(wt == 0, 55)
        }
        bar_sync(6, 128);
        if (sw == 3) {
            signal_cnt(&g_cnt.q[(lane & 3) * 32], lane, 4, true);
            TS(lane == 0, 3)
        }
        asm volatile("setmaxnreg.dec.sync.aligned.u32 32;");
        asm volatile("barrier.cluster.wait.aligned;" ::: "memory");
        if (sw == 1) {
            mbar_spin(bars + B_XS * 8, 0);
            signal_cnt(&g_cnt.x[(lane & 3) * 32], lane, 4, true);
            TS(lane == 0, 20)
        }
        if (sw == 2) {
            wait_cnt(&g_cnt.q[(id & 3) * 32], 128 * ep - SKIP_Q, true);
            if (elect()) {
                mbar_expect(bars + B_QRDY * 8, 28672);
                tma_ld2(sb + OFF_QT, &mp.qT, 80 * id, 0, bars + B_QRDY * 8);
                bulk_ld(sb + OFF_QT + 20480, g_qst, 8192, bars + B_QRDY * 8);
            }
            TS(lane == 0, 8)
        }
        if (sw == 1 || sw == 2) {
            mbar_spin(bars + B_XS * 8, 0);
            fence_async_smem();
            int n = sw & 1;
            const uint32_t plan = ring_tile(min(2 * lane + n, 59), grp, j).at;
#pragma unroll 1
            for (int s = 0; s < 7; s++) {
                const int e = (s >= 2) + (s >= 5), end = (0ull + LEAD1 + (20 << 8) + (24 << 16) + (30ull << 24) + (40ull << 32) + ((40ull + XLEAD) << 40) + (60ull << 48)) >> (8 * s) & 255;
                if (s == 1 || s == 4 || s == 6) mbar_spin(bars + (B_GATE + 2 + e) * 8, !e);
                else if (s != 3 || grp == 15) {
                    wait_cnt(s == 0 ? &g_cnt.x[(id & 3) * 32] : s == 5 ? &g_cnt.g2[grp * 32] : &g_cnt.g1[(s == 2 ? min(max(grp - 1 + min(lane, 2), 0), 15) : 16) * 32],
                             e == 0 ? 128 * ep - SKIP_X : (G_ALL ? 32 : 8) * ep - (e == 1 ? SKIP_G1 : SKIP_G2), true);
                    TS(lane == 0 && sw == 2 && s != 3, 26 + 2 * e)
                }
#pragma unroll 1
                for (; n < end; n += 2) {
                    const uint32_t at = __shfl_sync(~0u, plan, n >> 1);
                    mbar_spin(bars + (B_XEMPTY + (n & 7)) * 8, ((n >> 3) & 1) ^ 1);
                    TR2(lane == 0 && n < 40, 20 + n)
                    if (elect()) {
                        if (n == 40 || n == 40 + XLEAD) {
                            mbar_arrive(bars + (B_LAND + (n & 7)) * 8);
                            asm volatile("mbarrier.arrive.shared.b64 _, [%0], 8;" ::"r"(bars + (B_XEMPTY + (n & 7)) * 8) : "memory");
                        } else load_tile(mp, sb + OFF_XR + (n & 7) * 8192, e, at, bars + (B_LAND + (n & 7)) * 8);
                    }
                }
            }
            if (sw == 1) return;
            unsigned old = 0;
            asm volatile("{\n.reg .pred P;\nsetp.eq.s32 P, %2, 0;\n@P atom.relaxed.gpu.global.add.u32 %0, [%1], %3;\n}" : "+r"(old) : "l"(&g_cnt.done[0]), "r"(lane), "r"(1) : "memory");
            signal_cnt(&g_epoch, lane, old == 128 * ep - 1, true);
        } else if (sw == 0) {
            wait_cnt(&g_cnt.wr[0], 4 * ep);
            mbar_spin(bars + B_QRDY * 8, 0);
            mbar_spin(bars + B_MODR * 8, 0);
            const uint32_t wf = bars + B_WFULL * 8, we = bars + B_WEMPTY * 8;
#pragma unroll 1
            for (int n = 0; n < 5; n++) {
                if (n == 3) { mbar_spin(bars + B_XS * 8, 0); fence_async_smem(); }
                TR2(lane == 0, 70 + n)
                if (elect()) {
                    const uint32_t fb = wf + n * 8, dst = sb + OFF_W + n * 16384;
                    mbar_expect(fb, 20480);
#pragma unroll 1
                    for (int h = 0; h < 2; h++) {
                        const int kb = g1_block(2 * n + h, j);
                        tma_ld2(dst + h * 8192, &mp.w1, 64 * j, 64 * kb, fb);
                        bulk_ld(sb + OFF_REM + n * 4096 + h * 2048, &g_wr[(j * 10 + kb) * 128], 2048, fb);
                    }
                }
            }
            mbar_spin(bars + B_GATE * 8, 0);
#pragma unroll 1
            for (int i = -3; i < 5; i++) {
                const int n = i < 0 ? 8 + i : 5 + i;
                const uint32_t fb = wf + (n & 7) * 8;
                if (i >= 0) mbar_spin(we + i * 8, 0);
                TR2(lane == 0 && i >= 0, 70 + n)
                if (elect()) {
                    if (i < 0 || i >= 3) {
                        mbar_expect(fb, 20480);
#pragma unroll 1
                        for (int h = 0; h < 2; h++) tma_ld5(sb + OFF_W + (n & 7) * 16384 + h * 8192, n < 9 ? &mp.w2a : &mp.w2b, 64 * j, n < 9 ? 2 * g2_block(2 * n - 10 + h) : 4 * h, fb);
                    }
                    if (i >= 0) bulk_ld(sb + OFF_REM + i * 4096, &g_wr[((8 + j) * 10 + 2 * i) * 128], 4096, fb);
                }
            }
            mbar_spin(bars + (B_GATE + 1) * 8, 0);
#pragma unroll 1
            for (int n = 10; n < 30; n++) {
                if (n == W3_N2) mbar_spin(bars + (B_GATE + 2) * 8, 0);
                mbar_spin(we + (n & 7) * 8, ((n >> 3) & 1) ^ 1);
                TR2(lane == 0, 70 + n)
                if (elect()) {
                    const uint32_t dst = sb + OFF_W + (n & 7) * 16384, fb = wf + (n & 7) * 8;
                    mbar_expect(fb, 13824);
                    const int row = 64 * g3_block((n - 10) >> 1, j) + 32 * (n & 1);
                    tma_ld3(dst, &mp.w3a, 0, row, 3 * j, fb);
                    tma_ld2(dst + 12288, &mp.w3b, 1536 + 24 * j, row, fb);
                }
            }
            mbar_spin(we + 6 * 8, 0);
            mbar_spin(bars + B_VEC3 * 8, 0);
            if (elect()) { mbar_expect(wf + 6 * 8, 3456); bulk_ld(sb + OFF_W + 6 * 16384, &g_cs3b[216 * j], 3456, wf + 6 * 8); }
#pragma unroll 1
            for (int n = 31; n < 50; n++) {
                const int e = n < 38 ? 4 : (n - 38) & 3, m0 = n == 35, m1 = e == 3 ? -1 : m0 | (e == 1), rem = 96 + 3 * (j >> 1);
                const int c1_ = j ^ (n < 38 ? 6 : 4 >> ((n - 38) >> 2) & 6), c0_ = n < 38 ? 8 + (j & 1) : c1_;
                const int f = (0xC840A80C204ull >> (4 * min(n - 31, e + 7))) & 15;
                const int r0 = m0 ? rem : 6 * (j ^ (f >> 3)) + (f & 6), r1 = m1 ? rem : r0 + (n < 38 ? 0 : 2);
                mbar_spin(we + (n & 7) * 8, ((n >> 3) & 1) ^ 1);
                if (elect()) {
                    const uint32_t dst = sb + OFF_W + (n & 7) * 16384, fb = wf + (n & 7) * 8;
                    mbar_expect(fb, m1 < 0 ? 8192 : 16384 - 2048 * (m0 + m1));
                    tma_ld2(dst, &mp.w4[m0], 64 * c0_, r0 * (32 >> m0), fb);
                    if (m1 >= 0) tma_ld2(dst + 8192, &mp.w4[m1], 64 * c1_, r1 * (32 >> m1), fb);
                }
            }
        } else {
            {
                wait_cnt(&g_cnt.tab[0], ep);
                mbar_spin(bars + B_MODR * 8, 0);
                if (elect()) {
                    mbar_expect(bars + B_TAB * 8, TAB_BYTES / 2 + VEC_BYTES);
                    bulk_ld(sb + OFF_TAB, g_tab + (j & 1) * (TAB_BYTES / 32), TAB_BYTES / 2, bars + B_TAB * 8);
                    bulk_ld(sb + M_GB, g_tab + (TAB_BYTES + j * VEC_BYTES) / 16, VEC_BYTES, bars + B_TAB * 8);
                }
                TS(lane == 0, 5)
            }
            wait_cnt(&g_cnt.uv[0], 4 * ep);
#pragma unroll 1
            for (int c = lane; c < 80; c += 32) {
                const float* src = g_uv + (c < 64 ? 64 * j + c : 448 + 16 * j + c);
                const uint32_t u = split2(ldcg32f(src) + ldcg32f(src + 3 * D_)), v = split2(ldcg32f(src + D_) + ldcg32f(src + 4 * D_));
                const uint32_t s = split2(ldcg32f(src + 2 * D_) + ldcg32f(src + 5 * D_));
                sts128(sb + OFF_F1 + c * 16, u, __byte_perm(u, v, 0x5410), __byte_perm(v, 0, 0x1032), s);
                sts128(sb + M_F1 + c * 16, s & 0xffffu, 0, 0, 0);
            }
            fence_async_smem();
            warp_arrive(bars + B_VEC * 8);
            TS(lane == 0, 9)
#pragma unroll 1
            for (int e = 1; e < 3; e++) {
                wait_cnt(e == 1 ? &g_cnt.g1[min(grp + 15 + min(lane, 2), 31) * 32] : &g_cnt.g2[(grp + 16) * 32], (G_ALL ? 32 : 8) * ep - (e == 1 ? SKIP_G1 : SKIP_G2), true);
                if (elect()) mbar_arrive(bars + (B_GATE + 2 + e) * 8);
                TS(lane == 0, 27 + 2 * e)
            }
            wait_cnt(&g_cnt.cs2[0], 4 * ep);
            if (elect()) mbar_arrive(bars + B_VEC3 * 8);
            TS(lane == 0, 19)
        }
        return;
    }

    {
        uint32_t ep;
        {
            TIDS
            ep = ld_cold(&g_epoch);
            const int cp = (tid + 16) % 40, cp1 = tid % 40;
            const uint4 sh0 = ldg128(pp.shift_k + (80 * (id & 7) + 2 * cp1) * 4), sh1 = ldg128(pp.shift_k + (80 * (id & 7) + 2 * cp) * 4);
            uint32_t dd;
            asm volatile("ld.global.nc.u16 %0, [%1];" : "=r"(dd) : "l"(pp.ssm_D + 5 * id + min(wg + 3 * lane, 4)));
            TR4(lane == 0, 40 + warp)
            __syncthreads();
            asm volatile("barrier.cluster.arrive.relaxed.aligned;" ::: "memory");
            asm volatile("add.u32 %0, %0, 1;" : "+r"(ep));
#pragma unroll 1
            for (int hw = 0; hw < 2; hw++) {
                if ((unsigned)(warp - 2 * hw) >= 10) continue;
                const int u = tid - 64 * hw;
                const int c = hw ? cp : cp1, oc = u / 40, line = 31 - 16 * hw - (id >> 3);
                const uint4 sh = hw ? sh1 : sh0;
                const uint32_t st = sb + OFF_ST + hw * 10240, sta = st + c * 256 + ((((6 - 2 * (oc & 3)) ^ (oc >> 2) ^ (line & 1)) ^ (c & 7)) << 4), in = oc * 1280 + c * 4;
                const uint32_t f0 = __byte_perm(sh.x, sh.z, 0x5410), f1 = __byte_perm(sh.x, sh.z, 0x7632), f2 = __byte_perm(sh.y, sh.w, 0x5410), f3 = __byte_perm(sh.y, sh.w, 0x7632);
                uint32_t kk[11], vv[8];
                mbar_spin(bars + (B_IN + hw) * 8, 0);
                TS(tid == 64, 18 + 42 * hw)
#pragma unroll
                for (int i = 0; i < 11; i++) kk[i] = lds32(sb + OFF_KIN + hw * 10752 + in + i * 160);
#pragma unroll
                for (int i = 0; i < 8; i++) vv[i] = lds32(sb + OFF_VIN + hw * 10240 + in + i * 160);
#pragma unroll
                for (int i = 0; i < 8; i++) vv[i] = mul2(fma2(kk[i + 3], f0, fma2(kk[i + 2], f1, fma2(kk[i + 1], f2, mul2(kk[i], f3)))), vv[i]);
                sts128(sta, tag(__byte_perm(vv[0], vv[1], 0x5410), ep), __byte_perm(vv[2], vv[3], 0x5410), __byte_perm(vv[4], vv[5], 0x5410), __byte_perm(vv[6], vv[7], 0x5410));
                sts128(sta + 128, tag(__byte_perm(vv[0], vv[1], 0x7632), ep), __byte_perm(vv[2], vv[3], 0x7632), __byte_perm(vv[4], vv[5], 0x7632), __byte_perm(vv[6], vv[7], 0x7632));
                bar_sync(7 + hw, 320);
                flush_tile(st, g_kvT + (size_t)(80 * (id & 7)) * S_ + 64 * line, u);
                signal_cnt(&g_cnt.kv[(id & 7) * 32], lane, warp == 11, true);
                TS(tid == 64 && hw, 1)
            }
            if (tid < 320) sts128(sb + OFF_CH + (tid >> 6) * CH_BYTES + 4096 + (tid & 63) * 16, 0, 0, 0, 0);
            mbar_spin(bars + B_SSM * 8, 0);
            TS(tid == 0, 14)
#pragma unroll 1
            for (int u0 = wg; u0 < 20; u0 += 12) {
                uint2 w[4];
                uint32_t pv[4];
#pragma unroll
                for (int i = 0; i < 4; i++) {
                    const uint32_t a = sb + OFF_SSM + min(u0 + 3 * i, 19) * 1024 + wt * 8;
                    w[i] = lds64(a); pv[i] = lds32(a - 4);
                }
#pragma unroll
                for (int i = 0; i < 4; i++) {
                    const int un = min(u0 + 3 * i, 19);
                    sts128(sb + OFF_CH + (un >> 2) * CH_BYTES + OFF_P + (un & 3) * 2048 + wt * 16, __byte_perm(w[i].x, pv[i], 0x7610), __byte_perm(w[i].x, 0, 0x1032), __byte_perm(w[i].y, w[i].x, 0x7610), __byte_perm(w[i].y, 0, 0x1032));
                }
            }
            __syncwarp();
            if (wt < 2 - (wg >> 1)) {
                const uint32_t h = lds32(sb + OFF_SSM + (wg + 3 * wt) * 4096), h0 = pack2(blo(h) + blo(dd), 0.f);
                sts64f(sb + OFF_CH + (wg + 3 * wt) * CH_BYTES + OFF_P, __uint_as_float(h0), __uint_as_float(__byte_perm(h, h0, 0x5432)));
            }
            fence_async_smem();
            warp_arrive(bars + B_BK * 8);
            asm volatile("barrier.cluster.wait.aligned;" ::: "memory");
            mbar_spin(bars + B_BK * 8, 0);
            TS(tid == 0, 15)
        }

#pragma unroll 1
        for (int c = wg; c < 5; c += 3) {
            const uint32_t kvb = sb + OFF_CH + c * CH_BYTES;
            mbar_spin(bars + (c < 3 ? B_RAW : B_RAW3) * 8, 0);
            for (uint32_t ph = 0; c < 3; ph ^= 1) {
                const int wt = tid_now() & 127;
                if (!RARE(bar_any(1 + wg, lop3<0x7E>(lds32(kvb + wt * 16), ep, lds32(kvb + 2048 + wt * 16)) & 1))) break;
                if (wt == 0) { mbar_expect(bars + (B_RETRY + wg) * 8, 4096); bulk_ld(kvb, g_kvT + (size_t)(5 * id + c) * S_, 4096, bars + (B_RETRY + wg) * 8); }
                mbar_spin(bars + (B_RETRY + wg) * 8, ph);
            }
            TS(threadIdx.x == 0, c ? 13 : 11)
            float acc[64];
            {
                const int l = tid_now() & 31;
                conv_channel(acc, kvb + OFF_P + (8 * (warp & 3) + (l >> 2) - 2 * (l & 3)) * 4, (((uint64_t)0xC0000010u << 32) | ((kvb & 0x3FFFF) >> 4) | 0x10000u) + pp.nil);
            }
            TS(threadIdx.x == 0, c ? 16 : 12)
            if (c < 3) warp_arrive(bars + B_R1 * 8);
            else mbar_spin(bars + B_R1 * 8, 0);
            if (wg == 2 && id < 120) {
                TIDS
                mbar_spin(bars + B_RAW3 * 8, 0);
                mbar_spin(bars + B_WM * 8, 0);
                TS(wt == 0, 56)
                float d[4];
                gemv_tile<8>(d, sb + OFF_WM, sb + OFF_Z, 0);
                const float d2 = __shfl_up_sync(~0u, d[2], 1);
                TS(wt == 0, 7)
                if (t < 2) asm volatile("{\n.reg .b64 v;\nmov.b64 v, {%1, %2};\nst.relaxed.gpu.global.b64 [%0], v;\n}" ::"l"(g_mod + (id & 1) * 6 * D_ + 64 * pr + 16 * (warp & 3) + g + 8 * t),
                                        "r"(__float_as_uint(t ? d2 : d[0])), "r"(lds32(sb + M_EP)) : "memory");
            }
            TR4(threadIdx.x == 0, 60 + (c >= 3) * 10)
            TIDS
            const int e = 127 - 8 * (lane >> 4) - (lane & 7), u0 = (warp & 3) + 8 * (e >> 2) + (e & 3) + 4 * ((lane >> 3) & 1);
            const uint32_t ring = sb + OFF_RING + c * 16384 + (warp & 3) * 4096, wa = ring + (u0 ^ ((u0 >> 1) & 4)) * 16;
            if (lane < (warp & 3)) sts128(ring + lane * 16, 0, 0, 0, 0);
#pragma unroll
            for (int i = 0; i < 8; i++)
                stsm4t(i == 0 && u0 >= 256 ? sb + M_SINK : wa - 512 * i, pack2(acc[8 * i], acc[8 * i + 1]), pack2(acc[8 * i + 2], acc[8 * i + 3]),
                       pack2(acc[8 * i + 4], acc[8 * i + 5]), pack2(acc[8 * i + 6], acc[8 * i + 7]));
            warp_arrive(bars + (B_RING + c) * 8);
            TR4(threadIdx.x == 0, 61 + (c >= 3) * 10)
        }
        TIDS
        if (wg == 2) bar_sync(3, 128);
        if (warp == 9) {
            const int v = min(lane / 5, 3);
            const uint2* gm = g_mod + (v + (v == 3)) * D_ + 5 * id + lane % 5;
            const unsigned epoch = lds32(sb + M_EP);
            uint2 r0, r1;
            unsigned it = 0;
            do {
                r0 = ld_mod(gm); r1 = ld_mod(gm + 6 * D_);
                SPIN_CHECK(55)
            } while (!__all_sync(~0u, r0.y == epoch && r1.y == epoch));
            const float m0 = __uint_as_float(r0.x), m1 = __uint_as_float(r1.x);
            const float m = rbf(m0 + m1), p = rbf(1.f + m);
            const float cz = zscale(__shfl_sync(~0u, p, 15 + lane % 5)), ga = __shfl_sync(~0u, m, 10 + lane % 5);
            if (lane < 15) sts32(sb + M_AB + lane % 5 * 16 + v * 4, lane < 10 ? __float_as_uint(cz * ga * (lane < 5 ? m : p)) : pack2(cz, cz));
            warp_arrive(bars + B_MODR * 8);
            TS(lane == 0, 6)
        }
        mbar_spin(bars + B_QRDY * 8, 0);
        uint4 rs[2], nm[2];
#pragma unroll
        for (int h = 0; h < 2; h++) { rs[h] = lds128(sb + OFF_QT + 20480 + h * 2048 + wt * 16); nm[h] = lds128(sb + OFF_QT + 24576 + h * 2048 + wt * 16); }
        mbar_spin(bars + B_MODR * 8, 0);
        TR4(threadIdx.x == 0, 72)
        uint32_t it = 0;
        while (RARE(__any_sync(~0u, (lop3<0x7E>(rs[0].x, ep, rs[0].z) | lop3<0x7E>(nm[0].x, ep, nm[0].z) | lop3<0x7E>(rs[1].x, ep, rs[1].z) | lop3<0x7E>(nm[1].x, ep, nm[1].z)) & 1))) {
#pragma unroll
            for (int h = 0; h < 2; h++) { rs[h] = ld_part(g_qst + 1024 * h + 8 * wt); nm[h] = ld_part(g_qst + S_ + 1024 * h + 8 * wt); }
            STALE(1)
            SPIN_CHECK(53)
        }
        TR4(threadIdx.x == 0, 73)
#pragma unroll 1
        for (int c = wg == 2 ? 0 : 3 + wg; c < (wg == 2 ? 3 : 4 + wg); c++) {
            uint4 q[2], p[2][4];
#pragma unroll
            for (int h = 0; h < 2; h++) q[h] = lds128(sb + OFF_QT + h * 10240 + (wt >> 1) * 160 + c * 32 + (wt & 1) * 16);
            const float4 ab = lds128f(sb + M_AB + c * 16);
            mbar_spin(bars + (B_RING + c) * 8, 0);
            TR4(wt == 0, wg == 2 ? 80 + 2 * c : 74)
#pragma unroll
            for (int i = 0; i < 8; i++) p[i >> 2][i & 3] = lds128(sb + OFF_RING + c * 16384 + (i & 3) * 4096 + (i >> 2) * 2048 + (wt ^ ((wt >> 1) & 4)) * 16);
            while (RARE(__any_sync(~0u, lop3<0x7E>(q[0].x, ep, q[1].x) & 1))) {
#pragma unroll
                for (int h = 0; h < 2; h++) q[h] = ld_part(g_qT + ((64 * h + (wt >> 1)) * D_ + 5 * id + c) * 16 + 8 * (wt & 1));
                STALE(2)
                SPIN_CHECK(52)
            }
            TR4(wt == 0, wg == 2 ? 81 + 2 * c : 75)
#pragma unroll
            for (int h = 0; h < 2; h++) {
                const uint32_t qq[4] = {q[h].x, q[h].y, q[h].z, q[h].w}, r4[4] = {rs[h].x, rs[h].y, rs[h].z, rs[h].w}, n4[4] = {nm[h].x, nm[h].y, nm[h].z, nm[h].w};
                const uint4 y = add2(add2(p[h][0], p[h][1]), add2(p[h][2], p[h][3]));
                const uint32_t yy[4] = {y.x, y.y, y.z, y.w};
                uint32_t o[4];
#pragma unroll
                for (int i = 0; i < 4; i++) {
                    const uint32_t n = fma2(qq[i], r4[i], n4[i]);
                    o[i] = fma2(pack2(fmaf(blo(n), ab.y, ab.x), fmaf(bhi(n), ab.y, ab.x)), yy[i], mul2(qq[i], __float_as_uint(ab.z)));
                }
                stg128_tag(g_x1T + (size_t)(5 * id + c) * S_ + 1024 * h + 8 * wt, o[0], o[1], o[2], o[3], ep, ((5 * id + c) >> 3) & 3);
            }
        }
        warp_arrive(bars + B_XS * 8);
        TS(tid == 0, 17)
        TS(tid == 256, 52)
    }

    const uint32_t nil = pp.nil;
    const int wq = warp & 3;
    if (wg == 2) {
        TIDS
        asm volatile("setmaxnreg.dec.sync.aligned.u32 48;");
        {
            const uint32_t ep = lds32(sb + M_EP);
            uint32_t ph = 0;
            const Tile tl = ring_tile(min(4 * lane + wq, 59), grp, j);
            const uint32_t plan = bars + (B_XFULL + 10 * tl.w + tl.kb) * 8;
#pragma unroll 1
            for (int m = wq - 4; m < 60; m += 4) {
                const int n = max(m, 0);
                const uint32_t pl = __shfl_sync(~0u, plan, n >> 2), at = __shfl_sync(~0u, tl.at, n >> 2);
                const int e = (n >= 20) + (n >= 40);
                const uint32_t a = sb + OFF_XR + (n & 7) * 8192;
                uint32_t ta = a + (e == 0 ? lane * 128 + ((lane & 7) << 4) + (lane >> 3) * 4
                                 : e == 1 ? (lane & 15) * 128 + (((lane >> 4 << 1) ^ (lane & 7)) << 4) + (lane & 8) + (lane >> 4) * 4
                                          : lane * 32 + (lane >> 2) * 4);
                uint32_t tb = e == 0 ? ta ^ 32 : ta + 2048, tc = e == 2 ? ta + 1024 : ta ^ 64, td = e == 2 ? tb + 1024 : tb ^ 64;
                uint32_t live = m >= 0 && m != 40 && m != 40 + XLEAD,
                    f0 = pl;
                uint32_t f1 = m == GATE_W2 || m == GATE_W3 || m == GATE_W3B ? bars + (B_GATE + (m >= GATE_W3) + (m >= GATE_W3B)) * 8 : 0;
                if (lane) f0 = f1;
                if (lane > 1 || m < 0) f0 = 0;
                asm volatile("" : "+r"(ta), "+r"(tb), "+r"(tc), "+r"(td), "+r"(live), "+r"(f0));
                mbar_spin(bars + (m < 0 ? B_BK : B_LAND + (n & 7)) * 8, (n >> 3) & 1);
                TR5(lane == 0, n)
                while (true) {
                    uint32_t v[8];
#pragma unroll
                    for (int i = 0; i < 8; i++) v[i] = lds32(((i & 2) ? ((i & 1) ? td : tc) : (i & 1) ? tb : ta) + (i >> 2) * 4096);
                    const uint32_t bad = lop3<0xFE>(lop3<0x7E>(v[0], ep, v[1]), lop3<0x7E>(v[2], ep, v[3]), lop3<0x7E>(v[4], ep, v[5]));
                    if (!RARE(__any_sync(~0u, lop3<0xA8>(bad, lop3<0x7E>(v[6], ep, v[7]), live)))) break;
                    if (elect()) load_tile(mp, a, e, at, bars + (B_AGAIN + wq) * 8);
                    mbar_spin(bars + (B_AGAIN + wq) * 8, ph);
                    ph ^= 1;
                    STALE1(e)
                }
                TR5(lane == 0, 60 + n)
                if (f0) mbar_arrive(f0);
            }
        }
        if (wq == 0) {
#pragma unroll 1
            for (int w = 0; w < 2; w++) {
                const uint4* src = g_part + (size_t)(grp + 16 * w) * 40960;
                TR4(lane == 0, 90 + 2 * w)
                mbar_wait(bars + (B_RING + w) * 8, 1);
                TR4(lane == 0, 91 + 2 * w)
                if (elect()) {
                    const uint32_t fb = bars + (B_IN + w) * 8, rem = sb + OFF_OUT + w * 10240;
                    mbar_expect(fb, 10240);
                    bulk_ld(rem + 8192, &g_x1f[((grp + 16 * w) * 8 + j) * 640 + 512], 2048, fb);
#pragma unroll 1
                    for (int i = 0; i < 4; i++) bulk_ld(rem + i * 2048, src + ((j >> 2) + 2 * i) * 5120 + 4096 + j * 128, 2048, fb);
                }
            }
        }
#pragma unroll 1
        for (int uw = 0; uw < 2; uw++) {
            const int tile = grp + 16 * uw;
            const uint32_t ep = lds32(sb + M_EP), in = sb + OFF_OUT + uw * 10240 + wt * 16, sr = in - lane * 16;
            mbar_wait(bars + (B_IN + uw) * 8, 1);
            TR4(wt == 0, 94 + 3 * uw)
            uint4 u[4];
#pragma unroll
            for (int i = 0; i < 4; i++) u[i] = lds128(in + i * 2048);
            const uint4 base = lds128(in + 8192);
            const uint32_t ra = sb + M_F1 + (64 * uw + 16 * wq + g) * 4;
            const uint4 gr = scale16(lds64f(sb + M_GB + (64 + 2 * t) * 4), lds64f(sb + M_GB + (72 + 2 * t) * 4), __uint_as_float(lds32(ra)), __uint_as_float(lds32(ra + 32)));
            uint32_t it = 0;
            while (RARE(__any_sync(~0u, stale4(u, ep) & 1))) {
                ld_part4(u, g_part + (size_t)tile * 40960 + (j >> 2) * 5120 + 4096 + j * 128 + wt, 10240);
                STALE(3)
                if (++it > SPIN_LIMIT) SPIN_FAIL(58)
            }
            TR4(wt == 0, 95 + 3 * uw)
            const uint4 r = fin16(add2(add2(u[0], u[1]), add2(u[2], u[3])), base, gr);
            __syncwarp();
            stsm4(sr + (lane & 15) * 32 + (((lane >> 4) ^ ((lane >> 2) & 1)) << 4), r.x, r.y, r.z, r.w);
            __syncwarp();
            stg128(out + (size_t)(64 * tile + 16 * wq + (lane >> 1)) * D_ + 512 + 16 * j + 8 * (lane & 1), lds128(sr + (lane >> 1) * 32 + (((lane & 1) ^ ((lane >> 3) & 1)) << 4)));
            TR4(wt == 0, 96 + 3 * uw)
            __syncwarp();
        }
        TS(wt == 0, 21)
        if (wq == 0) {
            uint32_t it = 0;
            while (!mbar_try(bars + B_OWN * 8, 0)) { if (++it > SPIN_LIMIT) SPIN_FAIL(56) }
        }
        return;
    }

    TIDS
    const int uw = wg, tile = grp + 16 * uw, row0 = 64 * tile + 16 * wq;
    const bool leader = wt == 0; (void)leader;
    const uint32_t xfull = bars + (B_XFULL + 10 * uw) * 8, xempty = bars + B_XEMPTY * 8, wfull = bars + B_WFULL * 8, wempty = bars + B_WEMPTY * 8;
    const uint64_t dz = mkdesc(0) + pp.nil;
    auto xwait = [&](uint32_t kb, uint32_t e) { mbar_spin(xfull + kb * 8, e & 1); };
    asm volatile("setmaxnreg.inc.sync.aligned.u32 216;");
    const uint32_t ep = lds32(sb + M_EP);
    uint32_t x2[20];
    uint32_t res[20] = {};
    {
        float acc[40];
        const uint32_t la = ((lane & 7) + 8 * (lane >> 4)) * 128 + (((2 * wq + ((lane >> 3) & 1)) ^ (lane & 7)) << 4);
        auto pos = [&](int n) { return ring_pos(uw, n, LEAD1) & 7; };
        auto slot = [&](int n) { return sb + OFF_XR + pos(n) * 8192; };
        float al[2], r1[2], n1[2];
        {
            float sl[4], sq[4], v[4] = {};
            uint32_t z0[16], z1[16], zz[16];
            uint64_t bd = dz + b80_desc(dsb, 0, 0, 0), tb = (((uint64_t)8 << 32) | ((dsb + OFF_TAB) >> 4) | (7u << 16)) + pp.nil;
            auto ldfrag = [&](uint32_t (&z)[16], int n, bool even) {
#pragma unroll
                for (int q = 0; q < 4; q++) ldsm4t(slot(n) + la + q * 2048, z[4 * q], z[4 * q + 1], z[4 * q + 2], z[4 * q + 3]);
#pragma unroll
                for (int q = 0; q < 4; q++) ldsm4t_if(n == j >> 1, slot(n) + la + q * 2048, &res[4 * q]);
                if (even) ldsm4t_if(n == 4 && !((j ^ (j >> 2)) & 1), slot(n) + la + (j & 3) * 2048, &res[16]);
            };
            auto tile1 = [&](const uint32_t (&zc)[16], uint32_t (&zn)[16], int n, int h) {
                const bool last = h && n == 5, ok = mbar_test(xfull + (n + 1) * 8, 0), okw = !h || mbar_test(wfull + ((n + 1) >> 1) * 8, 0);
                wg_fence();
#pragma unroll
                for (int q = 0; q < 2; q++) wgmma_rs80(acc, zc[4 * q], zc[4 * q + 1], zc[4 * q + 2], zc[4 * q + 3], bd + q * B80_STEP, 1);
                wg_commit();
                if (lane < 2) mbar_arrive_after(xempty + pos(n) * 8, res[12], res[16], nil);
                wg_wait<1>();
                if (!h && n && lane == 0) mbar_arrive(wempty + ((n >> 1) - 1) * 8);
                if (!ok) xwait(n + 1, 0);
                if (!last) ldfrag(zn, n + 1, h);
#pragma unroll
                for (int e = 0; e < 16; e++) zz[e] = mul2(zc[e], zc[e]);
                const uint64_t t0 = last ? ((uint64_t)8 << 32) | ((dsb + M_NUL) >> 4) : tb;
                const uint32_t ts = last ? 0 : 14;
                wg_fence();
#pragma unroll
                for (int q = 0; q < 4; q++) wgmma_rs8(sl, zc[4 * q], zc[4 * q + 1], zc[4 * q + 2], zc[4 * q + 3], t0 + q * ts, 1);
#pragma unroll
                for (int q = 0; q < 4; q++) wgmma_rs8(sq, zz[4 * q], zz[4 * q + 1], zz[4 * q + 2], zz[4 * q + 3], t0 + q * ts, 1);
#pragma unroll
                for (int q = 2; q < 4; q++) wgmma_rs80(acc, zc[4 * q], zc[4 * q + 1], zc[4 * q + 2], zc[4 * q + 3], bd + q * B80_STEP, 1);
                wg_commit();
                tb += 56;
                bd = bd + (uint64_t)B80_HALF;
                if (!okw) mbar_spin(wfull + ((n + 1) >> 1) * 8, 0);
                TR(leader, 100 + 10 * uw + n)
            };
            zero(acc); zero(sl); zero(sq);
            mbar_spin(bars + B_TAB * 8, 0);
            float4 k = lds128f(sb + M_KS);
            float k4 = __uint_as_float(lds32(sb + M_KS + 16));
#pragma unroll
            for (int w = 1; w < 5; w++) {
                const float4 o = lds128f(sb + M_KS + w * 32);
                k.x += o.x; k.y += o.y; k.z += o.z; k.w += o.w; k4 += __uint_as_float(lds32(sb + M_KS + w * 32 + 16));
            }
            uint32_t fa[4];
            auto coefs = [&]() {
                mbar_spin(bars + (B_SUMS + uw) * 8, 0);
                TS(leader && !uw, 10)
                const float4 o = lds128f(sb + OFF_ROW + uw * 2048 + wt * 16);
                v[0] += o.x; v[1] += o.y; v[2] += o.z; v[3] += o.w;
#pragma unroll
                for (int h = 0; h < 2; h++) {
                    const int l0 = lane & ~3;
                    const float s1 = __shfl_sync(~0u, v[2 * h], l0), s2 = __shfl_sync(~0u, v[2 * h], l0 + 1), scc = __shfl_sync(~0u, v[2 * h], l0 + 2);
                    const float scs = __shfl_sync(~0u, v[2 * h + 1], l0 + 2), sc = __shfl_sync(~0u, v[2 * h], l0 + 3), sqq = __shfl_sync(~0u, v[2 * h + 1], l0 + 3);
                    const float m1 = s1 * (1.f / D_), va = fmaxf(s2 * (1.f / D_) - m1 * m1, 0.f) + 1e-5f, r = rsqrtf(va);
                    const float m2 = (r * (sc - m1 * k.x) + k.y) * (1.f / D_);
                    const float e2 = (r * (r * (sqq + m1 * (m1 * k.z - 2.f * scc)) + 2.f * (scs - m1 * k.w)) + k4) * (1.f / D_);
                    al[h] = r * 0.5f * rsqrtf(fmaxf(e2 - m2 * m2, 0.f) + 1e-5f); r1[h] = r; n1[h] = -m1 * r;
                    const uint32_t fb = split2(va * r), fx = split2(t == 3 ? -m2 * va * r : -m1), fc = __shfl_sync(~0u, fx, lane | 3);
                    fa[h] = __byte_perm(fx, fb, t == 1 ? 0x5432 : t == 2 ? 0x7654 : 0x1010);
                    fa[2 + h] = t ? 0 : fc >> 16;
                }
            };
            mbar_spin(wfull, 0);
            xwait(0, 0);
            TS(leader, 32 + uw)
            ldfrag(z0, 0, false);
#pragma unroll 1
            for (int n = 0; n < 6; n += 2) { tile1(z0, z1, n, 0); tile1(z1, z0, n + 1, 1); }
#pragma unroll
            for (int n = 6; n < 10; n++) {
                const uint64_t ad = dz + (((dsb + OFF_XR + pos(n) * 8192) >> 4) | 0x10000u);
                const bool ok = n == 9 || mbar_test(xfull + (n + 1) * 8, 0), okw = n != 7 || mbar_test(wfull + 4 * 8, 0);
                wg_fence();
#pragma unroll
                for (int q = 0; q < 4; q++) wgmma_ss80t(acc, ad + q * 128, bd + q * B80_STEP, 1);
                wg_commit();
                bd = bd + (uint64_t)B80_HALF;
                if (n == 8) coefs();
                if (n == 9) ldsm4t_if(9 - (j & 1) == 8 + (j >> 2), slot(9) + la + (j & 3) * 2048, &res[16]);
                wg_wait<1>();
                if (n > 6 && lane < 2) mbar_arrive(xempty + pos(n - 1) * 8);
                if (!(n & 1) && lane == 0) mbar_arrive(wempty + ((n >> 1) - 1) * 8);
                if (n == 6) {
                    reg_fence(sl); reg_fence(sq);
#pragma unroll
                    for (int e = 0; e < 2; e++) {
                        v[2 * e] = t == 0 ? sl[2 * e] + sl[2 * e + 1] : t == 1 ? sq[2 * e] + sq[2 * e + 1] : sl[2 * e];
                        v[2 * e + 1] = t == 2 ? sl[2 * e + 1] : sq[2 * e];
                    }
                    st_peer(peer_addr(sb + OFF_ROW + uw * 2048 + wt * 16), __float_as_uint(v[0]), __float_as_uint(v[1]), __float_as_uint(v[2]), __float_as_uint(v[3]), peer_addr(bars + (B_SUMS + uw) * 8));
                    TS(leader && !uw, 59)
                }
                if (!ok) xwait(n + 1, 0);
                if (!okw) mbar_spin(wfull + 4 * 8, 0);
                TR(leader, 100 + 10 * uw + n)
            }
            mbar_spin(bars + B_VEC * 8, 0);
            wg_fence();
            wgmma_rs80k(acc, fa[0], fa[1], fa[2], fa[3], ((uint64_t)8 << 32) | ((dsb + OFF_F1) >> 4) | (((M_F1 - OFF_F1) >> 4) << 16), 1);
            wg_commit();
        }
        wg_wait<0>();
        reg_fence(acc);
        if (lane < 2) mbar_arrive_after(xempty + pos(9) * 8, res[16], 0, nil);
        if (lane == 0) mbar_arrive(wempty + 4 * 8);
        TS(leader, 34 + uw)
        {
            bf16* const trow = g_t + (size_t)(row0 + g + 2) * D_;
#pragma unroll
            for (int b = 0; b < 3; b++) {
                uint32_t p[8];
#pragma unroll
                for (int ii = 0; ii < 4; ii++) {
                    const int i = 4 * b + ii;
                    if (i >= 10) continue;
#pragma unroll
                    for (int h = 0; h < 2; h++) p[(i & 3) + 4 * h] = pack2(gelu2(acc[4 * i + 2 * h] * al[h]), gelu2(acc[4 * i + 2 * h + 1] * al[h]));
                }
                if (b < 2) {
                    const int gr = (2 * j + b) / 5, sh = (gr & 1) ? -1 - (gr >> 1) : 1 + (gr >> 1);
                    bf16* dst = trow + 64 * j + 32 * b + 8 * t;
                    const int w = (((g + sh) >> 2) & 2) + (t >> 1);
                    stg128_tag(dst + sh * D_, p[0], p[1], p[2], p[3], ep, w);
                    stg128_tag(dst + (sh + 8) * D_, p[4], p[5], p[6], p[7], ep, w ^ 2);
                    if (row0 + g < sh || row0 + g + 8 >= S_ + sh) stg128_tag(dst + (sh > 0 ? 0 : 8) * D_, 0, 0, 0, 0, ep, (sh > 0 ? 0 : 2) + (t >> 1));
                } else {
                    bf16* dst = trow + 512 + 16 * j + 4 * t;
                    const uint32_t lo = t == (g < 2), hi = t == (g >= 2), o = j & 1;
                    stg64(dst - 2 * D_, lop3<0xB8>(p[0], lo & ~o, ep), lop3<0xB8>(p[1], lo & o, ep));
                    stg64(dst + 6 * D_, lop3<0xB8>(p[4], hi & ~o, ep), lop3<0xB8>(p[5], hi & o, ep));
                    if (row0 + g + 8 >= S_ - 2) stg64(dst + 8 * D_, ep & (t == 1) & ~o, ep & (t == 1) & o);
                }
            }
        }
        signal_cnt(&g_cnt.g1[tile * 32], lane, G_ALL || wq == 3, true);
        TS(leader, 36 + uw)
#pragma unroll
        for (int i = 0; i < 10; i++) {
            const float2 c = lds64f(sb + M_C + (8 * i + 2 * t) * 4), s = lds64f(sb + M_SB + (8 * i + 2 * t) * 4);
#pragma unroll
            for (int h = 0; h < 2; h++) {
                acc[4 * i + 2 * h] = fmaf(blo(res[2 * i + h]), r1[h], fmaf(n1[h], c.x, s.x));
                acc[4 * i + 2 * h + 1] = fmaf(bhi(res[2 * i + h]), r1[h], fmaf(n1[h], c.y, s.y));
            }
        }
        mbar_spin(wfull + 5 * 8, 0);
        xwait(0, 1);
        TS(leader, 22 + uw)
        uint32_t xo = 32 + 16 * uw, xp = 0;
        const uint64_t ax = dz + (((dsb + OFF_XR) >> 4) | 0x10000u);
        uint64_t ad = ax + xo * 64, bd = dz + b80_desc(dsb, 5, 0, 0);
#pragma unroll 1
        for (int i = 0; i < 5; i++) {
            const uint32_t x1 = xfull + (1 + 2 * i) * 8, p1 = 1, x2 = xfull + min(2 + 2 * i, 9) * 8, p2 = 1;
            const uint32_t w2 = wfull + (min(6 + i, 9) & 7) * 8, pw = i >= 2;
            const bool ok1 = mbar_test(x1, p1);
            wg_fence();
#pragma unroll
            for (int q = 0; q < 4; q++) wgmma_ss80(acc, ad + q * 2, bd + q * B80_STEP, 1);
            wg_commit();
            wg_wait<1>();
            if (lane < 2 && i) mbar_arrive(xempty + xp);
            if (lane == 0 && i) mbar_arrive(wempty + ((4 + i) & 7) * 8);
            if (!ok1) mbar_spin(x1, p1);
            const bool ok2 = mbar_test(x2, p2), okw = mbar_test(w2, pw);
            wg_fence();
#pragma unroll
            for (int q = 0; q < 4; q++) wgmma_ss80(acc, ad + 512 + q * 2, bd + (uint64_t)(B80_HALF + q * B80_STEP), 1);
            wg_commit();
            const uint32_t xc = xo;
            xp = xo + 8; xo = (xo + 16) & 48;
            ad = ax + xo * 64;
            bd += i == 2 ? 2 * B80_HALF - 8192 + (8192ll << 16) : 2 * B80_HALF;
            asm volatile("" : "+l"(ad), "+l"(bd));
            wg_wait<1>();
            if (lane < 2) mbar_arrive(xempty + xc);
            if (!ok2) mbar_spin(x2, p2);
            if (!okw) mbar_spin(w2, pw);
            TR(leader, (uw ? 86 : 20) + 2 * i)
        }
        wg_wait<0>();
        reg_fence(acc);
        if (lane < 2) mbar_arrive(xempty + xp);
        if (lane == 0) mbar_arrive(wempty + (9 & 7) * 8);
        TS(leader, 38 + uw)
        float a0 = 0.f, b0 = 0.f, a1 = 0.f, b1 = 0.f;
#pragma unroll
        for (int i = 0; i < 5; i++) {
            uint32_t* p = &x2[4 * i];
#pragma unroll
            for (int e = 0; e < 4; e++) p[e] = pack2(acc[8 * i + 2 * e], acc[8 * i + 2 * e + 1]);
#pragma unroll
            for (int e = 0; e < 4; e++) p[e] = lop3<0xB8>(p[e], (((wt >> 3) ^ (wt << 2)) & 7) == e, ep);
            stg128(&g_x2f[(tile * 40 + (i < 4 ? 4 * j + i : 32 + j)) * 128 + wt], p[0], p[1], p[2], p[3]);
#pragma unroll
            for (int e = 0; e < 8; e += 4) {
                const float* u = &acc[8 * i + e];
                a0 += u[0] + u[1]; b0 = fmaf(u[0], u[0], fmaf(u[1], u[1], b0));
                a1 += u[2] + u[3]; b1 = fmaf(u[2], u[2], fmaf(u[3], u[3], b1));
            }
        }
#pragma unroll
        for (int o = 1; o < 4; o *= 2) {
            a0 += __shfl_xor_sync(~0u, a0, o); b0 += __shfl_xor_sync(~0u, b0, o);
            a1 += __shfl_xor_sync(~0u, a1, o); b1 += __shfl_xor_sync(~0u, b1, o);
        }
        if (t < 2) stg64(&g_stats[(tile * 8 + j) * 64 + 16 * wq + g + 8 * t], tag(__float_as_uint(t ? a1 : a0), ep), __float_as_uint(t ? b1 : b0));
        signal_cnt(&g_cnt.g2[tile * 32], lane, G_ALL || wq == 3, true);
        TS(leader, 40 + uw)
#pragma unroll
        for (int i = 0; i < 10; i++) {
            const float2 c = lds64f(sb + M_GB + (8 * i + 2 * t) * 4), e = lds64f(sb + M_CI + (8 * i + 2 * t) * 4);
#pragma unroll
            for (int h = 0; h < 2; h++)
                res[2 * i + h] = fma2(pack2(c.x, c.y), x2[2 * i + h], pack2(e.x * blo(res[2 * i + h]), e.y * bhi(res[2 * i + h])));
        }
#pragma unroll
        for (int i = 0; i < 20; i++) asm volatile("" : "+r"(res[i]));
    }
    float acc0[64], acc1[44];
    float2 q[4];
    {
        uint4 f0, f1, f2, f3;
        auto xseq = [&](int kb) { return ring_pos(uw, kb, XLEAD) & 7; };
        auto step = [&](const uint4& f, uint64_t bd) {
            wg_fence();
            wgmma_rs128(acc0, f.x, f.y, f.z, f.w, bd, 1);
            wgmma_rs88(acc1, f.x, f.y, f.z, f.w, bd + 512, 1);
            wg_commit();
        };
        const uint32_t xa = sb + OFF_XR + wt * 16;
        const float2* const gs = &g_stats[(tile * 8 + 2 * t) * 64 + 16 * wq + g];
        zero(acc0); zero(acc1);
        uint32_t xs = 0;
        f0 = make_uint4(x2[0], x2[1], x2[2], x2[3]); f1 = make_uint4(x2[4], x2[5], x2[6], x2[7]);
        f2 = make_uint4(x2[8], x2[9], x2[10], x2[11]); f3 = make_uint4(x2[12], x2[13], x2[14], x2[15]);
#pragma unroll
        for (int i = 0; i < 4; i++) q[i] = make_float2(0.f, 0.f);
        mbar_spin(wempty + (9 & 7) * 8, 1);
        mbar_spin(wfull + (10 & 7) * 8, (10 >> 3) & 1);
#pragma unroll 1
        for (int kb = 0; kb < 10; kb++) {
            const uint32_t wn = 10 + 2 * kb;
            const uint64_t bd = dz + (((dsb + OFF_W + (wn & 7) * 16384) >> 4) | (256u << 16));
            step(f0, bd);
            wg_wait<1>();
            if (kb && lane == 0) mbar_arrive(wempty + ((wn - 1) & 7) * 8);
            lds128_if(kb, f2, xa + xs * 8192 + 4096); lds128_if(kb, f3, xa + xs * 8192 + 6144);
            const bool w1 = mbar_test(wfull + ((wn + 1) & 7) * 8, (wn >> 3) & 1), x1 = kb < 9 && mbar_test(xfull + (kb + 1) * 8, 0);
            step(f1, bd + 128);
            if (!w1) mbar_spin(wfull + ((wn + 1) & 7) * 8, (wn >> 3) & 1);
            step(f2, bd + 1024);
            if (lane < 2 && kb) mbar_arrive_after(xempty + xs * 8, f2.x, f3.x, nil);
            wg_wait<1>();
            if (lane == 0) mbar_arrive(wempty + (wn & 7) * 8);
            xs = xseq(kb + 1);
            if (x1) { f0 = lds128(xa + xs * 8192); f1 = lds128(xa + xs * 8192 + 2048); }
            const bool w2 = mbar_test(wfull + ((wn + 2) & 7) * 8, ((wn + 2) >> 3) & 1);
            step(f3, bd + 1152);
            if (kb < 9 && !x1) { xwait(kb + 1, 2); f0 = lds128(xa + xs * 8192); f1 = lds128(xa + xs * 8192 + 2048); }
            if (!w2) mbar_spin(wfull + ((wn + 2) & 7) * 8, ((wn + 2) >> 3) & 1);
            if (kb == 0) {
                TS(leader, 42 + uw)
#pragma unroll
                for (int i = 0; i < 4; i++) q[i] = ld_stat(gs + (i & 1) * 64 + 8 * (i >> 1));
            }
            if (kb == 4) {
                uint32_t it = 0;
                while (RARE(__any_sync(~0u, ((__float_as_uint(q[0].x) ^ ep) | (__float_as_uint(q[1].x) ^ ep) | (__float_as_uint(q[2].x) ^ ep) | (__float_as_uint(q[3].x) ^ ep)) & 1))) {
#pragma unroll
                    for (int i = 0; i < 4; i++) q[i] = ld_stat(gs + (i & 1) * 64 + 8 * (i >> 1));
                    SPIN_CHECK(49)
                }
                float a0 = q[0].x + q[1].x, b0 = q[0].y + q[1].y, a1 = q[2].x + q[3].x, b1 = q[2].y + q[3].y;
#pragma unroll
                for (int o = 1; o < 4; o *= 2) {
                    a0 += __shfl_xor_sync(~0u, a0, o); b0 += __shfl_xor_sync(~0u, b0, o);
                    a1 += __shfl_xor_sync(~0u, a1, o); b1 += __shfl_xor_sync(~0u, b1, o);
                }
                a0 *= 1.f / D_; a1 *= 1.f / D_;
                const float r0 = 0.5f * rsqrtf(fmaxf(b0 * (1.f / D_) - a0 * a0, 0.f) + 1e-5f), r1 = 0.5f * rsqrtf(fmaxf(b1 * (1.f / D_) - a1 * a1, 0.f) + 1e-5f);
                const uint32_t sel = t == 0 ? 0x1010 : t == 1 ? 0x4432 : 0x4444;
                if (t == 0) { sts32(sb + M_F1 + (64 * uw + 16 * wq + g) * 4, __float_as_uint(r0)); sts32(sb + M_F1 + (64 * uw + 16 * wq + g + 8) * 4, __float_as_uint(r1)); }
                q[2] = make_float2(8.f * 0.0356774081f * r0 * r0 * r0, 2.f * 0.7978845608f * r0);
                q[3] = make_float2(8.f * 0.0356774081f * r1 * r1 * r1, 2.f * 0.7978845608f * r1);
                q[1] = make_float2(__uint_as_float(__byte_perm(split2(-a0), 0, sel)), __uint_as_float(__byte_perm(split2(-a1), 0, sel)));
            }
            if (kb == 6) {
#pragma unroll
                for (int i = 0; i < 5; i++) stg128(&g_x1f[(tile * 8 + j) * 640 + i * 128 + wt], res[4 * i], res[4 * i + 1], res[4 * i + 2], res[4 * i + 3]);
            }
            if (kb == 8) asm volatile("fence.proxy.async.global;" ::: "memory");
            TR(leader, 10 * uw + kb)
        }
        const uint64_t fd = ((uint64_t)8 << 32) | ((dsb + OFF_W + 6 * 16384) >> 4);
        wg_fence();
        wgmma_rs128k(acc0, __float_as_uint(q[1].x), __float_as_uint(q[1].y), 0, 0, fd, 1);
        wgmma_rs88k(acc1, __float_as_uint(q[1].x), __float_as_uint(q[1].y), 0, 0, fd + 128, 1);
        wg_commit();
        if (lane == 0) {
            mbar_arrive(bars + B_XFREE * 8);
            asm volatile("mbarrier.arrive.shared::cluster.b64 _, [%0];" ::"r"(peer_addr(bars + B_XFREE * 8)) : "memory");
        }
    }
    const uint32_t recv = sb + recv_off(uw) + wt * 16;
    uint32_t ha[48] = {}, hb[48], hx[12];
    uint64_t wb = dz + (((dsb + OFF_W) >> 4) | (512u << 16));
    auto wdesc = [&](int n) { return wb + (n & 7) * 1024; };
    auto wwait = [&](int n) { mbar_spin(wfull + (n & 7) * 8, (n >> 3) & 1); };
    auto wfree = [&](int n) { if (lane == 0) mbar_arrive(wempty + (n & 7) * 8); };
    auto fresh = [&]() { wb += pp.nil; asm volatile("" : "+l"(wb)); };
    uint32_t pk[32];
    {
        float P0[64];
        const float2 r0 = q[2], r1 = q[3];
        const uint32_t ra = peer_addr(recv), rb = peer_addr(bars + (B_RECV + 4 * uw) * 8);
        auto conv32 = [&](const float* v, int b) {
#pragma unroll
            for (int i = 0; i < 4; i++) {
                ha[8 * b + 2 * i] = pack2(gelu2r(v[4 * i], r0), gelu2r(v[4 * i + 1], r0));
                ha[8 * b + 2 * i + 1] = pack2(gelu2r(v[4 * i + 2], r1), gelu2r(v[4 * i + 3], r1));
            }
#pragma unroll
            for (int s = 2 * b; s < 2 * b + 2; s++) st_peer(ra + s * 2048, ha[4 * s], ha[4 * s + 1], ha[4 * s + 2], ha[4 * s + 3], rb + (b >> 1) * 8);
        };
        auto fetch = [&](int k) {
            mbar_spin(bars + (B_RECV + 4 * uw + k) * 8, 0);
#pragma unroll
            for (int s = 4 * k; s < 4 * k + 4; s++) { const uint4 x = lds128(recv + s * 2048); hb[4 * s] = x.x; hb[4 * s + 1] = x.y; hb[4 * s + 2] = x.z; hb[4 * s + 3] = x.w; }
        };
        auto stage = [&](int n, const uint32_t* a, int steps, int sc) {
            wwait(n);
            wg_fence();
#pragma unroll
            for (int s = 0; s < steps; s++) wgmma_rs128(P0, a[4 * s], a[4 * s + 1], a[4 * s + 2], a[4 * s + 3], wdesc(n) + s * 128, sc || s);
            wg_commit();
        };
        wg_wait<0>();
        reg_fence(acc0); reg_fence(acc1);
        wfree(29); wfree(30);
        TS(leader, 44 + uw)
        if (uw) bar_sync(13, 256);
        uint32_t hr[6];
#pragma unroll
        for (int i = 0; i < 6; i++) {
            const float2 r = (i & 1) ? r1 : r0;
            hr[i] = pack2(gelu2r(acc1[32 + 2 * i], r), gelu2r(acc1[33 + 2 * i], r));
        }
        if (uw) mbar_spin(bars + B_XFREE * 8, 0);
        st_peer(ra + 24576, hr[0], hr[1], hr[2], hr[3], rb + 24);
        asm volatile("st.async.shared::cluster.mbarrier::complete_tx::bytes.v2.b32 [%0], {%1, %2}, [%3];" ::"r"(ra + 26624 - wt * 8), "r"(hr[4]), "r"(hr[5]), "r"(rb + 24) : "memory");
        conv32(&acc1[0], 4);
        conv32(&acc1[16], 5);
        TS(leader, 46 + uw)
        stage(31, &ha[32], 4, 0);
#pragma unroll
        for (int b = 0; b < 4; b++) {
            conv32(&acc0[16 * b], b);
            if (b == 0 && !uw) asm volatile("bar.arrive 13, 256;" ::: "memory");
            if (b == 3) {
                fetch(2);
                mbar_spin(bars + (B_RECV + 4 * uw + 3) * 8, 0);
                const uint4 x = lds128(recv + 24576);
                const uint2 y = lds64(recv + 26624 - wt * 8);
                const uint32_t hp[6] = {x.x, x.y, x.z, x.w, y.x, y.y};
#pragma unroll
                for (int i = 0; i < 6; i++) { hx[i] = (j & 1) ? hp[i] : hr[i]; hx[6 + i] = (j & 1) ? hr[i] : hp[i]; }
            }
            if (!(b & 1)) wwait(32 + (b >> 1));
            wg_fence();
#pragma unroll
            for (int s = 0; s < 2; s++) wgmma_rs128(P0, ha[8 * b + 4 * s], ha[8 * b + 4 * s + 1], ha[8 * b + 4 * s + 2], ha[8 * b + 4 * s + 3], wdesc(32 + (b >> 1)) + (2 * (b & 1) + s) * 128, 1);
            wg_commit();
            if (!(b & 1)) { wg_wait<1>(); wfree(31 + (b >> 1)); }
        }
        TR(leader, 64 + 10 * uw)
        fresh();
        stage(34, &hb[32], 4, 1); wg_wait<1>(); wfree(33);
        fetch(0);
        stage(35, hx, 3, 1); wg_wait<1>(); wfree(34);
        fetch(1);
        stage(36, &hb[0], 4, 1); wg_wait<1>(); wfree(35);
        stage(37, &hb[16], 4, 1); wg_wait<1>(); wfree(36);
        wg_wait<0>();
        reg_fence(P0);
        pack_part<64>(pk, P0, ep);
        uint32_t all = 0;
#pragma unroll
        for (int i = 0; i < 32; i++) all |= pk[i];
        if (lane == 0) mbar_arrive_after(wempty + (37 & 7) * 8, all, 0, nil);
        TR(leader, 65 + 10 * uw)
    }
    {
        uint4* const dst = g_part + (size_t)(tile * 8 + j) * 5120 + wt;
        const uint4* const src = g_part + (size_t)tile * 40960 + j * 512 + wt;
        float F[2][32];
        uint4 gb[4];
        float rr[2];
        float2 gf[8];
        uint4 base[4], u1[4], u2[4], u3[4];
#pragma unroll
        for (int c = 2; c < 5; c++) {
            float (&P)[32] = F[c & 1];
            fresh();
#pragma unroll
            for (int s = 0; s < 27; s++) {
                const int e = s < 8 ? 0 : s < 15 ? 1 : s < 23 ? 2 : 3, o = s - (e == 0 ? 0 : e == 1 ? 8 : e == 2 ? 15 : 23), n = 30 + 4 * c + e;
                const uint32_t* a = s < 12 ? &ha[4 * s] : s < 15 ? &hx[4 * (s - 12)] : &hb[4 * (s - 15)];
                if (o == 0) wwait(n);
                if (o == 0 || s == 1) wg_fence();
                wgmma_rs64(P, a[0], a[1], a[2], a[3], wdesc(n) + o * 128, s);
                if (o == 0) { wg_commit(); wg_wait<1>(); if (c > 2 || s) wfree(n - 1); }
                if (s == 0 && c > 2) { reg_fence(F[~c & 1]); pack_part<32>(pk, F[~c & 1], ep); }
                if (c == 2 && s % 3 == 0 && s < 24) st_part(dst + g4_block(s / 12, j) * 512 + (s / 3 & 3) * 128, &pk[4 * (s / 3)]);
                if (c == 3 && s % 4 == 1 && s < 16) st_part(dst + g4_block(2, j) * 512 + s / 4 * 128, &pk[4 * (s / 4)]);
                if (c == 4 && s < 4) st_part(dst + g4_block(3, j) * 512 + s * 128, &pk[4 * s]);
                if (c == 4 && s >= 4 && s < 8) base[s - 4] = ldcg128(&g_x1f[(tile * 8 + j) * 640 + (s - 4) * 128 + wt]);
                if (c == 4 && s >= 15 && s < 19) { const int i = s - 15; gf[2 * i] = lds64f(sb + M_GB + (16 * i + 2 * t) * 4); gf[2 * i + 1] = lds64f(sb + M_GB + (16 * i + 8 + 2 * t) * 4); }
                if (c == 4 && s >= 12 && s < 14) rr[s - 12] = __uint_as_float(lds32(sb + M_F1 + (64 * uw + 16 * wq + g + 8 * (s - 12)) * 4));
                if (c == 4 && s >= 8 && s < 12) u1[s - 8] = ld_part(src + (j ^ 6) * 5120 + (s - 8) * 128);
                if (c == 4 && s >= 19 && s < 23) u2[s - 19] = ld_part(src + (j ^ 4) * 5120 + (s - 19) * 128);
                if (c == 4 && s >= 23) u3[s - 23] = ld_part(src + (j ^ 2) * 5120 + (s - 23) * 128);
                if (27 * (c - 2) + s == R_GATE && lane == 0) mbar_arrive(bars + (B_RING + uw) * 8);
                if (s == 7 || s == 14 || s == 22 || s == 26) wg_commit();
                if (c == 4) { TR(leader && s == 7, 68 + 10 * uw) TR(leader && s == 14, 69 + 10 * uw) TR(leader && s == 22, 70 + 10 * uw) }
            }
            TR(leader, 64 + c + (c == 4 ? 3 : 0) + 10 * uw)
        }
        float (&O)[32] = F[0];
#pragma unroll
        for (int i = 0; i < 4; i++) gb[i] = scale16(gf[2 * i], gf[2 * i + 1], rr[0], rr[1]);
        uint32_t it = 0;
        while (__any_sync(~0u, (stale4(u1, ep) | stale4(u2, ep) | stale4(u3, ep)) & 1)) {
            STALE(__any_sync(~0u, stale4(u1, ep) & 1) ? 4 : __any_sync(~0u, stale4(u2, ep) & 1) ? 5 : 6)
            ld_part4(u1, src + (j ^ 6) * 5120, 128); ld_part4(u2, src + (j ^ 4) * 5120, 128); ld_part4(u3, src + (j ^ 2) * 5120, 128);
            SPIN_CHECK(58)
        }
        TR(leader, 73 + 10 * uw)
#pragma unroll
        for (int i = 0; i < 4; i++) u1[i] = add2(add2(u1[i], u2[i]), u3[i]);
        TS(leader, 50 + uw)
        wg_wait<0>();
        reg_fence(O);
        TS(leader, 48 + uw)
        const uint32_t so = sb + recv_off(uw) + wq * 2048;
#pragma unroll
        for (int i = 0; i < 4; i++) {
            const float* o = &O[8 * i];
            const uint4 r = fin16(add2(u1[i], make_uint4(pack2(o[0], o[1]), pack2(o[2], o[3]), pack2(o[4], o[5]), pack2(o[6], o[7]))), base[i], gb[i]);
            stsm4(so + (lane & 15) * 128 + (((2 * i + (lane >> 4)) ^ (lane & 7)) << 4), r.x, r.y, r.z, r.w);
        }
        TR4(leader, 100 + uw)
        __syncwarp();
#pragma unroll
        for (int i = 0; i < 4; i++) {
            const int row = (lane >> 3) + 4 * i;
            stg128(out + (size_t)(row0 + row) * D_ + 64 * j + 8 * (lane & 7), lds128(so + row * 128 + (((lane & 7) ^ (row & 7)) << 4)));
        }
        TS(leader, 24 + uw)
        warp_arrive(bars + B_OWN * 8);
    }
}

typedef CUresult (*EncFn)(CUtensorMap*, CUtensorMapDataType, cuuint32_t, void*, const cuuint64_t*, const cuuint64_t*, const cuuint32_t*,
                          const cuuint32_t*, CUtensorMapInterleave, CUtensorMapSwizzle, CUtensorMapL2promotion, CUtensorMapFloatOOBfill);

static void enc(EncFn fn, CUtensorMap* m, void* p, int rank, const cuuint64_t* dims, const cuuint64_t* strides, const cuuint32_t* box, bool plain = false) {
    const CUtensorMapSwizzle sw = box[0] > 64 || plain ? CU_TENSOR_MAP_SWIZZLE_NONE : CU_TENSOR_MAP_SWIZZLE_128B;
    cuuint32_t es[5] = {1, 1, 1, 1, 1};
    CUresult r = fn(m, CU_TENSOR_MAP_DATA_TYPE_BFLOAT16, rank, p, dims, strides, box, es, CU_TENSOR_MAP_INTERLEAVE_NONE, sw,
                    CU_TENSOR_MAP_L2_PROMOTION_L2_128B, CU_TENSOR_MAP_FLOAT_OOB_FILL_NONE);
    (void)r;
}
static void enc2(EncFn fn, CUtensorMap* m, void* p, uint64_t cols, uint64_t rows, uint32_t bc, uint32_t br, bool plain = false) {
    cuuint64_t dims[2] = {cols, rows}, st[1] = {cols * 2};
    cuuint32_t box[2] = {bc, br};
    enc(fn, m, p, 2, dims, st, box, plain);
}

extern "C" void kernel_launch(void* const* d_in, const int* in_sizes, int n_in, void* d_out, int out_size) {
    static Maps mp;
    static Ptrs pp;
    static void* cached[13];
    bool same = true;
    for (int i = 0; i < 13; i++) same = same && (cached[i] == d_in[i]);
    if (!same) {
        void* fnp = nullptr;
        cudaDriverEntryPointQueryResult qr;
        cudaGetDriverEntryPoint("cuTensorMapEncodeTiled", &fnp, cudaEnableDefault, &qr);
        EncFn fn = (EncFn)fnp;
        cudaGetSymbolAddress((void**)&pp.s, g_scratch);
        void *x1T = g_x1T, *t = g_t;
        cuuint64_t dq[3] = {64, S_, 10}, sq[2] = {D_ * 2, 128};
        cuuint32_t bq[3] = {64, 16, 10};
        enc(fn, &mp.q, d_in[0], 3, dq, sq, bq);
        enc2(fn, &mp.k, d_in[1], D_, S_, 80, 67); enc2(fn, &mp.v, d_in[2], D_, S_, 80, 64);
        enc2(fn, &mp.qT, g_qT, 16 * D_, 128, 80, 128);
        enc2(fn, &mp.x[0], x1T, S_, D_, 64, 64); enc2(fn, &mp.x[1], (bf16*)t + 2 * D_, D_, S_, 64, 64);
        enc2(fn, &mp.x[2], g_x2f, 64, 320 * 64, 64, 64, true);
        enc2(fn, &mp.w1, d_in[7], D_, D_, 64, 64); enc2(fn, &mp.w1h, d_in[7], D_, D_, 64, 160); enc2(fn, &mp.w3h, d_in[9], F_, D_, 64, 160);
        enc2(fn, &mp.wmod, d_in[12], 6 * D_, D_, 64, 160);
        const cuuint64_t R = D_ * 2;
        cuuint64_t da[5] = {D_, 2, 4, 4, 16}, sa[4] = {R, 8 * R, 2 * R, 32 * R}, db[5] = {D_, 2, 2, 4, 8}, sb[4] = {R, 8 * R, 2 * R, 16 * R};
        cuuint32_t ba[5] = {64, 2, 4, 4, 2}, bb[5] = {64, 2, 2, 4, 4};
        enc(fn, &mp.w2a, d_in[8], 5, da, sa, ba); enc(fn, &mp.w2b, (bf16*)d_in[8] + 512 * D_, 5, db, sb, bb);
        cuuint64_t dw[3] = {64, D_, 27}, sw[2] = {F_ * 2, 128};
        cuuint32_t bw[3] = {64, 32, 3};
        enc(fn, &mp.w3a, d_in[9], 3, dw, sw, bw);
        enc2(fn, &mp.w3b, d_in[9], F_, D_, 24, 32);
        enc2(fn, &mp.w4[0], d_in[10], D_, F_, 64, 64); enc2(fn, &mp.w4[1], d_in[10], D_, F_, 64, 48);
        pp.q = (const bf16*)d_in[0]; pp.w_mod = (const bf16*)d_in[12]; pp.shift_k = (const bf16*)d_in[3];
        pp.ssm_k = (const bf16*)d_in[4]; pp.ssm_D = (const bf16*)d_in[5]; pp.w1 = (const bf16*)d_in[7]; pp.w2 = (const bf16*)d_in[8];
        pp.w4 = (const bf16*)d_in[10]; pp.c = (const bf16*)d_in[11];
        cudaFuncSetAttribute(fused_kernel, cudaFuncAttributeMaxDynamicSharedMemorySize, SMEM_BYTES);
        for (int i = 0; i < 13; i++) cached[i] = d_in[i];
    }
    fused_kernel<<<NCTA, NTHR, SMEM_BYTES, cudaStreamPerThread>>>(pp, (bf16*)d_out, mp);
}
```
